```python
import torch

def _softmax(x, axis=-1):
    return torch.softmax(x, dim=axis)

def _gelu(x):
    return torch.nn.functional.gelu(x, approximate='tanh')

def _silu(x):
    return torch.nn.functional.silu(x)

def _sigmoid(x):
    return torch.sigmoid(x)

def _layernorm(x, axis=-1, eps=1e-05):
    m = x.mean(dim=axis, keepdim=True)
    v = x.var(dim=axis, keepdim=True, unbiased=False)
    return (x - m) / torch.sqrt(v + eps)

def _scatter_add(tgt, idx, src, axis=0):
    return tgt.clone().index_add_(axis, idx, src)

def _segment_sum(src, seg, n):
    out = torch.zeros((n,) + src.shape[1:], dtype=src.dtype)
    return out.index_add_(0, seg, src)

def _pad(x, pw):
    flat = tuple((v for pair in reversed(pw) for v in pair))
    return torch.nn.functional.pad(x, flat)
kernel_name = 'interleave_layers__memory_aug_recurrent_mem_tr__mixer_s_mlp__prompt'

def setup_inputs():

    _w = lambda a: (lambda t: t.to(torch.bfloat16) if t.is_floating_point() else t)(torch.as_tensor(a))

    def _A_setup():
        B, S, Dm = (1, 2048, 640)
        H, Dh = (32, 192)
        M, seg = (8, 32)
        seg = min(seg, S)
        S = S // seg * seg
        return {'x': _w((lambda *s: torch.randn(*s, dtype=torch.bfloat16) * 0.05)(B, S, Dm)), 'mem0': _w((lambda *s: torch.randn(*s, dtype=torch.bfloat16) * 0.8)(B, M, Dm)), 'Wq': _w((lambda *s: torch.randn(*s, dtype=torch.bfloat16) * 0.8)(Dm, H, Dh) * Dm ** (-0.5)), 'Wk': _w((lambda *s: torch.randn(*s, dtype=torch.bfloat16) * 0.8)(Dm, H, Dh) * Dm ** (-0.5)), 'Wv': _w((lambda *s: torch.randn(*s, dtype=torch.bfloat16) * 0.8)(Dm, H, Dh) * Dm ** (-0.5)), 'Wo': _w((lambda *s: torch.randn(*s, dtype=torch.bfloat16) * 0.8)(H, Dh, Dm) * (H * Dh) ** (-0.5)), 'seg_len': seg}
    _A_in = _A_setup()

    def _B_setup():
        B, S, D, F = (1, 2048, 640, 1536)
        return {'x': _w((lambda *s: torch.randn(*s, dtype=torch.bfloat16) * 0.05)(B, S, D)), 'w1': _w((lambda *s: torch.randn(*s, dtype=torch.bfloat16) * 0.8)(D, D) * D ** (-0.5)), 'w2': _w((lambda *s: torch.randn(*s, dtype=torch.bfloat16) * 0.8)(D, D) * D ** (-0.5)), 'w3': _w((lambda *s: torch.randn(*s, dtype=torch.bfloat16) * 0.8)(D, F) * D ** (-0.5)), 'w4': _w((lambda *s: torch.randn(*s, dtype=torch.bfloat16) * 0.8)(F, D) * F ** (-0.5))}
    _B_in = _B_setup()
    return {'A_x': _A_in['x'], 'A_mem0': _A_in['mem0'], 'A_Wq': _A_in['Wq'], 'A_Wk': _A_in['Wk'], 'A_Wv': _A_in['Wv'], 'A_Wo': _A_in['Wo'], 'A_seg_len': _A_in['seg_len'], 'B_x': _B_in['x'], 'B_w1': _B_in['w1'], 'B_w2': _B_in['w2'], 'B_w3': _B_in['w3'], 'B_w4': _B_in['w4']}

def reference(A_x, A_mem0, A_Wq, A_Wk, A_Wv, A_Wo, A_seg_len, B_x, B_w1, B_w2, B_w3, B_w4):

    def _A_ref(x, mem0, Wq, Wk, Wv, Wo, seg_len):
        B, S, Dm = x.shape
        H, Dh = (Wq.shape[1], Wq.shape[2])
        M = mem0.shape[1]
        scale = Dh ** (-0.5)
        n_seg = S // seg_len
        L = M + seg_len
        idx = torch.arange(L)
        mask = (idx[:, None] < M) | (idx[:, None] >= idx[None, :])
        mem = mem0
        outs = []
        for s in range(n_seg):
            xs = x[:, s * seg_len:(s + 1) * seg_len, :].clone()
            h = torch.concatenate([mem, xs], axis=1)
            q = torch.einsum('btd,dhe->bhte', h, Wq)
            k = torch.einsum('btd,dhe->bhte', h, Wk)
            v = torch.einsum('btd,dhe->bhte', h, Wv)
            scores = torch.einsum('bhqe,bhke->bhqk', q, k) * scale
            scores = torch.where(mask[None, None], scores, -1000000000.0)
            p = _softmax(scores, axis=-1)
            o = torch.einsum('bhqk,bhke->bhqe', p, v)
            o = torch.einsum('bhte,hed->btd', o, Wo)
            mem = o[:, :M, :].clone()
            outs.append(o[:, M:, :])
        return torch.concatenate(outs, axis=1)

    def _B_ref(x, w1, w2, w3, w4):
        B, S, D = x.shape
        h = _gelu(_layernorm(x, axis=-1) @ w1)
        c = D // 4
        g0 = _pad(h[:, :, 0 * c:1 * c], ((0, 0), (1, 0), (0, 0)))[:, :S, :]
        g1 = _pad(h[:, :, 1 * c:2 * c], ((0, 0), (0, 1), (0, 0)))[:, 1:, :]
        g2 = _pad(h[:, :, 2 * c:3 * c], ((0, 0), (2, 0), (0, 0)))[:, :S, :]
        g3 = _pad(h[:, :, 3 * c:], ((0, 0), (0, 2), (0, 0)))[:, 2:, :]
        hs = torch.concatenate([g0, g1, g2, g3], axis=-1) @ w2
        x1 = x + hs
        h2 = _gelu(_layernorm(x1, axis=-1) @ w3) @ w4
        return x1 + h2
    x = A_x
    x = x + _A_ref(_layernorm(x, axis=-1), A_mem0, A_Wq, A_Wk, A_Wv, A_Wo, A_seg_len)
    x = x + _B_ref(_layernorm(x, axis=-1), B_w1, B_w2, B_w3, B_w4)
    x = x + _A_ref(_layernorm(x, axis=-1), A_mem0, A_Wq, A_Wk, A_Wv, A_Wo, A_seg_len)
    x = x + _B_ref(_layernorm(x, axis=-1), B_w1, B_w2, B_w3, B_w4)
    return x
```

```cpp
#include <cuda_runtime.h>
#include <cuda_bf16.h>
#include <cuda.h>
#include <stdint.h>

#define S_LEN 2048
#define DM 640
#define NH 32
#define DH 192
#define HD 6144
#define NSEG 64
#define FF 1536

__device__ __forceinline__ uint32_t smem_u32(const void* p) { return (uint32_t)__cvta_generic_to_shared(p); }
__device__ __forceinline__ uint32_t mapa(uint32_t a, uint32_t r) {
  uint32_t o; asm volatile("mapa.shared::cluster.u32 %0, %1, %2;" : "=r"(o) : "r"(a), "r"(r)); return o; }
__device__ __forceinline__ void mbar_init(uint32_t b, uint32_t c) {
  asm volatile("mbarrier.init.shared::cta.b64 [%0], %1;" :: "r"(b), "r"(c) : "memory"); }
__device__ __forceinline__ void mbar_expect(uint32_t b, uint32_t tx) {
  asm volatile("mbarrier.arrive.expect_tx.shared::cta.b64 _, [%0], %1;" :: "r"(b), "r"(tx) : "memory"); }
__device__ __forceinline__ void mbar_arrive(uint32_t b) {
  asm volatile("mbarrier.arrive.shared::cta.b64 _, [%0];" :: "r"(b) : "memory"); }
__device__ __forceinline__ void mbar_arrive_remote(uint32_t rb) {
  asm volatile("mbarrier.arrive.relaxed.cluster.shared::cluster.b64 _, [%0];" :: "r"(rb) : "memory"); }
__device__ __forceinline__ void mbar_expect_if(bool p, uint32_t b, uint32_t tx) {
  asm volatile("{\n.reg .pred q;\nsetp.ne.u32 q, %2, 0;\n@q mbarrier.arrive.expect_tx.shared::cta.b64 _, [%0], %1;\n}" :: "r"(b), "r"(tx), "r"((uint32_t)p) : "memory"); }
__device__ __forceinline__ void mbar_arrive_if(bool p, uint32_t b) {
  asm volatile("{\n.reg .pred q;\nsetp.ne.u32 q, %1, 0;\n@q mbarrier.arrive.shared::cta.b64 _, [%0];\n}" :: "r"(b), "r"((uint32_t)p) : "memory"); }
__device__ __forceinline__ void mbar_arrive_remote_if(bool p, uint32_t rb) {
  asm volatile("{\n.reg .pred q;\nsetp.ne.u32 q, %1, 0;\n@q mbarrier.arrive.relaxed.cluster.shared::cluster.b64 _, [%0];\n}" :: "r"(rb), "r"((uint32_t)p) : "memory"); }
__device__ __forceinline__ void sts32_if(bool p, uint32_t a, uint32_t v) {
  asm volatile("{\n.reg .pred q;\nsetp.ne.u32 q, %2, 0;\n@q st.shared.b32 [%0], %1;\n}" :: "r"(a), "r"(v), "r"((uint32_t)p) : "memory"); }
__device__ __forceinline__ void sts128z_if(bool p, uint32_t a) {
  asm volatile("{\n.reg .pred q;\nsetp.ne.u32 q, %1, 0;\n@q st.shared.v4.b32 [%0], {0,0,0,0};\n}" :: "r"(a), "r"((uint32_t)p) : "memory"); }
__device__ __forceinline__ bool mbar_try(uint32_t b, uint32_t ph) {
  uint32_t ok;
  asm volatile("{\n.reg .pred p;\nmbarrier.try_wait.parity.shared::cta.b64 p, [%1], %2;\nselp.u32 %0, 1, 0, p;\n}"
               : "=r"(ok) : "r"(b), "r"(ph) : "memory");
  return ok; }
__device__ __forceinline__ bool mbar_test(uint32_t b, uint32_t ph) {
  uint32_t ok;
  asm volatile("{\n.reg .pred p;\nmbarrier.test_wait.parity.shared::cta.b64 p, [%1], %2;\nselp.u32 %0, 1, 0, p;\n}"
               : "=r"(ok) : "r"(b), "r"(ph) : "memory");
  return ok; }
#define SPIN_LIMIT 4000000
#define FAIL() asm volatile("st.global.u32 [%0], 0;" :: "l"(8ull) : "memory")
#define CFENCE() asm volatile("fence.proxy.async::generic.acquire.sync_restrict::shared::cluster.cluster;" ::: "memory")
__device__ __forceinline__ void mbar_wait(uint32_t b, uint32_t ph) {
  int n = 0;
  while (!mbar_try(b, ph)) { if (++n > SPIN_LIMIT) FAIL(); } }
#define TIMEOUT_ACT "@!p st.shared.u32 [%0+1], 0;"
#define WAIT_HINT ", 20000"
#define WAIT_LIM "200000"
__device__ __forceinline__ void mbar_slow(uint32_t b, uint32_t ph) {
  asm volatile("{\n.reg .pred p, q;\n.reg .u32 n;\nmov.u32 n, 0;\n"
               "WL:\nmbarrier.try_wait.parity.shared::cta.b64 p, [%0], %1" WAIT_HINT ";\nadd.u32 n, n, 1;\nsetp.lt.and.u32 q, n, " WAIT_LIM ", !p;\n@q bra.uni WL;\n"
               TIMEOUT_ACT "\n}" :: "r"(b), "r"(ph) : "memory"); }
__device__ __forceinline__ void mbar_waitw(uint32_t b, uint32_t ph) {
  asm volatile("{\n.reg .pred p, q;\n.reg .u32 n;\nmbarrier.try_wait.parity.shared::cta.b64 p, [%0], %1;\n@p bra.uni WD;\nmov.u32 n, 0;\n"
               "WL:\nmbarrier.try_wait.parity.shared::cta.b64 p, [%0], %1" WAIT_HINT ";\nadd.u32 n, n, 1;\nsetp.lt.and.u32 q, n, " WAIT_LIM ", !p;\n@q bra.uni WL;\n"
               TIMEOUT_ACT "\nWD:\n}" :: "r"(b), "r"(ph) : "memory"); }
__device__ __forceinline__ void mbar_waitw2(uint32_t b0, uint32_t b1, uint32_t ph) {
  uint32_t ok;
  asm volatile("{\n.reg .pred p, r;\nmbarrier.try_wait.parity.shared::cta.b64 p, [%1], %3;\nmbarrier.try_wait.parity.shared::cta.b64 r, [%2], %3;\n"
               "and.pred p, p, r;\nselp.u32 %0, 1, 0, p;\n}" : "=r"(ok) : "r"(b0), "r"(b1), "r"(ph) : "memory");
  if (__builtin_expect(!__all_sync(~0u, ok), 0)) { mbar_slow(b0, ph); mbar_slow(b1, ph); }
}
__device__ __forceinline__ void mbar_waitu(uint32_t b, uint32_t ph) {
  asm volatile("{\n.reg .pred p;\nmbarrier.try_wait.parity.shared::cta.b64 p, [%0], %1;\n@p bra.uni WD;\n"
               "WL:\nmbarrier.try_wait.parity.shared::cta.b64 p, [%0], %1" WAIT_HINT ";\n@!p bra.uni WL;\nWD:\n}" :: "r"(b), "r"(ph) : "memory"); }
__device__ __forceinline__ void mbar_waitu2(uint32_t b0, uint32_t b1, uint32_t ph) {
  asm volatile("{\n.reg .pred p, r;\nWL:\nmbarrier.try_wait.parity.shared::cta.b64 p, [%0], %2;\nmbarrier.try_wait.parity.shared::cta.b64 r, [%1], %2;\n"
               "and.pred p, p, r;\n@!p bra.uni WL;\n}" :: "r"(b0), "r"(b1), "r"(ph) : "memory"); }
__device__ __forceinline__ void mbar_waitw4(uint32_t b, uint32_t ph) { mbar_waitw2(b, b + 8, ph); mbar_waitw2(b + 16, b + 24, ph); }
__device__ __forceinline__ uint32_t clock32() { uint32_t t; asm volatile("mov.u32 %0, %%clock;" : "=r"(t) :: "memory"); return t; }
template <int L> __device__ __forceinline__ uint32_t lop3(uint32_t a, uint32_t b, uint32_t c) {
  uint32_t r; asm("lop3.b32 %0, %1, %2, %3, %4;" : "=r"(r) : "r"(a), "r"(b), "r"(c), "n"(L)); return r; }
__device__ __forceinline__ void st_async_v2_if(bool p, uint32_t a, uint32_t v0, uint32_t v1, uint32_t mb) {
  asm volatile("{\n.reg .pred q;\nsetp.ne.u32 q, %4, 0;\n@q st.async.weak.shared::cluster.mbarrier::complete_tx::bytes.v2.b32 [%0], {%1,%2}, [%3];\n}"
               :: "r"(a), "r"(v0), "r"(v1), "r"(mb), "r"((uint32_t)p) : "memory"); }
__device__ __forceinline__ void keep4(const uint32_t* r, int lane) {
  asm volatile("{\n.reg .pred q;\nsetp.lt.s32 q, %4, 0;\n@q st.shared.v4.b32 [%4], {%0,%1,%2,%3};\n}" :: "r"(r[0]), "r"(r[1]), "r"(r[2]), "r"(r[3]), "r"(lane) : "memory"); }
__device__ __forceinline__ uint32_t uni(uint32_t x) { return __shfl_sync(~0u, x, 0); }
__device__ __forceinline__ void bulk_g2s_mc_e(uint32_t dst, const void* src, uint32_t bytes, uint32_t mb, uint16_t mask) {
  asm volatile("{\n.reg .pred e;\nelect.sync _|e, 0xffffffff;\n"
               "@e cp.async.bulk.shared::cluster.global.mbarrier::complete_tx::bytes.multicast::cluster [%0], [%1], %2, [%3], %4;\n}"
               :: "r"(dst), "l"(src), "r"(bytes), "r"(mb), "h"(mask) : "memory"); }
__device__ __forceinline__ void bulk_s2g_e(void* dst, uint32_t src, uint32_t bytes) {
  asm volatile("{\n.reg .pred e;\nelect.sync _|e, 0xffffffff;\n@e cp.async.bulk.global.shared::cta.bulk_group [%0], [%1], %2;\n}"
               :: "l"(dst), "r"(src), "r"(bytes) : "memory"); }
__device__ __forceinline__ void bulk_g2s_e(uint32_t dst, const void* src, uint32_t bytes, uint32_t mb) {
  asm volatile("{\n.reg .pred e;\nelect.sync _|e, 0xffffffff;\n@e cp.async.bulk.shared::cluster.global.mbarrier::complete_tx::bytes [%0], [%1], %2, [%3];\n}"
               :: "r"(dst), "l"(src), "r"(bytes), "r"(mb) : "memory"); }
#define STREAM_HINT 1
__device__ __forceinline__ void bulk_s2g_es(void* dst, uint32_t src, uint32_t bytes) {
  asm volatile("{\n.reg .pred e;\n.reg .b64 pol;\ncreatepolicy.fractional.L2::evict_first.b64 pol;\nelect.sync _|e, 0xffffffff;\n"
               "@e cp.async.bulk.global.shared::cta.bulk_group.L2::cache_hint [%0], [%1], %2, pol;\n}" :: "l"(dst), "r"(src), "r"(bytes) : "memory");
}
__device__ __forceinline__ void bulk_g2s_es(uint32_t dst, const void* src, uint32_t bytes, uint32_t mb) {
  asm volatile("{\n.reg .pred e;\n.reg .b64 pol;\ncreatepolicy.fractional.L2::evict_first.b64 pol;\nelect.sync _|e, 0xffffffff;\n"
               "@e cp.async.bulk.shared::cluster.global.mbarrier::complete_tx::bytes.L2::cache_hint [%0], [%1], %2, [%3], pol;\n}"
               :: "r"(dst), "l"(src), "r"(bytes), "r"(mb) : "memory"); }
__device__ __forceinline__ void tma2d_e(uint32_t dst, const CUtensorMap* tm, int c0, int c1, uint32_t mb) {
  asm volatile("{\n.reg .pred e;\nelect.sync _|e, 0xffffffff;\n"
               "@e cp.async.bulk.tensor.2d.shared::cluster.global.mbarrier::complete_tx::bytes [%0], [%1, {%3, %4}], [%2];\n}"
               :: "r"(dst), "l"((uint64_t)tm), "r"(mb), "r"(c0), "r"(c1) : "memory"); }
__device__ __forceinline__ uint32_t hadd2bf(uint32_t a, uint32_t b) {
  uint32_t r; asm("add.rn.bf16x2 %0, %1, %2;" : "=r"(r) : "r"(a), "r"(b)); return r; }
__device__ __forceinline__ void cluster_sync_all() {
  asm volatile("barrier.cluster.arrive.release.aligned;\nbarrier.cluster.wait.acquire.aligned;" ::: "memory"); }
__device__ __forceinline__ void bar_arrive(int id, int n) { asm volatile("bar.arrive %0, %1;" :: "r"(id), "r"(n) : "memory"); }
__device__ __forceinline__ void bar_arrive_dep(int id, int n, uint32_t dep) {
  asm volatile("{\n.reg .u32 t;\nand.b32 t, %2, 0;\nadd.u32 t, t, %0;\nbar.sync t, %1;\n}" :: "r"(id), "r"(n), "r"(dep) : "memory"); }
__device__ __forceinline__ void bar_sync(int id, int n) { asm volatile("bar.sync %0, %1;" :: "r"(id), "r"(n) : "memory"); }
__device__ __forceinline__ void fence_async() { asm volatile("fence.proxy.async.shared::cta;" ::: "memory"); }
__device__ __forceinline__ void st_async_b32(uint32_t a, uint32_t v, uint32_t mb) {
  asm volatile("st.async.weak.shared::cluster.mbarrier::complete_tx::bytes.b32 [%0], %1, [%2];" :: "r"(a), "r"(v), "r"(mb) : "memory"); }
__device__ __forceinline__ void st_async_v2(uint32_t a, uint32_t v0, uint32_t v1, uint32_t mb) {
  asm volatile("st.async.weak.shared::cluster.mbarrier::complete_tx::bytes.v2.b32 [%0], {%1,%2}, [%3];" :: "r"(a), "r"(v0), "r"(v1), "r"(mb) : "memory"); }
__device__ __forceinline__ void st_async_v4(uint32_t a, uint32_t v0, uint32_t v1, uint32_t v2, uint32_t v3, uint32_t mb) {
  asm volatile("st.async.weak.shared::cluster.mbarrier::complete_tx::bytes.v4.b32 [%0], {%1,%2,%3,%4}, [%5];" :: "r"(a), "r"(v0), "r"(v1), "r"(v2), "r"(v3), "r"(mb) : "memory"); }
__device__ __forceinline__ void ldsm4(uint32_t& r0, uint32_t& r1, uint32_t& r2, uint32_t& r3, uint32_t a) {
  asm volatile("ldmatrix.sync.aligned.m8n8.x4.shared.b16 {%0,%1,%2,%3}, [%4];" : "=r"(r0), "=r"(r1), "=r"(r2), "=r"(r3) : "r"(a) : "memory"); }
__device__ __forceinline__ void ldsm4t(uint32_t& r0, uint32_t& r1, uint32_t& r2, uint32_t& r3, uint32_t a) {
  asm volatile("ldmatrix.sync.aligned.m8n8.x4.trans.shared.b16 {%0,%1,%2,%3}, [%4];" : "=r"(r0), "=r"(r1), "=r"(r2), "=r"(r3) : "r"(a) : "memory"); }
__device__ __forceinline__ void stsm2t(uint32_t a, uint32_t r0, uint32_t r1) {
  asm volatile("stmatrix.sync.aligned.m8n8.x2.trans.shared.b16 [%0], {%1,%2};" :: "r"(a), "r"(r0), "r"(r1) : "memory"); }
__device__ __forceinline__ void stsm4t(uint32_t a, uint32_t r0, uint32_t r1, uint32_t r2, uint32_t r3) {
  asm volatile("stmatrix.sync.aligned.m8n8.x4.trans.shared.b16 [%0], {%1,%2,%3,%4};" :: "r"(a), "r"(r0), "r"(r1), "r"(r2), "r"(r3) : "memory"); }
__device__ __forceinline__ uint32_t movm(uint32_t a) {
  uint32_t d; asm volatile("movmatrix.sync.aligned.m8n8.trans.b16 %0, %1;" : "=r"(d) : "r"(a)); return d; }
__device__ __forceinline__ void mma16816(float* d, uint32_t a0, uint32_t a1, uint32_t a2, uint32_t a3, uint32_t b0, uint32_t b1) {
  asm("mma.sync.aligned.m16n8k16.row.col.f32.bf16.bf16.f32 {%0,%1,%2,%3}, {%4,%5,%6,%7}, {%8,%9}, {%0,%1,%2,%3};"
               : "+f"(d[0]), "+f"(d[1]), "+f"(d[2]), "+f"(d[3]) : "r"(a0), "r"(a1), "r"(a2), "r"(a3), "r"(b0), "r"(b1)); }
__device__ __forceinline__ void mma16816v(float* d, uint32_t a0, uint32_t a1, uint32_t a2, uint32_t a3, uint32_t b0, uint32_t b1) {
  asm volatile("mma.sync.aligned.m16n8k16.row.col.f32.bf16.bf16.f32 {%0,%1,%2,%3}, {%4,%5,%6,%7}, {%8,%9}, {%0,%1,%2,%3};"
               : "+f"(d[0]), "+f"(d[1]), "+f"(d[2]), "+f"(d[3]) : "r"(a0), "r"(a1), "r"(a2), "r"(a3), "r"(b0), "r"(b1)); }
__device__ __forceinline__ uint32_t pack2(float lo, float hi) {
  uint32_t r; asm("cvt.rn.bf16x2.f32 %0, %1, %2;" : "=r"(r) : "f"(hi), "f"(lo)); return r; }
__device__ __forceinline__ uint32_t pack2v(float lo, float hi) {
  uint32_t r; asm volatile("cvt.rn.bf16x2.f32 %0, %1, %2;" : "=r"(r) : "f"(hi), "f"(lo)); return r; }
__device__ __forceinline__ float bf_lo(uint32_t w) { return __uint_as_float(w << 16); }
__device__ __forceinline__ float bf_hi(uint32_t w) { return __uint_as_float(w & 0xffff0000u); }
__device__ __forceinline__ uint4 lds128(uint32_t a) {
  uint4 v; asm volatile("ld.shared.v4.b32 {%0,%1,%2,%3}, [%4];" : "=r"(v.x), "=r"(v.y), "=r"(v.z), "=r"(v.w) : "r"(a) : "memory"); return v; }
__device__ __forceinline__ uint4 lds128_nv(uint32_t a) {
  uint4 v; asm volatile("ld.shared.v4.b32 {%0,%1,%2,%3}, [%4];" : "=r"(v.x), "=r"(v.y), "=r"(v.z), "=r"(v.w) : "r"(a)); return v; }
__device__ __forceinline__ void st_async_v2_nm(uint32_t a, uint32_t v0, uint32_t v1, uint32_t mb) {
  asm volatile("st.async.weak.shared::cluster.mbarrier::complete_tx::bytes.v2.b32 [%0], {%1,%2}, [%3];" :: "r"(a), "r"(v0), "r"(v1), "r"(mb)); }
__device__ __forceinline__ float rcpf(float x) { float y; asm("rcp.approx.ftz.f32 %0, %1;" : "=f"(y) : "f"(x)); return y; }
__device__ __forceinline__ void sts64(uint32_t a, uint32_t x, uint32_t y) { asm volatile("st.shared.v2.b32 [%0], {%1,%2};" :: "r"(a), "r"(x), "r"(y) : "memory"); }
__device__ __forceinline__ float ex2(float x) { float y; asm("ex2.approx.ftz.f32 %0, %1;" : "=f"(y) : "f"(x)); return y; }
__device__ __forceinline__ uint32_t lds32(uint32_t a) {
  uint32_t v; asm volatile("ld.shared.b32 %0, [%1];" : "=r"(v) : "r"(a) : "memory"); return v; }
__device__ __forceinline__ uint2 lds64(uint32_t a) {
  uint2 v; asm volatile("ld.shared.v2.b32 {%0,%1}, [%2];" : "=r"(v.x), "=r"(v.y) : "r"(a) : "memory"); return v; }
__device__ __forceinline__ void sts128(uint32_t a, uint32_t x, uint32_t y, uint32_t z, uint32_t w) {
  asm volatile("st.shared.v4.b32 [%0], {%1,%2,%3,%4};" :: "r"(a), "r"(x), "r"(y), "r"(z), "r"(w) : "memory"); }
__device__ __forceinline__ void sts32(uint32_t a, uint32_t x) { asm volatile("st.shared.b32 [%0], %1;" :: "r"(a), "r"(x) : "memory"); }
__device__ __forceinline__ void tma2d(uint32_t dst, const CUtensorMap* tm, int c0, int c1, uint32_t mb) {
  asm volatile("cp.async.bulk.tensor.2d.shared::cluster.global.mbarrier::complete_tx::bytes [%0], [%1, {%3, %4}], [%2];"
               :: "r"(dst), "l"((uint64_t)tm), "r"(mb), "r"(c0), "r"(c1) : "memory"); }
__device__ __forceinline__ void tma2d_prefetch(const CUtensorMap* tm, int c0, int c1) {
  asm volatile("cp.async.bulk.prefetch.tensor.2d.L2.global.tile [%0, {%1, %2}];" :: "l"((uint64_t)tm), "r"(c0), "r"(c1) : "memory"); }
__device__ __forceinline__ void bulk_g2s_mc(uint32_t dst, const void* src, uint32_t bytes, uint32_t mb, uint16_t mask) {
  asm volatile("cp.async.bulk.shared::cluster.global.mbarrier::complete_tx::bytes.multicast::cluster [%0], [%1], %2, [%3], %4;"
               :: "r"(dst), "l"(src), "r"(bytes), "r"(mb), "h"(mask) : "memory"); }
__device__ __forceinline__ void bulk_s2g(void* dst, uint32_t src, uint32_t bytes) {
  asm volatile("cp.async.bulk.global.shared::cta.bulk_group [%0], [%1], %2;" :: "l"(dst), "r"(src), "r"(bytes) : "memory"); }
__device__ __forceinline__ void wg_fence() { asm volatile("wgmma.fence.sync.aligned;" ::: "memory"); }
__device__ __forceinline__ void wg_commit() { asm volatile("wgmma.commit_group.sync.aligned;" ::: "memory"); }
template <int N> __device__ __forceinline__ void wg_wait() { asm volatile("wgmma.wait_group.sync.aligned %0;" :: "n"(N) : "memory"); }
__device__ __forceinline__ uint64_t mkdesc(uint32_t addr, uint32_t lbo, uint32_t sbo, uint32_t swz) {
  return (uint64_t)((addr & 0x3FFFF) >> 4) | ((uint64_t)(lbo >> 4) << 16) | ((uint64_t)(sbo >> 4) << 32) | ((uint64_t)swz << 62); }

#define ACC4(d) "+f"(d[0]),"+f"(d[1]),"+f"(d[2]),"+f"(d[3])
#define ACC8(d) ACC4(d), ACC4((d + 4))
#define ACC16(d) ACC8(d), ACC8((d + 8))
#define ACC20(d) ACC16(d), ACC4((d + 16))
#define ACC24(d) ACC16(d), ACC8((d + 16))
#define SMEM0 0x400
__host__ __device__ constexpr uint32_t dlo(uint32_t off, uint32_t lbo) { return ((SMEM0 + off) >> 4) | ((lbo >> 4) << 16); }
__host__ __device__ constexpr uint32_t dhi(uint32_t sbo, uint32_t swz) { return (sbo >> 4) | (swz << 30); }
#define R4S "{%0,%1,%2,%3}"
#define R8S "{%0,%1,%2,%3,%4,%5,%6,%7}"
#define R16S "{%0,%1,%2,%3,%4,%5,%6,%7,%8,%9,%10,%11,%12,%13,%14,%15}"
#define R20S "{%0,%1,%2,%3,%4,%5,%6,%7,%8,%9,%10,%11,%12,%13,%14,%15,%16,%17,%18,%19}"
#define R24S "{%0,%1,%2,%3,%4,%5,%6,%7,%8,%9,%10,%11,%12,%13,%14,%15,%16,%17,%18,%19,%20,%21,%22,%23}"
template <int N> struct MM;
#define DEF_MM(N, ACCM, RS_, I0, I1, I2, I3, I4, I5, I6, I7)                                                                      \
  template <> struct MM<N> {                                                                                                      \
    template <uint32_t BLO, uint32_t BHI, int ACC>                                                                                \
    static __device__ __forceinline__ void rs(float* d, uint32_t a0, uint32_t a1, uint32_t a2, uint32_t a3) {                     \
      asm volatile("{\n.reg .b64 b;\nmov.b64 b, {%" #I4 ", %" #I5 "};\n"                                                          \
                   "wgmma.mma_async.sync.aligned.m64n" #N "k16.f32.bf16.bf16 " RS_ ", {%" #I0 ",%" #I1 ",%" #I2 ",%" #I3 "}, b, %" #I6 ", 1, 1, 0;\n}" \
                   : ACCM(d) : "r"(a0), "r"(a1), "r"(a2), "r"(a3), "n"(BLO), "n"(BHI), "n"(ACC)); }                               \
    template <uint32_t ALO, uint32_t AHI, uint32_t BLO, uint32_t BHI, int ACC, int TA>                                            \
    static __device__ __forceinline__ void ss(float* d, uint32_t abase) {                                                         \
      asm volatile("{\n.reg .b64 a, b;\n.reg .b32 l;\nadd.u32 l, %" #I0 ", %" #I1 ";\nmov.b64 a, {l, %" #I2 "};\nmov.b64 b, {%" #I3 ", %" #I4 "};\n" \
                   "wgmma.mma_async.sync.aligned.m64n" #N "k16.f32.bf16.bf16 " RS_ ", a, b, %" #I5 ", 1, 1, %" #I6 ", 0;\n}"     \
                   : ACCM(d) : "r"(abase), "n"(ALO), "n"(AHI), "n"(BLO), "n"(BHI), "n"(ACC), "n"(TA)); }                          \
    template <int ACC>                                                                                                            \
    static __device__ __forceinline__ void rsd(float* d, uint32_t a0, uint32_t a1, uint32_t a2, uint32_t a3, uint64_t b) {        \
      asm volatile("wgmma.mma_async.sync.aligned.m64n" #N "k16.f32.bf16.bf16 " RS_ ", {%" #I0 ",%" #I1 ",%" #I2 ",%" #I3 "}, %" #I4 ", %" #I5 ", 1, 1, 0;" \
                   : ACCM(d) : "r"(a0), "r"(a1), "r"(a2), "r"(a3), "l"(b), "n"(ACC)); }                                           \
    template <int ACC>                                                                                                            \
    static __device__ __forceinline__ void ssd(float* d, uint64_t a, uint64_t b) {                                                \
      asm volatile("wgmma.mma_async.sync.aligned.m64n" #N "k16.f32.bf16.bf16 " RS_ ", %" #I0 ", %" #I1 ", %" #I2 ", 1, 1, 1, 0;"  \
                   : ACCM(d) : "l"(a), "l"(b), "n"(ACC)); }                                                                       \
    template <uint32_t ALO, uint32_t AHI, uint32_t BLO, uint32_t BHI, int ACC>                                                    \
    static __device__ __forceinline__ void ss2(float* d, uint32_t abase, uint32_t bbase) {                                        \
      asm volatile("{\n.reg .b64 a, b;\n.reg .b32 l, m;\nadd.u32 l, %" #I0 ", %" #I1 ";\nmov.b64 a, {l, %" #I2 "};\n"            \
                   "add.u32 m, %" #I6 ", %" #I3 ";\nmov.b64 b, {m, %" #I4 "};\n"                                                   \
                   "wgmma.mma_async.sync.aligned.m64n" #N "k16.f32.bf16.bf16 " RS_ ", a, b, %" #I5 ", 1, 1, 0, 0;\n}"            \
                   : ACCM(d) : "r"(abase), "n"(ALO), "n"(AHI), "n"(BLO), "n"(BHI), "n"(ACC), "r"(bbase)); }                                    \
  };
DEF_MM(8, ACC4, R4S, 4, 5, 6, 7, 8, 9, 10, 11)
DEF_MM(16, ACC8, R8S, 8, 9, 10, 11, 12, 13, 14, 15)
DEF_MM(32, ACC16, R16S, 16, 17, 18, 19, 20, 21, 22, 23)
DEF_MM(40, ACC20, R20S, 20, 21, 22, 23, 24, 25, 26, 27)
DEF_MM(48, ACC24, R24S, 24, 25, 26, 27, 28, 29, 30, 31)

#define LAG 10
#define NSTEP (NSEG + LAG)
#define NR (NSTEP + 1)
__device__ __align__(1024) __nv_bfloat16 g_xn[2][S_LEN * DM];
__device__ __align__(1024) unsigned char g_o[NSTEP * 96 * 8192];
__device__ __align__(1024) uint32_t g_part[6][7][40][64];
#define RD 16
#define TILE_B 81920
__device__ __align__(1024) float4 g_stat[S_LEN];
__device__ __align__(1024) unsigned char g_acc[6][RD][TILE_B];
#define NOP 19
#define NW12 5
#define NW34 12
#define NBC (NOP + NW12 + NW34)
__device__ __align__(1024) unsigned char g_wt[NOP * 10 * 12288];
enum { F_O = 0, F_R1 = NOP + 1, F_R2 = F_R1 + 4, F_R3 = F_R2 + 4, F_Z = F_R3 + 4, F_Z1, F_DONE, F_MISC, F_NUM };
__device__ __align__(128) uint32_t g_f[F_NUM][96];
__device__ __align__(128) int g_xready[128][8];
__device__ uint32_t g_tpc[128];
#define TS(i)
#define TSV(i, v)
#define TSN(i)
#define TSD(i, dep)
#define BTS(k, i)
#define BTS2(k, i)
#define RTS(i)
#define RTSD(i, dep)
#define RTS_OUT()
#define CTS(i)
#define PTS(i)
#define PTS1(i)
#define CTS_OUT()
#define GTS(i)

#define CL_SIZE 15
#define NCL 7
#define SSQ 13
#define SSV 16
#define OFF_WS 0
#define OFF_WO ((2 * SSQ + SSV) * 2048)
#define OFF_QK (OFF_WO + 26 * 2048)
#define OFF_PL (OFF_QK + 20480)
#define PL_SZ 5376
#define OFF_O (OFF_PL + 4352)
#define OFF_TILE (OFF_PL + 2 * PL_SZ)
#define TILE_SBO 2560
#define TILE_GRP 15360
#define LAND(k) (((k) >> 1) * TILE_GRP + ((k) & 1) * 1280)
#define LAND_F (5 * TILE_SBO)
#define OFF_XL (OFF_TILE + 3 * TILE_GRP)
#define OFF_XF (OFF_XL + LAND_F)
#define OFF_WT (OFF_XL + TILE_SBO)
#define OFF_BAR (OFF_TILE + 4 * TILE_GRP)
#define OFF_TAB (OFF_BAR + 240)
#define OFF_INV (OFF_TAB + 64)
#define OFF_TS (OFF_INV + 128)
#define A_SMEM 232448
static_assert(OFF_BAR + 512 == A_SMEM && OFF_WT % 1024 == 0, "smem map");
enum { B_W0 = 0, B_W1, B_F1, B_F2 = B_F1 + 4, B_R1 = B_F2 + 4, B_R2, B_MEMFREE, B_LANDFREE, B_OPEER, B_PLFREE, B_XFREE, B_SB, B_WOF = B_SB + 6, B_WTF, B_RS, B_NUM = B_RS + 4 };
static_assert(B_NUM <= 30, "barriers");
enum { N_C = 0, N_SISS, N_QK, N_V, N_PM, N_TURN, N_PI, N_VGO, N_O, N_PX, N_AB, N_SDONE, N_VDONE, N_G3, N_P, N_OX };

__device__ __forceinline__ bool is_dual(int j) { return j >= LAG && j < NSEG; }
__device__ __forceinline__ int sched_l(int j) { return j < NSEG ? j : NSEG + j - LAG; }
__device__ __forceinline__ int sched_f(int j) { return NSEG + j - LAG; }
__device__ __forceinline__ void wait_cnt(const int* p, int target) {
  int v, n = 0;
  do {
    asm volatile("ld.relaxed.gpu.global.b32 %0, [%1];" : "=r"(v) : "l"(p) : "memory");
    if (v >= target) break;
    __nanosleep(100);
    if (++n > SPIN_LIMIT) FAIL();
  } while (true);
  asm volatile("fence.acquire.gpu;" ::: "memory");
  asm volatile("fence.proxy.async.global;" ::: "memory");
}
__device__ __forceinline__ void red_release(void* p, uint32_t v) { asm volatile("red.release.gpu.global.add.u32 [%0], %1;" :: "l"(p), "r"(v) : "memory"); }
__device__ __forceinline__ void red_relaxed(void* p, uint32_t v) { asm volatile("red.relaxed.gpu.global.add.u32 [%0], %1;" :: "l"(p), "r"(v) : "memory"); }
#define VMASK 0xa5294a5294ull
__host__ __device__ constexpr int popc40(unsigned long long m) { int c = 0; for (; m; m &= m - 1) c++; return c; }
static_assert(popc40(VMASK) == SSV, "mask");
__host__ __device__ constexpr int ss_idx(int ks, int n) { return n == SSV ? popc40(VMASK & ((1ull << ks) - 1)) : ks * n / 40; }
__host__ __device__ constexpr bool is_ss(int ks, int n) { return ss_idx(ks + 1, n) != ss_idx(ks, n); }
__host__ __device__ constexpr int rs_idx(int ks, int n) { return ks - ss_idx(ks, n); }

#define SL2 (0.07216878364870322f * 1.4426950408889634f)

#define SUM_LOOP 0
#define TAB_N 32
struct DescTab { uint64_t tile[2][40], unit[2 * SSQ + SSV]; };
constexpr DescTab make_tab() {
  DescTab t = {};
  for (int rg = 0; rg < 2; rg++)
    for (int k = 0; k < 40; k++) t.tile[rg][k] = dlo(OFF_TILE + (k / 10) * TILE_GRP + rg * TILE_SBO + (k % 10) * 256, 128) | ((uint64_t)dhi(TILE_SBO, 0) << 32);
  for (int u = 0; u < 2 * SSQ + SSV; u++) t.unit[u] = dlo(u * 2048, 0) | ((uint64_t)dhi(1024, 1) << 32);
  return t;
}
__constant__ DescTab c_tab = make_tab();
template <int N, int NSS, int RG, int KS, int K1, int K0 = 0>
__device__ __forceinline__ void proj(float* acc, const uint32_t* W, uint32_t ub) {
  if constexpr (KS < K1) {
    constexpr int i = rs_idx(KS, NSS) * 4;
    if constexpr (N >= TAB_N) {
      if constexpr (is_ss(KS, NSS)) MM<N>::template ssd<(KS != K0)>(acc, c_tab.unit[ub + ss_idx(KS, NSS)], c_tab.tile[RG][KS]);
      else MM<N>::template rsd<(KS != K0)>(acc, W[i], W[i + 1], W[i + 2], W[i + 3], c_tab.tile[RG][KS]);
    } else {
      constexpr uint32_t BLO = dlo(OFF_TILE + (KS / 10) * TILE_GRP + RG * TILE_SBO + (KS % 10) * 256, 128), BHI = dhi(TILE_SBO, 0);
      if constexpr (is_ss(KS, NSS)) MM<N>::template ss<dlo(ss_idx(KS, NSS) * 2048, 0), dhi(1024, 1), BLO, BHI, (KS != K0), 1>(acc, ub * 128);
      else MM<N>::template rs<BLO, BHI, (KS != K0)>(acc, W[i], W[i + 1], W[i + 2], W[i + 3]);
    }
    proj<N, NSS, RG, KS + 1, K1, K0>(acc, W, ub);
  }
}
template <int N>
__device__ __forceinline__ void load_w(uint32_t* W, uint32_t stage, int warp, int lane) {
  const int kr = (lane >> 4) * 8 + (lane & 7);
  const int cb = warp * 2 + ((lane >> 3) & 1);
  const uint32_t a0 = stage + kr * 128 + ((cb ^ (lane & 7)) << 4);
#pragma unroll
  for (int i = 0; i < N; i++) ldsm4t(W[4 * i], W[4 * i + 1], W[4 * i + 2], W[4 * i + 3], a0 + i * 2048);
}
template <int N, int U, int OS, int ACC>
__device__ __forceinline__ void wo4(float* d) {
  constexpr uint32_t WA = U >= 4 ? OFF_WO + (U - 4) * 2048 : OFF_WT, OB = OS == 0 ? OFF_O : OS == 1 ? OFF_XL : OFF_XF, SBO = OS ? 1024 : PL_SZ;
  MM<N>::template ss<dlo(WA, 0), dhi(1024, 1), dlo(OB, 128), dhi(SBO, 0), ACC, 1>(d, 0);
  MM<N>::template ss<dlo(WA + 2048, 0), dhi(1024, 1), dlo(OB + 256, 128), dhi(SBO, 0), 1, 1>(d, 0);
  MM<N>::template ss<dlo(WA + 4096, 0), dhi(1024, 1), dlo(OB + 512, 128), dhi(SBO, 0), 1, 1>(d, 0);
  MM<N>::template ss<dlo(WA + 6144, 0), dhi(1024, 1), dlo(OB + 768, 128), dhi(SBO, 0), 1, 1>(d, 0);
}
__device__ __forceinline__ void wo_coord(int i, int t3, int head, int& c0, int& c1) {
  const int g = i >> 1;
  const int blk = g == 0 ? 9 : (g < 4 ? g - 1 : (g - 4) >> 1) * 3 + t3;
  int sl = g < 4 ? t3 : (g & 1) ? t3 + 1 : t3 + 2;
  if (sl >= 3) sl -= 3;
  c0 = blk * 64; c1 = head * DH + sl * 64 + (i & 1) * 32;
}
__device__ __forceinline__ void tok_softmax(uint32_t sb, int job, int lane) {
  const bool w1 = job & 1;
  const int dg = (lane >> 2) - (lane & 3) * 2;
  const uint32_t lo = sb + OFF_PL + (job >> 1) * PL_SZ + (job & 1) * 1792, l8 = lo + 512 + lane * 8, pa = lo + lane * 4;
  const uint32_t km = job & 2 ? 640 : 512;
  float x[14];
  {
    const uint4 a = lds128(lo + lane * 16);
    const uint2 e = lds64(l8);
    const uint32_t c = lds32(768 + pa);
    x[0] = bf_lo(a.x); x[1] = bf_hi(a.x); x[2] = bf_lo(a.y); x[3] = bf_hi(a.y); x[4] = bf_lo(a.z); x[5] = bf_hi(a.z); x[6] = bf_lo(a.w); x[7] = bf_hi(a.w);
    x[8] = bf_lo(c); x[9] = bf_hi(c); x[10] = bf_lo(e.x); x[11] = bf_hi(e.x); x[12] = bf_lo(e.y); x[13] = bf_hi(e.y);
  }
  if (dg < 0) { x[8] = -INFINITY; if (w1) x[4] = -INFINITY; else x[10] = -INFINITY; }
  if (dg < 1) { x[9] = -INFINITY; if (w1) x[5] = -INFINITY; else x[11] = -INFINITY; }
  const float m4 = fmaxf(x[8], x[9]);
  float m0 = fmaxf(fmaxf(fmaxf(x[0], x[1]), fmaxf(x[2], x[3])), fmaxf(fmaxf(x[4], x[5]), fmaxf(x[6], x[7])));
  float m1 = fmaxf(fmaxf(x[10], x[11]), fmaxf(x[12], x[13]));
  if (w1) m1 = fmaxf(m1, m4); else m0 = fmaxf(m0, m4);
  m0 = fmaxf(m0, __shfl_xor_sync(~0u, m0, 1)); m1 = fmaxf(m1, __shfl_xor_sync(~0u, m1, 1));
  sts32(pa + (w1 ? 384 : 896 + 128), 0u); sts32(pa + 1152 - km, 0u); sts32(pa + 896 + 1152 - km, 0u); sts64(l8 + 896 - 256, 0u, 0u);
  m0 = fmaxf(m0, __shfl_xor_sync(~0u, m0, 2)); m1 = fmaxf(m1, __shfl_xor_sync(~0u, m1, 2));
  m0 *= -SL2; m1 *= -SL2;
#pragma unroll
  for (int j = 0; j < 14; j++) x[j] = ex2(fmaf(x[j], SL2, j < 8 ? m0 : j >= 10 ? m1 : w1 ? m1 : m0));
  const float l4s = x[8] + x[9];
  float l0 = ((x[0] + x[1]) + (x[2] + x[3])) + ((x[4] + x[5]) + (x[6] + x[7])), l1 = (x[10] + x[11]) + (x[12] + x[13]);
  if (w1) l1 += l4s; else l0 += l4s;
  l0 += __shfl_xor_sync(~0u, l0, 1); l1 += __shfl_xor_sync(~0u, l1, 1);
  l0 += __shfl_xor_sync(~0u, l0, 2); l1 += __shfl_xor_sync(~0u, l1, 2);
  l0 = rcpf(l0); l1 = rcpf(l1);
#pragma unroll
  for (int j = 0; j < 7; j++) {
    const float iv = j < 4 ? l0 : j > 4 ? l1 : w1 ? l1 : l0;
    sts32(pa + (j < 3 ? j * 128 : j == 3 ? km : j == 4 ? (w1 ? 896 + 128 : 384) : j == 5 ? 896 : 896 + km), pack2(x[2 * j] * iv, x[2 * j + 1] * iv));
  }
}
template <int N>
__device__ __forceinline__ void wo_phase(uint32_t sb, int wg, int warp, int lane, uint32_t par, uint32_t r1) {
  const uint32_t bar = sb + OFF_BAR;
  float x[N / 2], y[N / 2];
  const uint2 ta = lds64(sb + OFF_TAB + (wg * 4 + warp) * 8);
  uint32_t xa = (ta.x & ~255u) + lane * 8, xb = (ta.x & 0xFF0000FFu) + SMEM0 + OFF_BAR, ya = (ta.y & ~255u) + lane * 8, yb = (ta.y & 0xFF0000FFu) + SMEM0 + OFF_BAR;
  asm volatile("" : "+r"(xa), "+r"(xb), "+r"(ya), "+r"(yb));
  auto scat = [&](uint32_t ad, uint32_t mb, const float* d) {
    st_async_v2(ad, pack2(d[0], d[1]), pack2(d[2], d[3]), mb);
    if (N == 16) st_async_v2(ad + LAND_F, pack2(d[4], d[5]), pack2(d[6], d[7]), mb);
  };
  if (wg == 0) {
    bar_sync(N_O, 384);
    wg_fence(); wo4<N, 4, 0, 0>(x); wo4<N, 8, 0, 0>(y); wg_commit();
    mbar_waitu(bar + 8 * B_OPEER, par);
    CFENCE(); wg_fence(); wo4<N, 16, 1, 1>(x); wo4<N, 20, 2, 1>(x); wg_commit();
    wo4<N, 24, 1, 1>(y); wg_commit();
    mbar_waitu2(bar + 8 * B_WOF, bar + 8 * B_MEMFREE, par);
    wg_fence(); wo4<N, 28, 2, 1>(y); wg_commit();
    bar_arrive(N_AB, 256);
    wg_wait<2>(); scat(xa, xb, x);
    wg_wait<0>(); scat(ya, yb, y);
  } else {
    bar_sync(N_O, 384);
    wg_fence(); wo4<N, 0, 0, 0>(x); wg_commit(); wo4<N, 12, 0, 0>(y); wg_commit();
    wg_wait<1>(); mbar_arrive_remote_if(lane == 0, r1);
    mbar_waitu(bar + 8 * B_MEMFREE, par);
    scat(xa, xb, x);
    bar_sync(N_AB, 256);
    CFENCE(); wg_fence(); wo4<N, 32, 1, 1>(y); wo4<N, 36, 2, 1>(y); wg_commit();
    bar_arrive(N_TURN, 256);
    wg_wait<0>(); scat(ya, yb, y);
  }
}
#define DS_DUAL 10
#define DS_SINGLE 20
#define POLL_GAP 100
#define POLL_GAPD 0
#define TOK_DELAY 250
#define LATE_SM 1
#define UMAX 40
#define VD1 6
#define VS1 4
#define VST 17
struct AMaps { CUtensorMap w16[3], wo32; };
__global__ void __launch_bounds__(512, 1)
acore_kernel(const __grid_constant__ AMaps M, const __nv_bfloat16* __restrict__ mem0, int sync_b) {
  extern __shared__ __align__(1024) unsigned char smem_raw[];
  const uint32_t sb = smem_u32(smem_raw);
  GTS(24);
  if (threadIdx.x == 0) {
    uint32_t smid; asm volatile("mov.u32 %0, %%smid;" : "=r"(smid));
    g_tpc[(smid >> 1) & 127] = 1;
    __threadfence();
    asm volatile("griddepcontrol.launch_dependents;");
  }
  const int lane0 = threadIdx.x & 31;
#define LANE_INIT() int lane; asm volatile("mov.u32 %0, %%laneid;" : "=r"(lane))
  const int warp = __shfl_sync(~0u, (threadIdx.x >> 5) & 3, 0);
  const int cl = blockIdx.x / CL_SIZE;
  const uint32_t rank = blockIdx.x - cl * CL_SIZE;
  const int nh = cl >= 1 && cl <= 3 ? 4 : 5;
  const int nA = 3 * nh;
  const int wg = __shfl_sync(~0u, (int)rank < nA ? threadIdx.x >> 7 : 4, 0);
  const int head = (cl < 4 ? (cl ? 1 + 4 * cl : 0) : 5 * cl - 3) + rank / 3;
  const int t3 = rank % 3;
  const int col0 = head * DH + t3 * 64;
  const uint32_t bar = sb + OFF_BAR;
  const uint32_t rb0 = SMEM0;
  const uint16_t mcmask = (uint16_t)((1u << nA) - 1);
  const uint32_t nxt = sb + ((t3 == 2 ? -2 : 1) << 24), prv = sb + ((t3 == 0 ? 2 : -1) << 24);
  const int ig = (int)rank - (nA - 4);

  if (threadIdx.x == 0) {
    if (mapa(sb, nA - 1) != rb0 + ((nA - 1) << 24) || mapa(sb, 0) != rb0 || mapa(sb, 1) != rb0 + (1u << 24) || sb != SMEM0 + (rank << 24)) FAIL();
    for (int i = 0; i < B_NUM; i++)
      mbar_init(bar + 8 * i, i == B_R1 ? 4 * nA : i == B_R2 ? 12 * nA : i == B_MEMFREE ? nA : i == B_LANDFREE ? 4 * nA : i == B_PLFREE || i == B_XFREE ? 2 : 1);
    asm volatile("fence.mbarrier_init.release.cluster;" ::: "memory");
    mbar_expect(bar + 8 * B_W0, (80 + SSV + VST) * 2048);
  }
  __syncthreads();
  if (lane0 == 0) {
    const int w12 = wg * 4 + warp;
    if (w12 < 10) {
#pragma unroll 1
      for (int ks = 4 * w12; ks < 4 * w12 + 4; ks++) {
        const bool ss = is_ss(ks, SSQ);
        tma2d(ss ? sb + OFF_WS + ss_idx(ks, SSQ) * 2048 : sb + OFF_WO + rs_idx(ks, SSQ) * 2048, &M.w16[0], col0, ks * 16, bar + 8 * B_W0);
        tma2d(ss ? sb + OFF_WS + (SSQ + ss_idx(ks, SSQ)) * 2048 : sb + OFF_WO + (40 - SSQ + rs_idx(ks, SSQ)) * 2048, &M.w16[1], col0, ks * 16, bar + 8 * B_W0);
        if (is_ss(ks, SSV)) tma2d(sb + OFF_WS + (2 * SSQ + ss_idx(ks, SSV)) * 2048, &M.w16[2], col0, ks * 16, bar + 8 * B_W0);
        else if (rs_idx(ks, SSV) < VST) tma2d(sb + OFF_WO + (80 - 2 * SSQ + rs_idx(ks, SSV)) * 2048, &M.w16[2], col0, ks * 16, bar + 8 * B_W0);
        else tma2d_prefetch(&M.w16[2], col0, ks * 16);
      }
      int c0, c1;
      wo_coord(2 * w12, t3, head, c0, c1);
      tma2d_prefetch(&M.wo32, c0, c1);
      tma2d_prefetch(&M.wo32, c0, c1 + 32);
    }
  }
  static_assert((80 - 2 * SSQ + VST) * 2048 <= OFF_BAR - OFF_WO && 40 - SSV - VST <= 10, "staging");
  if (lane0 < 2 && wg < 2) {
    const int u = 4 * (wg ? (lane0 ? 6 + t3 : 9) : (lane0 ? 3 + t3 : t3)) + warp;
    const int li = (u >= nA) + (u >= 2 * nA) + (u >= 3 * nA);
    sts32(sb + OFF_TAB + (wg * 4 + warp) * 8 + lane0 * 4,
          rb0 + ((u - li * nA) << 24) + OFF_TILE + LAND(li + (u >= 36 ? t3 : 0)) + (rank / 3) * 256 + 8 * (B_RS + li));
  }
  __syncthreads();
  GTS(25);

  auto issue_tok = [&](int sc, int fb, int rel = -1, uint32_t ph = 0) {
    if (sync_b) wait_cnt(&g_xready[sc][0], 32);
    if (rel >= 0) mbar_waitu(bar + 8 * rel, ph);
    bulk_g2s_mc_e(sb + OFF_TILE + ig * TILE_GRP + TILE_SBO, &g_xn[0][0] + uni(sc * (32 * DM)) + ig * 5120, 10240, bar + 8 * (fb + ig), mcmask);
  };
#define POLL(d, q) _Pragma("unroll") for (int k = 0; k < NCL; k++) \
      asm volatile("ld.relaxed.gpu.global.v2.b32 {%0,%1}, [%2];" : "=r"(d[k].x), "=r"(d[k].y) : "l"(q + k * 2560) : "memory")
#define L3(L, a, b, c) lop3<L>(a, b, c)
#define TAGS(L, d) L3(L, L3(L, L3(L, d[0].x, d[0].y, d[1].x), L3(L, d[1].y, d[2].x, d[2].y), L3(L, d[3].x, d[3].y, d[4].x)), L3(L, d[4].y, d[5].x, d[5].y), L3(L, d[6].x, d[6].y, d[6].y))
    auto deliver = [&](uint2* pa, const uint32_t* gq, int u, int c, int dc, int ds, int step, bool first, int lane) {
      const uint32_t off = uni(OFF_TILE + ((u * 205) >> 11) * (TILE_GRP - TILE_SBO) + u * 256 + dc * LAND_F), boff = uni(OFF_BAR + 8 * (B_F1 + ((u * 205) >> 11)));
      const uint32_t* mi = &g_part[4][0][0][0] + uni((c * NCL + cl) * 2560 + u * 64);
      mbar_waitu(bar + 8 * B_LANDFREE, step & 1);
      int n = 0;
      while (true) {
        const bool ok = __all_sync(~0u, ((step & 2 ? ~TAGS(0xFE, pa) : TAGS(0x80, pa)) & 1) != 0);
        if (ok) break;
        if (++n > SPIN_LIMIT) FAIL();
        POLL(pa, gq);
      }
      if (warp == 0 && first) { TS(19); TSV(10, n); }
      const uint32_t w0 = hadd2bf(hadd2bf(hadd2bf(pa[0].x, pa[1].x), hadd2bf(pa[2].x, pa[3].x)), hadd2bf(hadd2bf(pa[4].x, pa[5].x), pa[6].x));
      const uint32_t w1 = hadd2bf(hadd2bf(hadd2bf(pa[0].y, pa[1].y), hadd2bf(pa[2].y, pa[3].y)), hadd2bf(hadd2bf(pa[4].y, pa[5].y), pa[6].y));
      if (u < ds) {
        const uint32_t da = SMEM0 + off + lane * 8, db = SMEM0 + boff;
#pragma unroll
        for (int d = 0; d < 12; d++) st_async_v2((d << 24) + da, w0, w1, (d << 24) + db);
#pragma unroll
        for (int d = 12; d < 15; d++) st_async_v2_if(nA == 15, (d << 24) + da, w0, w1, (d << 24) + db);
      } else {
        *reinterpret_cast<uint2*>(const_cast<uint32_t*>(gq) + ((4 - 2 * (step & 1)) * NCL + cl) * 2560) = make_uint2(w0, w1);
        asm volatile("fence.proxy.async.global;" ::: "memory");
        __syncwarp();
        bulk_g2s_mc_e(sb + off, mi, 256, sb + boff, mcmask);
      }
    };
#define REL(b, g) mbar_arrive_remote_if(lane == 0, rb0 + ((nA - 4 + (g)) << 24) + OFF_BAR + 8 * (b))

  if (wg < 2) {
    asm volatile("setmaxnreg.inc.sync.aligned.u32 160;");
    LANE_INIT();
    uint32_t W[4 * (40 - SSQ)];
    mbar_waitw(bar + 8 * B_W0, 0);
    GTS(26);
    load_w<40 - SSQ>(W, sb + OFF_WO + wg * ((40 - SSQ) * 2048), warp, lane);
    fence_async();
    bar_sync(1, 384);
    cluster_sync_all();
    const uint32_t wbase = wg * SSQ;
    GTS(27);
#pragma unroll 1
    for (int step = -1; step < NSTEP; step++) {
      const uint32_t par = step & 1;
      asm volatile("" : "+r"(lane));
      const bool dual = is_dual(step), has_next = step + 1 < NSTEP;
#define QK_SA (sb + OFF_QK + wg * 15360 + (2 * warp + ((lane >> 3) & 1)) * 128 + (lane & 7) * 16)
#define QK_F (wg ? -5120 : 5120)
#define QK_S12 ((wg ? (lane >> 4) : 1 + 2 * (lane >> 4)) * 1024)
#define QK_S34 ((wg ? 2 + (lane >> 4) : 2 - 2 * (lane >> 4)) * 1024)
      if (step >= 0) {
        if (dual) {
          float acc[24];
          mbar_waitu(bar + 8 * (B_F1 + 0), par);
          if (wg + warp == 0) { TS(0); TSN(1); }
          CFENCE(); wg_fence(); proj<48, SSQ, 0, 0, 10>(acc, W, wbase); wg_commit();
          mbar_waitu(bar + 8 * (B_F1 + 1), par);
          CFENCE(); wg_fence(); proj<48, SSQ, 0, 10, 20>(acc, W, wbase); wg_commit();
          mbar_waitu(bar + 8 * (B_F1 + 2), par);
          CFENCE(); wg_fence(); proj<48, SSQ, 0, 20, 30>(acc, W, wbase); wg_commit();
          mbar_waitu2(bar + 8 * (B_F1 + 3), bar + 8 * B_PLFREE, par);
          if (wg + warp == 0) TS(2);
          CFENCE(); wg_fence(); proj<48, SSQ, 0, 30, 40>(acc, W, wbase); wg_commit();
          bar_arrive(N_VGO, 384);
          const uint32_t sa = QK_SA, s0 = sa + 4096 + (lane >> 4) * QK_F, s1 = sa + QK_F + QK_S12, s2 = sa + QK_F + QK_S34;
          wg_wait<0>();
          if (wg + warp == 0) TS(3);
          stsm4t(s0, pack2(acc[0], acc[1]), pack2(acc[2], acc[3]), pack2(acc[20], acc[21]), pack2(acc[22], acc[23]));
          stsm4t(s1, pack2(acc[4], acc[5]), pack2(acc[6], acc[7]), pack2(acc[8], acc[9]), pack2(acc[10], acc[11]));
          stsm4t(s2, pack2(acc[12], acc[13]), pack2(acc[14], acc[15]), pack2(acc[16], acc[17]), pack2(acc[18], acc[19]));
        } else {
          float acc[4];
          mbar_waitu(bar + 8 * (B_F1 + 0), par);
          if (wg + warp == 0) { TS(0); TSN(1); }
          CFENCE(); wg_fence(); proj<8, SSQ, 0, 0, 10>(acc, W, wbase); wg_commit();
          mbar_waitu(bar + 8 * (B_F1 + 1), par);
          CFENCE(); wg_fence(); proj<8, SSQ, 0, 10, 20>(acc, W, wbase); wg_commit();
          mbar_waitu(bar + 8 * (B_F1 + 2), par);
          CFENCE(); wg_fence(); proj<8, SSQ, 0, 20, 30>(acc, W, wbase); wg_commit();
          mbar_waitu2(bar + 8 * (B_F1 + 3), bar + 8 * B_PLFREE, par);
          if (wg + warp == 0) TS(2);
          CFENCE(); wg_fence(); proj<8, SSQ, 0, 30, 40>(acc, W, wbase); wg_commit();
          bar_arrive(N_VGO, 384);
          const uint32_t s0 = QK_SA + 4096;
          wg_wait<0>();
          if (wg + warp == 0) TS(3);
          stsm2t(s0, pack2(acc[0], acc[1]), pack2(acc[2], acc[3]));
        }
        fence_async();
        bar_sync(N_QK, 256);
        if (wg == 0 || dual) {
          float s[20];
          const uint32_t ab = wg * 192, bb = wg * -320;
          wg_fence();
          MM<40>::ss2<dlo(OFF_QK, 128), dhi(1024, 0), dlo(OFF_QK + 15360, 128), dhi(1024, 0), 0>(s, ab, bb);
          MM<40>::ss2<dlo(OFF_QK + 256, 128), dhi(1024, 0), dlo(OFF_QK + 15360 + 256, 128), dhi(1024, 0), 1>(s, ab, bb);
          MM<40>::ss2<dlo(OFF_QK + 512, 128), dhi(1024, 0), dlo(OFF_QK + 15360 + 512, 128), dhi(1024, 0), 1>(s, ab, bb);
          MM<40>::ss2<dlo(OFF_QK + 768, 128), dhi(1024, 0), dlo(OFF_QK + 15360 + 768, 128), dhi(1024, 0), 1>(s, ab, bb);
          wg_commit();
          bar_arrive(N_SISS, 384);
          const int rw = (warp - wg) & 3;
          const uint32_t bo = OFF_BAR + 8 * (B_SB + 3 * wg + rw), lo = OFF_PL + wg * PL_SZ + rw * 1792;
          const uint32_t km = wg ? 640 : 512;
          uint32_t l16 = lo + lane * 16, l4 = lo + lane * 4;
          mbar_expect_if(lane == 0 && rw < 3, sb + bo, rw < 2 ? 1792 : 1280);
          asm volatile("" : "+r"(l16), "+r"(l4));
          if (rw == 2) {
            wg_wait<0>();
            if (wg == 0) TSD(4, __float_as_uint(s[0]));
            {
              const uint32_t w0 = pack2(s[0], s[1]), w1 = pack2(s[4], s[5]), w2 = pack2(s[8], s[9]), w3 = pack2(s[12], s[13]), w4 = pack2(s[16], s[17]);
              st_async_v4(nxt + 896 + l16, w0, w1, w2, w3, nxt + bo);
              st_async_v4(prv + l16, w0, w1, w2, w3, prv + bo);
              st_async_b32(nxt + 896 + 768 + l4, w4, nxt + bo);
              st_async_b32(prv + 768 + l4, w4, prv + bo);
            }
            bar_arrive(N_SDONE, 256);
            mbar_waitu(sb + bo, (step - wg * LAG) & 1);
            if (wg == 0) TS(5);
            float x[10];
            {
              const uint4 a = lds128(sb + l16), b = lds128(sb + 896 + l16);
              const uint32_t c = lds32(sb + 768 + l4), d = lds32(sb + 896 + 768 + l4);
              const uint32_t e0 = hadd2bf(a.x, b.x), e1 = hadd2bf(a.y, b.y), e2 = hadd2bf(a.z, b.z), e3 = hadd2bf(a.w, b.w), e4 = hadd2bf(c, d);
              x[0] = s[0] + bf_lo(e0); x[1] = s[1] + bf_hi(e0); x[2] = s[4] + bf_lo(e1); x[3] = s[5] + bf_hi(e1); x[4] = s[8] + bf_lo(e2);
              x[5] = s[9] + bf_hi(e2); x[6] = s[12] + bf_lo(e3); x[7] = s[13] + bf_hi(e3); x[8] = s[16] + bf_lo(e4); x[9] = s[17] + bf_hi(e4);
            }
            float m0 = fmaxf(fmaxf(fmaxf(x[0], x[1]), fmaxf(x[2], x[3])), fmaxf(fmaxf(x[4], x[5]), fmaxf(fmaxf(x[6], x[7]), fmaxf(x[8], x[9]))));
            m0 = fmaxf(m0, __shfl_xor_sync(~0u, m0, 1));
            sts32(sb + l4 + 1152 - km, 0u);
            m0 = fmaxf(m0, __shfl_xor_sync(~0u, m0, 2));
            m0 *= -SL2;
#pragma unroll
            for (int j = 0; j < 5; j++) {
              x[2 * j] = ex2(fmaf(x[2 * j], SL2, m0)); x[2 * j + 1] = ex2(fmaf(x[2 * j + 1], SL2, m0));
              sts32(sb + l4 + (j < 4 ? j * 128 : km), pack2(x[2 * j], x[2 * j + 1]));
            }
            float l = ((x[0] + x[1]) + (x[2] + x[3])) + ((x[4] + x[5]) + ((x[6] + x[7]) + (x[8] + x[9])));
            l += __shfl_xor_sync(~0u, l, 1);
            fence_async();
            sts32(sb + OFF_INV + wg * 64 + (lane >> 1) * 4, __float_as_uint(l));
            bar_arrive(N_PM, dual ? 224 : 192);
            if (wg == 0) TS(6);
          } else if (rw < 2) {
            const bool w1 = rw == 1;
            const uint32_t l8 = lo + 512 + lane * 8;
            uint32_t tw[7];
            wg_wait<0>();
            bar_arrive(N_SDONE, 256);
            tw[0] = pack2(s[0], s[1]); tw[1] = pack2(s[4], s[5]); tw[2] = pack2(s[8], s[9]); tw[3] = pack2(s[16], s[17]);
            tw[4] = w1 ? pack2(s[6], s[7]) : pack2(s[12], s[13]); tw[5] = pack2(s[2], s[3]); tw[6] = pack2(s[18], s[19]);
            { const uint32_t t0 = clock32(); while (clock32() - t0 < TOK_DELAY) {} }
            st_async_v4(nxt + 896 + l16, tw[0], tw[1], tw[2], tw[3], nxt + bo);
            st_async_v4(prv + l16, tw[0], tw[1], tw[2], tw[3], prv + bo);
            st_async_v2(nxt + 896 + l8, tw[5], tw[6], nxt + bo);
            st_async_v2(prv + l8, tw[5], tw[6], prv + bo);
            st_async_b32(nxt + 896 + 768 + l4, tw[4], nxt + bo);
            st_async_b32(prv + 768 + l4, tw[4], prv + bo);
            mbar_waitu(sb + bo, (step - wg * LAG) & 1);
            const uint4 a = lds128(sb + l16), b = lds128(sb + 896 + l16);
            const uint2 e = lds64(sb + l8), f = lds64(sb + 896 + l8);
            const uint32_t c = lds32(sb + 768 + l4), d = lds32(sb + 896 + 768 + l4);
            sts128(sb + l16, hadd2bf(hadd2bf(a.x, b.x), tw[0]), hadd2bf(hadd2bf(a.y, b.y), tw[1]), hadd2bf(hadd2bf(a.z, b.z), tw[2]), hadd2bf(hadd2bf(a.w, b.w), tw[3]));
            sts64(sb + l8, hadd2bf(hadd2bf(e.x, f.x), tw[5]), hadd2bf(hadd2bf(e.y, f.y), tw[6]));
            sts32(sb + 768 + l4, hadd2bf(hadd2bf(c, d), tw[4]));
            bar_arrive(N_PX, dual ? 256 : 192);
            if (wg + warp == 0) TS(9);
          } else {
            wg_wait<0>();
            if (wg == 0) {
              mbar_expect_if(lane < 3 && has_next, bar + 8 * (lane == 2 ? B_OPEER : B_WOF + lane), lane == 2 ? (dual ? 4096 : 2048) : lane ? 8192 : 20480);
              auto fetch = [&](int i, int n, uint32_t dst, int mb) {
                int c0, c1; wo_coord(i, t3, head, c0, c1);
                tma2d_e(dst, &M.wo32, c0, c1, bar + 8 * mb); if (n == 2) tma2d_e(dst + 4096, &M.wo32, c0, c1 + 32, bar + 8 * mb);
              };
              bar_sync(N_G3, 160);
              if (has_next) {
                fetch(0, 2, sb + OFF_WT, B_WTF);
                mbar_arrive_remote_if(lane < 2, (lane ? nxt : prv) + OFF_BAR + 8 * B_XFREE);
              }
              bar_sync(N_SDONE, 256);
              if (has_next) {
                fetch(15, 1, sb + OFF_QK, B_WOF); fetch(16, 2, sb + OFF_QK + 4096, B_WOF); fetch(18, 2, sb + OFF_QK + 12288, B_WOF);
                mbar_waitu(bar + 8 * B_XFREE, par);
              }
              bar_arrive(N_PM, dual ? 224 : 192);
              bar_sync(N_VDONE, 160);
              mbar_arrive_remote_if(lane < nA && has_next, rb0 + (lane << 24) + OFF_BAR + 8 * B_MEMFREE);
              if (has_next) mbar_waitu(bar + 8 * B_WTF, par);
            } else {
              bar_arrive(N_SDONE, 256);
              if ((unsigned)ig < 3) issue_tok(sched_l(step + 1), B_F2, B_R1, (step - LAG) & 1);
            }
          }
        } else {
          bar_arrive(N_SISS, 384);
          bar_arrive(N_SDONE, 256);
        }
        if (has_next) {
          if (step == 0) mbar_waitw(bar + 8 * B_W0, 1);
          const uint32_t r1 = rb0 + ((nA - 1) << 24) + OFF_BAR + 8 * B_R1;
          if (dual) wo_phase<16>(sb, wg, warp, lane, par, r1); else wo_phase<8>(sb, wg, warp, lane, par, r1);
          bar_arrive(N_C, 288);
          if (warp == 0) TS(7 + wg);
        }
      }
      if (has_next) {
        float acc[16];
        mbar_waitu(bar + 8 * B_F2, par ^ 1);
        wg_fence(); proj<32, SSQ, 1, 0, 10>(acc, W, wbase); wg_commit();
        mbar_waitu(bar + 8 * (B_F2 + 1), par ^ 1);
        wg_fence(); proj<32, SSQ, 1, 10, 14>(acc, W, wbase); wg_commit();
        wg_wait<1>(); REL(B_R2, 0);
        wg_fence(); proj<32, SSQ, 1, 14, 20>(acc, W, wbase); wg_commit();
        mbar_waitu(bar + 8 * (B_F2 + 2), par ^ 1);
        wg_fence(); proj<32, SSQ, 1, 20, 24>(acc, W, wbase); wg_commit();
        wg_wait<1>(); REL(B_R2, 1);
        wg_fence(); proj<32, SSQ, 1, 24, 30>(acc, W, wbase); wg_commit();
        mbar_waitu(bar + 8 * (B_F2 + 3), par ^ 1);
        wg_fence(); proj<32, SSQ, 1, 30, 34>(acc, W, wbase); wg_commit();
        wg_wait<1>(); REL(B_R2, 2);
        wg_fence(); proj<32, SSQ, 1, 34, 40>(acc, W, wbase); wg_commit();
        const uint32_t sa = QK_SA, s1 = sa + QK_S12, s2 = sa + QK_S34;
        wg_wait<0>(); REL(B_R2, 3);
        if (warp == 0) TS(11 + wg);
        stsm4t(s1, pack2(acc[0], acc[1]), pack2(acc[2], acc[3]), pack2(acc[4], acc[5]), pack2(acc[6], acc[7]));
        stsm4t(s2, pack2(acc[8], acc[9]), pack2(acc[10], acc[11]), pack2(acc[12], acc[13]), pack2(acc[14], acc[15]));
      }
    }
    GTS(28);
    cluster_sync_all();
  } else if (wg == 2) {
    asm volatile("setmaxnreg.inc.sync.aligned.u32 160;");
    LANE_INIT();
    uint32_t W[4 * (40 - SSV)];
    mbar_waitw(bar + 8 * B_W0, 0);
    load_w<VST>(W, sb + OFF_WO + (80 - 2 * SSQ) * 2048, warp, lane);
    fence_async();
    bar_sync(1, 384);
    if (lane == 0) {
      if (warp == 0) {
        mbar_expect(bar + 8 * B_W1, (40 - SSV - VST) * 2048);
#pragma unroll 1
        for (int ks = 0; ks < 40; ks++)
          if (!is_ss(ks, SSV) && rs_idx(ks, SSV) >= VST) tma2d(sb + OFF_QK + (rs_idx(ks, SSV) - VST) * 2048, &M.w16[2], col0, ks * 16, bar + 8 * B_W1);
      } else {
        if (warp == 1) mbar_expect(bar + 8 * B_W0, 26 * 2048);
#pragma unroll 1
        for (int i = warp - 1; i < 13; i += 3) { int c0, c1; wo_coord(i + 2, t3, head, c0, c1); tma2d(sb + OFF_WO + i * 4096, &M.wo32, c0, c1, bar + 8 * B_W0); }
      }
    }
    __syncwarp();
#pragma unroll
    for (int i = 0; i < 5; i++) {
      const int t = i * 128 + warp * 32 + lane;
      const uint4 v = *reinterpret_cast<const uint4*>(mem0 + (t & 7) * DM + (t >> 3) * 8);
      sts128(sb + OFF_TILE + (t / 160) * (TILE_GRP - TILE_SBO) + t * 16, v.x, v.y, v.z, v.w);
    }
    mbar_waitw(bar + 8 * B_W1, 0);
    load_w<40 - SSV - VST>(W + 4 * VST, sb + OFF_QK, warp, lane);
    fence_async();
    mbar_arrive_if(lane == 0, bar + 8 * (B_F1 + warp));
    mbar_expect_if(lane == 0, bar + 8 * (B_F2 + warp), 10240);
    mbar_arrive_if(warp == 3 && lane < 2, bar + 8 * B_PLFREE);
    cluster_sync_all();
    uint32_t vl[8];
    constexpr uint32_t wbase = 2 * SSQ;
    {
      float v[16];
      mbar_waitw4(bar + 8 * B_F2, 0);
      wg_fence(); proj<32, SSV, 1, 0, 40>(v, W, wbase); wg_commit();
      wg_wait<0>();
      mbar_arrive_remote_if(lane < 4, rb0 + ((nA - 4 + lane) << 24) + OFF_BAR + 8 * B_R2);
#pragma unroll
      for (int j = 0; j < 8; j++) vl[j] = pack2v(v[2 * j], v[2 * j + 1]);
      if (warp == 0 && (unsigned)ig < 3) issue_tok(1, B_F2, B_R2, 0);
    }
#pragma unroll 1
    for (int step = 0; step < NSTEP; step++) {
      const uint32_t par = step & 1;
      asm volatile("" : "+r"(lane));
      const bool dual = is_dual(step), has_next = step + 1 < NSTEP;
      mbar_expect_if(lane == 0 && has_next, bar + 8 * (B_F2 + warp), 10240);
      if (warp == 0 && ig == 3 && has_next && sync_b) wait_cnt(&g_xready[sched_l(step + 1)][0], 32);
      bar_sync(N_VGO, 384);
      CFENCE();
#define F1_BYTES (is_dual(step + 1) ? 15360 : 2560)
#define ARM() do { \
        mbar_expect_if(lane == 0 && has_next, bar + 8 * (B_F1 + warp), F1_BYTES); \
        mbar_expect_if(lane == 0 && has_next && warp * nA + (int)rank < 40, bar + 8 * (B_RS + warp), (warp * nA + (int)rank >= 36 ? nA : nh) * (dual ? 512 : 256)); } while (0)
#define O_ADDR() uint32_t oa = sb + OFF_O + (lane >> 4) * PL_SZ + warp * 256 + (lane & 15) * 16, xo = (lane >> 4) * 1024 + warp * 256 + (lane & 15) * 16; \
        asm volatile("" : "+r"(oa), "+r"(xo))
#define O_READY(act) do { if (has_next) { const uint4 ov = lds128(oa); \
        if (act) { st_async_v4(nxt + OFF_XL + xo, ov.x, ov.y, ov.z, ov.w, nxt + OFF_BAR + 8 * B_OPEER); \
                   st_async_v4(prv + OFF_XF + xo, ov.x, ov.y, ov.z, ov.w, prv + OFF_BAR + 8 * B_OPEER); } \
        fence_async(); bar_arrive(N_O, 384); } \
        if (warp == 0) TS(15); } while (0)
#define TOK_L3() if (warp == 0 && ig == 3 && has_next) { mbar_waitu(bar + 8 * B_R1, par); \
        bulk_g2s_mc_e(sb + OFF_TILE + 3 * TILE_GRP + TILE_SBO, &g_xn[0][0] + uni(sched_l(step + 1) * (32 * DM)) + 3 * 5120, 10240, bar + 8 * (B_F2 + 3), mcmask); }
#define OX_SA (sb + OFF_PL + (lane & 7) * 128 + (((warp * 2 + ((lane >> 3) & 1)) ^ (lane & 7)) << 4))
      if (dual) {
        uint32_t vf[8], vm[4], vn[8];
        {
          float v[24];
          wg_fence(); proj<48, SSV, 0, 30, 30 + VD1, 30>(v, W, wbase); wg_commit();
          ARM();
          bar_sync(N_SISS, 384);
          wg_fence(); proj<48, SSV, 0, 30 + VD1, 40, 30>(v, W, wbase); wg_commit();
          proj<48, SSV, 0, 0, 3, 30>(v, W, wbase); wg_commit();
          wg_wait<1>(); bar_arrive(N_G3, 160);
          wg_fence(); proj<48, SSV, 0, 3, 10, 30>(v, W, wbase); wg_commit();
          proj<48, SSV, 0, 10, 13, 30>(v, W, wbase); wg_commit();
          wg_wait<1>(); REL(B_R1, 0);
          wg_fence(); proj<48, SSV, 0, 13, 20, 30>(v, W, wbase); wg_commit();
          proj<48, SSV, 0, 20, 23, 30>(v, W, wbase); wg_commit();
          wg_wait<1>(); REL(B_R1, 1);
          wg_fence(); proj<48, SSV, 0, 23, 30, 30>(v, W, wbase); wg_commit();
          wg_wait<0>(); REL(B_R1, 2);
          bar_arrive(N_VDONE, 160);
          if (warp == 0) TS(14);
#pragma unroll
          for (int j = 4; j < 8; j++) vf[j] = pack2v(v[4 + 2 * j], v[5 + 2 * j]);
          keep4(vf + 4, lane);
          vm[0] = pack2v(v[0], v[1]); vm[1] = pack2v(v[2], v[3]); vm[2] = pack2v(v[20], v[21]); vm[3] = pack2v(v[22], v[23]);
          keep4(vm, lane);
#pragma unroll
          for (int j = 0; j < 4; j++) vf[j] = pack2v(v[4 + 2 * j], v[5 + 2 * j]);
          keep4(vf, lane);
        }
        {
          float o[8];
          O_ADDR();
          bar_sync(N_PM, 224);
          wg_fence();
          MM<8>::rs<dlo(OFF_PL + 3584, 128), dhi(896, 0), 0>(o, vl[0], vl[1], vl[2], vl[3]);
          MM<8>::rs<dlo(OFF_PL + PL_SZ + 3584, 128), dhi(896, 0), 0>(o + 4, vf[0], vf[1], vf[2], vf[3]);
          MM<8>::rs<dlo(OFF_PL + 3584 + 256, 128), dhi(896, 0), 1>(o, vl[4], vl[5], vl[6], vl[7]);
          MM<8>::rs<dlo(OFF_PL + PL_SZ + 3584 + 256, 128), dhi(896, 0), 1>(o + 4, vf[4], vf[5], vf[6], vf[7]);
          MM<8>::rs<dlo(OFF_PL + 3584 + 512, 128), dhi(896, 0), 1>(o, vm[0], vm[1], vm[2], vm[3]);
          MM<8>::rs<dlo(OFF_PL + PL_SZ + 3584 + 512, 128), dhi(896, 0), 1>(o + 4, vm[0], vm[1], vm[2], vm[3]);
          wg_commit();
          const uint4 il = lds128(sb + OFF_INV + (lane & 3) * 16), jf = lds128(sb + OFF_INV + 64 + (lane & 3) * 16);
          const float i0 = rcpf(__uint_as_float(il.x) + __uint_as_float(il.y)), i1 = rcpf(__uint_as_float(il.z) + __uint_as_float(il.w));
          const float j0 = rcpf(__uint_as_float(jf.x) + __uint_as_float(jf.y)), j1 = rcpf(__uint_as_float(jf.z) + __uint_as_float(jf.w));
          wg_wait<0>();
          stsm4t(oa, pack2(o[0] * i0, o[1] * i1), pack2(o[2] * i0, o[3] * i1), pack2(o[4] * j0, o[5] * j1), pack2(o[6] * j0, o[7] * j1));
          O_READY(true);
          TOK_L3();
        }
        {
          float v[16];
          bar_sync(N_TURN, 256);
          mbar_waitu(bar + 8 * B_F2, par ^ 1);
          wg_fence(); proj<32, SSV, 1, 0, 10>(v, W, wbase); wg_commit();
          mbar_waitu(bar + 8 * (B_F2 + 1), par ^ 1);
          wg_fence(); proj<32, SSV, 1, 10, 14>(v, W, wbase); wg_commit();
          wg_wait<1>(); REL(B_R2, 0);
          wg_fence(); proj<32, SSV, 1, 14, 20>(v, W, wbase); wg_commit();
          mbar_waitu(bar + 8 * (B_F2 + 2), par ^ 1);
          wg_fence(); proj<32, SSV, 1, 20, 24>(v, W, wbase); wg_commit();
          wg_wait<1>(); REL(B_R2, 1);
          wg_fence(); proj<32, SSV, 1, 24, 30>(v, W, wbase); wg_commit();
          mbar_waitu(bar + 8 * (B_F2 + 3), par ^ 1);
          wg_fence(); proj<32, SSV, 1, 30, 34>(v, W, wbase); wg_commit();
          wg_wait<1>(); REL(B_R2, 2);
          wg_fence(); proj<32, SSV, 1, 34, 40>(v, W, wbase); wg_commit();
          wg_wait<0>(); REL(B_R2, 3);
#pragma unroll
          for (int j = 0; j < 8; j++) vn[j] = pack2v(v[2 * j], v[2 * j + 1]);
          keep4(vn, lane); keep4(vn + 4, lane);
          if (warp == 0) TS(18);
        }
        uint32_t ow[16];
        bar_sync(N_P, 256);
        fence_async();
#define PV16(i, off, va) { float o[8]; wg_fence(); \
          MM<16>::rs<dlo(OFF_PL + (off), 128), dhi(896, 0), 0>(o, va[0], va[1], va[2], va[3]); \
          MM<16>::rs<dlo(OFF_PL + (off) + 256, 128), dhi(896, 0), 1>(o, va[4], va[5], va[6], va[7]); \
          MM<16>::rs<dlo(OFF_PL + (off) + 512, 128), dhi(896, 0), 1>(o, vm[0], vm[1], vm[2], vm[3]); \
          wg_commit(); wg_wait<0>(); \
          _Pragma("unroll") for (int j = 0; j < 4; j++) ow[4 * (i) + j] = pack2v(o[2 * j], o[2 * j + 1]); \
          keep4(ow + 4 * (i), lane); }
        PV16(0, 0, vl) PV16(1, 1792, vl) PV16(2, PL_SZ, vf) PV16(3, PL_SZ + 1792, vf)
        const uint32_t s1 = OX_SA + (lane < 16 ? 3072 : 0), s2 = OX_SA + (lane < 16 ? 2048 : 1024);
        bar_sync(N_V, 128);
        stsm4t(s1, ow[0], ow[1], ow[2], ow[3]);
        stsm4t(s2, ow[4], ow[5], ow[6], ow[7]);
        stsm4t(s1 + PL_SZ, ow[8], ow[9], ow[10], ow[11]);
        stsm4t(s2 + PL_SZ, ow[12], ow[13], ow[14], ow[15]);
#pragma unroll
        for (int j = 0; j < 8; j++) vl[j] = vn[j];
      } else {
        uint32_t vm[4], vn[8];
        {
          float v[4];
          wg_fence(); proj<8, SSV, 0, 30, 40, 30>(v, W, wbase); wg_commit();
          proj<8, SSV, 0, 0, VS1, 30>(v, W, wbase); wg_commit();
          ARM();
          bar_sync(N_SISS, 384);
          wg_wait<1>(); bar_arrive(N_G3, 160);
          wg_fence(); proj<8, SSV, 0, VS1, 30, 30>(v, W, wbase); wg_commit();
          if (has_next) { mbar_waitu2(bar + 8 * B_F2, bar + 8 * (B_F2 + 1), par ^ 1); mbar_waitu(bar + 8 * (B_F2 + 2), par ^ 1); }
          wg_wait<0>();
          bar_arrive(N_VDONE, 160);
          vm[0] = pack2v(v[0], v[1]); vm[1] = pack2v(v[2], v[3]); vm[2] = pack2v(v[1], v[0]); vm[3] = pack2v(v[3], v[2]);
        }
        float v[16];
        {
          wg_fence(); proj<32, SSV, 1, 0, 30>(v, W, wbase); wg_commit();
          {
            float o[4];
            O_ADDR();
            bar_sync(N_PM, 192);
            if (warp == 0) TS(14);
            wg_fence();
            MM<8>::rs<dlo(OFF_PL + 3584, 128), dhi(896, 0), 0>(o, vl[0], vl[1], vl[2], vl[3]);
            MM<8>::rs<dlo(OFF_PL + 3584 + 256, 128), dhi(896, 0), 1>(o, vl[4], vl[5], vl[6], vl[7]);
            MM<8>::rs<dlo(OFF_PL + 3584 + 512, 128), dhi(896, 0), 1>(o, vm[0], vm[1], vm[2], vm[3]);
            wg_commit();
            const uint4 il = lds128(sb + OFF_INV + (lane & 3) * 16);
            const float i0 = rcpf(__uint_as_float(il.x) + __uint_as_float(il.y)), i1 = rcpf(__uint_as_float(il.z) + __uint_as_float(il.w));
            wg_wait<0>();
            stsm2t(oa, pack2(o[0] * i0, o[1] * i1), pack2(o[2] * i0, o[3] * i1));
            O_READY(lane < 16);
            TOK_L3();
          }
          if (has_next) {
            mbar_arrive_remote_if(lane < 3, rb0 + ((nA - 4 + lane) << 24) + OFF_BAR + 8 * B_R2);
            bar_sync(N_TURN, 256);
            mbar_waitu(bar + 8 * (B_F2 + 3), par ^ 1);
          }
          wg_fence(); proj<32, SSV, 1, 30, 40>(v, W, wbase); wg_commit();
          wg_wait<0>();
          if (has_next) REL(B_R2, 3);
#pragma unroll
          for (int j = 0; j < 8; j++) vn[j] = pack2v(v[2 * j], v[2 * j + 1]);
          keep4(vn, lane); keep4(vn + 4, lane);
          if (warp == 0) TS(18);
        }
        float o[16];
        bar_sync(N_P, 256);
        fence_async();
        wg_fence();
        MM<32>::rs<dlo(OFF_PL, 128), dhi(896, 0), 0>(o, vl[0], vl[1], vl[2], vl[3]);
        MM<32>::rs<dlo(OFF_PL + 256, 128), dhi(896, 0), 1>(o, vl[4], vl[5], vl[6], vl[7]);
        MM<32>::rs<dlo(OFF_PL + 512, 128), dhi(896, 0), 1>(o, vm[0], vm[1], vm[2], vm[3]);
        wg_commit();
        const uint32_t s1 = OX_SA + (lane < 16 ? 3072 : 0), s2 = OX_SA + (lane < 16 ? 2048 : 1024);
        wg_wait<0>();
        bar_sync(N_V, 128);
        stsm4t(s1, pack2(o[0], o[1]), pack2(o[2], o[3]), pack2(o[4], o[5]), pack2(o[6], o[7]));
        stsm4t(s2, pack2(o[8], o[9]), pack2(o[10], o[11]), pack2(o[12], o[13]), pack2(o[14], o[15]));
#pragma unroll
        for (int j = 0; j < 8; j++) vl[j] = vn[j];
      }
      bar_arrive(N_OX, 160);
      if (warp == 0) TS(16);
    }
    cluster_sync_all();
  } else {
    asm volatile("setmaxnreg.dec.sync.aligned.u32 32;");
    if (wg > 3) return;
    LANE_INIT();
    struct RsJob { uint32_t* gp; uint32_t la, mb; int n; };
    auto rs_prep = [&](int step, int s, int c) {
      RsJob j;
      const int u = s * nA + rank;
      j.gp = &g_part[0][0][0][0] + (uint32_t)((((step & 1) * 2 + c) * NCL + cl) * 2560 + u * 64 + lane);
      j.la = sb + OFF_TILE + c * LAND_F + LAND(s) + lane * 8;
      j.mb = bar + 8 * (B_RS + s);
      j.n = u >= 40 ? 0 : u >= 36 ? 3 : 1;
      asm volatile("" : "+l"(j.gp), "+r"(j.la));
      return j;
    };
    auto rs_sum = [&](RsJob j, int step) {
      if (j.n) {
        auto five = [&](uint32_t la) {
          uint2 p[5];
#pragma unroll
          for (int i = 0; i < 4; i++) p[i] = lds64(la + i * 256);
          asm volatile("{\n.reg .pred q;\nsetp.eq.s32 q, %3, 5;\nmov.u32 %0, 0;\nmov.u32 %1, 0;\n@q ld.shared.v2.b32 {%0,%1}, [%2];\n}"
                       : "=r"(p[4].x), "=r"(p[4].y) : "r"(la + 1024), "r"(nh) : "memory");
          return make_uint2(hadd2bf(hadd2bf(p[0].x, p[1].x), hadd2bf(hadd2bf(p[2].x, p[3].x), p[4].x)),
                            hadd2bf(hadd2bf(p[0].y, p[1].y), hadd2bf(hadd2bf(p[2].y, p[3].y), p[4].y)));
        };
        const uint32_t tag = ((step >> 1) & 1) ^ 1;
        mbar_waitw(j.mb, step & 1);
        uint2 t = five(j.la);
        if (j.n > 1) {
          const uint2 a = five(j.la + (nh == 5 ? 1280 : TILE_GRP - 1280)), b = five(j.la + TILE_GRP);
          t.x = hadd2bf(t.x, hadd2bf(a.x, b.x)); t.y = hadd2bf(t.y, hadd2bf(a.y, b.y));
        }
        const uint32_t t0 = (movm(t.x) & ~1u) | tag, t1 = (movm(t.y) & ~1u) | tag;
        asm volatile("st.relaxed.gpu.global.b32 [%0], %1;" :: "l"(j.gp), "r"(t0) : "memory");
        asm volatile("st.relaxed.gpu.global.b32 [%0], %1;" :: "l"(j.gp + 32), "r"(t1) : "memory");
      }
    };
    if (warp * nA + (int)rank < 40) {
#pragma unroll
      for (int e = LAG; e < LAG + 2; e++)
        if ((e >> 1) & 1) *reinterpret_cast<uint2*>(&g_part[(e & 1) * 2 + 1][cl][warp * nA + rank][lane * 2]) = make_uint2(1u, 1u);
      __threadfence();
    }
    cluster_sync_all();
    if (warp == 2 && ig >= 0) issue_tok(0, B_F2);
#pragma unroll 1
    for (int step = 0; step < NSTEP; step++) {
      const uint32_t par = step & 1;
      asm volatile("" : "+r"(lane));
      const bool dual = is_dual(step), has_next = step + 1 < NSTEP;
      {
        bar_sync(N_PX, dual ? 256 : 192);
        if (dual || warp >= 2) tok_softmax(sb, dual ? warp : warp - 2, lane);
        bar_arrive(N_P, 256);
        asm volatile("" : "+r"(lane));
        if (has_next) {
          if (step + 2 == LAG && lane < 20) asm volatile("prefetch.global.L2 [%0];" :: "l"(mem0 + (warp * 20 + lane) * 64));
          const int nw = ig >= 0 ? 3 : 4, j0 = warp < nw ? warp : 8;
          const int sh = dual ? 1 : 0;
          rs_sum(rs_prep(step, j0 >> sh, j0 & sh), step);
          if (warp == 0) TS(17);
          if (dual) rs_sum(rs_prep(step, (j0 + nw) >> 1, (j0 + nw) & 1), step);
          if (warp == 0) { bar_sync(N_C, 288); }
          mbar_arrive_remote_if(lane < nA, rb0 + (lane << 24) + OFF_BAR + 8 * B_LANDFREE);
          const uint32_t gap = dual ? POLL_GAPD : POLL_GAP;
          if (gap) { const uint32_t t0 = clock32(); while (clock32() - t0 < gap) {} }
#pragma unroll 1
          for (int j = j0; j < (dual ? 8 : 4); j += nw) {
            const int u = (j >> sh) * nA + rank, c = j & sh;
            if (u < UMAX && (c || step + 1 != NSEG)) {
              const uint32_t* gq = &g_part[0][0][0][0] + (uint32_t)((par * 2 + c) * NCL * 2560 + u * 64 + lane * 2);
              uint2 pa[NCL];
              POLL(pa, gq);
              deliver(pa, gq, u, c, step + 1 < NSEG ? c : 0, dual ? DS_DUAL : DS_SINGLE, step, j == 0, lane);
            }
            if (warp == 0 && j == 0) TS(13);
          }
          if (warp >= nw && (is_dual(step + 1) || (ig < 3 && step + 2 < NSTEP))) {
            issue_tok(is_dual(step + 1) ? sched_f(step + 1) : sched_l(step + 2), is_dual(step + 1) ? B_F1 : B_F2, B_R2, par ^ 1);
          }
          if (step + 1 == LAG && UMAX) {
            uint4 v[5];
#pragma unroll
            for (int i = 0; i < 5; i++) { const int t = warp * 160 + i * 32 + lane; v[i] = *reinterpret_cast<const uint4*>(mem0 + (t & 7) * DM + (t >> 3) * 8); }
            mbar_waitu(bar + 8 * B_LANDFREE, par);
#pragma unroll
            for (int i = 0; i < 5; i++)
              st_async_v4(sb + OFF_TILE + LAND_F + warp * TILE_GRP + (i * 32 + lane) * 16, v[i].x, v[i].y, v[i].z, v[i].w, bar + 8 * (B_F1 + warp));
          }
        }
      }
      if (warp == 3) {
        unsigned char* o0 = g_o + uni(step * (96 * 8192) + (head * 3 + t3) * (dual ? 8192 : 4096));
        bar_sync(N_OX, 160);
        fence_async();
        bulk_s2g_es(o0, sb + OFF_PL, 4096);
        if (dual) bulk_s2g_es(o0 + 4096, sb + OFF_PL + PL_SZ, 4096);
        asm volatile("cp.async.bulk.commit_group;" ::: "memory");
        asm volatile("cp.async.bulk.wait_group.read 0;" ::: "memory");
        __syncwarp();
        mbar_arrive_remote_if(lane < 2, (lane ? nxt : prv) + OFF_BAR + 8 * B_PLFREE);
        asm volatile("cp.async.bulk.wait_group 0;" ::: "memory");
        asm volatile("fence.proxy.async.global;" ::: "memory");
        __syncwarp();
        if (lane == 0) red_release(&g_f[F_O + (head * 3 + t3) / 5][step], 1u);
        __syncwarp();
      }
    }
    cluster_sync_all();
  }
}

__device__ __forceinline__ float gelu2(float x) {
  const float u = x * fmaf(x * x, 0.7978845608028654f * 0.044715f, 0.7978845608028654f);
  float t; asm("tanh.approx.f32 %0, %1;" : "=f"(t) : "f"(u));
  return fmaf(x, t, x); }

struct BParams {
  CUtensorMap wmap[5];
  CUtensorMap wo16;
  const __nv_bfloat16* x;
  __nv_bfloat16* out;
};
#define BO_O 0
#define BO_RES (6 * 8192)
#define OP_RES 63488
#define BO_STG (BO_RES + 2 * OP_RES)
#define BO_RING_OP (BO_STG + 16384)
#define OP_SLOT 12288
#define NS_OP 3
#define BO_H 81920
#define BO_W1 (BO_H + 16384)
#define BO_RING_MLP (BO_W1 + 81920)
#define BO_BAR 229376
#define BO_BOX (BO_BAR + 256)
#define BO_CARRY (BO_BAR + 512)
#define B_SMEM (BO_CARRY + 2048 + 512)
static_assert(B_SMEM <= 232448 && BO_RING_OP + NS_OP * OP_SLOT == BO_BAR && BO_RING_MLP + 3 * 16384 == BO_BAR && 2 * 83968 <= BO_RING_MLP, "smem");
enum { BB_W = 0, BB_FULL = 2, BB_TMP = BB_FULL + 3, BB_OFULL = BB_FULL + 5, BB_SFREE = BB_OFULL,
       BB_SEEN = BB_SFREE + 6, BB_ZFREE, BB_DONE = BB_ZFREE + 3,
       BB_EMPTY, BB_START = BB_EMPTY, BB_USED = BB_EMPTY + 2, BB_NUM = BB_USED + 3 };
enum { NB_PP = 1, NB_H = 3, NB_END = 4, NB_END2 = 5, NB_STAGED = 6, NB_FREE = 8, NB_EARLY = 10, NB_LAST = 11 };

#define ACC32(d) ACC16(d), ACC16((d + 16))
#define R32S "{%0,%1,%2,%3,%4,%5,%6,%7,%8,%9,%10,%11,%12,%13,%14,%15,%16,%17,%18,%19,%20,%21,%22,%23,%24,%25,%26,%27,%28,%29,%30,%31}"
template <int N> struct BM;
#define DEF_BM(N, ACCM, RS_, I0, I1, I2, I3, I4, I5, I6)                                                                          \
  template <> struct BM<N> {                                                                                                      \
    template <int BO, int ACC> static __device__ __forceinline__ void rs(float* d, const uint32_t* a, uint32_t blo) {             \
      asm volatile("{\n.reg .b32 m;\n.reg .b64 b;\nadd.u32 m, %" #I4 ", %" #I5 ";\nmov.b64 b, {m, 0x40000040};\n"                 \
                   "wgmma.mma_async.sync.aligned.m64n" #N "k16.f32.bf16.bf16 " RS_ ", {%" #I0 ",%" #I1 ",%" #I2 ",%" #I3 "}, b, %" #I6 ", 1, 1, 0;\n}" \
                   : ACCM(d) : "r"(a[0]), "r"(a[1]), "r"(a[2]), "r"(a[3]), "r"(blo), "n"(BO), "n"(ACC)); }                        \
    template <int AO, int BO, int ACC> static __device__ __forceinline__ void ss(float* d, uint32_t alo, uint32_t blo) {          \
      asm volatile("{\n.reg .b32 l, m;\n.reg .b64 a, b;\nadd.u32 l, %" #I0 ", %" #I1 ";\nadd.u32 m, %" #I2 ", %" #I3 ";\n"        \
                   "mov.b64 a, {l, 0x40000040};\nmov.b64 b, {m, 0x40000040};\n"                                                   \
                   "wgmma.mma_async.sync.aligned.m64n" #N "k16.f32.bf16.bf16 " RS_ ", a, b, %" #I4 ", 1, 1, 1, 0;\n}"             \
                   : ACCM(d) : "r"(alo), "n"(AO), "r"(blo), "n"(BO), "n"(ACC)); }                                                 \
  };
DEF_BM(32, ACC16, R16S, 16, 17, 18, 19, 20, 21, 22)
DEF_BM(64, ACC32, R32S, 32, 33, 34, 35, 36, 37, 38)
#define DESC_LO(off) (((SMEM0 + (off)) >> 4) | (1u << 16))

__device__ __forceinline__ uint32_t ld_relaxed(const uint32_t* p) { uint32_t v; asm volatile("ld.relaxed.gpu.global.b32 %0, [%1];" : "=r"(v) : "l"(p) : "memory"); return v; }
__device__ __forceinline__ int fmask(int r) { return (r < NSEG) | ((r >= LAG && r < NSTEP) << 1); }
__device__ __forceinline__ int bmask(int r) { return (r <= NSEG) | ((r >= LAG) << 1); }
__device__ __forceinline__ uint32_t rtarget(int mask) { return mask == 3 ? 64 : 32; }
__device__ __forceinline__ void warp_signal(uint32_t* p, int lane) {
  __syncwarp();
  asm volatile("{\n.reg .pred q;\nsetp.eq.u32 q, %1, 0;\n@q red.release.gpu.global.add.u32 [%0], 1;\n}" :: "l"(p), "r"(lane) : "memory");
}
__device__ __forceinline__ uint32_t pack2h(float lo, float hi) { uint32_t r; asm("cvt.rn.f16x2.f32 %0, %1, %2;" : "=r"(r) : "f"(hi), "f"(lo)); return r; }
template <bool H> __device__ __forceinline__ uint32_t pk(float lo, float hi) { return H ? pack2h(lo, hi) : pack2(lo, hi); }
template <int N, bool H> __device__ __forceinline__ void stage_out(const float* d, uint32_t dst, int warp, int lane) {
  const uint32_t sa = dst + ((lane >> 4) * 8 + (lane & 7)) * 128 + (((2 * warp + ((lane >> 3) & 1)) ^ (lane & 7)) << 4);
#pragma unroll
  for (int m = 0; m < N / 16; m++)
    stsm4t(sa + m * 2048, pk<H>(d[8 * m], d[8 * m + 1]), pk<H>(d[8 * m + 2], d[8 * m + 3]), pk<H>(d[8 * m + 4], d[8 * m + 5]), pk<H>(d[8 * m + 6], d[8 * m + 7]));
}
template <int N> __device__ __forceinline__ void acc_live(float* d) {
#pragma unroll
  for (int i = 0; i < N / 2; i++) asm volatile("" : "+f"(d[i]) :: "memory");
}
struct Ring {
  uint32_t sl, ph;
  template <int NS> __device__ __forceinline__ void step() { if (++sl == NS) { sl = 0; ph ^= 1; } }
};

#define LOCKSTEP 1
#define KOFF(x) (((x) >> 2) * (N * 8) + ((x) & 3) * 2)
template <int N, int P>
__device__ __forceinline__ void op_pass(const uint32_t* W, uint32_t bar, uint32_t alo, uint32_t blo, uint32_t xlo, bool x2, Ring& rg, int wg, int warp, int lane, int r) {
  float acc[N / 2];
  const uint32_t tlo = DESC_LO(BO_RING_OP) + uni(rg.sl) * (OP_SLOT / 16);
  if (P == 0) mbar_waitu(bar + 8 * BB_OFULL, r & 1);
  CTS(5 * P);
  if (!LOCKSTEP || P > 1 || P == wg) bar_sync(NB_PP + wg, 256);
  wg_fence();
#define OP_R(x) BM<N>::template rs<KOFF(4 * (x >> 1) + (x & 1)), (x != 0)>(acc, W + 32 * P + 4 * x, blo);
#define OP_S(x) BM<N>::template ss<(6 * P + x) * 128, KOFF(4 * (x >> 1) + 2 + (x & 1)), 1>(acc, alo, blo);
#define OP_T(x) BM<N>::template ss<x * 128, KOFF(14 + x), 1>(acc, tlo, blo);
  OP_R(0) OP_S(0) OP_R(1) OP_S(1) OP_R(2) OP_S(2) OP_R(3) OP_S(3)
  if (P == 0) mbar_waitu(bar + 8 * (BB_OFULL + 1), r & 1);
  if (P == 4) wg_commit();
  OP_R(4) OP_S(4) OP_R(5) OP_S(5)
  if (P == 1 && x2) BM<N>::template ss<30 * 128, KOFF(20), 1>(acc, alo, xlo);
  if (P == 4) { wg_commit(); wg_wait<1>(); bar_arrive(NB_EARLY, 288); CTS(21); wg_fence(); }
  mbar_waitu(bar + 8 * (BB_FULL + rg.sl), rg.ph);
  OP_R(6) OP_T(0) OP_R(7) OP_T(1)
  if (P == 0) mbar_waitu(bar + 8 * (BB_OFULL + 2), r & 1);
  OP_T(2) OP_T(3)
  if (P == 0) BM<N>::template rs<KOFF(20), 1>(acc, W + 160, xlo);
  OP_T(4) OP_T(5)
  wg_commit();
  if (!LOCKSTEP || P) bar_arrive(NB_PP + 1 - wg, 256);
  CTS(5 * P + 2);
  bar_sync(NB_FREE + wg, 160);
  wg_wait<0>();
  acc_live<N>(acc);
  if (P == 4) bar_arrive(NB_LAST, 288);
  mbar_arrive_if(lane == 0, bar + 8 * (BB_USED + rg.sl));
  CTS(5 * P + 3);
  stage_out<N, false>(acc, SMEM0 + BO_STG + wg * 8192, warp, lane);
  bar_arrive(NB_STAGED + wg, 160);
  CTS(5 * P + 4);
  rg.step<NS_OP>(); rg.step<NS_OP>();
}
template <int N>
__device__ __forceinline__ void op_round(const uint32_t* W, uint32_t bar, uint32_t alo, uint32_t blo, uint32_t xlo, bool x2, Ring& rg, int wg, int warp, int lane, int r) {
  op_pass<N, 0>(W, bar, alo, blo, xlo, x2, rg, wg, warp, lane, r);
  op_pass<N, 1>(W, bar, alo, blo, xlo, x2, rg, wg, warp, lane, r);
  op_pass<N, 2>(W, bar, alo, blo, xlo, x2, rg, wg, warp, lane, r);
  op_pass<N, 3>(W, bar, alo, blo, xlo, x2, rg, wg, warp, lane, r);
  op_pass<N, 4>(W, bar, alo, blo, xlo, x2, rg, wg, warp, lane, r);
}
__device__ __forceinline__ void carry_in(uint32_t sb, int wg, int warp, int lane) {
  const int row = (lane >> 1) & 3;
  if (lane < 16) {
    const uint4 v = lds128(sb + BO_CARRY + (wg * 4 + warp) * 256 + lane * 16);
    sts128(sb + BO_H + wg * 8192 + (lane >> 3) * 4096 + row * 128 + (((2 * warp + (lane & 1)) ^ row) << 4), v.x, v.y, v.z, v.w);
  }
  __syncwarp();
}
template <int N, int Z>
__device__ __forceinline__ void p1_pair(float* acc, const uint32_t* W, uint32_t bar, uint32_t alo, uint32_t blo, int lane, int r) {
  mbar_waitu(bar + 8 * (BB_FULL + Z), r & 1);
  CTS(40 + Z);
  wg_fence();
#define P1_B(k) \
  BM<N>::template rs<(2 * Z % 3) * 1024 + k * 512, (2 * Z + k != 0)>(acc, W + 16 * Z + 8 * k, blo); \
  BM<N>::template ss<BO_W1 / 16 + (2 * Z + k) * 512, (2 * Z % 3) * 1024 + k * 512 + 4, 1>(acc, alo, blo); \
  BM<N>::template rs<(2 * Z % 3) * 1024 + k * 512 + 2, 1>(acc, W + 16 * Z + 8 * k + 4, blo); \
  BM<N>::template ss<BO_W1 / 16 + (2 * Z + k) * 512 + 128, (2 * Z % 3) * 1024 + k * 512 + 6, 1>(acc, alo, blo);
  P1_B(0)
  if (Z == 1 || Z == 2) { wg_commit(); wg_wait<1>(); mbar_arrive_if(lane == 0, bar + 8 * (BB_EMPTY + Z - 1)); wg_fence(); }
  P1_B(1)
  wg_commit();
}
template <int N>
__device__ __forceinline__ void phase1(const uint32_t* W, uint32_t sb, uint32_t alo, int half, int wg, int warp, int lane, int off, int r) {
  float acc[N / 2];
  const uint32_t bar = sb + BO_BAR, blo = DESC_LO(BO_RING_MLP) + half * 256;
  CTS(30);
  p1_pair<N, 0>(acc, W, bar, alo, blo, lane, r);
  p1_pair<N, 1>(acc, W, bar, alo, blo, lane, r);
  p1_pair<N, 2>(acc, W, bar, alo, blo, lane, r);
  p1_pair<N, 3>(acc, W, bar, alo, blo, lane, r);
  p1_pair<N, 4>(acc, W, bar, alo, blo, lane, r);
  carry_in(sb, wg, warp, lane);
  const int c = (lane >> 3) & 1, i0 = (lane >> 4) * 8 + (lane & 7) + off;
  uint32_t a0 = sb + BO_H + wg * 8192 + half * 4096 + i0 * 128 + (((2 * warp + c) ^ (i0 & 7)) << 4);
  uint32_t a1 = i0 >= 16 ? sb + BO_CARRY + (wg * 4 + warp) * 256 + half * 128 + (i0 - 16) * 32 + c * 16 : a0 + 2048, a3 = a1 + (i0 >= 16 ? 128 : 4096);
  asm volatile("" : "+r"(a0), "+r"(a1), "+r"(a3));
  wg_wait<0>();
  acc_live<N>(acc);
  CTS(32);
#pragma unroll
  for (int j = 0; j < N / 2; j++) acc[j] = gelu2(acc[j]);
#pragma unroll
  for (int m = 0; m < N / 16; m++)
    stsm4t(m == 1 ? a1 : m == 3 ? a3 : a0 + m * 2048, pack2(acc[8 * m], acc[8 * m + 1]), pack2(acc[8 * m + 2], acc[8 * m + 3]), pack2(acc[8 * m + 4], acc[8 * m + 5]), pack2(acc[8 * m + 6], acc[8 * m + 7]));
}
template <int N, int P>
__device__ __forceinline__ void p2_pass(const uint32_t* W, uint32_t bar, uint32_t alo, uint32_t blo, int wg, int warp, int lane, int r) {
  float acc[N / 2];
  CTS(5 * P);
  if (P || wg) bar_sync(NB_PP + wg, 256);
  wg_fence();
  BM<N>::template rs<0, 0>(acc, W + 80 + 16 * P, blo);      BM<N>::template ss<P * 1024, 512, 1>(acc, alo, blo);
  BM<N>::template rs<2, 1>(acc, W + 84 + 16 * P, blo);      BM<N>::template ss<P * 1024 + 128, 514, 1>(acc, alo, blo);
  BM<N>::template rs<4, 1>(acc, W + 88 + 16 * P, blo);      BM<N>::template ss<P * 1024 + 512, 516, 1>(acc, alo, blo);
  BM<N>::template rs<6, 1>(acc, W + 92 + 16 * P, blo);      BM<N>::template ss<P * 1024 + 640, 518, 1>(acc, alo, blo);
  wg_commit();
  if (P < 4 || !wg) bar_arrive(NB_PP + 1 - wg, 256);
  CTS(5 * P + 2);
  if (P >= 2) mbar_waitu(bar + 8 * (BB_SFREE + 2 * (P - 2) + wg), r & 1);
  wg_wait<0>();
  acc_live<N>(acc);
  CTS(5 * P + 3);
  stage_out<N, true>(acc, SMEM0 + BO_RING_MLP + (1 + (P & 1)) * 16384 + wg * 8192, warp, lane);
  bar_arrive(NB_STAGED + 2 * (P & 1) + wg, 160);
  CTS(5 * P + 4);
}
template <int N>
__device__ __forceinline__ void phase2(const uint32_t* W, uint32_t bar, uint32_t alo, uint32_t blo, int wg, int warp, int lane, int r) {
  p2_pass<N, 0>(W, bar, alo, blo, wg, warp, lane, r);
  p2_pass<N, 1>(W, bar, alo, blo, wg, warp, lane, r);
  p2_pass<N, 2>(W, bar, alo, blo, wg, warp, lane, r);
  p2_pass<N, 3>(W, bar, alo, blo, wg, warp, lane, r);
  p2_pass<N, 4>(W, bar, alo, blo, wg, warp, lane, r);
}

__device__ __forceinline__ void ldg4(uint32_t* v, const void* p) {
  asm volatile("ld.relaxed.gpu.global.v4.u32 {%0,%1,%2,%3}, [%4];" : "=r"(v[0]), "=r"(v[1]), "=r"(v[2]), "=r"(v[3]) : "l"(p) : "memory"); }
__device__ __forceinline__ void stg4(void* p, const uint32_t* v) {
  asm volatile("st.global.v4.u32 [%0], {%1,%2,%3,%4};" :: "l"(p), "r"(v[0]), "r"(v[1]), "r"(v[2]), "r"(v[3]) : "memory"); }
struct RowPtr {
  unsigned char *p, *q, *t;
  __device__ __forceinline__ void ld(uint32_t* v, int o) const {
    ldg4(v, p + o); ldg4(v + 4, q + o);
    asm volatile("ld.relaxed.gpu.global.v2.u32 {%0,%1}, [%2];" : "=r"(v[8]), "=r"(v[9]) : "l"(t + o) : "memory");
  }
  template <bool H> __device__ __forceinline__ void st(const float* v, float a, float b, int o) const {
    uint32_t w[10];
#pragma unroll
    for (int i = 0; i < 10; i++) w[i] = pk<H>(fmaf(v[2 * i], a, b), fmaf(v[2 * i + 1], a, b));
    stg4(p + o, w); stg4(q + o, w + 4);
    asm volatile("st.global.v2.u32 [%0], {%1,%2};" :: "l"(t + o), "r"(w[8]), "r"(w[9]) : "memory");
  }
};
__device__ __forceinline__ RowPtr row_img(int r, int n, int lane) {
  unsigned char* b = &g_acc[0][r % RD][n * 128];
  unsigned char* p = b + (uint32_t)((lane >> 3) * 8192 + (((lane ^ n) & 7) << 4));
  return {p, p + 32768, b + (uint32_t)(65536 + (lane >> 4) * 8192 + ((((lane >> 1) ^ n) & 7) << 4) + (lane & 1) * 8)};
}
__device__ __forceinline__ RowPtr row_ext(const void* lin, bool xn, int layer, int tok, int lane) {
  unsigned char* b = xn ? reinterpret_cast<unsigned char*>(&g_xn[layer][0]) + (uint32_t)((tok >> 5) * 40960 + ((tok >> 3) & 3) * 2560 + (tok & 7) * 16)
                        : (unsigned char*)lin + (uint32_t)(tok * 1280);
  return {b + (uint32_t)(xn ? lane * 128 + (lane >= 20 ? 7680 : 0) : lane * 16),
          b + (uint32_t)(xn ? lane * 128 + 4096 + 7680 + (lane >= 8 ? 7680 : 0) + (lane >= 28 ? 7680 : 0) : lane * 16 + 512),
          b + (uint32_t)(xn ? (lane >> 1) * 128 + (lane & 1) * 8 + 8192 + 3 * 7680 : lane * 8 + 1024)};
}
__device__ __forceinline__ float2 h2f(uint32_t w) {
  float2 f; asm("{\n.reg .f16 l, h;\nmov.b32 {l, h}, %2;\ncvt.f32.f16 %0, l;\ncvt.f32.f16 %1, h;\n}" : "=f"(f.x), "=f"(f.y) : "r"(w)); return f; }
__device__ __forceinline__ float rsq(float x) { float y; asm("rsqrt.approx.ftz.f32 %0, %1;" : "=f"(y) : "f"(x)); return y; }
__device__ __forceinline__ void red_if(uint32_t v, const void* a) {
  asm volatile("{\n.reg .pred q;\nsetp.ne.u32 q, %1, 0;\n@q red.relaxed.gpu.global.add.u32 [%0], %1;\n}" :: "l"(a), "r"(v) : "memory"); }
__device__ __forceinline__ uint32_t dep0(uint32_t w, int lane) { uint32_t z; asm volatile("shr.b32 %0, %1, %2;" : "=r"(z) : "r"(w), "r"(lane + 32)); return z; }
__device__ __forceinline__ int lane_of(uint32_t w) {
  int lane; asm volatile("{\n.reg .u32 t;\nmov.u32 t, %%laneid;\nshr.u32 %0, %1, 20;\nadd.u32 %0, %0, t;\n}" : "=r"(lane) : "r"(w)); return lane; }
#define BUF (RD * TILE_B)
#define GO_NAP 0
__device__ __forceinline__ int await(const uint32_t* p, uint32_t target, bool lazy) {
  int n = 0;
  uint32_t v;
  while (true) {
    v = ld_relaxed(p);
    if (__all_sync(~0u, v >= target)) break;
    if (lazy) __nanosleep(200); else if (GO_NAP) __nanosleep(GO_NAP);
    if (++n > SPIN_LIMIT) FAIL();
  }
  asm volatile("fence.acquire.gpu;" ::: "memory");
  return lane_of(v);
}
template <int W> __device__ __forceinline__ void sum2(float& s, float& q, int lane) {
  const bool up = lane & (W / 2);
  float e = (up ? q : s) + __shfl_xor_sync(~0u, up ? s : q, W / 2);
#pragma unroll
  for (int o = W / 4; o; o >>= 1) e += __shfl_xor_sync(~0u, e, o);
  const float f = __shfl_xor_sync(~0u, e, W / 2);
  s = up ? f : e; q = up ? e : f;
}
template <int TYPE>
__device__ __forceinline__ void rrow(int r, int row, int tok, int lane, const uint32_t* go, int role, const __nv_bfloat16* x) {
  const int half = TYPE ? 0 : row >> 5;
  float v[20];
  {
    float4 st = make_float4(1.f, 0.f, 0.f, 0.f);
    uint32_t a[10], c[10], u[10], sh = 16;
    if (TYPE == 2) row_img(r + RD - ((row & 31) < 2), (row & 32) + ((row - 2) & 31), lane).ld(u, 4 * BUF);
    else row_ext(x, half, 1, tok, lane).ld(u, 0);
    if (TYPE == 2 || (TYPE == 0 && half))
      asm volatile("ld.relaxed.gpu.global.v4.f32 {%0,%1,%2,%3}, [%4];" : "=f"(st.x), "=f"(st.y), "=f"(st.z), "=f"(st.w) : "l"(g_stat + tok) : "memory");
    RowPtr ap = row_img(r, row, lane);
    if (TYPE == 2) {
      ap.ld(c, 5 * BUF);
      sh |= dep0(c[9], lane);
      st.y += st.w;
#pragma unroll
      for (int i = 0; i < 10; i++) {
        v[2 * i] = fmaf(__uint_as_float(c[i] << sh), st.z, fmaf(__uint_as_float(u[i] << sh), st.x, st.y));
        v[2 * i + 1] = fmaf(__uint_as_float(c[i] & (0xffffu << sh)), st.z, fmaf(__uint_as_float(u[i] & (0xffffu << sh)), st.x, st.y));
        sh |= dep0(__float_as_uint(v[2 * i]) | __float_as_uint(v[2 * i + 1]), lane);
      }
    }
    if (TYPE != 3) {
      asm volatile("" : "+l"(ap.p), "+l"(ap.t));
      ap.q = ap.p + 32768;
      lane = await(go, NOP * NW12 * NW34, false); BTS2(r, 8 + 2 * TYPE); RTS(0);
      ap.ld(a, TYPE ? 3 * BUF : 0);
    }
    if (TYPE == 0) {
      ap.ld(c, BUF);
      const uint32_t one = 0x3f803f80u | dep0(c[9], lane);
#pragma unroll
      for (int i = 0; i < 10; i++) asm volatile("fma.rn.bf16x2 %0, %0, %1, %2;" : "+r"(a[i]) : "r"(one), "r"(c[i]));
      sh |= dep0(a[9], lane);
    }
    const float k = TYPE == 2 ? __uint_as_float(0x3f000000u | dep0(a[9], lane)) : 0.f;
#pragma unroll
    for (int i = 0; i < 10; i++) {
      if (TYPE == 2) { const float2 h = h2f(a[i]); v[2 * i] = fmaf(h.x, k, v[2 * i]); v[2 * i + 1] = fmaf(h.y, k, v[2 * i + 1]); continue; }
      float p = __uint_as_float(u[i] << sh), q = __uint_as_float(u[i] & (0xffffu << sh));
      if (TYPE == 0) { p = fmaf(p, st.x, st.y) + bf_lo(a[i]); q = fmaf(q, st.x, st.y) + bf_hi(a[i]); }
      v[2 * i] = p; v[2 * i + 1] = q;
    }
  }
  RTSD(1, v[19]);
  float rs, mr;
  {
    float s = 0.f, q = 0.f;
#pragma unroll
    for (int i = 0; i < 5; i++) {
      s += (v[4 * i] + v[4 * i + 1]) + (v[4 * i + 2] + v[4 * i + 3]);
      q += fmaf(v[4 * i], v[4 * i], v[4 * i + 1] * v[4 * i + 1]) + fmaf(v[4 * i + 2], v[4 * i + 2], v[4 * i + 3] * v[4 * i + 3]);
    }
    sum2<32>(s, q, lane);
    const float mean = s * (1.f / DM), var = fmaxf(q * (1.f / DM) - mean * mean, 0.f);
    rs = rsq(var + 1e-5f);
    float sd = (var + 1e-5f) * rs;
    RTSD(2, rs);
    if (TYPE == 0) {
      row_img(r + ((row & 31) >= 30), (row & 32) + ((row + 2) & 31), lane).st<true>(v, 2.f * rs, -2.f * mean * rs, 2 * BUF);
      const float v2 = fmaf(var * rs, rs, 1e-5f), r2 = rsq(v2);
      rs *= r2; sd *= v2 * r2;
    }
    mr = -mean * rs;
    if (TYPE != 3 && lane == 0) *reinterpret_cast<float2*>(g_stat + tok) = make_float2(sd, mean);
  }
  if (TYPE) row_ext(nullptr, true, TYPE == 2, tok, lane).template st<false>(v, rs, mr, 0);
  else row_img(r, row, lane).st<false>(v, rs, mr, 4 * BUF);
}
__device__ __forceinline__ void r2rows(int r, int row, int tok, int lane) {
  const int n = row + (lane >> 4);
  unsigned char* ap = &g_acc[2][r % RD][0] + (uint32_t)(n * 128 + ((lane >> 3) & 1) * 8192 + (((lane ^ n) & 7) << 4));
  uint32_t a[20];
#pragma unroll
  for (int i = 0; i < 5; i++) ldg4(a + 4 * i, ap + i * 16384);
  uint32_t z = dep0(a[19], lane);
  float s = 0.f, q = 0.f, q2 = 0.f;
#pragma unroll
  for (int i = 0; i < 20; i++) { const float2 h = h2f(a[i] | z); s += h.x + h.y; q = fmaf(h.x, h.x, q); q2 = fmaf(h.y, h.y, q2); }
  q += q2;
  RTSD(1, q);
  sum2<16>(s, q, lane);
  const float mean = s * (0.5f / DM), var = fmaxf(q * (0.25f / DM) - mean * mean, 0.f) + 1e-5f, rs = rsq(var), r2 = 0.5f * rs, mr = -mean * rs;
  RTSD(2, rs);
  z = dep0(__float_as_uint(rs), lane);
#pragma unroll
  for (int i = 0; i < 20; i++) { const float2 h = h2f(a[i] | z); a[i] = pack2(fmaf(h.x, r2, mr), fmaf(h.y, r2, mr)); }
#pragma unroll
  for (int i = 0; i < 5; i++) stg4(ap + 3 * BUF + i * 16384, a + 4 * i);
  if ((lane & 15) == 0) reinterpret_cast<float2*>(g_stat + tok + (lane >> 4))[1] = make_float2(var * rs, mean);
}
__device__ __forceinline__ void r3rows(int r, int row, int tok, int lane, __nv_bfloat16* out) {
  const int n = row + (lane >> 4), m = 32 + ((n - 2) & 31);
  const unsigned char* ap = &g_acc[0][r % RD][0] + (uint32_t)(n * 128 + ((lane >> 3) & 1) * 8192 + (((lane ^ n) & 7) << 4));
  const unsigned char* zp = &g_acc[4][(r + RD - (row == 32)) % RD][0] + (uint32_t)(m * 128 + ((lane >> 3) & 1) * 8192 + (((lane ^ m) & 7) << 4));
  unsigned char* op = reinterpret_cast<unsigned char*>(out) + (uint32_t)((tok + (lane >> 4)) * 1280 + (lane & 15) * 16);
  float4 st;
  asm volatile("ld.relaxed.gpu.global.v4.f32 {%0,%1,%2,%3}, [%4];" : "=f"(st.x), "=f"(st.y), "=f"(st.z), "=f"(st.w) : "l"(g_stat + tok + (lane >> 4)) : "memory");
#pragma unroll
  for (int i0 = 0; i0 < 5; i0 += 2) {
    uint32_t a[8], c[8], u[8];
#pragma unroll
    for (int i = 0; i < (i0 < 4 ? 2 : 1); i++) { ldg4(a + 4 * i, ap + 3 * BUF + (i0 + i) * 16384); ldg4(c + 4 * i, ap + 5 * BUF + (i0 + i) * 16384); ldg4(u + 4 * i, zp + (i0 + i) * 16384); }
    uint32_t z = dep0(u[i0 < 4 ? 7 : 3], lane);
#pragma unroll
    for (int i = 0; i < (i0 < 4 ? 8 : 4); i++) {
      const float2 h = h2f(a[i] | z);
      a[i] = pack2(fmaf(bf_lo(c[i] | z), st.z, fmaf(bf_lo(u[i] | z), st.x, fmaf(h.x, 0.5f, st.y + st.w))), fmaf(bf_hi(c[i] | z), st.z, fmaf(bf_hi(u[i] | z), st.x, fmaf(h.y, 0.5f, st.y + st.w))));
      if (i & 1) z = dep0(a[i], lane);
    }
#pragma unroll
    for (int i = 0; i < (i0 < 4 ? 2 : 1); i++) stg4(op + (i0 + i) * 256, a + 4 * i);
  }
}
template <int TYPE>
__device__ __forceinline__ void rloop(int row, int cp, int role, const __nv_bfloat16* x, __nv_bfloat16* out) {
  constexpr int ST = TYPE == 4 ? 2 : TYPE;
  const int r0 = row & 32 ? LAG : 0;
#pragma unroll 1
  for (int r = r0; r < r0 + NSEG + (TYPE > 0); r++) {
    const int tok = (r - r0) * 32 + (row & 31) - (TYPE ? 2 : 0);
    const bool valid = TYPE == 0 || (unsigned)tok < S_LEN;
    const uint32_t* go = &g_f[F_R1 + 4 * ST + cp][r];
    if constexpr (TYPE == 1 || TYPE == 4) {
      const int lane = await(go, NOP * NW12 * NW34, false);
      BTS2(r, 8 + 2 * ST); RTS(0);
      if (valid) { if (TYPE == 1) r2rows(r, row, tok, lane); else r3rows(r, row, tok, lane, out); }
    } else {
      if (TYPE || row >= 32) await(TYPE ? &g_f[F_Z1][r] : (const uint32_t*)&g_xready[NSEG + r - r0][0], TYPE ? rtarget(bmask(r)) : 32, true);
      if (valid) rrow<TYPE>(r, row, tok, lane_of(r), go, role, x);
    }
    const int lane = lane_of(r);
    const void* f = lane ? (const void*)&g_xready[NSEG + (tok >> 5)][0] : (const void*)&g_f[F_Z + ST][r];
    asm volatile("" : "+l"(f));
    __syncwarp();
    RTS(3);
    asm volatile("fence.release.gpu;" ::: "memory");
    RTS(4);
    red_if(lane == 0 || (TYPE == 2 && lane == 1 && valid) ? (TYPE & 5 ? 2 : 1) : 0, f);
    RTS(5);
    RTS_OUT();
    BTS2(r, 9 + 2 * ST);
  }
}

#define W_DELAY 0
#define BULK_ADD(T, dst, src, len) asm volatile("{\n.reg .pred e;\nelect.sync _|e, 0xffffffff;\n@e cp.reduce.async.bulk.global.shared::cta.bulk_group.add.noftz." T " [%0], [%1], %2;\n}" \
                                               :: "l"(dst), "r"(src), "r"(len) : "memory")
#define COMMIT() asm volatile("cp.async.bulk.commit_group;" ::: "memory")
#define DRAINED(n) do { asm volatile("cp.async.bulk.wait_group.read " #n ";" ::: "memory"); __syncwarp(); } while (0)
#define WRITTEN() do { asm volatile("cp.async.bulk.wait_group 0;\nfence.proxy.async.global;" ::: "memory"); __syncwarp(); } while (0)
__device__ __forceinline__ void wait_flags(const uint32_t* p, uint32_t target) {
  int n = 0;
  while (!__all_sync(~0u, ld_relaxed(p) >= target)) { if (++n > SPIN_LIMIT) FAIL(); }
  asm volatile("fence.acquire.gpu;" ::: "memory");
  asm volatile("fence.proxy.async.global;" ::: "memory");
}
__global__ void __launch_bounds__(512, 1) bworker_kernel(const __grid_constant__ BParams P) {
  extern __shared__ __align__(1024) unsigned char smem_raw[];
  const uint32_t sb = SMEM0, bar = sb + BO_BAR;
  const int wg = __shfl_sync(~0u, threadIdx.x >> 7, 0), warp = __shfl_sync(~0u, (threadIdx.x >> 5) & 3, 0);
  if (threadIdx.x == 0) {
    if (smem_u32(smem_raw) != SMEM0) FAIL();
    uint32_t smid; asm volatile("mov.u32 %0, %%smid;" : "=r"(smid));
    bool lone = ld_relaxed(&g_tpc[(smid >> 1) & 127]) == 0;
    if (lone && smid >= 64 && smid < 124 && atomicAdd(&g_f[F_MISC][34], 1u) == 0) lone = false;
    uint32_t i = atomicAdd(&g_f[F_MISC][lone ? 32 : 33], 1u);
    bool op = lone;
    if (i >= (lone ? NOP : NBC - NOP)) { op = !lone; i = atomicAdd(&g_f[F_MISC][op ? 32 : 33], 1u); }
    sts32(sb + BO_BOX, op ? i : NOP + i);
    for (int k = 0; k < BB_NUM; k++) mbar_init(bar + 8 * k, k >= BB_USED ? 4 : k >= BB_EMPTY ? 8 : k == BB_DONE && !op ? 3 : k >= BB_ZFREE ? 2 : 1);
    asm volatile("fence.mbarrier_init.release.cluster;" ::: "memory");
  }
  if (threadIdx.x < 128) sts128(sb + BO_CARRY + threadIdx.x * 16, 0u, 0u, 0u, 0u);
  fence_async();
  __syncthreads();
  const int role = uni(lds32(sb + BO_BOX));
  const bool op = role < NOP, w12 = role < NOP + NW12;
  const int j = op ? role : w12 ? role - NOP : role - NOP - NW12;
  const int rot = op ? (j ? 2 * ((j + 1) % 5) : 0) : 2 * (j % 5);
  if (wg == 3) {
    asm volatile("setmaxnreg.dec.sync.aligned.u32 24;");
    LANE_INIT();
    if (warp < 2) {
      if (op) {
        int mt = rot + warp;
        bar_arrive(NB_FREE + warp, 160);
#pragma unroll 1
        for (int r = 0; r < NSTEP; r++) {
          const uint32_t len = fmask(r) == 3 ? 8192 : 4096;
          unsigned char* acc = &g_acc[j & 1][r % RD][fmask(r) == 2 ? 4096 : 0];
#pragma unroll 1
          for (int p = 0; p < 5; p++) {
            bar_sync(NB_STAGED + warp, 160);
            PTS(50 + 2 * p + warp);
            fence_async();
            BULK_ADD("bf16", acc + mt * 8192, sb + BO_STG + warp * 8192, len);
            COMMIT();
            PTS(64 + 50 + 2 * p + warp);
            mt = mt >= 8 ? mt - 8 : mt + 2;
            DRAINED(0);
            bar_arrive(NB_FREE + warp, 160);
          }
          WRITTEN();
          mbar_arrive_if(lane == 0, bar + 8 * BB_DONE);
        }
      } else {
#pragma unroll 1
        for (int r = 0; r < NR; r++) {
          const uint32_t len = bmask(r) == 3 ? 8192 : 4096;
          unsigned char* acc = &g_acc[w12 ? 2 : 3][r % RD][bmask(r) == 2 ? 4096 : 0];
          int mt = rot + warp;
#pragma unroll 1
          for (int p = 0; p < 5; p++) {
            bar_sync(NB_STAGED + 2 * (p & 1) + warp, 160);
            PTS(50 + 2 * p + warp);
            fence_async();
            BULK_ADD("f16", acc + mt * 8192, sb + BO_RING_MLP + (1 + (p & 1)) * 16384 + warp * 8192, len);
            COMMIT();
            PTS(64 + 50 + 2 * p + warp);
            mt = mt >= 8 ? mt - 8 : mt + 2;
            DRAINED(1);
            mbar_arrive_if(lane == 0, bar + 8 * (p & 3 ? BB_SFREE + 2 * (p - 1) + warp : BB_ZFREE + (p >> 2)));
          }
          WRITTEN();
          mbar_arrive_if(lane < 2, bar + 8 * (BB_ZFREE + 2 + lane));
        }
      }
    } else {
      auto clear = [&](int r) {
#pragma unroll 1
        for (int c = j; c < (op && r + 1 < NSTEP ? 40 : 80); c += op ? NOP : NW34)
          bulk_s2g_e(&g_acc[op ? 3 : c / 40][(r + (op ? c / 40 : 0)) % RD][c % 40 * 2048], sb + BO_CARRY, 2048);
        COMMIT();
      };
      auto announce = [&](int r) {
        const uint32_t* f = &g_f[(op ? F_R1 : w12 ? F_R2 : F_R3) + (lane & 3)][r];
        asm volatile("" : "+l"(f));
        mbar_waitw(bar + 8 * BB_DONE, r & 1);
        PTS(60);
        asm volatile("fence.release.gpu;" ::: "memory");
        red_if(lane >= 4 ? 0 : op ? NW12 * NW34 : w12 ? NOP * NW34 : NOP * NW12, f);
        PTS(61);
        BTS(r, 4);
      };
      if (op && warp == 2) {
        unsigned char* wt = g_wt + j * (10 * OP_SLOT);
#pragma unroll 1
        for (int m0 = 0; m0 < 10; m0 += 3) {
          const int nu = m0 < 9 ? 9 : 3;
          mbar_expect_if(lane == 0, bar + 8 * BB_TMP, nu * 4096);
#pragma unroll 1
          for (int k = 0; k < nu; k++) tma2d_e(sb + BO_RING_OP + k * 4096, &P.wmap[0], (m0 + k / 3) * 64, 320 * j + 224 + 32 * (k % 3), bar + 8 * BB_TMP);
          mbar_waitw(bar + 8 * BB_TMP, m0 & 1);
          bulk_s2g_e(wt + m0 * OP_SLOT, sb + BO_RING_OP, nu * 4096);
          COMMIT();
          WRITTEN();
        }
        asm volatile("fence.acq_rel.gpu;" ::: "memory");
        int sl = 0, ph = 1, mt = rot;
#pragma unroll 1
        for (int r = -1; r < NSTEP; r++) {
#pragma unroll 1
          for (int n = r < 0 ? 7 : 0; n < (r + 1 < NSTEP ? 10 : 7); n++) {
            mbar_waitw(bar + 8 * (BB_USED + sl), ph);
            mbar_expect_if(lane == 0, bar + 8 * (BB_FULL + sl), OP_SLOT);
            bulk_g2s_e(sb + BO_RING_OP + sl * OP_SLOT, wt + mt * OP_SLOT, OP_SLOT, bar + 8 * (BB_FULL + sl));
            if (++sl == 3) { sl = 0; ph ^= 1; }
            mt = mt == 9 ? 0 : mt + 1;
            if (n == 1) clear(r);
          }
          if (r >= 0) { WRITTEN(); announce(r); }
        }
      } else if (op) {
        mbar_waitw(bar + 8 * BB_START, 0);
#pragma unroll 1
        for (int r = 0; r < NSTEP; r++) {
          const int rb = r - RD + 1;
          const uint32_t len = fmask(r) == 3 ? 8192 : 4096;
          const unsigned char* src = g_o + (uint32_t)(r * (96 * 8192) + 5 * j * len);
          wait_flags(lane < 2 ? &g_f[F_O + (lane ? NOP : j)][r] : rb >= 0 ? &g_f[F_DONE][rb] : &g_f[F_MISC][0],
                     lane < 2 ? (lane ? 1 : 5) : rb >= 0 ? rtarget(bmask(rb)) : NBC * 8);
          PTS1(35);
          if (r) bar_sync(NB_EARLY, 288);
          if (r == LAG) bar_sync(NB_LAST, 288);
          mbar_expect_if(lane < 3, bar + 8 * (BB_OFULL + lane), 2 * len);
          bulk_g2s_e(sb + BO_O, src, 2 * len, bar + 8 * BB_OFULL);
          PTS(62); PTS1(38);
          if (r && r != LAG) bar_sync(NB_LAST, 288);
          bulk_g2s_e(sb + BO_O + 2 * len, src + 2 * len, 2 * len, bar + 8 * (BB_OFULL + 1));
          bulk_g2s_e(sb + BO_O + 4 * len, src + 4 * len, len, bar + 8 * (BB_OFULL + 2));
          bulk_g2s_e(sb + BO_O + 5 * len, src + (95 - 5 * j) * len, len, bar + 8 * (BB_OFULL + 2));
          PTS1(64 + 35);
          BTS(r, 0);
        }
      } else if (warp == 2) {
#pragma unroll 1
        for (int r = 0; r < NR; r++) {
          const int mk = w12 ? fmask(r) : bmask(r);
          if (mk) {
            const unsigned char* src = &g_acc[w12 ? 4 : 5][r % RD][mk == 2 ? 4096 : 0];
            wait_flags(&g_f[w12 ? F_Z : F_Z1][r], rtarget(mk));
#pragma unroll 1
            for (int z = 0; z < 5; z++) {
              const uint32_t fb = bar + 8 * (BB_FULL + z), dst = sb + BO_RING_MLP + 2 * z % 3 * 16384 + (mk == 2 ? 4096 : 0);
              mbar_waitw(bar + 8 * (z < 3 ? BB_ZFREE + z : BB_EMPTY + z - 3), (r + (z < 3)) & 1);
              if (z == 0) PTS(62);
              mbar_expect_if(lane == 0, fb, mk == 3 ? 16384 : 8192);
              bulk_g2s_e(dst, src + z * 16384, mk == 3 ? 16384 : 4096, fb);
              if (mk != 3) bulk_g2s_e(dst + 8192, src + z * 16384 + 8192, 4096, fb);
              if (z == 0) BTS(r, 0);
            }
          }
          if (!w12) { clear(r); WRITTEN(); }
          mbar_waitw(bar + 8 * BB_SEEN, (r + 1) & 1);
          mbar_arrive_if(lane == 0, bar + 8 * BB_DONE);
        }
      } else {
#pragma unroll 1
        for (int r = 0; r < NR; r++) { announce(r); mbar_arrive_if(lane == 0, bar + 8 * BB_SEEN); }
      }
    }
    bar_arrive(NB_END, 512);
  } else if (wg == 2) {
    asm volatile("setmaxnreg.dec.sync.aligned.u32 40;");
#define RMAP 2
    const int ord = op ? (j < 15 ? 9 + j : 17 + j) : w12 ? j : j < 4 ? 5 + j : 20 + j;
    const int gw = RMAP == 1 ? ord * 4 + warp : RMAP == 2 ? (op ? 68 + warp * NOP + role : warp * 17 + role - NOP) : warp * NBC + role, row = gw < 64 ? gw : gw < 96 ? gw - 64 : gw < 128 ? 2 * gw - 192 : 2 * gw - 224;
#pragma unroll 1
    for (int t = gw; t < S_LEN; t = row < 32 ? S_LEN : t < 4 * NBC ? 4 * NBC + (gw < 64 ? gw - 32 : gw - 80) : t + 64) {
      const int lane = lane_of(t);
      rrow<3>(0, 0, t, lane, nullptr, role, P.x);
      __syncwarp();
      asm volatile("fence.release.gpu;" ::: "memory");
      red_if(lane == 0, &g_xready[t >> 5][0]);
    }
    if (gw < 64) rloop<0>(row, gw & 3, role, P.x, P.out);
    else if (gw < 96) rloop<2>(row, gw & 3, role, P.x, P.out);
    else if (gw < 128) rloop<1>(row, gw & 3, role, P.x, P.out);
    else rloop<4>(row, gw & 3, role, P.x, P.out);
    asm volatile("griddepcontrol.wait;" ::: "memory");
    const int t = threadIdx.x & 127;
    for (int i = (blockIdx.x * 128 + t) * 4; i < 4 * NCL * 2560; i += NBC * 512)
      *reinterpret_cast<uint4*>(&g_part[0][0][0][0] + i) = make_uint4(0u, 0u, 0u, 0u);
    bar_sync(NB_END, 512);
    if (t == 0) {
      uint32_t n;
      asm volatile("atom.acq_rel.gpu.global.add.u32 %0, [%1], 1;" : "=r"(n) : "l"(&g_f[F_MISC][64]) : "memory");
      sts32(sb + BO_BOX, n);
    }
    bar_sync(NB_END2, 128);
    if (lds32(sb + BO_BOX) == NBC - 1) {
      for (int i = t; i < F_NUM * 24; i += 128) reinterpret_cast<uint4*>(&g_f[0][0])[i] = make_uint4(0u, 0u, 0u, 0u);
      g_xready[t][0] = 0; g_tpc[t] = 0;
    }
  } else {
    asm volatile("setmaxnreg.inc.sync.aligned.u32 224;");
    LANE_INIT();
    for (int i = blockIdx.x * 256 + threadIdx.x; i < 2 * RD * TILE_B / 16; i += NBC * 256) reinterpret_cast<uint4*>(&g_acc[0][0][0])[i] = make_uint4(0u, 0u, 0u, 0u);
    warp_signal(&g_f[F_MISC][0], lane);
    const int mt0 = (rot + wg) % 10;
    auto boxes = [&](int ss) {
      const int nb = op && ss ? 3 : 4;
      const uint32_t base = sb + (ss ? BO_RES + wg * OP_RES : wg * 83968);
      mbar_expect_if(warp == 0 && lane == 0, bar + 8 * (BB_W + wg), nb * 20480 + (op ? 2048 : 0));
      bar_sync(NB_H, 256);
      if (warp < nb) {
#pragma unroll 1
        for (int i = warp; i < 5 * nb; i += nb) {
          const int p = op ? i / nb : (i - 10) >> 1, mt = (mt0 + 2 * p) % 10;
          const bool first = !op && i < 10;
          tma2d_e(op || !ss ? base + i * 4096 : sb + (first ? BO_W1 : -81920) + (2 * i + wg) * 4096, &P.wmap[op ? 0 : (w12 ? 1 : 3) + !first], first ? 128 * j + 64 * wg : mt * 64,
                  op ? 320 * j + 64 * warp + 32 * ss : first ? 64 * i + 32 * ss : 128 * j + 32 * (i & 1) + 64 * ss, bar + 8 * (BB_W + wg));
        }
      }
      if (op && warp == 3) tma2d_e(base + nb * 20480, &P.wo16, (mt0 + 2 * ss) % 10 * 64, 95 * 64 + (j + 1) / 5 * 16, bar + 8 * (BB_W + wg));
      mbar_waitw(bar + 8 * (BB_W + wg), ss);
    };
    if (W_DELAY) __nanosleep(W_DELAY);
    uint32_t W[164];
    boxes(0);
    load_w<41>(W, sb + wg * 83968, warp, lane);
    fence_async();
    boxes(1);
    const uint32_t alo = uni((SMEM0 + (op ? BO_RES + wg * OP_RES : wg * 4096)) >> 4);
    if (op) {
      Ring rg = {(uint32_t)wg, 0};
      mbar_arrive_if(lane == 0, bar + 8 * BB_START);
      if (wg) bar_arrive(NB_PP, 256);
      const uint32_t blo = DESC_LO(BO_O), xlo = blo + (j + 1) / 5 * 2;
#pragma unroll 1
      for (int r = 0; r < NSTEP; r++) {
        asm volatile("" : "+r"(lane));
        if (fmask(r) == 3) op_round<64>(W, bar, alo, blo, xlo, j == 0, rg, wg, warp, lane, r);
        else op_round<32>(W, bar, alo, blo, xlo, j == 0, rg, wg, warp, lane, r);
        if (warp == 0) BTS(r, 2 + wg);
      }
    } else {
      const int q4 = (128 * j + 64 * wg + 16 * warp) / 160, off = w12 ? (0x0413 >> (4 * q4)) & 7 : 0;
#pragma unroll 1
      for (int r = 0; r < NR; r++) {
        asm volatile("" : "+r"(lane));
        const int bm = bmask(r), fm = w12 ? fmask(r) : bm;
        if (fm == 3) phase1<64>(W, sb, alo, 0, wg, warp, lane, off, r);
        else if (fm) phase1<32>(W, sb, alo, fm >> 1, wg, warp, lane, off, r);
        else { mbar_waitu(bar + 8 * BB_DONE, (r - 1) & 1); carry_in(sb, wg, warp, lane); }
        CTS(33);
        fence_async();
        bar_sync(NB_H, 256);
        if (wg + warp == 0) BTS(r, 1);
        if (bm == 3) phase2<64>(W, bar, alo, DESC_LO(BO_H), wg, warp, lane, r);
        else phase2<32>(W, bar, alo, uni(DESC_LO(BO_H) + (bm >> 1) * 256), wg, warp, lane, r);
        if (warp == 0) BTS(r, 2 + wg);
      }
    }
    CTS_OUT();
    bar_arrive(NB_END, 512);
  }
}

typedef CUresult (*EncodeFn)(CUtensorMap*, CUtensorMapDataType, cuuint32_t, void*, const cuuint64_t*, const cuuint64_t*, const cuuint32_t*,
                             const cuuint32_t*, CUtensorMapInterleave, CUtensorMapSwizzle, CUtensorMapL2promotion, CUtensorMapFloatOOBfill);
static void make_map(EncodeFn fn, CUtensorMap* tm, const void* ptr, uint64_t cols, uint64_t rows, uint32_t bc, uint32_t br) {
  cuuint64_t dims[2] = {cols, rows}; cuuint64_t strides[1] = {cols * 2}; cuuint32_t box[2] = {bc, br}; cuuint32_t es[2] = {1, 1};
  fn(tm, CU_TENSOR_MAP_DATA_TYPE_BFLOAT16, 2, const_cast<void*>(ptr), dims, strides, box, es, CU_TENSOR_MAP_INTERLEAVE_NONE,
     CU_TENSOR_MAP_SWIZZLE_128B, CU_TENSOR_MAP_L2_PROMOTION_L2_256B, CU_TENSOR_MAP_FLOAT_OOB_FILL_NONE);
}
extern "C" void kernel_launch(void* const* d_in, const int* in_sizes, int n_in, void* d_out, int out_size) {
  void* fnp = nullptr; cudaDriverEntryPointQueryResult qr;
  cudaGetDriverEntryPoint("cuTensorMapEncodeTiled", &fnp, cudaEnableDefault, &qr);
  EncodeFn fn = (EncodeFn)fnp;
  cudaStream_t st = cudaStreamPerThread;
  cudaFuncSetAttribute(bworker_kernel, cudaFuncAttributeMaxDynamicSharedMemorySize, B_SMEM);
  {
    AMaps M;
    for (int i = 0; i < 3; i++) make_map(fn, &M.w16[i], d_in[2 + i], HD, DM, 64, 16);
    make_map(fn, &M.wo32, d_in[5], DM, HD, 64, 32);
    cudaFuncSetAttribute(acore_kernel, cudaFuncAttributeMaxDynamicSharedMemorySize, A_SMEM);
    cudaFuncSetAttribute(acore_kernel, cudaFuncAttributeNonPortableClusterSizeAllowed, 1);
    cudaLaunchConfig_t cfg = {};
    cfg.gridDim = dim3(CL_SIZE * NCL); cfg.blockDim = dim3(512); cfg.dynamicSmemBytes = A_SMEM; cfg.stream = st;
    cudaLaunchAttribute at[1]; at[0].id = cudaLaunchAttributeClusterDimension;
    at[0].val.clusterDim.x = CL_SIZE; at[0].val.clusterDim.y = 1; at[0].val.clusterDim.z = 1;
    cfg.attrs = at; cfg.numAttrs = 1;
    cudaLaunchKernelEx(&cfg, acore_kernel, M, (const __nv_bfloat16*)d_in[1], 1);
  }
  {
    BParams P;
    make_map(fn, &P.wmap[0], d_in[5], DM, HD, 64, 32);
    make_map(fn, &P.wo16, d_in[5], DM, HD, 64, 16);
    make_map(fn, &P.wmap[1], d_in[8], DM, DM, 64, 32);
    make_map(fn, &P.wmap[2], d_in[9], DM, DM, 64, 32);
    make_map(fn, &P.wmap[3], d_in[10], FF, DM, 64, 32);
    make_map(fn, &P.wmap[4], d_in[11], DM, FF, 64, 32);
    P.x = (const __nv_bfloat16*)d_in[0];
    P.out = (__nv_bfloat16*)d_out;
    cudaLaunchConfig_t cfg = {};
    cfg.gridDim = dim3(NBC); cfg.blockDim = dim3(512); cfg.dynamicSmemBytes = B_SMEM; cfg.stream = st;
    cudaLaunchAttribute at[1]; at[0].id = cudaLaunchAttributeProgrammaticStreamSerialization; at[0].val.programmaticStreamSerializationAllowed = 1;
    cfg.attrs = at; cfg.numAttrs = 1;
    cudaLaunchKernelEx(&cfg, bworker_kernel, P);
  }
}
```

```cpp
#include <cuda_runtime.h>
#include <cuda_bf16.h>
#include <cuda.h>
#include <stdint.h>

#define S_LEN 2048
#define DM 640
#define NH 32
#define DH 192
#define HD 6144
#define NSEG 64
#define FF 1536

__device__ __forceinline__ uint32_t smem_u32(const void* p) { return (uint32_t)__cvta_generic_to_shared(p); }
__device__ __forceinline__ uint32_t mapa(uint32_t a, uint32_t r) {
  uint32_t o; asm volatile("mapa.shared::cluster.u32 %0, %1, %2;" : "=r"(o) : "r"(a), "r"(r)); return o; }
__device__ __forceinline__ void mbar_init(uint32_t b, uint32_t c) {
  asm volatile("mbarrier.init.shared::cta.b64 [%0], %1;" :: "r"(b), "r"(c) : "memory"); }
__device__ __forceinline__ void mbar_expect(uint32_t b, uint32_t tx) {
  asm volatile("mbarrier.arrive.expect_tx.shared::cta.b64 _, [%0], %1;" :: "r"(b), "r"(tx) : "memory"); }
__device__ __forceinline__ void mbar_arrive(uint32_t b) {
  asm volatile("mbarrier.arrive.shared::cta.b64 _, [%0];" :: "r"(b) : "memory"); }
__device__ __forceinline__ void mbar_arrive_remote(uint32_t rb) {
  asm volatile("mbarrier.arrive.relaxed.cluster.shared::cluster.b64 _, [%0];" :: "r"(rb) : "memory"); }
__device__ __forceinline__ void mbar_expect_if(bool p, uint32_t b, uint32_t tx) {
  asm volatile("{\n.reg .pred q;\nsetp.ne.u32 q, %2, 0;\n@q mbarrier.arrive.expect_tx.shared::cta.b64 _, [%0], %1;\n}" :: "r"(b), "r"(tx), "r"((uint32_t)p) : "memory"); }
__device__ __forceinline__ void mbar_arrive_if(bool p, uint32_t b) {
  asm volatile("{\n.reg .pred q;\nsetp.ne.u32 q, %1, 0;\n@q mbarrier.arrive.shared::cta.b64 _, [%0];\n}" :: "r"(b), "r"((uint32_t)p) : "memory"); }
__device__ __forceinline__ void mbar_arrive_remote_if(bool p, uint32_t rb) {
  asm volatile("{\n.reg .pred q;\nsetp.ne.u32 q, %1, 0;\n@q mbarrier.arrive.relaxed.cluster.shared::cluster.b64 _, [%0];\n}" :: "r"(rb), "r"((uint32_t)p) : "memory"); }
__device__ __forceinline__ void sts32_if(bool p, uint32_t a, uint32_t v) {
  asm volatile("{\n.reg .pred q;\nsetp.ne.u32 q, %2, 0;\n@q st.shared.b32 [%0], %1;\n}" :: "r"(a), "r"(v), "r"((uint32_t)p) : "memory"); }
__device__ __forceinline__ void sts128z_if(bool p, uint32_t a) {
  asm volatile("{\n.reg .pred q;\nsetp.ne.u32 q, %1, 0;\n@q st.shared.v4.b32 [%0], {0,0,0,0};\n}" :: "r"(a), "r"((uint32_t)p) : "memory"); }
__device__ __forceinline__ bool mbar_try(uint32_t b, uint32_t ph) {
  uint32_t ok;
  asm volatile("{\n.reg .pred p;\nmbarrier.try_wait.parity.shared::cta.b64 p, [%1], %2;\nselp.u32 %0, 1, 0, p;\n}"
               : "=r"(ok) : "r"(b), "r"(ph) : "memory");
  return ok; }
__device__ __forceinline__ bool mbar_test(uint32_t b, uint32_t ph) {
  uint32_t ok;
  asm volatile("{\n.reg .pred p;\nmbarrier.test_wait.parity.shared::cta.b64 p, [%1], %2;\nselp.u32 %0, 1, 0, p;\n}"
               : "=r"(ok) : "r"(b), "r"(ph) : "memory");
  return ok; }
#define SPIN_LIMIT 4000000
#define FAIL() asm volatile("st.global.u32 [%0], 0;" :: "l"(8ull) : "memory")
#define CFENCE() asm volatile("fence.proxy.async::generic.acquire.sync_restrict::shared::cluster.cluster;" ::: "memory")
__device__ __forceinline__ void mbar_wait(uint32_t b, uint32_t ph) {
  int n = 0;
  while (!mbar_try(b, ph)) { if (++n > SPIN_LIMIT) FAIL(); } }
#define TIMEOUT_ACT "@!p st.shared.u32 [%0+1], 0;"
#define WAIT_HINT ", 20000"
#define WAIT_LIM "200000"
__device__ __forceinline__ void mbar_slow(uint32_t b, uint32_t ph) {
  asm volatile("{\n.reg .pred p, q;\n.reg .u32 n;\nmov.u32 n, 0;\n"
               "WL:\nmbarrier.try_wait.parity.shared::cta.b64 p, [%0], %1" WAIT_HINT ";\nadd.u32 n, n, 1;\nsetp.lt.and.u32 q, n, " WAIT_LIM ", !p;\n@q bra.uni WL;\n"
               TIMEOUT_ACT "\n}" :: "r"(b), "r"(ph) : "memory"); }
__device__ __forceinline__ void mbar_waitw(uint32_t b, uint32_t ph) {
  asm volatile("{\n.reg .pred p, q;\n.reg .u32 n;\nmbarrier.try_wait.parity.shared::cta.b64 p, [%0], %1;\n@p bra.uni WD;\nmov.u32 n, 0;\n"
               "WL:\nmbarrier.try_wait.parity.shared::cta.b64 p, [%0], %1" WAIT_HINT ";\nadd.u32 n, n, 1;\nsetp.lt.and.u32 q, n, " WAIT_LIM ", !p;\n@q bra.uni WL;\n"
               TIMEOUT_ACT "\nWD:\n}" :: "r"(b), "r"(ph) : "memory"); }
__device__ __forceinline__ void mbar_waitw2(uint32_t b0, uint32_t b1, uint32_t ph) {
  uint32_t ok;
  asm volatile("{\n.reg .pred p, r;\nmbarrier.try_wait.parity.shared::cta.b64 p, [%1], %3;\nmbarrier.try_wait.parity.shared::cta.b64 r, [%2], %3;\n"
               "and.pred p, p, r;\nselp.u32 %0, 1, 0, p;\n}" : "=r"(ok) : "r"(b0), "r"(b1), "r"(ph) : "memory");
  if (__builtin_expect(!__all_sync(~0u, ok), 0)) { mbar_slow(b0, ph); mbar_slow(b1, ph); }
}
__device__ __forceinline__ void mbar_waitu(uint32_t b, uint32_t ph) {
  asm volatile("{\n.reg .pred p;\nmbarrier.try_wait.parity.shared::cta.b64 p, [%0], %1;\n@p bra.uni WD;\n"
               "WL:\nmbarrier.try_wait.parity.shared::cta.b64 p, [%0], %1" WAIT_HINT ";\n@!p bra.uni WL;\nWD:\n}" :: "r"(b), "r"(ph) : "memory"); }
__device__ __forceinline__ void mbar_waitu2(uint32_t b0, uint32_t b1, uint32_t ph) {
  asm volatile("{\n.reg .pred p, r;\nWL:\nmbarrier.try_wait.parity.shared::cta.b64 p, [%0], %2;\nmbarrier.try_wait.parity.shared::cta.b64 r, [%1], %2;\n"
               "and.pred p, p, r;\n@!p bra.uni WL;\n}" :: "r"(b0), "r"(b1), "r"(ph) : "memory"); }
__device__ __forceinline__ void mbar_waitw4(uint32_t b, uint32_t ph) { mbar_waitw2(b, b + 8, ph); mbar_waitw2(b + 16, b + 24, ph); }
__device__ __forceinline__ uint32_t clock32() { uint32_t t; asm volatile("mov.u32 %0, %%clock;" : "=r"(t) :: "memory"); return t; }
template <int L> __device__ __forceinline__ uint32_t lop3(uint32_t a, uint32_t b, uint32_t c) {
  uint32_t r; asm("lop3.b32 %0, %1, %2, %3, %4;" : "=r"(r) : "r"(a), "r"(b), "r"(c), "n"(L)); return r; }
__device__ __forceinline__ void st_async_v2_if(bool p, uint32_t a, uint32_t v0, uint32_t v1, uint32_t mb) {
  asm volatile("{\n.reg .pred q;\nsetp.ne.u32 q, %4, 0;\n@q st.async.weak.shared::cluster.mbarrier::complete_tx::bytes.v2.b32 [%0], {%1,%2}, [%3];\n}"
               :: "r"(a), "r"(v0), "r"(v1), "r"(mb), "r"((uint32_t)p) : "memory"); }
__device__ __forceinline__ void keep4(const uint32_t* r, int lane) {
  asm volatile("{\n.reg .pred q;\nsetp.lt.s32 q, %4, 0;\n@q st.shared.v4.b32 [%4], {%0,%1,%2,%3};\n}" :: "r"(r[0]), "r"(r[1]), "r"(r[2]), "r"(r[3]), "r"(lane) : "memory"); }
__device__ __forceinline__ uint32_t uni(uint32_t x) { return __shfl_sync(~0u, x, 0); }
__device__ __forceinline__ void bulk_g2s_mc_e(uint32_t dst, const void* src, uint32_t bytes, uint32_t mb, uint16_t mask) {
  asm volatile("{\n.reg .pred e;\nelect.sync _|e, 0xffffffff;\n"
               "@e cp.async.bulk.shared::cluster.global.mbarrier::complete_tx::bytes.multicast::cluster [%0], [%1], %2, [%3], %4;\n}"
               :: "r"(dst), "l"(src), "r"(bytes), "r"(mb), "h"(mask) : "memory"); }
__device__ __forceinline__ void bulk_s2g_e(void* dst, uint32_t src, uint32_t bytes) {
  asm volatile("{\n.reg .pred e;\nelect.sync _|e, 0xffffffff;\n@e cp.async.bulk.global.shared::cta.bulk_group [%0], [%1], %2;\n}"
               :: "l"(dst), "r"(src), "r"(bytes) : "memory"); }
__device__ __forceinline__ void bulk_g2s_e(uint32_t dst, const void* src, uint32_t bytes, uint32_t mb) {
  asm volatile("{\n.reg .pred e;\nelect.sync _|e, 0xffffffff;\n@e cp.async.bulk.shared::cluster.global.mbarrier::complete_tx::bytes [%0], [%1], %2, [%3];\n}"
               :: "r"(dst), "l"(src), "r"(bytes), "r"(mb) : "memory"); }
#define STREAM_HINT 1
__device__ __forceinline__ void bulk_s2g_es(void* dst, uint32_t src, uint32_t bytes) {
  asm volatile("{\n.reg .pred e;\n.reg .b64 pol;\ncreatepolicy.fractional.L2::evict_first.b64 pol;\nelect.sync _|e, 0xffffffff;\n"
               "@e cp.async.bulk.global.shared::cta.bulk_group.L2::cache_hint [%0], [%1], %2, pol;\n}" :: "l"(dst), "r"(src), "r"(bytes) : "memory");
}
__device__ __forceinline__ void bulk_g2s_es(uint32_t dst, const void* src, uint32_t bytes, uint32_t mb) {
  asm volatile("{\n.reg .pred e;\n.reg .b64 pol;\ncreatepolicy.fractional.L2::evict_first.b64 pol;\nelect.sync _|e, 0xffffffff;\n"
               "@e cp.async.bulk.shared::cluster.global.mbarrier::complete_tx::bytes.L2::cache_hint [%0], [%1], %2, [%3], pol;\n}"
               :: "r"(dst), "l"(src), "r"(bytes), "r"(mb) : "memory"); }
__device__ __forceinline__ void tma2d_e(uint32_t dst, const CUtensorMap* tm, int c0, int c1, uint32_t mb) {
  asm volatile("{\n.reg .pred e;\nelect.sync _|e, 0xffffffff;\n"
               "@e cp.async.bulk.tensor.2d.shared::cluster.global.mbarrier::complete_tx::bytes [%0], [%1, {%3, %4}], [%2];\n}"
               :: "r"(dst), "l"((uint64_t)tm), "r"(mb), "r"(c0), "r"(c1) : "memory"); }
__device__ __forceinline__ uint32_t hadd2bf(uint32_t a, uint32_t b) {
  uint32_t r; asm("add.rn.bf16x2 %0, %1, %2;" : "=r"(r) : "r"(a), "r"(b)); return r; }
__device__ __forceinline__ void cluster_sync_all() {
  asm volatile("barrier.cluster.arrive.release.aligned;\nbarrier.cluster.wait.acquire.aligned;" ::: "memory"); }
__device__ __forceinline__ void bar_arrive(int id, int n) { asm volatile("bar.arrive %0, %1;" :: "r"(id), "r"(n) : "memory"); }
__device__ __forceinline__ void bar_arrive_dep(int id, int n, uint32_t dep) {
  asm volatile("{\n.reg .u32 t;\nand.b32 t, %2, 0;\nadd.u32 t, t, %0;\nbar.sync t, %1;\n}" :: "r"(id), "r"(n), "r"(dep) : "memory"); }
__device__ __forceinline__ void bar_sync(int id, int n) { asm volatile("bar.sync %0, %1;" :: "r"(id), "r"(n) : "memory"); }
__device__ __forceinline__ void fence_async() { asm volatile("fence.proxy.async.shared::cta;" ::: "memory"); }
__device__ __forceinline__ void st_async_b32(uint32_t a, uint32_t v, uint32_t mb) {
  asm volatile("st.async.weak.shared::cluster.mbarrier::complete_tx::bytes.b32 [%0], %1, [%2];" :: "r"(a), "r"(v), "r"(mb) : "memory"); }
__device__ __forceinline__ void st_async_v2(uint32_t a, uint32_t v0, uint32_t v1, uint32_t mb) {
  asm volatile("st.async.weak.shared::cluster.mbarrier::complete_tx::bytes.v2.b32 [%0], {%1,%2}, [%3];" :: "r"(a), "r"(v0), "r"(v1), "r"(mb) : "memory"); }
__device__ __forceinline__ void st_async_v4(uint32_t a, uint32_t v0, uint32_t v1, uint32_t v2, uint32_t v3, uint32_t mb) {
  asm volatile("st.async.weak.shared::cluster.mbarrier::complete_tx::bytes.v4.b32 [%0], {%1,%2,%3,%4}, [%5];" :: "r"(a), "r"(v0), "r"(v1), "r"(v2), "r"(v3), "r"(mb) : "memory"); }
__device__ __forceinline__ void ldsm4(uint32_t& r0, uint32_t& r1, uint32_t& r2, uint32_t& r3, uint32_t a) {
  asm volatile("ldmatrix.sync.aligned.m8n8.x4.shared.b16 {%0,%1,%2,%3}, [%4];" : "=r"(r0), "=r"(r1), "=r"(r2), "=r"(r3) : "r"(a) : "memory"); }
__device__ __forceinline__ void ldsm4t(uint32_t& r0, uint32_t& r1, uint32_t& r2, uint32_t& r3, uint32_t a) {
  asm volatile("ldmatrix.sync.aligned.m8n8.x4.trans.shared.b16 {%0,%1,%2,%3}, [%4];" : "=r"(r0), "=r"(r1), "=r"(r2), "=r"(r3) : "r"(a) : "memory"); }
__device__ __forceinline__ void stsm2t(uint32_t a, uint32_t r0, uint32_t r1) {
  asm volatile("stmatrix.sync.aligned.m8n8.x2.trans.shared.b16 [%0], {%1,%2};" :: "r"(a), "r"(r0), "r"(r1) : "memory"); }
__device__ __forceinline__ void stsm4t(uint32_t a, uint32_t r0, uint32_t r1, uint32_t r2, uint32_t r3) {
  asm volatile("stmatrix.sync.aligned.m8n8.x4.trans.shared.b16 [%0], {%1,%2,%3,%4};" :: "r"(a), "r"(r0), "r"(r1), "r"(r2), "r"(r3) : "memory"); }
__device__ __forceinline__ uint32_t movm(uint32_t a) {
  uint32_t d; asm volatile("movmatrix.sync.aligned.m8n8.trans.b16 %0, %1;" : "=r"(d) : "r"(a)); return d; }
__device__ __forceinline__ void mma16816(float* d, uint32_t a0, uint32_t a1, uint32_t a2, uint32_t a3, uint32_t b0, uint32_t b1) {
  asm("mma.sync.aligned.m16n8k16.row.col.f32.bf16.bf16.f32 {%0,%1,%2,%3}, {%4,%5,%6,%7}, {%8,%9}, {%0,%1,%2,%3};"
               : "+f"(d[0]), "+f"(d[1]), "+f"(d[2]), "+f"(d[3]) : "r"(a0), "r"(a1), "r"(a2), "r"(a3), "r"(b0), "r"(b1)); }
__device__ __forceinline__ void mma16816v(float* d, uint32_t a0, uint32_t a1, uint32_t a2, uint32_t a3, uint32_t b0, uint32_t b1) {
  asm volatile("mma.sync.aligned.m16n8k16.row.col.f32.bf16.bf16.f32 {%0,%1,%2,%3}, {%4,%5,%6,%7}, {%8,%9}, {%0,%1,%2,%3};"
               : "+f"(d[0]), "+f"(d[1]), "+f"(d[2]), "+f"(d[3]) : "r"(a0), "r"(a1), "r"(a2), "r"(a3), "r"(b0), "r"(b1)); }
__device__ __forceinline__ uint32_t pack2(float lo, float hi) {
  uint32_t r; asm("cvt.rn.bf16x2.f32 %0, %1, %2;" : "=r"(r) : "f"(hi), "f"(lo)); return r; }
__device__ __forceinline__ uint32_t pack2v(float lo, float hi) {
  uint32_t r; asm volatile("cvt.rn.bf16x2.f32 %0, %1, %2;" : "=r"(r) : "f"(hi), "f"(lo)); return r; }
__device__ __forceinline__ float bf_lo(uint32_t w) { return __uint_as_float(w << 16); }
__device__ __forceinline__ float bf_hi(uint32_t w) { return __uint_as_float(w & 0xffff0000u); }
__device__ __forceinline__ uint4 lds128(uint32_t a) {
  uint4 v; asm volatile("ld.shared.v4.b32 {%0,%1,%2,%3}, [%4];" : "=r"(v.x), "=r"(v.y), "=r"(v.z), "=r"(v.w) : "r"(a) : "memory"); return v; }
__device__ __forceinline__ uint4 lds128_nv(uint32_t a) {
  uint4 v; asm volatile("ld.shared.v4.b32 {%0,%1,%2,%3}, [%4];" : "=r"(v.x), "=r"(v.y), "=r"(v.z), "=r"(v.w) : "r"(a)); return v; }
__device__ __forceinline__ void st_async_v2_nm(uint32_t a, uint32_t v0, uint32_t v1, uint32_t mb) {
  asm volatile("st.async.weak.shared::cluster.mbarrier::complete_tx::bytes.v2.b32 [%0], {%1,%2}, [%3];" :: "r"(a), "r"(v0), "r"(v1), "r"(mb)); }
__device__ __forceinline__ float rcpf(float x) { float y; asm("rcp.approx.ftz.f32 %0, %1;" : "=f"(y) : "f"(x)); return y; }
__device__ __forceinline__ void sts64(uint32_t a, uint32_t x, uint32_t y) { asm volatile("st.shared.v2.b32 [%0], {%1,%2};" :: "r"(a), "r"(x), "r"(y) : "memory"); }
__device__ __forceinline__ float ex2(float x) { float y; asm("ex2.approx.ftz.f32 %0, %1;" : "=f"(y) : "f"(x)); return y; }
__device__ __forceinline__ uint32_t lds32(uint32_t a) {
  uint32_t v; asm volatile("ld.shared.b32 %0, [%1];" : "=r"(v) : "r"(a) : "memory"); return v; }
__device__ __forceinline__ uint2 lds64(uint32_t a) {
  uint2 v; asm volatile("ld.shared.v2.b32 {%0,%1}, [%2];" : "=r"(v.x), "=r"(v.y) : "r"(a) : "memory"); return v; }
__device__ __forceinline__ void sts128(uint32_t a, uint32_t x, uint32_t y, uint32_t z, uint32_t w) {
  asm volatile("st.shared.v4.b32 [%0], {%1,%2,%3,%4};" :: "r"(a), "r"(x), "r"(y), "r"(z), "r"(w) : "memory"); }
__device__ __forceinline__ void sts32(uint32_t a, uint32_t x) { asm volatile("st.shared.b32 [%0], %1;" :: "r"(a), "r"(x) : "memory"); }
__device__ __forceinline__ void tma2d(uint32_t dst, const CUtensorMap* tm, int c0, int c1, uint32_t mb) {
  asm volatile("cp.async.bulk.tensor.2d.shared::cluster.global.mbarrier::complete_tx::bytes [%0], [%1, {%3, %4}], [%2];"
               :: "r"(dst), "l"((uint64_t)tm), "r"(mb), "r"(c0), "r"(c1) : "memory"); }
__device__ __forceinline__ void tma2d_prefetch(const CUtensorMap* tm, int c0, int c1) {
  asm volatile("cp.async.bulk.prefetch.tensor.2d.L2.global.tile [%0, {%1, %2}];" :: "l"((uint64_t)tm), "r"(c0), "r"(c1) : "memory"); }
__device__ __forceinline__ void bulk_g2s_mc(uint32_t dst, const void* src, uint32_t bytes, uint32_t mb, uint16_t mask) {
  asm volatile("cp.async.bulk.shared::cluster.global.mbarrier::complete_tx::bytes.multicast::cluster [%0], [%1], %2, [%3], %4;"
               :: "r"(dst), "l"(src), "r"(bytes), "r"(mb), "h"(mask) : "memory"); }
__device__ __forceinline__ void bulk_s2g(void* dst, uint32_t src, uint32_t bytes) {
  asm volatile("cp.async.bulk.global.shared::cta.bulk_group [%0], [%1], %2;" :: "l"(dst), "r"(src), "r"(bytes) : "memory"); }
__device__ __forceinline__ void wg_fence() { asm volatile("wgmma.fence.sync.aligned;" ::: "memory"); }
__device__ __forceinline__ void wg_commit() { asm volatile("wgmma.commit_group.sync.aligned;" ::: "memory"); }
template <int N> __device__ __forceinline__ void wg_wait() { asm volatile("wgmma.wait_group.sync.aligned %0;" :: "n"(N) : "memory"); }
__device__ __forceinline__ uint64_t mkdesc(uint32_t addr, uint32_t lbo, uint32_t sbo, uint32_t swz) {
  return (uint64_t)((addr & 0x3FFFF) >> 4) | ((uint64_t)(lbo >> 4) << 16) | ((uint64_t)(sbo >> 4) << 32) | ((uint64_t)swz << 62); }

#define ACC4(d) "+f"(d[0]),"+f"(d[1]),"+f"(d[2]),"+f"(d[3])
#define ACC8(d) ACC4(d), ACC4((d + 4))
#define ACC16(d) ACC8(d), ACC8((d + 8))
#define ACC20(d) ACC16(d), ACC4((d + 16))
#define ACC24(d) ACC16(d), ACC8((d + 16))
#define SMEM0 0x400
__host__ __device__ constexpr uint32_t dlo(uint32_t off, uint32_t lbo) { return ((SMEM0 + off) >> 4) | ((lbo >> 4) << 16); }
__host__ __device__ constexpr uint32_t dhi(uint32_t sbo, uint32_t swz) { return (sbo >> 4) | (swz << 30); }
#define R4S "{%0,%1,%2,%3}"
#define R8S "{%0,%1,%2,%3,%4,%5,%6,%7}"
#define R16S "{%0,%1,%2,%3,%4,%5,%6,%7,%8,%9,%10,%11,%12,%13,%14,%15}"
#define R20S "{%0,%1,%2,%3,%4,%5,%6,%7,%8,%9,%10,%11,%12,%13,%14,%15,%16,%17,%18,%19}"
#define R24S "{%0,%1,%2,%3,%4,%5,%6,%7,%8,%9,%10,%11,%12,%13,%14,%15,%16,%17,%18,%19,%20,%21,%22,%23}"
template <int N> struct MM;
#define DEF_MM(N, ACCM, RS_, I0, I1, I2, I3, I4, I5, I6, I7)                                                                      \
  template <> struct MM<N> {                                                                                                      \
    template <uint32_t BLO, uint32_t BHI, int ACC>                                                                                \
    static __device__ __forceinline__ void rs(float* d, uint32_t a0, uint32_t a1, uint32_t a2, uint32_t a3) {                     \
      asm volatile("{\n.reg .b64 b;\nmov.b64 b, {%" #I4 ", %" #I5 "};\n"                                                          \
                   "wgmma.mma_async.sync.aligned.m64n" #N "k16.f32.bf16.bf16 " RS_ ", {%" #I0 ",%" #I1 ",%" #I2 ",%" #I3 "}, b, %" #I6 ", 1, 1, 0;\n}" \
                   : ACCM(d) : "r"(a0), "r"(a1), "r"(a2), "r"(a3), "n"(BLO), "n"(BHI), "n"(ACC)); }                               \
    template <uint32_t ALO, uint32_t AHI, uint32_t BLO, uint32_t BHI, int ACC, int TA>                                            \
    static __device__ __forceinline__ void ss(float* d, uint32_t abase) {                                                         \
      asm volatile("{\n.reg .b64 a, b;\n.reg .b32 l;\nadd.u32 l, %" #I0 ", %" #I1 ";\nmov.b64 a, {l, %" #I2 "};\nmov.b64 b, {%" #I3 ", %" #I4 "};\n" \
                   "wgmma.mma_async.sync.aligned.m64n" #N "k16.f32.bf16.bf16 " RS_ ", a, b, %" #I5 ", 1, 1, %" #I6 ", 0;\n}"     \
                   : ACCM(d) : "r"(abase), "n"(ALO), "n"(AHI), "n"(BLO), "n"(BHI), "n"(ACC), "n"(TA)); }                          \
    template <int ACC>                                                                                                            \
    static __device__ __forceinline__ void rsd(float* d, uint32_t a0, uint32_t a1, uint32_t a2, uint32_t a3, uint64_t b) {        \
      asm volatile("wgmma.mma_async.sync.aligned.m64n" #N "k16.f32.bf16.bf16 " RS_ ", {%" #I0 ",%" #I1 ",%" #I2 ",%" #I3 "}, %" #I4 ", %" #I5 ", 1, 1, 0;" \
                   : ACCM(d) : "r"(a0), "r"(a1), "r"(a2), "r"(a3), "l"(b), "n"(ACC)); }                                           \
    template <int ACC>                                                                                                            \
    static __device__ __forceinline__ void ssd(float* d, uint64_t a, uint64_t b) {                                                \
      asm volatile("wgmma.mma_async.sync.aligned.m64n" #N "k16.f32.bf16.bf16 " RS_ ", %" #I0 ", %" #I1 ", %" #I2 ", 1, 1, 1, 0;"  \
                   : ACCM(d) : "l"(a), "l"(b), "n"(ACC)); }                                                                       \
    template <uint32_t ALO, uint32_t AHI, uint32_t BLO, uint32_t BHI, int ACC>                                                    \
    static __device__ __forceinline__ void ss2(float* d, uint32_t abase, uint32_t bbase) {                                        \
      asm volatile("{\n.reg .b64 a, b;\n.reg .b32 l, m;\nadd.u32 l, %" #I0 ", %" #I1 ";\nmov.b64 a, {l, %" #I2 "};\n"            \
                   "add.u32 m, %" #I6 ", %" #I3 ";\nmov.b64 b, {m, %" #I4 "};\n"                                                   \
                   "wgmma.mma_async.sync.aligned.m64n" #N "k16.f32.bf16.bf16 " RS_ ", a, b, %" #I5 ", 1, 1, 0, 0;\n}"            \
                   : ACCM(d) : "r"(abase), "n"(ALO), "n"(AHI), "n"(BLO), "n"(BHI), "n"(ACC), "r"(bbase)); }                                    \
  };
DEF_MM(8, ACC4, R4S, 4, 5, 6, 7, 8, 9, 10, 11)
DEF_MM(16, ACC8, R8S, 8, 9, 10, 11, 12, 13, 14, 15)
DEF_MM(32, ACC16, R16S, 16, 17, 18, 19, 20, 21, 22, 23)
DEF_MM(40, ACC20, R20S, 20, 21, 22, 23, 24, 25, 26, 27)
DEF_MM(48, ACC24, R24S, 24, 25, 26, 27, 28, 29, 30, 31)

#define LAG 11
#define NSTEP (NSEG + LAG)
#define NR (NSTEP + 1)
__device__ __align__(1024) __nv_bfloat16 g_xn[2][S_LEN * DM];
__device__ __align__(1024) unsigned char g_o[NSTEP * 96 * 8192];
__device__ __align__(1024) uint32_t g_part[6][7][40][64];
#define RD 16
#define TILE_B 81920
__device__ __align__(1024) float2 g_stat[S_LEN];
__device__ __align__(1024) uint32_t g_st2[RD][64];
__device__ __align__(1024) unsigned char g_acc[5][RD][TILE_B];
#define NOP 19
#define NW12 5
#define NW34 12
#define NBC (NOP + NW12 + NW34)
__device__ __align__(1024) unsigned char g_wt[NOP * 10 * 12288];
enum { F_O = 0, F_R1 = NOP + 1, F_R2 = F_R1 + 4, F_R3 = F_R2 + 4, F_Z = F_R3 + 4, F_DONE, F_MISC, F_NUM };
__device__ __align__(128) uint32_t g_f[F_NUM][96];
__device__ __align__(128) int g_xready[129][8];
__device__ uint32_t g_tpc[128];
#define TS(i)
#define TSV(i, v)
#define TSN(i)
#define TSD(i, dep)
#define BTS(k, i)
#define BTS2(k, i)
#define RTS(i)
#define RTSD(i, dep)
#define RTS_OUT()
#define CTS(i)
#define PTS(i)
#define PTS1(i)
#define CTS_OUT()
#define GTS(i)

#define CL_SIZE 15
#define NCL 7
#define SSQ 13
#define SSV 16
#define PL_SZ 5376
#define TILE_SBO 2560
#define TILE_GRP 15360
#define WS_SZ ((2 * SSQ + SSV) * 2048)
#define OFF_QK (OFF_WO + 26 * 2048)
#define LAYOUT 2
#define OFF_TILE 0
#define OFF_WS (4 * TILE_GRP)
#define OFF_WO (OFF_WS + WS_SZ)
#define OFF_PL (OFF_QK + 20480)
#define OFF_BAR (OFF_PL + 2 * PL_SZ)
#define STG_Q OFF_TILE
#define STG_K OFF_WO
#define VA 14
#define STG_V2 (OFF_TILE + 27 * 2048)
#define OFF_O (OFF_PL + 4352)
#define LAND(k) (((k) >> 1) * TILE_GRP + ((k) & 1) * 1280)
#define LAND_F (5 * TILE_SBO)
#define OFF_XL (OFF_TILE + 3 * TILE_GRP)
#define OFF_XF (OFF_XL + LAND_F)
#define OFF_WT ((OFF_XL + TILE_SBO + 1023) & ~1023)
#define OFF_TAB (OFF_BAR + 240)
#define OFF_INV (OFF_TAB + 64)
#define OFF_TS (OFF_INV + 128)
#define A_SMEM 232448
static_assert(WS_SZ + 72 * 1024 + 2 * PL_SZ + 4 * TILE_GRP + 512 == A_SMEM && OFF_WS % 1024 == 0 && OFF_WO % 1024 == 0 && SSQ == 13, "smem map");
enum { B_W0 = 0, B_W1, B_F1, B_F2 = B_F1 + 4, B_R1 = B_F2 + 4, B_R2, B_MEMFREE, B_LANDFREE, B_OPEER, B_PLFREE, B_XFREE, B_SB, B_WOF = B_SB + 6, B_WTF, B_RS, B_NUM = B_RS + 4 };
static_assert(B_NUM <= 30, "barriers");
enum { N_C = 0, N_SISS, N_QK, N_V, N_PM, N_TURN, N_PI, N_VGO, N_O, N_PX, N_AB, N_SDONE, N_VDONE, N_G3, N_P, N_OX };

__device__ __forceinline__ bool is_dual(int j) { return j >= LAG && j < NSEG; }
__device__ __forceinline__ int sched_l(int j) { return j < NSEG ? j : NSEG + j - LAG; }
__device__ __forceinline__ int sched_f(int j) { return NSEG + j - LAG; }
__device__ __forceinline__ void wait_cnt(const int* p, int target) {
  int v, n = 0;
  do {
    asm volatile("ld.relaxed.gpu.global.b32 %0, [%1];" : "=r"(v) : "l"(p) : "memory");
    if (v >= target) break;
    __nanosleep(100);
    if (++n > SPIN_LIMIT) FAIL();
  } while (true);
  asm volatile("fence.acquire.gpu;" ::: "memory");
  asm volatile("fence.proxy.async.global;" ::: "memory");
}
__device__ __forceinline__ void red_release(void* p, uint32_t v) { asm volatile("red.release.gpu.global.add.u32 [%0], %1;" :: "l"(p), "r"(v) : "memory"); }
__device__ __forceinline__ void red_relaxed(void* p, uint32_t v) { asm volatile("red.relaxed.gpu.global.add.u32 [%0], %1;" :: "l"(p), "r"(v) : "memory"); }
#define VMASK 0xa5294a5294ull
__host__ __device__ constexpr int popc40(unsigned long long m) { int c = 0; for (; m; m &= m - 1) c++; return c; }
static_assert(popc40(VMASK) == SSV, "mask");
__host__ __device__ constexpr int ss_idx(int ks, int n) { return n == SSV ? popc40(VMASK & ((1ull << ks) - 1)) : ks * n / 40; }
__host__ __device__ constexpr bool is_ss(int ks, int n) { return ss_idx(ks + 1, n) != ss_idx(ks, n); }
__host__ __device__ constexpr int rs_idx(int ks, int n) { return ks - ss_idx(ks, n); }

#define SL2 (0.07216878364870322f * 1.4426950408889634f)

#define SUM_LOOP 0
#define IMM_K 0
#define TAB_N 32
struct DescTab { uint64_t tile[2][40], unit[2 * SSQ + SSV]; };
constexpr DescTab make_tab() {
  DescTab t = {};
  for (int rg = 0; rg < 2; rg++)
    for (int k = 0; k < 40; k++) t.tile[rg][k] = dlo(OFF_TILE + (k / 10) * TILE_GRP + rg * TILE_SBO + (k % 10) * 256, 128) | ((uint64_t)dhi(TILE_SBO, 0) << 32);
  for (int u = 0; u < 2 * SSQ + SSV; u++) t.unit[u] = dlo(OFF_WS + u * 2048, 0) | ((uint64_t)dhi(1024, 1) << 32);
  return t;
}
__constant__ DescTab c_tab = make_tab();
template <int N, int NSS, int RG, int KS, int K1, int K0 = 0>
__device__ __forceinline__ void proj(float* acc, const uint32_t* W, uint32_t ub) {
  if constexpr (KS < K1) {
    constexpr int i = rs_idx(KS, NSS) * 4;
    if constexpr (N >= TAB_N && !(RG == 0 && NSS == SSQ && KS < IMM_K)) {
      if constexpr (is_ss(KS, NSS)) MM<N>::template ssd<(KS != K0)>(acc, c_tab.unit[ub + ss_idx(KS, NSS)], c_tab.tile[RG][KS]);
      else MM<N>::template rsd<(KS != K0)>(acc, W[i], W[i + 1], W[i + 2], W[i + 3], c_tab.tile[RG][KS]);
    } else {
      constexpr uint32_t BLO = dlo(OFF_TILE + (KS / 10) * TILE_GRP + RG * TILE_SBO + (KS % 10) * 256, 128), BHI = dhi(TILE_SBO, 0);
      if constexpr (is_ss(KS, NSS)) MM<N>::template ss<dlo(OFF_WS + ss_idx(KS, NSS) * 2048, 0), dhi(1024, 1), BLO, BHI, (KS != K0), 1>(acc, ub * 128);
      else MM<N>::template rs<BLO, BHI, (KS != K0)>(acc, W[i], W[i + 1], W[i + 2], W[i + 3]);
    }
    proj<N, NSS, RG, KS + 1, K1, K0>(acc, W, ub);
  }
}
template <int N>
__device__ __forceinline__ void load_w(uint32_t* W, uint32_t stage, int warp, int lane) {
  const int kr = (lane >> 4) * 8 + (lane & 7);
  const int cb = warp * 2 + ((lane >> 3) & 1);
  const uint32_t a0 = stage + kr * 128 + ((cb ^ (lane & 7)) << 4);
#pragma unroll
  for (int i = 0; i < N; i++) ldsm4t(W[4 * i], W[4 * i + 1], W[4 * i + 2], W[4 * i + 3], a0 + i * 2048);
}
template <int N, int U, int OS, int ACC>
__device__ __forceinline__ void wo4(float* d) {
  constexpr uint32_t WA = U >= 4 ? OFF_WO + (U - 4) * 2048 : OFF_WT, OB = OS == 0 ? OFF_O : OS == 1 ? OFF_XL : OFF_XF, SBO = OS ? 1024 : PL_SZ;
  MM<N>::template ss<dlo(WA, 0), dhi(1024, 1), dlo(OB, 128), dhi(SBO, 0), ACC, 1>(d, 0);
  MM<N>::template ss<dlo(WA + 2048, 0), dhi(1024, 1), dlo(OB + 256, 128), dhi(SBO, 0), 1, 1>(d, 0);
  MM<N>::template ss<dlo(WA + 4096, 0), dhi(1024, 1), dlo(OB + 512, 128), dhi(SBO, 0), 1, 1>(d, 0);
  MM<N>::template ss<dlo(WA + 6144, 0), dhi(1024, 1), dlo(OB + 768, 128), dhi(SBO, 0), 1, 1>(d, 0);
}
__device__ __forceinline__ void wo_coord(int i, int t3, int head, int& c0, int& c1) {
  const int g = i >> 1;
  const int blk = g == 0 ? 9 : (g < 4 ? g - 1 : (g - 4) >> 1) * 3 + t3;
  int sl = g < 4 ? t3 : (g & 1) ? t3 + 1 : t3 + 2;
  if (sl >= 3) sl -= 3;
  c0 = blk * 64; c1 = head * DH + sl * 64 + (i & 1) * 32;
}
__device__ __forceinline__ void tok_softmax(uint32_t sb, int job, int lane) {
  const bool w1 = job & 1;
  const int dg = (lane >> 2) - (lane & 3) * 2;
  const uint32_t lo = sb + OFF_PL + (job >> 1) * PL_SZ + (job & 1) * 1792, l8 = lo + 512 + lane * 8, pa = lo + lane * 4;
  const uint32_t km = job & 2 ? 640 : 512;
  float x[14];
  {
    const uint4 a = lds128(lo + lane * 16);
    const uint2 e = lds64(l8);
    const uint32_t c = lds32(768 + pa);
    x[0] = bf_lo(a.x); x[1] = bf_hi(a.x); x[2] = bf_lo(a.y); x[3] = bf_hi(a.y); x[4] = bf_lo(a.z); x[5] = bf_hi(a.z); x[6] = bf_lo(a.w); x[7] = bf_hi(a.w);
    x[8] = bf_lo(c); x[9] = bf_hi(c); x[10] = bf_lo(e.x); x[11] = bf_hi(e.x); x[12] = bf_lo(e.y); x[13] = bf_hi(e.y);
  }
  if (dg < 0) { x[8] = -INFINITY; if (w1) x[4] = -INFINITY; else x[10] = -INFINITY; }
  if (dg < 1) { x[9] = -INFINITY; if (w1) x[5] = -INFINITY; else x[11] = -INFINITY; }
  const float m4 = fmaxf(x[8], x[9]);
  float m0 = fmaxf(fmaxf(fmaxf(x[0], x[1]), fmaxf(x[2], x[3])), fmaxf(fmaxf(x[4], x[5]), fmaxf(x[6], x[7])));
  float m1 = fmaxf(fmaxf(x[10], x[11]), fmaxf(x[12], x[13]));
  if (w1) m1 = fmaxf(m1, m4); else m0 = fmaxf(m0, m4);
  m0 = fmaxf(m0, __shfl_xor_sync(~0u, m0, 1)); m1 = fmaxf(m1, __shfl_xor_sync(~0u, m1, 1));
  sts32(pa + (w1 ? 384 : 896 + 128), 0u); sts32(pa + 1152 - km, 0u); sts32(pa + 896 + 1152 - km, 0u); sts64(l8 + 896 - 256, 0u, 0u);
  m0 = fmaxf(m0, __shfl_xor_sync(~0u, m0, 2)); m1 = fmaxf(m1, __shfl_xor_sync(~0u, m1, 2));
  m0 *= -SL2; m1 *= -SL2;
#pragma unroll
  for (int j = 0; j < 14; j++) x[j] = ex2(fmaf(x[j], SL2, j < 8 ? m0 : j >= 10 ? m1 : w1 ? m1 : m0));
  const float l4s = x[8] + x[9];
  float l0 = ((x[0] + x[1]) + (x[2] + x[3])) + ((x[4] + x[5]) + (x[6] + x[7])), l1 = (x[10] + x[11]) + (x[12] + x[13]);
  if (w1) l1 += l4s; else l0 += l4s;
  l0 += __shfl_xor_sync(~0u, l0, 1); l1 += __shfl_xor_sync(~0u, l1, 1);
  l0 += __shfl_xor_sync(~0u, l0, 2); l1 += __shfl_xor_sync(~0u, l1, 2);
  l0 = rcpf(l0); l1 = rcpf(l1);
#pragma unroll
  for (int j = 0; j < 7; j++) {
    const float iv = j < 4 ? l0 : j > 4 ? l1 : w1 ? l1 : l0;
    sts32(pa + (j < 3 ? j * 128 : j == 3 ? km : j == 4 ? (w1 ? 896 + 128 : 384) : j == 5 ? 896 : 896 + km), pack2(x[2 * j] * iv, x[2 * j + 1] * iv));
  }
}
template <int N>
__device__ __forceinline__ void wo_phase(uint32_t sb, int wg, int warp, int lane, uint32_t par, uint32_t r1) {
  const uint32_t bar = sb + OFF_BAR;
  float x[N / 2], y[N / 2];
  const uint2 ta = lds64(sb + OFF_TAB + (wg * 4 + warp) * 8);
  uint32_t xa = (ta.x & ~255u) + lane * 8, xb = (ta.x & 0xFF0000FFu) + SMEM0 + OFF_BAR, ya = (ta.y & ~255u) + lane * 8, yb = (ta.y & 0xFF0000FFu) + SMEM0 + OFF_BAR;
  asm volatile("" : "+r"(xa), "+r"(xb), "+r"(ya), "+r"(yb));
  auto scat = [&](uint32_t ad, uint32_t mb, const float* d) {
    st_async_v2(ad, pack2(d[0], d[1]), pack2(d[2], d[3]), mb);
    if (N == 16) st_async_v2(ad + LAND_F, pack2(d[4], d[5]), pack2(d[6], d[7]), mb);
  };
  if (wg == 0) {
    bar_sync(N_O, 384);
    wg_fence(); wo4<N, 4, 0, 0>(x); wo4<N, 8, 0, 0>(y); wg_commit();
    mbar_waitu(bar + 8 * B_OPEER, par);
    CFENCE(); wg_fence(); wo4<N, 16, 1, 1>(x); wo4<N, 20, 2, 1>(x); wg_commit();
    wo4<N, 24, 1, 1>(y); wg_commit();
    mbar_waitu2(bar + 8 * B_WOF, bar + 8 * B_MEMFREE, par);
    wg_fence(); wo4<N, 28, 2, 1>(y); wg_commit();
    bar_arrive(N_AB, 256);
    wg_wait<2>(); scat(xa, xb, x);
    wg_wait<0>(); scat(ya, yb, y);
  } else {
    bar_sync(N_O, 384);
    wg_fence(); wo4<N, 0, 0, 0>(x); wg_commit(); wo4<N, 12, 0, 0>(y); wg_commit();
    wg_wait<1>(); mbar_arrive_remote_if(lane == 0, r1);
    mbar_waitu(bar + 8 * B_MEMFREE, par);
    scat(xa, xb, x);
    bar_sync(N_AB, 256);
    CFENCE(); wg_fence(); wo4<N, 32, 1, 1>(y); wo4<N, 36, 2, 1>(y); wg_commit();
    bar_arrive(N_TURN, 256);
    wg_wait<0>(); scat(ya, yb, y);
  }
}
#define DS_DUAL 10
#define DS_SINGLE 20
#define POLL_GAP 100
#define POLL_GAPD 0
#define TOK_DELAY 250
#define LATE_SM 1
#define UMAX 40
#define VD1 6
#define VS1 4
#define VST 17
struct AMaps { CUtensorMap w16[3], wo32; };
__global__ void __launch_bounds__(512, 1)
acore_kernel(const __grid_constant__ AMaps M, const __nv_bfloat16* __restrict__ mem0, int sync_b) {
  extern __shared__ __align__(1024) unsigned char smem_raw[];
  const uint32_t sb = smem_u32(smem_raw);
  GTS(24);
  if (threadIdx.x == 0) {
    uint32_t smid; asm volatile("mov.u32 %0, %%smid;" : "=r"(smid));
    g_tpc[(smid >> 1) & 127] = 1;
    __threadfence();
    asm volatile("griddepcontrol.launch_dependents;");
  }
  const int lane0 = threadIdx.x & 31;
#define LANE_INIT() int lane; asm volatile("mov.u32 %0, %%laneid;" : "=r"(lane))
  const int warp = __shfl_sync(~0u, (threadIdx.x >> 5) & 3, 0);
  const int cl = blockIdx.x / CL_SIZE;
  const uint32_t rank = blockIdx.x - cl * CL_SIZE;
  const int nh = cl >= 1 && cl <= 3 ? 4 : 5;
  const int nA = 3 * nh;
  const int wg = __shfl_sync(~0u, (int)rank < nA ? threadIdx.x >> 7 : 4, 0);
  const int head = (cl < 4 ? (cl ? 1 + 4 * cl : 0) : 5 * cl - 3) + rank / 3;
  const int t3 = rank % 3;
  const int col0 = head * DH + t3 * 64;
  const uint32_t bar = sb + OFF_BAR;
  const uint32_t rb0 = SMEM0;
  const uint16_t mcmask = (uint16_t)((1u << nA) - 1);
  const uint32_t nxt = sb + ((t3 == 2 ? -2 : 1) << 24), prv = sb + ((t3 == 0 ? 2 : -1) << 24);
  const int ig = (int)rank - (nA - 4);

  if (threadIdx.x == 0) {
    if (mapa(sb, nA - 1) != rb0 + ((nA - 1) << 24) || mapa(sb, 0) != rb0 || mapa(sb, 1) != rb0 + (1u << 24) || sb != SMEM0 + (rank << 24)) FAIL();
    for (int i = 0; i < B_NUM; i++)
      mbar_init(bar + 8 * i, i == B_R1 ? 4 * nA : i == B_R2 ? 12 * nA : i == B_MEMFREE ? nA : i == B_LANDFREE ? 4 * nA : i == B_PLFREE || i == B_XFREE ? 2 : 1);
    asm volatile("fence.mbarrier_init.release.cluster;" ::: "memory");
    mbar_expect(bar + 8 * B_W0, (80 + SSV + VST) * 2048);
  }
  __syncthreads();
  if (lane0 == 0) {
    const int w12 = wg * 4 + warp;
    if (w12 < 10) {
#pragma unroll 1
      for (int ks = 4 * w12; ks < 4 * w12 + 4; ks++) {
        const bool ss = is_ss(ks, SSQ);
        tma2d(ss ? sb + OFF_WS + ss_idx(ks, SSQ) * 2048 : sb + STG_Q + rs_idx(ks, SSQ) * 2048, &M.w16[0], col0, ks * 16, bar + 8 * B_W0);
        tma2d(ss ? sb + OFF_WS + (SSQ + ss_idx(ks, SSQ)) * 2048 : sb + STG_K + rs_idx(ks, SSQ) * 2048, &M.w16[1], col0, ks * 16, bar + 8 * B_W0);
        if (is_ss(ks, SSV)) tma2d(sb + OFF_WS + (2 * SSQ + ss_idx(ks, SSV)) * 2048, &M.w16[2], col0, ks * 16, bar + 8 * B_W0);
        else if (rs_idx(ks, SSV) < VST) tma2d(sb + (rs_idx(ks, SSV) < VA ? STG_K + 27 * 2048 : STG_V2 - VA * 2048) + rs_idx(ks, SSV) * 2048, &M.w16[2], col0, ks * 16, bar + 8 * B_W0);
        else tma2d_prefetch(&M.w16[2], col0, ks * 16);
      }
      int c0, c1;
      wo_coord(2 * w12, t3, head, c0, c1);
      tma2d_prefetch(&M.wo32, c0, c1);
      tma2d_prefetch(&M.wo32, c0, c1 + 32);
    }
  }
  static_assert(40 - SSV - VST <= 10, "staging");
  if (lane0 < 2 && wg < 2) {
    const int u = 4 * (wg ? (lane0 ? 6 + t3 : 9) : (lane0 ? 3 + t3 : t3)) + warp;
    const int li = (u >= nA) + (u >= 2 * nA) + (u >= 3 * nA);
    sts32(sb + OFF_TAB + (wg * 4 + warp) * 8 + lane0 * 4,
          rb0 + ((u - li * nA) << 24) + OFF_TILE + LAND(li + (u >= 36 ? t3 : 0)) + (rank / 3) * 256 + 8 * (B_RS + li));
  }
  __syncthreads();
  GTS(25);

  auto issue_tok = [&](int sc, int fb, int rel = -1, uint32_t ph = 0) {
    if (sync_b) wait_cnt(&g_xready[sc][0], 32);
    if (rel >= 0) mbar_waitu(bar + 8 * rel, ph);
    bulk_g2s_mc_e(sb + OFF_TILE + ig * TILE_GRP + TILE_SBO, &g_xn[0][0] + uni(sc * (32 * DM)) + ig * 5120, 10240, bar + 8 * (fb + ig), mcmask);
  };
#define POLL(d, q) _Pragma("unroll") for (int k = 0; k < NCL; k++) \
      asm volatile("ld.relaxed.gpu.global.v2.b32 {%0,%1}, [%2];" : "=r"(d[k].x), "=r"(d[k].y) : "l"(q + k * 2560) : "memory")
#define L3(L, a, b, c) lop3<L>(a, b, c)
#define TAGS(L, d) L3(L, L3(L, L3(L, d[0].x, d[0].y, d[1].x), L3(L, d[1].y, d[2].x, d[2].y), L3(L, d[3].x, d[3].y, d[4].x)), L3(L, d[4].y, d[5].x, d[5].y), L3(L, d[6].x, d[6].y, d[6].y))
    auto deliver = [&](uint2* pa, const uint32_t* gq, int u, int c, int dc, int ds, int step, bool first, int lane) {
      const uint32_t off = uni(OFF_TILE + ((u * 205) >> 11) * (TILE_GRP - TILE_SBO) + u * 256 + dc * LAND_F), boff = uni(OFF_BAR + 8 * (B_F1 + ((u * 205) >> 11)));
      const uint32_t* mi = &g_part[4][0][0][0] + uni((c * NCL + cl) * 2560 + u * 64);
      mbar_waitu(bar + 8 * B_LANDFREE, step & 1);
      int n = 0;
      while (true) {
        const bool ok = __all_sync(~0u, ((step & 2 ? ~TAGS(0xFE, pa) : TAGS(0x80, pa)) & 1) != 0);
        if (ok) break;
        if (++n > SPIN_LIMIT) FAIL();
        POLL(pa, gq);
      }
      if (warp == 0 && first) { TS(19); TSV(10, n); }
      const uint32_t w0 = hadd2bf(hadd2bf(hadd2bf(pa[0].x, pa[1].x), hadd2bf(pa[2].x, pa[3].x)), hadd2bf(hadd2bf(pa[4].x, pa[5].x), pa[6].x));
      const uint32_t w1 = hadd2bf(hadd2bf(hadd2bf(pa[0].y, pa[1].y), hadd2bf(pa[2].y, pa[3].y)), hadd2bf(hadd2bf(pa[4].y, pa[5].y), pa[6].y));
      if (u < ds) {
        const uint32_t da = SMEM0 + off + lane * 8, db = SMEM0 + boff;
#pragma unroll
        for (int d = 0; d < 12; d++) st_async_v2((d << 24) + da, w0, w1, (d << 24) + db);
#pragma unroll
        for (int d = 12; d < 15; d++) st_async_v2_if(nA == 15, (d << 24) + da, w0, w1, (d << 24) + db);
      } else {
        *reinterpret_cast<uint2*>(const_cast<uint32_t*>(gq) + ((4 - 2 * (step & 1)) * NCL + cl) * 2560) = make_uint2(w0, w1);
        asm volatile("fence.proxy.async.global;" ::: "memory");
        __syncwarp();
        bulk_g2s_mc_e(sb + off, mi, 256, sb + boff, mcmask);
      }
    };
#define REL(b, g) mbar_arrive_remote_if(lane == 0, rb0 + ((nA - 4 + (g)) << 24) + OFF_BAR + 8 * (b))

  if (wg < 2) {
    asm volatile("setmaxnreg.inc.sync.aligned.u32 160;");
    LANE_INIT();
    uint32_t W[4 * (40 - SSQ)];
    mbar_waitw(bar + 8 * B_W0, 0);
    GTS(26);
    load_w<40 - SSQ>(W, sb + (wg ? STG_K : STG_Q), warp, lane);
    fence_async();
    bar_sync(1, 384);
    cluster_sync_all();
    const uint32_t wbase = wg * SSQ;
    GTS(27);
#pragma unroll 1
    for (int step = -1; step < NSTEP; step++) {
      const uint32_t par = step & 1;
      asm volatile("" : "+r"(lane));
      const bool dual = is_dual(step), has_next = step + 1 < NSTEP;
#define QK_SA (sb + OFF_QK + wg * 15360 + (2 * warp + ((lane >> 3) & 1)) * 128 + (lane & 7) * 16)
#define QK_F (wg ? -5120 : 5120)
#define QK_S12 ((wg ? (lane >> 4) : 1 + 2 * (lane >> 4)) * 1024)
#define QK_S34 ((wg ? 2 + (lane >> 4) : 2 - 2 * (lane >> 4)) * 1024)
      if (step >= 0) {
        if (dual) {
          float acc[24];
          mbar_waitu(bar + 8 * (B_F1 + 0), par);
          if (wg + warp == 0) { TS(0); TSN(1); }
          CFENCE(); wg_fence(); proj<48, SSQ, 0, 0, 10>(acc, W, wbase); wg_commit();
          mbar_waitu(bar + 8 * (B_F1 + 1), par);
          CFENCE(); wg_fence(); proj<48, SSQ, 0, 10, 20>(acc, W, wbase); wg_commit();
          mbar_waitu(bar + 8 * (B_F1 + 2), par);
          CFENCE(); wg_fence(); proj<48, SSQ, 0, 20, 30>(acc, W, wbase); wg_commit();
          mbar_waitu2(bar + 8 * (B_F1 + 3), bar + 8 * B_PLFREE, par);
          if (wg + warp == 0) TS(2);
          CFENCE(); wg_fence(); proj<48, SSQ, 0, 30, 40>(acc, W, wbase); wg_commit();
          bar_arrive(N_VGO, 384);
          const uint32_t sa = QK_SA, s0 = sa + 4096 + (lane >> 4) * QK_F, s1 = sa + QK_F + QK_S12, s2 = sa + QK_F + QK_S34;
          wg_wait<0>();
          if (wg + warp == 0) TS(3);
          stsm4t(s0, pack2(acc[0], acc[1]), pack2(acc[2], acc[3]), pack2(acc[20], acc[21]), pack2(acc[22], acc[23]));
          stsm4t(s1, pack2(acc[4], acc[5]), pack2(acc[6], acc[7]), pack2(acc[8], acc[9]), pack2(acc[10], acc[11]));
          stsm4t(s2, pack2(acc[12], acc[13]), pack2(acc[14], acc[15]), pack2(acc[16], acc[17]), pack2(acc[18], acc[19]));
        } else {
          float acc[4];
          mbar_waitu(bar + 8 * (B_F1 + 0), par);
          if (wg + warp == 0) { TS(0); TSN(1); }
          CFENCE(); wg_fence(); proj<8, SSQ, 0, 0, 10>(acc, W, wbase); wg_commit();
          mbar_waitu(bar + 8 * (B_F1 + 1), par);
          CFENCE(); wg_fence(); proj<8, SSQ, 0, 10, 20>(acc, W, wbase); wg_commit();
          mbar_waitu(bar + 8 * (B_F1 + 2), par);
          CFENCE(); wg_fence(); proj<8, SSQ, 0, 20, 30>(acc, W, wbase); wg_commit();
          mbar_waitu2(bar + 8 * (B_F1 + 3), bar + 8 * B_PLFREE, par);
          if (wg + warp == 0) TS(2);
          CFENCE(); wg_fence(); proj<8, SSQ, 0, 30, 40>(acc, W, wbase); wg_commit();
          bar_arrive(N_VGO, 384);
          const uint32_t s0 = QK_SA + 4096;
          wg_wait<0>();
          if (wg + warp == 0) TS(3);
          stsm2t(s0, pack2(acc[0], acc[1]), pack2(acc[2], acc[3]));
        }
        fence_async();
        bar_sync(N_QK, 256);
        if (wg == 0 || dual) {
          float s[20];
          const uint32_t ab = wg * 192, bb = wg * -320;
          wg_fence();
          MM<40>::ss2<dlo(OFF_QK, 128), dhi(1024, 0), dlo(OFF_QK + 15360, 128), dhi(1024, 0), 0>(s, ab, bb);
          MM<40>::ss2<dlo(OFF_QK + 256, 128), dhi(1024, 0), dlo(OFF_QK + 15360 + 256, 128), dhi(1024, 0), 1>(s, ab, bb);
          MM<40>::ss2<dlo(OFF_QK + 512, 128), dhi(1024, 0), dlo(OFF_QK + 15360 + 512, 128), dhi(1024, 0), 1>(s, ab, bb);
          MM<40>::ss2<dlo(OFF_QK + 768, 128), dhi(1024, 0), dlo(OFF_QK + 15360 + 768, 128), dhi(1024, 0), 1>(s, ab, bb);
          wg_commit();
          bar_arrive(N_SISS, 384);
          const int rw = (warp - wg) & 3;
          const uint32_t bo = OFF_BAR + 8 * (B_SB + 3 * wg + rw), lo = OFF_PL + wg * PL_SZ + rw * 1792;
          const uint32_t km = wg ? 640 : 512;
          uint32_t l16 = lo + lane * 16, l4 = lo + lane * 4;
          mbar_expect_if(lane == 0 && rw < 3, sb + bo, rw < 2 ? 1792 : 1280);
          asm volatile("" : "+r"(l16), "+r"(l4));
          if (rw == 2) {
            wg_wait<0>();
            if (wg == 0) TSD(4, __float_as_uint(s[0]));
            {
              const uint32_t w0 = pack2(s[0], s[1]), w1 = pack2(s[4], s[5]), w2 = pack2(s[8], s[9]), w3 = pack2(s[12], s[13]), w4 = pack2(s[16], s[17]);
              st_async_v4(nxt + 896 + l16, w0, w1, w2, w3, nxt + bo);
              st_async_v4(prv + l16, w0, w1, w2, w3, prv + bo);
              st_async_b32(nxt + 896 + 768 + l4, w4, nxt + bo);
              st_async_b32(prv + 768 + l4, w4, prv + bo);
            }
            bar_arrive(N_SDONE, 256);
            mbar_waitu(sb + bo, (step - wg * LAG) & 1);
            if (wg == 0) TS(5);
            float x[10];
            {
              const uint4 a = lds128(sb + l16), b = lds128(sb + 896 + l16);
              const uint32_t c = lds32(sb + 768 + l4), d = lds32(sb + 896 + 768 + l4);
              const uint32_t e0 = hadd2bf(a.x, b.x), e1 = hadd2bf(a.y, b.y), e2 = hadd2bf(a.z, b.z), e3 = hadd2bf(a.w, b.w), e4 = hadd2bf(c, d);
              x[0] = s[0] + bf_lo(e0); x[1] = s[1] + bf_hi(e0); x[2] = s[4] + bf_lo(e1); x[3] = s[5] + bf_hi(e1); x[4] = s[8] + bf_lo(e2);
              x[5] = s[9] + bf_hi(e2); x[6] = s[12] + bf_lo(e3); x[7] = s[13] + bf_hi(e3); x[8] = s[16] + bf_lo(e4); x[9] = s[17] + bf_hi(e4);
            }
            float m0 = fmaxf(fmaxf(fmaxf(x[0], x[1]), fmaxf(x[2], x[3])), fmaxf(fmaxf(x[4], x[5]), fmaxf(fmaxf(x[6], x[7]), fmaxf(x[8], x[9]))));
            m0 = fmaxf(m0, __shfl_xor_sync(~0u, m0, 1));
            sts32(sb + l4 + 1152 - km, 0u);
            m0 = fmaxf(m0, __shfl_xor_sync(~0u, m0, 2));
            m0 *= -SL2;
#pragma unroll
            for (int j = 0; j < 5; j++) {
              x[2 * j] = ex2(fmaf(x[2 * j], SL2, m0)); x[2 * j + 1] = ex2(fmaf(x[2 * j + 1], SL2, m0));
              sts32(sb + l4 + (j < 4 ? j * 128 : km), pack2(x[2 * j], x[2 * j + 1]));
            }
            float l = ((x[0] + x[1]) + (x[2] + x[3])) + ((x[4] + x[5]) + ((x[6] + x[7]) + (x[8] + x[9])));
            l += __shfl_xor_sync(~0u, l, 1);
            fence_async();
            sts32(sb + OFF_INV + wg * 64 + (lane >> 1) * 4, __float_as_uint(l));
            bar_arrive(N_PM, dual ? 224 : 192);
            if (wg == 0) TS(6);
          } else if (rw < 2) {
            const bool w1 = rw == 1;
            const uint32_t l8 = lo + 512 + lane * 8;
            uint32_t tw[7];
            wg_wait<0>();
            bar_arrive(N_SDONE, 256);
            tw[0] = pack2(s[0], s[1]); tw[1] = pack2(s[4], s[5]); tw[2] = pack2(s[8], s[9]); tw[3] = pack2(s[16], s[17]);
            tw[4] = w1 ? pack2(s[6], s[7]) : pack2(s[12], s[13]); tw[5] = pack2(s[2], s[3]); tw[6] = pack2(s[18], s[19]);
            { const uint32_t t0 = clock32(); while (clock32() - t0 < TOK_DELAY) {} }
            st_async_v4(nxt + 896 + l16, tw[0], tw[1], tw[2], tw[3], nxt + bo);
            st_async_v4(prv + l16, tw[0], tw[1], tw[2], tw[3], prv + bo);
            st_async_v2(nxt + 896 + l8, tw[5], tw[6], nxt + bo);
            st_async_v2(prv + l8, tw[5], tw[6], prv + bo);
            st_async_b32(nxt + 896 + 768 + l4, tw[4], nxt + bo);
            st_async_b32(prv + 768 + l4, tw[4], prv + bo);
            mbar_waitu(sb + bo, (step - wg * LAG) & 1);
            const uint4 a = lds128(sb + l16), b = lds128(sb + 896 + l16);
            const uint2 e = lds64(sb + l8), f = lds64(sb + 896 + l8);
            const uint32_t c = lds32(sb + 768 + l4), d = lds32(sb + 896 + 768 + l4);
            sts128(sb + l16, hadd2bf(hadd2bf(a.x, b.x), tw[0]), hadd2bf(hadd2bf(a.y, b.y), tw[1]), hadd2bf(hadd2bf(a.z, b.z), tw[2]), hadd2bf(hadd2bf(a.w, b.w), tw[3]));
            sts64(sb + l8, hadd2bf(hadd2bf(e.x, f.x), tw[5]), hadd2bf(hadd2bf(e.y, f.y), tw[6]));
            sts32(sb + 768 + l4, hadd2bf(hadd2bf(c, d), tw[4]));
            bar_arrive(N_PX, dual ? 256 : 192);
            if (wg + warp == 0) TS(9);
          } else {
            wg_wait<0>();
            if (wg == 0) {
              mbar_expect_if(lane < 3 && has_next, bar + 8 * (lane == 2 ? B_OPEER : B_WOF + lane), lane == 2 ? (dual ? 4096 : 2048) : lane ? 8192 : 20480);
              auto fetch = [&](int i, int n, uint32_t dst, int mb) {
                int c0, c1; wo_coord(i, t3, head, c0, c1);
                tma2d_e(dst, &M.wo32, c0, c1, bar + 8 * mb); if (n == 2) tma2d_e(dst + 4096, &M.wo32, c0, c1 + 32, bar + 8 * mb);
              };
              bar_sync(N_G3, 160);
              if (has_next) {
                fetch(0, 2, sb + OFF_WT, B_WTF);
                mbar_arrive_remote_if(lane < 2, (lane ? nxt : prv) + OFF_BAR + 8 * B_XFREE);
              }
              bar_sync(N_SDONE, 256);
              if (has_next) {
                fetch(15, 1, sb + OFF_QK, B_WOF); fetch(16, 2, sb + OFF_QK + 4096, B_WOF); fetch(18, 2, sb + OFF_QK + 12288, B_WOF);
                mbar_waitu(bar + 8 * B_XFREE, par);
              }
              bar_arrive(N_PM, dual ? 224 : 192);
              bar_sync(N_VDONE, 160);
              mbar_arrive_remote_if(lane < nA && has_next, rb0 + (lane << 24) + OFF_BAR + 8 * B_MEMFREE);
              if (has_next) mbar_waitu(bar + 8 * B_WTF, par);
            } else {
              bar_arrive(N_SDONE, 256);
              if ((unsigned)ig < 3) issue_tok(sched_l(step + 1), B_F2, B_R1, (step - LAG) & 1);
            }
          }
        } else {
          bar_arrive(N_SISS, 384);
          bar_arrive(N_SDONE, 256);
        }
        if (has_next) {
          if (step == 0) mbar_waitw(bar + 8 * B_W0, 1);
          const uint32_t r1 = rb0 + ((nA - 1) << 24) + OFF_BAR + 8 * B_R1;
          if (dual) wo_phase<16>(sb, wg, warp, lane, par, r1); else wo_phase<8>(sb, wg, warp, lane, par, r1);
          bar_arrive(N_C, 288);
          if (warp == 0) TS(7 + wg);
        }
      }
      if (has_next) {
        float acc[16];
        mbar_waitu(bar + 8 * B_F2, par ^ 1);
        wg_fence(); proj<32, SSQ, 1, 0, 10>(acc, W, wbase); wg_commit();
        mbar_waitu(bar + 8 * (B_F2 + 1), par ^ 1);
        wg_fence(); proj<32, SSQ, 1, 10, 14>(acc, W, wbase); wg_commit();
        wg_wait<1>(); REL(B_R2, 0);
        wg_fence(); proj<32, SSQ, 1, 14, 20>(acc, W, wbase); wg_commit();
        mbar_waitu(bar + 8 * (B_F2 + 2), par ^ 1);
        wg_fence(); proj<32, SSQ, 1, 20, 24>(acc, W, wbase); wg_commit();
        wg_wait<1>(); REL(B_R2, 1);
        wg_fence(); proj<32, SSQ, 1, 24, 30>(acc, W, wbase); wg_commit();
        mbar_waitu(bar + 8 * (B_F2 + 3), par ^ 1);
        wg_fence(); proj<32, SSQ, 1, 30, 34>(acc, W, wbase); wg_commit();
        wg_wait<1>(); REL(B_R2, 2);
        wg_fence(); proj<32, SSQ, 1, 34, 40>(acc, W, wbase); wg_commit();
        const uint32_t sa = QK_SA, s1 = sa + QK_S12, s2 = sa + QK_S34;
        wg_wait<0>(); REL(B_R2, 3);
        if (warp == 0) TS(11 + wg);
        stsm4t(s1, pack2(acc[0], acc[1]), pack2(acc[2], acc[3]), pack2(acc[4], acc[5]), pack2(acc[6], acc[7]));
        stsm4t(s2, pack2(acc[8], acc[9]), pack2(acc[10], acc[11]), pack2(acc[12], acc[13]), pack2(acc[14], acc[15]));
      }
    }
    GTS(28);
    cluster_sync_all();
  } else if (wg == 2) {
    asm volatile("setmaxnreg.inc.sync.aligned.u32 160;");
    LANE_INIT();
    uint32_t W[4 * (40 - SSV)];
    mbar_waitw(bar + 8 * B_W0, 0);
    load_w<VA>(W, sb + STG_K + 27 * 2048, warp, lane);
    load_w<VST - VA>(W + 4 * VA, sb + STG_V2, warp, lane);
    fence_async();
    bar_sync(1, 384);
    if (lane == 0) {
      if (warp == 0) {
        mbar_expect(bar + 8 * B_W1, (40 - SSV - VST) * 2048);
#pragma unroll 1
        for (int ks = 0; ks < 40; ks++)
          if (!is_ss(ks, SSV) && rs_idx(ks, SSV) >= VST) tma2d(sb + OFF_QK + (rs_idx(ks, SSV) - VST) * 2048, &M.w16[2], col0, ks * 16, bar + 8 * B_W1);
      } else {
        if (warp == 1) mbar_expect(bar + 8 * B_W0, 26 * 2048);
#pragma unroll 1
        for (int i = warp - 1; i < 13; i += 3) { int c0, c1; wo_coord(i + 2, t3, head, c0, c1); tma2d(sb + OFF_WO + i * 4096, &M.wo32, c0, c1, bar + 8 * B_W0); }
      }
    }
    __syncwarp();
#pragma unroll
    for (int i = 0; i < 5; i++) {
      const int t = i * 128 + warp * 32 + lane;
      const uint4 v = *reinterpret_cast<const uint4*>(mem0 + (t & 7) * DM + (t >> 3) * 8);
      sts128(sb + OFF_TILE + (t / 160) * (TILE_GRP - TILE_SBO) + t * 16, v.x, v.y, v.z, v.w);
    }
    mbar_waitw(bar + 8 * B_W1, 0);
    load_w<40 - SSV - VST>(W + 4 * VST, sb + OFF_QK, warp, lane);
    fence_async();
    mbar_arrive_if(lane == 0, bar + 8 * (B_F1 + warp));
    mbar_expect_if(lane == 0, bar + 8 * (B_F2 + warp), 10240);
    mbar_arrive_if(warp == 3 && lane < 2, bar + 8 * B_PLFREE);
    cluster_sync_all();
    uint32_t vl[8];
    constexpr uint32_t wbase = 2 * SSQ;
    {
      float v[16];
      mbar_waitw4(bar + 8 * B_F2, 0);
      wg_fence(); proj<32, SSV, 1, 0, 40>(v, W, wbase); wg_commit();
      wg_wait<0>();
      mbar_arrive_remote_if(lane < 4, rb0 + ((nA - 4 + lane) << 24) + OFF_BAR + 8 * B_R2);
#pragma unroll
      for (int j = 0; j < 8; j++) vl[j] = pack2v(v[2 * j], v[2 * j + 1]);
      if (warp == 0 && (unsigned)ig < 3) issue_tok(1, B_F2, B_R2, 0);
    }
#pragma unroll 1
    for (int step = 0; step < NSTEP; step++) {
      const uint32_t par = step & 1;
      asm volatile("" : "+r"(lane));
      const bool dual = is_dual(step), has_next = step + 1 < NSTEP;
      mbar_expect_if(lane == 0 && has_next, bar + 8 * (B_F2 + warp), 10240);
      if (warp == 0 && ig == 3 && has_next && sync_b) wait_cnt(&g_xready[sched_l(step + 1)][0], 32);
      bar_sync(N_VGO, 384);
      CFENCE();
#define F1_BYTES (is_dual(step + 1) ? 15360 : 2560)
#define ARM() do { \
        mbar_expect_if(lane == 0 && has_next, bar + 8 * (B_F1 + warp), F1_BYTES); \
        mbar_expect_if(lane == 0 && has_next && warp * nA + (int)rank < 40, bar + 8 * (B_RS + warp), (warp * nA + (int)rank >= 36 ? nA : nh) * (dual ? 512 : 256)); } while (0)
#define O_ADDR() uint32_t oa = sb + OFF_O + (lane >> 4) * PL_SZ + warp * 256 + (lane & 15) * 16, xo = (lane >> 4) * 1024 + warp * 256 + (lane & 15) * 16; \
        asm volatile("" : "+r"(oa), "+r"(xo))
#define O_READY(act) do { if (has_next) { const uint4 ov = lds128(oa); \
        if (act) { st_async_v4(nxt + OFF_XL + xo, ov.x, ov.y, ov.z, ov.w, nxt + OFF_BAR + 8 * B_OPEER); \
                   st_async_v4(prv + OFF_XF + xo, ov.x, ov.y, ov.z, ov.w, prv + OFF_BAR + 8 * B_OPEER); } \
        fence_async(); bar_arrive(N_O, 384); } \
        if (warp == 0) TS(15); } while (0)
#define TOK_L3() if (warp == 0 && ig == 3 && has_next) { mbar_waitu(bar + 8 * B_R1, par); \
        bulk_g2s_mc_e(sb + OFF_TILE + 3 * TILE_GRP + TILE_SBO, &g_xn[0][0] + uni(sched_l(step + 1) * (32 * DM)) + 3 * 5120, 10240, bar + 8 * (B_F2 + 3), mcmask); }
#define OX_SA (sb + OFF_PL + (lane & 7) * 128 + (((warp * 2 + ((lane >> 3) & 1)) ^ (lane & 7)) << 4))
      if (dual) {
        uint32_t vf[8], vm[4], vn[8];
        {
          float v[24];
          wg_fence(); proj<48, SSV, 0, 30, 30 + VD1, 30>(v, W, wbase); wg_commit();
          ARM();
          bar_sync(N_SISS, 384);
          wg_fence(); proj<48, SSV, 0, 30 + VD1, 40, 30>(v, W, wbase); wg_commit();
          proj<48, SSV, 0, 0, 3, 30>(v, W, wbase); wg_commit();
          wg_wait<1>(); bar_arrive(N_G3, 160);
          wg_fence(); proj<48, SSV, 0, 3, 10, 30>(v, W, wbase); wg_commit();
          proj<48, SSV, 0, 10, 13, 30>(v, W, wbase); wg_commit();
          wg_wait<1>(); REL(B_R1, 0);
          wg_fence(); proj<48, SSV, 0, 13, 20, 30>(v, W, wbase); wg_commit();
          proj<48, SSV, 0, 20, 23, 30>(v, W, wbase); wg_commit();
          wg_wait<1>(); REL(B_R1, 1);
          wg_fence(); proj<48, SSV, 0, 23, 30, 30>(v, W, wbase); wg_commit();
          wg_wait<0>(); REL(B_R1, 2);
          bar_arrive(N_VDONE, 160);
          if (warp == 0) TS(14);
#pragma unroll
          for (int j = 4; j < 8; j++) vf[j] = pack2v(v[4 + 2 * j], v[5 + 2 * j]);
          keep4(vf + 4, lane);
          vm[0] = pack2v(v[0], v[1]); vm[1] = pack2v(v[2], v[3]); vm[2] = pack2v(v[20], v[21]); vm[3] = pack2v(v[22], v[23]);
          keep4(vm, lane);
#pragma unroll
          for (int j = 0; j < 4; j++) vf[j] = pack2v(v[4 + 2 * j], v[5 + 2 * j]);
          keep4(vf, lane);
        }
        {
          float o[8];
          O_ADDR();
          bar_sync(N_PM, 224);
          wg_fence();
          MM<8>::rs<dlo(OFF_PL + 3584, 128), dhi(896, 0), 0>(o, vl[0], vl[1], vl[2], vl[3]);
          MM<8>::rs<dlo(OFF_PL + PL_SZ + 3584, 128), dhi(896, 0), 0>(o + 4, vf[0], vf[1], vf[2], vf[3]);
          MM<8>::rs<dlo(OFF_PL + 3584 + 256, 128), dhi(896, 0), 1>(o, vl[4], vl[5], vl[6], vl[7]);
          MM<8>::rs<dlo(OFF_PL + PL_SZ + 3584 + 256, 128), dhi(896, 0), 1>(o + 4, vf[4], vf[5], vf[6], vf[7]);
          MM<8>::rs<dlo(OFF_PL + 3584 + 512, 128), dhi(896, 0), 1>(o, vm[0], vm[1], vm[2], vm[3]);
          MM<8>::rs<dlo(OFF_PL + PL_SZ + 3584 + 512, 128), dhi(896, 0), 1>(o + 4, vm[0], vm[1], vm[2], vm[3]);
          wg_commit();
          const uint4 il = lds128(sb + OFF_INV + (lane & 3) * 16), jf = lds128(sb + OFF_INV + 64 + (lane & 3) * 16);
          const float i0 = rcpf(__uint_as_float(il.x) + __uint_as_float(il.y)), i1 = rcpf(__uint_as_float(il.z) + __uint_as_float(il.w));
          const float j0 = rcpf(__uint_as_float(jf.x) + __uint_as_float(jf.y)), j1 = rcpf(__uint_as_float(jf.z) + __uint_as_float(jf.w));
          wg_wait<0>();
          stsm4t(oa, pack2(o[0] * i0, o[1] * i1), pack2(o[2] * i0, o[3] * i1), pack2(o[4] * j0, o[5] * j1), pack2(o[6] * j0, o[7] * j1));
          O_READY(true);
          TOK_L3();
        }
        {
          float v[16];
          bar_sync(N_TURN, 256);
          mbar_waitu(bar + 8 * B_F2, par ^ 1);
          wg_fence(); proj<32, SSV, 1, 0, 10>(v, W, wbase); wg_commit();
          mbar_waitu(bar + 8 * (B_F2 + 1), par ^ 1);
          wg_fence(); proj<32, SSV, 1, 10, 14>(v, W, wbase); wg_commit();
          wg_wait<1>(); REL(B_R2, 0);
          wg_fence(); proj<32, SSV, 1, 14, 20>(v, W, wbase); wg_commit();
          mbar_waitu(bar + 8 * (B_F2 + 2), par ^ 1);
          wg_fence(); proj<32, SSV, 1, 20, 24>(v, W, wbase); wg_commit();
          wg_wait<1>(); REL(B_R2, 1);
          wg_fence(); proj<32, SSV, 1, 24, 30>(v, W, wbase); wg_commit();
          mbar_waitu(bar + 8 * (B_F2 + 3), par ^ 1);
          wg_fence(); proj<32, SSV, 1, 30, 34>(v, W, wbase); wg_commit();
          wg_wait<1>(); REL(B_R2, 2);
          wg_fence(); proj<32, SSV, 1, 34, 40>(v, W, wbase); wg_commit();
          wg_wait<0>(); REL(B_R2, 3);
#pragma unroll
          for (int j = 0; j < 8; j++) vn[j] = pack2v(v[2 * j], v[2 * j + 1]);
          keep4(vn, lane); keep4(vn + 4, lane);
          if (warp == 0) TS(18);
        }
        uint32_t ow[16];
        bar_sync(N_P, 256);
        fence_async();
#define PV16(i, off, va) { float o[8]; wg_fence(); \
          MM<16>::rs<dlo(OFF_PL + (off), 128), dhi(896, 0), 0>(o, va[0], va[1], va[2], va[3]); \
          MM<16>::rs<dlo(OFF_PL + (off) + 256, 128), dhi(896, 0), 1>(o, va[4], va[5], va[6], va[7]); \
          MM<16>::rs<dlo(OFF_PL + (off) + 512, 128), dhi(896, 0), 1>(o, vm[0], vm[1], vm[2], vm[3]); \
          wg_commit(); wg_wait<0>(); \
          _Pragma("unroll") for (int j = 0; j < 4; j++) ow[4 * (i) + j] = pack2v(o[2 * j], o[2 * j + 1]); \
          keep4(ow + 4 * (i), lane); }
        PV16(0, 0, vl) PV16(1, 1792, vl) PV16(2, PL_SZ, vf) PV16(3, PL_SZ + 1792, vf)
        const uint32_t s1 = OX_SA + (lane < 16 ? 3072 : 0), s2 = OX_SA + (lane < 16 ? 2048 : 1024);
        bar_sync(N_V, 128);
        stsm4t(s1, ow[0], ow[1], ow[2], ow[3]);
        stsm4t(s2, ow[4], ow[5], ow[6], ow[7]);
        stsm4t(s1 + PL_SZ, ow[8], ow[9], ow[10], ow[11]);
        stsm4t(s2 + PL_SZ, ow[12], ow[13], ow[14], ow[15]);
#pragma unroll
        for (int j = 0; j < 8; j++) vl[j] = vn[j];
      } else {
        uint32_t vm[4], vn[8];
        {
          float v[4];
          wg_fence(); proj<8, SSV, 0, 30, 40, 30>(v, W, wbase); wg_commit();
          proj<8, SSV, 0, 0, VS1, 30>(v, W, wbase); wg_commit();
          ARM();
          bar_sync(N_SISS, 384);
          wg_wait<1>(); bar_arrive(N_G3, 160);
          wg_fence(); proj<8, SSV, 0, VS1, 30, 30>(v, W, wbase); wg_commit();
          if (has_next) { mbar_waitu2(bar + 8 * B_F2, bar + 8 * (B_F2 + 1), par ^ 1); mbar_waitu(bar + 8 * (B_F2 + 2), par ^ 1); }
          wg_wait<0>();
          bar_arrive(N_VDONE, 160);
          vm[0] = pack2v(v[0], v[1]); vm[1] = pack2v(v[2], v[3]); vm[2] = pack2v(v[1], v[0]); vm[3] = pack2v(v[3], v[2]);
        }
        float v[16];
        {
          wg_fence(); proj<32, SSV, 1, 0, 30>(v, W, wbase); wg_commit();
          {
            float o[4];
            O_ADDR();
            bar_sync(N_PM, 192);
            if (warp == 0) TS(14);
            wg_fence();
            MM<8>::rs<dlo(OFF_PL + 3584, 128), dhi(896, 0), 0>(o, vl[0], vl[1], vl[2], vl[3]);
            MM<8>::rs<dlo(OFF_PL + 3584 + 256, 128), dhi(896, 0), 1>(o, vl[4], vl[5], vl[6], vl[7]);
            MM<8>::rs<dlo(OFF_PL + 3584 + 512, 128), dhi(896, 0), 1>(o, vm[0], vm[1], vm[2], vm[3]);
            wg_commit();
            const uint4 il = lds128(sb + OFF_INV + (lane & 3) * 16);
            const float i0 = rcpf(__uint_as_float(il.x) + __uint_as_float(il.y)), i1 = rcpf(__uint_as_float(il.z) + __uint_as_float(il.w));
            wg_wait<0>();
            stsm2t(oa, pack2(o[0] * i0, o[1] * i1), pack2(o[2] * i0, o[3] * i1));
            O_READY(lane < 16);
            TOK_L3();
          }
          if (has_next) {
            mbar_arrive_remote_if(lane < 3, rb0 + ((nA - 4 + lane) << 24) + OFF_BAR + 8 * B_R2);
            bar_sync(N_TURN, 256);
            mbar_waitu(bar + 8 * (B_F2 + 3), par ^ 1);
          }
          wg_fence(); proj<32, SSV, 1, 30, 40>(v, W, wbase); wg_commit();
          wg_wait<0>();
          if (has_next) REL(B_R2, 3);
#pragma unroll
          for (int j = 0; j < 8; j++) vn[j] = pack2v(v[2 * j], v[2 * j + 1]);
          keep4(vn, lane); keep4(vn + 4, lane);
          if (warp == 0) TS(18);
        }
        float o[16];
        bar_sync(N_P, 256);
        fence_async();
        wg_fence();
        MM<32>::rs<dlo(OFF_PL, 128), dhi(896, 0), 0>(o, vl[0], vl[1], vl[2], vl[3]);
        MM<32>::rs<dlo(OFF_PL + 256, 128), dhi(896, 0), 1>(o, vl[4], vl[5], vl[6], vl[7]);
        MM<32>::rs<dlo(OFF_PL + 512, 128), dhi(896, 0), 1>(o, vm[0], vm[1], vm[2], vm[3]);
        wg_commit();
        const uint32_t s1 = OX_SA + (lane < 16 ? 3072 : 0), s2 = OX_SA + (lane < 16 ? 2048 : 1024);
        wg_wait<0>();
        bar_sync(N_V, 128);
        stsm4t(s1, pack2(o[0], o[1]), pack2(o[2], o[3]), pack2(o[4], o[5]), pack2(o[6], o[7]));
        stsm4t(s2, pack2(o[8], o[9]), pack2(o[10], o[11]), pack2(o[12], o[13]), pack2(o[14], o[15]));
#pragma unroll
        for (int j = 0; j < 8; j++) vl[j] = vn[j];
      }
      bar_arrive(N_OX, 160);
      if (warp == 0) TS(16);
    }
    cluster_sync_all();
  } else {
    asm volatile("setmaxnreg.dec.sync.aligned.u32 32;");
    if (wg > 3) return;
    LANE_INIT();
    struct RsJob { uint32_t* gp; uint32_t la, mb; int n; };
    auto rs_prep = [&](int step, int s, int c) {
      RsJob j;
      const int u = s * nA + rank;
      j.gp = &g_part[0][0][0][0] + (uint32_t)((((step & 1) * 2 + c) * NCL + cl) * 2560 + u * 64 + lane);
      j.la = sb + OFF_TILE + c * LAND_F + LAND(s) + lane * 8;
      j.mb = bar + 8 * (B_RS + s);
      j.n = u >= 40 ? 0 : u >= 36 ? 3 : 1;
      asm volatile("" : "+l"(j.gp), "+r"(j.la));
      return j;
    };
    auto rs_sum = [&](RsJob j, int step) {
      if (j.n) {
        auto five = [&](uint32_t la) {
          uint2 p[5];
#pragma unroll
          for (int i = 0; i < 4; i++) p[i] = lds64(la + i * 256);
          asm volatile("{\n.reg .pred q;\nsetp.eq.s32 q, %3, 5;\nmov.u32 %0, 0;\nmov.u32 %1, 0;\n@q ld.shared.v2.b32 {%0,%1}, [%2];\n}"
                       : "=r"(p[4].x), "=r"(p[4].y) : "r"(la + 1024), "r"(nh) : "memory");
          return make_uint2(hadd2bf(hadd2bf(p[0].x, p[1].x), hadd2bf(hadd2bf(p[2].x, p[3].x), p[4].x)),
                            hadd2bf(hadd2bf(p[0].y, p[1].y), hadd2bf(hadd2bf(p[2].y, p[3].y), p[4].y)));
        };
        const uint32_t tag = ((step >> 1) & 1) ^ 1;
        mbar_waitw(j.mb, step & 1);
        uint2 t = five(j.la);
        if (j.n > 1) {
          const uint2 a = five(j.la + (nh == 5 ? 1280 : TILE_GRP - 1280)), b = five(j.la + TILE_GRP);
          t.x = hadd2bf(t.x, hadd2bf(a.x, b.x)); t.y = hadd2bf(t.y, hadd2bf(a.y, b.y));
        }
        const uint32_t t0 = (movm(t.x) & ~1u) | tag, t1 = (movm(t.y) & ~1u) | tag;
        asm volatile("st.relaxed.gpu.global.b32 [%0], %1;" :: "l"(j.gp), "r"(t0) : "memory");
        asm volatile("st.relaxed.gpu.global.b32 [%0], %1;" :: "l"(j.gp + 32), "r"(t1) : "memory");
      }
    };
    if (warp * nA + (int)rank < 40) {
#pragma unroll
      for (int e = LAG; e < LAG + 2; e++)
        if ((e >> 1) & 1) *reinterpret_cast<uint2*>(&g_part[(e & 1) * 2 + 1][cl][warp * nA + rank][lane * 2]) = make_uint2(1u, 1u);
      __threadfence();
    }
    cluster_sync_all();
    if (warp == 2 && ig >= 0) issue_tok(0, B_F2);
#pragma unroll 1
    for (int step = 0; step < NSTEP; step++) {
      const uint32_t par = step & 1;
      asm volatile("" : "+r"(lane));
      const bool dual = is_dual(step), has_next = step + 1 < NSTEP;
      {
        bar_sync(N_PX, dual ? 256 : 192);
        if (dual || warp >= 2) tok_softmax(sb, dual ? warp : warp - 2, lane);
        bar_arrive(N_P, 256);
        asm volatile("" : "+r"(lane));
        if (has_next) {
          if (step + 2 == LAG && lane < 20) asm volatile("prefetch.global.L2 [%0];" :: "l"(mem0 + (warp * 20 + lane) * 64));
          const int nw = ig >= 0 ? 3 : 4, j0 = warp < nw ? warp : 8;
          const int sh = dual ? 1 : 0;
          rs_sum(rs_prep(step, j0 >> sh, j0 & sh), step);
          if (warp == 0) TS(17);
          if (dual) rs_sum(rs_prep(step, (j0 + nw) >> 1, (j0 + nw) & 1), step);
          if (warp == 0) { bar_sync(N_C, 288); }
          mbar_arrive_remote_if(lane < nA, rb0 + (lane << 24) + OFF_BAR + 8 * B_LANDFREE);
          const uint32_t gap = dual ? POLL_GAPD : POLL_GAP;
          if (gap) { const uint32_t t0 = clock32(); while (clock32() - t0 < gap) {} }
#pragma unroll 1
          for (int j = j0; j < (dual ? 8 : 4); j += nw) {
            const int u = (j >> sh) * nA + rank, c = j & sh;
            if (u < UMAX && (c || step + 1 != NSEG)) {
              const uint32_t* gq = &g_part[0][0][0][0] + (uint32_t)((par * 2 + c) * NCL * 2560 + u * 64 + lane * 2);
              uint2 pa[NCL];
              POLL(pa, gq);
              deliver(pa, gq, u, c, step + 1 < NSEG ? c : 0, dual ? DS_DUAL : DS_SINGLE, step, j == 0, lane);
            }
            if (warp == 0 && j == 0) TS(13);
          }
          if (warp >= nw && (is_dual(step + 1) || (ig < 3 && step + 2 < NSTEP))) {
            issue_tok(is_dual(step + 1) ? sched_f(step + 1) : sched_l(step + 2), is_dual(step + 1) ? B_F1 : B_F2, B_R2, par ^ 1);
          }
          if (step + 1 == LAG && UMAX) {
            uint4 v[5];
#pragma unroll
            for (int i = 0; i < 5; i++) { const int t = warp * 160 + i * 32 + lane; v[i] = *reinterpret_cast<const uint4*>(mem0 + (t & 7) * DM + (t >> 3) * 8); }
            mbar_waitu(bar + 8 * B_LANDFREE, par);
#pragma unroll
            for (int i = 0; i < 5; i++)
              st_async_v4(sb + OFF_TILE + LAND_F + warp * TILE_GRP + (i * 32 + lane) * 16, v[i].x, v[i].y, v[i].z, v[i].w, bar + 8 * (B_F1 + warp));
          }
        }
      }
      if (warp == 3) {
        unsigned char* o0 = g_o + uni(step * (96 * 8192) + (head * 3 + t3) * (dual ? 8192 : 4096));
        bar_sync(N_OX, 160);
        fence_async();
        bulk_s2g_es(o0, sb + OFF_PL, 4096);
        if (dual) bulk_s2g_es(o0 + 4096, sb + OFF_PL + PL_SZ, 4096);
        asm volatile("cp.async.bulk.commit_group;" ::: "memory");
        asm volatile("cp.async.bulk.wait_group.read 0;" ::: "memory");
        __syncwarp();
        mbar_arrive_remote_if(lane < 2, (lane ? nxt : prv) + OFF_BAR + 8 * B_PLFREE);
        asm volatile("cp.async.bulk.wait_group 0;" ::: "memory");
        asm volatile("fence.proxy.async.global;" ::: "memory");
        __syncwarp();
        if (lane == 0) red_release(&g_f[F_O + (head * 3 + t3) / 5][step], 1u);
        __syncwarp();
      }
    }
    cluster_sync_all();
  }
}

__device__ __forceinline__ float gelu2(float x) {
  const float u = x * fmaf(x * x, 0.7978845608028654f * 0.044715f, 0.7978845608028654f);
  float t; asm("tanh.approx.f32 %0, %1;" : "=f"(t) : "f"(u));
  return fmaf(x, t, x); }

struct BParams {
  CUtensorMap wmap[5];
  CUtensorMap wo16;
  const __nv_bfloat16* x;
  __nv_bfloat16* out;
};
#define BO_O 0
#define BO_RES (6 * 8192)
#define OP_RES 63488
#define BO_STG (BO_RES + 2 * OP_RES)
#define BO_RING_OP (BO_STG + 16384)
#define OP_SLOT 12288
#define NS_OP 3
#define BO_H 81920
#define BO_W1 (BO_H + 16384)
#define BO_RING_MLP (BO_W1 + 81920)
#define BO_BAR 229376
#define BO_BOX (BO_BAR + 248)
#define BO_CARRY (BO_BAR + 512)
#define BO_STAT (BO_CARRY + 2048)
#define B_SMEM (BO_STAT + 256)
static_assert(B_SMEM <= 232448 && BO_RING_OP + NS_OP * OP_SLOT == BO_BAR && BO_RING_MLP + 3 * 16384 == BO_BAR && 2 * 83968 <= BO_RING_MLP, "smem");
enum { BB_W = 0, BB_FULL = 2, BB_TMP = BB_FULL + 3, BB_OFULL = BB_FULL + 5, BB_SFREE = BB_OFULL,
       BB_STAT = BB_SFREE + 6, BB_ZFREE, BB_DONE = BB_ZFREE + 3,
       BB_EMPTY, BB_START = BB_EMPTY, BB_USED = BB_EMPTY + 2, BB_NUM = BB_USED + 3 };
enum { NB_PP = 1, NB_H = 3, NB_END = 4, NB_END2 = 5, NB_STAGED = 6, NB_FREE = 8, NB_EARLY = 10, NB_LAST = 11 };

#define ACC32(d) ACC16(d), ACC16((d + 16))
#define R32S "{%0,%1,%2,%3,%4,%5,%6,%7,%8,%9,%10,%11,%12,%13,%14,%15,%16,%17,%18,%19,%20,%21,%22,%23,%24,%25,%26,%27,%28,%29,%30,%31}"
template <int N, bool H = false> struct BM;
#define DEF_BM(N, H, T, ACCM, RS_, I0, I1, I2, I3, I4, I5, I6)                                                                          \
  template <> struct BM<N, H> {                                                                                                      \
    template <int BO, int ACC> static __device__ __forceinline__ void rs(float* d, const uint32_t* a, uint32_t blo) {             \
      asm volatile("{\n.reg .b32 m;\n.reg .b64 b;\nadd.u32 m, %" #I4 ", %" #I5 ";\nmov.b64 b, {m, 0x40000040};\n"                 \
                   "wgmma.mma_async.sync.aligned.m64n" #N "k16.f32." T "." T " " RS_ ", {%" #I0 ",%" #I1 ",%" #I2 ",%" #I3 "}, b, %" #I6 ", 1, 1, 0;\n}" \
                   : ACCM(d) : "r"(a[0]), "r"(a[1]), "r"(a[2]), "r"(a[3]), "r"(blo), "n"(BO), "n"(ACC)); }                        \
    template <int AO, int BO, int ACC> static __device__ __forceinline__ void ss(float* d, uint32_t alo, uint32_t blo) {          \
      asm volatile("{\n.reg .b32 l, m;\n.reg .b64 a, b;\nadd.u32 l, %" #I0 ", %" #I1 ";\nadd.u32 m, %" #I2 ", %" #I3 ";\n"        \
                   "mov.b64 a, {l, 0x40000040};\nmov.b64 b, {m, 0x40000040};\n"                                                   \
                   "wgmma.mma_async.sync.aligned.m64n" #N "k16.f32." T "." T " " RS_ ", a, b, %" #I4 ", 1, 1, 1, 0;\n}"             \
                   : ACCM(d) : "r"(alo), "n"(AO), "r"(blo), "n"(BO), "n"(ACC)); }                                                 \
  };
DEF_BM(32, false, "bf16", ACC16, R16S, 16, 17, 18, 19, 20, 21, 22)
DEF_BM(64, false, "bf16", ACC32, R32S, 32, 33, 34, 35, 36, 37, 38)
DEF_BM(32, true, "f16", ACC16, R16S, 16, 17, 18, 19, 20, 21, 22)
DEF_BM(64, true, "f16", ACC32, R32S, 32, 33, 34, 35, 36, 37, 38)
#define DESC_LO(off) (((SMEM0 + (off)) >> 4) | (1u << 16))

__device__ __forceinline__ uint32_t ld_relaxed(const uint32_t* p) { uint32_t v; asm volatile("ld.relaxed.gpu.global.b32 %0, [%1];" : "=r"(v) : "l"(p) : "memory"); return v; }
__device__ __forceinline__ int fmask(int r) { return (r < NSEG) | ((r >= LAG && r < NSTEP) << 1); }
__device__ __forceinline__ int bmask(int r) { return (r <= NSEG) | ((r >= LAG) << 1); }
__device__ __forceinline__ uint32_t rtarget(int mask) { return mask == 3 ? 64 : 32; }
__device__ __forceinline__ void warp_signal(uint32_t* p, int lane) {
  __syncwarp();
  asm volatile("{\n.reg .pred q;\nsetp.eq.u32 q, %1, 0;\n@q red.release.gpu.global.add.u32 [%0], 1;\n}" :: "l"(p), "r"(lane) : "memory");
}
__device__ __forceinline__ uint32_t pack2h(float lo, float hi) { uint32_t r; asm("cvt.rn.f16x2.f32 %0, %1, %2;" : "=r"(r) : "f"(hi), "f"(lo)); return r; }
template <bool H> __device__ __forceinline__ uint32_t pk(float lo, float hi) { return H ? pack2h(lo, hi) : pack2(lo, hi); }
template <int N, bool H> __device__ __forceinline__ void stage_out(const float* d, uint32_t dst, int warp, int lane) {
  const uint32_t sa = dst + ((lane >> 4) * 8 + (lane & 7)) * 128 + (((2 * warp + ((lane >> 3) & 1)) ^ (lane & 7)) << 4);
#pragma unroll
  for (int m = 0; m < N / 16; m++)
    stsm4t(sa + m * 2048, pk<H>(d[8 * m], d[8 * m + 1]), pk<H>(d[8 * m + 2], d[8 * m + 3]), pk<H>(d[8 * m + 4], d[8 * m + 5]), pk<H>(d[8 * m + 6], d[8 * m + 7]));
}
template <int N> __device__ __forceinline__ void acc_live(float* d) {
#pragma unroll
  for (int i = 0; i < N / 2; i++) asm volatile("" : "+f"(d[i]) :: "memory");
}
struct Ring {
  uint32_t sl, ph;
  template <int NS> __device__ __forceinline__ void step() { if (++sl == NS) { sl = 0; ph ^= 1; } }
};

#define LOCKSTEP 0
#define KOFF(x) (((x) >> 2) * (N * 8) + ((x) & 3) * 2)
template <int N, int P>
__device__ __forceinline__ void op_pass(const uint32_t* W, uint32_t bar, uint32_t alo, uint32_t blo, uint32_t xlo, bool x2, Ring& rg, int wg, int warp, int lane, int r) {
  float acc[N / 2];
  const uint32_t tlo = DESC_LO(BO_RING_OP) + uni(rg.sl) * (OP_SLOT / 16);
  if (P == 0) mbar_waitu(bar + 8 * BB_OFULL, r & 1);
  CTS(5 * P);
  if (!LOCKSTEP || P > 1 || P == wg) bar_sync(NB_PP + wg, 256);
  wg_fence();
#define OP_R(x) BM<N>::template rs<KOFF(4 * (x >> 1) + (x & 1)), (x != 0)>(acc, W + 32 * P + 4 * x, blo);
#define OP_S(x) BM<N>::template ss<(6 * P + x) * 128, KOFF(4 * (x >> 1) + 2 + (x & 1)), 1>(acc, alo, blo);
#define OP_T(x) BM<N>::template ss<x * 128, KOFF(14 + x), 1>(acc, tlo, blo);
  OP_R(0) OP_S(0) OP_R(1) OP_S(1) OP_R(2) OP_S(2) OP_R(3) OP_S(3)
  if (P == 0) mbar_waitu(bar + 8 * (BB_OFULL + 1), r & 1);
  if (P == 4) wg_commit();
  OP_R(4) OP_S(4) OP_R(5) OP_S(5)
  if (P == 1 && x2) BM<N>::template ss<30 * 128, KOFF(20), 1>(acc, alo, xlo);
  if (P == 4) { wg_commit(); wg_wait<1>(); bar_arrive(NB_EARLY, 288); CTS(21); wg_fence(); }
  mbar_waitu(bar + 8 * (BB_FULL + rg.sl), rg.ph);
  OP_R(6) OP_T(0) OP_R(7) OP_T(1)
  if (P == 0) mbar_waitu(bar + 8 * (BB_OFULL + 2), r & 1);
  OP_T(2) OP_T(3)
  if (P == 0) BM<N>::template rs<KOFF(20), 1>(acc, W + 160, xlo);
  OP_T(4) OP_T(5)
  wg_commit();
  if (!LOCKSTEP || P) bar_arrive(NB_PP + 1 - wg, 256);
  CTS(5 * P + 2);
  bar_sync(NB_FREE + wg, 160);
  wg_wait<0>();
  acc_live<N>(acc);
  if (P == 4) bar_arrive(NB_LAST, 288);
  mbar_arrive_if(lane == 0, bar + 8 * (BB_USED + rg.sl));
  CTS(5 * P + 3);
  stage_out<N, false>(acc, SMEM0 + BO_STG + wg * 8192, warp, lane);
  bar_arrive(NB_STAGED + wg, 160);
  CTS(5 * P + 4);
  rg.step<NS_OP>(); rg.step<NS_OP>();
}
template <int N>
__device__ __forceinline__ void op_round(const uint32_t* W, uint32_t bar, uint32_t alo, uint32_t blo, uint32_t xlo, bool x2, Ring& rg, int wg, int warp, int lane, int r) {
  op_pass<N, 0>(W, bar, alo, blo, xlo, x2, rg, wg, warp, lane, r);
  op_pass<N, 1>(W, bar, alo, blo, xlo, x2, rg, wg, warp, lane, r);
  op_pass<N, 2>(W, bar, alo, blo, xlo, x2, rg, wg, warp, lane, r);
  op_pass<N, 3>(W, bar, alo, blo, xlo, x2, rg, wg, warp, lane, r);
  op_pass<N, 4>(W, bar, alo, blo, xlo, x2, rg, wg, warp, lane, r);
}
__device__ __forceinline__ void carry_in(uint32_t sb, int wg, int warp, int lane) {
  const int row = (lane >> 1) & 3;
  if (lane < 16) {
    const uint4 v = lds128(sb + BO_CARRY + (wg * 4 + warp) * 256 + lane * 16);
    sts128(sb + BO_H + wg * 8192 + (lane >> 3) * 4096 + row * 128 + (((2 * warp + (lane & 1)) ^ row) << 4), v.x, v.y, v.z, v.w);
  }
  __syncwarp();
}
#define STAGGER 0
template <int N, int Z>
__device__ __forceinline__ void p1_pair(float* acc, const uint32_t* W, uint32_t bar, uint32_t alo, uint32_t blo, int lane, int r) {
  mbar_waitu(bar + 8 * (BB_FULL + Z), r & 1);
  CTS(40 + Z);
  wg_fence();
#define P1_B(k) \
  BM<N, true>::template rs<(2 * Z % 3) * 1024 + k * 512, (2 * Z + k != 0)>(acc, W + 16 * Z + 8 * k, blo); \
  BM<N, true>::template ss<BO_W1 / 16 + (2 * Z + k) * 512, (2 * Z % 3) * 1024 + k * 512 + 4, 1>(acc, alo, blo); \
  BM<N, true>::template rs<(2 * Z % 3) * 1024 + k * 512 + 2, 1>(acc, W + 16 * Z + 8 * k + 4, blo); \
  BM<N, true>::template ss<BO_W1 / 16 + (2 * Z + k) * 512 + 128, (2 * Z % 3) * 1024 + k * 512 + 6, 1>(acc, alo, blo);
  P1_B(0)
  if (Z == 1 || Z == 2) { wg_commit(); wg_wait<1>(); mbar_arrive_if(lane == 0, bar + 8 * (BB_EMPTY + Z - 1)); wg_fence(); }
  P1_B(1)
  wg_commit();
}
template <int N>
__device__ __forceinline__ void phase1(const uint32_t* W, uint32_t sb, uint32_t alo, int half, int wg, int warp, int lane, int off, int r, uint32_t sph) {
  float acc[N / 2];
  const uint32_t bar = sb + BO_BAR, blo = DESC_LO(BO_RING_MLP) + half * 256;
  CTS(30);
  p1_pair<N, 0>(acc, W, bar, alo, blo, lane, r);
  p1_pair<N, 1>(acc, W, bar, alo, blo, lane, r);
  p1_pair<N, 2>(acc, W, bar, alo, blo, lane, r);
  mbar_waitu(bar + 8 * (BB_SFREE + 4 + wg), (r + 1) & 1);
  carry_in(sb, wg, warp, lane);
  if (STAGGER && wg) bar_sync(NB_PP + 1, 256);
  p1_pair<N, 3>(acc, W, bar, alo, blo, lane, r);
  p1_pair<N, 4>(acc, W, bar, alo, blo, lane, r);
  if (STAGGER && !wg) bar_arrive(NB_PP + 1, 256);
  const int c = (lane >> 3) & 1, i0 = (lane >> 4) * 8 + (lane & 7) + off;
  uint32_t a0 = sb + BO_H + wg * 8192 + half * 4096 + i0 * 128 + (((2 * warp + c) ^ (i0 & 7)) << 4);
  uint32_t a1 = i0 >= 16 ? sb + BO_CARRY + (wg * 4 + warp) * 256 + half * 128 + (i0 - 16) * 32 + c * 16 : a0 + 2048, a3 = a1 + (i0 >= 16 ? 128 : 4096);
  asm volatile("" : "+r"(a0), "+r"(a1), "+r"(a3));
  mbar_waitu(bar + 8 * BB_STAT, sph);
  const uint32_t sa = sb + BO_STAT + half * 128 + (lane & 3) * 32;
  uint4 t[2] = {lds128(sa), lds128(sa + 16)};
  wg_wait<0>();
  acc_live<N>(acc);
  CTS(32);
#pragma unroll
  for (int m = 0; m < N / 16; m++) {
    const float s0 = __uint_as_float(t[m & 1].x), s1 = __uint_as_float(t[m & 1].y), s2 = __uint_as_float(t[m & 1].z), s3 = __uint_as_float(t[m & 1].w);
    float* d = acc + 8 * m;
    d[0] *= s0; d[1] *= s1; d[2] *= s0; d[3] *= s1; d[4] *= s2; d[5] *= s3; d[6] *= s2; d[7] *= s3;
    if (m + 2 < N / 16) t[m & 1] = lds128(sa + 128 + m * 16);
#pragma unroll
    for (int j = 0; j < 8; j++) d[j] = gelu2(d[j]);
  }
#pragma unroll
  for (int m = 0; m < N / 16; m++)
    stsm4t(m == 1 ? a1 : m == 3 ? a3 : a0 + m * 2048, pack2(acc[8 * m], acc[8 * m + 1]), pack2(acc[8 * m + 2], acc[8 * m + 3]), pack2(acc[8 * m + 4], acc[8 * m + 5]), pack2(acc[8 * m + 6], acc[8 * m + 7]));
}
template <int N, int P>
__device__ __forceinline__ void p2_pass(const uint32_t* W, uint32_t bar, uint32_t alo, uint32_t blo, int wg, int warp, int lane, int r) {
  float acc[N / 2];
  CTS(5 * P);
  if (P || wg) bar_sync(NB_PP + wg, 256);
  wg_fence();
  BM<N>::template rs<0, 0>(acc, W + 80 + 16 * P, blo);      BM<N>::template ss<P * 1024, 512, 1>(acc, alo, blo);
  BM<N>::template rs<2, 1>(acc, W + 84 + 16 * P, blo);      BM<N>::template ss<P * 1024 + 128, 514, 1>(acc, alo, blo);
  BM<N>::template rs<4, 1>(acc, W + 88 + 16 * P, blo);      BM<N>::template ss<P * 1024 + 512, 516, 1>(acc, alo, blo);
  BM<N>::template rs<6, 1>(acc, W + 92 + 16 * P, blo);      BM<N>::template ss<P * 1024 + 640, 518, 1>(acc, alo, blo);
  wg_commit();
  if (P < 4 || !wg) bar_arrive(NB_PP + 1 - wg, 256);
  CTS(5 * P + 2);
  if (P == 2 || P == 3) mbar_waitu(bar + 8 * (BB_SFREE + 2 * (P - 2) + wg), r & 1);
  wg_wait<0>();
  acc_live<N>(acc);
  if (P == 4) bar_sync(NB_H, 256);
  CTS(5 * P + 3);
  stage_out<N, true>(acc, SMEM0 + (P == 4 ? BO_H : BO_RING_MLP + (2 - (P & 1)) * 16384) + wg * 8192, warp, lane);
  bar_arrive(NB_STAGED + (P == 4 ? 4 : 2 * (P & 1)) + wg, 160);
  CTS(5 * P + 4);
}
template <int N>
__device__ __forceinline__ void phase2(const uint32_t* W, uint32_t bar, uint32_t alo, uint32_t blo, int wg, int warp, int lane, int r) {
  p2_pass<N, 0>(W, bar, alo, blo, wg, warp, lane, r);
  p2_pass<N, 1>(W, bar, alo, blo, wg, warp, lane, r);
  p2_pass<N, 2>(W, bar, alo, blo, wg, warp, lane, r);
  p2_pass<N, 3>(W, bar, alo, blo, wg, warp, lane, r);
  p2_pass<N, 4>(W, bar, alo, blo, wg, warp, lane, r);
}

__device__ __forceinline__ void ldg4(uint32_t* v, const void* p) {
  asm volatile("ld.relaxed.gpu.global.v4.u32 {%0,%1,%2,%3}, [%4];" : "=r"(v[0]), "=r"(v[1]), "=r"(v[2]), "=r"(v[3]) : "l"(p) : "memory"); }
__device__ __forceinline__ void stg4(void* p, const uint32_t* v) {
  asm volatile("st.global.v4.u32 [%0], {%1,%2,%3,%4};" :: "l"(p), "r"(v[0]), "r"(v[1]), "r"(v[2]), "r"(v[3]) : "memory"); }
struct RowPtr {
  unsigned char *p, *q, *t;
  __device__ __forceinline__ void ld(uint32_t* v, int o) const {
    ldg4(v, p + o); ldg4(v + 4, q + o);
    asm volatile("ld.relaxed.gpu.global.v2.u32 {%0,%1}, [%2];" : "=r"(v[8]), "=r"(v[9]) : "l"(t + o) : "memory");
  }
  template <bool H> __device__ __forceinline__ void st(const float* v, float a, float b, int o) const {
    uint32_t w[10];
#pragma unroll
    for (int i = 0; i < 10; i++) w[i] = pk<H>(fmaf(v[2 * i], a, b), fmaf(v[2 * i + 1], a, b));
    stg4(p + o, w); stg4(q + o, w + 4);
    asm volatile("st.global.v2.u32 [%0], {%1,%2};" :: "l"(t + o), "r"(w[8]), "r"(w[9]) : "memory");
  }
};
__device__ __forceinline__ RowPtr row_img(int r, int n, int lane) {
  unsigned char* b = &g_acc[0][r % RD][n * 128];
  unsigned char* p = b + (uint32_t)((lane >> 3) * 8192 + (((lane ^ n) & 7) << 4));
  return {p, p + 32768, b + (uint32_t)(65536 + (lane >> 4) * 8192 + ((((lane >> 1) ^ n) & 7) << 4) + (lane & 1) * 8)};
}
__device__ __forceinline__ RowPtr row_ext(const void* lin, bool xn, int layer, int tok, int lane) {
  unsigned char* b = xn ? reinterpret_cast<unsigned char*>(&g_xn[layer][0]) + (uint32_t)((tok >> 5) * 40960 + ((tok >> 3) & 3) * 2560 + (tok & 7) * 16)
                        : (unsigned char*)lin + (uint32_t)(tok * 1280);
  return {b + (uint32_t)(xn ? lane * 128 + (lane >= 20 ? 7680 : 0) : lane * 16),
          b + (uint32_t)(xn ? lane * 128 + 4096 + 7680 + (lane >= 8 ? 7680 : 0) + (lane >= 28 ? 7680 : 0) : lane * 16 + 512),
          b + (uint32_t)(xn ? (lane >> 1) * 128 + (lane & 1) * 8 + 8192 + 3 * 7680 : lane * 8 + 1024)};
}
__device__ __forceinline__ float2 h2f(uint32_t w) {
  float2 f; asm("{\n.reg .f16 l, h;\nmov.b32 {l, h}, %2;\ncvt.f32.f16 %0, l;\ncvt.f32.f16 %1, h;\n}" : "=f"(f.x), "=f"(f.y) : "r"(w)); return f; }
__device__ __forceinline__ float rsq(float x) { float y; asm("rsqrt.approx.ftz.f32 %0, %1;" : "=f"(y) : "f"(x)); return y; }
__device__ __forceinline__ void red_if(uint32_t v, const void* a) {
  asm volatile("{\n.reg .pred q;\nsetp.ne.u32 q, %1, 0;\n@q red.relaxed.gpu.global.add.u32 [%0], %1;\n}" :: "l"(a), "r"(v) : "memory"); }
__device__ __forceinline__ uint32_t dep0(uint32_t w, int lane) { uint32_t z; asm volatile("shr.b32 %0, %1, %2;" : "=r"(z) : "r"(w), "r"(lane + 32)); return z; }
__device__ __forceinline__ int lane_of(uint32_t w) {
  int lane; asm volatile("{\n.reg .u32 t;\nmov.u32 t, %%laneid;\nshr.u32 %0, %1, 20;\nadd.u32 %0, %0, t;\n}" : "=r"(lane) : "r"(w)); return lane; }
#define BUF (RD * TILE_B)
__device__ __forceinline__ int await(uint32_t v, const uint32_t* p, uint32_t target, bool lazy) {
  int n = 0;
  while (!__all_sync(~0u, v >= target)) {
    if (lazy) __nanosleep(200);
    if (++n > SPIN_LIMIT) FAIL();
    v = ld_relaxed(p);
  }
  asm volatile("fence.acquire.gpu;" ::: "memory");
  return lane_of(v);
}
template <int W> __device__ __forceinline__ void sum2(float& s, float& q, int lane) {
  const bool up = lane & (W / 2);
  float e = (up ? q : s) + __shfl_xor_sync(~0u, up ? s : q, W / 2);
#pragma unroll
  for (int o = W / 4; o; o >>= 1) e += __shfl_xor_sync(~0u, e, o);
  const float f = __shfl_xor_sync(~0u, e, W / 2);
  s = up ? f : e; q = up ? e : f;
}
template <int TYPE>
__device__ __forceinline__ void rrow(int r, int row, int tok, int lane, const uint32_t* go, int role, const __nv_bfloat16* x) {
  const int half = TYPE ? 0 : row >> 5;
  float v[20];
  {
    float2 st = make_float2(1.f, 0.f);
    uint32_t a[10], c[10], u[10], sh = 16;
    if (TYPE == 2) row_img(r + RD - ((row & 31) < 2), (row & 32) + ((row - 2) & 31), lane).ld(u, 4 * BUF);
    else row_ext(x, half, 1, tok, lane).ld(u, 0);
    if (TYPE == 2 || (TYPE == 0 && half))
      asm volatile("ld.relaxed.gpu.global.v2.f32 {%0,%1}, [%2];" : "=f"(st.x), "=f"(st.y) : "l"(g_stat + tok) : "memory");
    RowPtr ap = row_img(r, row, lane);
    const uint32_t g0 = TYPE != 3 ? ld_relaxed(go) : 0;
    if (TYPE == 2) {
      ap.ld(c, 2 * BUF);
      uint32_t z = dep0(c[9], lane);
#pragma unroll
      for (int i = 0; i < 10; i++) {
        const float2 g = h2f(u[i] | z), h = h2f(c[i] | z);
        v[2 * i] = fmaf(h.x, 0.5f, fmaf(g.x, st.x, st.y)); v[2 * i + 1] = fmaf(h.y, 0.5f, fmaf(g.y, st.x, st.y));
        if (i & 1) z = dep0(__float_as_uint(v[2 * i]) | __float_as_uint(v[2 * i + 1]), lane);
      }
    }
    if (TYPE != 3) {
      asm volatile("" : "+l"(ap.p), "+l"(ap.t));
      ap.q = ap.p + 32768;
      lane = await(g0, go, NOP * NW12 * NW34, false); BTS2(r, 8 + 2 * TYPE); RTS(0);
      ap.ld(a, TYPE ? 3 * BUF : 0);
    }
    if (TYPE == 0) {
      ap.ld(c, BUF);
      const uint32_t one = 0x3f803f80u | dep0(c[9], lane);
#pragma unroll
      for (int i = 0; i < 10; i++) asm volatile("fma.rn.bf16x2 %0, %0, %1, %2;" : "+r"(a[i]) : "r"(one), "r"(c[i]));
      sh |= dep0(a[9], lane);
    }
    const float k = TYPE == 2 ? __uint_as_float(0x3f000000u | dep0(a[9], lane)) : 0.f;
#pragma unroll
    for (int i = 0; i < 10; i++) {
      if (TYPE == 2) { const float2 h = h2f(a[i]); v[2 * i] = fmaf(h.x, k, v[2 * i]); v[2 * i + 1] = fmaf(h.y, k, v[2 * i + 1]); continue; }
      float p = __uint_as_float(u[i] << sh), q = __uint_as_float(u[i] & (0xffffu << sh));
      if (TYPE == 0) { p = fmaf(p, st.x, st.y) + bf_lo(a[i]); q = fmaf(q, st.x, st.y) + bf_hi(a[i]); }
      v[2 * i] = p; v[2 * i + 1] = q;
    }
  }
  RTSD(1, v[19]);
  float rs, mr;
  {
    float s = 0.f, q = 0.f;
#pragma unroll
    for (int i = 0; i < 5; i++) {
      s += (v[4 * i] + v[4 * i + 1]) + (v[4 * i + 2] + v[4 * i + 3]);
      q += fmaf(v[4 * i], v[4 * i], v[4 * i + 1] * v[4 * i + 1]) + fmaf(v[4 * i + 2], v[4 * i + 2], v[4 * i + 3] * v[4 * i + 3]);
    }
    sum2<32>(s, q, lane);
    const float mean = s * (1.f / DM), var = fmaxf(q * (1.f / DM) - mean * mean, 0.f);
    rs = rsq(var + 1e-5f);
    float sd = (var + 1e-5f) * rs;
    RTSD(2, rs);
    if (TYPE == 0) {
      row_img(r + ((row & 31) >= 30), (row & 32) + ((row + 2) & 31), lane).st<true>(v, 2.f * rs, -2.f * mean * rs, 2 * BUF);
      const float v2 = fmaf(var * rs, rs, 1e-5f), r2 = rsq(v2);
      rs *= r2; sd *= v2 * r2;
    }
    mr = -mean * rs;
    if (TYPE != 3 && lane == 0) g_stat[tok] = make_float2(sd, mean);
  }
  if (TYPE) row_ext(nullptr, true, TYPE == 2, tok, lane).template st<false>(v, rs, mr, 0);
  else row_img(r, row, lane).st<true>(v, rs, mr, 4 * BUF);
}
__device__ __forceinline__ void r2rows(int r, int row, int lane) {
  const int n = row + (lane >> 4);
  const unsigned char* ap = &g_acc[2][r % RD][0] + (uint32_t)(n * 128 + ((lane >> 3) & 1) * 8192 + (((lane ^ n) & 7) << 4));
  uint32_t a[20];
#pragma unroll
  for (int i = 0; i < 5; i++) ldg4(a + 4 * i, ap + i * 16384);
  const uint32_t z = dep0(a[19], lane);
  float s = 0.f, q = 0.f, q2 = 0.f;
#pragma unroll
  for (int i = 0; i < 20; i++) { const float2 h = h2f(a[i] | z); s += h.x + h.y; q = fmaf(h.x, h.x, q); q2 = fmaf(h.y, h.y, q2); }
  q += q2;
  sum2<16>(s, q, lane);
  const float mean = s * (0.5f / DM), rs = rsq(fmaxf(q * (0.25f / DM) - mean * mean, 0.f) + 1e-5f);
  if ((lane & 15) == 0) asm volatile("st.relaxed.gpu.global.u32 [%0], %1;" :: "l"(&g_st2[r % RD][n]), "r"((__float_as_uint(0.5f * rs) & ~127u) | (r + 1)) : "memory");
}
__device__ __forceinline__ void r3rows(int r, int row, int tok, int lane, __nv_bfloat16* out) {
  const int n = row + (lane >> 4), m = 32 + ((n - 2) & 31);
  const unsigned char* ap = &g_acc[0][r % RD][0] + (uint32_t)(n * 128 + ((lane >> 3) & 1) * 8192 + (((lane ^ n) & 7) << 4));
  const unsigned char* zp = &g_acc[4][(r + RD - (row == 32)) % RD][0] + (uint32_t)(m * 128 + ((lane >> 3) & 1) * 8192 + (((lane ^ m) & 7) << 4));
  unsigned char* op = reinterpret_cast<unsigned char*>(out) + (uint32_t)((tok + (lane >> 4)) * 1280 + (lane & 15) * 16);
  float2 st;
  asm volatile("ld.relaxed.gpu.global.v2.f32 {%0,%1}, [%2];" : "=f"(st.x), "=f"(st.y) : "l"(g_stat + tok + (lane >> 4)) : "memory");
#pragma unroll
  for (int i0 = 0; i0 < 5; i0 += 2) {
    uint32_t a[8], c[8], u[8];
#pragma unroll
    for (int i = 0; i < (i0 < 4 ? 2 : 1); i++) { ldg4(a + 4 * i, ap + 3 * BUF + (i0 + i) * 16384); ldg4(c + 4 * i, ap + 2 * BUF + (i0 + i) * 16384); ldg4(u + 4 * i, zp + (i0 + i) * 16384); }
    uint32_t z = dep0(u[i0 < 4 ? 7 : 3], lane);
#pragma unroll
    for (int i = 0; i < (i0 < 4 ? 8 : 4); i++) {
      const float2 h = h2f(a[i] | z), e = h2f(c[i] | z), g = h2f(u[i] | z);
      a[i] = pack2(fmaf(h.x + e.x, 0.5f, fmaf(g.x, st.x, st.y)), fmaf(h.y + e.y, 0.5f, fmaf(g.y, st.x, st.y)));
      if (i & 1) z = dep0(a[i], lane);
    }
#pragma unroll
    for (int i = 0; i < (i0 < 4 ? 2 : 1); i++) stg4(op + (i0 + i) * 256, a + 4 * i);
  }
}
template <int TYPE>
__device__ __forceinline__ void rloop(int row, int cp, int role, const __nv_bfloat16* x, __nv_bfloat16* out) {
  constexpr int ST = TYPE == 4 ? 2 : TYPE;
  const int r0 = row & 32 ? LAG : 0;
  uint32_t v = 0;
#pragma unroll 1
  for (int r = r0; r < r0 + NSEG + (TYPE > 0); r++) {
    const int tok = (r - r0) * 32 + (row & 31) - (TYPE ? 2 : 0);
    const bool valid = TYPE == 0 || (unsigned)tok < S_LEN;
    const uint32_t* go = &g_f[F_R1 + 4 * ST + cp][r];
    const uint32_t* first = TYPE == 2 ? &g_f[F_R2 + cp][r] : TYPE ? go : (const uint32_t*)&g_xready[NSEG + r - r0][0];
    if constexpr (TYPE == 1 || TYPE == 4) {
      const int lane = await(v, go, NOP * NW12 * NW34, false);
      BTS2(r, 8 + 2 * ST); RTS(0);
      if (TYPE == 1) { r2rows(r, row, lane); BTS2(r, 11); continue; }
      if (valid) r3rows(r, row, tok, lane, out);
    } else {
      if (TYPE || row >= 32) await(v, first, TYPE ? NOP * NW12 * NW34 : 32, true);
      if (valid) rrow<TYPE>(r, row, tok, lane_of(r), go, role, x);
    }
    const int lane = lane_of(r);
    const void* f = lane ? (const void*)&g_xready[NSEG + (tok >> 5)][0] : (const void*)&g_f[TYPE ? F_DONE : F_Z][r];
    asm volatile("" : "+l"(f));
    __syncwarp();
    RTS(3);
    v = ld_relaxed(first + (TYPE ? 1 : 8));
    asm volatile("fence.release.gpu;" ::: "memory");
    RTS(4);
    red_if(lane == 0 || (TYPE == 2 && lane == 1 && valid) ? (TYPE & 5 ? 2 : 1) : 0, f);
    RTS(5);
    RTS_OUT();
    BTS2(r, 9 + 2 * ST);
  }
}

#define RSLOW 1
#define RNEAR 20
#define W_DELAY 0
#define BULK_ADD(T, dst, src, len) asm volatile("{\n.reg .pred e;\nelect.sync _|e, 0xffffffff;\n@e cp.reduce.async.bulk.global.shared::cta.bulk_group.add.noftz." T " [%0], [%1], %2;\n}" \
                                               :: "l"(dst), "r"(src), "r"(len) : "memory")
#define COMMIT() asm volatile("cp.async.bulk.commit_group;" ::: "memory")
#define DRAINED(n) do { asm volatile("cp.async.bulk.wait_group.read " #n ";" ::: "memory"); __syncwarp(); } while (0)
#define WRITTEN() do { asm volatile("cp.async.bulk.wait_group 0;\nfence.proxy.async.global;" ::: "memory"); __syncwarp(); } while (0)
__device__ __forceinline__ void wait_flags(const uint32_t* p, uint32_t target) {
  int n = 0;
  while (!__all_sync(~0u, ld_relaxed(p) >= target)) { if (++n > SPIN_LIMIT) FAIL(); }
  asm volatile("fence.acquire.gpu;" ::: "memory");
  asm volatile("fence.proxy.async.global;" ::: "memory");
}
__global__ void __launch_bounds__(512, 1) bworker_kernel(const __grid_constant__ BParams P) {
  extern __shared__ __align__(1024) unsigned char smem_raw[];
  const uint32_t sb = SMEM0, bar = sb + BO_BAR;
  const int wg = __shfl_sync(~0u, threadIdx.x >> 7, 0), warp = __shfl_sync(~0u, (threadIdx.x >> 5) & 3, 0);
  if (threadIdx.x == 0) {
    if (smem_u32(smem_raw) != SMEM0) FAIL();
    uint32_t smid; asm volatile("mov.u32 %0, %%smid;" : "=r"(smid));
#define POLICY 0
    const bool lone = ld_relaxed(&g_tpc[(smid >> 1) & 127]) == 0, far = lone && (smid < 64 || smid >= 124);
    int kind = far ? 0 : 2;
    if (POLICY == 0 && !far) { const uint32_t n = atomicAdd(&g_f[F_MISC][lone ? 35 : 36], 1u); kind = lone ? (n ? 0 : 2) : n < NW12 ? 1 : 2; }
    if (POLICY == 1) kind = far ? (!(smid & 1) && smid <= 124 ? 1 : 0) : (lone || (smid & 1 && atomicAdd(&g_f[F_MISC][35], 1u) < 4)) ? 0 : 2;
    uint32_t i;
    while ((i = atomicAdd(&g_f[F_MISC][32 + kind], 1u)) >= (kind == 0 ? NOP : kind == 1 ? NW12 : NW34)) kind = (kind + 1) % 3;
    const bool op = kind == 0;
    const bool slow = RSLOW ? far : op;
    const uint32_t o = atomicAdd(&g_f[F_MISC][37 + slow], 1u);
    sts64(sb + BO_BOX, i + (kind == 0 ? 0 : kind == 1 ? NOP : NOP + NW12), slow ? NBC - 1 - o : o);
    for (int k = 0; k < BB_NUM; k++) mbar_init(bar + 8 * k, k >= BB_USED ? 4 : k >= BB_EMPTY ? 8 : k >= BB_ZFREE ? 2 : 1);
    asm volatile("fence.mbarrier_init.release.cluster;" ::: "memory");
  }
  if (threadIdx.x < 144) { const uint32_t one = threadIdx.x < 128 ? 0u : 0x3f800000u; sts128(sb + BO_CARRY + threadIdx.x * 16, one, one, one, one); }
  fence_async();
  __syncthreads();
  const int role = uni(lds32(sb + BO_BOX));
  const bool op = role < NOP, w12 = role < NOP + NW12;
  const int j = op ? role : w12 ? role - NOP : role - NOP - NW12;
  const int rot = op ? (j ? 2 * ((j + 1) % 5) : 0) : 2 * (j % 5);
  if (wg == 3) {
    asm volatile("setmaxnreg.dec.sync.aligned.u32 24;");
    LANE_INIT();
    if (warp < 2) {
      auto announce = [&](int r) {
        const uint32_t* f = &g_f[(op ? F_R1 : w12 ? F_R2 : F_R3) + (lane & 3)][r];
        asm volatile("" : "+l"(f));
        if (warp == 0) { mbar_arrive_if(lane == 0, bar + 8 * BB_DONE); return; }
        mbar_waitw(bar + 8 * BB_DONE, r & 1);
        PTS(60);
        asm volatile("fence.release.gpu;" ::: "memory");
        red_if(lane >= 4 ? 0 : op ? NW12 * NW34 : w12 ? NOP * NW34 : NOP * NW12, f);
        PTS(61);
        BTS(r, 4);
      };
      if (op) {
        int mt = rot + warp;
        bar_arrive(NB_FREE + warp, 160);
#pragma unroll 1
        for (int r = 0; r < NSTEP; r++) {
          const uint32_t len = fmask(r) == 3 ? 8192 : 4096;
          unsigned char* acc = &g_acc[j & 1][r % RD][fmask(r) == 2 ? 4096 : 0];
#pragma unroll 1
          for (int p = 0; p < 5; p++) {
            bar_sync(NB_STAGED + warp, 160);
            PTS(50 + 2 * p + warp);
            fence_async();
            BULK_ADD("bf16", acc + mt * 8192, sb + BO_STG + warp * 8192, len);
            COMMIT();
            PTS(64 + 50 + 2 * p + warp);
            mt = mt >= 8 ? mt - 8 : mt + 2;
            DRAINED(0);
            bar_arrive(NB_FREE + warp, 160);
          }
          WRITTEN();
          announce(r);
        }
      } else {
#pragma unroll 1
        for (int r = 0; r < NR; r++) {
          const uint32_t len = bmask(r) == 3 ? 8192 : 4096;
          unsigned char* acc = &g_acc[w12 ? 2 : 3][r % RD][bmask(r) == 2 ? 4096 : 0];
          int mt = rot + warp;
#pragma unroll 1
          for (int p = 0; p < 5; p++) {
            bar_sync(NB_STAGED + (p == 4 ? 4 : 2 * (p & 1)) + warp, 160);
            PTS(50 + 2 * p + warp);
            fence_async();
            BULK_ADD("f16", acc + mt * 8192, sb + (p == 4 ? BO_H : BO_RING_MLP + (2 - (p & 1)) * 16384) + warp * 8192, len);
            COMMIT();
            PTS(64 + 50 + 2 * p + warp);
            mt = mt >= 8 ? mt - 8 : mt + 2;
            if (p == 4) break;
            DRAINED(1);
            mbar_arrive_if(lane == 0, bar + 8 * (p == 1 || p == 2 ? BB_SFREE + 2 * (p - 1) + warp : BB_ZFREE + (p >> 1)));
            if (p == 3) { DRAINED(0); mbar_arrive_if(lane == 0, bar + 8 * (BB_ZFREE + 2)); }
          }
          WRITTEN();
          mbar_arrive_if(lane == 0, bar + 8 * (BB_SFREE + 4 + warp));
          announce(r);
        }
      }
    } else {
      auto clear = [&](int r) {
#pragma unroll 1
        for (int c = j; c < (op && r + 1 < NSTEP ? 40 : 80); c += op ? NOP : NW34)
          bulk_s2g_e(&g_acc[op ? 3 : c / 40][(r + (op ? c / 40 : 0)) % RD][c % 40 * 2048], sb + BO_CARRY, 2048);
        COMMIT();
      };
      if (op && warp == 2) {
        unsigned char* wt = g_wt + j * (10 * OP_SLOT);
#pragma unroll 1
        for (int m0 = 0; m0 < 10; m0 += 3) {
          const int nu = m0 < 9 ? 9 : 3;
          mbar_expect_if(lane == 0, bar + 8 * BB_TMP, nu * 4096);
#pragma unroll 1
          for (int k = 0; k < nu; k++) tma2d_e(sb + BO_RING_OP + k * 4096, &P.wmap[0], (m0 + k / 3) * 64, 320 * j + 224 + 32 * (k % 3), bar + 8 * BB_TMP);
          mbar_waitw(bar + 8 * BB_TMP, m0 & 1);
          bulk_s2g_e(wt + m0 * OP_SLOT, sb + BO_RING_OP, nu * 4096);
          COMMIT();
          WRITTEN();
        }
        asm volatile("fence.acq_rel.gpu;" ::: "memory");
        int sl = 0, ph = 1, mt = rot;
#pragma unroll 1
        for (int r = -1; r < NSTEP; r++) {
#pragma unroll 1
          for (int n = r < 0 ? 7 : 0; n < (r + 1 < NSTEP ? 10 : 7); n++) {
            mbar_waitw(bar + 8 * (BB_USED + sl), ph);
            mbar_expect_if(lane == 0, bar + 8 * (BB_FULL + sl), OP_SLOT);
            bulk_g2s_e(sb + BO_RING_OP + sl * OP_SLOT, wt + mt * OP_SLOT, OP_SLOT, bar + 8 * (BB_FULL + sl));
            if (++sl == 3) { sl = 0; ph ^= 1; }
            mt = mt == 9 ? 0 : mt + 1;
            if (n == 1) clear(r);
            if (n == 5) { WRITTEN(); mbar_arrive_if(lane == 0, bar + 8 * BB_DONE); }
          }
        }
      } else if (op) {
        mbar_waitw(bar + 8 * BB_START, 0);
#pragma unroll 1
        for (int r = 0; r < NSTEP; r++) {
          const int rb = r - RD + 1;
          const uint32_t len = fmask(r) == 3 ? 8192 : 4096;
          const unsigned char* src = g_o + (uint32_t)(r * (96 * 8192) + 5 * j * len);
          wait_flags(lane < 2 ? &g_f[F_O + (lane ? NOP : j)][r] : rb >= 0 ? &g_f[F_DONE][rb] : &g_f[F_MISC][0],
                     lane < 2 ? (lane ? 1 : 5) : rb >= 0 ? rtarget(bmask(rb)) : NBC * 8);
          PTS1(35);
          if (r) bar_sync(NB_EARLY, 288);
          if (r == LAG) bar_sync(NB_LAST, 288);
          mbar_expect_if(lane < 3, bar + 8 * (BB_OFULL + lane), 2 * len);
          bulk_g2s_e(sb + BO_O, src, 2 * len, bar + 8 * BB_OFULL);
          PTS(62); PTS1(38);
          if (r && r != LAG) bar_sync(NB_LAST, 288);
          bulk_g2s_e(sb + BO_O + 2 * len, src + 2 * len, 2 * len, bar + 8 * (BB_OFULL + 1));
          bulk_g2s_e(sb + BO_O + 4 * len, src + 4 * len, len, bar + 8 * (BB_OFULL + 2));
          bulk_g2s_e(sb + BO_O + 5 * len, src + (95 - 5 * j) * len, len, bar + 8 * (BB_OFULL + 2));
          PTS1(64 + 35);
          BTS(r, 0);
        }
      } else if (warp == 2) {
#pragma unroll 1
        for (int r = 0; r < NR; r++) {
          const int mk = w12 ? fmask(r) : bmask(r);
          if (mk) {
            const unsigned char* src = &g_acc[w12 ? 4 : 2][r % RD][mk == 2 ? 4096 : 0];
            wait_flags(&g_f[w12 ? F_Z : F_R2 + (j & 3)][r], w12 ? rtarget(mk) : NOP * NW12 * NW34);
#pragma unroll 1
            for (int z = 0; z < 5; z++) {
              const uint32_t fb = bar + 8 * (BB_FULL + z), dst = sb + BO_RING_MLP + 2 * z % 3 * 16384 + (mk == 2 ? 4096 : 0);
              mbar_waitw(bar + 8 * (z < 3 ? BB_ZFREE + z : BB_EMPTY + z - 3), (r + (z < 3)) & 1);
              if (z == 0) PTS(62);
              mbar_expect_if(lane == 0, fb, mk == 3 ? 16384 : 8192);
              bulk_g2s_e(dst, src + z * 16384, mk == 3 ? 16384 : 4096, fb);
              if (mk != 3) bulk_g2s_e(dst + 8192, src + z * 16384 + 8192, 4096, fb);
              if (z == 0) BTS(r, 0);
            }
          }
          if (!w12) { clear(r); WRITTEN(); }
          mbar_waitw(bar + 8 * BB_DONE, (r + 1) & 1);
          mbar_arrive_if(lane == 0, bar + 8 * BB_DONE);
        }
      } else if (!w12) {
#pragma unroll 1
        for (int r = 0; r < NR; r++) {
          const bool idle = !(bmask(r) >> (lane >> 4) & 1);
          uint32_t t0, t1;
          int n = 0;
          mbar_waitw(bar + 8 * BB_FULL, r & 1);
          do {
            asm volatile("ld.relaxed.gpu.global.v2.u32 {%0,%1}, [%2];" : "=r"(t0), "=r"(t1) : "l"(&g_st2[r % RD][2 * lane]) : "memory");
            if (++n > SPIN_LIMIT) FAIL();
          } while (!__all_sync(~0u, idle || (((t0 ^ (r + 1)) | (t1 ^ (r + 1))) & 127) == 0));
          sts64(sb + BO_STAT + (lane >> 4) * 128 + (lane & 3) * 32 + ((lane >> 2) & 3) * 8, t0, t1);
          __syncwarp();
          mbar_arrive_if(lane == 0, bar + 8 * BB_STAT);
          PTS(63);
        }
      }
    }
    bar_arrive(NB_END, 512);
  } else if (wg == 2) {
    asm volatile("setmaxnreg.dec.sync.aligned.u32 40;");
    const int ord = uni(lds32(sb + BO_BOX + 4));
    const int gw = ord < RNEAR ? warp * RNEAR + ord : 4 * RNEAR + warp * (NBC - RNEAR) + ord - RNEAR, row = gw < 64 ? gw : gw < 96 ? gw - 64 : gw < 128 ? 2 * gw - 192 : 2 * gw - 224;
#pragma unroll 1
    for (int t = gw; t < S_LEN; t = row < 32 ? S_LEN : t < 4 * NBC ? 4 * NBC + (gw < 64 ? gw - 32 : gw - 80) : t + 64) {
      const int lane = lane_of(t);
      if (lane < 20 && t + 128 < S_LEN) asm volatile("prefetch.global.L2 [%0];" :: "l"(P.x + (t + (t < 4 * NBC ? 4 * NBC : 128)) * DM + (lane >> 1) * 64));
      rrow<3>(0, 0, t, lane, nullptr, role, P.x);
      __syncwarp();
      asm volatile("fence.release.gpu;" ::: "memory");
      red_if(lane == 0, &g_xready[t >> 5][0]);
    }
    if (gw < 64) rloop<0>(row, gw & 3, role, P.x, P.out);
    else if (gw < 96) rloop<2>(row, gw & 3, role, P.x, P.out);
    else if (gw < 128) rloop<1>(row, gw & 3, role, P.x, P.out);
    else rloop<4>(row, gw & 3, role, P.x, P.out);
    asm volatile("griddepcontrol.wait;" ::: "memory");
    const int t = threadIdx.x & 127;
    for (int i = (blockIdx.x * 128 + t) * 4; i < 4 * NCL * 2560; i += NBC * 512)
      *reinterpret_cast<uint4*>(&g_part[0][0][0][0] + i) = make_uint4(0u, 0u, 0u, 0u);
    bar_sync(NB_END, 512);
    if (t == 0) {
      uint32_t n;
      asm volatile("atom.acq_rel.gpu.global.add.u32 %0, [%1], 1;" : "=r"(n) : "l"(&g_f[F_MISC][64]) : "memory");
      sts32(sb + BO_BOX, n);
    }
    bar_sync(NB_END2, 128);
    if (lds32(sb + BO_BOX) == NBC - 1) {
      for (int i = t; i < F_NUM * 24; i += 128) reinterpret_cast<uint4*>(&g_f[0][0])[i] = make_uint4(0u, 0u, 0u, 0u);
      g_xready[t][0] = 0; g_tpc[t] = 0;
    }
  } else {
    asm volatile("setmaxnreg.inc.sync.aligned.u32 224;");
    LANE_INIT();
    for (int i = blockIdx.x * 256 + threadIdx.x; i < 2 * RD * TILE_B / 16; i += NBC * 256) reinterpret_cast<uint4*>(&g_acc[0][0][0])[i] = make_uint4(0u, 0u, 0u, 0u);
    warp_signal(&g_f[F_MISC][0], lane);
    const int mt0 = (rot + wg) % 10;
    auto boxes = [&](int ss) {
      const int nb = op && ss ? 3 : 4;
      const uint32_t base = sb + (ss ? BO_RES + wg * OP_RES : wg * 83968);
      mbar_expect_if(warp == 0 && lane == 0, bar + 8 * (BB_W + wg), nb * 20480 + (op ? 2048 : 0));
      bar_sync(NB_H, 256);
      if (warp < nb) {
#pragma unroll 1
        for (int i = warp; i < 5 * nb; i += nb) {
          const int p = op ? i / nb : (i - 10) >> 1, mt = (mt0 + 2 * p) % 10;
          const bool first = !op && i < 10;
          tma2d_e(op || !ss ? base + i * 4096 : sb + (first ? BO_W1 : -81920) + (2 * i + wg) * 4096, &P.wmap[op ? 0 : (w12 ? 1 : 3) + !first], first ? 128 * j + 64 * wg : mt * 64,
                  op ? 320 * j + 64 * warp + 32 * ss : first ? 64 * i + 32 * ss : 128 * j + 32 * (i & 1) + 64 * ss, bar + 8 * (BB_W + wg));
        }
      }
      if (op && warp == 3) tma2d_e(base + nb * 20480, &P.wo16, (mt0 + 2 * ss) % 10 * 64, 95 * 64 + (j + 1) / 5 * 16, bar + 8 * (BB_W + wg));
      mbar_waitw(bar + 8 * (BB_W + wg), ss);
    };
    if (W_DELAY) __nanosleep(W_DELAY);
    uint32_t W[164];
    boxes(0);
    load_w<41>(W, sb + wg * 83968, warp, lane);
    fence_async();
    boxes(1);
    if (!op) {
      float cs[2] = {0.f, 0.f};
      const uint32_t a0 = sb + BO_W1 + wg * 4096 + ((lane >> 4) * 8 + (lane & 7)) * 128 + (((warp * 2 + ((lane >> 3) & 1)) ^ (lane & 7)) << 4);
#pragma unroll
      for (int i = 0; i < 80; i++) cs[i & 1] += bf_lo(W[i]) + bf_hi(W[i]);
#pragma unroll 1
      for (int i = 0; i < 40; i++) {
        uint32_t t[4];
        const uint32_t ad = a0 + (i % 20 >> 1) * 8192 + (i & 1) * 2048;
        ldsm4t(t[0], t[1], t[2], t[3], ad);
#pragma unroll
        for (int k = 0; k < 4; k++) {
          if (i < 20) cs[k & 1] += bf_lo(t[k]) + bf_hi(t[k]);
          t[k] = pack2h(bf_lo(t[k]) - cs[k & 1], bf_hi(t[k]) - cs[k & 1]);
        }
        if (i >= 20) stsm4t(ad, t[0], t[1], t[2], t[3]);
        if (i == 19) {
#pragma unroll
          for (int k = 0; k < 2; k++) { cs[k] += __shfl_xor_sync(~0u, cs[k], 1); cs[k] += __shfl_xor_sync(~0u, cs[k], 2); cs[k] *= 1.f / DM; }
        }
      }
      const uint32_t z = dep0(__float_as_uint(cs[0]), lane);
#pragma unroll
      for (int i = 0; i < 80; i++) W[i] = pack2h(bf_lo(W[i] | z) - cs[i & 1], bf_hi(W[i] | z) - cs[i & 1]);
      fence_async();
      bar_sync(NB_H, 256);
    }
    const uint32_t alo = uni((SMEM0 + (op ? BO_RES + wg * OP_RES : wg * 4096)) >> 4);
    if (op) {
      Ring rg = {(uint32_t)wg, 0};
      mbar_arrive_if(lane == 0, bar + 8 * BB_START);
      if (wg) bar_arrive(NB_PP, 256);
      const uint32_t blo = DESC_LO(BO_O), xlo = blo + (j + 1) / 5 * 2;
#pragma unroll 1
      for (int r = 0; r < NSTEP; r++) {
        asm volatile("" : "+r"(lane));
        if (fmask(r) == 3) op_round<64>(W, bar, alo, blo, xlo, j == 0, rg, wg, warp, lane, r);
        else op_round<32>(W, bar, alo, blo, xlo, j == 0, rg, wg, warp, lane, r);
        if (warp == 0) BTS(r, 2 + wg);
      }
    } else {
      const int q4 = (128 * j + 64 * wg + 16 * warp) / 160, off = w12 ? (0x0413 >> (4 * q4)) & 7 : 0;
#pragma unroll 1
      for (int r = 0; r < NR; r++) {
        asm volatile("" : "+r"(lane));
        const int bm = bmask(r), fm = w12 ? fmask(r) : bm;
        if (fm == 3) phase1<64>(W, sb, alo, 0, wg, warp, lane, off, r, w12 ? 1 : r & 1);
        else if (fm) phase1<32>(W, sb, alo, fm >> 1, wg, warp, lane, off, r, w12 ? 1 : r & 1);
        else { mbar_waitu(bar + 8 * (BB_SFREE + 4 + wg), (r + 1) & 1); carry_in(sb, wg, warp, lane); }
        CTS(33);
        fence_async();
        bar_sync(NB_H, 256);
        if (wg + warp == 0) BTS(r, 1);
        if (bm == 3) phase2<64>(W, bar, alo, DESC_LO(BO_H), wg, warp, lane, r);
        else phase2<32>(W, bar, alo, uni(DESC_LO(BO_H) + (bm >> 1) * 256), wg, warp, lane, r);
        if (warp == 0) BTS(r, 2 + wg);
      }
    }
    CTS_OUT();
    bar_arrive(NB_END, 512);
  }
}

typedef CUresult (*EncodeFn)(CUtensorMap*, CUtensorMapDataType, cuuint32_t, void*, const cuuint64_t*, const cuuint64_t*, const cuuint32_t*,
                             const cuuint32_t*, CUtensorMapInterleave, CUtensorMapSwizzle, CUtensorMapL2promotion, CUtensorMapFloatOOBfill);
static void make_map(EncodeFn fn, CUtensorMap* tm, const void* ptr, uint64_t cols, uint64_t rows, uint32_t bc, uint32_t br) {
  cuuint64_t dims[2] = {cols, rows}; cuuint64_t strides[1] = {cols * 2}; cuuint32_t box[2] = {bc, br}; cuuint32_t es[2] = {1, 1};
  fn(tm, CU_TENSOR_MAP_DATA_TYPE_BFLOAT16, 2, const_cast<void*>(ptr), dims, strides, box, es, CU_TENSOR_MAP_INTERLEAVE_NONE,
     CU_TENSOR_MAP_SWIZZLE_128B, CU_TENSOR_MAP_L2_PROMOTION_L2_256B, CU_TENSOR_MAP_FLOAT_OOB_FILL_NONE);
}
#define dbg_a_only 0
extern "C" void kernel_launch(void* const* d_in, const int* in_sizes, int n_in, void* d_out, int out_size) {
  void* fnp = nullptr; cudaDriverEntryPointQueryResult qr;
  cudaGetDriverEntryPoint("cuTensorMapEncodeTiled", &fnp, cudaEnableDefault, &qr);
  EncodeFn fn = (EncodeFn)fnp;
  cudaStream_t st = cudaStreamPerThread;
  cudaFuncSetAttribute(bworker_kernel, cudaFuncAttributeMaxDynamicSharedMemorySize, B_SMEM);
  {
    AMaps M;
    for (int i = 0; i < 3; i++) make_map(fn, &M.w16[i], d_in[2 + i], HD, DM, 64, 16);
    make_map(fn, &M.wo32, d_in[5], DM, HD, 64, 32);
    cudaFuncSetAttribute(acore_kernel, cudaFuncAttributeMaxDynamicSharedMemorySize, A_SMEM);
    cudaFuncSetAttribute(acore_kernel, cudaFuncAttributeNonPortableClusterSizeAllowed, 1);
    cudaLaunchConfig_t cfg = {};
    cfg.gridDim = dim3(CL_SIZE * NCL); cfg.blockDim = dim3(512); cfg.dynamicSmemBytes = A_SMEM; cfg.stream = st;
    cudaLaunchAttribute at[1]; at[0].id = cudaLaunchAttributeClusterDimension;
    at[0].val.clusterDim.x = CL_SIZE; at[0].val.clusterDim.y = 1; at[0].val.clusterDim.z = 1;
    cfg.attrs = at; cfg.numAttrs = 1;
    cudaLaunchKernelEx(&cfg, acore_kernel, M, (const __nv_bfloat16*)d_in[1], dbg_a_only ? 0 : 1);
  }
  if (!dbg_a_only) {
    BParams P;
    make_map(fn, &P.wmap[0], d_in[5], DM, HD, 64, 32);
    make_map(fn, &P.wo16, d_in[5], DM, HD, 64, 16);
    make_map(fn, &P.wmap[1], d_in[8], DM, DM, 64, 32);
    make_map(fn, &P.wmap[2], d_in[9], DM, DM, 64, 32);
    make_map(fn, &P.wmap[3], d_in[10], FF, DM, 64, 32);
    make_map(fn, &P.wmap[4], d_in[11], DM, FF, 64, 32);
    P.x = (const __nv_bfloat16*)d_in[0];
    P.out = (__nv_bfloat16*)d_out;
    cudaLaunchConfig_t cfg = {};
    cfg.gridDim = dim3(NBC); cfg.blockDim = dim3(512); cfg.dynamicSmemBytes = B_SMEM; cfg.stream = st;
    cudaLaunchAttribute at[1]; at[0].id = cudaLaunchAttributeProgrammaticStreamSerialization; at[0].val.programmaticStreamSerializationAllowed = 1;
    cfg.attrs = at; cfg.numAttrs = 1;
    cudaLaunchKernelEx(&cfg, bworker_kernel, P);
  }
}
```

```cpp
#include <cuda_runtime.h>
#include <cuda_bf16.h>
#include <cuda.h>
#include <stdint.h>

#define S_LEN 2048
#define DM 640
#define NH 32
#define DH 192
#define HD 6144
#define NSEG 64
#define FF 1536

__device__ __forceinline__ uint32_t smem_u32(const void* p) { return (uint32_t)__cvta_generic_to_shared(p); }
__device__ __forceinline__ uint32_t mapa(uint32_t a, uint32_t r) {
  uint32_t o; asm volatile("mapa.shared::cluster.u32 %0, %1, %2;" : "=r"(o) : "r"(a), "r"(r)); return o; }
__device__ __forceinline__ void mbar_init(uint32_t b, uint32_t c) {
  asm volatile("mbarrier.init.shared::cta.b64 [%0], %1;" :: "r"(b), "r"(c) : "memory"); }
__device__ __forceinline__ void mbar_expect(uint32_t b, uint32_t tx) {
  asm volatile("mbarrier.arrive.expect_tx.shared::cta.b64 _, [%0], %1;" :: "r"(b), "r"(tx) : "memory"); }
__device__ __forceinline__ void mbar_arrive(uint32_t b) {
  asm volatile("mbarrier.arrive.shared::cta.b64 _, [%0];" :: "r"(b) : "memory"); }
__device__ __forceinline__ void mbar_arrive_remote(uint32_t rb) {
  asm volatile("mbarrier.arrive.relaxed.cluster.shared::cluster.b64 _, [%0];" :: "r"(rb) : "memory"); }
__device__ __forceinline__ void mbar_expect_if(bool p, uint32_t b, uint32_t tx) {
  asm volatile("{\n.reg .pred q;\nsetp.ne.u32 q, %2, 0;\n@q mbarrier.arrive.expect_tx.shared::cta.b64 _, [%0], %1;\n}" :: "r"(b), "r"(tx), "r"((uint32_t)p) : "memory"); }
__device__ __forceinline__ void mbar_arrive_if(bool p, uint32_t b) {
  asm volatile("{\n.reg .pred q;\nsetp.ne.u32 q, %1, 0;\n@q mbarrier.arrive.shared::cta.b64 _, [%0];\n}" :: "r"(b), "r"((uint32_t)p) : "memory"); }
__device__ __forceinline__ void mbar_arrive_remote_if(bool p, uint32_t rb) {
  asm volatile("{\n.reg .pred q;\nsetp.ne.u32 q, %1, 0;\n@q mbarrier.arrive.relaxed.cluster.shared::cluster.b64 _, [%0];\n}" :: "r"(rb), "r"((uint32_t)p) : "memory"); }
__device__ __forceinline__ void sts32_if(bool p, uint32_t a, uint32_t v) {
  asm volatile("{\n.reg .pred q;\nsetp.ne.u32 q, %2, 0;\n@q st.shared.b32 [%0], %1;\n}" :: "r"(a), "r"(v), "r"((uint32_t)p) : "memory"); }
__device__ __forceinline__ void sts128z_if(bool p, uint32_t a) {
  asm volatile("{\n.reg .pred q;\nsetp.ne.u32 q, %1, 0;\n@q st.shared.v4.b32 [%0], {0,0,0,0};\n}" :: "r"(a), "r"((uint32_t)p) : "memory"); }
__device__ __forceinline__ bool mbar_try(uint32_t b, uint32_t ph) {
  uint32_t ok;
  asm volatile("{\n.reg .pred p;\nmbarrier.try_wait.parity.shared::cta.b64 p, [%1], %2;\nselp.u32 %0, 1, 0, p;\n}"
               : "=r"(ok) : "r"(b), "r"(ph) : "memory");
  return ok; }
__device__ __forceinline__ bool mbar_test(uint32_t b, uint32_t ph) {
  uint32_t ok;
  asm volatile("{\n.reg .pred p;\nmbarrier.test_wait.parity.shared::cta.b64 p, [%1], %2;\nselp.u32 %0, 1, 0, p;\n}"
               : "=r"(ok) : "r"(b), "r"(ph) : "memory");
  return ok; }
#define SPIN_LIMIT 4000000
#define FAIL() asm volatile("st.global.u32 [%0], 0;" :: "l"(8ull) : "memory")
#define CFENCE() asm volatile("fence.proxy.async::generic.acquire.sync_restrict::shared::cluster.cluster;" ::: "memory")
__device__ __forceinline__ void mbar_wait(uint32_t b, uint32_t ph) {
  int n = 0;
  while (!mbar_try(b, ph)) { if (++n > SPIN_LIMIT) FAIL(); } }
#define TIMEOUT_ACT "@!p st.shared.u32 [%0+1], 0;"
#define WAIT_HINT ", 20000"
#define WAIT_LIM "200000"
__device__ __forceinline__ void mbar_slow(uint32_t b, uint32_t ph) {
  asm volatile("{\n.reg .pred p, q;\n.reg .u32 n;\nmov.u32 n, 0;\n"
               "WL:\nmbarrier.try_wait.parity.shared::cta.b64 p, [%0], %1" WAIT_HINT ";\nadd.u32 n, n, 1;\nsetp.lt.and.u32 q, n, " WAIT_LIM ", !p;\n@q bra.uni WL;\n"
               TIMEOUT_ACT "\n}" :: "r"(b), "r"(ph) : "memory"); }
__device__ __forceinline__ void mbar_waitw(uint32_t b, uint32_t ph) {
  asm volatile("{\n.reg .pred p, q;\n.reg .u32 n;\nmbarrier.try_wait.parity.shared::cta.b64 p, [%0], %1;\n@p bra.uni WD;\nmov.u32 n, 0;\n"
               "WL:\nmbarrier.try_wait.parity.shared::cta.b64 p, [%0], %1" WAIT_HINT ";\nadd.u32 n, n, 1;\nsetp.lt.and.u32 q, n, " WAIT_LIM ", !p;\n@q bra.uni WL;\n"
               TIMEOUT_ACT "\nWD:\n}" :: "r"(b), "r"(ph) : "memory"); }
__device__ __forceinline__ void mbar_waitw2(uint32_t b0, uint32_t b1, uint32_t ph) {
  uint32_t ok;
  asm volatile("{\n.reg .pred p, r;\nmbarrier.try_wait.parity.shared::cta.b64 p, [%1], %3;\nmbarrier.try_wait.parity.shared::cta.b64 r, [%2], %3;\n"
               "and.pred p, p, r;\nselp.u32 %0, 1, 0, p;\n}" : "=r"(ok) : "r"(b0), "r"(b1), "r"(ph) : "memory");
  if (__builtin_expect(!__all_sync(~0u, ok), 0)) { mbar_slow(b0, ph); mbar_slow(b1, ph); }
}
__device__ __forceinline__ void mbar_waitu(uint32_t b, uint32_t ph) {
  asm volatile("{\n.reg .pred p;\nmbarrier.try_wait.parity.shared::cta.b64 p, [%0], %1;\n@p bra.uni WD;\n"
               "WL:\nmbarrier.try_wait.parity.shared::cta.b64 p, [%0], %1" WAIT_HINT ";\n@!p bra.uni WL;\nWD:\n}" :: "r"(b), "r"(ph) : "memory"); }
__device__ __forceinline__ void mbar_waitu2(uint32_t b0, uint32_t b1, uint32_t ph) {
  asm volatile("{\n.reg .pred p, r;\nWL:\nmbarrier.try_wait.parity.shared::cta.b64 p, [%0], %2;\nmbarrier.try_wait.parity.shared::cta.b64 r, [%1], %2;\n"
               "and.pred p, p, r;\n@!p bra.uni WL;\n}" :: "r"(b0), "r"(b1), "r"(ph) : "memory"); }
__device__ __forceinline__ void mbar_waitw4(uint32_t b, uint32_t ph) { mbar_waitw2(b, b + 8, ph); mbar_waitw2(b + 16, b + 24, ph); }
__device__ __forceinline__ uint32_t clock32() { uint32_t t; asm volatile("mov.u32 %0, %%clock;" : "=r"(t) :: "memory"); return t; }
template <int L> __device__ __forceinline__ uint32_t lop3(uint32_t a, uint32_t b, uint32_t c) {
  uint32_t r; asm("lop3.b32 %0, %1, %2, %3, %4;" : "=r"(r) : "r"(a), "r"(b), "r"(c), "n"(L)); return r; }
__device__ __forceinline__ void st_async_v2_if(bool p, uint32_t a, uint32_t v0, uint32_t v1, uint32_t mb) {
  asm volatile("{\n.reg .pred q;\nsetp.ne.u32 q, %4, 0;\n@q st.async.weak.shared::cluster.mbarrier::complete_tx::bytes.v2.b32 [%0], {%1,%2}, [%3];\n}"
               :: "r"(a), "r"(v0), "r"(v1), "r"(mb), "r"((uint32_t)p) : "memory"); }
__device__ __forceinline__ void keep4(const uint32_t* r, int lane) {
  asm volatile("{\n.reg .pred q;\nsetp.lt.s32 q, %4, 0;\n@q st.shared.v4.b32 [%4], {%0,%1,%2,%3};\n}" :: "r"(r[0]), "r"(r[1]), "r"(r[2]), "r"(r[3]), "r"(lane) : "memory"); }
__device__ __forceinline__ uint32_t uni(uint32_t x) { return __shfl_sync(~0u, x, 0); }
__device__ __forceinline__ void bulk_g2s_mc_e(uint32_t dst, const void* src, uint32_t bytes, uint32_t mb, uint16_t mask) {
  asm volatile("{\n.reg .pred e;\nelect.sync _|e, 0xffffffff;\n"
               "@e cp.async.bulk.shared::cluster.global.mbarrier::complete_tx::bytes.multicast::cluster [%0], [%1], %2, [%3], %4;\n}"
               :: "r"(dst), "l"(src), "r"(bytes), "r"(mb), "h"(mask) : "memory"); }
__device__ __forceinline__ void bulk_s2g_e(void* dst, uint32_t src, uint32_t bytes) {
  asm volatile("{\n.reg .pred e;\nelect.sync _|e, 0xffffffff;\n@e cp.async.bulk.global.shared::cta.bulk_group [%0], [%1], %2;\n}"
               :: "l"(dst), "r"(src), "r"(bytes) : "memory"); }
__device__ __forceinline__ void bulk_g2s_e(uint32_t dst, const void* src, uint32_t bytes, uint32_t mb) {
  asm volatile("{\n.reg .pred e;\nelect.sync _|e, 0xffffffff;\n@e cp.async.bulk.shared::cluster.global.mbarrier::complete_tx::bytes [%0], [%1], %2, [%3];\n}"
               :: "r"(dst), "l"(src), "r"(bytes), "r"(mb) : "memory"); }
#define STREAM_HINT 1
__device__ __forceinline__ void bulk_s2g_es(void* dst, uint32_t src, uint32_t bytes) {
  asm volatile("{\n.reg .pred e;\n.reg .b64 pol;\ncreatepolicy.fractional.L2::evict_first.b64 pol;\nelect.sync _|e, 0xffffffff;\n"
               "@e cp.async.bulk.global.shared::cta.bulk_group.L2::cache_hint [%0], [%1], %2, pol;\n}" :: "l"(dst), "r"(src), "r"(bytes) : "memory");
}
__device__ __forceinline__ void bulk_g2s_es(uint32_t dst, const void* src, uint32_t bytes, uint32_t mb) {
  asm volatile("{\n.reg .pred e;\n.reg .b64 pol;\ncreatepolicy.fractional.L2::evict_first.b64 pol;\nelect.sync _|e, 0xffffffff;\n"
               "@e cp.async.bulk.shared::cluster.global.mbarrier::complete_tx::bytes.L2::cache_hint [%0], [%1], %2, [%3], pol;\n}"
               :: "r"(dst), "l"(src), "r"(bytes), "r"(mb) : "memory"); }
__device__ __forceinline__ void tma2d_e(uint32_t dst, const CUtensorMap* tm, int c0, int c1, uint32_t mb) {
  asm volatile("{\n.reg .pred e;\nelect.sync _|e, 0xffffffff;\n"
               "@e cp.async.bulk.tensor.2d.shared::cluster.global.mbarrier::complete_tx::bytes [%0], [%1, {%3, %4}], [%2];\n}"
               :: "r"(dst), "l"((uint64_t)tm), "r"(mb), "r"(c0), "r"(c1) : "memory"); }
__device__ __forceinline__ uint32_t hadd2bf(uint32_t a, uint32_t b) {
  uint32_t r; asm("add.rn.bf16x2 %0, %1, %2;" : "=r"(r) : "r"(a), "r"(b)); return r; }
__device__ __forceinline__ void cluster_sync_all() {
  asm volatile("barrier.cluster.arrive.release.aligned;\nbarrier.cluster.wait.acquire.aligned;" ::: "memory"); }
__device__ __forceinline__ void bar_arrive(int id, int n) { asm volatile("bar.arrive %0, %1;" :: "r"(id), "r"(n) : "memory"); }
__device__ __forceinline__ void bar_arrive_dep(int id, int n, uint32_t dep) {
  asm volatile("{\n.reg .u32 t;\nand.b32 t, %2, 0;\nadd.u32 t, t, %0;\nbar.sync t, %1;\n}" :: "r"(id), "r"(n), "r"(dep) : "memory"); }
__device__ __forceinline__ void bar_sync(int id, int n) { asm volatile("bar.sync %0, %1;" :: "r"(id), "r"(n) : "memory"); }
__device__ __forceinline__ void fence_async() { asm volatile("fence.proxy.async.shared::cta;" ::: "memory"); }
__device__ __forceinline__ void st_async_b32(uint32_t a, uint32_t v, uint32_t mb) {
  asm volatile("st.async.weak.shared::cluster.mbarrier::complete_tx::bytes.b32 [%0], %1, [%2];" :: "r"(a), "r"(v), "r"(mb) : "memory"); }
__device__ __forceinline__ void st_async_v2(uint32_t a, uint32_t v0, uint32_t v1, uint32_t mb) {
  asm volatile("st.async.weak.shared::cluster.mbarrier::complete_tx::bytes.v2.b32 [%0], {%1,%2}, [%3];" :: "r"(a), "r"(v0), "r"(v1), "r"(mb) : "memory"); }
__device__ __forceinline__ void st_async_v4(uint32_t a, uint32_t v0, uint32_t v1, uint32_t v2, uint32_t v3, uint32_t mb) {
  asm volatile("st.async.weak.shared::cluster.mbarrier::complete_tx::bytes.v4.b32 [%0], {%1,%2,%3,%4}, [%5];" :: "r"(a), "r"(v0), "r"(v1), "r"(v2), "r"(v3), "r"(mb) : "memory"); }
__device__ __forceinline__ void ldsm4(uint32_t& r0, uint32_t& r1, uint32_t& r2, uint32_t& r3, uint32_t a) {
  asm volatile("ldmatrix.sync.aligned.m8n8.x4.shared.b16 {%0,%1,%2,%3}, [%4];" : "=r"(r0), "=r"(r1), "=r"(r2), "=r"(r3) : "r"(a) : "memory"); }
__device__ __forceinline__ void ldsm4t(uint32_t& r0, uint32_t& r1, uint32_t& r2, uint32_t& r3, uint32_t a) {
  asm volatile("ldmatrix.sync.aligned.m8n8.x4.trans.shared.b16 {%0,%1,%2,%3}, [%4];" : "=r"(r0), "=r"(r1), "=r"(r2), "=r"(r3) : "r"(a) : "memory"); }
__device__ __forceinline__ void stsm2t(uint32_t a, uint32_t r0, uint32_t r1) {
  asm volatile("stmatrix.sync.aligned.m8n8.x2.trans.shared.b16 [%0], {%1,%2};" :: "r"(a), "r"(r0), "r"(r1) : "memory"); }
__device__ __forceinline__ void stsm4t(uint32_t a, uint32_t r0, uint32_t r1, uint32_t r2, uint32_t r3) {
  asm volatile("stmatrix.sync.aligned.m8n8.x4.trans.shared.b16 [%0], {%1,%2,%3,%4};" :: "r"(a), "r"(r0), "r"(r1), "r"(r2), "r"(r3) : "memory"); }
__device__ __forceinline__ uint32_t movm(uint32_t a) {
  uint32_t d; asm volatile("movmatrix.sync.aligned.m8n8.trans.b16 %0, %1;" : "=r"(d) : "r"(a)); return d; }
__device__ __forceinline__ void mma16816(float* d, uint32_t a0, uint32_t a1, uint32_t a2, uint32_t a3, uint32_t b0, uint32_t b1) {
  asm("mma.sync.aligned.m16n8k16.row.col.f32.bf16.bf16.f32 {%0,%1,%2,%3}, {%4,%5,%6,%7}, {%8,%9}, {%0,%1,%2,%3};"
               : "+f"(d[0]), "+f"(d[1]), "+f"(d[2]), "+f"(d[3]) : "r"(a0), "r"(a1), "r"(a2), "r"(a3), "r"(b0), "r"(b1)); }
__device__ __forceinline__ void mma16816v(float* d, uint32_t a0, uint32_t a1, uint32_t a2, uint32_t a3, uint32_t b0, uint32_t b1) {
  asm volatile("mma.sync.aligned.m16n8k16.row.col.f32.bf16.bf16.f32 {%0,%1,%2,%3}, {%4,%5,%6,%7}, {%8,%9}, {%0,%1,%2,%3};"
               : "+f"(d[0]), "+f"(d[1]), "+f"(d[2]), "+f"(d[3]) : "r"(a0), "r"(a1), "r"(a2), "r"(a3), "r"(b0), "r"(b1)); }
__device__ __forceinline__ uint32_t pack2(float lo, float hi) {
  uint32_t r; asm("cvt.rn.bf16x2.f32 %0, %1, %2;" : "=r"(r) : "f"(hi), "f"(lo)); return r; }
__device__ __forceinline__ uint32_t pack2v(float lo, float hi) {
  uint32_t r; asm volatile("cvt.rn.bf16x2.f32 %0, %1, %2;" : "=r"(r) : "f"(hi), "f"(lo)); return r; }
__device__ __forceinline__ float bf_lo(uint32_t w) { return __uint_as_float(w << 16); }
__device__ __forceinline__ float bf_hi(uint32_t w) { return __uint_as_float(w & 0xffff0000u); }
__device__ __forceinline__ uint4 lds128(uint32_t a) {
  uint4 v; asm volatile("ld.shared.v4.b32 {%0,%1,%2,%3}, [%4];" : "=r"(v.x), "=r"(v.y), "=r"(v.z), "=r"(v.w) : "r"(a) : "memory"); return v; }
__device__ __forceinline__ uint4 lds128_nv(uint32_t a) {
  uint4 v; asm volatile("ld.shared.v4.b32 {%0,%1,%2,%3}, [%4];" : "=r"(v.x), "=r"(v.y), "=r"(v.z), "=r"(v.w) : "r"(a)); return v; }
__device__ __forceinline__ void st_async_v2_nm(uint32_t a, uint32_t v0, uint32_t v1, uint32_t mb) {
  asm volatile("st.async.weak.shared::cluster.mbarrier::complete_tx::bytes.v2.b32 [%0], {%1,%2}, [%3];" :: "r"(a), "r"(v0), "r"(v1), "r"(mb)); }
__device__ __forceinline__ float rcpf(float x) { float y; asm("rcp.approx.ftz.f32 %0, %1;" : "=f"(y) : "f"(x)); return y; }
__device__ __forceinline__ void sts64(uint32_t a, uint32_t x, uint32_t y) { asm volatile("st.shared.v2.b32 [%0], {%1,%2};" :: "r"(a), "r"(x), "r"(y) : "memory"); }
__device__ __forceinline__ float ex2(float x) { float y; asm("ex2.approx.ftz.f32 %0, %1;" : "=f"(y) : "f"(x)); return y; }
__device__ __forceinline__ uint32_t lds32(uint32_t a) {
  uint32_t v; asm volatile("ld.shared.b32 %0, [%1];" : "=r"(v) : "r"(a) : "memory"); return v; }
__device__ __forceinline__ uint2 lds64(uint32_t a) {
  uint2 v; asm volatile("ld.shared.v2.b32 {%0,%1}, [%2];" : "=r"(v.x), "=r"(v.y) : "r"(a) : "memory"); return v; }
__device__ __forceinline__ void sts128(uint32_t a, uint32_t x, uint32_t y, uint32_t z, uint32_t w) {
  asm volatile("st.shared.v4.b32 [%0], {%1,%2,%3,%4};" :: "r"(a), "r"(x), "r"(y), "r"(z), "r"(w) : "memory"); }
__device__ __forceinline__ void sts32(uint32_t a, uint32_t x) { asm volatile("st.shared.b32 [%0], %1;" :: "r"(a), "r"(x) : "memory"); }
__device__ __forceinline__ void tma2d(uint32_t dst, const CUtensorMap* tm, int c0, int c1, uint32_t mb) {
  asm volatile("cp.async.bulk.tensor.2d.shared::cluster.global.mbarrier::complete_tx::bytes [%0], [%1, {%3, %4}], [%2];"
               :: "r"(dst), "l"((uint64_t)tm), "r"(mb), "r"(c0), "r"(c1) : "memory"); }
__device__ __forceinline__ void tma2d_prefetch(const CUtensorMap* tm, int c0, int c1) {
  asm volatile("cp.async.bulk.prefetch.tensor.2d.L2.global.tile [%0, {%1, %2}];" :: "l"((uint64_t)tm), "r"(c0), "r"(c1) : "memory"); }
__device__ __forceinline__ void bulk_g2s_mc(uint32_t dst, const void* src, uint32_t bytes, uint32_t mb, uint16_t mask) {
  asm volatile("cp.async.bulk.shared::cluster.global.mbarrier::complete_tx::bytes.multicast::cluster [%0], [%1], %2, [%3], %4;"
               :: "r"(dst), "l"(src), "r"(bytes), "r"(mb), "h"(mask) : "memory"); }
__device__ __forceinline__ void bulk_s2g(void* dst, uint32_t src, uint32_t bytes) {
  asm volatile("cp.async.bulk.global.shared::cta.bulk_group [%0], [%1], %2;" :: "l"(dst), "r"(src), "r"(bytes) : "memory"); }
__device__ __forceinline__ void wg_fence() { asm volatile("wgmma.fence.sync.aligned;" ::: "memory"); }
__device__ __forceinline__ void wg_commit() { asm volatile("wgmma.commit_group.sync.aligned;" ::: "memory"); }
template <int N> __device__ __forceinline__ void wg_wait() { asm volatile("wgmma.wait_group.sync.aligned %0;" :: "n"(N) : "memory"); }
__device__ __forceinline__ uint64_t mkdesc(uint32_t addr, uint32_t lbo, uint32_t sbo, uint32_t swz) {
  return (uint64_t)((addr & 0x3FFFF) >> 4) | ((uint64_t)(lbo >> 4) << 16) | ((uint64_t)(sbo >> 4) << 32) | ((uint64_t)swz << 62); }

#define ACC4(d) "+f"(d[0]),"+f"(d[1]),"+f"(d[2]),"+f"(d[3])
#define ACC8(d) ACC4(d), ACC4((d + 4))
#define ACC16(d) ACC8(d), ACC8((d + 8))
#define ACC20(d) ACC16(d), ACC4((d + 16))
#define ACC24(d) ACC16(d), ACC8((d + 16))
#define SMEM0 0x400
__host__ __device__ constexpr uint32_t dlo(uint32_t off, uint32_t lbo) { return ((SMEM0 + off) >> 4) | ((lbo >> 4) << 16); }
__host__ __device__ constexpr uint32_t dhi(uint32_t sbo, uint32_t swz) { return (sbo >> 4) | (swz << 30); }
#define R4S "{%0,%1,%2,%3}"
#define R8S "{%0,%1,%2,%3,%4,%5,%6,%7}"
#define R16S "{%0,%1,%2,%3,%4,%5,%6,%7,%8,%9,%10,%11,%12,%13,%14,%15}"
#define R20S "{%0,%1,%2,%3,%4,%5,%6,%7,%8,%9,%10,%11,%12,%13,%14,%15,%16,%17,%18,%19}"
#define R24S "{%0,%1,%2,%3,%4,%5,%6,%7,%8,%9,%10,%11,%12,%13,%14,%15,%16,%17,%18,%19,%20,%21,%22,%23}"
template <int N> struct MM;
#define DEF_MM(N, ACCM, RS_, I0, I1, I2, I3, I4, I5, I6, I7)                                                                      \
  template <> struct MM<N> {                                                                                                      \
    template <uint32_t BLO, uint32_t BHI, int ACC>                                                                                \
    static __device__ __forceinline__ void rs(float* d, uint32_t a0, uint32_t a1, uint32_t a2, uint32_t a3) {                     \
      asm volatile("{\n.reg .b64 b;\nmov.b64 b, {%" #I4 ", %" #I5 "};\n"                                                          \
                   "wgmma.mma_async.sync.aligned.m64n" #N "k16.f32.bf16.bf16 " RS_ ", {%" #I0 ",%" #I1 ",%" #I2 ",%" #I3 "}, b, %" #I6 ", 1, 1, 0;\n}" \
                   : ACCM(d) : "r"(a0), "r"(a1), "r"(a2), "r"(a3), "n"(BLO), "n"(BHI), "n"(ACC)); }                               \
    template <uint32_t ALO, uint32_t AHI, uint32_t BLO, uint32_t BHI, int ACC, int TA>                                            \
    static __device__ __forceinline__ void ss(float* d, uint32_t abase) {                                                         \
      asm volatile("{\n.reg .b64 a, b;\n.reg .b32 l;\nadd.u32 l, %" #I0 ", %" #I1 ";\nmov.b64 a, {l, %" #I2 "};\nmov.b64 b, {%" #I3 ", %" #I4 "};\n" \
                   "wgmma.mma_async.sync.aligned.m64n" #N "k16.f32.bf16.bf16 " RS_ ", a, b, %" #I5 ", 1, 1, %" #I6 ", 0;\n}"     \
                   : ACCM(d) : "r"(abase), "n"(ALO), "n"(AHI), "n"(BLO), "n"(BHI), "n"(ACC), "n"(TA)); }                          \
    template <int ACC>                                                                                                            \
    static __device__ __forceinline__ void rsd(float* d, uint32_t a0, uint32_t a1, uint32_t a2, uint32_t a3, uint64_t b) {        \
      asm volatile("wgmma.mma_async.sync.aligned.m64n" #N "k16.f32.bf16.bf16 " RS_ ", {%" #I0 ",%" #I1 ",%" #I2 ",%" #I3 "}, %" #I4 ", %" #I5 ", 1, 1, 0;" \
                   : ACCM(d) : "r"(a0), "r"(a1), "r"(a2), "r"(a3), "l"(b), "n"(ACC)); }                                           \
    template <int ACC>                                                                                                            \
    static __device__ __forceinline__ void ssd(float* d, uint64_t a, uint64_t b) {                                                \
      asm volatile("wgmma.mma_async.sync.aligned.m64n" #N "k16.f32.bf16.bf16 " RS_ ", %" #I0 ", %" #I1 ", %" #I2 ", 1, 1, 1, 0;"  \
                   : ACCM(d) : "l"(a), "l"(b), "n"(ACC)); }                                                                       \
    template <uint32_t ALO, uint32_t AHI, uint32_t BLO, uint32_t BHI, int ACC>                                                    \
    static __device__ __forceinline__ void ss2(float* d, uint32_t abase, uint32_t bbase) {                                        \
      asm volatile("{\n.reg .b64 a, b;\n.reg .b32 l, m;\nadd.u32 l, %" #I0 ", %" #I1 ";\nmov.b64 a, {l, %" #I2 "};\n"            \
                   "add.u32 m, %" #I6 ", %" #I3 ";\nmov.b64 b, {m, %" #I4 "};\n"                                                   \
                   "wgmma.mma_async.sync.aligned.m64n" #N "k16.f32.bf16.bf16 " RS_ ", a, b, %" #I5 ", 1, 1, 0, 0;\n}"            \
                   : ACCM(d) : "r"(abase), "n"(ALO), "n"(AHI), "n"(BLO), "n"(BHI), "n"(ACC), "r"(bbase)); }                                    \
  };
DEF_MM(8, ACC4, R4S, 4, 5, 6, 7, 8, 9, 10, 11)
DEF_MM(16, ACC8, R8S, 8, 9, 10, 11, 12, 13, 14, 15)
DEF_MM(32, ACC16, R16S, 16, 17, 18, 19, 20, 21, 22, 23)
DEF_MM(40, ACC20, R20S, 20, 21, 22, 23, 24, 25, 26, 27)
DEF_MM(48, ACC24, R24S, 24, 25, 26, 27, 28, 29, 30, 31)

#define LAG 11
#define NSTEP (NSEG + LAG)
#define NR (NSTEP + 1)
__device__ __align__(1024) __nv_bfloat16 g_xn[2][S_LEN * DM];
__device__ __align__(1024) unsigned char g_o[NSTEP * 96 * 8192];
__device__ __align__(1024) uint32_t g_part[6][7][40][64];
#define RD 16
#define TILE_B 81920
__device__ __align__(1024) float2 g_stat[S_LEN];
__device__ __align__(1024) uint32_t g_st2[2][RD][64];
__device__ __align__(1024) unsigned char g_acc[5][RD][TILE_B];
#define NOP 19
#define NW12 5
#define NW34 12
#define NBC (NOP + NW12 + NW34)
__device__ __align__(1024) unsigned char g_wt[NOP * 10 * 12288];
enum { F_O = 0, F_R1 = NOP + 1, F_R2 = F_R1 + 4, F_R3 = F_R2 + 4, F_Z = F_R3 + 4, F_DONE, F_MISC, F_NUM };
__device__ __align__(128) uint32_t g_f[F_NUM][96];
__device__ __align__(128) int g_xready[129][8];
__device__ uint32_t g_tpc[128];
#define TS(i)
#define TSV(i, v)
#define TSN(i)
#define TSD(i, dep)
#define BTS(k, i)
#define BTS2(k, i)
#define RTS(i)
#define RTSD(i, dep)
#define RTS_OUT()
#define CTS(i)
#define PTS(i)
#define PTS1(i)
#define CTS_OUT()
#define GTS(i)

#define CL_SIZE 15
#define NCL 7
#define SSQ 13
#define SSV 16
#define PL_SZ 5376
#define TILE_SBO 2560
#define TILE_GRP 15360
#define WS_SZ ((2 * SSQ + SSV) * 2048)
#define OFF_QK (OFF_WO + 26 * 2048)
#define LAYOUT 2
#define OFF_TILE 0
#define OFF_WS (4 * TILE_GRP)
#define OFF_WO (OFF_WS + WS_SZ)
#define OFF_PL (OFF_QK + 20480)
#define OFF_BAR (OFF_PL + 2 * PL_SZ)
#define STG_Q OFF_TILE
#define STG_K OFF_WO
#define VA 14
#define STG_V2 (OFF_TILE + 27 * 2048)
#define OFF_O (OFF_PL + 4352)
#define LAND(k) (((k) >> 1) * TILE_GRP + ((k) & 1) * 1280)
#define LAND_F (5 * TILE_SBO)
#define OFF_XL (OFF_TILE + 3 * TILE_GRP)
#define OFF_XF (OFF_XL + LAND_F)
#define OFF_WT ((OFF_XL + TILE_SBO + 1023) & ~1023)
#define OFF_TAB (OFF_BAR + 240)
#define OFF_INV (OFF_TAB + 64)
#define OFF_TS (OFF_INV + 128)
#define A_SMEM 232448
static_assert(WS_SZ + 72 * 1024 + 2 * PL_SZ + 4 * TILE_GRP + 512 == A_SMEM && OFF_WS % 1024 == 0 && OFF_WO % 1024 == 0 && SSQ == 13, "smem map");
enum { B_W0 = 0, B_W1, B_F1, B_F2 = B_F1 + 4, B_R1 = B_F2 + 4, B_R2, B_MEMFREE, B_LANDFREE, B_OPEER, B_PLFREE, B_XFREE, B_SB, B_WOF = B_SB + 6, B_WTF, B_RS, B_NUM = B_RS + 4 };
static_assert(B_NUM <= 30, "barriers");
enum { N_C = 0, N_SISS, N_QK, N_V, N_PM, N_TURN, N_PI, N_VGO, N_O, N_PX, N_AB, N_SDONE, N_VDONE, N_G3, N_P, N_OX };

__device__ __forceinline__ bool is_dual(int j) { return j >= LAG && j < NSEG; }
__device__ __forceinline__ int sched_l(int j) { return j < NSEG ? j : NSEG + j - LAG; }
__device__ __forceinline__ int sched_f(int j) { return NSEG + j - LAG; }
__device__ __forceinline__ void wait_cnt(const int* p, int target) {
  int v, n = 0;
  do {
    asm volatile("ld.relaxed.gpu.global.b32 %0, [%1];" : "=r"(v) : "l"(p) : "memory");
    if (v >= target) break;
    __nanosleep(100);
    if (++n > SPIN_LIMIT) FAIL();
  } while (true);
  asm volatile("fence.acquire.gpu;" ::: "memory");
  asm volatile("fence.proxy.async.global;" ::: "memory");
}
__device__ __forceinline__ void red_release(void* p, uint32_t v) { asm volatile("red.release.gpu.global.add.u32 [%0], %1;" :: "l"(p), "r"(v) : "memory"); }
__device__ __forceinline__ void red_relaxed(void* p, uint32_t v) { asm volatile("red.relaxed.gpu.global.add.u32 [%0], %1;" :: "l"(p), "r"(v) : "memory"); }
#define VMASK 0xa5294a5294ull
__host__ __device__ constexpr int popc40(unsigned long long m) { int c = 0; for (; m; m &= m - 1) c++; return c; }
static_assert(popc40(VMASK) == SSV, "mask");
__host__ __device__ constexpr int ss_idx(int ks, int n) { return n == SSV ? popc40(VMASK & ((1ull << ks) - 1)) : ks * n / 40; }
__host__ __device__ constexpr bool is_ss(int ks, int n) { return ss_idx(ks + 1, n) != ss_idx(ks, n); }
__host__ __device__ constexpr int rs_idx(int ks, int n) { return ks - ss_idx(ks, n); }

#define SL2 (0.07216878364870322f * 1.4426950408889634f)

#define SUM_LOOP 0
#define IMM_K 0
#define TAB_N 32
struct DescTab { uint64_t tile[2][40], unit[2 * SSQ + SSV]; };
constexpr DescTab make_tab() {
  DescTab t = {};
  for (int rg = 0; rg < 2; rg++)
    for (int k = 0; k < 40; k++) t.tile[rg][k] = dlo(OFF_TILE + (k / 10) * TILE_GRP + rg * TILE_SBO + (k % 10) * 256, 128) | ((uint64_t)dhi(TILE_SBO, 0) << 32);
  for (int u = 0; u < 2 * SSQ + SSV; u++) t.unit[u] = dlo(OFF_WS + u * 2048, 0) | ((uint64_t)dhi(1024, 1) << 32);
  return t;
}
__constant__ DescTab c_tab = make_tab();
template <int N, int NSS, int RG, int KS, int K1, int K0 = 0>
__device__ __forceinline__ void proj(float* acc, const uint32_t* W, uint32_t ub) {
  if constexpr (KS < K1) {
    constexpr int i = rs_idx(KS, NSS) * 4;
    if constexpr (N >= TAB_N && !(RG == 0 && NSS == SSQ && KS < IMM_K)) {
      if constexpr (is_ss(KS, NSS)) MM<N>::template ssd<(KS != K0)>(acc, c_tab.unit[ub + ss_idx(KS, NSS)], c_tab.tile[RG][KS]);
      else MM<N>::template rsd<(KS != K0)>(acc, W[i], W[i + 1], W[i + 2], W[i + 3], c_tab.tile[RG][KS]);
    } else {
      constexpr uint32_t BLO = dlo(OFF_TILE + (KS / 10) * TILE_GRP + RG * TILE_SBO + (KS % 10) * 256, 128), BHI = dhi(TILE_SBO, 0);
      if constexpr (is_ss(KS, NSS)) MM<N>::template ss<dlo(OFF_WS + ss_idx(KS, NSS) * 2048, 0), dhi(1024, 1), BLO, BHI, (KS != K0), 1>(acc, ub * 128);
      else MM<N>::template rs<BLO, BHI, (KS != K0)>(acc, W[i], W[i + 1], W[i + 2], W[i + 3]);
    }
    proj<N, NSS, RG, KS + 1, K1, K0>(acc, W, ub);
  }
}
template <int N>
__device__ __forceinline__ void load_w(uint32_t* W, uint32_t stage, int warp, int lane) {
  const int kr = (lane >> 4) * 8 + (lane & 7);
  const int cb = warp * 2 + ((lane >> 3) & 1);
  const uint32_t a0 = stage + kr * 128 + ((cb ^ (lane & 7)) << 4);
#pragma unroll
  for (int i = 0; i < N; i++) ldsm4t(W[4 * i], W[4 * i + 1], W[4 * i + 2], W[4 * i + 3], a0 + i * 2048);
}
template <int N, int U, int OS, int ACC>
__device__ __forceinline__ void wo4(float* d) {
  constexpr uint32_t WA = U >= 4 ? OFF_WO + (U - 4) * 2048 : OFF_WT, OB = OS == 0 ? OFF_O : OS == 1 ? OFF_XL : OFF_XF, SBO = OS ? 1024 : PL_SZ;
  MM<N>::template ss<dlo(WA, 0), dhi(1024, 1), dlo(OB, 128), dhi(SBO, 0), ACC, 1>(d, 0);
  MM<N>::template ss<dlo(WA + 2048, 0), dhi(1024, 1), dlo(OB + 256, 128), dhi(SBO, 0), 1, 1>(d, 0);
  MM<N>::template ss<dlo(WA + 4096, 0), dhi(1024, 1), dlo(OB + 512, 128), dhi(SBO, 0), 1, 1>(d, 0);
  MM<N>::template ss<dlo(WA + 6144, 0), dhi(1024, 1), dlo(OB + 768, 128), dhi(SBO, 0), 1, 1>(d, 0);
}
__device__ __forceinline__ void wo_coord(int i, int t3, int head, int& c0, int& c1) {
  const int g = i >> 1;
  const int blk = g == 0 ? 9 : (g < 4 ? g - 1 : (g - 4) >> 1) * 3 + t3;
  int sl = g < 4 ? t3 : (g & 1) ? t3 + 1 : t3 + 2;
  if (sl >= 3) sl -= 3;
  c0 = blk * 64; c1 = head * DH + sl * 64 + (i & 1) * 32;
}
__device__ __forceinline__ void tok_softmax(uint32_t sb, int job, int lane) {
  const bool w1 = job & 1;
  const int dg = (lane >> 2) - (lane & 3) * 2;
  const uint32_t lo = sb + OFF_PL + (job >> 1) * PL_SZ + (job & 1) * 1792, l8 = lo + 512 + lane * 8, pa = lo + lane * 4;
  const uint32_t km = job & 2 ? 640 : 512;
  float x[14];
  {
    const uint4 a = lds128(lo + lane * 16);
    const uint2 e = lds64(l8);
    const uint32_t c = lds32(768 + pa);
    x[0] = bf_lo(a.x); x[1] = bf_hi(a.x); x[2] = bf_lo(a.y); x[3] = bf_hi(a.y); x[4] = bf_lo(a.z); x[5] = bf_hi(a.z); x[6] = bf_lo(a.w); x[7] = bf_hi(a.w);
    x[8] = bf_lo(c); x[9] = bf_hi(c); x[10] = bf_lo(e.x); x[11] = bf_hi(e.x); x[12] = bf_lo(e.y); x[13] = bf_hi(e.y);
  }
  if (dg < 0) { x[8] = -INFINITY; if (w1) x[4] = -INFINITY; else x[10] = -INFINITY; }
  if (dg < 1) { x[9] = -INFINITY; if (w1) x[5] = -INFINITY; else x[11] = -INFINITY; }
  const float m4 = fmaxf(x[8], x[9]);
  float m0 = fmaxf(fmaxf(fmaxf(x[0], x[1]), fmaxf(x[2], x[3])), fmaxf(fmaxf(x[4], x[5]), fmaxf(x[6], x[7])));
  float m1 = fmaxf(fmaxf(x[10], x[11]), fmaxf(x[12], x[13]));
  if (w1) m1 = fmaxf(m1, m4); else m0 = fmaxf(m0, m4);
  m0 = fmaxf(m0, __shfl_xor_sync(~0u, m0, 1)); m1 = fmaxf(m1, __shfl_xor_sync(~0u, m1, 1));
  sts32(pa + (w1 ? 384 : 896 + 128), 0u); sts32(pa + 1152 - km, 0u); sts32(pa + 896 + 1152 - km, 0u); sts64(l8 + 896 - 256, 0u, 0u);
  m0 = fmaxf(m0, __shfl_xor_sync(~0u, m0, 2)); m1 = fmaxf(m1, __shfl_xor_sync(~0u, m1, 2));
  m0 *= -SL2; m1 *= -SL2;
#pragma unroll
  for (int j = 0; j < 14; j++) x[j] = ex2(fmaf(x[j], SL2, j < 8 ? m0 : j >= 10 ? m1 : w1 ? m1 : m0));
  const float l4s = x[8] + x[9];
  float l0 = ((x[0] + x[1]) + (x[2] + x[3])) + ((x[4] + x[5]) + (x[6] + x[7])), l1 = (x[10] + x[11]) + (x[12] + x[13]);
  if (w1) l1 += l4s; else l0 += l4s;
  l0 += __shfl_xor_sync(~0u, l0, 1); l1 += __shfl_xor_sync(~0u, l1, 1);
  l0 += __shfl_xor_sync(~0u, l0, 2); l1 += __shfl_xor_sync(~0u, l1, 2);
  l0 = rcpf(l0); l1 = rcpf(l1);
#pragma unroll
  for (int j = 0; j < 7; j++) {
    const float iv = j < 4 ? l0 : j > 4 ? l1 : w1 ? l1 : l0;
    sts32(pa + (j < 3 ? j * 128 : j == 3 ? km : j == 4 ? (w1 ? 896 + 128 : 384) : j == 5 ? 896 : 896 + km), pack2(x[2 * j] * iv, x[2 * j + 1] * iv));
  }
}
template <int N>
__device__ __forceinline__ void wo_phase(uint32_t sb, int wg, int warp, int lane, uint32_t par, uint32_t r1) {
  const uint32_t bar = sb + OFF_BAR;
  float x[N / 2], y[N / 2];
  const uint2 ta = lds64(sb + OFF_TAB + (wg * 4 + warp) * 8);
  uint32_t xa = (ta.x & ~255u) + lane * 8, xb = (ta.x & 0xFF0000FFu) + SMEM0 + OFF_BAR, ya = (ta.y & ~255u) + lane * 8, yb = (ta.y & 0xFF0000FFu) + SMEM0 + OFF_BAR;
  asm volatile("" : "+r"(xa), "+r"(xb), "+r"(ya), "+r"(yb));
  auto scat = [&](uint32_t ad, uint32_t mb, const float* d) {
    st_async_v2(ad, pack2(d[0], d[1]), pack2(d[2], d[3]), mb);
    if (N == 16) st_async_v2(ad + LAND_F, pack2(d[4], d[5]), pack2(d[6], d[7]), mb);
  };
  if (wg == 0) {
    bar_sync(N_O, 384);
    wg_fence(); wo4<N, 4, 0, 0>(x); wo4<N, 8, 0, 0>(y); wg_commit();
    mbar_waitu(bar + 8 * B_OPEER, par);
    CFENCE(); wg_fence(); wo4<N, 16, 1, 1>(x); wo4<N, 20, 2, 1>(x); wg_commit();
    wo4<N, 24, 1, 1>(y); wg_commit();
    mbar_waitu2(bar + 8 * B_WOF, bar + 8 * B_MEMFREE, par);
    wg_fence(); wo4<N, 28, 2, 1>(y); wg_commit();
    bar_arrive(N_AB, 256);
    wg_wait<2>(); scat(xa, xb, x);
    wg_wait<0>(); scat(ya, yb, y);
  } else {
    bar_sync(N_O, 384);
    wg_fence(); wo4<N, 0, 0, 0>(x); wg_commit(); wo4<N, 12, 0, 0>(y); wg_commit();
    wg_wait<1>(); mbar_arrive_remote_if(lane == 0, r1);
    mbar_waitu(bar + 8 * B_MEMFREE, par);
    scat(xa, xb, x);
    bar_sync(N_AB, 256);
    CFENCE(); wg_fence(); wo4<N, 32, 1, 1>(y); wo4<N, 36, 2, 1>(y); wg_commit();
    bar_arrive(N_TURN, 256);
    wg_wait<0>(); scat(ya, yb, y);
  }
}
#define DS_DUAL 10
#define DS_SINGLE 20
#define POLL_GAP 100
#define POLL_GAPD 0
#define TOK_DELAY 250
#define LATE_SM 1
#define UMAX 40
#define VD1 6
#define VS1 4
#define VST 17
struct AMaps { CUtensorMap w16[3], wo32; };
__global__ void __launch_bounds__(512, 1)
acore_kernel(const __grid_constant__ AMaps M, const __nv_bfloat16* __restrict__ mem0, int sync_b) {
  extern __shared__ __align__(1024) unsigned char smem_raw[];
  const uint32_t sb = smem_u32(smem_raw);
  GTS(24);
  if (threadIdx.x == 0) {
    uint32_t smid; asm volatile("mov.u32 %0, %%smid;" : "=r"(smid));
    g_tpc[(smid >> 1) & 127] = 1;
    __threadfence();
    asm volatile("griddepcontrol.launch_dependents;");
  }
  const int lane0 = threadIdx.x & 31;
#define LANE_INIT() int lane; asm volatile("mov.u32 %0, %%laneid;" : "=r"(lane))
  const int warp = __shfl_sync(~0u, (threadIdx.x >> 5) & 3, 0);
  const int cl = blockIdx.x / CL_SIZE;
  const uint32_t rank = blockIdx.x - cl * CL_SIZE;
  const int nh = cl >= 1 && cl <= 3 ? 4 : 5;
  const int nA = 3 * nh;
  const int wg = __shfl_sync(~0u, (int)rank < nA ? threadIdx.x >> 7 : 4, 0);
  const int head = (cl < 4 ? (cl ? 1 + 4 * cl : 0) : 5 * cl - 3) + rank / 3;
  const int t3 = rank % 3;
  const int col0 = head * DH + t3 * 64;
  const uint32_t bar = sb + OFF_BAR;
  const uint32_t rb0 = SMEM0;
  const uint16_t mcmask = (uint16_t)((1u << nA) - 1);
  const uint32_t nxt = sb + ((t3 == 2 ? -2 : 1) << 24), prv = sb + ((t3 == 0 ? 2 : -1) << 24);
  const int ig = (int)rank - (nA - 4);

  if (threadIdx.x == 0) {
    if (mapa(sb, nA - 1) != rb0 + ((nA - 1) << 24) || mapa(sb, 0) != rb0 || mapa(sb, 1) != rb0 + (1u << 24) || sb != SMEM0 + (rank << 24)) FAIL();
    for (int i = 0; i < B_NUM; i++)
      mbar_init(bar + 8 * i, i == B_R1 ? 4 * nA : i == B_R2 ? 12 * nA : i == B_MEMFREE ? nA : i == B_LANDFREE ? 4 * nA : i == B_PLFREE || i == B_XFREE ? 2 : 1);
    asm volatile("fence.mbarrier_init.release.cluster;" ::: "memory");
    mbar_expect(bar + 8 * B_W0, (80 + SSV + VST) * 2048);
  }
  __syncthreads();
  if (lane0 == 0) {
    const int w12 = wg * 4 + warp;
    if (w12 < 10) {
#pragma unroll 1
      for (int ks = 4 * w12; ks < 4 * w12 + 4; ks++) {
        const bool ss = is_ss(ks, SSQ);
        tma2d(ss ? sb + OFF_WS + ss_idx(ks, SSQ) * 2048 : sb + STG_Q + rs_idx(ks, SSQ) * 2048, &M.w16[0], col0, ks * 16, bar + 8 * B_W0);
        tma2d(ss ? sb + OFF_WS + (SSQ + ss_idx(ks, SSQ)) * 2048 : sb + STG_K + rs_idx(ks, SSQ) * 2048, &M.w16[1], col0, ks * 16, bar + 8 * B_W0);
        if (is_ss(ks, SSV)) tma2d(sb + OFF_WS + (2 * SSQ + ss_idx(ks, SSV)) * 2048, &M.w16[2], col0, ks * 16, bar + 8 * B_W0);
        else if (rs_idx(ks, SSV) < VST) tma2d(sb + (rs_idx(ks, SSV) < VA ? STG_K + 27 * 2048 : STG_V2 - VA * 2048) + rs_idx(ks, SSV) * 2048, &M.w16[2], col0, ks * 16, bar + 8 * B_W0);
        else tma2d_prefetch(&M.w16[2], col0, ks * 16);
      }
      int c0, c1;
      wo_coord(2 * w12, t3, head, c0, c1);
      tma2d_prefetch(&M.wo32, c0, c1);
      tma2d_prefetch(&M.wo32, c0, c1 + 32);
    }
  }
  static_assert(40 - SSV - VST <= 10, "staging");
  if (lane0 < 2 && wg < 2) {
    const int u = 4 * (wg ? (lane0 ? 6 + t3 : 9) : (lane0 ? 3 + t3 : t3)) + warp;
    const int li = (u >= nA) + (u >= 2 * nA) + (u >= 3 * nA);
    sts32(sb + OFF_TAB + (wg * 4 + warp) * 8 + lane0 * 4,
          rb0 + ((u - li * nA) << 24) + OFF_TILE + LAND(li + (u >= 36 ? t3 : 0)) + (rank / 3) * 256 + 8 * (B_RS + li));
  }
  __syncthreads();
  GTS(25);

  auto issue_tok = [&](int sc, int fb, int rel = -1, uint32_t ph = 0) {
    if (sync_b) wait_cnt(&g_xready[sc][0], 32);
    if (rel >= 0) mbar_waitu(bar + 8 * rel, ph);
    bulk_g2s_mc_e(sb + OFF_TILE + ig * TILE_GRP + TILE_SBO, &g_xn[0][0] + uni(sc * (32 * DM)) + ig * 5120, 10240, bar + 8 * (fb + ig), mcmask);
  };
#define POLL(d, q) _Pragma("unroll") for (int k = 0; k < NCL; k++) \
      asm volatile("ld.relaxed.gpu.global.v2.b32 {%0,%1}, [%2];" : "=r"(d[k].x), "=r"(d[k].y) : "l"(q + k * 2560) : "memory")
#define L3(L, a, b, c) lop3<L>(a, b, c)
#define TAGS(L, d) L3(L, L3(L, L3(L, d[0].x, d[0].y, d[1].x), L3(L, d[1].y, d[2].x, d[2].y), L3(L, d[3].x, d[3].y, d[4].x)), L3(L, d[4].y, d[5].x, d[5].y), L3(L, d[6].x, d[6].y, d[6].y))
    auto deliver = [&](uint2* pa, const uint32_t* gq, int u, int c, int dc, int ds, int step, bool first, int lane) {
      const uint32_t off = uni(OFF_TILE + ((u * 205) >> 11) * (TILE_GRP - TILE_SBO) + u * 256 + dc * LAND_F), boff = uni(OFF_BAR + 8 * (B_F1 + ((u * 205) >> 11)));
      const uint32_t* mi = &g_part[4][0][0][0] + uni((c * NCL + cl) * 2560 + u * 64);
      mbar_waitu(bar + 8 * B_LANDFREE, step & 1);
      int n = 0;
      while (true) {
        const bool ok = __all_sync(~0u, ((step & 2 ? ~TAGS(0xFE, pa) : TAGS(0x80, pa)) & 1) != 0);
        if (ok) break;
        if (++n > SPIN_LIMIT) FAIL();
        POLL(pa, gq);
      }
      if (warp == 0 && first) { TS(19); TSV(10, n); }
      const uint32_t w0 = hadd2bf(hadd2bf(hadd2bf(pa[0].x, pa[1].x), hadd2bf(pa[2].x, pa[3].x)), hadd2bf(hadd2bf(pa[4].x, pa[5].x), pa[6].x));
      const uint32_t w1 = hadd2bf(hadd2bf(hadd2bf(pa[0].y, pa[1].y), hadd2bf(pa[2].y, pa[3].y)), hadd2bf(hadd2bf(pa[4].y, pa[5].y), pa[6].y));
      if (u < ds) {
        const uint32_t da = SMEM0 + off + lane * 8, db = SMEM0 + boff;
#pragma unroll
        for (int d = 0; d < 12; d++) st_async_v2((d << 24) + da, w0, w1, (d << 24) + db);
#pragma unroll
        for (int d = 12; d < 15; d++) st_async_v2_if(nA == 15, (d << 24) + da, w0, w1, (d << 24) + db);
      } else {
        *reinterpret_cast<uint2*>(const_cast<uint32_t*>(gq) + ((4 - 2 * (step & 1)) * NCL + cl) * 2560) = make_uint2(w0, w1);
        asm volatile("fence.proxy.async.global;" ::: "memory");
        __syncwarp();
        bulk_g2s_mc_e(sb + off, mi, 256, sb + boff, mcmask);
      }
    };
#define REL(b, g) mbar_arrive_remote_if(lane == 0, rb0 + ((nA - 4 + (g)) << 24) + OFF_BAR + 8 * (b))

  if (wg < 2) {
    asm volatile("setmaxnreg.inc.sync.aligned.u32 160;");
    LANE_INIT();
    uint32_t W[4 * (40 - SSQ)];
    mbar_waitw(bar + 8 * B_W0, 0);
    GTS(26);
    load_w<40 - SSQ>(W, sb + (wg ? STG_K : STG_Q), warp, lane);
    fence_async();
    bar_sync(1, 384);
    cluster_sync_all();
    const uint32_t wbase = wg * SSQ;
    GTS(27);
#pragma unroll 1
    for (int step = -1; step < NSTEP; step++) {
      const uint32_t par = step & 1;
      asm volatile("" : "+r"(lane));
      const bool dual = is_dual(step), has_next = step + 1 < NSTEP;
#define QK_SA (sb + OFF_QK + wg * 15360 + (2 * warp + ((lane >> 3) & 1)) * 128 + (lane & 7) * 16)
#define QK_F (wg ? -5120 : 5120)
#define QK_S12 ((wg ? (lane >> 4) : 1 + 2 * (lane >> 4)) * 1024)
#define QK_S34 ((wg ? 2 + (lane >> 4) : 2 - 2 * (lane >> 4)) * 1024)
      if (step >= 0) {
        if (dual) {
          float acc[24];
          mbar_waitu(bar + 8 * (B_F1 + 0), par);
          if (wg + warp == 0) { TS(0); TSN(1); }
          CFENCE(); wg_fence(); proj<48, SSQ, 0, 0, 10>(acc, W, wbase); wg_commit();
          mbar_waitu(bar + 8 * (B_F1 + 1), par);
          CFENCE(); wg_fence(); proj<48, SSQ, 0, 10, 20>(acc, W, wbase); wg_commit();
          mbar_waitu(bar + 8 * (B_F1 + 2), par);
          CFENCE(); wg_fence(); proj<48, SSQ, 0, 20, 30>(acc, W, wbase); wg_commit();
          mbar_waitu2(bar + 8 * (B_F1 + 3), bar + 8 * B_PLFREE, par);
          if (wg + warp == 0) TS(2);
          CFENCE(); wg_fence(); proj<48, SSQ, 0, 30, 40>(acc, W, wbase); wg_commit();
          bar_arrive(N_VGO, 384);
          const uint32_t sa = QK_SA, s0 = sa + 4096 + (lane >> 4) * QK_F, s1 = sa + QK_F + QK_S12, s2 = sa + QK_F + QK_S34;
          wg_wait<0>();
          if (wg + warp == 0) TS(3);
          stsm4t(s0, pack2(acc[0], acc[1]), pack2(acc[2], acc[3]), pack2(acc[20], acc[21]), pack2(acc[22], acc[23]));
          stsm4t(s1, pack2(acc[4], acc[5]), pack2(acc[6], acc[7]), pack2(acc[8], acc[9]), pack2(acc[10], acc[11]));
          stsm4t(s2, pack2(acc[12], acc[13]), pack2(acc[14], acc[15]), pack2(acc[16], acc[17]), pack2(acc[18], acc[19]));
        } else {
          float acc[4];
          mbar_waitu(bar + 8 * (B_F1 + 0), par);
          if (wg + warp == 0) { TS(0); TSN(1); }
          CFENCE(); wg_fence(); proj<8, SSQ, 0, 0, 10>(acc, W, wbase); wg_commit();
          mbar_waitu(bar + 8 * (B_F1 + 1), par);
          CFENCE(); wg_fence(); proj<8, SSQ, 0, 10, 20>(acc, W, wbase); wg_commit();
          mbar_waitu(bar + 8 * (B_F1 + 2), par);
          CFENCE(); wg_fence(); proj<8, SSQ, 0, 20, 30>(acc, W, wbase); wg_commit();
          mbar_waitu2(bar + 8 * (B_F1 + 3), bar + 8 * B_PLFREE, par);
          if (wg + warp == 0) TS(2);
          CFENCE(); wg_fence(); proj<8, SSQ, 0, 30, 40>(acc, W, wbase); wg_commit();
          bar_arrive(N_VGO, 384);
          const uint32_t s0 = QK_SA + 4096;
          wg_wait<0>();
          if (wg + warp == 0) TS(3);
          stsm2t(s0, pack2(acc[0], acc[1]), pack2(acc[2], acc[3]));
        }
        fence_async();
        bar_sync(N_QK, 256);
        if (wg == 0 || dual) {
          float s[20];
          const uint32_t ab = wg * 192, bb = wg * -320;
          wg_fence();
          MM<40>::ss2<dlo(OFF_QK, 128), dhi(1024, 0), dlo(OFF_QK + 15360, 128), dhi(1024, 0), 0>(s, ab, bb);
          MM<40>::ss2<dlo(OFF_QK + 256, 128), dhi(1024, 0), dlo(OFF_QK + 15360 + 256, 128), dhi(1024, 0), 1>(s, ab, bb);
          MM<40>::ss2<dlo(OFF_QK + 512, 128), dhi(1024, 0), dlo(OFF_QK + 15360 + 512, 128), dhi(1024, 0), 1>(s, ab, bb);
          MM<40>::ss2<dlo(OFF_QK + 768, 128), dhi(1024, 0), dlo(OFF_QK + 15360 + 768, 128), dhi(1024, 0), 1>(s, ab, bb);
          wg_commit();
          bar_arrive(N_SISS, 384);
          const int rw = (warp - wg) & 3;
          const uint32_t bo = OFF_BAR + 8 * (B_SB + 3 * wg + rw), lo = OFF_PL + wg * PL_SZ + rw * 1792;
          const uint32_t km = wg ? 640 : 512;
          uint32_t l16 = lo + lane * 16, l4 = lo + lane * 4;
          mbar_expect_if(lane == 0 && rw < 3, sb + bo, rw < 2 ? 1792 : 1280);
          asm volatile("" : "+r"(l16), "+r"(l4));
          if (rw == 2) {
            wg_wait<0>();
            if (wg == 0) TSD(4, __float_as_uint(s[0]));
            {
              const uint32_t w0 = pack2(s[0], s[1]), w1 = pack2(s[4], s[5]), w2 = pack2(s[8], s[9]), w3 = pack2(s[12], s[13]), w4 = pack2(s[16], s[17]);
              st_async_v4(nxt + 896 + l16, w0, w1, w2, w3, nxt + bo);
              st_async_v4(prv + l16, w0, w1, w2, w3, prv + bo);
              st_async_b32(nxt + 896 + 768 + l4, w4, nxt + bo);
              st_async_b32(prv + 768 + l4, w4, prv + bo);
            }
            bar_arrive(N_SDONE, 256);
            mbar_waitu(sb + bo, (step - wg * LAG) & 1);
            if (wg == 0) TS(5);
            float x[10];
            {
              const uint4 a = lds128(sb + l16), b = lds128(sb + 896 + l16);
              const uint32_t c = lds32(sb + 768 + l4), d = lds32(sb + 896 + 768 + l4);
              const uint32_t e0 = hadd2bf(a.x, b.x), e1 = hadd2bf(a.y, b.y), e2 = hadd2bf(a.z, b.z), e3 = hadd2bf(a.w, b.w), e4 = hadd2bf(c, d);
              x[0] = s[0] + bf_lo(e0); x[1] = s[1] + bf_hi(e0); x[2] = s[4] + bf_lo(e1); x[3] = s[5] + bf_hi(e1); x[4] = s[8] + bf_lo(e2);
              x[5] = s[9] + bf_hi(e2); x[6] = s[12] + bf_lo(e3); x[7] = s[13] + bf_hi(e3); x[8] = s[16] + bf_lo(e4); x[9] = s[17] + bf_hi(e4);
            }
            float m0 = fmaxf(fmaxf(fmaxf(x[0], x[1]), fmaxf(x[2], x[3])), fmaxf(fmaxf(x[4], x[5]), fmaxf(fmaxf(x[6], x[7]), fmaxf(x[8], x[9]))));
            m0 = fmaxf(m0, __shfl_xor_sync(~0u, m0, 1));
            sts32(sb + l4 + 1152 - km, 0u);
            m0 = fmaxf(m0, __shfl_xor_sync(~0u, m0, 2));
            m0 *= -SL2;
#pragma unroll
            for (int j = 0; j < 5; j++) {
              x[2 * j] = ex2(fmaf(x[2 * j], SL2, m0)); x[2 * j + 1] = ex2(fmaf(x[2 * j + 1], SL2, m0));
              sts32(sb + l4 + (j < 4 ? j * 128 : km), pack2(x[2 * j], x[2 * j + 1]));
            }
            float l = ((x[0] + x[1]) + (x[2] + x[3])) + ((x[4] + x[5]) + ((x[6] + x[7]) + (x[8] + x[9])));
            l += __shfl_xor_sync(~0u, l, 1);
            fence_async();
            sts32(sb + OFF_INV + wg * 64 + (lane >> 1) * 4, __float_as_uint(l));
            bar_arrive(N_PM, dual ? 224 : 192);
            if (wg == 0) TS(6);
          } else if (rw < 2) {
            const bool w1 = rw == 1;
            const uint32_t l8 = lo + 512 + lane * 8;
            uint32_t tw[7];
            wg_wait<0>();
            bar_arrive(N_SDONE, 256);
            tw[0] = pack2(s[0], s[1]); tw[1] = pack2(s[4], s[5]); tw[2] = pack2(s[8], s[9]); tw[3] = pack2(s[16], s[17]);
            tw[4] = w1 ? pack2(s[6], s[7]) : pack2(s[12], s[13]); tw[5] = pack2(s[2], s[3]); tw[6] = pack2(s[18], s[19]);
            { const uint32_t t0 = clock32(); while (clock32() - t0 < TOK_DELAY) {} }
            st_async_v4(nxt + 896 + l16, tw[0], tw[1], tw[2], tw[3], nxt + bo);
            st_async_v4(prv + l16, tw[0], tw[1], tw[2], tw[3], prv + bo);
            st_async_v2(nxt + 896 + l8, tw[5], tw[6], nxt + bo);
            st_async_v2(prv + l8, tw[5], tw[6], prv + bo);
            st_async_b32(nxt + 896 + 768 + l4, tw[4], nxt + bo);
            st_async_b32(prv + 768 + l4, tw[4], prv + bo);
            mbar_waitu(sb + bo, (step - wg * LAG) & 1);
            const uint4 a = lds128(sb + l16), b = lds128(sb + 896 + l16);
            const uint2 e = lds64(sb + l8), f = lds64(sb + 896 + l8);
            const uint32_t c = lds32(sb + 768 + l4), d = lds32(sb + 896 + 768 + l4);
            sts128(sb + l16, hadd2bf(hadd2bf(a.x, b.x), tw[0]), hadd2bf(hadd2bf(a.y, b.y), tw[1]), hadd2bf(hadd2bf(a.z, b.z), tw[2]), hadd2bf(hadd2bf(a.w, b.w), tw[3]));
            sts64(sb + l8, hadd2bf(hadd2bf(e.x, f.x), tw[5]), hadd2bf(hadd2bf(e.y, f.y), tw[6]));
            sts32(sb + 768 + l4, hadd2bf(hadd2bf(c, d), tw[4]));
            bar_arrive(N_PX, dual ? 256 : 192);
            if (wg + warp == 0) TS(9);
          } else {
            wg_wait<0>();
            if (wg == 0) {
              mbar_expect_if(lane < 3 && has_next, bar + 8 * (lane == 2 ? B_OPEER : B_WOF + lane), lane == 2 ? (dual ? 4096 : 2048) : lane ? 8192 : 20480);
              auto fetch = [&](int i, int n, uint32_t dst, int mb) {
                int c0, c1; wo_coord(i, t3, head, c0, c1);
                tma2d_e(dst, &M.wo32, c0, c1, bar + 8 * mb); if (n == 2) tma2d_e(dst + 4096, &M.wo32, c0, c1 + 32, bar + 8 * mb);
              };
              bar_sync(N_G3, 160);
              if (has_next) {
                fetch(0, 2, sb + OFF_WT, B_WTF);
                mbar_arrive_remote_if(lane < 2, (lane ? nxt : prv) + OFF_BAR + 8 * B_XFREE);
              }
              bar_sync(N_SDONE, 256);
              if (has_next) {
                fetch(15, 1, sb + OFF_QK, B_WOF); fetch(16, 2, sb + OFF_QK + 4096, B_WOF); fetch(18, 2, sb + OFF_QK + 12288, B_WOF);
                mbar_waitu(bar + 8 * B_XFREE, par);
              }
              bar_arrive(N_PM, dual ? 224 : 192);
              bar_sync(N_VDONE, 160);
              mbar_arrive_remote_if(lane < nA && has_next, rb0 + (lane << 24) + OFF_BAR + 8 * B_MEMFREE);
              if (has_next) mbar_waitu(bar + 8 * B_WTF, par);
            } else {
              bar_arrive(N_SDONE, 256);
              if ((unsigned)ig < 3) issue_tok(sched_l(step + 1), B_F2, B_R1, (step - LAG) & 1);
            }
          }
        } else {
          bar_arrive(N_SISS, 384);
          bar_arrive(N_SDONE, 256);
        }
        if (has_next) {
          if (step == 0) mbar_waitw(bar + 8 * B_W0, 1);
          const uint32_t r1 = rb0 + ((nA - 1) << 24) + OFF_BAR + 8 * B_R1;
          if (dual) wo_phase<16>(sb, wg, warp, lane, par, r1); else wo_phase<8>(sb, wg, warp, lane, par, r1);
          bar_arrive(N_C, 288);
          if (warp == 0) TS(7 + wg);
        }
      }
      if (has_next) {
        float acc[16];
        mbar_waitu(bar + 8 * B_F2, par ^ 1);
        wg_fence(); proj<32, SSQ, 1, 0, 10>(acc, W, wbase); wg_commit();
        mbar_waitu(bar + 8 * (B_F2 + 1), par ^ 1);
        wg_fence(); proj<32, SSQ, 1, 10, 14>(acc, W, wbase); wg_commit();
        wg_wait<1>(); REL(B_R2, 0);
        wg_fence(); proj<32, SSQ, 1, 14, 20>(acc, W, wbase); wg_commit();
        mbar_waitu(bar + 8 * (B_F2 + 2), par ^ 1);
        wg_fence(); proj<32, SSQ, 1, 20, 24>(acc, W, wbase); wg_commit();
        wg_wait<1>(); REL(B_R2, 1);
        wg_fence(); proj<32, SSQ, 1, 24, 30>(acc, W, wbase); wg_commit();
        mbar_waitu(bar + 8 * (B_F2 + 3), par ^ 1);
        wg_fence(); proj<32, SSQ, 1, 30, 34>(acc, W, wbase); wg_commit();
        wg_wait<1>(); REL(B_R2, 2);
        wg_fence(); proj<32, SSQ, 1, 34, 40>(acc, W, wbase); wg_commit();
        const uint32_t sa = QK_SA, s1 = sa + QK_S12, s2 = sa + QK_S34;
        wg_wait<0>(); REL(B_R2, 3);
        if (warp == 0) TS(11 + wg);
        stsm4t(s1, pack2(acc[0], acc[1]), pack2(acc[2], acc[3]), pack2(acc[4], acc[5]), pack2(acc[6], acc[7]));
        stsm4t(s2, pack2(acc[8], acc[9]), pack2(acc[10], acc[11]), pack2(acc[12], acc[13]), pack2(acc[14], acc[15]));
      }
    }
    GTS(28);
    cluster_sync_all();
  } else if (wg == 2) {
    asm volatile("setmaxnreg.inc.sync.aligned.u32 160;");
    LANE_INIT();
    uint32_t W[4 * (40 - SSV)];
    mbar_waitw(bar + 8 * B_W0, 0);
    load_w<VA>(W, sb + STG_K + 27 * 2048, warp, lane);
    load_w<VST - VA>(W + 4 * VA, sb + STG_V2, warp, lane);
    fence_async();
    bar_sync(1, 384);
    if (lane == 0) {
      if (warp == 0) {
        mbar_expect(bar + 8 * B_W1, (40 - SSV - VST) * 2048);
#pragma unroll 1
        for (int ks = 0; ks < 40; ks++)
          if (!is_ss(ks, SSV) && rs_idx(ks, SSV) >= VST) tma2d(sb + OFF_QK + (rs_idx(ks, SSV) - VST) * 2048, &M.w16[2], col0, ks * 16, bar + 8 * B_W1);
      } else {
        if (warp == 1) mbar_expect(bar + 8 * B_W0, 26 * 2048);
#pragma unroll 1
        for (int i = warp - 1; i < 13; i += 3) { int c0, c1; wo_coord(i + 2, t3, head, c0, c1); tma2d(sb + OFF_WO + i * 4096, &M.wo32, c0, c1, bar + 8 * B_W0); }
      }
    }
    __syncwarp();
#pragma unroll
    for (int i = 0; i < 5; i++) {
      const int t = i * 128 + warp * 32 + lane;
      const uint4 v = *reinterpret_cast<const uint4*>(mem0 + (t & 7) * DM + (t >> 3) * 8);
      sts128(sb + OFF_TILE + (t / 160) * (TILE_GRP - TILE_SBO) + t * 16, v.x, v.y, v.z, v.w);
    }
    mbar_waitw(bar + 8 * B_W1, 0);
    load_w<40 - SSV - VST>(W + 4 * VST, sb + OFF_QK, warp, lane);
    fence_async();
    mbar_arrive_if(lane == 0, bar + 8 * (B_F1 + warp));
    mbar_expect_if(lane == 0, bar + 8 * (B_F2 + warp), 10240);
    mbar_arrive_if(warp == 3 && lane < 2, bar + 8 * B_PLFREE);
    cluster_sync_all();
    uint32_t vl[8];
    constexpr uint32_t wbase = 2 * SSQ;
    {
      float v[16];
      mbar_waitw4(bar + 8 * B_F2, 0);
      wg_fence(); proj<32, SSV, 1, 0, 40>(v, W, wbase); wg_commit();
      wg_wait<0>();
      mbar_arrive_remote_if(lane < 4, rb0 + ((nA - 4 + lane) << 24) + OFF_BAR + 8 * B_R2);
#pragma unroll
      for (int j = 0; j < 8; j++) vl[j] = pack2v(v[2 * j], v[2 * j + 1]);
      if (warp == 0 && (unsigned)ig < 3) issue_tok(1, B_F2, B_R2, 0);
    }
#pragma unroll 1
    for (int step = 0; step < NSTEP; step++) {
      const uint32_t par = step & 1;
      asm volatile("" : "+r"(lane));
      const bool dual = is_dual(step), has_next = step + 1 < NSTEP;
      mbar_expect_if(lane == 0 && has_next, bar + 8 * (B_F2 + warp), 10240);
      if (warp == 0 && ig == 3 && has_next && sync_b) wait_cnt(&g_xready[sched_l(step + 1)][0], 32);
      bar_sync(N_VGO, 384);
      CFENCE();
#define F1_BYTES (is_dual(step + 1) ? 15360 : 2560)
#define ARM() do { \
        mbar_expect_if(lane == 0 && has_next, bar + 8 * (B_F1 + warp), F1_BYTES); \
        mbar_expect_if(lane == 0 && has_next && warp * nA + (int)rank < 40, bar + 8 * (B_RS + warp), (warp * nA + (int)rank >= 36 ? nA : nh) * (dual ? 512 : 256)); } while (0)
#define O_ADDR() uint32_t oa = sb + OFF_O + (lane >> 4) * PL_SZ + warp * 256 + (lane & 15) * 16, xo = (lane >> 4) * 1024 + warp * 256 + (lane & 15) * 16; \
        asm volatile("" : "+r"(oa), "+r"(xo))
#define O_READY(act) do { if (has_next) { const uint4 ov = lds128(oa); \
        if (act) { st_async_v4(nxt + OFF_XL + xo, ov.x, ov.y, ov.z, ov.w, nxt + OFF_BAR + 8 * B_OPEER); \
                   st_async_v4(prv + OFF_XF + xo, ov.x, ov.y, ov.z, ov.w, prv + OFF_BAR + 8 * B_OPEER); } \
        fence_async(); bar_arrive(N_O, 384); } \
        if (warp == 0) TS(15); } while (0)
#define TOK_L3() if (warp == 0 && ig == 3 && has_next) { mbar_waitu(bar + 8 * B_R1, par); \
        bulk_g2s_mc_e(sb + OFF_TILE + 3 * TILE_GRP + TILE_SBO, &g_xn[0][0] + uni(sched_l(step + 1) * (32 * DM)) + 3 * 5120, 10240, bar + 8 * (B_F2 + 3), mcmask); }
#define OX_SA (sb + OFF_PL + (lane & 7) * 128 + (((warp * 2 + ((lane >> 3) & 1)) ^ (lane & 7)) << 4))
      if (dual) {
        uint32_t vf[8], vm[4], vn[8];
        {
          float v[24];
          wg_fence(); proj<48, SSV, 0, 30, 30 + VD1, 30>(v, W, wbase); wg_commit();
          ARM();
          bar_sync(N_SISS, 384);
          wg_fence(); proj<48, SSV, 0, 30 + VD1, 40, 30>(v, W, wbase); wg_commit();
          proj<48, SSV, 0, 0, 3, 30>(v, W, wbase); wg_commit();
          wg_wait<1>(); bar_arrive(N_G3, 160);
          wg_fence(); proj<48, SSV, 0, 3, 10, 30>(v, W, wbase); wg_commit();
          proj<48, SSV, 0, 10, 13, 30>(v, W, wbase); wg_commit();
          wg_wait<1>(); REL(B_R1, 0);
          wg_fence(); proj<48, SSV, 0, 13, 20, 30>(v, W, wbase); wg_commit();
          proj<48, SSV, 0, 20, 23, 30>(v, W, wbase); wg_commit();
          wg_wait<1>(); REL(B_R1, 1);
          wg_fence(); proj<48, SSV, 0, 23, 30, 30>(v, W, wbase); wg_commit();
          wg_wait<0>(); REL(B_R1, 2);
          bar_arrive(N_VDONE, 160);
          if (warp == 0) TS(14);
#pragma unroll
          for (int j = 4; j < 8; j++) vf[j] = pack2v(v[4 + 2 * j], v[5 + 2 * j]);
          keep4(vf + 4, lane);
          vm[0] = pack2v(v[0], v[1]); vm[1] = pack2v(v[2], v[3]); vm[2] = pack2v(v[20], v[21]); vm[3] = pack2v(v[22], v[23]);
          keep4(vm, lane);
#pragma unroll
          for (int j = 0; j < 4; j++) vf[j] = pack2v(v[4 + 2 * j], v[5 + 2 * j]);
          keep4(vf, lane);
        }
        {
          float o[8];
          O_ADDR();
          bar_sync(N_PM, 224);
          wg_fence();
          MM<8>::rs<dlo(OFF_PL + 3584, 128), dhi(896, 0), 0>(o, vl[0], vl[1], vl[2], vl[3]);
          MM<8>::rs<dlo(OFF_PL + PL_SZ + 3584, 128), dhi(896, 0), 0>(o + 4, vf[0], vf[1], vf[2], vf[3]);
          MM<8>::rs<dlo(OFF_PL + 3584 + 256, 128), dhi(896, 0), 1>(o, vl[4], vl[5], vl[6], vl[7]);
          MM<8>::rs<dlo(OFF_PL + PL_SZ + 3584 + 256, 128), dhi(896, 0), 1>(o + 4, vf[4], vf[5], vf[6], vf[7]);
          MM<8>::rs<dlo(OFF_PL + 3584 + 512, 128), dhi(896, 0), 1>(o, vm[0], vm[1], vm[2], vm[3]);
          MM<8>::rs<dlo(OFF_PL + PL_SZ + 3584 + 512, 128), dhi(896, 0), 1>(o + 4, vm[0], vm[1], vm[2], vm[3]);
          wg_commit();
          const uint4 il = lds128(sb + OFF_INV + (lane & 3) * 16), jf = lds128(sb + OFF_INV + 64 + (lane & 3) * 16);
          const float i0 = rcpf(__uint_as_float(il.x) + __uint_as_float(il.y)), i1 = rcpf(__uint_as_float(il.z) + __uint_as_float(il.w));
          const float j0 = rcpf(__uint_as_float(jf.x) + __uint_as_float(jf.y)), j1 = rcpf(__uint_as_float(jf.z) + __uint_as_float(jf.w));
          wg_wait<0>();
          stsm4t(oa, pack2(o[0] * i0, o[1] * i1), pack2(o[2] * i0, o[3] * i1), pack2(o[4] * j0, o[5] * j1), pack2(o[6] * j0, o[7] * j1));
          O_READY(true);
          TOK_L3();
        }
        {
          float v[16];
          bar_sync(N_TURN, 256);
          mbar_waitu(bar + 8 * B_F2, par ^ 1);
          wg_fence(); proj<32, SSV, 1, 0, 10>(v, W, wbase); wg_commit();
          mbar_waitu(bar + 8 * (B_F2 + 1), par ^ 1);
          wg_fence(); proj<32, SSV, 1, 10, 14>(v, W, wbase); wg_commit();
          wg_wait<1>(); REL(B_R2, 0);
          wg_fence(); proj<32, SSV, 1, 14, 20>(v, W, wbase); wg_commit();
          mbar_waitu(bar + 8 * (B_F2 + 2), par ^ 1);
          wg_fence(); proj<32, SSV, 1, 20, 24>(v, W, wbase); wg_commit();
          wg_wait<1>(); REL(B_R2, 1);
          wg_fence(); proj<32, SSV, 1, 24, 30>(v, W, wbase); wg_commit();
          mbar_waitu(bar + 8 * (B_F2 + 3), par ^ 1);
          wg_fence(); proj<32, SSV, 1, 30, 34>(v, W, wbase); wg_commit();
          wg_wait<1>(); REL(B_R2, 2);
          wg_fence(); proj<32, SSV, 1, 34, 40>(v, W, wbase); wg_commit();
          wg_wait<0>(); REL(B_R2, 3);
#pragma unroll
          for (int j = 0; j < 8; j++) vn[j] = pack2v(v[2 * j], v[2 * j + 1]);
          keep4(vn, lane); keep4(vn + 4, lane);
          if (warp == 0) TS(18);
        }
        uint32_t ow[16];
        bar_sync(N_P, 256);
        fence_async();
#define PV16(i, off, va) { float o[8]; wg_fence(); \
          MM<16>::rs<dlo(OFF_PL + (off), 128), dhi(896, 0), 0>(o, va[0], va[1], va[2], va[3]); \
          MM<16>::rs<dlo(OFF_PL + (off) + 256, 128), dhi(896, 0), 1>(o, va[4], va[5], va[6], va[7]); \
          MM<16>::rs<dlo(OFF_PL + (off) + 512, 128), dhi(896, 0), 1>(o, vm[0], vm[1], vm[2], vm[3]); \
          wg_commit(); wg_wait<0>(); \
          _Pragma("unroll") for (int j = 0; j < 4; j++) ow[4 * (i) + j] = pack2v(o[2 * j], o[2 * j + 1]); \
          keep4(ow + 4 * (i), lane); }
        PV16(0, 0, vl) PV16(1, 1792, vl) PV16(2, PL_SZ, vf) PV16(3, PL_SZ + 1792, vf)
        const uint32_t s1 = OX_SA + (lane < 16 ? 3072 : 0), s2 = OX_SA + (lane < 16 ? 2048 : 1024);
        bar_sync(N_V, 128);
        stsm4t(s1, ow[0], ow[1], ow[2], ow[3]);
        stsm4t(s2, ow[4], ow[5], ow[6], ow[7]);
        stsm4t(s1 + PL_SZ, ow[8], ow[9], ow[10], ow[11]);
        stsm4t(s2 + PL_SZ, ow[12], ow[13], ow[14], ow[15]);
#pragma unroll
        for (int j = 0; j < 8; j++) vl[j] = vn[j];
      } else {
        uint32_t vm[4], vn[8];
        {
          float v[4];
          wg_fence(); proj<8, SSV, 0, 30, 40, 30>(v, W, wbase); wg_commit();
          proj<8, SSV, 0, 0, VS1, 30>(v, W, wbase); wg_commit();
          ARM();
          bar_sync(N_SISS, 384);
          wg_wait<1>(); bar_arrive(N_G3, 160);
          wg_fence(); proj<8, SSV, 0, VS1, 30, 30>(v, W, wbase); wg_commit();
          if (has_next) { mbar_waitu2(bar + 8 * B_F2, bar + 8 * (B_F2 + 1), par ^ 1); mbar_waitu(bar + 8 * (B_F2 + 2), par ^ 1); }
          wg_wait<0>();
          bar_arrive(N_VDONE, 160);
          vm[0] = pack2v(v[0], v[1]); vm[1] = pack2v(v[2], v[3]); vm[2] = pack2v(v[1], v[0]); vm[3] = pack2v(v[3], v[2]);
        }
        float v[16];
        {
          wg_fence(); proj<32, SSV, 1, 0, 30>(v, W, wbase); wg_commit();
          {
            float o[4];
            O_ADDR();
            bar_sync(N_PM, 192);
            if (warp == 0) TS(14);
            wg_fence();
            MM<8>::rs<dlo(OFF_PL + 3584, 128), dhi(896, 0), 0>(o, vl[0], vl[1], vl[2], vl[3]);
            MM<8>::rs<dlo(OFF_PL + 3584 + 256, 128), dhi(896, 0), 1>(o, vl[4], vl[5], vl[6], vl[7]);
            MM<8>::rs<dlo(OFF_PL + 3584 + 512, 128), dhi(896, 0), 1>(o, vm[0], vm[1], vm[2], vm[3]);
            wg_commit();
            const uint4 il = lds128(sb + OFF_INV + (lane & 3) * 16);
            const float i0 = rcpf(__uint_as_float(il.x) + __uint_as_float(il.y)), i1 = rcpf(__uint_as_float(il.z) + __uint_as_float(il.w));
            wg_wait<0>();
            stsm2t(oa, pack2(o[0] * i0, o[1] * i1), pack2(o[2] * i0, o[3] * i1));
            O_READY(lane < 16);
            TOK_L3();
          }
          if (has_next) {
            mbar_arrive_remote_if(lane < 3, rb0 + ((nA - 4 + lane) << 24) + OFF_BAR + 8 * B_R2);
            bar_sync(N_TURN, 256);
            mbar_waitu(bar + 8 * (B_F2 + 3), par ^ 1);
          }
          wg_fence(); proj<32, SSV, 1, 30, 40>(v, W, wbase); wg_commit();
          wg_wait<0>();
          if (has_next) REL(B_R2, 3);
#pragma unroll
          for (int j = 0; j < 8; j++) vn[j] = pack2v(v[2 * j], v[2 * j + 1]);
          keep4(vn, lane); keep4(vn + 4, lane);
          if (warp == 0) TS(18);
        }
        float o[16];
        bar_sync(N_P, 256);
        fence_async();
        wg_fence();
        MM<32>::rs<dlo(OFF_PL, 128), dhi(896, 0), 0>(o, vl[0], vl[1], vl[2], vl[3]);
        MM<32>::rs<dlo(OFF_PL + 256, 128), dhi(896, 0), 1>(o, vl[4], vl[5], vl[6], vl[7]);
        MM<32>::rs<dlo(OFF_PL + 512, 128), dhi(896, 0), 1>(o, vm[0], vm[1], vm[2], vm[3]);
        wg_commit();
        const uint32_t s1 = OX_SA + (lane < 16 ? 3072 : 0), s2 = OX_SA + (lane < 16 ? 2048 : 1024);
        wg_wait<0>();
        bar_sync(N_V, 128);
        stsm4t(s1, pack2(o[0], o[1]), pack2(o[2], o[3]), pack2(o[4], o[5]), pack2(o[6], o[7]));
        stsm4t(s2, pack2(o[8], o[9]), pack2(o[10], o[11]), pack2(o[12], o[13]), pack2(o[14], o[15]));
#pragma unroll
        for (int j = 0; j < 8; j++) vl[j] = vn[j];
      }
      bar_arrive(N_OX, 160);
      if (warp == 0) TS(16);
    }
    cluster_sync_all();
  } else {
    asm volatile("setmaxnreg.dec.sync.aligned.u32 32;");
    if (wg > 3) return;
    LANE_INIT();
    struct RsJob { uint32_t* gp; uint32_t la, mb; int n; };
    auto rs_prep = [&](int step, int s, int c) {
      RsJob j;
      const int u = s * nA + rank;
      j.gp = &g_part[0][0][0][0] + (uint32_t)((((step & 1) * 2 + c) * NCL + cl) * 2560 + u * 64 + lane);
      j.la = sb + OFF_TILE + c * LAND_F + LAND(s) + lane * 8;
      j.mb = bar + 8 * (B_RS + s);
      j.n = u >= 40 ? 0 : u >= 36 ? 3 : 1;
      asm volatile("" : "+l"(j.gp), "+r"(j.la));
      return j;
    };
    auto rs_sum = [&](RsJob j, int step) {
      if (j.n) {
        auto five = [&](uint32_t la) {
          uint2 p[5];
#pragma unroll
          for (int i = 0; i < 4; i++) p[i] = lds64(la + i * 256);
          asm volatile("{\n.reg .pred q;\nsetp.eq.s32 q, %3, 5;\nmov.u32 %0, 0;\nmov.u32 %1, 0;\n@q ld.shared.v2.b32 {%0,%1}, [%2];\n}"
                       : "=r"(p[4].x), "=r"(p[4].y) : "r"(la + 1024), "r"(nh) : "memory");
          return make_uint2(hadd2bf(hadd2bf(p[0].x, p[1].x), hadd2bf(hadd2bf(p[2].x, p[3].x), p[4].x)),
                            hadd2bf(hadd2bf(p[0].y, p[1].y), hadd2bf(hadd2bf(p[2].y, p[3].y), p[4].y)));
        };
        const uint32_t tag = ((step >> 1) & 1) ^ 1;
        mbar_waitw(j.mb, step & 1);
        uint2 t = five(j.la);
        if (j.n > 1) {
          const uint2 a = five(j.la + (nh == 5 ? 1280 : TILE_GRP - 1280)), b = five(j.la + TILE_GRP);
          t.x = hadd2bf(t.x, hadd2bf(a.x, b.x)); t.y = hadd2bf(t.y, hadd2bf(a.y, b.y));
        }
        const uint32_t t0 = (movm(t.x) & ~1u) | tag, t1 = (movm(t.y) & ~1u) | tag;
        asm volatile("st.relaxed.gpu.global.b32 [%0], %1;" :: "l"(j.gp), "r"(t0) : "memory");
        asm volatile("st.relaxed.gpu.global.b32 [%0], %1;" :: "l"(j.gp + 32), "r"(t1) : "memory");
      }
    };
    if (warp * nA + (int)rank < 40) {
#pragma unroll
      for (int e = LAG; e < LAG + 2; e++)
        if ((e >> 1) & 1) *reinterpret_cast<uint2*>(&g_part[(e & 1) * 2 + 1][cl][warp * nA + rank][lane * 2]) = make_uint2(1u, 1u);
      __threadfence();
    }
    cluster_sync_all();
    if (warp == 2 && ig >= 0) issue_tok(0, B_F2);
#pragma unroll 1
    for (int step = 0; step < NSTEP; step++) {
      const uint32_t par = step & 1;
      asm volatile("" : "+r"(lane));
      const bool dual = is_dual(step), has_next = step + 1 < NSTEP;
      {
        bar_sync(N_PX, dual ? 256 : 192);
        if (dual || warp >= 2) tok_softmax(sb, dual ? warp : warp - 2, lane);
        bar_arrive(N_P, 256);
        asm volatile("" : "+r"(lane));
        if (has_next) {
          if (step + 2 == LAG && lane < 20) asm volatile("prefetch.global.L2 [%0];" :: "l"(mem0 + (warp * 20 + lane) * 64));
          const int nw = ig >= 0 ? 3 : 4, j0 = warp < nw ? warp : 8;
          const int sh = dual ? 1 : 0;
          rs_sum(rs_prep(step, j0 >> sh, j0 & sh), step);
          if (warp == 0) TS(17);
          if (dual) rs_sum(rs_prep(step, (j0 + nw) >> 1, (j0 + nw) & 1), step);
          if (warp == 0) { bar_sync(N_C, 288); }
          mbar_arrive_remote_if(lane < nA, rb0 + (lane << 24) + OFF_BAR + 8 * B_LANDFREE);
          const uint32_t gap = dual ? POLL_GAPD : POLL_GAP;
          if (gap) { const uint32_t t0 = clock32(); while (clock32() - t0 < gap) {} }
#pragma unroll 1
          for (int j = j0; j < (dual ? 8 : 4); j += nw) {
            const int u = (j >> sh) * nA + rank, c = j & sh;
            if (u < UMAX && (c || step + 1 != NSEG)) {
              const uint32_t* gq = &g_part[0][0][0][0] + (uint32_t)((par * 2 + c) * NCL * 2560 + u * 64 + lane * 2);
              uint2 pa[NCL];
              POLL(pa, gq);
              deliver(pa, gq, u, c, step + 1 < NSEG ? c : 0, dual ? DS_DUAL : DS_SINGLE, step, j == 0, lane);
            }
            if (warp == 0 && j == 0) TS(13);
          }
          if (warp >= nw && (is_dual(step + 1) || (ig < 3 && step + 2 < NSTEP))) {
            issue_tok(is_dual(step + 1) ? sched_f(step + 1) : sched_l(step + 2), is_dual(step + 1) ? B_F1 : B_F2, B_R2, par ^ 1);
          }
          if (step + 1 == LAG && UMAX) {
            uint4 v[5];
#pragma unroll
            for (int i = 0; i < 5; i++) { const int t = warp * 160 + i * 32 + lane; v[i] = *reinterpret_cast<const uint4*>(mem0 + (t & 7) * DM + (t >> 3) * 8); }
            mbar_waitu(bar + 8 * B_LANDFREE, par);
#pragma unroll
            for (int i = 0; i < 5; i++)
              st_async_v4(sb + OFF_TILE + LAND_F + warp * TILE_GRP + (i * 32 + lane) * 16, v[i].x, v[i].y, v[i].z, v[i].w, bar + 8 * (B_F1 + warp));
          }
        }
      }
      if (warp == 3) {
        unsigned char* o0 = g_o + uni(step * (96 * 8192) + (head * 3 + t3) * (dual ? 8192 : 4096));
        bar_sync(N_OX, 160);
        fence_async();
        bulk_s2g_es(o0, sb + OFF_PL, 4096);
        if (dual) bulk_s2g_es(o0 + 4096, sb + OFF_PL + PL_SZ, 4096);
        asm volatile("cp.async.bulk.commit_group;" ::: "memory");
        asm volatile("cp.async.bulk.wait_group.read 0;" ::: "memory");
        __syncwarp();
        mbar_arrive_remote_if(lane < 2, (lane ? nxt : prv) + OFF_BAR + 8 * B_PLFREE);
        asm volatile("cp.async.bulk.wait_group 0;" ::: "memory");
        asm volatile("fence.proxy.async.global;" ::: "memory");
        __syncwarp();
        if (lane == 0) red_release(&g_f[F_O + (head * 3 + t3) / 5][step], 1u);
        __syncwarp();
      }
    }
    cluster_sync_all();
  }
}

__device__ __forceinline__ float gelu2(float x) {
  const float u = x * fmaf(x * x, 0.7978845608028654f * 0.044715f, 0.7978845608028654f);
  float t; asm("tanh.approx.f32 %0, %1;" : "=f"(t) : "f"(u));
  return fmaf(x, t, x); }

struct BParams {
  CUtensorMap wmap[5];
  CUtensorMap wo16;
  const __nv_bfloat16* x;
  __nv_bfloat16* out;
};
#define BO_O 0
#define BO_RES (6 * 8192)
#define OP_RES 63488
#define BO_STG (BO_RES + 2 * OP_RES)
#define BO_RING_OP (BO_STG + 16384)
#define OP_SLOT 12288
#define NS_OP 3
#define BO_H 81920
#define BO_W1 (BO_H + 16384)
#define BO_RING_MLP (BO_W1 + 81920)
#define BO_BAR 229376
#define BO_BOX (BO_BAR + 248)
#define BO_CARRY (BO_BAR + 512)
#define BO_STAT (BO_CARRY + 2048)
#define B_SMEM (BO_STAT + 256)
static_assert(B_SMEM <= 232448 && BO_RING_OP + NS_OP * OP_SLOT == BO_BAR && BO_RING_MLP + 3 * 16384 == BO_BAR && 2 * 83968 <= BO_RING_MLP, "smem");
enum { BB_W = 0, BB_FULL = 2, BB_TMP = BB_FULL + 3, BB_OFULL = BB_FULL + 5, BB_SFREE = BB_OFULL,
       BB_STAT = BB_SFREE + 6, BB_ZFREE, BB_DONE = BB_ZFREE + 3,
       BB_EMPTY, BB_START = BB_EMPTY, BB_USED = BB_EMPTY + 2, BB_NUM = BB_USED + 3 };
enum { NB_PP = 1, NB_H = 3, NB_END = 4, NB_END2 = 5, NB_STAGED = 6, NB_FREE = 8, NB_EARLY = 10, NB_LAST = 11 };

#define ACC32(d) ACC16(d), ACC16((d + 16))
#define R32S "{%0,%1,%2,%3,%4,%5,%6,%7,%8,%9,%10,%11,%12,%13,%14,%15,%16,%17,%18,%19,%20,%21,%22,%23,%24,%25,%26,%27,%28,%29,%30,%31}"
template <int N, bool H = false> struct BM;
#define DEF_BM(N, H, T, ACCM, RS_, I0, I1, I2, I3, I4, I5, I6)                                                                          \
  template <> struct BM<N, H> {                                                                                                      \
    template <int BO, int ACC> static __device__ __forceinline__ void rs(float* d, const uint32_t* a, uint32_t blo) {             \
      asm volatile("{\n.reg .b32 m;\n.reg .b64 b;\nadd.u32 m, %" #I4 ", %" #I5 ";\nmov.b64 b, {m, 0x40000040};\n"                 \
                   "wgmma.mma_async.sync.aligned.m64n" #N "k16.f32." T "." T " " RS_ ", {%" #I0 ",%" #I1 ",%" #I2 ",%" #I3 "}, b, %" #I6 ", 1, 1, 0;\n}" \
                   : ACCM(d) : "r"(a[0]), "r"(a[1]), "r"(a[2]), "r"(a[3]), "r"(blo), "n"(BO), "n"(ACC)); }                        \
    template <int AO, int BO, int ACC> static __device__ __forceinline__ void ss(float* d, uint32_t alo, uint32_t blo) {          \
      asm volatile("{\n.reg .b32 l, m;\n.reg .b64 a, b;\nadd.u32 l, %" #I0 ", %" #I1 ";\nadd.u32 m, %" #I2 ", %" #I3 ";\n"        \
                   "mov.b64 a, {l, 0x40000040};\nmov.b64 b, {m, 0x40000040};\n"                                                   \
                   "wgmma.mma_async.sync.aligned.m64n" #N "k16.f32." T "." T " " RS_ ", a, b, %" #I4 ", 1, 1, 1, 0;\n}"             \
                   : ACCM(d) : "r"(alo), "n"(AO), "r"(blo), "n"(BO), "n"(ACC)); }                                                 \
  };
DEF_BM(32, false, "bf16", ACC16, R16S, 16, 17, 18, 19, 20, 21, 22)
DEF_BM(64, false, "bf16", ACC32, R32S, 32, 33, 34, 35, 36, 37, 38)
DEF_BM(32, true, "f16", ACC16, R16S, 16, 17, 18, 19, 20, 21, 22)
DEF_BM(64, true, "f16", ACC32, R32S, 32, 33, 34, 35, 36, 37, 38)
#define DESC_LO(off) (((SMEM0 + (off)) >> 4) | (1u << 16))

__device__ __forceinline__ uint32_t ld_relaxed(const uint32_t* p) { uint32_t v; asm volatile("ld.relaxed.gpu.global.b32 %0, [%1];" : "=r"(v) : "l"(p) : "memory"); return v; }
__device__ __forceinline__ int fmask(int r) { return (r < NSEG) | ((r >= LAG && r < NSTEP) << 1); }
__device__ __forceinline__ int bmask(int r) { return (r <= NSEG) | ((r >= LAG) << 1); }
__device__ __forceinline__ uint32_t rtarget(int mask) { return mask == 3 ? 64 : 32; }
__device__ __forceinline__ void warp_signal(uint32_t* p, int lane) {
  __syncwarp();
  asm volatile("{\n.reg .pred q;\nsetp.eq.u32 q, %1, 0;\n@q red.release.gpu.global.add.u32 [%0], 1;\n}" :: "l"(p), "r"(lane) : "memory");
}
__device__ __forceinline__ uint32_t pack2h(float lo, float hi) { uint32_t r; asm("cvt.rn.f16x2.f32 %0, %1, %2;" : "=r"(r) : "f"(hi), "f"(lo)); return r; }
template <bool H> __device__ __forceinline__ uint32_t pk(float lo, float hi) { return H ? pack2h(lo, hi) : pack2(lo, hi); }
template <int N, bool H> __device__ __forceinline__ void stage_out(const float* d, uint32_t dst, int warp, int lane) {
  const uint32_t sa = dst + ((lane >> 4) * 8 + (lane & 7)) * 128 + (((2 * warp + ((lane >> 3) & 1)) ^ (lane & 7)) << 4);
#pragma unroll
  for (int m = 0; m < N / 16; m++)
    stsm4t(sa + m * 2048, pk<H>(d[8 * m], d[8 * m + 1]), pk<H>(d[8 * m + 2], d[8 * m + 3]), pk<H>(d[8 * m + 4], d[8 * m + 5]), pk<H>(d[8 * m + 6], d[8 * m + 7]));
}
template <int N> __device__ __forceinline__ void acc_live(float* d) {
#pragma unroll
  for (int i = 0; i < N / 2; i++) asm volatile("" : "+f"(d[i]) :: "memory");
}
struct Ring {
  uint32_t sl, ph;
  template <int NS> __device__ __forceinline__ void step() { if (++sl == NS) { sl = 0; ph ^= 1; } }
};

#define LOCKSTEP 0
#define KOFF(x) (((x) >> 2) * (N * 8) + ((x) & 3) * 2)
template <int N, int P>
__device__ __forceinline__ void op_pass(const uint32_t* W, uint32_t bar, uint32_t alo, uint32_t blo, uint32_t xlo, bool x2, Ring& rg, int wg, int warp, int lane, int r) {
  float acc[N / 2];
  const uint32_t tlo = DESC_LO(BO_RING_OP) + uni(rg.sl) * (OP_SLOT / 16);
  if (P == 0) mbar_waitu(bar + 8 * BB_OFULL, r & 1);
  CTS(5 * P);
  if (!LOCKSTEP || P > 1 || P == wg) bar_sync(NB_PP + wg, 256);
  wg_fence();
#define OP_R(x) BM<N>::template rs<KOFF(4 * (x >> 1) + (x & 1)), (x != 0)>(acc, W + 32 * P + 4 * x, blo);
#define OP_S(x) BM<N>::template ss<(6 * P + x) * 128, KOFF(4 * (x >> 1) + 2 + (x & 1)), 1>(acc, alo, blo);
#define OP_T(x) BM<N>::template ss<x * 128, KOFF(14 + x), 1>(acc, tlo, blo);
  OP_R(0) OP_S(0) OP_R(1) OP_S(1) OP_R(2) OP_S(2) OP_R(3) OP_S(3)
  if (P == 0) mbar_waitu(bar + 8 * (BB_OFULL + 1), r & 1);
  if (P == 4) wg_commit();
  OP_R(4) OP_S(4) OP_R(5) OP_S(5)
  if (P == 1 && x2) BM<N>::template ss<30 * 128, KOFF(20), 1>(acc, alo, xlo);
  if (P == 4) { wg_commit(); wg_wait<1>(); bar_arrive(NB_EARLY, 288); CTS(21); wg_fence(); }
  mbar_waitu(bar + 8 * (BB_FULL + rg.sl), rg.ph);
  OP_R(6) OP_T(0) OP_R(7) OP_T(1)
  if (P == 0) mbar_waitu(bar + 8 * (BB_OFULL + 2), r & 1);
  OP_T(2) OP_T(3)
  if (P == 0) BM<N>::template rs<KOFF(20), 1>(acc, W + 160, xlo);
  OP_T(4) OP_T(5)
  wg_commit();
  if (!LOCKSTEP || P) bar_arrive(NB_PP + 1 - wg, 256);
  CTS(5 * P + 2);
  bar_sync(NB_FREE + wg, 160);
  wg_wait<0>();
  acc_live<N>(acc);
  if (P == 4) bar_arrive(NB_LAST, 288);
  mbar_arrive_if(lane == 0, bar + 8 * (BB_USED + rg.sl));
  CTS(5 * P + 3);
  stage_out<N, false>(acc, SMEM0 + BO_STG + wg * 8192, warp, lane);
  bar_arrive(NB_STAGED + wg, 160);
  CTS(5 * P + 4);
  rg.step<NS_OP>(); rg.step<NS_OP>();
}
template <int N>
__device__ __forceinline__ void op_round(const uint32_t* W, uint32_t bar, uint32_t alo, uint32_t blo, uint32_t xlo, bool x2, Ring& rg, int wg, int warp, int lane, int r) {
  op_pass<N, 0>(W, bar, alo, blo, xlo, x2, rg, wg, warp, lane, r);
  op_pass<N, 1>(W, bar, alo, blo, xlo, x2, rg, wg, warp, lane, r);
  op_pass<N, 2>(W, bar, alo, blo, xlo, x2, rg, wg, warp, lane, r);
  op_pass<N, 3>(W, bar, alo, blo, xlo, x2, rg, wg, warp, lane, r);
  op_pass<N, 4>(W, bar, alo, blo, xlo, x2, rg, wg, warp, lane, r);
}
__device__ __forceinline__ void carry_in(uint32_t sb, int wg, int warp, int lane) {
  const int row = (lane >> 1) & 3;
  if (lane < 16) {
    const uint4 v = lds128(sb + BO_CARRY + (wg * 4 + warp) * 256 + lane * 16);
    sts128(sb + BO_H + wg * 8192 + (lane >> 3) * 4096 + row * 128 + (((2 * warp + (lane & 1)) ^ row) << 4), v.x, v.y, v.z, v.w);
  }
  __syncwarp();
}
#define STAGGER 0
template <int N, int Z>
__device__ __forceinline__ void p1_pair(float* acc, const uint32_t* W, uint32_t bar, uint32_t alo, uint32_t blo, int lane, int r) {
  mbar_waitu(bar + 8 * (BB_FULL + Z), r & 1);
  CTS(40 + Z);
  wg_fence();
#define P1_B(k) \
  BM<N, true>::template rs<(2 * Z % 3) * 1024 + k * 512, (2 * Z + k != 0)>(acc, W + 16 * Z + 8 * k, blo); \
  BM<N, true>::template ss<BO_W1 / 16 + (2 * Z + k) * 512, (2 * Z % 3) * 1024 + k * 512 + 4, 1>(acc, alo, blo); \
  BM<N, true>::template rs<(2 * Z % 3) * 1024 + k * 512 + 2, 1>(acc, W + 16 * Z + 8 * k + 4, blo); \
  BM<N, true>::template ss<BO_W1 / 16 + (2 * Z + k) * 512 + 128, (2 * Z % 3) * 1024 + k * 512 + 6, 1>(acc, alo, blo);
  P1_B(0)
  if (Z == 1 || Z == 2) { wg_commit(); wg_wait<1>(); mbar_arrive_if(lane == 0, bar + 8 * (BB_EMPTY + Z - 1)); wg_fence(); }
  P1_B(1)
  wg_commit();
}
template <int N>
__device__ __forceinline__ void phase1(const uint32_t* W, uint32_t sb, uint32_t alo, int half, int wg, int warp, int lane, int off, int r) {
  float acc[N / 2];
  const uint32_t bar = sb + BO_BAR, blo = DESC_LO(BO_RING_MLP) + half * 256;
  CTS(30);
  p1_pair<N, 0>(acc, W, bar, alo, blo, lane, r);
  p1_pair<N, 1>(acc, W, bar, alo, blo, lane, r);
  p1_pair<N, 2>(acc, W, bar, alo, blo, lane, r);
  mbar_waitu(bar + 8 * (BB_SFREE + 4 + wg), (r + 1) & 1);
  carry_in(sb, wg, warp, lane);
  if (STAGGER && wg) bar_sync(NB_PP + 1, 256);
  p1_pair<N, 3>(acc, W, bar, alo, blo, lane, r);
  p1_pair<N, 4>(acc, W, bar, alo, blo, lane, r);
  if (STAGGER && !wg) bar_arrive(NB_PP + 1, 256);
  const int c = (lane >> 3) & 1, i0 = (lane >> 4) * 8 + (lane & 7) + off;
  uint32_t a0 = sb + BO_H + wg * 8192 + half * 4096 + i0 * 128 + (((2 * warp + c) ^ (i0 & 7)) << 4);
  uint32_t a1 = i0 >= 16 ? sb + BO_CARRY + (wg * 4 + warp) * 256 + half * 128 + (i0 - 16) * 32 + c * 16 : a0 + 2048, a3 = a1 + (i0 >= 16 ? 128 : 4096);
  asm volatile("" : "+r"(a0), "+r"(a1), "+r"(a3));
  mbar_waitu(bar + 8 * BB_STAT, r & 1);
  const uint32_t sa = sb + BO_STAT + half * 128 + (lane & 3) * 32;
  uint4 t[2] = {lds128(sa), lds128(sa + 16)};
  wg_wait<0>();
  acc_live<N>(acc);
  CTS(32);
#pragma unroll
  for (int m = 0; m < N / 16; m++) {
    const float s0 = __uint_as_float(t[m & 1].x), s1 = __uint_as_float(t[m & 1].y), s2 = __uint_as_float(t[m & 1].z), s3 = __uint_as_float(t[m & 1].w);
    float* d = acc + 8 * m;
    d[0] *= s0; d[1] *= s1; d[2] *= s0; d[3] *= s1; d[4] *= s2; d[5] *= s3; d[6] *= s2; d[7] *= s3;
    if (m + 2 < N / 16) t[m & 1] = lds128(sa + 128 + m * 16);
#pragma unroll
    for (int j = 0; j < 8; j++) d[j] = gelu2(d[j]);
  }
#pragma unroll
  for (int m = 0; m < N / 16; m++)
    stsm4t(m == 1 ? a1 : m == 3 ? a3 : a0 + m * 2048, pack2(acc[8 * m], acc[8 * m + 1]), pack2(acc[8 * m + 2], acc[8 * m + 3]), pack2(acc[8 * m + 4], acc[8 * m + 5]), pack2(acc[8 * m + 6], acc[8 * m + 7]));
}
template <int N, int P>
__device__ __forceinline__ void p2_pass(const uint32_t* W, uint32_t bar, uint32_t alo, uint32_t blo, int wg, int warp, int lane, int r) {
  float acc[N / 2];
  CTS(5 * P);
  if (P || wg) bar_sync(NB_PP + wg, 256);
  wg_fence();
  BM<N>::template rs<0, 0>(acc, W + 80 + 16 * P, blo);      BM<N>::template ss<P * 1024, 512, 1>(acc, alo, blo);
  BM<N>::template rs<2, 1>(acc, W + 84 + 16 * P, blo);      BM<N>::template ss<P * 1024 + 128, 514, 1>(acc, alo, blo);
  BM<N>::template rs<4, 1>(acc, W + 88 + 16 * P, blo);      BM<N>::template ss<P * 1024 + 512, 516, 1>(acc, alo, blo);
  BM<N>::template rs<6, 1>(acc, W + 92 + 16 * P, blo);      BM<N>::template ss<P * 1024 + 640, 518, 1>(acc, alo, blo);
  wg_commit();
  if (P < 4 || !wg) bar_arrive(NB_PP + 1 - wg, 256);
  CTS(5 * P + 2);
  if (P == 2 || P == 3) mbar_waitu(bar + 8 * (BB_SFREE + 2 * (P - 2) + wg), r & 1);
  wg_wait<0>();
  acc_live<N>(acc);
  if (P == 4) bar_sync(NB_H, 256);
  CTS(5 * P + 3);
  stage_out<N, true>(acc, SMEM0 + (P == 4 ? BO_H : BO_RING_MLP + (2 - (P & 1)) * 16384) + wg * 8192, warp, lane);
  bar_arrive(NB_STAGED + (P == 4 ? 4 : 2 * (P & 1)) + wg, 160);
  CTS(5 * P + 4);
}
template <int N>
__device__ __forceinline__ void phase2(const uint32_t* W, uint32_t bar, uint32_t alo, uint32_t blo, int wg, int warp, int lane, int r) {
  p2_pass<N, 0>(W, bar, alo, blo, wg, warp, lane, r);
  p2_pass<N, 1>(W, bar, alo, blo, wg, warp, lane, r);
  p2_pass<N, 2>(W, bar, alo, blo, wg, warp, lane, r);
  p2_pass<N, 3>(W, bar, alo, blo, wg, warp, lane, r);
  p2_pass<N, 4>(W, bar, alo, blo, wg, warp, lane, r);
}

__device__ __forceinline__ void ldg4(uint32_t* v, const void* p) {
  asm volatile("ld.relaxed.gpu.global.v4.u32 {%0,%1,%2,%3}, [%4];" : "=r"(v[0]), "=r"(v[1]), "=r"(v[2]), "=r"(v[3]) : "l"(p) : "memory"); }
__device__ __forceinline__ void stg4(void* p, const uint32_t* v) {
  asm volatile("st.global.v4.u32 [%0], {%1,%2,%3,%4};" :: "l"(p), "r"(v[0]), "r"(v[1]), "r"(v[2]), "r"(v[3]) : "memory"); }
struct RowPtr {
  unsigned char *p, *q, *t;
  __device__ __forceinline__ void ld(uint32_t* v, int o) const {
    ldg4(v, p + o); ldg4(v + 4, q + o);
    asm volatile("ld.relaxed.gpu.global.v2.u32 {%0,%1}, [%2];" : "=r"(v[8]), "=r"(v[9]) : "l"(t + o) : "memory");
  }
  __device__ __forceinline__ void st(const uint32_t* w, int o) const {
    stg4(p + o, w); stg4(q + o, w + 4);
    asm volatile("st.global.v2.u32 [%0], {%1,%2};" :: "l"(t + o), "r"(w[8]), "r"(w[9]) : "memory");
  }
};
__device__ __forceinline__ RowPtr row_img(int r, int n, int lane) {
  unsigned char* b = &g_acc[0][r % RD][n * 128];
  unsigned char* p = b + (uint32_t)((lane >> 3) * 8192 + (((lane ^ n) & 7) << 4));
  return {p, p + 32768, b + (uint32_t)(65536 + (lane >> 4) * 8192 + ((((lane >> 1) ^ n) & 7) << 4) + (lane & 1) * 8)};
}
__device__ __forceinline__ RowPtr row_ext(const void* lin, bool xn, int layer, int tok, int lane) {
  unsigned char* b = xn ? reinterpret_cast<unsigned char*>(&g_xn[layer][0]) + (uint32_t)((tok >> 5) * 40960 + ((tok >> 3) & 3) * 2560 + (tok & 7) * 16)
                        : (unsigned char*)lin + (uint32_t)(tok * 1280);
  return {b + (uint32_t)(xn ? lane * 128 + (lane >= 20 ? 7680 : 0) : lane * 16),
          b + (uint32_t)(xn ? lane * 128 + 4096 + 7680 + (lane >= 8 ? 7680 : 0) + (lane >= 28 ? 7680 : 0) : lane * 16 + 512),
          b + (uint32_t)(xn ? (lane >> 1) * 128 + (lane & 1) * 8 + 8192 + 3 * 7680 : lane * 8 + 1024)};
}
__device__ __forceinline__ float2 h2f(uint32_t w) {
  float2 f; asm("{\n.reg .f16 l, h;\nmov.b32 {l, h}, %2;\ncvt.f32.f16 %0, l;\ncvt.f32.f16 %1, h;\n}" : "=f"(f.x), "=f"(f.y) : "r"(w)); return f; }
__device__ __forceinline__ float rsq(float x) { float y; asm("rsqrt.approx.ftz.f32 %0, %1;" : "=f"(y) : "f"(x)); return y; }
__device__ __forceinline__ void red_if(uint32_t v, const void* a) {
  asm volatile("{\n.reg .pred q;\nsetp.ne.u32 q, %1, 0;\n@q red.relaxed.gpu.global.add.u32 [%0], %1;\n}" :: "l"(a), "r"(v) : "memory"); }
__device__ __forceinline__ uint32_t dep0(uint32_t w, int lane) { uint32_t z; asm volatile("shr.b32 %0, %1, %2;" : "=r"(z) : "r"(w), "r"(lane + 32)); return z; }
__device__ __forceinline__ int lane_of(uint32_t w) {
  int lane; asm volatile("{\n.reg .u32 t;\nmov.u32 t, %%laneid;\nshr.u32 %0, %1, 20;\nadd.u32 %0, %0, t;\n}" : "=r"(lane) : "r"(w)); return lane; }
#define BUF (RD * TILE_B)
__device__ __forceinline__ int await(uint32_t v, const uint32_t* p, uint32_t target, bool lazy) {
  int n = 0;
  while (!__all_sync(~0u, v >= target)) {
    if (lazy) __nanosleep(200);
    if (++n > SPIN_LIMIT) FAIL();
    v = ld_relaxed(p);
  }
  asm volatile("fence.acquire.gpu;" ::: "memory");
  return lane_of(v);
}
template <int W> __device__ __forceinline__ void sum2(float& s, float& q, int lane) {
  const bool up = lane & (W / 2);
  float e = (up ? q : s) + __shfl_xor_sync(~0u, up ? s : q, W / 2);
#pragma unroll
  for (int o = W / 4; o; o >>= 1) e += __shfl_xor_sync(~0u, e, o);
  const float f = __shfl_xor_sync(~0u, e, W / 2);
  s = up ? f : e; q = up ? e : f;
}
template <int TYPE>
__device__ __forceinline__ void rrow(int r, int row, int tok, int lane, const uint32_t* go, int role, const __nv_bfloat16* x) {
  const int half = TYPE ? 0 : row >> 5;
  float v[20];
  float2 st = make_float2(1.f, 0.f);
  {
    uint32_t a[10], c[10], u[10], sh = 16;
    if (TYPE == 2) row_img(r + RD - ((row & 31) < 2), (row & 32) + ((row - 2) & 31), lane).ld(u, 4 * BUF);
    else row_ext(x, half, 1, tok, lane).ld(u, 0);
    if (TYPE == 2 || (TYPE == 0 && half))
      asm volatile("ld.relaxed.gpu.global.v2.f32 {%0,%1}, [%2];" : "=f"(st.x), "=f"(st.y) : "l"(g_stat + tok) : "memory");
    RowPtr ap = row_img(r, row, lane);
    const uint32_t g0 = TYPE != 3 ? ld_relaxed(go) : 0;
    if (TYPE == 2) {
      ap.ld(c, 2 * BUF);
      uint32_t z = dep0(c[9], lane);
#pragma unroll
      for (int i = 0; i < 10; i++) {
        const float2 g = h2f(u[i] | z), h = h2f(c[i] | z);
        v[2 * i] = fmaf(h.x, 0.5f, g.x * st.x); v[2 * i + 1] = fmaf(h.y, 0.5f, g.y * st.x);
        if (i & 1) z = dep0(__float_as_uint(v[2 * i]) | __float_as_uint(v[2 * i + 1]), lane);
      }
    }
    if (TYPE != 3) {
      asm volatile("" : "+l"(ap.p), "+l"(ap.t));
      ap.q = ap.p + 32768;
      lane = await(g0, go, NOP * NW12 * NW34, false); BTS2(r, 8 + 2 * TYPE); RTS(0);
      ap.ld(a, TYPE ? 3 * BUF : 0);
    }
    if (TYPE == 0) {
      ap.ld(c, BUF);
      const uint32_t one = 0x3f803f80u | dep0(c[9], lane);
#pragma unroll
      for (int i = 0; i < 10; i++) asm volatile("fma.rn.bf16x2 %0, %0, %1, %2;" : "+r"(a[i]) : "r"(one), "r"(c[i]));
      sh |= dep0(a[9], lane);
    }
    const float k = TYPE == 2 ? __uint_as_float(0x3f000000u | dep0(a[9], lane)) : 0.f;
#pragma unroll
    for (int i = 0; i < 10; i++) {
      if (TYPE == 2) { const float2 h = h2f(a[i]); v[2 * i] = fmaf(h.x, k, v[2 * i]); v[2 * i + 1] = fmaf(h.y, k, v[2 * i + 1]); continue; }
      float p = __uint_as_float(u[i] << sh), q = __uint_as_float(u[i] & (0xffffu << sh));
      if (TYPE == 0) { p = fmaf(p, st.x, bf_lo(a[i])); q = fmaf(q, st.x, bf_hi(a[i])); }
      v[2 * i] = p; v[2 * i + 1] = q;
    }
  }
  RTSD(1, v[19]);
  float s = 0.f, q = 0.f;
#pragma unroll
  for (int i = 0; i < 5; i++) {
    s += (v[4 * i] + v[4 * i + 1]) + (v[4 * i + 2] + v[4 * i + 3]);
    q += fmaf(v[4 * i], v[4 * i], v[4 * i + 1] * v[4 * i + 1]) + fmaf(v[4 * i + 2], v[4 * i + 2], v[4 * i + 3] * v[4 * i + 3]);
  }
  sum2<32>(s, q, lane);
  const float mean = s * (1.f / DM), var = fmaxf(q * (1.f / DM) - mean * mean, 0.f), rs = rsq(var + 1e-5f), k = TYPE ? rs : 2.f * rs, mr = -mean * k;
  RTSD(2, rs);
  uint32_t w[10];
#pragma unroll
  for (int i = 0; i < 10; i++) w[i] = pk<TYPE == 0>(fmaf(v[2 * i], k, mr), fmaf(v[2 * i + 1], k, mr));
  if (TYPE) row_ext(nullptr, true, TYPE == 2, tok, lane).st(w, 0);
  else {
    row_img(r, row, lane).st(w, 4 * BUF);
    row_img(r + ((row & 31) >= 30), (row & 32) + ((row + 2) & 31), lane).st(w, 2 * BUF);
    if (lane == 1) g_st2[0][r % RD][row] = (__float_as_uint(0.5f * rsq(fmaf(var * rs, rs, 1e-5f))) & ~127u) | (r + 1);
  }
  if (TYPE != 3 && lane == 0) g_stat[tok] = make_float2((var + 1e-5f) * rs * (TYPE ? 1.f : 0.5f), mean + st.y);
}
__device__ __forceinline__ void r2rows(int r, int row, int lane) {
  const int n = row + (lane >> 4);
  const unsigned char* ap = &g_acc[2][r % RD][0] + (uint32_t)(n * 128 + ((lane >> 3) & 1) * 8192 + (((lane ^ n) & 7) << 4));
  uint32_t a[20];
#pragma unroll
  for (int i = 0; i < 5; i++) ldg4(a + 4 * i, ap + i * 16384);
  const uint32_t z = dep0(a[19], lane);
  float s = 0.f, q = 0.f, q2 = 0.f;
#pragma unroll
  for (int i = 0; i < 20; i++) { const float2 h = h2f(a[i] | z); s += h.x + h.y; q = fmaf(h.x, h.x, q); q2 = fmaf(h.y, h.y, q2); }
  q += q2;
  sum2<16>(s, q, lane);
  const float mean = s * (0.5f / DM), rs = rsq(fmaxf(q * (0.25f / DM) - mean * mean, 0.f) + 1e-5f);
  if ((lane & 15) == 0) asm volatile("st.relaxed.gpu.global.u32 [%0], %1;" :: "l"(&g_st2[1][r % RD][n]), "r"((__float_as_uint(0.5f * rs) & ~127u) | (r + 1)) : "memory");
}
__device__ __forceinline__ void r3rows(int r, int row, int tok, int lane, __nv_bfloat16* out) {
  const int n = row + (lane >> 4), m = 32 + ((n - 2) & 31);
  const unsigned char* ap = &g_acc[0][r % RD][0] + (uint32_t)(n * 128 + ((lane >> 3) & 1) * 8192 + (((lane ^ n) & 7) << 4));
  const unsigned char* zp = &g_acc[4][(r + RD - (row == 32)) % RD][0] + (uint32_t)(m * 128 + ((lane >> 3) & 1) * 8192 + (((lane ^ m) & 7) << 4));
  unsigned char* op = reinterpret_cast<unsigned char*>(out) + (uint32_t)((tok + (lane >> 4)) * 1280 + (lane & 15) * 16);
  float2 st;
  asm volatile("ld.relaxed.gpu.global.v2.f32 {%0,%1}, [%2];" : "=f"(st.x), "=f"(st.y) : "l"(g_stat + tok + (lane >> 4)) : "memory");
#pragma unroll
  for (int i0 = 0; i0 < 5; i0 += 2) {
    uint32_t a[8], c[8], u[8];
#pragma unroll
    for (int i = 0; i < (i0 < 4 ? 2 : 1); i++) { ldg4(a + 4 * i, ap + 3 * BUF + (i0 + i) * 16384); ldg4(c + 4 * i, ap + 2 * BUF + (i0 + i) * 16384); ldg4(u + 4 * i, zp + (i0 + i) * 16384); }
    uint32_t z = dep0(u[i0 < 4 ? 7 : 3], lane);
#pragma unroll
    for (int i = 0; i < (i0 < 4 ? 8 : 4); i++) {
      const float2 h = h2f(a[i] | z), e = h2f(c[i] | z), g = h2f(u[i] | z);
      a[i] = pack2(fmaf(h.x + e.x, 0.5f, fmaf(g.x, st.x, st.y)), fmaf(h.y + e.y, 0.5f, fmaf(g.y, st.x, st.y)));
      if (i & 1) z = dep0(a[i], lane);
    }
#pragma unroll
    for (int i = 0; i < (i0 < 4 ? 2 : 1); i++) stg4(op + (i0 + i) * 256, a + 4 * i);
  }
}
template <int TYPE>
__device__ __forceinline__ void rloop(int row, int cp, int role, const __nv_bfloat16* x, __nv_bfloat16* out) {
  constexpr int ST = TYPE == 4 ? 2 : TYPE;
  const int r0 = row & 32 ? LAG : 0;
  uint32_t v = 0;
#pragma unroll 1
  for (int r = r0; r < r0 + NSEG + (TYPE > 0); r++) {
    const int tok = (r - r0) * 32 + (row & 31) - (TYPE ? 2 : 0);
    const bool valid = TYPE == 0 || (unsigned)tok < S_LEN;
    const uint32_t* go = &g_f[F_R1 + 4 * ST + cp][r];
    const uint32_t* first = TYPE == 2 ? &g_f[F_R2 + cp][r] : TYPE ? go : (const uint32_t*)&g_xready[NSEG + r - r0][0];
    if constexpr (TYPE == 1 || TYPE == 4) {
      const int lane = await(v, go, NOP * NW12 * NW34, false);
      BTS2(r, 8 + 2 * ST); RTS(0);
      if (TYPE == 1) { r2rows(r, row, lane); BTS2(r, 11); continue; }
      if (valid) r3rows(r, row, tok, lane, out);
    } else {
      if (TYPE || row >= 32) await(v, first, TYPE ? NOP * NW12 * NW34 : 32, true);
      if (valid) rrow<TYPE>(r, row, tok, lane_of(r), go, role, x);
    }
    const int lane = lane_of(r);
    const void* f = lane ? (const void*)&g_xready[NSEG + (tok >> 5)][0] : (const void*)&g_f[TYPE ? F_DONE : F_Z][r];
    asm volatile("" : "+l"(f));
    __syncwarp();
    RTS(3);
    v = ld_relaxed(first + (TYPE ? 1 : 8));
    asm volatile("fence.release.gpu;" ::: "memory");
    RTS(4);
    red_if(lane == 0 || (TYPE == 2 && lane == 1 && valid) ? (TYPE & 5 ? 2 : 1) : 0, f);
    RTS(5);
    RTS_OUT();
    BTS2(r, 9 + 2 * ST);
  }
}

#define RSLOW 1
#define RNEAR 20
#define W_DELAY 0
#define BULK_ADD(T, dst, src, len) asm volatile("{\n.reg .pred e;\nelect.sync _|e, 0xffffffff;\n@e cp.reduce.async.bulk.global.shared::cta.bulk_group.add.noftz." T " [%0], [%1], %2;\n}" \
                                               :: "l"(dst), "r"(src), "r"(len) : "memory")
#define COMMIT() asm volatile("cp.async.bulk.commit_group;" ::: "memory")
#define DRAINED(n) do { asm volatile("cp.async.bulk.wait_group.read " #n ";" ::: "memory"); __syncwarp(); } while (0)
#define WRITTEN() do { asm volatile("cp.async.bulk.wait_group 0;\nfence.proxy.async.global;" ::: "memory"); __syncwarp(); } while (0)
__device__ __forceinline__ void wait_flags(const uint32_t* p, uint32_t target) {
  int n = 0;
  while (!__all_sync(~0u, ld_relaxed(p) >= target)) { if (++n > SPIN_LIMIT) FAIL(); }
  asm volatile("fence.acquire.gpu;" ::: "memory");
  asm volatile("fence.proxy.async.global;" ::: "memory");
}
__global__ void __launch_bounds__(512, 1) bworker_kernel(const __grid_constant__ BParams P) {
  extern __shared__ __align__(1024) unsigned char smem_raw[];
  const uint32_t sb = SMEM0, bar = sb + BO_BAR;
  const int wg = __shfl_sync(~0u, threadIdx.x >> 7, 0), warp = __shfl_sync(~0u, (threadIdx.x >> 5) & 3, 0);
  if (threadIdx.x == 0) {
    if (smem_u32(smem_raw) != SMEM0) FAIL();
    uint32_t smid; asm volatile("mov.u32 %0, %%smid;" : "=r"(smid));
#define POLICY 0
    const bool lone = ld_relaxed(&g_tpc[(smid >> 1) & 127]) == 0, far = lone && (smid < 64 || smid >= 124);
    int kind = far ? 0 : 2;
    if (POLICY == 0 && !far) { const uint32_t n = atomicAdd(&g_f[F_MISC][lone ? 35 : 36], 1u); kind = lone ? (n ? 0 : 2) : n < NW12 ? 1 : 2; }
    if (POLICY == 1) kind = far ? (!(smid & 1) && smid <= 124 ? 1 : 0) : (lone || (smid & 1 && atomicAdd(&g_f[F_MISC][35], 1u) < 4)) ? 0 : 2;
    uint32_t i;
    while ((i = atomicAdd(&g_f[F_MISC][32 + kind], 1u)) >= (kind == 0 ? NOP : kind == 1 ? NW12 : NW34)) kind = (kind + 1) % 3;
    const bool op = kind == 0;
    const bool slow = RSLOW ? far : op;
    const uint32_t o = atomicAdd(&g_f[F_MISC][37 + slow], 1u);
    sts64(sb + BO_BOX, i + (kind == 0 ? 0 : kind == 1 ? NOP : NOP + NW12), slow ? NBC - 1 - o : o);
    for (int k = 0; k < BB_NUM; k++) mbar_init(bar + 8 * k, k >= BB_USED ? 4 : k >= BB_EMPTY ? 8 : k >= BB_ZFREE ? 2 : 1);
    asm volatile("fence.mbarrier_init.release.cluster;" ::: "memory");
  }
  if (threadIdx.x < 128) sts128(sb + BO_CARRY + threadIdx.x * 16, 0u, 0u, 0u, 0u);
  fence_async();
  __syncthreads();
  const int role = uni(lds32(sb + BO_BOX));
  const bool op = role < NOP, w12 = role < NOP + NW12;
  const int j = op ? role : w12 ? role - NOP : role - NOP - NW12;
  const int rot = op ? (j ? 2 * ((j + 1) % 5) : 0) : 2 * (j % 5);
  if (wg == 3) {
    asm volatile("setmaxnreg.dec.sync.aligned.u32 24;");
    LANE_INIT();
    if (warp < 2) {
      auto announce = [&](int r) {
        const uint32_t* f = &g_f[(op ? F_R1 : w12 ? F_R2 : F_R3) + (lane & 3)][r];
        asm volatile("" : "+l"(f));
        if (warp == 0) { mbar_arrive_if(lane == 0, bar + 8 * BB_DONE); return; }
        mbar_waitw(bar + 8 * BB_DONE, r & 1);
        PTS(60);
        asm volatile("fence.release.gpu;" ::: "memory");
        red_if(lane >= 4 ? 0 : op ? NW12 * NW34 : w12 ? NOP * NW34 : NOP * NW12, f);
        PTS(61);
        BTS(r, 4);
      };
      if (op) {
        int mt = rot + warp;
        bar_arrive(NB_FREE + warp, 160);
#pragma unroll 1
        for (int r = 0; r < NSTEP; r++) {
          const uint32_t len = fmask(r) == 3 ? 8192 : 4096;
          unsigned char* acc = &g_acc[j & 1][r % RD][fmask(r) == 2 ? 4096 : 0];
#pragma unroll 1
          for (int p = 0; p < 5; p++) {
            bar_sync(NB_STAGED + warp, 160);
            PTS(50 + 2 * p + warp);
            fence_async();
            BULK_ADD("bf16", acc + mt * 8192, sb + BO_STG + warp * 8192, len);
            COMMIT();
            PTS(64 + 50 + 2 * p + warp);
            mt = mt >= 8 ? mt - 8 : mt + 2;
            DRAINED(0);
            bar_arrive(NB_FREE + warp, 160);
          }
          WRITTEN();
          announce(r);
        }
      } else {
#pragma unroll 1
        for (int r = 0; r < NR; r++) {
          const uint32_t len = bmask(r) == 3 ? 8192 : 4096;
          unsigned char* acc = &g_acc[w12 ? 2 : 3][r % RD][bmask(r) == 2 ? 4096 : 0];
          int mt = rot + warp;
#pragma unroll 1
          for (int p = 0; p < 5; p++) {
            bar_sync(NB_STAGED + (p == 4 ? 4 : 2 * (p & 1)) + warp, 160);
            PTS(50 + 2 * p + warp);
            fence_async();
            BULK_ADD("f16", acc + mt * 8192, sb + (p == 4 ? BO_H : BO_RING_MLP + (2 - (p & 1)) * 16384) + warp * 8192, len);
            COMMIT();
            PTS(64 + 50 + 2 * p + warp);
            mt = mt >= 8 ? mt - 8 : mt + 2;
            if (p == 4) break;
            DRAINED(1);
            mbar_arrive_if(lane == 0, bar + 8 * (p == 1 || p == 2 ? BB_SFREE + 2 * (p - 1) + warp : BB_ZFREE + (p >> 1)));
            if (p == 3) { DRAINED(0); mbar_arrive_if(lane == 0, bar + 8 * (BB_ZFREE + 2)); }
          }
          WRITTEN();
          mbar_arrive_if(lane == 0, bar + 8 * (BB_SFREE + 4 + warp));
          announce(r);
        }
      }
    } else {
      auto clear = [&](int r) {
#pragma unroll 1
        for (int c = j; c < (op && r + 1 < NSTEP ? 40 : 80); c += op ? NOP : NW34)
          bulk_s2g_e(&g_acc[op ? 3 : c / 40][(r + (op ? c / 40 : 0)) % RD][c % 40 * 2048], sb + BO_CARRY, 2048);
        COMMIT();
      };
      if (op && warp == 2) {
        unsigned char* wt = g_wt + j * (10 * OP_SLOT);
#pragma unroll 1
        for (int m0 = 0; m0 < 10; m0 += 3) {
          const int nu = m0 < 9 ? 9 : 3;
          mbar_expect_if(lane == 0, bar + 8 * BB_TMP, nu * 4096);
#pragma unroll 1
          for (int k = 0; k < nu; k++) tma2d_e(sb + BO_RING_OP + k * 4096, &P.wmap[0], (m0 + k / 3) * 64, 320 * j + 224 + 32 * (k % 3), bar + 8 * BB_TMP);
          mbar_waitw(bar + 8 * BB_TMP, m0 & 1);
          bulk_s2g_e(wt + m0 * OP_SLOT, sb + BO_RING_OP, nu * 4096);
          COMMIT();
          WRITTEN();
        }
        asm volatile("fence.acq_rel.gpu;" ::: "memory");
        int sl = 0, ph = 1, mt = rot;
#pragma unroll 1
        for (int r = -1; r < NSTEP; r++) {
#pragma unroll 1
          for (int n = r < 0 ? 7 : 0; n < (r + 1 < NSTEP ? 10 : 7); n++) {
            mbar_waitw(bar + 8 * (BB_USED + sl), ph);
            mbar_expect_if(lane == 0, bar + 8 * (BB_FULL + sl), OP_SLOT);
            bulk_g2s_e(sb + BO_RING_OP + sl * OP_SLOT, wt + mt * OP_SLOT, OP_SLOT, bar + 8 * (BB_FULL + sl));
            if (++sl == 3) { sl = 0; ph ^= 1; }
            mt = mt == 9 ? 0 : mt + 1;
            if (n == 1) clear(r);
            if (n == 5) { WRITTEN(); mbar_arrive_if(lane == 0, bar + 8 * BB_DONE); }
          }
        }
      } else if (op) {
        mbar_waitw(bar + 8 * BB_START, 0);
#pragma unroll 1
        for (int r = 0; r < NSTEP; r++) {
          const int rb = r - RD + 1;
          const uint32_t len = fmask(r) == 3 ? 8192 : 4096;
          const unsigned char* src = g_o + (uint32_t)(r * (96 * 8192) + 5 * j * len);
          wait_flags(lane < 2 ? &g_f[F_O + (lane ? NOP : j)][r] : rb >= 0 ? &g_f[F_DONE][rb] : &g_f[F_MISC][0],
                     lane < 2 ? (lane ? 1 : 5) : rb >= 0 ? rtarget(bmask(rb)) : NBC * 8);
          PTS1(35);
          if (r) bar_sync(NB_EARLY, 288);
          if (r == LAG) bar_sync(NB_LAST, 288);
          mbar_expect_if(lane < 3, bar + 8 * (BB_OFULL + lane), 2 * len);
          bulk_g2s_e(sb + BO_O, src, 2 * len, bar + 8 * BB_OFULL);
          PTS(62); PTS1(38);
          if (r && r != LAG) bar_sync(NB_LAST, 288);
          bulk_g2s_e(sb + BO_O + 2 * len, src + 2 * len, 2 * len, bar + 8 * (BB_OFULL + 1));
          bulk_g2s_e(sb + BO_O + 4 * len, src + 4 * len, len, bar + 8 * (BB_OFULL + 2));
          bulk_g2s_e(sb + BO_O + 5 * len, src + (95 - 5 * j) * len, len, bar + 8 * (BB_OFULL + 2));
          PTS1(64 + 35);
          BTS(r, 0);
        }
      } else if (warp == 2) {
#pragma unroll 1
        for (int r = 0; r < NR; r++) {
          const int mk = w12 ? fmask(r) : bmask(r);
          if (mk) {
            const unsigned char* src = &g_acc[w12 ? 4 : 2][r % RD][mk == 2 ? 4096 : 0];
            wait_flags(&g_f[w12 ? F_Z : F_R2 + (j & 3)][r], w12 ? rtarget(mk) : NOP * NW12 * NW34);
#pragma unroll 1
            for (int z = 0; z < 5; z++) {
              const uint32_t fb = bar + 8 * (BB_FULL + z), dst = sb + BO_RING_MLP + 2 * z % 3 * 16384 + (mk == 2 ? 4096 : 0);
              mbar_waitw(bar + 8 * (z < 3 ? BB_ZFREE + z : BB_EMPTY + z - 3), (r + (z < 3)) & 1);
              if (z == 0) PTS(62);
              mbar_expect_if(lane == 0, fb, mk == 3 ? 16384 : 8192);
              bulk_g2s_e(dst, src + z * 16384, mk == 3 ? 16384 : 4096, fb);
              if (mk != 3) bulk_g2s_e(dst + 8192, src + z * 16384 + 8192, 4096, fb);
              if (z == 0) BTS(r, 0);
            }
          }
          if (!w12) { clear(r); WRITTEN(); }
          mbar_waitw(bar + 8 * BB_DONE, (r + 1) & 1);
          mbar_arrive_if(lane == 0, bar + 8 * BB_DONE);
        }
      } else {
#pragma unroll 1
        for (int r = 0; r < (w12 ? NSTEP : NR); r++) {
          const bool idle = !((w12 ? fmask(r) : bmask(r)) >> (lane >> 4) & 1);
          uint32_t t0, t1;
          int n = 0;
          mbar_waitw(bar + 8 * BB_FULL, r & 1);
          do {
            asm volatile("ld.relaxed.gpu.global.v2.u32 {%0,%1}, [%2];" : "=r"(t0), "=r"(t1) : "l"(&g_st2[!w12][r % RD][2 * lane]) : "memory");
            if (++n > SPIN_LIMIT) FAIL();
          } while (!__all_sync(~0u, idle || (((t0 ^ (r + 1)) | (t1 ^ (r + 1))) & 127) == 0));
          sts64(sb + BO_STAT + (lane >> 4) * 128 + (lane & 3) * 32 + ((lane >> 2) & 3) * 8, t0, t1);
          __syncwarp();
          mbar_arrive_if(lane == 0, bar + 8 * BB_STAT);
          PTS(63);
        }
      }
    }
    bar_arrive(NB_END, 512);
  } else if (wg == 2) {
    asm volatile("setmaxnreg.dec.sync.aligned.u32 40;");
    const int ord = uni(lds32(sb + BO_BOX + 4));
    const int gw = ord < RNEAR ? warp * RNEAR + ord : 4 * RNEAR + warp * (NBC - RNEAR) + ord - RNEAR, row = gw < 64 ? gw : gw < 96 ? gw - 64 : gw < 128 ? 2 * gw - 192 : 2 * gw - 224;
#pragma unroll 1
    for (int t = gw; t < S_LEN; t = row < 32 ? S_LEN : t < 4 * NBC ? 4 * NBC + (gw < 64 ? gw - 32 : gw - 80) : t + 64) {
      const int lane = lane_of(t);
      if (lane < 20 && t + 128 < S_LEN) asm volatile("prefetch.global.L2 [%0];" :: "l"(P.x + (t + (t < 4 * NBC ? 4 * NBC : 128)) * DM + (lane >> 1) * 64));
      rrow<3>(0, 0, t, lane, nullptr, role, P.x);
      __syncwarp();
      asm volatile("fence.release.gpu;" ::: "memory");
      red_if(lane == 0, &g_xready[t >> 5][0]);
    }
    if (gw < 64) rloop<0>(row, gw & 3, role, P.x, P.out);
    else if (gw < 96) rloop<2>(row, gw & 3, role, P.x, P.out);
    else if (gw < 128) rloop<1>(row, gw & 3, role, P.x, P.out);
    else rloop<4>(row, gw & 3, role, P.x, P.out);
    asm volatile("griddepcontrol.wait;" ::: "memory");
    const int t = threadIdx.x & 127;
    for (int i = (blockIdx.x * 128 + t) * 4; i < 4 * NCL * 2560; i += NBC * 512)
      *reinterpret_cast<uint4*>(&g_part[0][0][0][0] + i) = make_uint4(0u, 0u, 0u, 0u);
    bar_sync(NB_END, 512);
    if (t == 0) {
      uint32_t n;
      asm volatile("atom.acq_rel.gpu.global.add.u32 %0, [%1], 1;" : "=r"(n) : "l"(&g_f[F_MISC][64]) : "memory");
      sts32(sb + BO_BOX, n);
    }
    bar_sync(NB_END2, 128);
    if (lds32(sb + BO_BOX) == NBC - 1) {
      for (int i = t; i < F_NUM * 24; i += 128) reinterpret_cast<uint4*>(&g_f[0][0])[i] = make_uint4(0u, 0u, 0u, 0u);
      g_xready[t][0] = 0; g_tpc[t] = 0;
    }
  } else {
    asm volatile("setmaxnreg.inc.sync.aligned.u32 224;");
    LANE_INIT();
    for (int i = blockIdx.x * 256 + threadIdx.x; i < 2 * RD * TILE_B / 16; i += NBC * 256) reinterpret_cast<uint4*>(&g_acc[0][0][0])[i] = make_uint4(0u, 0u, 0u, 0u);
    warp_signal(&g_f[F_MISC][0], lane);
    const int mt0 = (rot + wg) % 10;
    auto boxes = [&](int ss) {
      const int nb = op && ss ? 3 : 4;
      const uint32_t base = sb + (ss ? BO_RES + wg * OP_RES : wg * 83968);
      mbar_expect_if(warp == 0 && lane == 0, bar + 8 * (BB_W + wg), nb * 20480 + (op ? 2048 : 0));
      bar_sync(NB_H, 256);
      if (warp < nb) {
#pragma unroll 1
        for (int i = warp; i < 5 * nb; i += nb) {
          const int p = op ? i / nb : (i - 10) >> 1, mt = (mt0 + 2 * p) % 10;
          const bool first = !op && i < 10;
          tma2d_e(op || !ss ? base + i * 4096 : sb + (first ? BO_W1 : -81920) + (2 * i + wg) * 4096, &P.wmap[op ? 0 : (w12 ? 1 : 3) + !first], first ? 128 * j + 64 * wg : mt * 64,
                  op ? 320 * j + 64 * warp + 32 * ss : first ? 64 * i + 32 * ss : 128 * j + 32 * (i & 1) + 64 * ss, bar + 8 * (BB_W + wg));
        }
      }
      if (op && warp == 3) tma2d_e(base + nb * 20480, &P.wo16, (mt0 + 2 * ss) % 10 * 64, 95 * 64 + (j + 1) / 5 * 16, bar + 8 * (BB_W + wg));
      mbar_waitw(bar + 8 * (BB_W + wg), ss);
    };
    if (W_DELAY) __nanosleep(W_DELAY);
    uint32_t W[164];
    boxes(0);
    load_w<41>(W, sb + wg * 83968, warp, lane);
    fence_async();
    boxes(1);
    if (!op) {
      float cs[2] = {0.f, 0.f};
      const uint32_t a0 = sb + BO_W1 + wg * 4096 + ((lane >> 4) * 8 + (lane & 7)) * 128 + (((warp * 2 + ((lane >> 3) & 1)) ^ (lane & 7)) << 4);
#pragma unroll
      for (int i = 0; i < 80; i++) cs[i & 1] += bf_lo(W[i]) + bf_hi(W[i]);
#pragma unroll 1
      for (int i = 0; i < 40; i++) {
        uint32_t t[4];
        const uint32_t ad = a0 + (i % 20 >> 1) * 8192 + (i & 1) * 2048;
        ldsm4t(t[0], t[1], t[2], t[3], ad);
#pragma unroll
        for (int k = 0; k < 4; k++) {
          if (i < 20) cs[k & 1] += bf_lo(t[k]) + bf_hi(t[k]);
          t[k] = pack2h(bf_lo(t[k]) - cs[k & 1], bf_hi(t[k]) - cs[k & 1]);
        }
        if (i >= 20) stsm4t(ad, t[0], t[1], t[2], t[3]);
        if (i == 19) {
#pragma unroll
          for (int k = 0; k < 2; k++) { cs[k] += __shfl_xor_sync(~0u, cs[k], 1); cs[k] += __shfl_xor_sync(~0u, cs[k], 2); cs[k] *= 1.f / DM; }
        }
      }
      const uint32_t z = dep0(__float_as_uint(cs[0]), lane);
#pragma unroll
      for (int i = 0; i < 80; i++) W[i] = pack2h(bf_lo(W[i] | z) - cs[i & 1], bf_hi(W[i] | z) - cs[i & 1]);
      fence_async();
      bar_sync(NB_H, 256);
    }
    const uint32_t alo = uni((SMEM0 + (op ? BO_RES + wg * OP_RES : wg * 4096)) >> 4);
    if (op) {
      Ring rg = {(uint32_t)wg, 0};
      mbar_arrive_if(lane == 0, bar + 8 * BB_START);
      if (wg) bar_arrive(NB_PP, 256);
      const uint32_t blo = DESC_LO(BO_O), xlo = blo + (j + 1) / 5 * 2;
#pragma unroll 1
      for (int r = 0; r < NSTEP; r++) {
        asm volatile("" : "+r"(lane));
        if (fmask(r) == 3) op_round<64>(W, bar, alo, blo, xlo, j == 0, rg, wg, warp, lane, r);
        else op_round<32>(W, bar, alo, blo, xlo, j == 0, rg, wg, warp, lane, r);
        if (warp == 0) BTS(r, 2 + wg);
      }
    } else {
      const int q4 = (128 * j + 64 * wg + 16 * warp) / 160, off = w12 ? (0x0413 >> (4 * q4)) & 7 : 0;
#pragma unroll 1
      for (int r = 0; r < NR; r++) {
        asm volatile("" : "+r"(lane));
        const int bm = bmask(r), fm = w12 ? fmask(r) : bm;
        if (fm == 3) phase1<64>(W, sb, alo, 0, wg, warp, lane, off, r);
        else if (fm) phase1<32>(W, sb, alo, fm >> 1, wg, warp, lane, off, r);
        else { mbar_waitu(bar + 8 * (BB_SFREE + 4 + wg), (r + 1) & 1); carry_in(sb, wg, warp, lane); }
        CTS(33);
        fence_async();
        bar_sync(NB_H, 256);
        if (wg + warp == 0) BTS(r, 1);
        if (bm == 3) phase2<64>(W, bar, alo, DESC_LO(BO_H), wg, warp, lane, r);
        else phase2<32>(W, bar, alo, uni(DESC_LO(BO_H) + (bm >> 1) * 256), wg, warp, lane, r);
        if (warp == 0) BTS(r, 2 + wg);
      }
    }
    CTS_OUT();
    bar_arrive(NB_END, 512);
  }
}

typedef CUresult (*EncodeFn)(CUtensorMap*, CUtensorMapDataType, cuuint32_t, void*, const cuuint64_t*, const cuuint64_t*, const cuuint32_t*,
                             const cuuint32_t*, CUtensorMapInterleave, CUtensorMapSwizzle, CUtensorMapL2promotion, CUtensorMapFloatOOBfill);
static void make_map(EncodeFn fn, CUtensorMap* tm, const void* ptr, uint64_t cols, uint64_t rows, uint32_t bc, uint32_t br) {
  cuuint64_t dims[2] = {cols, rows}; cuuint64_t strides[1] = {cols * 2}; cuuint32_t box[2] = {bc, br}; cuuint32_t es[2] = {1, 1};
  fn(tm, CU_TENSOR_MAP_DATA_TYPE_BFLOAT16, 2, const_cast<void*>(ptr), dims, strides, box, es, CU_TENSOR_MAP_INTERLEAVE_NONE,
     CU_TENSOR_MAP_SWIZZLE_128B, CU_TENSOR_MAP_L2_PROMOTION_L2_256B, CU_TENSOR_MAP_FLOAT_OOB_FILL_NONE);
}
#define dbg_a_only 0
extern "C" void kernel_launch(void* const* d_in, const int* in_sizes, int n_in, void* d_out, int out_size) {
  void* fnp = nullptr; cudaDriverEntryPointQueryResult qr;
  cudaGetDriverEntryPoint("cuTensorMapEncodeTiled", &fnp, cudaEnableDefault, &qr);
  EncodeFn fn = (EncodeFn)fnp;
  cudaStream_t st = cudaStreamPerThread;
  cudaFuncSetAttribute(bworker_kernel, cudaFuncAttributeMaxDynamicSharedMemorySize, B_SMEM);
  {
    AMaps M;
    for (int i = 0; i < 3; i++) make_map(fn, &M.w16[i], d_in[2 + i], HD, DM, 64, 16);
    make_map(fn, &M.wo32, d_in[5], DM, HD, 64, 32);
    cudaFuncSetAttribute(acore_kernel, cudaFuncAttributeMaxDynamicSharedMemorySize, A_SMEM);
    cudaFuncSetAttribute(acore_kernel, cudaFuncAttributeNonPortableClusterSizeAllowed, 1);
    cudaLaunchConfig_t cfg = {};
    cfg.gridDim = dim3(CL_SIZE * NCL); cfg.blockDim = dim3(512); cfg.dynamicSmemBytes = A_SMEM; cfg.stream = st;
    cudaLaunchAttribute at[1]; at[0].id = cudaLaunchAttributeClusterDimension;
    at[0].val.clusterDim.x = CL_SIZE; at[0].val.clusterDim.y = 1; at[0].val.clusterDim.z = 1;
    cfg.attrs = at; cfg.numAttrs = 1;
    cudaLaunchKernelEx(&cfg, acore_kernel, M, (const __nv_bfloat16*)d_in[1], dbg_a_only ? 0 : 1);
  }
  if (!dbg_a_only) {
    BParams P;
    make_map(fn, &P.wmap[0], d_in[5], DM, HD, 64, 32);
    make_map(fn, &P.wo16, d_in[5], DM, HD, 64, 16);
    make_map(fn, &P.wmap[1], d_in[8], DM, DM, 64, 32);
    make_map(fn, &P.wmap[2], d_in[9], DM, DM, 64, 32);
    make_map(fn, &P.wmap[3], d_in[10], FF, DM, 64, 32);
    make_map(fn, &P.wmap[4], d_in[11], DM, FF, 64, 32);
    P.x = (const __nv_bfloat16*)d_in[0];
    P.out = (__nv_bfloat16*)d_out;
    cudaLaunchConfig_t cfg = {};
    cfg.gridDim = dim3(NBC); cfg.blockDim = dim3(512); cfg.dynamicSmemBytes = B_SMEM; cfg.stream = st;
    cudaLaunchAttribute at[1]; at[0].id = cudaLaunchAttributeProgrammaticStreamSerialization; at[0].val.programmaticStreamSerializationAllowed = 1;
    cfg.attrs = at; cfg.numAttrs = 1;
    cudaLaunchKernelEx(&cfg, bworker_kernel, P);
  }
}
```

```cpp
#include <cuda_runtime.h>
#include <cuda_bf16.h>
#include <cuda.h>
#include <stdint.h>

#define S_LEN 2048
#define DM 640
#define NH 32
#define DH 192
#define HD 6144
#define NSEG 64
#define FF 1536

__device__ __forceinline__ uint32_t smem_u32(const void* p) { return (uint32_t)__cvta_generic_to_shared(p); }
__device__ __forceinline__ uint32_t mapa(uint32_t a, uint32_t r) {
  uint32_t o; asm volatile("mapa.shared::cluster.u32 %0, %1, %2;" : "=r"(o) : "r"(a), "r"(r)); return o; }
__device__ __forceinline__ void mbar_init(uint32_t b, uint32_t c) {
  asm volatile("mbarrier.init.shared::cta.b64 [%0], %1;" :: "r"(b), "r"(c) : "memory"); }
__device__ __forceinline__ void mbar_expect(uint32_t b, uint32_t tx) {
  asm volatile("mbarrier.arrive.expect_tx.shared::cta.b64 _, [%0], %1;" :: "r"(b), "r"(tx) : "memory"); }
__device__ __forceinline__ void mbar_arrive(uint32_t b) {
  asm volatile("mbarrier.arrive.shared::cta.b64 _, [%0];" :: "r"(b) : "memory"); }
__device__ __forceinline__ void mbar_arrive_remote(uint32_t rb) {
  asm volatile("mbarrier.arrive.relaxed.cluster.shared::cluster.b64 _, [%0];" :: "r"(rb) : "memory"); }
__device__ __forceinline__ void mbar_expect_if(bool p, uint32_t b, uint32_t tx) {
  asm volatile("{\n.reg .pred q;\nsetp.ne.u32 q, %2, 0;\n@q mbarrier.arrive.expect_tx.shared::cta.b64 _, [%0], %1;\n}" :: "r"(b), "r"(tx), "r"((uint32_t)p) : "memory"); }
__device__ __forceinline__ void mbar_arrive_if(bool p, uint32_t b) {
  asm volatile("{\n.reg .pred q;\nsetp.ne.u32 q, %1, 0;\n@q mbarrier.arrive.shared::cta.b64 _, [%0];\n}" :: "r"(b), "r"((uint32_t)p) : "memory"); }
__device__ __forceinline__ void mbar_arrive_remote_if(bool p, uint32_t rb) {
  asm volatile("{\n.reg .pred q;\nsetp.ne.u32 q, %1, 0;\n@q mbarrier.arrive.relaxed.cluster.shared::cluster.b64 _, [%0];\n}" :: "r"(rb), "r"((uint32_t)p) : "memory"); }
__device__ __forceinline__ void sts32_if(bool p, uint32_t a, uint32_t v) {
  asm volatile("{\n.reg .pred q;\nsetp.ne.u32 q, %2, 0;\n@q st.shared.b32 [%0], %1;\n}" :: "r"(a), "r"(v), "r"((uint32_t)p) : "memory"); }
__device__ __forceinline__ void sts128z_if(bool p, uint32_t a) {
  asm volatile("{\n.reg .pred q;\nsetp.ne.u32 q, %1, 0;\n@q st.shared.v4.b32 [%0], {0,0,0,0};\n}" :: "r"(a), "r"((uint32_t)p) : "memory"); }
__device__ __forceinline__ bool mbar_try(uint32_t b, uint32_t ph) {
  uint32_t ok;
  asm volatile("{\n.reg .pred p;\nmbarrier.try_wait.parity.shared::cta.b64 p, [%1], %2;\nselp.u32 %0, 1, 0, p;\n}"
               : "=r"(ok) : "r"(b), "r"(ph) : "memory");
  return ok; }
__device__ __forceinline__ bool mbar_test(uint32_t b, uint32_t ph) {
  uint32_t ok;
  asm volatile("{\n.reg .pred p;\nmbarrier.test_wait.parity.shared::cta.b64 p, [%1], %2;\nselp.u32 %0, 1, 0, p;\n}"
               : "=r"(ok) : "r"(b), "r"(ph) : "memory");
  return ok; }
#define SPIN_LIMIT 4000000
#define FAIL() asm volatile("st.global.u32 [%0], 0;" :: "l"(8ull) : "memory")
#define CFENCE() asm volatile("fence.proxy.async::generic.acquire.sync_restrict::shared::cluster.cluster;" ::: "memory")
__device__ __forceinline__ void mbar_wait(uint32_t b, uint32_t ph) {
  int n = 0;
  while (!mbar_try(b, ph)) { if (++n > SPIN_LIMIT) FAIL(); } }
#define TIMEOUT_ACT "@!p st.shared.u32 [%0+1], 0;"
#define WAIT_HINT ", 20000"
#define WAIT_LIM "200000"
__device__ __forceinline__ void mbar_slow(uint32_t b, uint32_t ph) {
  asm volatile("{\n.reg .pred p, q;\n.reg .u32 n;\nmov.u32 n, 0;\n"
               "WL:\nmbarrier.try_wait.parity.shared::cta.b64 p, [%0], %1" WAIT_HINT ";\nadd.u32 n, n, 1;\nsetp.lt.and.u32 q, n, " WAIT_LIM ", !p;\n@q bra.uni WL;\n"
               TIMEOUT_ACT "\n}" :: "r"(b), "r"(ph) : "memory"); }
__device__ __forceinline__ void mbar_waitw(uint32_t b, uint32_t ph) {
  asm volatile("{\n.reg .pred p, q;\n.reg .u32 n;\nmbarrier.try_wait.parity.shared::cta.b64 p, [%0], %1;\n@p bra.uni WD;\nmov.u32 n, 0;\n"
               "WL:\nmbarrier.try_wait.parity.shared::cta.b64 p, [%0], %1" WAIT_HINT ";\nadd.u32 n, n, 1;\nsetp.lt.and.u32 q, n, " WAIT_LIM ", !p;\n@q bra.uni WL;\n"
               TIMEOUT_ACT "\nWD:\n}" :: "r"(b), "r"(ph) : "memory"); }
__device__ __forceinline__ void mbar_waitw2(uint32_t b0, uint32_t b1, uint32_t ph) {
  uint32_t ok;
  asm volatile("{\n.reg .pred p, r;\nmbarrier.try_wait.parity.shared::cta.b64 p, [%1], %3;\nmbarrier.try_wait.parity.shared::cta.b64 r, [%2], %3;\n"
               "and.pred p, p, r;\nselp.u32 %0, 1, 0, p;\n}" : "=r"(ok) : "r"(b0), "r"(b1), "r"(ph) : "memory");
  if (__builtin_expect(!__all_sync(~0u, ok), 0)) { mbar_slow(b0, ph); mbar_slow(b1, ph); }
}
__device__ __forceinline__ void mbar_waitu(uint32_t b, uint32_t ph) {
  asm volatile("{\n.reg .pred p;\nmbarrier.try_wait.parity.shared::cta.b64 p, [%0], %1;\n@p bra.uni WD;\n"
               "WL:\nmbarrier.try_wait.parity.shared::cta.b64 p, [%0], %1" WAIT_HINT ";\n@!p bra.uni WL;\nWD:\n}" :: "r"(b), "r"(ph) : "memory"); }
__device__ __forceinline__ void mbar_waitu2(uint32_t b0, uint32_t b1, uint32_t ph) {
  asm volatile("{\n.reg .pred p, r;\nWL:\nmbarrier.try_wait.parity.shared::cta.b64 p, [%0], %2;\nmbarrier.try_wait.parity.shared::cta.b64 r, [%1], %2;\n"
               "and.pred p, p, r;\n@!p bra.uni WL;\n}" :: "r"(b0), "r"(b1), "r"(ph) : "memory"); }
__device__ __forceinline__ void mbar_waitw4(uint32_t b, uint32_t ph) { mbar_waitw2(b, b + 8, ph); mbar_waitw2(b + 16, b + 24, ph); }
__device__ __forceinline__ uint32_t clock32() { uint32_t t; asm volatile("mov.u32 %0, %%clock;" : "=r"(t) :: "memory"); return t; }
template <int L> __device__ __forceinline__ uint32_t lop3(uint32_t a, uint32_t b, uint32_t c) {
  uint32_t r; asm("lop3.b32 %0, %1, %2, %3, %4;" : "=r"(r) : "r"(a), "r"(b), "r"(c), "n"(L)); return r; }
__device__ __forceinline__ void st_async_v2_if(bool p, uint32_t a, uint32_t v0, uint32_t v1, uint32_t mb) {
  asm volatile("{\n.reg .pred q;\nsetp.ne.u32 q, %4, 0;\n@q st.async.weak.shared::cluster.mbarrier::complete_tx::bytes.v2.b32 [%0], {%1,%2}, [%3];\n}"
               :: "r"(a), "r"(v0), "r"(v1), "r"(mb), "r"((uint32_t)p) : "memory"); }
__device__ __forceinline__ void keep4(const uint32_t* r, int lane) {
  asm volatile("{\n.reg .pred q;\nsetp.lt.s32 q, %4, 0;\n@q st.shared.v4.b32 [%4], {%0,%1,%2,%3};\n}" :: "r"(r[0]), "r"(r[1]), "r"(r[2]), "r"(r[3]), "r"(lane) : "memory"); }
__device__ __forceinline__ uint32_t uni(uint32_t x) { return __shfl_sync(~0u, x, 0); }
__device__ __forceinline__ void bulk_g2s_mc_e(uint32_t dst, const void* src, uint32_t bytes, uint32_t mb, uint16_t mask) {
  asm volatile("{\n.reg .pred e;\nelect.sync _|e, 0xffffffff;\n"
               "@e cp.async.bulk.shared::cluster.global.mbarrier::complete_tx::bytes.multicast::cluster [%0], [%1], %2, [%3], %4;\n}"
               :: "r"(dst), "l"(src), "r"(bytes), "r"(mb), "h"(mask) : "memory"); }
__device__ __forceinline__ void bulk_s2g_e(void* dst, uint32_t src, uint32_t bytes) {
  asm volatile("{\n.reg .pred e;\nelect.sync _|e, 0xffffffff;\n@e cp.async.bulk.global.shared::cta.bulk_group [%0], [%1], %2;\n}"
               :: "l"(dst), "r"(src), "r"(bytes) : "memory"); }
__device__ __forceinline__ void bulk_g2s_e(uint32_t dst, const void* src, uint32_t bytes, uint32_t mb) {
  asm volatile("{\n.reg .pred e;\nelect.sync _|e, 0xffffffff;\n@e cp.async.bulk.shared::cluster.global.mbarrier::complete_tx::bytes [%0], [%1], %2, [%3];\n}"
               :: "r"(dst), "l"(src), "r"(bytes), "r"(mb) : "memory"); }
#define STREAM_HINT 1
__device__ __forceinline__ void bulk_s2g_es(void* dst, uint32_t src, uint32_t bytes) {
  asm volatile("{\n.reg .pred e;\n.reg .b64 pol;\ncreatepolicy.fractional.L2::evict_first.b64 pol;\nelect.sync _|e, 0xffffffff;\n"
               "@e cp.async.bulk.global.shared::cta.bulk_group.L2::cache_hint [%0], [%1], %2, pol;\n}" :: "l"(dst), "r"(src), "r"(bytes) : "memory");
}
__device__ __forceinline__ void bulk_g2s_es(uint32_t dst, const void* src, uint32_t bytes, uint32_t mb) {
  asm volatile("{\n.reg .pred e;\n.reg .b64 pol;\ncreatepolicy.fractional.L2::evict_first.b64 pol;\nelect.sync _|e, 0xffffffff;\n"
               "@e cp.async.bulk.shared::cluster.global.mbarrier::complete_tx::bytes.L2::cache_hint [%0], [%1], %2, [%3], pol;\n}"
               :: "r"(dst), "l"(src), "r"(bytes), "r"(mb) : "memory"); }
__device__ __forceinline__ void tma2d_e(uint32_t dst, const CUtensorMap* tm, int c0, int c1, uint32_t mb) {
  asm volatile("{\n.reg .pred e;\nelect.sync _|e, 0xffffffff;\n"
               "@e cp.async.bulk.tensor.2d.shared::cluster.global.mbarrier::complete_tx::bytes [%0], [%1, {%3, %4}], [%2];\n}"
               :: "r"(dst), "l"((uint64_t)tm), "r"(mb), "r"(c0), "r"(c1) : "memory"); }
__device__ __forceinline__ uint32_t hadd2bf(uint32_t a, uint32_t b) {
  uint32_t r; asm("add.rn.bf16x2 %0, %1, %2;" : "=r"(r) : "r"(a), "r"(b)); return r; }
__device__ __forceinline__ void cluster_sync_all() {
  asm volatile("barrier.cluster.arrive.release.aligned;\nbarrier.cluster.wait.acquire.aligned;" ::: "memory"); }
__device__ __forceinline__ void bar_arrive(int id, int n) { asm volatile("bar.arrive %0, %1;" :: "r"(id), "r"(n) : "memory"); }
__device__ __forceinline__ void bar_arrive_dep(int id, int n, uint32_t dep) {
  asm volatile("{\n.reg .u32 t;\nand.b32 t, %2, 0;\nadd.u32 t, t, %0;\nbar.sync t, %1;\n}" :: "r"(id), "r"(n), "r"(dep) : "memory"); }
__device__ __forceinline__ void bar_sync(int id, int n) { asm volatile("bar.sync %0, %1;" :: "r"(id), "r"(n) : "memory"); }
__device__ __forceinline__ void fence_async() { asm volatile("fence.proxy.async.shared::cta;" ::: "memory"); }
__device__ __forceinline__ void st_async_b32(uint32_t a, uint32_t v, uint32_t mb) {
  asm volatile("st.async.weak.shared::cluster.mbarrier::complete_tx::bytes.b32 [%0], %1, [%2];" :: "r"(a), "r"(v), "r"(mb) : "memory"); }
__device__ __forceinline__ void st_async_v2(uint32_t a, uint32_t v0, uint32_t v1, uint32_t mb) {
  asm volatile("st.async.weak.shared::cluster.mbarrier::complete_tx::bytes.v2.b32 [%0], {%1,%2}, [%3];" :: "r"(a), "r"(v0), "r"(v1), "r"(mb) : "memory"); }
__device__ __forceinline__ void st_async_v4(uint32_t a, uint32_t v0, uint32_t v1, uint32_t v2, uint32_t v3, uint32_t mb) {
  asm volatile("st.async.weak.shared::cluster.mbarrier::complete_tx::bytes.v4.b32 [%0], {%1,%2,%3,%4}, [%5];" :: "r"(a), "r"(v0), "r"(v1), "r"(v2), "r"(v3), "r"(mb) : "memory"); }
__device__ __forceinline__ void ldsm4(uint32_t& r0, uint32_t& r1, uint32_t& r2, uint32_t& r3, uint32_t a) {
  asm volatile("ldmatrix.sync.aligned.m8n8.x4.shared.b16 {%0,%1,%2,%3}, [%4];" : "=r"(r0), "=r"(r1), "=r"(r2), "=r"(r3) : "r"(a) : "memory"); }
__device__ __forceinline__ void ldsm4t(uint32_t& r0, uint32_t& r1, uint32_t& r2, uint32_t& r3, uint32_t a) {
  asm volatile("ldmatrix.sync.aligned.m8n8.x4.trans.shared.b16 {%0,%1,%2,%3}, [%4];" : "=r"(r0), "=r"(r1), "=r"(r2), "=r"(r3) : "r"(a) : "memory"); }
__device__ __forceinline__ void stsm2t(uint32_t a, uint32_t r0, uint32_t r1) {
  asm volatile("stmatrix.sync.aligned.m8n8.x2.trans.shared.b16 [%0], {%1,%2};" :: "r"(a), "r"(r0), "r"(r1) : "memory"); }
__device__ __forceinline__ void stsm4t(uint32_t a, uint32_t r0, uint32_t r1, uint32_t r2, uint32_t r3) {
  asm volatile("stmatrix.sync.aligned.m8n8.x4.trans.shared.b16 [%0], {%1,%2,%3,%4};" :: "r"(a), "r"(r0), "r"(r1), "r"(r2), "r"(r3) : "memory"); }
__device__ __forceinline__ uint32_t movm(uint32_t a) {
  uint32_t d; asm volatile("movmatrix.sync.aligned.m8n8.trans.b16 %0, %1;" : "=r"(d) : "r"(a)); return d; }
__device__ __forceinline__ void mma16816(float* d, uint32_t a0, uint32_t a1, uint32_t a2, uint32_t a3, uint32_t b0, uint32_t b1) {
  asm("mma.sync.aligned.m16n8k16.row.col.f32.bf16.bf16.f32 {%0,%1,%2,%3}, {%4,%5,%6,%7}, {%8,%9}, {%0,%1,%2,%3};"
               : "+f"(d[0]), "+f"(d[1]), "+f"(d[2]), "+f"(d[3]) : "r"(a0), "r"(a1), "r"(a2), "r"(a3), "r"(b0), "r"(b1)); }
__device__ __forceinline__ void mma16816v(float* d, uint32_t a0, uint32_t a1, uint32_t a2, uint32_t a3, uint32_t b0, uint32_t b1) {
  asm volatile("mma.sync.aligned.m16n8k16.row.col.f32.bf16.bf16.f32 {%0,%1,%2,%3}, {%4,%5,%6,%7}, {%8,%9}, {%0,%1,%2,%3};"
               : "+f"(d[0]), "+f"(d[1]), "+f"(d[2]), "+f"(d[3]) : "r"(a0), "r"(a1), "r"(a2), "r"(a3), "r"(b0), "r"(b1)); }
__device__ __forceinline__ uint32_t pack2(float lo, float hi) {
  uint32_t r; asm("cvt.rn.bf16x2.f32 %0, %1, %2;" : "=r"(r) : "f"(hi), "f"(lo)); return r; }
__device__ __forceinline__ uint32_t pack2v(float lo, float hi) {
  uint32_t r; asm volatile("cvt.rn.bf16x2.f32 %0, %1, %2;" : "=r"(r) : "f"(hi), "f"(lo)); return r; }
__device__ __forceinline__ float bf_lo(uint32_t w) { return __uint_as_float(w << 16); }
__device__ __forceinline__ float bf_hi(uint32_t w) { return __uint_as_float(w & 0xffff0000u); }
__device__ __forceinline__ uint4 lds128(uint32_t a) {
  uint4 v; asm volatile("ld.shared.v4.b32 {%0,%1,%2,%3}, [%4];" : "=r"(v.x), "=r"(v.y), "=r"(v.z), "=r"(v.w) : "r"(a) : "memory"); return v; }
__device__ __forceinline__ uint4 lds128_nv(uint32_t a) {
  uint4 v; asm volatile("ld.shared.v4.b32 {%0,%1,%2,%3}, [%4];" : "=r"(v.x), "=r"(v.y), "=r"(v.z), "=r"(v.w) : "r"(a)); return v; }
__device__ __forceinline__ void st_async_v2_nm(uint32_t a, uint32_t v0, uint32_t v1, uint32_t mb) {
  asm volatile("st.async.weak.shared::cluster.mbarrier::complete_tx::bytes.v2.b32 [%0], {%1,%2}, [%3];" :: "r"(a), "r"(v0), "r"(v1), "r"(mb)); }
__device__ __forceinline__ float rcpf(float x) { float y; asm("rcp.approx.ftz.f32 %0, %1;" : "=f"(y) : "f"(x)); return y; }
__device__ __forceinline__ void sts64(uint32_t a, uint32_t x, uint32_t y) { asm volatile("st.shared.v2.b32 [%0], {%1,%2};" :: "r"(a), "r"(x), "r"(y) : "memory"); }
__device__ __forceinline__ float ex2(float x) { float y; asm("ex2.approx.ftz.f32 %0, %1;" : "=f"(y) : "f"(x)); return y; }
__device__ __forceinline__ uint32_t lds32(uint32_t a) {
  uint32_t v; asm volatile("ld.shared.b32 %0, [%1];" : "=r"(v) : "r"(a) : "memory"); return v; }
__device__ __forceinline__ uint2 lds64(uint32_t a) {
  uint2 v; asm volatile("ld.shared.v2.b32 {%0,%1}, [%2];" : "=r"(v.x), "=r"(v.y) : "r"(a) : "memory"); return v; }
__device__ __forceinline__ void sts128(uint32_t a, uint32_t x, uint32_t y, uint32_t z, uint32_t w) {
  asm volatile("st.shared.v4.b32 [%0], {%1,%2,%3,%4};" :: "r"(a), "r"(x), "r"(y), "r"(z), "r"(w) : "memory"); }
__device__ __forceinline__ void sts32(uint32_t a, uint32_t x) { asm volatile("st.shared.b32 [%0], %1;" :: "r"(a), "r"(x) : "memory"); }
__device__ __forceinline__ void tma2d(uint32_t dst, const CUtensorMap* tm, int c0, int c1, uint32_t mb) {
  asm volatile("cp.async.bulk.tensor.2d.shared::cluster.global.mbarrier::complete_tx::bytes [%0], [%1, {%3, %4}], [%2];"
               :: "r"(dst), "l"((uint64_t)tm), "r"(mb), "r"(c0), "r"(c1) : "memory"); }
__device__ __forceinline__ void tma2d_prefetch(const CUtensorMap* tm, int c0, int c1) {
  asm volatile("cp.async.bulk.prefetch.tensor.2d.L2.global.tile [%0, {%1, %2}];" :: "l"((uint64_t)tm), "r"(c0), "r"(c1) : "memory"); }
__device__ __forceinline__ void bulk_g2s_mc(uint32_t dst, const void* src, uint32_t bytes, uint32_t mb, uint16_t mask) {
  asm volatile("cp.async.bulk.shared::cluster.global.mbarrier::complete_tx::bytes.multicast::cluster [%0], [%1], %2, [%3], %4;"
               :: "r"(dst), "l"(src), "r"(bytes), "r"(mb), "h"(mask) : "memory"); }
__device__ __forceinline__ void bulk_s2g(void* dst, uint32_t src, uint32_t bytes) {
  asm volatile("cp.async.bulk.global.shared::cta.bulk_group [%0], [%1], %2;" :: "l"(dst), "r"(src), "r"(bytes) : "memory"); }
__device__ __forceinline__ void wg_fence() { asm volatile("wgmma.fence.sync.aligned;" ::: "memory"); }
__device__ __forceinline__ void wg_commit() { asm volatile("wgmma.commit_group.sync.aligned;" ::: "memory"); }
template <int N> __device__ __forceinline__ void wg_wait() { asm volatile("wgmma.wait_group.sync.aligned %0;" :: "n"(N) : "memory"); }
__device__ __forceinline__ uint64_t mkdesc(uint32_t addr, uint32_t lbo, uint32_t sbo, uint32_t swz) {
  return (uint64_t)((addr & 0x3FFFF) >> 4) | ((uint64_t)(lbo >> 4) << 16) | ((uint64_t)(sbo >> 4) << 32) | ((uint64_t)swz << 62); }

#define ACC4(d) "+f"(d[0]),"+f"(d[1]),"+f"(d[2]),"+f"(d[3])
#define ACC8(d) ACC4(d), ACC4((d + 4))
#define ACC16(d) ACC8(d), ACC8((d + 8))
#define ACC20(d) ACC16(d), ACC4((d + 16))
#define ACC24(d) ACC16(d), ACC8((d + 16))
#define SMEM0 0x400
__host__ __device__ constexpr uint32_t dlo(uint32_t off, uint32_t lbo) { return ((SMEM0 + off) >> 4) | ((lbo >> 4) << 16); }
__host__ __device__ constexpr uint32_t dhi(uint32_t sbo, uint32_t swz) { return (sbo >> 4) | (swz << 30); }
#define R4S "{%0,%1,%2,%3}"
#define R8S "{%0,%1,%2,%3,%4,%5,%6,%7}"
#define R16S "{%0,%1,%2,%3,%4,%5,%6,%7,%8,%9,%10,%11,%12,%13,%14,%15}"
#define R20S "{%0,%1,%2,%3,%4,%5,%6,%7,%8,%9,%10,%11,%12,%13,%14,%15,%16,%17,%18,%19}"
#define R24S "{%0,%1,%2,%3,%4,%5,%6,%7,%8,%9,%10,%11,%12,%13,%14,%15,%16,%17,%18,%19,%20,%21,%22,%23}"
template <int N> struct MM;
#define DEF_MM(N, ACCM, RS_, I0, I1, I2, I3, I4, I5, I6, I7)                                                                      \
  template <> struct MM<N> {                                                                                                      \
    template <uint32_t BLO, uint32_t BHI, int ACC>                                                                                \
    static __device__ __forceinline__ void rs(float* d, uint32_t a0, uint32_t a1, uint32_t a2, uint32_t a3) {                     \
      asm volatile("{\n.reg .b64 b;\nmov.b64 b, {%" #I4 ", %" #I5 "};\n"                                                          \
                   "wgmma.mma_async.sync.aligned.m64n" #N "k16.f32.bf16.bf16 " RS_ ", {%" #I0 ",%" #I1 ",%" #I2 ",%" #I3 "}, b, %" #I6 ", 1, 1, 0;\n}" \
                   : ACCM(d) : "r"(a0), "r"(a1), "r"(a2), "r"(a3), "n"(BLO), "n"(BHI), "n"(ACC)); }                               \
    template <uint32_t ALO, uint32_t AHI, uint32_t BLO, uint32_t BHI, int ACC, int TA>                                            \
    static __device__ __forceinline__ void ss(float* d, uint32_t abase) {                                                         \
      asm volatile("{\n.reg .b64 a, b;\n.reg .b32 l;\nadd.u32 l, %" #I0 ", %" #I1 ";\nmov.b64 a, {l, %" #I2 "};\nmov.b64 b, {%" #I3 ", %" #I4 "};\n" \
                   "wgmma.mma_async.sync.aligned.m64n" #N "k16.f32.bf16.bf16 " RS_ ", a, b, %" #I5 ", 1, 1, %" #I6 ", 0;\n}"     \
                   : ACCM(d) : "r"(abase), "n"(ALO), "n"(AHI), "n"(BLO), "n"(BHI), "n"(ACC), "n"(TA)); }                          \
    template <int ACC>                                                                                                            \
    static __device__ __forceinline__ void rsd(float* d, uint32_t a0, uint32_t a1, uint32_t a2, uint32_t a3, uint64_t b) {        \
      asm volatile("wgmma.mma_async.sync.aligned.m64n" #N "k16.f32.bf16.bf16 " RS_ ", {%" #I0 ",%" #I1 ",%" #I2 ",%" #I3 "}, %" #I4 ", %" #I5 ", 1, 1, 0;" \
                   : ACCM(d) : "r"(a0), "r"(a1), "r"(a2), "r"(a3), "l"(b), "n"(ACC)); }                                           \
    template <int ACC>                                                                                                            \
    static __device__ __forceinline__ void ssd(float* d, uint64_t a, uint64_t b) {                                                \
      asm volatile("wgmma.mma_async.sync.aligned.m64n" #N "k16.f32.bf16.bf16 " RS_ ", %" #I0 ", %" #I1 ", %" #I2 ", 1, 1, 1, 0;"  \
                   : ACCM(d) : "l"(a), "l"(b), "n"(ACC)); }                                                                       \
    template <uint32_t ALO, uint32_t AHI, uint32_t BLO, uint32_t BHI, int ACC>                                                    \
    static __device__ __forceinline__ void ss2(float* d, uint32_t abase, uint32_t bbase) {                                        \
      asm volatile("{\n.reg .b64 a, b;\n.reg .b32 l, m;\nadd.u32 l, %" #I0 ", %" #I1 ";\nmov.b64 a, {l, %" #I2 "};\n"            \
                   "add.u32 m, %" #I6 ", %" #I3 ";\nmov.b64 b, {m, %" #I4 "};\n"                                                   \
                   "wgmma.mma_async.sync.aligned.m64n" #N "k16.f32.bf16.bf16 " RS_ ", a, b, %" #I5 ", 1, 1, 0, 0;\n}"            \
                   : ACCM(d) : "r"(abase), "n"(ALO), "n"(AHI), "n"(BLO), "n"(BHI), "n"(ACC), "r"(bbase)); }                                    \
  };
DEF_MM(8, ACC4, R4S, 4, 5, 6, 7, 8, 9, 10, 11)
DEF_MM(16, ACC8, R8S, 8, 9, 10, 11, 12, 13, 14, 15)
DEF_MM(32, ACC16, R16S, 16, 17, 18, 19, 20, 21, 22, 23)
DEF_MM(40, ACC20, R20S, 20, 21, 22, 23, 24, 25, 26, 27)
DEF_MM(48, ACC24, R24S, 24, 25, 26, 27, 28, 29, 30, 31)

#define LAG 11
#define NSTEP (NSEG + LAG)
#define NR (NSTEP + 1)
__device__ __align__(1024) __nv_bfloat16 g_xn[2][S_LEN * DM];
__device__ __align__(1024) unsigned char g_o[NSTEP * 96 * 8192];
__device__ __align__(1024) uint32_t g_part[6][7][40][64];
#define RD 16
#define TILE_B 81920
__device__ __align__(1024) float2 g_stat[S_LEN];
__device__ __align__(1024) uint32_t g_st2[2][RD][64];
__device__ __align__(1024) unsigned char g_acc[5][RD][TILE_B];
#define NOP 19
#define NW12 5
#define NW34 12
#define NBC (NOP + NW12 + NW34)
__device__ __align__(1024) unsigned char g_wt[NOP * 10 * 12288];
enum { F_O = 0, F_R1 = NOP + 1, F_R2 = F_R1 + 4, F_R3 = F_R2 + 4, F_Z = F_R3 + 4, F_DONE, F_MISC, F_NUM };
__device__ __align__(128) uint32_t g_f[F_NUM][96];
__device__ __align__(128) int g_xready[129][8];
__device__ uint32_t g_tpc[128];
#define TS(i)
#define TSV(i, v)
#define TSN(i)
#define TSD(i, dep)
#define BTS(k, i)
#define BTS2(k, i)
#define RTS(i)
#define RTSD(i, dep)
#define RTS_OUT()
#define CTS(i)
#define PTS(i)
#define PTS1(i)
#define CTS_OUT()
#define GTS(i)

#define CL_SIZE 15
#define NCL 7
#define SSQ 13
#define SSV 16
#define PL_SZ 5376
#define TILE_SBO 2560
#define TILE_GRP 15360
#define WS_SZ ((2 * SSQ + SSV) * 2048)
#define OFF_QK (OFF_WO + 26 * 2048)
#define LAYOUT 2
#define OFF_TILE 0
#define OFF_WS (4 * TILE_GRP)
#define OFF_WO (OFF_WS + WS_SZ)
#define OFF_PL (OFF_QK + 20480)
#define OFF_BAR (OFF_PL + 2 * PL_SZ)
#define STG_Q OFF_TILE
#define STG_K OFF_WO
#define VA 14
#define STG_V2 (OFF_TILE + 27 * 2048)
#define OFF_O (OFF_PL + 4352)
#define LAND(k) (((k) >> 1) * TILE_GRP + ((k) & 1) * 1280)
#define LAND_F (5 * TILE_SBO)
#define OFF_XL (OFF_TILE + 3 * TILE_GRP)
#define OFF_XF (OFF_XL + LAND_F)
#define OFF_WT ((OFF_XL + TILE_SBO + 1023) & ~1023)
#define OFF_TAB (OFF_BAR + 240)
#define OFF_INV (OFF_TAB + 64)
#define OFF_TS (OFF_INV + 128)
#define A_SMEM 232448
static_assert(WS_SZ + 72 * 1024 + 2 * PL_SZ + 4 * TILE_GRP + 512 == A_SMEM && OFF_WS % 1024 == 0 && OFF_WO % 1024 == 0 && SSQ == 13, "smem map");
enum { B_W0 = 0, B_W1, B_F1, B_F2 = B_F1 + 4, B_R1 = B_F2 + 4, B_R2, B_MEMFREE, B_LANDFREE, B_OPEER, B_PLFREE, B_XFREE, B_SB, B_WOF = B_SB + 6, B_WTF, B_RS, B_NUM = B_RS + 4 };
static_assert(B_NUM <= 30, "barriers");
enum { N_C = 0, N_SISS, N_QK, N_V, N_PM, N_TURN, N_PI, N_VGO, N_O, N_PX, N_AB, N_SDONE, N_VDONE, N_G3, N_P, N_OX };

__device__ __forceinline__ bool is_dual(int j) { return j >= LAG && j < NSEG; }
__device__ __forceinline__ int sched_l(int j) { return j < NSEG ? j : NSEG + j - LAG; }
__device__ __forceinline__ int sched_f(int j) { return NSEG + j - LAG; }
__device__ __forceinline__ void wait_cnt(const int* p, int target) {
  int v, n = 0;
  do {
    asm volatile("ld.relaxed.gpu.global.b32 %0, [%1];" : "=r"(v) : "l"(p) : "memory");
    if (v >= target) break;
    __nanosleep(100);
    if (++n > SPIN_LIMIT) FAIL();
  } while (true);
  asm volatile("fence.acquire.gpu;" ::: "memory");
  asm volatile("fence.proxy.async.global;" ::: "memory");
}
__device__ __forceinline__ void red_release(void* p, uint32_t v) { asm volatile("red.release.gpu.global.add.u32 [%0], %1;" :: "l"(p), "r"(v) : "memory"); }
__device__ __forceinline__ void red_relaxed(void* p, uint32_t v) { asm volatile("red.relaxed.gpu.global.add.u32 [%0], %1;" :: "l"(p), "r"(v) : "memory"); }
#define VMASK 0xa5294a5294ull
__host__ __device__ constexpr int popc40(unsigned long long m) { int c = 0; for (; m; m &= m - 1) c++; return c; }
static_assert(popc40(VMASK) == SSV, "mask");
__host__ __device__ constexpr int ss_idx(int ks, int n) { return n == SSV ? popc40(VMASK & ((1ull << ks) - 1)) : ks * n / 40; }
__host__ __device__ constexpr bool is_ss(int ks, int n) { return ss_idx(ks + 1, n) != ss_idx(ks, n); }
__host__ __device__ constexpr int rs_idx(int ks, int n) { return ks - ss_idx(ks, n); }

#define SL2 (0.07216878364870322f * 1.4426950408889634f)

#define SUM_LOOP 0
#define IMM_K 0
#define TAB_N 32
struct DescTab { uint64_t tile[2][40], unit[2 * SSQ + SSV]; };
constexpr DescTab make_tab() {
  DescTab t = {};
  for (int rg = 0; rg < 2; rg++)
    for (int k = 0; k < 40; k++) t.tile[rg][k] = dlo(OFF_TILE + (k / 10) * TILE_GRP + rg * TILE_SBO + (k % 10) * 256, 128) | ((uint64_t)dhi(TILE_SBO, 0) << 32);
  for (int u = 0; u < 2 * SSQ + SSV; u++) t.unit[u] = dlo(OFF_WS + u * 2048, 0) | ((uint64_t)dhi(1024, 1) << 32);
  return t;
}
__constant__ DescTab c_tab = make_tab();
template <int N, int NSS, int RG, int KS, int K1, int K0 = 0>
__device__ __forceinline__ void proj(float* acc, const uint32_t* W, uint32_t ub) {
  if constexpr (KS < K1) {
    constexpr int i = rs_idx(KS, NSS) * 4;
    if constexpr (N >= TAB_N && !(RG == 0 && NSS == SSQ && KS < IMM_K)) {
      if constexpr (is_ss(KS, NSS)) MM<N>::template ssd<(KS != K0)>(acc, c_tab.unit[ub + ss_idx(KS, NSS)], c_tab.tile[RG][KS]);
      else MM<N>::template rsd<(KS != K0)>(acc, W[i], W[i + 1], W[i + 2], W[i + 3], c_tab.tile[RG][KS]);
    } else {
      constexpr uint32_t BLO = dlo(OFF_TILE + (KS / 10) * TILE_GRP + RG * TILE_SBO + (KS % 10) * 256, 128), BHI = dhi(TILE_SBO, 0);
      if constexpr (is_ss(KS, NSS)) MM<N>::template ss<dlo(OFF_WS + ss_idx(KS, NSS) * 2048, 0), dhi(1024, 1), BLO, BHI, (KS != K0), 1>(acc, ub * 128);
      else MM<N>::template rs<BLO, BHI, (KS != K0)>(acc, W[i], W[i + 1], W[i + 2], W[i + 3]);
    }
    proj<N, NSS, RG, KS + 1, K1, K0>(acc, W, ub);
  }
}
template <int N>
__device__ __forceinline__ void load_w(uint32_t* W, uint32_t stage, int warp, int lane) {
  const int kr = (lane >> 4) * 8 + (lane & 7);
  const int cb = warp * 2 + ((lane >> 3) & 1);
  const uint32_t a0 = stage + kr * 128 + ((cb ^ (lane & 7)) << 4);
#pragma unroll
  for (int i = 0; i < N; i++) ldsm4t(W[4 * i], W[4 * i + 1], W[4 * i + 2], W[4 * i + 3], a0 + i * 2048);
}
template <int N, int U, int OS, int ACC>
__device__ __forceinline__ void wo4(float* d) {
  constexpr uint32_t WA = U >= 4 ? OFF_WO + (U - 4) * 2048 : OFF_WT, OB = OS == 0 ? OFF_O : OS == 1 ? OFF_XL : OFF_XF, SBO = OS ? 1024 : PL_SZ;
  MM<N>::template ss<dlo(WA, 0), dhi(1024, 1), dlo(OB, 128), dhi(SBO, 0), ACC, 1>(d, 0);
  MM<N>::template ss<dlo(WA + 2048, 0), dhi(1024, 1), dlo(OB + 256, 128), dhi(SBO, 0), 1, 1>(d, 0);
  MM<N>::template ss<dlo(WA + 4096, 0), dhi(1024, 1), dlo(OB + 512, 128), dhi(SBO, 0), 1, 1>(d, 0);
  MM<N>::template ss<dlo(WA + 6144, 0), dhi(1024, 1), dlo(OB + 768, 128), dhi(SBO, 0), 1, 1>(d, 0);
}
__device__ __forceinline__ void wo_coord(int i, int t3, int head, int& c0, int& c1) {
  const int g = i >> 1;
  const int blk = g == 0 ? 9 : (g < 4 ? g - 1 : (g - 4) >> 1) * 3 + t3;
  int sl = g < 4 ? t3 : (g & 1) ? t3 + 1 : t3 + 2;
  if (sl >= 3) sl -= 3;
  c0 = blk * 64; c1 = head * DH + sl * 64 + (i & 1) * 32;
}
__device__ __forceinline__ void tok_softmax(uint32_t sb, int job, int lane) {
  const bool w1 = job & 1;
  const int dg = (lane >> 2) - (lane & 3) * 2;
  const uint32_t lo = sb + OFF_PL + (job >> 1) * PL_SZ + (job & 1) * 1792, l8 = lo + 512 + lane * 8, pa = lo + lane * 4;
  const uint32_t km = job & 2 ? 640 : 512;
  float x[14];
  {
    const uint4 a = lds128(lo + lane * 16);
    const uint2 e = lds64(l8);
    const uint32_t c = lds32(768 + pa);
    x[0] = bf_lo(a.x); x[1] = bf_hi(a.x); x[2] = bf_lo(a.y); x[3] = bf_hi(a.y); x[4] = bf_lo(a.z); x[5] = bf_hi(a.z); x[6] = bf_lo(a.w); x[7] = bf_hi(a.w);
    x[8] = bf_lo(c); x[9] = bf_hi(c); x[10] = bf_lo(e.x); x[11] = bf_hi(e.x); x[12] = bf_lo(e.y); x[13] = bf_hi(e.y);
  }
  if (dg < 0) { x[8] = -INFINITY; if (w1) x[4] = -INFINITY; else x[10] = -INFINITY; }
  if (dg < 1) { x[9] = -INFINITY; if (w1) x[5] = -INFINITY; else x[11] = -INFINITY; }
  const float m4 = fmaxf(x[8], x[9]);
  float m0 = fmaxf(fmaxf(fmaxf(x[0], x[1]), fmaxf(x[2], x[3])), fmaxf(fmaxf(x[4], x[5]), fmaxf(x[6], x[7])));
  float m1 = fmaxf(fmaxf(x[10], x[11]), fmaxf(x[12], x[13]));
  if (w1) m1 = fmaxf(m1, m4); else m0 = fmaxf(m0, m4);
  m0 = fmaxf(m0, __shfl_xor_sync(~0u, m0, 1)); m1 = fmaxf(m1, __shfl_xor_sync(~0u, m1, 1));
  sts32(pa + (w1 ? 384 : 896 + 128), 0u); sts32(pa + 1152 - km, 0u); sts32(pa + 896 + 1152 - km, 0u); sts64(l8 + 896 - 256, 0u, 0u);
  m0 = fmaxf(m0, __shfl_xor_sync(~0u, m0, 2)); m1 = fmaxf(m1, __shfl_xor_sync(~0u, m1, 2));
  m0 *= -SL2; m1 *= -SL2;
#pragma unroll
  for (int j = 0; j < 14; j++) x[j] = ex2(fmaf(x[j], SL2, j < 8 ? m0 : j >= 10 ? m1 : w1 ? m1 : m0));
  const float l4s = x[8] + x[9];
  float l0 = ((x[0] + x[1]) + (x[2] + x[3])) + ((x[4] + x[5]) + (x[6] + x[7])), l1 = (x[10] + x[11]) + (x[12] + x[13]);
  if (w1) l1 += l4s; else l0 += l4s;
  l0 += __shfl_xor_sync(~0u, l0, 1); l1 += __shfl_xor_sync(~0u, l1, 1);
  l0 += __shfl_xor_sync(~0u, l0, 2); l1 += __shfl_xor_sync(~0u, l1, 2);
  l0 = rcpf(l0); l1 = rcpf(l1);
#pragma unroll
  for (int j = 0; j < 7; j++) {
    const float iv = j < 4 ? l0 : j > 4 ? l1 : w1 ? l1 : l0;
    sts32(pa + (j < 3 ? j * 128 : j == 3 ? km : j == 4 ? (w1 ? 896 + 128 : 384) : j == 5 ? 896 : 896 + km), pack2(x[2 * j] * iv, x[2 * j + 1] * iv));
  }
}
template <int N>
__device__ __forceinline__ void wo_phase(uint32_t sb, int wg, int warp, int lane, uint32_t par, uint32_t r1) {
  const uint32_t bar = sb + OFF_BAR;
  float x[N / 2], y[N / 2];
  const uint2 ta = lds64(sb + OFF_TAB + (wg * 4 + warp) * 8);
  uint32_t xa = (ta.x & ~255u) + lane * 8, xb = (ta.x & 0xFF0000FFu) + SMEM0 + OFF_BAR, ya = (ta.y & ~255u) + lane * 8, yb = (ta.y & 0xFF0000FFu) + SMEM0 + OFF_BAR;
  asm volatile("" : "+r"(xa), "+r"(xb), "+r"(ya), "+r"(yb));
  auto scat = [&](uint32_t ad, uint32_t mb, const float* d) {
    st_async_v2(ad, pack2(d[0], d[1]), pack2(d[2], d[3]), mb);
    if (N == 16) st_async_v2(ad + LAND_F, pack2(d[4], d[5]), pack2(d[6], d[7]), mb);
  };
  if (wg == 0) {
    bar_sync(N_O, 384);
    wg_fence(); wo4<N, 4, 0, 0>(x); wo4<N, 8, 0, 0>(y); wg_commit();
    mbar_waitu(bar + 8 * B_OPEER, par);
    CFENCE(); wg_fence(); wo4<N, 16, 1, 1>(x); wo4<N, 20, 2, 1>(x); wg_commit();
    wo4<N, 24, 1, 1>(y); wg_commit();
    mbar_waitu2(bar + 8 * B_WOF, bar + 8 * B_MEMFREE, par);
    wg_fence(); wo4<N, 28, 2, 1>(y); wg_commit();
    bar_arrive(N_AB, 256);
    wg_wait<2>(); scat(xa, xb, x);
    wg_wait<0>(); scat(ya, yb, y);
  } else {
    bar_sync(N_O, 384);
    wg_fence(); wo4<N, 0, 0, 0>(x); wg_commit(); wo4<N, 12, 0, 0>(y); wg_commit();
    wg_wait<1>(); mbar_arrive_remote_if(lane == 0, r1);
    mbar_waitu(bar + 8 * B_MEMFREE, par);
    scat(xa, xb, x);
    bar_sync(N_AB, 256);
    CFENCE(); wg_fence(); wo4<N, 32, 1, 1>(y); wo4<N, 36, 2, 1>(y); wg_commit();
    bar_arrive(N_TURN, 256);
    wg_wait<0>(); scat(ya, yb, y);
  }
}
#define DS_DUAL 10
#define DS_SINGLE 20
#define POLL_GAP 100
#define POLL_GAPD 0
#define TOK_DELAY 250
#define LATE_SM 1
#define UMAX 40
#define VD1 6
#define VS1 4
#define VST 17
struct AMaps { CUtensorMap w16[3], wo32; };
__global__ void __launch_bounds__(512, 1)
acore_kernel(const __grid_constant__ AMaps M, const __nv_bfloat16* __restrict__ mem0, int sync_b) {
  extern __shared__ __align__(1024) unsigned char smem_raw[];
  const uint32_t sb = smem_u32(smem_raw);
  GTS(24);
  if (threadIdx.x == 0) {
    uint32_t smid; asm volatile("mov.u32 %0, %%smid;" : "=r"(smid));
    g_tpc[(smid >> 1) & 127] = blockIdx.x - CL_SIZE < 3 * CL_SIZE && blockIdx.x % CL_SIZE >= 12 ? 1 : 2;
    __threadfence();
    asm volatile("griddepcontrol.launch_dependents;");
  }
  const int lane0 = threadIdx.x & 31;
#define LANE_INIT() int lane; asm volatile("mov.u32 %0, %%laneid;" : "=r"(lane))
  const int warp = __shfl_sync(~0u, (threadIdx.x >> 5) & 3, 0);
  const int cl = blockIdx.x / CL_SIZE;
  const uint32_t rank = blockIdx.x - cl * CL_SIZE;
  const int nh = cl >= 1 && cl <= 3 ? 4 : 5;
  const int nA = 3 * nh;
  const int wg = __shfl_sync(~0u, (int)rank < nA ? threadIdx.x >> 7 : 4, 0);
  const int head = (cl < 4 ? (cl ? 1 + 4 * cl : 0) : 5 * cl - 3) + rank / 3;
  const int t3 = rank % 3;
  const int col0 = head * DH + t3 * 64;
  const uint32_t bar = sb + OFF_BAR;
  const uint32_t rb0 = SMEM0;
  const uint16_t mcmask = (uint16_t)((1u << nA) - 1);
  const uint32_t nxt = sb + ((t3 == 2 ? -2 : 1) << 24), prv = sb + ((t3 == 0 ? 2 : -1) << 24);
  const int ig = (int)rank - (nA - 4);

  if (threadIdx.x == 0) {
    if (mapa(sb, nA - 1) != rb0 + ((nA - 1) << 24) || mapa(sb, 0) != rb0 || mapa(sb, 1) != rb0 + (1u << 24) || sb != SMEM0 + (rank << 24)) FAIL();
    for (int i = 0; i < B_NUM; i++)
      mbar_init(bar + 8 * i, i == B_R1 ? 4 * nA : i == B_R2 ? 12 * nA : i == B_MEMFREE ? nA : i == B_LANDFREE ? 4 * nA : i == B_PLFREE || i == B_XFREE ? 2 : 1);
    asm volatile("fence.mbarrier_init.release.cluster;" ::: "memory");
    mbar_expect(bar + 8 * B_W0, (80 + SSV + VST) * 2048);
  }
  __syncthreads();
  if (lane0 == 0) {
    const int w12 = wg * 4 + warp;
    if (w12 < 10) {
#pragma unroll 1
      for (int ks = 4 * w12; ks < 4 * w12 + 4; ks++) {
        const bool ss = is_ss(ks, SSQ);
        tma2d(ss ? sb + OFF_WS + ss_idx(ks, SSQ) * 2048 : sb + STG_Q + rs_idx(ks, SSQ) * 2048, &M.w16[0], col0, ks * 16, bar + 8 * B_W0);
        tma2d(ss ? sb + OFF_WS + (SSQ + ss_idx(ks, SSQ)) * 2048 : sb + STG_K + rs_idx(ks, SSQ) * 2048, &M.w16[1], col0, ks * 16, bar + 8 * B_W0);
        if (is_ss(ks, SSV)) tma2d(sb + OFF_WS + (2 * SSQ + ss_idx(ks, SSV)) * 2048, &M.w16[2], col0, ks * 16, bar + 8 * B_W0);
        else if (rs_idx(ks, SSV) < VST) tma2d(sb + (rs_idx(ks, SSV) < VA ? STG_K + 27 * 2048 : STG_V2 - VA * 2048) + rs_idx(ks, SSV) * 2048, &M.w16[2], col0, ks * 16, bar + 8 * B_W0);
        else tma2d_prefetch(&M.w16[2], col0, ks * 16);
      }
      int c0, c1;
      wo_coord(2 * w12, t3, head, c0, c1);
      tma2d_prefetch(&M.wo32, c0, c1);
      tma2d_prefetch(&M.wo32, c0, c1 + 32);
    }
  }
  static_assert(40 - SSV - VST <= 10, "staging");
  if (lane0 < 2 && wg < 2) {
    const int u = 4 * (wg ? (lane0 ? 6 + t3 : 9) : (lane0 ? 3 + t3 : t3)) + warp;
    const int li = (u >= nA) + (u >= 2 * nA) + (u >= 3 * nA);
    sts32(sb + OFF_TAB + (wg * 4 + warp) * 8 + lane0 * 4,
          rb0 + ((u - li * nA) << 24) + OFF_TILE + LAND(li + (u >= 36 ? t3 : 0)) + (rank / 3) * 256 + 8 * (B_RS + li));
  }
  __syncthreads();
  GTS(25);

  auto issue_tok = [&](int sc, int fb, int rel = -1, uint32_t ph = 0) {
    if (sync_b) wait_cnt(&g_xready[sc][0], 32);
    if (rel >= 0) mbar_waitu(bar + 8 * rel, ph);
    bulk_g2s_mc_e(sb + OFF_TILE + ig * TILE_GRP + TILE_SBO, &g_xn[0][0] + uni(sc * (32 * DM)) + ig * 5120, 10240, bar + 8 * (fb + ig), mcmask);
  };
#define POLL(d, q) _Pragma("unroll") for (int k = 0; k < NCL; k++) \
      asm volatile("ld.relaxed.gpu.global.v2.b32 {%0,%1}, [%2];" : "=r"(d[k].x), "=r"(d[k].y) : "l"(q + k * 2560) : "memory")
#define L3(L, a, b, c) lop3<L>(a, b, c)
#define TAGS(L, d) L3(L, L3(L, L3(L, d[0].x, d[0].y, d[1].x), L3(L, d[1].y, d[2].x, d[2].y), L3(L, d[3].x, d[3].y, d[4].x)), L3(L, d[4].y, d[5].x, d[5].y), L3(L, d[6].x, d[6].y, d[6].y))
    auto deliver = [&](uint2* pa, const uint32_t* gq, int u, int c, int dc, int ds, int step, bool first, int lane) {
      const uint32_t off = uni(OFF_TILE + ((u * 205) >> 11) * (TILE_GRP - TILE_SBO) + u * 256 + dc * LAND_F), boff = uni(OFF_BAR + 8 * (B_F1 + ((u * 205) >> 11)));
      const uint32_t* mi = &g_part[4][0][0][0] + uni((c * NCL + cl) * 2560 + u * 64);
      mbar_waitu(bar + 8 * B_LANDFREE, step & 1);
      int n = 0;
      while (true) {
        const bool ok = __all_sync(~0u, ((step & 2 ? ~TAGS(0xFE, pa) : TAGS(0x80, pa)) & 1) != 0);
        if (ok) break;
        if (++n > SPIN_LIMIT) FAIL();
        POLL(pa, gq);
      }
      if (warp == 0 && first) { TS(19); TSV(10, n); }
      const uint32_t w0 = hadd2bf(hadd2bf(hadd2bf(pa[0].x, pa[1].x), hadd2bf(pa[2].x, pa[3].x)), hadd2bf(hadd2bf(pa[4].x, pa[5].x), pa[6].x));
      const uint32_t w1 = hadd2bf(hadd2bf(hadd2bf(pa[0].y, pa[1].y), hadd2bf(pa[2].y, pa[3].y)), hadd2bf(hadd2bf(pa[4].y, pa[5].y), pa[6].y));
      if (u < ds) {
        const uint32_t da = SMEM0 + off + lane * 8, db = SMEM0 + boff;
#pragma unroll
        for (int d = 0; d < 12; d++) st_async_v2((d << 24) + da, w0, w1, (d << 24) + db);
#pragma unroll
        for (int d = 12; d < 15; d++) st_async_v2_if(nA == 15, (d << 24) + da, w0, w1, (d << 24) + db);
      } else {
        *reinterpret_cast<uint2*>(const_cast<uint32_t*>(gq) + ((4 - 2 * (step & 1)) * NCL + cl) * 2560) = make_uint2(w0, w1);
        asm volatile("fence.proxy.async.global;" ::: "memory");
        __syncwarp();
        bulk_g2s_mc_e(sb + off, mi, 256, sb + boff, mcmask);
      }
    };
#define REL(b, g) mbar_arrive_remote_if(lane == 0, rb0 + ((nA - 4 + (g)) << 24) + OFF_BAR + 8 * (b))

  if (wg < 2) {
    asm volatile("setmaxnreg.inc.sync.aligned.u32 160;");
    LANE_INIT();
    uint32_t W[4 * (40 - SSQ)];
    mbar_waitw(bar + 8 * B_W0, 0);
    GTS(26);
    load_w<40 - SSQ>(W, sb + (wg ? STG_K : STG_Q), warp, lane);
    fence_async();
    bar_sync(1, 384);
    cluster_sync_all();
    const uint32_t wbase = wg * SSQ;
    GTS(27);
#pragma unroll 1
    for (int step = -1; step < NSTEP; step++) {
      const uint32_t par = step & 1;
      asm volatile("" : "+r"(lane));
      const bool dual = is_dual(step), has_next = step + 1 < NSTEP;
#define QK_SA (sb + OFF_QK + wg * 15360 + (2 * warp + ((lane >> 3) & 1)) * 128 + (lane & 7) * 16)
#define QK_F (wg ? -5120 : 5120)
#define QK_S12 ((wg ? (lane >> 4) : 1 + 2 * (lane >> 4)) * 1024)
#define QK_S34 ((wg ? 2 + (lane >> 4) : 2 - 2 * (lane >> 4)) * 1024)
      if (step >= 0) {
        if (dual) {
          float acc[24];
          mbar_waitu(bar + 8 * (B_F1 + 0), par);
          if (wg + warp == 0) { TS(0); TSN(1); }
          CFENCE(); wg_fence(); proj<48, SSQ, 0, 0, 10>(acc, W, wbase); wg_commit();
          mbar_waitu(bar + 8 * (B_F1 + 1), par);
          CFENCE(); wg_fence(); proj<48, SSQ, 0, 10, 20>(acc, W, wbase); wg_commit();
          mbar_waitu(bar + 8 * (B_F1 + 2), par);
          CFENCE(); wg_fence(); proj<48, SSQ, 0, 20, 30>(acc, W, wbase); wg_commit();
          mbar_waitu2(bar + 8 * (B_F1 + 3), bar + 8 * B_PLFREE, par);
          if (wg + warp == 0) TS(2);
          CFENCE(); wg_fence(); proj<48, SSQ, 0, 30, 40>(acc, W, wbase); wg_commit();
          bar_arrive(N_VGO, 384);
          const uint32_t sa = QK_SA, s0 = sa + 4096 + (lane >> 4) * QK_F, s1 = sa + QK_F + QK_S12, s2 = sa + QK_F + QK_S34;
          wg_wait<0>();
          if (wg + warp == 0) TS(3);
          stsm4t(s0, pack2(acc[0], acc[1]), pack2(acc[2], acc[3]), pack2(acc[20], acc[21]), pack2(acc[22], acc[23]));
          stsm4t(s1, pack2(acc[4], acc[5]), pack2(acc[6], acc[7]), pack2(acc[8], acc[9]), pack2(acc[10], acc[11]));
          stsm4t(s2, pack2(acc[12], acc[13]), pack2(acc[14], acc[15]), pack2(acc[16], acc[17]), pack2(acc[18], acc[19]));
        } else {
          float acc[4];
          mbar_waitu(bar + 8 * (B_F1 + 0), par);
          if (wg + warp == 0) { TS(0); TSN(1); }
          CFENCE(); wg_fence(); proj<8, SSQ, 0, 0, 10>(acc, W, wbase); wg_commit();
          mbar_waitu(bar + 8 * (B_F1 + 1), par);
          CFENCE(); wg_fence(); proj<8, SSQ, 0, 10, 20>(acc, W, wbase); wg_commit();
          mbar_waitu(bar + 8 * (B_F1 + 2), par);
          CFENCE(); wg_fence(); proj<8, SSQ, 0, 20, 30>(acc, W, wbase); wg_commit();
          mbar_waitu2(bar + 8 * (B_F1 + 3), bar + 8 * B_PLFREE, par);
          if (wg + warp == 0) TS(2);
          CFENCE(); wg_fence(); proj<8, SSQ, 0, 30, 40>(acc, W, wbase); wg_commit();
          bar_arrive(N_VGO, 384);
          const uint32_t s0 = QK_SA + 4096;
          wg_wait<0>();
          if (wg + warp == 0) TS(3);
          stsm2t(s0, pack2(acc[0], acc[1]), pack2(acc[2], acc[3]));
        }
        fence_async();
        bar_sync(N_QK, 256);
        if (wg == 0 || dual) {
          float s[20];
          const uint32_t ab = wg * 192, bb = wg * -320;
          wg_fence();
          MM<40>::ss2<dlo(OFF_QK, 128), dhi(1024, 0), dlo(OFF_QK + 15360, 128), dhi(1024, 0), 0>(s, ab, bb);
          MM<40>::ss2<dlo(OFF_QK + 256, 128), dhi(1024, 0), dlo(OFF_QK + 15360 + 256, 128), dhi(1024, 0), 1>(s, ab, bb);
          MM<40>::ss2<dlo(OFF_QK + 512, 128), dhi(1024, 0), dlo(OFF_QK + 15360 + 512, 128), dhi(1024, 0), 1>(s, ab, bb);
          MM<40>::ss2<dlo(OFF_QK + 768, 128), dhi(1024, 0), dlo(OFF_QK + 15360 + 768, 128), dhi(1024, 0), 1>(s, ab, bb);
          wg_commit();
          bar_arrive(N_SISS, 384);
          const int rw = (warp - wg) & 3;
          const uint32_t bo = OFF_BAR + 8 * (B_SB + 3 * wg + rw), lo = OFF_PL + wg * PL_SZ + rw * 1792;
          const uint32_t km = wg ? 640 : 512;
          uint32_t l16 = lo + lane * 16, l4 = lo + lane * 4;
          mbar_expect_if(lane == 0 && rw < 3, sb + bo, rw < 2 ? 1792 : 1280);
          asm volatile("" : "+r"(l16), "+r"(l4));
          if (rw == 2) {
            wg_wait<0>();
            if (wg == 0) TSD(4, __float_as_uint(s[0]));
            {
              const uint32_t w0 = pack2(s[0], s[1]), w1 = pack2(s[4], s[5]), w2 = pack2(s[8], s[9]), w3 = pack2(s[12], s[13]), w4 = pack2(s[16], s[17]);
              st_async_v4(nxt + 896 + l16, w0, w1, w2, w3, nxt + bo);
              st_async_v4(prv + l16, w0, w1, w2, w3, prv + bo);
              st_async_b32(nxt + 896 + 768 + l4, w4, nxt + bo);
              st_async_b32(prv + 768 + l4, w4, prv + bo);
            }
            bar_arrive(N_SDONE, 256);
            mbar_waitu(sb + bo, (step - wg * LAG) & 1);
            if (wg == 0) TS(5);
            float x[10];
            {
              const uint4 a = lds128(sb + l16), b = lds128(sb + 896 + l16);
              const uint32_t c = lds32(sb + 768 + l4), d = lds32(sb + 896 + 768 + l4);
              const uint32_t e0 = hadd2bf(a.x, b.x), e1 = hadd2bf(a.y, b.y), e2 = hadd2bf(a.z, b.z), e3 = hadd2bf(a.w, b.w), e4 = hadd2bf(c, d);
              x[0] = s[0] + bf_lo(e0); x[1] = s[1] + bf_hi(e0); x[2] = s[4] + bf_lo(e1); x[3] = s[5] + bf_hi(e1); x[4] = s[8] + bf_lo(e2);
              x[5] = s[9] + bf_hi(e2); x[6] = s[12] + bf_lo(e3); x[7] = s[13] + bf_hi(e3); x[8] = s[16] + bf_lo(e4); x[9] = s[17] + bf_hi(e4);
            }
            float m0 = fmaxf(fmaxf(fmaxf(x[0], x[1]), fmaxf(x[2], x[3])), fmaxf(fmaxf(x[4], x[5]), fmaxf(fmaxf(x[6], x[7]), fmaxf(x[8], x[9]))));
            m0 = fmaxf(m0, __shfl_xor_sync(~0u, m0, 1));
            sts32(sb + l4 + 1152 - km, 0u);
            m0 = fmaxf(m0, __shfl_xor_sync(~0u, m0, 2));
            m0 *= -SL2;
#pragma unroll
            for (int j = 0; j < 5; j++) {
              x[2 * j] = ex2(fmaf(x[2 * j], SL2, m0)); x[2 * j + 1] = ex2(fmaf(x[2 * j + 1], SL2, m0));
              sts32(sb + l4 + (j < 4 ? j * 128 : km), pack2(x[2 * j], x[2 * j + 1]));
            }
            float l = ((x[0] + x[1]) + (x[2] + x[3])) + ((x[4] + x[5]) + ((x[6] + x[7]) + (x[8] + x[9])));
            l += __shfl_xor_sync(~0u, l, 1);
            fence_async();
            sts32(sb + OFF_INV + wg * 64 + (lane >> 1) * 4, __float_as_uint(l));
            bar_arrive(N_PM, dual ? 224 : 192);
            if (wg == 0) TS(6);
          } else if (rw < 2) {
            const bool w1 = rw == 1;
            const uint32_t l8 = lo + 512 + lane * 8;
            uint32_t tw[7];
            wg_wait<0>();
            bar_arrive(N_SDONE, 256);
            tw[0] = pack2(s[0], s[1]); tw[1] = pack2(s[4], s[5]); tw[2] = pack2(s[8], s[9]); tw[3] = pack2(s[16], s[17]);
            tw[4] = w1 ? pack2(s[6], s[7]) : pack2(s[12], s[13]); tw[5] = pack2(s[2], s[3]); tw[6] = pack2(s[18], s[19]);
            { const uint32_t t0 = clock32(); while (clock32() - t0 < TOK_DELAY) {} }
            st_async_v4(nxt + 896 + l16, tw[0], tw[1], tw[2], tw[3], nxt + bo);
            st_async_v4(prv + l16, tw[0], tw[1], tw[2], tw[3], prv + bo);
            st_async_v2(nxt + 896 + l8, tw[5], tw[6], nxt + bo);
            st_async_v2(prv + l8, tw[5], tw[6], prv + bo);
            st_async_b32(nxt + 896 + 768 + l4, tw[4], nxt + bo);
            st_async_b32(prv + 768 + l4, tw[4], prv + bo);
            mbar_waitu(sb + bo, (step - wg * LAG) & 1);
            const uint4 a = lds128(sb + l16), b = lds128(sb + 896 + l16);
            const uint2 e = lds64(sb + l8), f = lds64(sb + 896 + l8);
            const uint32_t c = lds32(sb + 768 + l4), d = lds32(sb + 896 + 768 + l4);
            sts128(sb + l16, hadd2bf(hadd2bf(a.x, b.x), tw[0]), hadd2bf(hadd2bf(a.y, b.y), tw[1]), hadd2bf(hadd2bf(a.z, b.z), tw[2]), hadd2bf(hadd2bf(a.w, b.w), tw[3]));
            sts64(sb + l8, hadd2bf(hadd2bf(e.x, f.x), tw[5]), hadd2bf(hadd2bf(e.y, f.y), tw[6]));
            sts32(sb + 768 + l4, hadd2bf(hadd2bf(c, d), tw[4]));
            bar_arrive(N_PX, dual ? 256 : 192);
            if (wg + warp == 0) TS(9);
          } else {
            wg_wait<0>();
            if (wg == 0) {
              mbar_expect_if(lane < 3 && has_next, bar + 8 * (lane == 2 ? B_OPEER : B_WOF + lane), lane == 2 ? (dual ? 4096 : 2048) : lane ? 8192 : 20480);
              auto fetch = [&](int i, int n, uint32_t dst, int mb) {
                int c0, c1; wo_coord(i, t3, head, c0, c1);
                tma2d_e(dst, &M.wo32, c0, c1, bar + 8 * mb); if (n == 2) tma2d_e(dst + 4096, &M.wo32, c0, c1 + 32, bar + 8 * mb);
              };
              bar_sync(N_G3, 160);
              if (has_next) {
                fetch(0, 2, sb + OFF_WT, B_WTF);
                mbar_arrive_remote_if(lane < 2, (lane ? nxt : prv) + OFF_BAR + 8 * B_XFREE);
              }
              bar_sync(N_SDONE, 256);
              if (has_next) {
                fetch(15, 1, sb + OFF_QK, B_WOF); fetch(16, 2, sb + OFF_QK + 4096, B_WOF); fetch(18, 2, sb + OFF_QK + 12288, B_WOF);
                mbar_waitu(bar + 8 * B_XFREE, par);
              }
              bar_arrive(N_PM, dual ? 224 : 192);
              bar_sync(N_VDONE, 160);
              mbar_arrive_remote_if(lane < nA && has_next, rb0 + (lane << 24) + OFF_BAR + 8 * B_MEMFREE);
              if (has_next) mbar_waitu(bar + 8 * B_WTF, par);
            } else {
              bar_arrive(N_SDONE, 256);
              if ((unsigned)ig < 3) issue_tok(sched_l(step + 1), B_F2, B_R1, (step - LAG) & 1);
            }
          }
        } else {
          bar_arrive(N_SISS, 384);
          bar_arrive(N_SDONE, 256);
        }
        if (has_next) {
          if (step == 0) mbar_waitw(bar + 8 * B_W0, 1);
          const uint32_t r1 = rb0 + ((nA - 1) << 24) + OFF_BAR + 8 * B_R1;
          if (dual) wo_phase<16>(sb, wg, warp, lane, par, r1); else wo_phase<8>(sb, wg, warp, lane, par, r1);
          bar_arrive(N_C, 288);
          if (warp == 0) TS(7 + wg);
        }
      }
      if (has_next) {
        float acc[16];
        mbar_waitu(bar + 8 * B_F2, par ^ 1);
        wg_fence(); proj<32, SSQ, 1, 0, 10>(acc, W, wbase); wg_commit();
        mbar_waitu(bar + 8 * (B_F2 + 1), par ^ 1);
        wg_fence(); proj<32, SSQ, 1, 10, 14>(acc, W, wbase); wg_commit();
        wg_wait<1>(); REL(B_R2, 0);
        wg_fence(); proj<32, SSQ, 1, 14, 20>(acc, W, wbase); wg_commit();
        mbar_waitu(bar + 8 * (B_F2 + 2), par ^ 1);
        wg_fence(); proj<32, SSQ, 1, 20, 24>(acc, W, wbase); wg_commit();
        wg_wait<1>(); REL(B_R2, 1);
        wg_fence(); proj<32, SSQ, 1, 24, 30>(acc, W, wbase); wg_commit();
        mbar_waitu(bar + 8 * (B_F2 + 3), par ^ 1);
        wg_fence(); proj<32, SSQ, 1, 30, 34>(acc, W, wbase); wg_commit();
        wg_wait<1>(); REL(B_R2, 2);
        wg_fence(); proj<32, SSQ, 1, 34, 40>(acc, W, wbase); wg_commit();
        const uint32_t sa = QK_SA, s1 = sa + QK_S12, s2 = sa + QK_S34;
        wg_wait<0>(); REL(B_R2, 3);
        if (warp == 0) TS(11 + wg);
        stsm4t(s1, pack2(acc[0], acc[1]), pack2(acc[2], acc[3]), pack2(acc[4], acc[5]), pack2(acc[6], acc[7]));
        stsm4t(s2, pack2(acc[8], acc[9]), pack2(acc[10], acc[11]), pack2(acc[12], acc[13]), pack2(acc[14], acc[15]));
      }
    }
    GTS(28);
    cluster_sync_all();
  } else if (wg == 2) {
    asm volatile("setmaxnreg.inc.sync.aligned.u32 160;");
    LANE_INIT();
    uint32_t W[4 * (40 - SSV)];
    mbar_waitw(bar + 8 * B_W0, 0);
    load_w<VA>(W, sb + STG_K + 27 * 2048, warp, lane);
    load_w<VST - VA>(W + 4 * VA, sb + STG_V2, warp, lane);
    fence_async();
    bar_sync(1, 384);
    if (lane == 0) {
      if (warp == 0) {
        mbar_expect(bar + 8 * B_W1, (40 - SSV - VST) * 2048);
#pragma unroll 1
        for (int ks = 0; ks < 40; ks++)
          if (!is_ss(ks, SSV) && rs_idx(ks, SSV) >= VST) tma2d(sb + OFF_QK + (rs_idx(ks, SSV) - VST) * 2048, &M.w16[2], col0, ks * 16, bar + 8 * B_W1);
      } else {
        if (warp == 1) mbar_expect(bar + 8 * B_W0, 26 * 2048);
#pragma unroll 1
        for (int i = warp - 1; i < 13; i += 3) { int c0, c1; wo_coord(i + 2, t3, head, c0, c1); tma2d(sb + OFF_WO + i * 4096, &M.wo32, c0, c1, bar + 8 * B_W0); }
      }
    }
    __syncwarp();
#pragma unroll
    for (int i = 0; i < 5; i++) {
      const int t = i * 128 + warp * 32 + lane;
      const uint4 v = *reinterpret_cast<const uint4*>(mem0 + (t & 7) * DM + (t >> 3) * 8);
      sts128(sb + OFF_TILE + (t / 160) * (TILE_GRP - TILE_SBO) + t * 16, v.x, v.y, v.z, v.w);
    }
    mbar_waitw(bar + 8 * B_W1, 0);
    load_w<40 - SSV - VST>(W + 4 * VST, sb + OFF_QK, warp, lane);
    fence_async();
    mbar_arrive_if(lane == 0, bar + 8 * (B_F1 + warp));
    mbar_expect_if(lane == 0, bar + 8 * (B_F2 + warp), 10240);
    mbar_arrive_if(warp == 3 && lane < 2, bar + 8 * B_PLFREE);
    cluster_sync_all();
    uint32_t vl[8];
    constexpr uint32_t wbase = 2 * SSQ;
    {
      float v[16];
      mbar_waitw4(bar + 8 * B_F2, 0);
      wg_fence(); proj<32, SSV, 1, 0, 40>(v, W, wbase); wg_commit();
      wg_wait<0>();
      mbar_arrive_remote_if(lane < 4, rb0 + ((nA - 4 + lane) << 24) + OFF_BAR + 8 * B_R2);
#pragma unroll
      for (int j = 0; j < 8; j++) vl[j] = pack2v(v[2 * j], v[2 * j + 1]);
      if (warp == 0 && (unsigned)ig < 3) issue_tok(1, B_F2, B_R2, 0);
    }
#pragma unroll 1
    for (int step = 0; step < NSTEP; step++) {
      const uint32_t par = step & 1;
      asm volatile("" : "+r"(lane));
      const bool dual = is_dual(step), has_next = step + 1 < NSTEP;
      mbar_expect_if(lane == 0 && has_next, bar + 8 * (B_F2 + warp), 10240);
      if (warp == 0 && ig == 3 && has_next && sync_b) wait_cnt(&g_xready[sched_l(step + 1)][0], 32);
      bar_sync(N_VGO, 384);
      CFENCE();
#define F1_BYTES (is_dual(step + 1) ? 15360 : 2560)
#define ARM() do { \
        mbar_expect_if(lane == 0 && has_next, bar + 8 * (B_F1 + warp), F1_BYTES); \
        mbar_expect_if(lane == 0 && has_next && warp * nA + (int)rank < 40, bar + 8 * (B_RS + warp), (warp * nA + (int)rank >= 36 ? nA : nh) * (dual ? 512 : 256)); } while (0)
#define O_ADDR() uint32_t oa = sb + OFF_O + (lane >> 4) * PL_SZ + warp * 256 + (lane & 15) * 16, xo = (lane >> 4) * 1024 + warp * 256 + (lane & 15) * 16; \
        asm volatile("" : "+r"(oa), "+r"(xo))
#define O_READY(act) do { if (has_next) { const uint4 ov = lds128(oa); \
        if (act) { st_async_v4(nxt + OFF_XL + xo, ov.x, ov.y, ov.z, ov.w, nxt + OFF_BAR + 8 * B_OPEER); \
                   st_async_v4(prv + OFF_XF + xo, ov.x, ov.y, ov.z, ov.w, prv + OFF_BAR + 8 * B_OPEER); } \
        fence_async(); bar_arrive(N_O, 384); } \
        if (warp == 0) TS(15); } while (0)
#define TOK_L3() if (warp == 0 && ig == 3 && has_next) { mbar_waitu(bar + 8 * B_R1, par); \
        bulk_g2s_mc_e(sb + OFF_TILE + 3 * TILE_GRP + TILE_SBO, &g_xn[0][0] + uni(sched_l(step + 1) * (32 * DM)) + 3 * 5120, 10240, bar + 8 * (B_F2 + 3), mcmask); }
#define OX_SA (sb + OFF_PL + (lane & 7) * 128 + (((warp * 2 + ((lane >> 3) & 1)) ^ (lane & 7)) << 4))
      if (dual) {
        uint32_t vf[8], vm[4], vn[8];
        {
          float v[24];
          wg_fence(); proj<48, SSV, 0, 30, 30 + VD1, 30>(v, W, wbase); wg_commit();
          ARM();
          bar_sync(N_SISS, 384);
          wg_fence(); proj<48, SSV, 0, 30 + VD1, 40, 30>(v, W, wbase); wg_commit();
          proj<48, SSV, 0, 0, 3, 30>(v, W, wbase); wg_commit();
          wg_wait<1>(); bar_arrive(N_G3, 160);
          wg_fence(); proj<48, SSV, 0, 3, 10, 30>(v, W, wbase); wg_commit();
          proj<48, SSV, 0, 10, 13, 30>(v, W, wbase); wg_commit();
          wg_wait<1>(); REL(B_R1, 0);
          wg_fence(); proj<48, SSV, 0, 13, 20, 30>(v, W, wbase); wg_commit();
          proj<48, SSV, 0, 20, 23, 30>(v, W, wbase); wg_commit();
          wg_wait<1>(); REL(B_R1, 1);
          wg_fence(); proj<48, SSV, 0, 23, 30, 30>(v, W, wbase); wg_commit();
          wg_wait<0>(); REL(B_R1, 2);
          bar_arrive(N_VDONE, 160);
          if (warp == 0) TS(14);
#pragma unroll
          for (int j = 4; j < 8; j++) vf[j] = pack2v(v[4 + 2 * j], v[5 + 2 * j]);
          keep4(vf + 4, lane);
          vm[0] = pack2v(v[0], v[1]); vm[1] = pack2v(v[2], v[3]); vm[2] = pack2v(v[20], v[21]); vm[3] = pack2v(v[22], v[23]);
          keep4(vm, lane);
#pragma unroll
          for (int j = 0; j < 4; j++) vf[j] = pack2v(v[4 + 2 * j], v[5 + 2 * j]);
          keep4(vf, lane);
        }
        {
          float o[8];
          O_ADDR();
          bar_sync(N_PM, 224);
          wg_fence();
          MM<8>::rs<dlo(OFF_PL + 3584, 128), dhi(896, 0), 0>(o, vl[0], vl[1], vl[2], vl[3]);
          MM<8>::rs<dlo(OFF_PL + PL_SZ + 3584, 128), dhi(896, 0), 0>(o + 4, vf[0], vf[1], vf[2], vf[3]);
          MM<8>::rs<dlo(OFF_PL + 3584 + 256, 128), dhi(896, 0), 1>(o, vl[4], vl[5], vl[6], vl[7]);
          MM<8>::rs<dlo(OFF_PL + PL_SZ + 3584 + 256, 128), dhi(896, 0), 1>(o + 4, vf[4], vf[5], vf[6], vf[7]);
          MM<8>::rs<dlo(OFF_PL + 3584 + 512, 128), dhi(896, 0), 1>(o, vm[0], vm[1], vm[2], vm[3]);
          MM<8>::rs<dlo(OFF_PL + PL_SZ + 3584 + 512, 128), dhi(896, 0), 1>(o + 4, vm[0], vm[1], vm[2], vm[3]);
          wg_commit();
          const uint4 il = lds128(sb + OFF_INV + (lane & 3) * 16), jf = lds128(sb + OFF_INV + 64 + (lane & 3) * 16);
          const float i0 = rcpf(__uint_as_float(il.x) + __uint_as_float(il.y)), i1 = rcpf(__uint_as_float(il.z) + __uint_as_float(il.w));
          const float j0 = rcpf(__uint_as_float(jf.x) + __uint_as_float(jf.y)), j1 = rcpf(__uint_as_float(jf.z) + __uint_as_float(jf.w));
          wg_wait<0>();
          stsm4t(oa, pack2(o[0] * i0, o[1] * i1), pack2(o[2] * i0, o[3] * i1), pack2(o[4] * j0, o[5] * j1), pack2(o[6] * j0, o[7] * j1));
          O_READY(true);
          TOK_L3();
        }
        {
          float v[16];
          bar_sync(N_TURN, 256);
          mbar_waitu(bar + 8 * B_F2, par ^ 1);
          wg_fence(); proj<32, SSV, 1, 0, 10>(v, W, wbase); wg_commit();
          mbar_waitu(bar + 8 * (B_F2 + 1), par ^ 1);
          wg_fence(); proj<32, SSV, 1, 10, 14>(v, W, wbase); wg_commit();
          wg_wait<1>(); REL(B_R2, 0);
          wg_fence(); proj<32, SSV, 1, 14, 20>(v, W, wbase); wg_commit();
          mbar_waitu(bar + 8 * (B_F2 + 2), par ^ 1);
          wg_fence(); proj<32, SSV, 1, 20, 24>(v, W, wbase); wg_commit();
          wg_wait<1>(); REL(B_R2, 1);
          wg_fence(); proj<32, SSV, 1, 24, 30>(v, W, wbase); wg_commit();
          mbar_waitu(bar + 8 * (B_F2 + 3), par ^ 1);
          wg_fence(); proj<32, SSV, 1, 30, 34>(v, W, wbase); wg_commit();
          wg_wait<1>(); REL(B_R2, 2);
          wg_fence(); proj<32, SSV, 1, 34, 40>(v, W, wbase); wg_commit();
          wg_wait<0>(); REL(B_R2, 3);
#pragma unroll
          for (int j = 0; j < 8; j++) vn[j] = pack2v(v[2 * j], v[2 * j + 1]);
          keep4(vn, lane); keep4(vn + 4, lane);
          if (warp == 0) TS(18);
        }
        uint32_t ow[16];
        bar_sync(N_P, 256);
        fence_async();
#define PV16(i, off, va) { float o[8]; wg_fence(); \
          MM<16>::rs<dlo(OFF_PL + (off), 128), dhi(896, 0), 0>(o, va[0], va[1], va[2], va[3]); \
          MM<16>::rs<dlo(OFF_PL + (off) + 256, 128), dhi(896, 0), 1>(o, va[4], va[5], va[6], va[7]); \
          MM<16>::rs<dlo(OFF_PL + (off) + 512, 128), dhi(896, 0), 1>(o, vm[0], vm[1], vm[2], vm[3]); \
          wg_commit(); wg_wait<0>(); \
          _Pragma("unroll") for (int j = 0; j < 4; j++) ow[4 * (i) + j] = pack2v(o[2 * j], o[2 * j + 1]); \
          keep4(ow + 4 * (i), lane); }
        PV16(0, 0, vl) PV16(1, 1792, vl) PV16(2, PL_SZ, vf) PV16(3, PL_SZ + 1792, vf)
        const uint32_t s1 = OX_SA + (lane < 16 ? 3072 : 0), s2 = OX_SA + (lane < 16 ? 2048 : 1024);
        bar_sync(N_V, 128);
        stsm4t(s1, ow[0], ow[1], ow[2], ow[3]);
        stsm4t(s2, ow[4], ow[5], ow[6], ow[7]);
        stsm4t(s1 + PL_SZ, ow[8], ow[9], ow[10], ow[11]);
        stsm4t(s2 + PL_SZ, ow[12], ow[13], ow[14], ow[15]);
#pragma unroll
        for (int j = 0; j < 8; j++) vl[j] = vn[j];
      } else {
        uint32_t vm[4], vn[8];
        {
          float v[4];
          wg_fence(); proj<8, SSV, 0, 30, 40, 30>(v, W, wbase); wg_commit();
          proj<8, SSV, 0, 0, VS1, 30>(v, W, wbase); wg_commit();
          ARM();
          bar_sync(N_SISS, 384);
          wg_wait<1>(); bar_arrive(N_G3, 160);
          wg_fence(); proj<8, SSV, 0, VS1, 30, 30>(v, W, wbase); wg_commit();
          if (has_next) { mbar_waitu2(bar + 8 * B_F2, bar + 8 * (B_F2 + 1), par ^ 1); mbar_waitu(bar + 8 * (B_F2 + 2), par ^ 1); }
          wg_wait<0>();
          bar_arrive(N_VDONE, 160);
          vm[0] = pack2v(v[0], v[1]); vm[1] = pack2v(v[2], v[3]); vm[2] = pack2v(v[1], v[0]); vm[3] = pack2v(v[3], v[2]);
        }
        float v[16];
        {
          wg_fence(); proj<32, SSV, 1, 0, 30>(v, W, wbase); wg_commit();
          {
            float o[4];
            O_ADDR();
            bar_sync(N_PM, 192);
            if (warp == 0) TS(14);
            wg_fence();
            MM<8>::rs<dlo(OFF_PL + 3584, 128), dhi(896, 0), 0>(o, vl[0], vl[1], vl[2], vl[3]);
            MM<8>::rs<dlo(OFF_PL + 3584 + 256, 128), dhi(896, 0), 1>(o, vl[4], vl[5], vl[6], vl[7]);
            MM<8>::rs<dlo(OFF_PL + 3584 + 512, 128), dhi(896, 0), 1>(o, vm[0], vm[1], vm[2], vm[3]);
            wg_commit();
            const uint4 il = lds128(sb + OFF_INV + (lane & 3) * 16);
            const float i0 = rcpf(__uint_as_float(il.x) + __uint_as_float(il.y)), i1 = rcpf(__uint_as_float(il.z) + __uint_as_float(il.w));
            wg_wait<0>();
            stsm2t(oa, pack2(o[0] * i0, o[1] * i1), pack2(o[2] * i0, o[3] * i1));
            O_READY(lane < 16);
            TOK_L3();
          }
          if (has_next) {
            mbar_arrive_remote_if(lane < 3, rb0 + ((nA - 4 + lane) << 24) + OFF_BAR + 8 * B_R2);
            bar_sync(N_TURN, 256);
            mbar_waitu(bar + 8 * (B_F2 + 3), par ^ 1);
          }
          wg_fence(); proj<32, SSV, 1, 30, 40>(v, W, wbase); wg_commit();
          wg_wait<0>();
          if (has_next) REL(B_R2, 3);
#pragma unroll
          for (int j = 0; j < 8; j++) vn[j] = pack2v(v[2 * j], v[2 * j + 1]);
          keep4(vn, lane); keep4(vn + 4, lane);
          if (warp == 0) TS(18);
        }
        float o[16];
        bar_sync(N_P, 256);
        fence_async();
        wg_fence();
        MM<32>::rs<dlo(OFF_PL, 128), dhi(896, 0), 0>(o, vl[0], vl[1], vl[2], vl[3]);
        MM<32>::rs<dlo(OFF_PL + 256, 128), dhi(896, 0), 1>(o, vl[4], vl[5], vl[6], vl[7]);
        MM<32>::rs<dlo(OFF_PL + 512, 128), dhi(896, 0), 1>(o, vm[0], vm[1], vm[2], vm[3]);
        wg_commit();
        const uint32_t s1 = OX_SA + (lane < 16 ? 3072 : 0), s2 = OX_SA + (lane < 16 ? 2048 : 1024);
        wg_wait<0>();
        bar_sync(N_V, 128);
        stsm4t(s1, pack2(o[0], o[1]), pack2(o[2], o[3]), pack2(o[4], o[5]), pack2(o[6], o[7]));
        stsm4t(s2, pack2(o[8], o[9]), pack2(o[10], o[11]), pack2(o[12], o[13]), pack2(o[14], o[15]));
#pragma unroll
        for (int j = 0; j < 8; j++) vl[j] = vn[j];
      }
      bar_arrive(N_OX, 160);
      if (warp == 0) TS(16);
    }
    cluster_sync_all();
  } else {
    asm volatile("setmaxnreg.dec.sync.aligned.u32 32;");
    if (wg > 3) return;
    LANE_INIT();
    struct RsJob { uint32_t* gp; uint32_t la, mb; int n; };
    auto rs_prep = [&](int step, int s, int c) {
      RsJob j;
      const int u = s * nA + rank;
      j.gp = &g_part[0][0][0][0] + (uint32_t)((((step & 1) * 2 + c) * NCL + cl) * 2560 + u * 64 + lane);
      j.la = sb + OFF_TILE + c * LAND_F + LAND(s) + lane * 8;
      j.mb = bar + 8 * (B_RS + s);
      j.n = u >= 40 ? 0 : u >= 36 ? 3 : 1;
      asm volatile("" : "+l"(j.gp), "+r"(j.la));
      return j;
    };
    auto rs_sum = [&](RsJob j, int step) {
      if (j.n) {
        auto five = [&](uint32_t la) {
          uint2 p[5];
#pragma unroll
          for (int i = 0; i < 4; i++) p[i] = lds64(la + i * 256);
          asm volatile("{\n.reg .pred q;\nsetp.eq.s32 q, %3, 5;\nmov.u32 %0, 0;\nmov.u32 %1, 0;\n@q ld.shared.v2.b32 {%0,%1}, [%2];\n}"
                       : "=r"(p[4].x), "=r"(p[4].y) : "r"(la + 1024), "r"(nh) : "memory");
          return make_uint2(hadd2bf(hadd2bf(p[0].x, p[1].x), hadd2bf(hadd2bf(p[2].x, p[3].x), p[4].x)),
                            hadd2bf(hadd2bf(p[0].y, p[1].y), hadd2bf(hadd2bf(p[2].y, p[3].y), p[4].y)));
        };
        const uint32_t tag = ((step >> 1) & 1) ^ 1;
        mbar_waitw(j.mb, step & 1);
        uint2 t = five(j.la);
        if (j.n > 1) {
          const uint2 a = five(j.la + (nh == 5 ? 1280 : TILE_GRP - 1280)), b = five(j.la + TILE_GRP);
          t.x = hadd2bf(t.x, hadd2bf(a.x, b.x)); t.y = hadd2bf(t.y, hadd2bf(a.y, b.y));
        }
        const uint32_t t0 = (movm(t.x) & ~1u) | tag, t1 = (movm(t.y) & ~1u) | tag;
        asm volatile("st.relaxed.gpu.global.b32 [%0], %1;" :: "l"(j.gp), "r"(t0) : "memory");
        asm volatile("st.relaxed.gpu.global.b32 [%0], %1;" :: "l"(j.gp + 32), "r"(t1) : "memory");
      }
    };
    if (warp * nA + (int)rank < 40) {
#pragma unroll
      for (int e = LAG; e < LAG + 2; e++)
        if ((e >> 1) & 1) *reinterpret_cast<uint2*>(&g_part[(e & 1) * 2 + 1][cl][warp * nA + rank][lane * 2]) = make_uint2(1u, 1u);
      __threadfence();
    }
    cluster_sync_all();
    if (warp == 2 && ig >= 0) issue_tok(0, B_F2);
#pragma unroll 1
    for (int step = 0; step < NSTEP; step++) {
      const uint32_t par = step & 1;
      asm volatile("" : "+r"(lane));
      const bool dual = is_dual(step), has_next = step + 1 < NSTEP;
      {
        bar_sync(N_PX, dual ? 256 : 192);
        if (dual || warp >= 2) tok_softmax(sb, dual ? warp : warp - 2, lane);
        bar_arrive(N_P, 256);
        asm volatile("" : "+r"(lane));
        if (has_next) {
          if (step + 2 == LAG && lane < 20) asm volatile("prefetch.global.L2 [%0];" :: "l"(mem0 + (warp * 20 + lane) * 64));
          const int nw = ig >= 0 ? 3 : 4, j0 = warp < nw ? warp : 8;
          const int sh = dual ? 1 : 0;
          rs_sum(rs_prep(step, j0 >> sh, j0 & sh), step);
          if (warp == 0) TS(17);
          if (dual) rs_sum(rs_prep(step, (j0 + nw) >> 1, (j0 + nw) & 1), step);
          if (warp == 0) { bar_sync(N_C, 288); }
          mbar_arrive_remote_if(lane < nA, rb0 + (lane << 24) + OFF_BAR + 8 * B_LANDFREE);
          const uint32_t gap = dual ? POLL_GAPD : POLL_GAP;
          if (gap) { const uint32_t t0 = clock32(); while (clock32() - t0 < gap) {} }
#pragma unroll 1
          for (int j = j0; j < (dual ? 8 : 4); j += nw) {
            const int u = (j >> sh) * nA + rank, c = j & sh;
            if (u < UMAX && (c || step + 1 != NSEG)) {
              const uint32_t* gq = &g_part[0][0][0][0] + (uint32_t)((par * 2 + c) * NCL * 2560 + u * 64 + lane * 2);
              uint2 pa[NCL];
              POLL(pa, gq);
              deliver(pa, gq, u, c, step + 1 < NSEG ? c : 0, dual ? DS_DUAL : DS_SINGLE, step, j == 0, lane);
            }
            if (warp == 0 && j == 0) TS(13);
          }
          if (warp >= nw && (is_dual(step + 1) || (ig < 3 && step + 2 < NSTEP))) {
            issue_tok(is_dual(step + 1) ? sched_f(step + 1) : sched_l(step + 2), is_dual(step + 1) ? B_F1 : B_F2, B_R2, par ^ 1);
          }
          if (step + 1 == LAG && UMAX) {
            uint4 v[5];
#pragma unroll
            for (int i = 0; i < 5; i++) { const int t = warp * 160 + i * 32 + lane; v[i] = *reinterpret_cast<const uint4*>(mem0 + (t & 7) * DM + (t >> 3) * 8); }
            mbar_waitu(bar + 8 * B_LANDFREE, par);
#pragma unroll
            for (int i = 0; i < 5; i++)
              st_async_v4(sb + OFF_TILE + LAND_F + warp * TILE_GRP + (i * 32 + lane) * 16, v[i].x, v[i].y, v[i].z, v[i].w, bar + 8 * (B_F1 + warp));
          }
        }
      }
      if (warp == 3) {
        unsigned char* o0 = g_o + uni(step * (96 * 8192) + (head * 3 + t3) * (dual ? 8192 : 4096));
        bar_sync(N_OX, 160);
        fence_async();
        bulk_s2g_es(o0, sb + OFF_PL, 4096);
        if (dual) bulk_s2g_es(o0 + 4096, sb + OFF_PL + PL_SZ, 4096);
        asm volatile("cp.async.bulk.commit_group;" ::: "memory");
        asm volatile("cp.async.bulk.wait_group.read 0;" ::: "memory");
        __syncwarp();
        mbar_arrive_remote_if(lane < 2, (lane ? nxt : prv) + OFF_BAR + 8 * B_PLFREE);
        asm volatile("cp.async.bulk.wait_group 0;" ::: "memory");
        asm volatile("fence.proxy.async.global;" ::: "memory");
        __syncwarp();
        if (lane == 0) red_release(&g_f[F_O + (head * 3 + t3) / 5][step], 1u);
        __syncwarp();
      }
    }
    cluster_sync_all();
  }
}

__device__ __forceinline__ float gelu2(float x) {
  const float u = x * fmaf(x * x, 0.7978845608028654f * 0.044715f, 0.7978845608028654f);
  float t; asm("tanh.approx.f32 %0, %1;" : "=f"(t) : "f"(u));
  return fmaf(x, t, x); }

struct BParams {
  CUtensorMap wmap[5];
  CUtensorMap wo16;
  const __nv_bfloat16* x;
  __nv_bfloat16* out;
};
#define BO_O 0
#define BO_RES (6 * 8192)
#define OP_RES 63488
#define BO_STG (BO_RES + 2 * OP_RES)
#define BO_RING_OP (BO_STG + 16384)
#define OP_SLOT 12288
#define NS_OP 3
#define BO_H 81920
#define BO_W1 (BO_H + 16384)
#define BO_RING_MLP (BO_W1 + 81920)
#define BO_BAR 229376
#define BO_BOX (BO_BAR + 248)
#define BO_CARRY (BO_BAR + 512)
#define BO_STAT (BO_CARRY + 2048)
#define B_SMEM (BO_STAT + 256)
static_assert(B_SMEM <= 232448 && BO_RING_OP + NS_OP * OP_SLOT == BO_BAR && BO_RING_MLP + 3 * 16384 == BO_BAR && 2 * 83968 <= BO_RING_MLP, "smem");
enum { BB_W = 0, BB_FULL = 2, BB_TMP = BB_FULL + 3, BB_OFULL = BB_FULL + 5, BB_SFREE = BB_OFULL,
       BB_STAT = BB_SFREE + 6, BB_ZFREE, BB_DONE = BB_ZFREE + 3,
       BB_EMPTY, BB_START = BB_EMPTY, BB_USED = BB_EMPTY + 2, BB_NUM = BB_USED + 3 };
enum { NB_PP = 1, NB_H = 3, NB_END = 4, NB_END2 = 5, NB_STAGED = 6, NB_FREE = 8, NB_EARLY = 10, NB_LAST = 11 };

#define ACC32(d) ACC16(d), ACC16((d + 16))
#define R32S "{%0,%1,%2,%3,%4,%5,%6,%7,%8,%9,%10,%11,%12,%13,%14,%15,%16,%17,%18,%19,%20,%21,%22,%23,%24,%25,%26,%27,%28,%29,%30,%31}"
template <int N, bool H = false> struct BM;
#define DEF_BM(N, H, T, ACCM, RS_, I0, I1, I2, I3, I4, I5, I6)                                                                          \
  template <> struct BM<N, H> {                                                                                                      \
    template <int BO, int ACC> static __device__ __forceinline__ void rs(float* d, const uint32_t* a, uint32_t blo) {             \
      asm volatile("{\n.reg .b32 m;\n.reg .b64 b;\nadd.u32 m, %" #I4 ", %" #I5 ";\nmov.b64 b, {m, 0x40000040};\n"                 \
                   "wgmma.mma_async.sync.aligned.m64n" #N "k16.f32." T "." T " " RS_ ", {%" #I0 ",%" #I1 ",%" #I2 ",%" #I3 "}, b, %" #I6 ", 1, 1, 0;\n}" \
                   : ACCM(d) : "r"(a[0]), "r"(a[1]), "r"(a[2]), "r"(a[3]), "r"(blo), "n"(BO), "n"(ACC)); }                        \
    template <int AO, int BO, int ACC> static __device__ __forceinline__ void ss(float* d, uint32_t alo, uint32_t blo) {          \
      asm volatile("{\n.reg .b32 l, m;\n.reg .b64 a, b;\nadd.u32 l, %" #I0 ", %" #I1 ";\nadd.u32 m, %" #I2 ", %" #I3 ";\n"        \
                   "mov.b64 a, {l, 0x40000040};\nmov.b64 b, {m, 0x40000040};\n"                                                   \
                   "wgmma.mma_async.sync.aligned.m64n" #N "k16.f32." T "." T " " RS_ ", a, b, %" #I4 ", 1, 1, 1, 0;\n}"             \
                   : ACCM(d) : "r"(alo), "n"(AO), "r"(blo), "n"(BO), "n"(ACC)); }                                                 \
  };
DEF_BM(32, false, "bf16", ACC16, R16S, 16, 17, 18, 19, 20, 21, 22)
DEF_BM(64, false, "bf16", ACC32, R32S, 32, 33, 34, 35, 36, 37, 38)
DEF_BM(32, true, "f16", ACC16, R16S, 16, 17, 18, 19, 20, 21, 22)
DEF_BM(64, true, "f16", ACC32, R32S, 32, 33, 34, 35, 36, 37, 38)
#define DESC_LO(off) (((SMEM0 + (off)) >> 4) | (1u << 16))

__device__ __forceinline__ uint32_t ld_relaxed(const uint32_t* p) { uint32_t v; asm volatile("ld.relaxed.gpu.global.b32 %0, [%1];" : "=r"(v) : "l"(p) : "memory"); return v; }
__device__ __forceinline__ int fmask(int r) { return (r < NSEG) | ((r >= LAG && r < NSTEP) << 1); }
__device__ __forceinline__ int bmask(int r) { return (r <= NSEG) | ((r >= LAG) << 1); }
__device__ __forceinline__ uint32_t rtarget(int mask) { return mask == 3 ? 64 : 32; }
__device__ __forceinline__ void warp_signal(uint32_t* p, int lane) {
  __syncwarp();
  asm volatile("{\n.reg .pred q;\nsetp.eq.u32 q, %1, 0;\n@q red.release.gpu.global.add.u32 [%0], 1;\n}" :: "l"(p), "r"(lane) : "memory");
}
__device__ __forceinline__ uint32_t pack2h(float lo, float hi) { uint32_t r; asm("cvt.rn.f16x2.f32 %0, %1, %2;" : "=r"(r) : "f"(hi), "f"(lo)); return r; }
template <bool H> __device__ __forceinline__ uint32_t pk(float lo, float hi) { return H ? pack2h(lo, hi) : pack2(lo, hi); }
template <int N, bool H> __device__ __forceinline__ void stage_out(const float* d, uint32_t dst, int warp, int lane) {
  const uint32_t sa = dst + ((lane >> 4) * 8 + (lane & 7)) * 128 + (((2 * warp + ((lane >> 3) & 1)) ^ (lane & 7)) << 4);
#pragma unroll
  for (int m = 0; m < N / 16; m++)
    stsm4t(sa + m * 2048, pk<H>(d[8 * m], d[8 * m + 1]), pk<H>(d[8 * m + 2], d[8 * m + 3]), pk<H>(d[8 * m + 4], d[8 * m + 5]), pk<H>(d[8 * m + 6], d[8 * m + 7]));
}
template <int N> __device__ __forceinline__ void acc_live(float* d) {
#pragma unroll
  for (int i = 0; i < N / 2; i++) asm volatile("" : "+f"(d[i]) :: "memory");
}
struct Ring {
  uint32_t sl, ph;
  template <int NS> __device__ __forceinline__ void step() { if (++sl == NS) { sl = 0; ph ^= 1; } }
};

#define LOCKSTEP 0
#define KOFF(x) (((x) >> 2) * (N * 8) + ((x) & 3) * 2)
template <int N, int P>
__device__ __forceinline__ void op_pass(const uint32_t* W, uint32_t bar, uint32_t alo, uint32_t blo, uint32_t xlo, bool x2, Ring& rg, int wg, int warp, int lane, int r) {
  float acc[N / 2];
  const uint32_t tlo = DESC_LO(BO_RING_OP) + uni(rg.sl) * (OP_SLOT / 16);
  if (P == 0) mbar_waitu(bar + 8 * BB_OFULL, r & 1);
  CTS(5 * P);
  if (!LOCKSTEP || P > 1 || P == wg) bar_sync(NB_PP + wg, 256);
  wg_fence();
#define OP_R(x) BM<N>::template rs<KOFF(4 * (x >> 1) + (x & 1)), (x != 0)>(acc, W + 32 * P + 4 * x, blo);
#define OP_S(x) BM<N>::template ss<(6 * P + x) * 128, KOFF(4 * (x >> 1) + 2 + (x & 1)), 1>(acc, alo, blo);
#define OP_T(x) BM<N>::template ss<x * 128, KOFF(14 + x), 1>(acc, tlo, blo);
  OP_R(0) OP_S(0) OP_R(1) OP_S(1) OP_R(2) OP_S(2) OP_R(3) OP_S(3)
  if (P == 0) mbar_waitu(bar + 8 * (BB_OFULL + 1), r & 1);
  if (P == 4) wg_commit();
  OP_R(4) OP_S(4) OP_R(5) OP_S(5)
  if (P == 1 && x2) BM<N>::template ss<30 * 128, KOFF(20), 1>(acc, alo, xlo);
  if (P == 4) { wg_commit(); wg_wait<1>(); bar_arrive(NB_EARLY, 288); CTS(21); wg_fence(); }
  mbar_waitu(bar + 8 * (BB_FULL + rg.sl), rg.ph);
  OP_R(6) OP_T(0) OP_R(7) OP_T(1)
  if (P == 0) mbar_waitu(bar + 8 * (BB_OFULL + 2), r & 1);
  OP_T(2) OP_T(3)
  if (P == 0) BM<N>::template rs<KOFF(20), 1>(acc, W + 160, xlo);
  OP_T(4) OP_T(5)
  wg_commit();
  if (!LOCKSTEP || P) bar_arrive(NB_PP + 1 - wg, 256);
  CTS(5 * P + 2);
  bar_sync(NB_FREE + wg, 160);
  wg_wait<0>();
  acc_live<N>(acc);
  if (P == 4) bar_arrive(NB_LAST, 288);
  mbar_arrive_if(lane == 0, bar + 8 * (BB_USED + rg.sl));
  CTS(5 * P + 3);
  stage_out<N, false>(acc, SMEM0 + BO_STG + wg * 8192, warp, lane);
  bar_arrive(NB_STAGED + wg, 160);
  CTS(5 * P + 4);
  rg.step<NS_OP>(); rg.step<NS_OP>();
}
template <int N>
__device__ __forceinline__ void op_round(const uint32_t* W, uint32_t bar, uint32_t alo, uint32_t blo, uint32_t xlo, bool x2, Ring& rg, int wg, int warp, int lane, int r) {
  op_pass<N, 0>(W, bar, alo, blo, xlo, x2, rg, wg, warp, lane, r);
  op_pass<N, 1>(W, bar, alo, blo, xlo, x2, rg, wg, warp, lane, r);
  op_pass<N, 2>(W, bar, alo, blo, xlo, x2, rg, wg, warp, lane, r);
  op_pass<N, 3>(W, bar, alo, blo, xlo, x2, rg, wg, warp, lane, r);
  op_pass<N, 4>(W, bar, alo, blo, xlo, x2, rg, wg, warp, lane, r);
}
__device__ __forceinline__ void carry_in(uint32_t sb, int wg, int warp, int lane) {
  const int row = (lane >> 1) & 3;
  if (lane < 16) {
    const uint4 v = lds128(sb + BO_CARRY + (wg * 4 + warp) * 256 + lane * 16);
    sts128(sb + BO_H + wg * 8192 + (lane >> 3) * 4096 + row * 128 + (((2 * warp + (lane & 1)) ^ row) << 4), v.x, v.y, v.z, v.w);
  }
  __syncwarp();
}
#define STAGGER 0
template <int N, int Z>
__device__ __forceinline__ void p1_pair(float* acc, const uint32_t* W, uint32_t bar, uint32_t alo, uint32_t blo, int lane, int r) {
  mbar_waitu(bar + 8 * (BB_FULL + Z), r & 1);
  CTS(40 + Z);
  wg_fence();
#define P1_B(k) \
  BM<N, true>::template rs<(2 * Z % 3) * 1024 + k * 512, (2 * Z + k != 0)>(acc, W + 16 * Z + 8 * k, blo); \
  BM<N, true>::template ss<BO_W1 / 16 + (2 * Z + k) * 512, (2 * Z % 3) * 1024 + k * 512 + 4, 1>(acc, alo, blo); \
  BM<N, true>::template rs<(2 * Z % 3) * 1024 + k * 512 + 2, 1>(acc, W + 16 * Z + 8 * k + 4, blo); \
  BM<N, true>::template ss<BO_W1 / 16 + (2 * Z + k) * 512 + 128, (2 * Z % 3) * 1024 + k * 512 + 6, 1>(acc, alo, blo);
  P1_B(0)
  if (Z == 1 || Z == 2) { wg_commit(); wg_wait<1>(); mbar_arrive_if(lane == 0, bar + 8 * (BB_EMPTY + Z - 1)); wg_fence(); }
  P1_B(1)
  wg_commit();
}
template <int N>
__device__ __forceinline__ void phase1(const uint32_t* W, uint32_t sb, uint32_t alo, int half, int wg, int warp, int lane, int off, int r) {
  float acc[N / 2];
  const uint32_t bar = sb + BO_BAR, blo = DESC_LO(BO_RING_MLP) + half * 256;
  CTS(30);
  p1_pair<N, 0>(acc, W, bar, alo, blo, lane, r);
  p1_pair<N, 1>(acc, W, bar, alo, blo, lane, r);
  p1_pair<N, 2>(acc, W, bar, alo, blo, lane, r);
  mbar_waitu(bar + 8 * (BB_SFREE + 4 + wg), (r + 1) & 1);
  carry_in(sb, wg, warp, lane);
  if (STAGGER && wg) bar_sync(NB_PP + 1, 256);
  p1_pair<N, 3>(acc, W, bar, alo, blo, lane, r);
  p1_pair<N, 4>(acc, W, bar, alo, blo, lane, r);
  if (STAGGER && !wg) bar_arrive(NB_PP + 1, 256);
  const int c = (lane >> 3) & 1, i0 = (lane >> 4) * 8 + (lane & 7) + off;
  uint32_t a0 = sb + BO_H + wg * 8192 + half * 4096 + i0 * 128 + (((2 * warp + c) ^ (i0 & 7)) << 4);
  uint32_t a1 = i0 >= 16 ? sb + BO_CARRY + (wg * 4 + warp) * 256 + half * 128 + (i0 - 16) * 32 + c * 16 : a0 + 2048, a3 = a1 + (i0 >= 16 ? 128 : 4096);
  asm volatile("" : "+r"(a0), "+r"(a1), "+r"(a3));
  mbar_waitu(bar + 8 * BB_STAT, r & 1);
  const uint32_t sa = sb + BO_STAT + half * 128 + (lane & 3) * 32;
  uint4 t[2] = {lds128(sa), lds128(sa + 16)};
  wg_wait<0>();
  acc_live<N>(acc);
  CTS(32);
#pragma unroll
  for (int m = 0; m < N / 16; m++) {
    const float s0 = __uint_as_float(t[m & 1].x), s1 = __uint_as_float(t[m & 1].y), s2 = __uint_as_float(t[m & 1].z), s3 = __uint_as_float(t[m & 1].w);
    float* d = acc + 8 * m;
    d[0] *= s0; d[1] *= s1; d[2] *= s0; d[3] *= s1; d[4] *= s2; d[5] *= s3; d[6] *= s2; d[7] *= s3;
    if (m + 2 < N / 16) t[m & 1] = lds128(sa + 128 + m * 16);
#pragma unroll
    for (int j = 0; j < 8; j++) d[j] = gelu2(d[j]);
  }
#pragma unroll
  for (int m = 0; m < N / 16; m++)
    stsm4t(m == 1 ? a1 : m == 3 ? a3 : a0 + m * 2048, pack2(acc[8 * m], acc[8 * m + 1]), pack2(acc[8 * m + 2], acc[8 * m + 3]), pack2(acc[8 * m + 4], acc[8 * m + 5]), pack2(acc[8 * m + 6], acc[8 * m + 7]));
}
template <int N, int P>
__device__ __forceinline__ void p2_pass(const uint32_t* W, uint32_t bar, uint32_t alo, uint32_t blo, int wg, int warp, int lane, int r) {
  float acc[N / 2];
  CTS(5 * P);
  if (P || wg) bar_sync(NB_PP + wg, 256);
  wg_fence();
  BM<N>::template rs<0, 0>(acc, W + 80 + 16 * P, blo);      BM<N>::template ss<P * 1024, 512, 1>(acc, alo, blo);
  BM<N>::template rs<2, 1>(acc, W + 84 + 16 * P, blo);      BM<N>::template ss<P * 1024 + 128, 514, 1>(acc, alo, blo);
  BM<N>::template rs<4, 1>(acc, W + 88 + 16 * P, blo);      BM<N>::template ss<P * 1024 + 512, 516, 1>(acc, alo, blo);
  BM<N>::template rs<6, 1>(acc, W + 92 + 16 * P, blo);      BM<N>::template ss<P * 1024 + 640, 518, 1>(acc, alo, blo);
  wg_commit();
  if (P < 4 || !wg) bar_arrive(NB_PP + 1 - wg, 256);
  CTS(5 * P + 2);
  if (P == 2 || P == 3) mbar_waitu(bar + 8 * (BB_SFREE + 2 * (P - 2) + wg), r & 1);
  wg_wait<0>();
  acc_live<N>(acc);
  if (P == 4) bar_sync(NB_H, 256);
  CTS(5 * P + 3);
  stage_out<N, true>(acc, SMEM0 + (P == 4 ? BO_H : BO_RING_MLP + (2 - (P & 1)) * 16384) + wg * 8192, warp, lane);
  bar_arrive(NB_STAGED + (P == 4 ? 4 : 2 * (P & 1)) + wg, 160);
  CTS(5 * P + 4);
}
template <int N>
__device__ __forceinline__ void phase2(const uint32_t* W, uint32_t bar, uint32_t alo, uint32_t blo, int wg, int warp, int lane, int r) {
  p2_pass<N, 0>(W, bar, alo, blo, wg, warp, lane, r);
  p2_pass<N, 1>(W, bar, alo, blo, wg, warp, lane, r);
  p2_pass<N, 2>(W, bar, alo, blo, wg, warp, lane, r);
  p2_pass<N, 3>(W, bar, alo, blo, wg, warp, lane, r);
  p2_pass<N, 4>(W, bar, alo, blo, wg, warp, lane, r);
}

__device__ __forceinline__ void ldg4(uint32_t* v, const void* p) {
  asm volatile("ld.relaxed.gpu.global.v4.u32 {%0,%1,%2,%3}, [%4];" : "=r"(v[0]), "=r"(v[1]), "=r"(v[2]), "=r"(v[3]) : "l"(p) : "memory"); }
__device__ __forceinline__ void stg4(void* p, const uint32_t* v) {
  asm volatile("st.global.v4.u32 [%0], {%1,%2,%3,%4};" :: "l"(p), "r"(v[0]), "r"(v[1]), "r"(v[2]), "r"(v[3]) : "memory"); }
struct RowPtr {
  unsigned char *p, *q, *t;
  __device__ __forceinline__ void ld(uint32_t* v, int o) const {
    ldg4(v, p + o); ldg4(v + 4, q + o);
    asm volatile("ld.relaxed.gpu.global.v2.u32 {%0,%1}, [%2];" : "=r"(v[8]), "=r"(v[9]) : "l"(t + o) : "memory");
  }
  __device__ __forceinline__ void st(const uint32_t* w, int o) const {
    stg4(p + o, w); stg4(q + o, w + 4);
    asm volatile("st.global.v2.u32 [%0], {%1,%2};" :: "l"(t + o), "r"(w[8]), "r"(w[9]) : "memory");
  }
};
__device__ __forceinline__ RowPtr row_img(int r, int n, int lane) {
  unsigned char* b = &g_acc[0][r % RD][n * 128];
  unsigned char* p = b + (uint32_t)((lane >> 3) * 8192 + (((lane ^ n) & 7) << 4));
  return {p, p + 32768, b + (uint32_t)(65536 + (lane >> 4) * 8192 + ((((lane >> 1) ^ n) & 7) << 4) + (lane & 1) * 8)};
}
__device__ __forceinline__ RowPtr row_ext(const void* lin, bool xn, int layer, int tok, int lane) {
  unsigned char* b = xn ? reinterpret_cast<unsigned char*>(&g_xn[layer][0]) + (uint32_t)((tok >> 5) * 40960 + ((tok >> 3) & 3) * 2560 + (tok & 7) * 16)
                        : (unsigned char*)lin + (uint32_t)(tok * 1280);
  return {b + (uint32_t)(xn ? lane * 128 + (lane >= 20 ? 7680 : 0) : lane * 16),
          b + (uint32_t)(xn ? lane * 128 + 4096 + 7680 + (lane >= 8 ? 7680 : 0) + (lane >= 28 ? 7680 : 0) : lane * 16 + 512),
          b + (uint32_t)(xn ? (lane >> 1) * 128 + (lane & 1) * 8 + 8192 + 3 * 7680 : lane * 8 + 1024)};
}
__device__ __forceinline__ float2 h2f(uint32_t w) {
  float2 f; asm("{\n.reg .f16 l, h;\nmov.b32 {l, h}, %2;\ncvt.f32.f16 %0, l;\ncvt.f32.f16 %1, h;\n}" : "=f"(f.x), "=f"(f.y) : "r"(w)); return f; }
__device__ __forceinline__ float rsq(float x) { float y; asm("rsqrt.approx.ftz.f32 %0, %1;" : "=f"(y) : "f"(x)); return y; }
__device__ __forceinline__ void red_if(uint32_t v, const void* a) {
  asm volatile("{\n.reg .pred q;\nsetp.ne.u32 q, %1, 0;\n@q red.relaxed.gpu.global.add.u32 [%0], %1;\n}" :: "l"(a), "r"(v) : "memory"); }
__device__ __forceinline__ uint32_t dep0(uint32_t w, int lane) { uint32_t z; asm volatile("shr.b32 %0, %1, %2;" : "=r"(z) : "r"(w), "r"(lane + 32)); return z; }
__device__ __forceinline__ int lane_of(uint32_t w) {
  int lane; asm volatile("{\n.reg .u32 t;\nmov.u32 t, %%laneid;\nshr.u32 %0, %1, 20;\nadd.u32 %0, %0, t;\n}" : "=r"(lane) : "r"(w)); return lane; }
#define BUF (RD * TILE_B)
__device__ __forceinline__ int await(uint32_t v, const uint32_t* p, uint32_t target, bool lazy) {
  int n = 0;
  while (!__all_sync(~0u, v >= target)) {
    if (lazy) __nanosleep(200);
    if (++n > SPIN_LIMIT) FAIL();
    v = ld_relaxed(p);
  }
  asm volatile("fence.acquire.gpu;" ::: "memory");
  return lane_of(v);
}
template <int W> __device__ __forceinline__ void sum2(float& s, float& q, int lane) {
  const bool up = lane & (W / 2);
  float e = (up ? q : s) + __shfl_xor_sync(~0u, up ? s : q, W / 2);
#pragma unroll
  for (int o = W / 4; o; o >>= 1) e += __shfl_xor_sync(~0u, e, o);
  const float f = __shfl_xor_sync(~0u, e, W / 2);
  s = up ? f : e; q = up ? e : f;
}
template <int TYPE>
__device__ __forceinline__ void rrow(int r, int row, int tok, int lane, const uint32_t* go, int role, const __nv_bfloat16* x) {
  const int half = TYPE ? 0 : row >> 5;
  float v[20];
  float2 st = make_float2(1.f, 0.f);
  {
    uint32_t a[10], c[10], u[10], sh = 16;
    if (TYPE == 2) row_img(r + RD - ((row & 31) < 2), (row & 32) + ((row - 2) & 31), lane).ld(u, 4 * BUF);
    else row_ext(x, half, 1, tok, lane).ld(u, 0);
    if (TYPE == 2 || (TYPE == 0 && half))
      asm volatile("ld.relaxed.gpu.global.v2.f32 {%0,%1}, [%2];" : "=f"(st.x), "=f"(st.y) : "l"(g_stat + tok) : "memory");
    RowPtr ap = row_img(r, row, lane);
    const uint32_t g0 = TYPE != 3 ? ld_relaxed(go) : 0;
    if (TYPE == 2) {
      ap.ld(c, 2 * BUF);
      uint32_t z = dep0(c[9], lane);
#pragma unroll
      for (int i = 0; i < 10; i++) {
        const float2 g = h2f(u[i] | z), h = h2f(c[i] | z);
        v[2 * i] = fmaf(h.x, 0.5f, g.x * st.x); v[2 * i + 1] = fmaf(h.y, 0.5f, g.y * st.x);
        if (i & 1) z = dep0(__float_as_uint(v[2 * i]) | __float_as_uint(v[2 * i + 1]), lane);
      }
    }
    if (TYPE != 3) {
      asm volatile("" : "+l"(ap.p), "+l"(ap.t));
      ap.q = ap.p + 32768;
      lane = await(g0, go, NOP * NW12 * NW34, false); BTS2(r, 8 + 2 * TYPE); RTS(0);
      ap.ld(a, TYPE ? 3 * BUF : 0);
    }
    if (TYPE == 0) {
      ap.ld(c, BUF);
      const uint32_t one = 0x3f803f80u | dep0(c[9], lane);
#pragma unroll
      for (int i = 0; i < 10; i++) asm volatile("fma.rn.bf16x2 %0, %0, %1, %2;" : "+r"(a[i]) : "r"(one), "r"(c[i]));
      sh |= dep0(a[9], lane);
    }
    const float k = TYPE == 2 ? __uint_as_float(0x3f000000u | dep0(a[9], lane)) : 0.f;
#pragma unroll
    for (int i = 0; i < 10; i++) {
      if (TYPE == 2) { const float2 h = h2f(a[i]); v[2 * i] = fmaf(h.x, k, v[2 * i]); v[2 * i + 1] = fmaf(h.y, k, v[2 * i + 1]); continue; }
      float p = __uint_as_float(u[i] << sh), q = __uint_as_float(u[i] & (0xffffu << sh));
      if (TYPE == 0) { p = fmaf(p, st.x, bf_lo(a[i])); q = fmaf(q, st.x, bf_hi(a[i])); }
      v[2 * i] = p; v[2 * i + 1] = q;
    }
  }
  RTSD(1, v[19]);
  float s = 0.f, q = 0.f;
#pragma unroll
  for (int i = 0; i < 5; i++) {
    s += (v[4 * i] + v[4 * i + 1]) + (v[4 * i + 2] + v[4 * i + 3]);
    q += fmaf(v[4 * i], v[4 * i], v[4 * i + 1] * v[4 * i + 1]) + fmaf(v[4 * i + 2], v[4 * i + 2], v[4 * i + 3] * v[4 * i + 3]);
  }
  sum2<32>(s, q, lane);
  const float mean = s * (1.f / DM), var = fmaxf(q * (1.f / DM) - mean * mean, 0.f), rs = rsq(var + 1e-5f), k = TYPE ? rs : 2.f * rs, mr = -mean * k;
  RTSD(2, rs);
  uint32_t w[10];
#pragma unroll
  for (int i = 0; i < 10; i++) w[i] = pk<TYPE == 0>(fmaf(v[2 * i], k, mr), fmaf(v[2 * i + 1], k, mr));
  if (TYPE) row_ext(nullptr, true, TYPE == 2, tok, lane).st(w, 0);
  else {
    row_img(r, row, lane).st(w, 4 * BUF);
    row_img(r + ((row & 31) >= 30), (row & 32) + ((row + 2) & 31), lane).st(w, 2 * BUF);
    if (lane == 1) g_st2[0][r % RD][row] = (__float_as_uint(0.5f * rsq(fmaf(var * rs, rs, 1e-5f))) & ~127u) | (r + 1);
  }
  if (TYPE != 3 && lane == 0) g_stat[tok] = make_float2((var + 1e-5f) * rs * (TYPE ? 1.f : 0.5f), mean + st.y);
}
__device__ __forceinline__ void r2rows(int r, int row, int lane) {
  const int n = row + (lane >> 4);
  const unsigned char* ap = &g_acc[2][r % RD][0] + (uint32_t)(n * 128 + ((lane >> 3) & 1) * 8192 + (((lane ^ n) & 7) << 4));
  uint32_t a[20];
#pragma unroll
  for (int i = 0; i < 5; i++) ldg4(a + 4 * i, ap + i * 16384);
  const uint32_t z = dep0(a[19], lane);
  float s = 0.f, q = 0.f, q2 = 0.f;
#pragma unroll
  for (int i = 0; i < 20; i++) { const float2 h = h2f(a[i] | z); s += h.x + h.y; q = fmaf(h.x, h.x, q); q2 = fmaf(h.y, h.y, q2); }
  q += q2;
  sum2<16>(s, q, lane);
  const float mean = s * (0.5f / DM), rs = rsq(fmaxf(q * (0.25f / DM) - mean * mean, 0.f) + 1e-5f);
  if ((lane & 15) == 0) asm volatile("st.relaxed.gpu.global.u32 [%0], %1;" :: "l"(&g_st2[1][r % RD][n]), "r"((__float_as_uint(0.5f * rs) & ~127u) | (r + 1)) : "memory");
}
__device__ __forceinline__ void r3rows(int r, int row, int tok, int lane, __nv_bfloat16* out) {
  const int n = row + (lane >> 4), m = 32 + ((n - 2) & 31);
  const unsigned char* ap = &g_acc[0][r % RD][0] + (uint32_t)(n * 128 + ((lane >> 3) & 1) * 8192 + (((lane ^ n) & 7) << 4));
  const unsigned char* zp = &g_acc[4][(r + RD - (row == 32)) % RD][0] + (uint32_t)(m * 128 + ((lane >> 3) & 1) * 8192 + (((lane ^ m) & 7) << 4));
  unsigned char* op = reinterpret_cast<unsigned char*>(out) + (uint32_t)((tok + (lane >> 4)) * 1280 + (lane & 15) * 16);
  float2 st;
  asm volatile("ld.relaxed.gpu.global.v2.f32 {%0,%1}, [%2];" : "=f"(st.x), "=f"(st.y) : "l"(g_stat + tok + (lane >> 4)) : "memory");
#pragma unroll 1
  for (int i0 = 0; i0 < 3; i0++) {
    uint32_t a[8], c[8], u[8];
#pragma unroll
    for (int i = 0; i < 2; i++) { ldg4(a + 4 * i, ap + 3 * BUF + i * 16384); ldg4(c + 4 * i, ap + 2 * BUF + i * 16384); ldg4(u + 4 * i, zp + i * 16384); }
    uint32_t z = dep0(u[7], lane);
#pragma unroll
    for (int i = 0; i < 8; i++) {
      const float2 h = h2f(a[i] | z), e = h2f(c[i] | z), g = h2f(u[i] | z);
      a[i] = pack2(fmaf(h.x + e.x, 0.5f, fmaf(g.x, st.x, st.y)), fmaf(h.y + e.y, 0.5f, fmaf(g.y, st.x, st.y)));
      if (i & 1) z = dep0(a[i], lane);
    }
    if (i0 < 2) stg4(op, a);
    stg4(op + 256, a + 4);
    ap += 32768 >> i0; zp += 32768 >> i0; op += 512 >> i0;
  }
}
template <int TYPE>
__device__ __forceinline__ void rloop(int row, int cp, int role, const __nv_bfloat16* x, __nv_bfloat16* out) {
  constexpr int ST = TYPE == 4 ? 2 : TYPE;
  const int r0 = row & 32 ? LAG : 0;
  uint32_t v = 0;
#pragma unroll 1
  for (int r = r0; r < r0 + NSEG + (TYPE > 0); r++) {
    const int tok = (r - r0) * 32 + (row & 31) - (TYPE ? 2 : 0);
    const bool valid = TYPE == 0 || (unsigned)tok < S_LEN;
    const uint32_t* go = &g_f[F_R1 + 4 * ST + cp][r];
    const uint32_t* first = TYPE == 2 ? &g_f[F_R2 + cp][r] : TYPE ? go : (const uint32_t*)&g_xready[NSEG + r - r0][0];
    if constexpr (TYPE == 1 || TYPE == 4) {
      const int lane = await(v, go, NOP * NW12 * NW34, false);
      BTS2(r, 8 + 2 * ST); RTS(0);
      if (TYPE == 1) { r2rows(r, row, lane); BTS2(r, 11); continue; }
      if (valid) r3rows(r, row, tok, lane, out);
    } else {
      if (TYPE || row >= 32) await(v, first, TYPE ? NOP * NW12 * NW34 : 32, true);
      if (valid) rrow<TYPE>(r, row, tok, lane_of(r), go, role, x);
    }
    const int lane = lane_of(r);
    const void* f = lane ? (const void*)&g_xready[NSEG + (tok >> 5)][0] : (const void*)&g_f[TYPE ? F_DONE : F_Z][r];
    asm volatile("" : "+l"(f));
    __syncwarp();
    RTS(3);
    v = ld_relaxed(first + (TYPE ? 1 : 8));
    asm volatile("fence.release.gpu;" ::: "memory");
    RTS(4);
    red_if(lane == 0 || (TYPE == 2 && lane == 1 && valid) ? (TYPE & 5 ? 2 : 1) : 0, f);
    RTS(5);
    RTS_OUT();
    BTS2(r, 9 + 2 * ST);
  }
}

#define SINGLE_OP 3
#define SINGLE_W 0
#define W_DELAY 0
#define BULK_ADD(T, dst, src, len) asm volatile("{\n.reg .pred e;\nelect.sync _|e, 0xffffffff;\n@e cp.reduce.async.bulk.global.shared::cta.bulk_group.add.noftz." T " [%0], [%1], %2;\n}" \
                                               :: "l"(dst), "r"(src), "r"(len) : "memory")
#define COMMIT() asm volatile("cp.async.bulk.commit_group;" ::: "memory")
#define DRAINED(n) do { asm volatile("cp.async.bulk.wait_group.read " #n ";" ::: "memory"); __syncwarp(); } while (0)
#define WRITTEN() do { asm volatile("cp.async.bulk.wait_group 0;\nfence.proxy.async.global;" ::: "memory"); __syncwarp(); } while (0)
__device__ __forceinline__ void wait_flags(const uint32_t* p, uint32_t target) {
  int n = 0;
  while (!__all_sync(~0u, ld_relaxed(p) >= target)) { if (++n > SPIN_LIMIT) FAIL(); }
  asm volatile("fence.acquire.gpu;" ::: "memory");
  asm volatile("fence.proxy.async.global;" ::: "memory");
}
__global__ void __launch_bounds__(512, 1) bworker_kernel(const __grid_constant__ BParams P) {
  extern __shared__ __align__(1024) unsigned char smem_raw[];
  const uint32_t sb = SMEM0, bar = sb + BO_BAR;
  const int wg = __shfl_sync(~0u, threadIdx.x >> 7, 0), warp = __shfl_sync(~0u, (threadIdx.x >> 5) & 3, 0);
  if (threadIdx.x == 0) {
    if (smem_u32(smem_raw) != SMEM0) FAIL();
    uint32_t smid; asm volatile("mov.u32 %0, %%smid;" : "=r"(smid));
    const uint32_t nb = ld_relaxed(&g_tpc[(smid >> 1) & 127]);
    const bool single = nb > 1, far = nb == 0 && (smid < 64 || smid >= 124);
    int kind = far || (single && atomicAdd(&g_f[F_MISC][35], 1u) < SINGLE_OP) ? 0 : single ? 1 + SINGLE_W : 1;
    int rc = single || (smid >> 1) == 16 || (smid >> 1) == 63 ? 1 : far ? 2 : 0;
    uint32_t i, o;
    while ((i = atomicAdd(&g_f[F_MISC][32 + kind], 1u)) >= (kind == 0 ? NOP : kind == 1 ? NW12 : NW34)) kind = (kind + 1) % 3;
    while ((o = atomicAdd(&g_f[F_MISC][36 + rc], 1u)) >= (rc == 0 ? 16 : rc == 1 ? 8 : 12)) rc = (rc + 1) % 3;
    sts64(sb + BO_BOX, i + (kind == 0 ? 0 : kind == 1 ? NOP : NOP + NW12), o + (rc ? 8 + 8 * rc : 0));
    for (int k = 0; k < BB_NUM; k++) mbar_init(bar + 8 * k, k >= BB_USED ? 4 : k >= BB_EMPTY ? 8 : k >= BB_ZFREE && kind ? 2 : 1);
    asm volatile("fence.mbarrier_init.release.cluster;" ::: "memory");
  }
  if (threadIdx.x < 128) sts128(sb + BO_CARRY + threadIdx.x * 16, 0u, 0u, 0u, 0u);
  fence_async();
  __syncthreads();
  const int role = uni(lds32(sb + BO_BOX));
  const bool op = role < NOP, w12 = role < NOP + NW12;
  const int j = op ? role : w12 ? role - NOP : role - NOP - NW12;
  const int rot = op ? (j ? 2 * ((j + 1) % 5) : 0) : 2 * (j % 5);
  if (wg == 3) {
    asm volatile("setmaxnreg.dec.sync.aligned.u32 24;");
    LANE_INIT();
    if (warp < 2) {
      auto announce = [&](int r) {
        const uint32_t* f = &g_f[(op ? F_R1 : w12 ? F_R2 : F_R3) + (lane & 3)][r];
        asm volatile("" : "+l"(f));
        if (warp == 0) { mbar_arrive_if(lane == 0, bar + 8 * BB_DONE); return; }
        mbar_waitw(bar + 8 * BB_DONE, r & 1);
        PTS(60);
        asm volatile("fence.release.gpu;" ::: "memory");
        red_if(lane >= 4 ? 0 : op ? NW12 * NW34 : w12 ? NOP * NW34 : NOP * NW12, f);
        PTS(61);
        BTS(r, 4);
      };
      if (op) {
        int mt = rot + warp;
        bar_arrive(NB_FREE + warp, 160);
#pragma unroll 1
        for (int r = 0; r < NSTEP; r++) {
          const uint32_t len = fmask(r) == 3 ? 8192 : 4096;
          unsigned char* acc = &g_acc[j & 1][r % RD][fmask(r) == 2 ? 4096 : 0];
#pragma unroll 1
          for (int p = 0; p < 5; p++) {
            bar_sync(NB_STAGED + warp, 160);
            PTS(50 + 2 * p + warp);
            fence_async();
            BULK_ADD("bf16", acc + mt * 8192, sb + BO_STG + warp * 8192, len);
            COMMIT();
            PTS(64 + 50 + 2 * p + warp);
            mt = mt >= 8 ? mt - 8 : mt + 2;
            DRAINED(0);
            bar_arrive(NB_FREE + warp, 160);
          }
          WRITTEN();
          announce(r);
        }
      } else {
#pragma unroll 1
        for (int r = 0; r < NR; r++) {
          const uint32_t len = bmask(r) == 3 ? 8192 : 4096;
          unsigned char* acc = &g_acc[w12 ? 2 : 3][r % RD][bmask(r) == 2 ? 4096 : 0];
          int mt = rot + warp;
#pragma unroll 1
          for (int p = 0; p < 5; p++) {
            bar_sync(NB_STAGED + (p == 4 ? 4 : 2 * (p & 1)) + warp, 160);
            PTS(50 + 2 * p + warp);
            fence_async();
            BULK_ADD("f16", acc + mt * 8192, sb + (p == 4 ? BO_H : BO_RING_MLP + (2 - (p & 1)) * 16384) + warp * 8192, len);
            COMMIT();
            PTS(64 + 50 + 2 * p + warp);
            mt = mt >= 8 ? mt - 8 : mt + 2;
            if (p == 4) break;
            DRAINED(1);
            mbar_arrive_if(lane == 0, bar + 8 * (p == 1 || p == 2 ? BB_SFREE + 2 * (p - 1) + warp : BB_ZFREE + (p >> 1)));
            if (p == 3) { DRAINED(0); mbar_arrive_if(lane == 0, bar + 8 * (BB_ZFREE + 2)); }
          }
          WRITTEN();
          mbar_arrive_if(lane == 0, bar + 8 * (BB_SFREE + 4 + warp));
          announce(r);
        }
      }
    } else {
      if (op && warp == 2) {
        unsigned char* wt = g_wt + j * (10 * OP_SLOT);
#pragma unroll 1
        for (int m0 = 0; m0 < 10; m0 += 3) {
          const int nu = m0 < 9 ? 9 : 3;
          mbar_expect_if(lane == 0, bar + 8 * BB_TMP, nu * 4096);
#pragma unroll 1
          for (int k = 0; k < nu; k++) tma2d_e(sb + BO_RING_OP + k * 4096, &P.wmap[0], (m0 + k / 3) * 64, 320 * j + 224 + 32 * (k % 3), bar + 8 * BB_TMP);
          mbar_waitw(bar + 8 * BB_TMP, m0 & 1);
          bulk_s2g_e(wt + m0 * OP_SLOT, sb + BO_RING_OP, nu * 4096);
          COMMIT();
          WRITTEN();
        }
        asm volatile("fence.acq_rel.gpu;" ::: "memory");
        int sl = 0, ph = 1, mt = rot;
#pragma unroll 1
        for (int r = -1; r < NSTEP; r++) {
#pragma unroll 1
          for (int n = r < 0 ? 7 : 0; n < (r + 1 < NSTEP ? 10 : 7); n++) {
            mbar_waitw(bar + 8 * (BB_USED + sl), ph);
            mbar_expect_if(lane == 0, bar + 8 * (BB_FULL + sl), OP_SLOT);
            bulk_g2s_e(sb + BO_RING_OP + sl * OP_SLOT, wt + mt * OP_SLOT, OP_SLOT, bar + 8 * (BB_FULL + sl));
            if (++sl == 3) { sl = 0; ph ^= 1; }
            mt = mt == 9 ? 0 : mt + 1;
          }
        }
      } else if (op) {
        mbar_waitw(bar + 8 * BB_START, 0);
#pragma unroll 1
        for (int r = 0; r < NSTEP; r++) {
          const int rb = r - RD + 2;
          const uint32_t len = fmask(r) == 3 ? 8192 : 4096;
          const unsigned char* src = g_o + (uint32_t)(r * (96 * 8192) + 5 * j * len);
          wait_flags(lane < 2 ? &g_f[F_O + (lane ? NOP : j)][r] : rb >= 0 ? &g_f[F_DONE][rb] : &g_f[F_MISC][0],
                     lane < 2 ? (lane ? 1 : 5) : rb >= 0 ? rtarget(bmask(rb)) : NBC * 8);
          PTS1(35);
          if (r) bar_sync(NB_EARLY, 288);
          if (r == LAG) bar_sync(NB_LAST, 288);
          mbar_expect_if(lane < 3, bar + 8 * (BB_OFULL + lane), 2 * len);
          bulk_g2s_e(sb + BO_O, src, 2 * len, bar + 8 * BB_OFULL);
          PTS(62); PTS1(38);
          if (r && r != LAG) bar_sync(NB_LAST, 288);
          bulk_g2s_e(sb + BO_O + 2 * len, src + 2 * len, 2 * len, bar + 8 * (BB_OFULL + 1));
          bulk_g2s_e(sb + BO_O + 4 * len, src + 4 * len, len, bar + 8 * (BB_OFULL + 2));
          bulk_g2s_e(sb + BO_O + 5 * len, src + (95 - 5 * j) * len, len, bar + 8 * (BB_OFULL + 2));
          PTS1(64 + 35);
          BTS(r, 0);
        }
      } else if (warp == 2) {
#pragma unroll 1
        for (int r = 0; r < NR; r++) {
          const int mk = w12 ? fmask(r) : bmask(r);
          if (mk) {
            const unsigned char* src = &g_acc[w12 ? 4 : 2][r % RD][mk == 2 ? 4096 : 0];
            wait_flags(w12 ? &g_f[F_Z][r] : lane && r >= 2 ? &g_f[F_R3 + (j & 3)][r - 2] : &g_f[F_R2 + (j & 3)][r], w12 ? rtarget(mk) : NOP * NW12 * NW34);
#pragma unroll 1
            for (int z = 0; z < 5; z++) {
              const uint32_t fb = bar + 8 * (BB_FULL + z), dst = sb + BO_RING_MLP + 2 * z % 3 * 16384 + (mk == 2 ? 4096 : 0);
              mbar_waitw(bar + 8 * (z < 3 ? BB_ZFREE + z : BB_EMPTY + z - 3), (r + (z < 3)) & 1);
              if (z == 0) PTS(62);
              mbar_expect_if(lane == 0, fb, mk == 3 ? 16384 : 8192);
              bulk_g2s_e(dst, src + z * 16384, mk == 3 ? 16384 : 4096, fb);
              if (mk != 3) bulk_g2s_e(dst + 8192, src + z * 16384 + 8192, 4096, fb);
              if (z == 0) BTS(r, 0);
            }
          }
          if (!w12) {
#pragma unroll 1
            for (int c = j; c < 120; c += NW34) bulk_s2g_e(&g_acc[c < 80 ? c / 40 : 3][(r + (c < 80 ? 0 : 2)) % RD][c % 40 * 2048], sb + BO_CARRY, 2048);
            COMMIT();
            WRITTEN();
          }
          mbar_waitw(bar + 8 * BB_DONE, (r + 1) & 1);
          mbar_arrive_if(lane == 0, bar + 8 * BB_DONE);
        }
      } else {
#pragma unroll 1
        for (int r = 0; r < (w12 ? NSTEP : NR); r++) {
          const bool idle = !((w12 ? fmask(r) : bmask(r)) >> (lane >> 4) & 1);
          uint32_t t0, t1;
          int n = 0;
          mbar_waitw(bar + 8 * BB_FULL, r & 1);
          do {
            asm volatile("ld.relaxed.gpu.global.v2.u32 {%0,%1}, [%2];" : "=r"(t0), "=r"(t1) : "l"(&g_st2[!w12][r % RD][2 * lane]) : "memory");
            if (++n > SPIN_LIMIT) FAIL();
          } while (!__all_sync(~0u, idle || (((t0 ^ (r + 1)) | (t1 ^ (r + 1))) & 127) == 0));
          sts64(sb + BO_STAT + (lane >> 4) * 128 + (lane & 3) * 32 + ((lane >> 2) & 3) * 8, t0, t1);
          __syncwarp();
          mbar_arrive_if(lane == 0, bar + 8 * BB_STAT);
          PTS(63);
        }
      }
    }
    bar_arrive(NB_END, 512);
  } else if (wg == 2) {
    asm volatile("setmaxnreg.dec.sync.aligned.u32 40;");
    const int ord = uni(lds32(sb + BO_BOX + 4));
    const int gw = ord < 16 ? warp * 16 + ord : ord < 24 ? 48 + warp * 8 + ord : 72 + warp * 12 + ord, row = gw < 64 ? gw : gw < 96 ? gw - 64 : gw < 128 ? 2 * gw - 192 : 2 * gw - 224;
#pragma unroll 1
    for (int t = gw; t < S_LEN; t = row < 32 ? S_LEN : t < 4 * NBC ? 4 * NBC + (gw < 64 ? gw - 32 : gw - 80) : t + 64) {
      const int lane = lane_of(t);
      if (lane < 20 && t + 128 < S_LEN) asm volatile("prefetch.global.L2 [%0];" :: "l"(P.x + (t + (t < 4 * NBC ? 4 * NBC : 128)) * DM + (lane >> 1) * 64));
      rrow<3>(0, 0, t, lane, nullptr, role, P.x);
      __syncwarp();
      asm volatile("fence.release.gpu;" ::: "memory");
      red_if(lane == 0, &g_xready[t >> 5][0]);
    }
    if (gw < 64) rloop<0>(row, gw & 3, role, P.x, P.out);
    else if (gw < 96) rloop<2>(row, gw & 3, role, P.x, P.out);
    else if (gw < 128) rloop<1>(row, gw & 3, role, P.x, P.out);
    else rloop<4>(row, gw & 3, role, P.x, P.out);
    asm volatile("griddepcontrol.wait;" ::: "memory");
    const int t = threadIdx.x & 127;
    for (int i = (blockIdx.x * 128 + t) * 4; i < 4 * NCL * 2560; i += NBC * 512)
      *reinterpret_cast<uint4*>(&g_part[0][0][0][0] + i) = make_uint4(0u, 0u, 0u, 0u);
    bar_sync(NB_END, 512);
    if (t == 0) {
      uint32_t n;
      asm volatile("atom.acq_rel.gpu.global.add.u32 %0, [%1], 1;" : "=r"(n) : "l"(&g_f[F_MISC][64]) : "memory");
      sts32(sb + BO_BOX, n);
    }
    bar_sync(NB_END2, 128);
    if (lds32(sb + BO_BOX) == NBC - 1) {
      for (int i = t; i < F_NUM * 24; i += 128) reinterpret_cast<uint4*>(&g_f[0][0])[i] = make_uint4(0u, 0u, 0u, 0u);
      g_xready[t][0] = 0; g_tpc[t] = 0;
    }
  } else {
    asm volatile("setmaxnreg.inc.sync.aligned.u32 224;");
    LANE_INIT();
    for (int i = blockIdx.x * 256 + threadIdx.x; i < 2 * (RD + 1) * TILE_B / 16; i += NBC * 256)
      reinterpret_cast<uint4*>(&g_acc[i < 2 * RD * TILE_B / 16 ? 0 : 1][0][0])[i] = make_uint4(0u, 0u, 0u, 0u);
    warp_signal(&g_f[F_MISC][0], lane);
    const int mt0 = (rot + wg) % 10;
    auto boxes = [&](int ss) {
      const int nb = op && ss ? 3 : 4;
      const uint32_t base = sb + (ss ? BO_RES + wg * OP_RES : wg * 83968);
      mbar_expect_if(warp == 0 && lane == 0, bar + 8 * (BB_W + wg), nb * 20480 + (op ? 2048 : 0));
      bar_sync(NB_H, 256);
      if (warp < nb) {
#pragma unroll 1
        for (int i = warp; i < 5 * nb; i += nb) {
          const int p = op ? i / nb : (i - 10) >> 1, mt = (mt0 + 2 * p) % 10;
          const bool first = !op && i < 10;
          tma2d_e(op || !ss ? base + i * 4096 : sb + (first ? BO_W1 : -81920) + (2 * i + wg) * 4096, &P.wmap[op ? 0 : (w12 ? 1 : 3) + !first], first ? 128 * j + 64 * wg : mt * 64,
                  op ? 320 * j + 64 * warp + 32 * ss : first ? 64 * i + 32 * ss : 128 * j + 32 * (i & 1) + 64 * ss, bar + 8 * (BB_W + wg));
        }
      }
      if (op && warp == 3) tma2d_e(base + nb * 20480, &P.wo16, (mt0 + 2 * ss) % 10 * 64, 95 * 64 + (j + 1) / 5 * 16, bar + 8 * (BB_W + wg));
      mbar_waitw(bar + 8 * (BB_W + wg), ss);
    };
    if (W_DELAY) __nanosleep(W_DELAY);
    uint32_t W[164];
    boxes(0);
    load_w<41>(W, sb + wg * 83968, warp, lane);
    fence_async();
    boxes(1);
    if (!op) {
      float cs[2] = {0.f, 0.f};
      const uint32_t a0 = sb + BO_W1 + wg * 4096 + ((lane >> 4) * 8 + (lane & 7)) * 128 + (((warp * 2 + ((lane >> 3) & 1)) ^ (lane & 7)) << 4);
#pragma unroll
      for (int i = 0; i < 80; i++) cs[i & 1] += bf_lo(W[i]) + bf_hi(W[i]);
#pragma unroll 1
      for (int i = 0; i < 40; i++) {
        uint32_t t[4];
        const uint32_t ad = a0 + (i % 20 >> 1) * 8192 + (i & 1) * 2048;
        ldsm4t(t[0], t[1], t[2], t[3], ad);
#pragma unroll
        for (int k = 0; k < 4; k++) {
          if (i < 20) cs[k & 1] += bf_lo(t[k]) + bf_hi(t[k]);
          t[k] = pack2h(bf_lo(t[k]) - cs[k & 1], bf_hi(t[k]) - cs[k & 1]);
        }
        if (i >= 20) stsm4t(ad, t[0], t[1], t[2], t[3]);
        if (i == 19) {
#pragma unroll
          for (int k = 0; k < 2; k++) { cs[k] += __shfl_xor_sync(~0u, cs[k], 1); cs[k] += __shfl_xor_sync(~0u, cs[k], 2); cs[k] *= 1.f / DM; }
        }
      }
      const uint32_t z = dep0(__float_as_uint(cs[0]), lane);
#pragma unroll
      for (int i = 0; i < 80; i++) W[i] = pack2h(bf_lo(W[i] | z) - cs[i & 1], bf_hi(W[i] | z) - cs[i & 1]);
      fence_async();
      bar_sync(NB_H, 256);
    }
    const uint32_t alo = uni((SMEM0 + (op ? BO_RES + wg * OP_RES : wg * 4096)) >> 4);
    if (op) {
      Ring rg = {(uint32_t)wg, 0};
      mbar_arrive_if(lane == 0, bar + 8 * BB_START);
      if (wg) bar_arrive(NB_PP, 256);
      const uint32_t blo = DESC_LO(BO_O), xlo = blo + (j + 1) / 5 * 2;
#pragma unroll 1
      for (int r = 0; r < NSTEP; r++) {
        asm volatile("" : "+r"(lane));
        if (fmask(r) == 3) op_round<64>(W, bar, alo, blo, xlo, j == 0, rg, wg, warp, lane, r);
        else op_round<32>(W, bar, alo, blo, xlo, j == 0, rg, wg, warp, lane, r);
        if (warp == 0) BTS(r, 2 + wg);
      }
    } else {
      const int q4 = (128 * j + 64 * wg + 16 * warp) / 160, off = w12 ? (0x0413 >> (4 * q4)) & 7 : 0;
#pragma unroll 1
      for (int r = 0; r < NR; r++) {
        asm volatile("" : "+r"(lane));
        const int bm = bmask(r), fm = w12 ? fmask(r) : bm;
        if (fm == 3) phase1<64>(W, sb, alo, 0, wg, warp, lane, off, r);
        else if (fm) phase1<32>(W, sb, alo, fm >> 1, wg, warp, lane, off, r);
        else { mbar_waitu(bar + 8 * (BB_SFREE + 4 + wg), (r + 1) & 1); carry_in(sb, wg, warp, lane); }
        CTS(33);
        fence_async();
        bar_sync(NB_H, 256);
        if (wg + warp == 0) BTS(r, 1);
        if (bm == 3) phase2<64>(W, bar, alo, DESC_LO(BO_H), wg, warp, lane, r);
        else phase2<32>(W, bar, alo, uni(DESC_LO(BO_H) + (bm >> 1) * 256), wg, warp, lane, r);
        if (warp == 0) BTS(r, 2 + wg);
      }
    }
    CTS_OUT();
    bar_arrive(NB_END, 512);
  }
}

typedef CUresult (*EncodeFn)(CUtensorMap*, CUtensorMapDataType, cuuint32_t, void*, const cuuint64_t*, const cuuint64_t*, const cuuint32_t*,
                             const cuuint32_t*, CUtensorMapInterleave, CUtensorMapSwizzle, CUtensorMapL2promotion, CUtensorMapFloatOOBfill);
static void make_map(EncodeFn fn, CUtensorMap* tm, const void* ptr, uint64_t cols, uint64_t rows, uint32_t bc, uint32_t br) {
  cuuint64_t dims[2] = {cols, rows}; cuuint64_t strides[1] = {cols * 2}; cuuint32_t box[2] = {bc, br}; cuuint32_t es[2] = {1, 1};
  fn(tm, CU_TENSOR_MAP_DATA_TYPE_BFLOAT16, 2, const_cast<void*>(ptr), dims, strides, box, es, CU_TENSOR_MAP_INTERLEAVE_NONE,
     CU_TENSOR_MAP_SWIZZLE_128B, CU_TENSOR_MAP_L2_PROMOTION_L2_256B, CU_TENSOR_MAP_FLOAT_OOB_FILL_NONE);
}
#define dbg_a_only 0
extern "C" void kernel_launch(void* const* d_in, const int* in_sizes, int n_in, void* d_out, int out_size) {
  void* fnp = nullptr; cudaDriverEntryPointQueryResult qr;
  cudaGetDriverEntryPoint("cuTensorMapEncodeTiled", &fnp, cudaEnableDefault, &qr);
  EncodeFn fn = (EncodeFn)fnp;
  cudaStream_t st = cudaStreamPerThread;
  cudaFuncSetAttribute(bworker_kernel, cudaFuncAttributeMaxDynamicSharedMemorySize, B_SMEM);
  {
    AMaps M;
    for (int i = 0; i < 3; i++) make_map(fn, &M.w16[i], d_in[2 + i], HD, DM, 64, 16);
    make_map(fn, &M.wo32, d_in[5], DM, HD, 64, 32);
    cudaFuncSetAttribute(acore_kernel, cudaFuncAttributeMaxDynamicSharedMemorySize, A_SMEM);
    cudaFuncSetAttribute(acore_kernel, cudaFuncAttributeNonPortableClusterSizeAllowed, 1);
    cudaLaunchConfig_t cfg = {};
    cfg.gridDim = dim3(CL_SIZE * NCL); cfg.blockDim = dim3(512); cfg.dynamicSmemBytes = A_SMEM; cfg.stream = st;
    cudaLaunchAttribute at[1]; at[0].id = cudaLaunchAttributeClusterDimension;
    at[0].val.clusterDim.x = CL_SIZE; at[0].val.clusterDim.y = 1; at[0].val.clusterDim.z = 1;
    cfg.attrs = at; cfg.numAttrs = 1;
    cudaLaunchKernelEx(&cfg, acore_kernel, M, (const __nv_bfloat16*)d_in[1], dbg_a_only ? 0 : 1);
  }
  if (!dbg_a_only) {
    BParams P;
    make_map(fn, &P.wmap[0], d_in[5], DM, HD, 64, 32);
    make_map(fn, &P.wo16, d_in[5], DM, HD, 64, 16);
    make_map(fn, &P.wmap[1], d_in[8], DM, DM, 64, 32);
    make_map(fn, &P.wmap[2], d_in[9], DM, DM, 64, 32);
    make_map(fn, &P.wmap[3], d_in[10], FF, DM, 64, 32);
    make_map(fn, &P.wmap[4], d_in[11], DM, FF, 64, 32);
    P.x = (const __nv_bfloat16*)d_in[0];
    P.out = (__nv_bfloat16*)d_out;
    cudaLaunchConfig_t cfg = {};
    cfg.gridDim = dim3(NBC); cfg.blockDim = dim3(512); cfg.dynamicSmemBytes = B_SMEM; cfg.stream = st;
    cudaLaunchAttribute at[1]; at[0].id = cudaLaunchAttributeProgrammaticStreamSerialization; at[0].val.programmaticStreamSerializationAllowed = 1;
    cfg.attrs = at; cfg.numAttrs = 1;
    cudaLaunchKernelEx(&cfg, bworker_kernel, P);
  }
}
```

```cpp
#include <cuda_runtime.h>
#include <cuda_bf16.h>
#include <cuda.h>
#include <stdint.h>

#define S_LEN 2048
#define DM 640
#define NH 32
#define DH 192
#define HD 6144
#define NSEG 64
#define FF 1536

__device__ __forceinline__ uint32_t smem_u32(const void* p) { return (uint32_t)__cvta_generic_to_shared(p); }
__device__ __forceinline__ uint32_t mapa(uint32_t a, uint32_t r) {
  uint32_t o; asm volatile("mapa.shared::cluster.u32 %0, %1, %2;" : "=r"(o) : "r"(a), "r"(r)); return o; }
__device__ __forceinline__ void mbar_init(uint32_t b, uint32_t c) {
  asm volatile("mbarrier.init.shared::cta.b64 [%0], %1;" :: "r"(b), "r"(c) : "memory"); }
__device__ __forceinline__ void mbar_expect(uint32_t b, uint32_t tx) {
  asm volatile("mbarrier.arrive.expect_tx.shared::cta.b64 _, [%0], %1;" :: "r"(b), "r"(tx) : "memory"); }
__device__ __forceinline__ void mbar_arrive(uint32_t b) {
  asm volatile("mbarrier.arrive.shared::cta.b64 _, [%0];" :: "r"(b) : "memory"); }
__device__ __forceinline__ void mbar_arrive_remote(uint32_t rb) {
  asm volatile("mbarrier.arrive.relaxed.cluster.shared::cluster.b64 _, [%0];" :: "r"(rb) : "memory"); }
__device__ __forceinline__ void mbar_expect_if(bool p, uint32_t b, uint32_t tx) {
  asm volatile("{\n.reg .pred q;\nsetp.ne.u32 q, %2, 0;\n@q mbarrier.arrive.expect_tx.shared::cta.b64 _, [%0], %1;\n}" :: "r"(b), "r"(tx), "r"((uint32_t)p) : "memory"); }
__device__ __forceinline__ void mbar_arrive_if(bool p, uint32_t b) {
  asm volatile("{\n.reg .pred q;\nsetp.ne.u32 q, %1, 0;\n@q mbarrier.arrive.shared::cta.b64 _, [%0];\n}" :: "r"(b), "r"((uint32_t)p) : "memory"); }
__device__ __forceinline__ void mbar_arrive_remote_if(bool p, uint32_t rb) {
  asm volatile("{\n.reg .pred q;\nsetp.ne.u32 q, %1, 0;\n@q mbarrier.arrive.relaxed.cluster.shared::cluster.b64 _, [%0];\n}" :: "r"(rb), "r"((uint32_t)p) : "memory"); }
__device__ __forceinline__ void sts32_if(bool p, uint32_t a, uint32_t v) {
  asm volatile("{\n.reg .pred q;\nsetp.ne.u32 q, %2, 0;\n@q st.shared.b32 [%0], %1;\n}" :: "r"(a), "r"(v), "r"((uint32_t)p) : "memory"); }
__device__ __forceinline__ void sts128z_if(bool p, uint32_t a) {
  asm volatile("{\n.reg .pred q;\nsetp.ne.u32 q, %1, 0;\n@q st.shared.v4.b32 [%0], {0,0,0,0};\n}" :: "r"(a), "r"((uint32_t)p) : "memory"); }
__device__ __forceinline__ bool mbar_try(uint32_t b, uint32_t ph) {
  uint32_t ok;
  asm volatile("{\n.reg .pred p;\nmbarrier.try_wait.parity.shared::cta.b64 p, [%1], %2;\nselp.u32 %0, 1, 0, p;\n}"
               : "=r"(ok) : "r"(b), "r"(ph) : "memory");
  return ok; }
__device__ __forceinline__ bool mbar_test(uint32_t b, uint32_t ph) {
  uint32_t ok;
  asm volatile("{\n.reg .pred p;\nmbarrier.test_wait.parity.shared::cta.b64 p, [%1], %2;\nselp.u32 %0, 1, 0, p;\n}"
               : "=r"(ok) : "r"(b), "r"(ph) : "memory");
  return ok; }
#define SPIN_LIMIT 4000000
#define FAIL() asm volatile("st.global.u32 [%0], 0;" :: "l"(8ull) : "memory")
#define CFENCE() asm volatile("fence.proxy.async::generic.acquire.sync_restrict::shared::cluster.cluster;" ::: "memory")
__device__ __forceinline__ void mbar_wait(uint32_t b, uint32_t ph) {
  int n = 0;
  while (!mbar_try(b, ph)) { if (++n > SPIN_LIMIT) FAIL(); } }
#define TIMEOUT_ACT "@!p st.shared.u32 [%0+1], 0;"
#define WAIT_HINT ", 20000"
#define WAIT_LIM "200000"
__device__ __forceinline__ void mbar_slow(uint32_t b, uint32_t ph) {
  asm volatile("{\n.reg .pred p, q;\n.reg .u32 n;\nmov.u32 n, 0;\n"
               "WL:\nmbarrier.try_wait.parity.shared::cta.b64 p, [%0], %1" WAIT_HINT ";\nadd.u32 n, n, 1;\nsetp.lt.and.u32 q, n, " WAIT_LIM ", !p;\n@q bra.uni WL;\n"
               TIMEOUT_ACT "\n}" :: "r"(b), "r"(ph) : "memory"); }
__device__ __forceinline__ void mbar_waitw(uint32_t b, uint32_t ph) {
  asm volatile("{\n.reg .pred p, q;\n.reg .u32 n;\nmbarrier.try_wait.parity.shared::cta.b64 p, [%0], %1;\n@p bra.uni WD;\nmov.u32 n, 0;\n"
               "WL:\nmbarrier.try_wait.parity.shared::cta.b64 p, [%0], %1" WAIT_HINT ";\nadd.u32 n, n, 1;\nsetp.lt.and.u32 q, n, " WAIT_LIM ", !p;\n@q bra.uni WL;\n"
               TIMEOUT_ACT "\nWD:\n}" :: "r"(b), "r"(ph) : "memory"); }
__device__ __forceinline__ void mbar_waitw2(uint32_t b0, uint32_t b1, uint32_t ph) {
  uint32_t ok;
  asm volatile("{\n.reg .pred p, r;\nmbarrier.try_wait.parity.shared::cta.b64 p, [%1], %3;\nmbarrier.try_wait.parity.shared::cta.b64 r, [%2], %3;\n"
               "and.pred p, p, r;\nselp.u32 %0, 1, 0, p;\n}" : "=r"(ok) : "r"(b0), "r"(b1), "r"(ph) : "memory");
  if (__builtin_expect(!__all_sync(~0u, ok), 0)) { mbar_slow(b0, ph); mbar_slow(b1, ph); }
}
__device__ __forceinline__ void mbar_waitu(uint32_t b, uint32_t ph) {
  asm volatile("{\n.reg .pred p;\nmbarrier.try_wait.parity.shared::cta.b64 p, [%0], %1;\n@p bra.uni WD;\n"
               "WL:\nmbarrier.try_wait.parity.shared::cta.b64 p, [%0], %1" WAIT_HINT ";\n@!p bra.uni WL;\nWD:\n}" :: "r"(b), "r"(ph) : "memory"); }
__device__ __forceinline__ void mbar_waitu2(uint32_t b0, uint32_t b1, uint32_t ph) {
  asm volatile("{\n.reg .pred p, r;\nWL:\nmbarrier.try_wait.parity.shared::cta.b64 p, [%0], %2;\nmbarrier.try_wait.parity.shared::cta.b64 r, [%1], %2;\n"
               "and.pred p, p, r;\n@!p bra.uni WL;\n}" :: "r"(b0), "r"(b1), "r"(ph) : "memory"); }
__device__ __forceinline__ void mbar_waitw4(uint32_t b, uint32_t ph) { mbar_waitw2(b, b + 8, ph); mbar_waitw2(b + 16, b + 24, ph); }
__device__ __forceinline__ uint32_t clock32() { uint32_t t; asm volatile("mov.u32 %0, %%clock;" : "=r"(t) :: "memory"); return t; }
template <int L> __device__ __forceinline__ uint32_t lop3(uint32_t a, uint32_t b, uint32_t c) {
  uint32_t r; asm("lop3.b32 %0, %1, %2, %3, %4;" : "=r"(r) : "r"(a), "r"(b), "r"(c), "n"(L)); return r; }
__device__ __forceinline__ void st_async_v2_if(bool p, uint32_t a, uint32_t v0, uint32_t v1, uint32_t mb) {
  asm volatile("{\n.reg .pred q;\nsetp.ne.u32 q, %4, 0;\n@q st.async.weak.shared::cluster.mbarrier::complete_tx::bytes.v2.b32 [%0], {%1,%2}, [%3];\n}"
               :: "r"(a), "r"(v0), "r"(v1), "r"(mb), "r"((uint32_t)p) : "memory"); }
__device__ __forceinline__ void keep4(const uint32_t* r, int lane) {
  asm volatile("{\n.reg .pred q;\nsetp.lt.s32 q, %4, 0;\n@q st.shared.v4.b32 [%4], {%0,%1,%2,%3};\n}" :: "r"(r[0]), "r"(r[1]), "r"(r[2]), "r"(r[3]), "r"(lane) : "memory"); }
__device__ __forceinline__ uint32_t uni(uint32_t x) { return __shfl_sync(~0u, x, 0); }
__device__ __forceinline__ void bulk_g2s_mc_e(uint32_t dst, const void* src, uint32_t bytes, uint32_t mb, uint16_t mask) {
  asm volatile("{\n.reg .pred e;\nelect.sync _|e, 0xffffffff;\n"
               "@e cp.async.bulk.shared::cluster.global.mbarrier::complete_tx::bytes.multicast::cluster [%0], [%1], %2, [%3], %4;\n}"
               :: "r"(dst), "l"(src), "r"(bytes), "r"(mb), "h"(mask) : "memory"); }
__device__ __forceinline__ void bulk_s2g_e(void* dst, uint32_t src, uint32_t bytes) {
  asm volatile("{\n.reg .pred e;\nelect.sync _|e, 0xffffffff;\n@e cp.async.bulk.global.shared::cta.bulk_group [%0], [%1], %2;\n}"
               :: "l"(dst), "r"(src), "r"(bytes) : "memory"); }
__device__ __forceinline__ void bulk_g2s_e(uint32_t dst, const void* src, uint32_t bytes, uint32_t mb) {
  asm volatile("{\n.reg .pred e;\nelect.sync _|e, 0xffffffff;\n@e cp.async.bulk.shared::cluster.global.mbarrier::complete_tx::bytes [%0], [%1], %2, [%3];\n}"
               :: "r"(dst), "l"(src), "r"(bytes), "r"(mb) : "memory"); }
#define STREAM_HINT 1
__device__ __forceinline__ void bulk_s2g_es(void* dst, uint32_t src, uint32_t bytes) {
  asm volatile("{\n.reg .pred e;\n.reg .b64 pol;\ncreatepolicy.fractional.L2::evict_first.b64 pol;\nelect.sync _|e, 0xffffffff;\n"
               "@e cp.async.bulk.global.shared::cta.bulk_group.L2::cache_hint [%0], [%1], %2, pol;\n}" :: "l"(dst), "r"(src), "r"(bytes) : "memory");
}
__device__ __forceinline__ void bulk_g2s_es(uint32_t dst, const void* src, uint32_t bytes, uint32_t mb) {
  asm volatile("{\n.reg .pred e;\n.reg .b64 pol;\ncreatepolicy.fractional.L2::evict_first.b64 pol;\nelect.sync _|e, 0xffffffff;\n"
               "@e cp.async.bulk.shared::cluster.global.mbarrier::complete_tx::bytes.L2::cache_hint [%0], [%1], %2, [%3], pol;\n}"
               :: "r"(dst), "l"(src), "r"(bytes), "r"(mb) : "memory"); }
__device__ __forceinline__ void tma2d_e(uint32_t dst, const CUtensorMap* tm, int c0, int c1, uint32_t mb) {
  asm volatile("{\n.reg .pred e;\nelect.sync _|e, 0xffffffff;\n"
               "@e cp.async.bulk.tensor.2d.shared::cluster.global.mbarrier::complete_tx::bytes [%0], [%1, {%3, %4}], [%2];\n}"
               :: "r"(dst), "l"((uint64_t)tm), "r"(mb), "r"(c0), "r"(c1) : "memory"); }
__device__ __forceinline__ uint32_t hadd2bf(uint32_t a, uint32_t b) {
  uint32_t r; asm("add.rn.bf16x2 %0, %1, %2;" : "=r"(r) : "r"(a), "r"(b)); return r; }
__device__ __forceinline__ void cluster_sync_all() {
  asm volatile("barrier.cluster.arrive.release.aligned;\nbarrier.cluster.wait.acquire.aligned;" ::: "memory"); }
__device__ __forceinline__ void bar_arrive(int id, int n) { asm volatile("bar.arrive %0, %1;" :: "r"(id), "r"(n) : "memory"); }
__device__ __forceinline__ void bar_arrive_dep(int id, int n, uint32_t dep) {
  asm volatile("{\n.reg .u32 t;\nand.b32 t, %2, 0;\nadd.u32 t, t, %0;\nbar.sync t, %1;\n}" :: "r"(id), "r"(n), "r"(dep) : "memory"); }
__device__ __forceinline__ void bar_sync(int id, int n) { asm volatile("bar.sync %0, %1;" :: "r"(id), "r"(n) : "memory"); }
__device__ __forceinline__ void fence_async() { asm volatile("fence.proxy.async.shared::cta;" ::: "memory"); }
__device__ __forceinline__ void st_async_b32(uint32_t a, uint32_t v, uint32_t mb) {
  asm volatile("st.async.weak.shared::cluster.mbarrier::complete_tx::bytes.b32 [%0], %1, [%2];" :: "r"(a), "r"(v), "r"(mb) : "memory"); }
__device__ __forceinline__ void st_async_v2(uint32_t a, uint32_t v0, uint32_t v1, uint32_t mb) {
  asm volatile("st.async.weak.shared::cluster.mbarrier::complete_tx::bytes.v2.b32 [%0], {%1,%2}, [%3];" :: "r"(a), "r"(v0), "r"(v1), "r"(mb) : "memory"); }
__device__ __forceinline__ void st_async_v4(uint32_t a, uint32_t v0, uint32_t v1, uint32_t v2, uint32_t v3, uint32_t mb) {
  asm volatile("st.async.weak.shared::cluster.mbarrier::complete_tx::bytes.v4.b32 [%0], {%1,%2,%3,%4}, [%5];" :: "r"(a), "r"(v0), "r"(v1), "r"(v2), "r"(v3), "r"(mb) : "memory"); }
__device__ __forceinline__ void ldsm4(uint32_t& r0, uint32_t& r1, uint32_t& r2, uint32_t& r3, uint32_t a) {
  asm volatile("ldmatrix.sync.aligned.m8n8.x4.shared.b16 {%0,%1,%2,%3}, [%4];" : "=r"(r0), "=r"(r1), "=r"(r2), "=r"(r3) : "r"(a) : "memory"); }
__device__ __forceinline__ void ldsm4t(uint32_t& r0, uint32_t& r1, uint32_t& r2, uint32_t& r3, uint32_t a) {
  asm volatile("ldmatrix.sync.aligned.m8n8.x4.trans.shared.b16 {%0,%1,%2,%3}, [%4];" : "=r"(r0), "=r"(r1), "=r"(r2), "=r"(r3) : "r"(a) : "memory"); }
__device__ __forceinline__ void stsm2t(uint32_t a, uint32_t r0, uint32_t r1) {
  asm volatile("stmatrix.sync.aligned.m8n8.x2.trans.shared.b16 [%0], {%1,%2};" :: "r"(a), "r"(r0), "r"(r1) : "memory"); }
__device__ __forceinline__ void stsm4t(uint32_t a, uint32_t r0, uint32_t r1, uint32_t r2, uint32_t r3) {
  asm volatile("stmatrix.sync.aligned.m8n8.x4.trans.shared.b16 [%0], {%1,%2,%3,%4};" :: "r"(a), "r"(r0), "r"(r1), "r"(r2), "r"(r3) : "memory"); }
__device__ __forceinline__ uint32_t movm(uint32_t a) {
  uint32_t d; asm volatile("movmatrix.sync.aligned.m8n8.trans.b16 %0, %1;" : "=r"(d) : "r"(a)); return d; }
__device__ __forceinline__ void mma16816(float* d, uint32_t a0, uint32_t a1, uint32_t a2, uint32_t a3, uint32_t b0, uint32_t b1) {
  asm("mma.sync.aligned.m16n8k16.row.col.f32.bf16.bf16.f32 {%0,%1,%2,%3}, {%4,%5,%6,%7}, {%8,%9}, {%0,%1,%2,%3};"
               : "+f"(d[0]), "+f"(d[1]), "+f"(d[2]), "+f"(d[3]) : "r"(a0), "r"(a1), "r"(a2), "r"(a3), "r"(b0), "r"(b1)); }
__device__ __forceinline__ void mma16816v(float* d, uint32_t a0, uint32_t a1, uint32_t a2, uint32_t a3, uint32_t b0, uint32_t b1) {
  asm volatile("mma.sync.aligned.m16n8k16.row.col.f32.bf16.bf16.f32 {%0,%1,%2,%3}, {%4,%5,%6,%7}, {%8,%9}, {%0,%1,%2,%3};"
               : "+f"(d[0]), "+f"(d[1]), "+f"(d[2]), "+f"(d[3]) : "r"(a0), "r"(a1), "r"(a2), "r"(a3), "r"(b0), "r"(b1)); }
__device__ __forceinline__ uint32_t pack2(float lo, float hi) {
  uint32_t r; asm("cvt.rn.bf16x2.f32 %0, %1, %2;" : "=r"(r) : "f"(hi), "f"(lo)); return r; }
__device__ __forceinline__ uint32_t pack2v(float lo, float hi) {
  uint32_t r; asm volatile("cvt.rn.bf16x2.f32 %0, %1, %2;" : "=r"(r) : "f"(hi), "f"(lo)); return r; }
__device__ __forceinline__ float bf_lo(uint32_t w) { return __uint_as_float(w << 16); }
__device__ __forceinline__ float bf_hi(uint32_t w) { return __uint_as_float(w & 0xffff0000u); }
__device__ __forceinline__ uint4 lds128(uint32_t a) {
  uint4 v; asm volatile("ld.shared.v4.b32 {%0,%1,%2,%3}, [%4];" : "=r"(v.x), "=r"(v.y), "=r"(v.z), "=r"(v.w) : "r"(a) : "memory"); return v; }
__device__ __forceinline__ uint4 lds128_nv(uint32_t a) {
  uint4 v; asm volatile("ld.shared.v4.b32 {%0,%1,%2,%3}, [%4];" : "=r"(v.x), "=r"(v.y), "=r"(v.z), "=r"(v.w) : "r"(a)); return v; }
__device__ __forceinline__ void st_async_v2_nm(uint32_t a, uint32_t v0, uint32_t v1, uint32_t mb) {
  asm volatile("st.async.weak.shared::cluster.mbarrier::complete_tx::bytes.v2.b32 [%0], {%1,%2}, [%3];" :: "r"(a), "r"(v0), "r"(v1), "r"(mb)); }
__device__ __forceinline__ float rcpf(float x) { float y; asm("rcp.approx.ftz.f32 %0, %1;" : "=f"(y) : "f"(x)); return y; }
__device__ __forceinline__ void sts64(uint32_t a, uint32_t x, uint32_t y) { asm volatile("st.shared.v2.b32 [%0], {%1,%2};" :: "r"(a), "r"(x), "r"(y) : "memory"); }
__device__ __forceinline__ float ex2(float x) { float y; asm("ex2.approx.ftz.f32 %0, %1;" : "=f"(y) : "f"(x)); return y; }
__device__ __forceinline__ uint32_t lds32(uint32_t a) {
  uint32_t v; asm volatile("ld.shared.b32 %0, [%1];" : "=r"(v) : "r"(a) : "memory"); return v; }
__device__ __forceinline__ uint2 lds64(uint32_t a) {
  uint2 v; asm volatile("ld.shared.v2.b32 {%0,%1}, [%2];" : "=r"(v.x), "=r"(v.y) : "r"(a) : "memory"); return v; }
__device__ __forceinline__ void sts128(uint32_t a, uint32_t x, uint32_t y, uint32_t z, uint32_t w) {
  asm volatile("st.shared.v4.b32 [%0], {%1,%2,%3,%4};" :: "r"(a), "r"(x), "r"(y), "r"(z), "r"(w) : "memory"); }
__device__ __forceinline__ void sts32(uint32_t a, uint32_t x) { asm volatile("st.shared.b32 [%0], %1;" :: "r"(a), "r"(x) : "memory"); }
__device__ __forceinline__ void tma2d(uint32_t dst, const CUtensorMap* tm, int c0, int c1, uint32_t mb) {
  asm volatile("cp.async.bulk.tensor.2d.shared::cluster.global.mbarrier::complete_tx::bytes [%0], [%1, {%3, %4}], [%2];"
               :: "r"(dst), "l"((uint64_t)tm), "r"(mb), "r"(c0), "r"(c1) : "memory"); }
__device__ __forceinline__ void tma2d_prefetch(const CUtensorMap* tm, int c0, int c1) {
  asm volatile("cp.async.bulk.prefetch.tensor.2d.L2.global.tile [%0, {%1, %2}];" :: "l"((uint64_t)tm), "r"(c0), "r"(c1) : "memory"); }
__device__ __forceinline__ void bulk_g2s_mc(uint32_t dst, const void* src, uint32_t bytes, uint32_t mb, uint16_t mask) {
  asm volatile("cp.async.bulk.shared::cluster.global.mbarrier::complete_tx::bytes.multicast::cluster [%0], [%1], %2, [%3], %4;"
               :: "r"(dst), "l"(src), "r"(bytes), "r"(mb), "h"(mask) : "memory"); }
__device__ __forceinline__ void bulk_s2g(void* dst, uint32_t src, uint32_t bytes) {
  asm volatile("cp.async.bulk.global.shared::cta.bulk_group [%0], [%1], %2;" :: "l"(dst), "r"(src), "r"(bytes) : "memory"); }
__device__ __forceinline__ void wg_fence() { asm volatile("wgmma.fence.sync.aligned;" ::: "memory"); }
__device__ __forceinline__ void wg_commit() { asm volatile("wgmma.commit_group.sync.aligned;" ::: "memory"); }
template <int N> __device__ __forceinline__ void wg_wait() { asm volatile("wgmma.wait_group.sync.aligned %0;" :: "n"(N) : "memory"); }
__device__ __forceinline__ uint64_t mkdesc(uint32_t addr, uint32_t lbo, uint32_t sbo, uint32_t swz) {
  return (uint64_t)((addr & 0x3FFFF) >> 4) | ((uint64_t)(lbo >> 4) << 16) | ((uint64_t)(sbo >> 4) << 32) | ((uint64_t)swz << 62); }

#define ACC4(d) "+f"(d[0]),"+f"(d[1]),"+f"(d[2]),"+f"(d[3])
#define ACC8(d) ACC4(d), ACC4((d + 4))
#define ACC16(d) ACC8(d), ACC8((d + 8))
#define ACC20(d) ACC16(d), ACC4((d + 16))
#define ACC24(d) ACC16(d), ACC8((d + 16))
#define SMEM0 0x400
__host__ __device__ constexpr uint32_t dlo(uint32_t off, uint32_t lbo) { return ((SMEM0 + off) >> 4) | ((lbo >> 4) << 16); }
__host__ __device__ constexpr uint32_t dhi(uint32_t sbo, uint32_t swz) { return (sbo >> 4) | (swz << 30); }
#define R4S "{%0,%1,%2,%3}"
#define R8S "{%0,%1,%2,%3,%4,%5,%6,%7}"
#define R16S "{%0,%1,%2,%3,%4,%5,%6,%7,%8,%9,%10,%11,%12,%13,%14,%15}"
#define R20S "{%0,%1,%2,%3,%4,%5,%6,%7,%8,%9,%10,%11,%12,%13,%14,%15,%16,%17,%18,%19}"
#define R24S "{%0,%1,%2,%3,%4,%5,%6,%7,%8,%9,%10,%11,%12,%13,%14,%15,%16,%17,%18,%19,%20,%21,%22,%23}"
template <int N> struct MM;
#define DEF_MM(N, ACCM, RS_, I0, I1, I2, I3, I4, I5, I6, I7)                                                                      \
  template <> struct MM<N> {                                                                                                      \
    template <uint32_t BLO, uint32_t BHI, int ACC>                                                                                \
    static __device__ __forceinline__ void rs(float* d, uint32_t a0, uint32_t a1, uint32_t a2, uint32_t a3) {                     \
      asm volatile("{\n.reg .b64 b;\nmov.b64 b, {%" #I4 ", %" #I5 "};\n"                                                          \
                   "wgmma.mma_async.sync.aligned.m64n" #N "k16.f32.bf16.bf16 " RS_ ", {%" #I0 ",%" #I1 ",%" #I2 ",%" #I3 "}, b, %" #I6 ", 1, 1, 0;\n}" \
                   : ACCM(d) : "r"(a0), "r"(a1), "r"(a2), "r"(a3), "n"(BLO), "n"(BHI), "n"(ACC)); }                               \
    template <uint32_t ALO, uint32_t AHI, uint32_t BLO, uint32_t BHI, int ACC, int TA>                                            \
    static __device__ __forceinline__ void ss(float* d, uint32_t abase) {                                                         \
      asm volatile("{\n.reg .b64 a, b;\n.reg .b32 l;\nadd.u32 l, %" #I0 ", %" #I1 ";\nmov.b64 a, {l, %" #I2 "};\nmov.b64 b, {%" #I3 ", %" #I4 "};\n" \
                   "wgmma.mma_async.sync.aligned.m64n" #N "k16.f32.bf16.bf16 " RS_ ", a, b, %" #I5 ", 1, 1, %" #I6 ", 0;\n}"     \
                   : ACCM(d) : "r"(abase), "n"(ALO), "n"(AHI), "n"(BLO), "n"(BHI), "n"(ACC), "n"(TA)); }                          \
    template <int ACC>                                                                                                            \
    static __device__ __forceinline__ void rsd(float* d, uint32_t a0, uint32_t a1, uint32_t a2, uint32_t a3, uint64_t b) {        \
      asm volatile("wgmma.mma_async.sync.aligned.m64n" #N "k16.f32.bf16.bf16 " RS_ ", {%" #I0 ",%" #I1 ",%" #I2 ",%" #I3 "}, %" #I4 ", %" #I5 ", 1, 1, 0;" \
                   : ACCM(d) : "r"(a0), "r"(a1), "r"(a2), "r"(a3), "l"(b), "n"(ACC)); }                                           \
    template <int ACC>                                                                                                            \
    static __device__ __forceinline__ void ssd(float* d, uint64_t a, uint64_t b) {                                                \
      asm volatile("wgmma.mma_async.sync.aligned.m64n" #N "k16.f32.bf16.bf16 " RS_ ", %" #I0 ", %" #I1 ", %" #I2 ", 1, 1, 1, 0;"  \
                   : ACCM(d) : "l"(a), "l"(b), "n"(ACC)); }                                                                       \
    template <uint32_t ALO, uint32_t AHI, uint32_t BLO, uint32_t BHI, int ACC>                                                    \
    static __device__ __forceinline__ void ss2(float* d, uint32_t abase, uint32_t bbase) {                                        \
      asm volatile("{\n.reg .b64 a, b;\n.reg .b32 l, m;\nadd.u32 l, %" #I0 ", %" #I1 ";\nmov.b64 a, {l, %" #I2 "};\n"            \
                   "add.u32 m, %" #I6 ", %" #I3 ";\nmov.b64 b, {m, %" #I4 "};\n"                                                   \
                   "wgmma.mma_async.sync.aligned.m64n" #N "k16.f32.bf16.bf16 " RS_ ", a, b, %" #I5 ", 1, 1, 0, 0;\n}"            \
                   : ACCM(d) : "r"(abase), "n"(ALO), "n"(AHI), "n"(BLO), "n"(BHI), "n"(ACC), "r"(bbase)); }                                    \
  };
DEF_MM(8, ACC4, R4S, 4, 5, 6, 7, 8, 9, 10, 11)
DEF_MM(16, ACC8, R8S, 8, 9, 10, 11, 12, 13, 14, 15)
DEF_MM(32, ACC16, R16S, 16, 17, 18, 19, 20, 21, 22, 23)
DEF_MM(40, ACC20, R20S, 20, 21, 22, 23, 24, 25, 26, 27)
DEF_MM(48, ACC24, R24S, 24, 25, 26, 27, 28, 29, 30, 31)

#define LAG 10
#define NSTEP (NSEG + LAG)
#define NR (NSTEP + 1)
__device__ __align__(1024) __nv_bfloat16 g_xn[2][S_LEN * DM];
#define RO 16
static_assert(RO > LAG + 1, "ring");
__device__ __align__(1024) unsigned char g_o[RO * 96 * 8192];
__device__ __align__(1024) uint32_t g_part[6][7][40][64];
#define RD 16
#define TILE_B 81920
__device__ __align__(1024) float2 g_stat[S_LEN];
__device__ __align__(1024) uint32_t g_st2[2][RD][64];
__device__ __align__(1024) unsigned char g_acc[5][RD][TILE_B];
#define NOP 19
#define NW12 5
#define NW34 12
#define NBC (NOP + NW12 + NW34)
__device__ __align__(1024) unsigned char g_wt[NOP * 10 * 12288];
enum { F_O = 0, F_R1 = NOP + 1, F_R2 = F_R1 + 4, F_R3 = F_R2 + 4, F_Z = F_R3 + 4, F_DONE, F_MISC, F_NUM };
__device__ __align__(128) uint32_t g_f[F_NUM][96];
__device__ __align__(128) int g_xready[129][8];
__device__ uint32_t g_tpc[128];
#define TS(i)
#define TSV(i, v)
#define TSN(i)
#define TSD(i, dep)
#define BTS(k, i)
#define BTS2(k, i)
#define RTS(i)
#define RTSD(i, dep)
#define RTS_OUT()
#define CTS(i)
#define PTS(i)
#define PTS1(i)
#define CTS_OUT()
#define GTS(i)

#define CL_SIZE 15
#define NCL 7
#define SSQ 13
#define SSV 16
#define PL_SZ 5376
#define TILE_SBO 2560
#define TILE_GRP 15360
#define WS_SZ ((2 * SSQ + SSV) * 2048)
#define OFF_QK (OFF_WO + 26 * 2048)
#define LAYOUT 2
#define OFF_TILE 0
#define OFF_WS (4 * TILE_GRP)
#define OFF_WO (OFF_WS + WS_SZ)
#define OFF_PL (OFF_QK + 20480)
#define OFF_BAR (OFF_PL + 2 * PL_SZ)
#define STG_Q OFF_TILE
#define STG_K OFF_WO
#define VA 14
#define STG_V2 (OFF_TILE + 27 * 2048)
#define OFF_O (OFF_PL + 4352)
#define LAND(k) (((k) >> 1) * TILE_GRP + ((k) & 1) * 1280)
#define LAND_F (5 * TILE_SBO)
#define OFF_XL (OFF_TILE + 3 * TILE_GRP)
#define OFF_XF (OFF_XL + LAND_F)
#define OFF_WT ((OFF_XL + TILE_SBO + 1023) & ~1023)
#define OFF_TAB (OFF_BAR + 240)
#define OFF_INV (OFF_TAB + 64)
#define OFF_TS (OFF_INV + 128)
#define A_SMEM 232448
static_assert(WS_SZ + 72 * 1024 + 2 * PL_SZ + 4 * TILE_GRP + 512 == A_SMEM && OFF_WS % 1024 == 0 && OFF_WO % 1024 == 0 && SSQ == 13, "smem map");
enum { B_W0 = 0, B_W1, B_F1, B_F2 = B_F1 + 4, B_R1 = B_F2 + 4, B_R2, B_MEMFREE, B_LANDFREE, B_OPEER, B_PLFREE, B_XFREE, B_SB, B_WOF = B_SB + 6, B_WTF, B_RS, B_NUM = B_RS + 4 };
static_assert(B_NUM <= 30, "barriers");
enum { N_C = 0, N_SISS, N_QK, N_V, N_PM, N_TURN, N_PI, N_VGO, N_O, N_PX, N_AB, N_SDONE, N_VDONE, N_G3, N_P, N_OX };

__device__ __forceinline__ bool is_dual(int j) { return j >= LAG && j < NSEG; }
__device__ __forceinline__ int sched_l(int j) { return j < NSEG ? j : NSEG + j - LAG; }
__device__ __forceinline__ int sched_f(int j) { return NSEG + j - LAG; }
__device__ __forceinline__ void wait_cnt(const int* p, int target) {
  int v, n = 0;
  do {
    asm volatile("ld.relaxed.gpu.global.b32 %0, [%1];" : "=r"(v) : "l"(p) : "memory");
    if (v >= target) break;
    __nanosleep(100);
    if (++n > SPIN_LIMIT) FAIL();
  } while (true);
  asm volatile("fence.acquire.gpu;" ::: "memory");
  asm volatile("fence.proxy.async.global;" ::: "memory");
}
__device__ __forceinline__ void red_release(void* p, uint32_t v) { asm volatile("red.release.gpu.global.add.u32 [%0], %1;" :: "l"(p), "r"(v) : "memory"); }
__device__ __forceinline__ void red_relaxed(void* p, uint32_t v) { asm volatile("red.relaxed.gpu.global.add.u32 [%0], %1;" :: "l"(p), "r"(v) : "memory"); }
#define VMASK 0xa5294a5294ull
__host__ __device__ constexpr int popc40(unsigned long long m) { int c = 0; for (; m; m &= m - 1) c++; return c; }
static_assert(popc40(VMASK) == SSV, "mask");
__host__ __device__ constexpr int ss_idx(int ks, int n) { return n == SSV ? popc40(VMASK & ((1ull << ks) - 1)) : ks * n / 40; }
__host__ __device__ constexpr bool is_ss(int ks, int n) { return ss_idx(ks + 1, n) != ss_idx(ks, n); }
__host__ __device__ constexpr int rs_idx(int ks, int n) { return ks - ss_idx(ks, n); }

#define SL2 (0.07216878364870322f * 1.4426950408889634f)

#define SUM_LOOP 0
#define IMM_K 0
#define TAB_N 32
struct DescTab { uint64_t tile[2][40], unit[2 * SSQ + SSV]; };
constexpr DescTab make_tab() {
  DescTab t = {};
  for (int rg = 0; rg < 2; rg++)
    for (int k = 0; k < 40; k++) t.tile[rg][k] = dlo(OFF_TILE + (k / 10) * TILE_GRP + rg * TILE_SBO + (k % 10) * 256, 128) | ((uint64_t)dhi(TILE_SBO, 3) << 32);
  for (int u = 0; u < 2 * SSQ + SSV; u++) t.unit[u] = dlo(OFF_WS + u * 2048, 0) | ((uint64_t)dhi(1024, 1) << 32);
  return t;
}
__constant__ DescTab c_tab = make_tab();
template <int N, int NSS, int RG, int KS, int K1, int K0 = 0>
__device__ __forceinline__ void proj(float* acc, const uint32_t* W, uint32_t ub) {
  if constexpr (KS < K1) {
    constexpr int i = rs_idx(KS, NSS) * 4;
    if constexpr (N >= TAB_N && !(RG == 0 && NSS == SSQ && KS < IMM_K)) {
      if constexpr (is_ss(KS, NSS)) MM<N>::template ssd<(KS != K0)>(acc, c_tab.unit[ub + ss_idx(KS, NSS)], c_tab.tile[RG][KS]);
      else MM<N>::template rsd<(KS != K0)>(acc, W[i], W[i + 1], W[i + 2], W[i + 3], c_tab.tile[RG][KS]);
    } else {
      constexpr uint32_t BLO = dlo(OFF_TILE + (KS / 10) * TILE_GRP + RG * TILE_SBO + (KS % 10) * 256, 128), BHI = dhi(TILE_SBO, 3);
      if constexpr (is_ss(KS, NSS)) MM<N>::template ss<dlo(OFF_WS + ss_idx(KS, NSS) * 2048, 0), dhi(1024, 1), BLO, BHI, (KS != K0), 1>(acc, ub * 128);
      else MM<N>::template rs<BLO, BHI, (KS != K0)>(acc, W[i], W[i + 1], W[i + 2], W[i + 3]);
    }
    proj<N, NSS, RG, KS + 1, K1, K0>(acc, W, ub);
  }
}
template <int N>
__device__ __forceinline__ void load_w(uint32_t* W, uint32_t stage, int warp, int lane) {
  const int kr = (lane >> 4) * 8 + (lane & 7);
  const int cb = warp * 2 + ((lane >> 3) & 1);
  const uint32_t a0 = stage + kr * 128 + ((cb ^ (lane & 7)) << 4);
#pragma unroll
  for (int i = 0; i < N; i++) ldsm4t(W[4 * i], W[4 * i + 1], W[4 * i + 2], W[4 * i + 3], a0 + i * 2048);
}
template <int N, int U, int OS, int ACC>
__device__ __forceinline__ void wo4(float* d) {
  constexpr uint32_t WA = U >= 4 ? OFF_WO + (U - 4) * 2048 : OFF_WT, OB = OS == 0 ? OFF_O : OS == 1 ? OFF_XL : OFF_XF, SBO = OS ? 1024 : PL_SZ;
  MM<N>::template ss<dlo(WA, 0), dhi(1024, 1), dlo(OB, 128), dhi(SBO, 0), ACC, 1>(d, 0);
  MM<N>::template ss<dlo(WA + 2048, 0), dhi(1024, 1), dlo(OB + 256, 128), dhi(SBO, 0), 1, 1>(d, 0);
  MM<N>::template ss<dlo(WA + 4096, 0), dhi(1024, 1), dlo(OB + 512, 128), dhi(SBO, 0), 1, 1>(d, 0);
  MM<N>::template ss<dlo(WA + 6144, 0), dhi(1024, 1), dlo(OB + 768, 128), dhi(SBO, 0), 1, 1>(d, 0);
}
__device__ __forceinline__ void wo_coord(int i, int t3, int head, int& c0, int& c1) {
  const int g = i >> 1;
  const int blk = g == 0 ? 9 : (g < 4 ? g - 1 : (g - 4) >> 1) * 3 + t3;
  int sl = g < 4 ? t3 : (g & 1) ? t3 + 1 : t3 + 2;
  if (sl >= 3) sl -= 3;
  c0 = blk * 64; c1 = head * DH + sl * 64 + (i & 1) * 32;
}
__device__ __forceinline__ void tok_softmax(uint32_t sb, int job, int lane) {
  const bool w1 = job & 1;
  const int dg = (lane >> 2) - (lane & 3) * 2;
  const uint32_t lo = sb + OFF_PL + (job >> 1) * PL_SZ + (job & 1) * 1792, l8 = lo + 512 + lane * 8, pa = lo + lane * 4;
  const uint32_t km = job & 2 ? 640 : 512;
  float x[14];
  {
    const uint4 a = lds128(lo + lane * 16);
    const uint2 e = lds64(l8);
    const uint32_t c = lds32(768 + pa);
    x[0] = bf_lo(a.x); x[1] = bf_hi(a.x); x[2] = bf_lo(a.y); x[3] = bf_hi(a.y); x[4] = bf_lo(a.z); x[5] = bf_hi(a.z); x[6] = bf_lo(a.w); x[7] = bf_hi(a.w);
    x[8] = bf_lo(c); x[9] = bf_hi(c); x[10] = bf_lo(e.x); x[11] = bf_hi(e.x); x[12] = bf_lo(e.y); x[13] = bf_hi(e.y);
  }
  if (dg < 0) { x[8] = -INFINITY; if (w1) x[4] = -INFINITY; else x[10] = -INFINITY; }
  if (dg < 1) { x[9] = -INFINITY; if (w1) x[5] = -INFINITY; else x[11] = -INFINITY; }
  const float m4 = fmaxf(x[8], x[9]);
  float m0 = fmaxf(fmaxf(fmaxf(x[0], x[1]), fmaxf(x[2], x[3])), fmaxf(fmaxf(x[4], x[5]), fmaxf(x[6], x[7])));
  float m1 = fmaxf(fmaxf(x[10], x[11]), fmaxf(x[12], x[13]));
  if (w1) m1 = fmaxf(m1, m4); else m0 = fmaxf(m0, m4);
  m0 = fmaxf(m0, __shfl_xor_sync(~0u, m0, 1)); m1 = fmaxf(m1, __shfl_xor_sync(~0u, m1, 1));
  sts32(pa + (w1 ? 384 : 896 + 128), 0u); sts32(pa + 1152 - km, 0u); sts32(pa + 896 + 1152 - km, 0u); sts64(l8 + 896 - 256, 0u, 0u);
  m0 = fmaxf(m0, __shfl_xor_sync(~0u, m0, 2)); m1 = fmaxf(m1, __shfl_xor_sync(~0u, m1, 2));
  m0 *= -SL2; m1 *= -SL2;
#pragma unroll
  for (int j = 0; j < 14; j++) x[j] = ex2(fmaf(x[j], SL2, j < 8 ? m0 : j >= 10 ? m1 : w1 ? m1 : m0));
  const float l4s = x[8] + x[9];
  float l0 = ((x[0] + x[1]) + (x[2] + x[3])) + ((x[4] + x[5]) + (x[6] + x[7])), l1 = (x[10] + x[11]) + (x[12] + x[13]);
  if (w1) l1 += l4s; else l0 += l4s;
  l0 += __shfl_xor_sync(~0u, l0, 1); l1 += __shfl_xor_sync(~0u, l1, 1);
  l0 += __shfl_xor_sync(~0u, l0, 2); l1 += __shfl_xor_sync(~0u, l1, 2);
  l0 = rcpf(l0); l1 = rcpf(l1);
#pragma unroll
  for (int j = 0; j < 7; j++) {
    const float iv = j < 4 ? l0 : j > 4 ? l1 : w1 ? l1 : l0;
    sts32(pa + (j < 3 ? j * 128 : j == 3 ? km : j == 4 ? (w1 ? 896 + 128 : 384) : j == 5 ? 896 : 896 + km), pack2(x[2 * j] * iv, x[2 * j + 1] * iv));
  }
}
template <int N>
__device__ __forceinline__ void wo_phase(uint32_t sb, int wg, int warp, int lane, uint32_t par, uint32_t r1) {
  const uint32_t bar = sb + OFF_BAR;
  float x[N / 2], y[N / 2];
  const uint2 ta = lds64(sb + OFF_TAB + (wg * 4 + warp) * 8);
  uint32_t xa = (ta.x & ~255u) + lane * 8, xb = (ta.x & 0xFF0000FFu) + SMEM0 + OFF_BAR, ya = (ta.y & ~255u) + lane * 8, yb = (ta.y & 0xFF0000FFu) + SMEM0 + OFF_BAR;
  asm volatile("" : "+r"(xa), "+r"(xb), "+r"(ya), "+r"(yb));
  auto scat = [&](uint32_t ad, uint32_t mb, const float* d) {
    st_async_v2(ad, pack2(d[0], d[1]), pack2(d[2], d[3]), mb);
    if (N == 16) st_async_v2(ad + LAND_F, pack2(d[4], d[5]), pack2(d[6], d[7]), mb);
  };
  if (wg == 0) {
    bar_sync(N_O, 384);
    wg_fence(); wo4<N, 4, 0, 0>(x); wo4<N, 8, 0, 0>(y); wg_commit();
    mbar_waitu(bar + 8 * B_OPEER, par);
    CFENCE(); wg_fence(); wo4<N, 16, 1, 1>(x); wo4<N, 20, 2, 1>(x); wg_commit();
    wo4<N, 24, 1, 1>(y); wg_commit();
    mbar_waitu2(bar + 8 * B_WOF, bar + 8 * B_MEMFREE, par);
    wg_fence(); wo4<N, 28, 2, 1>(y); wg_commit();
    bar_arrive(N_AB, 256);
    wg_wait<2>(); scat(xa, xb, x);
    wg_wait<0>(); scat(ya, yb, y);
  } else {
    bar_sync(N_O, 384);
    wg_fence(); wo4<N, 0, 0, 0>(x); wg_commit(); wo4<N, 12, 0, 0>(y); wg_commit();
    wg_wait<1>(); mbar_arrive_remote_if(lane == 0, r1);
    mbar_waitu(bar + 8 * B_MEMFREE, par);
    scat(xa, xb, x);
    bar_sync(N_AB, 256);
    CFENCE(); wg_fence(); wo4<N, 32, 1, 1>(y); wo4<N, 36, 2, 1>(y); wg_commit();
    bar_arrive(N_TURN, 256);
    wg_wait<0>(); scat(ya, yb, y);
  }
}
#define DS_DUAL 10
#define DS_SINGLE 20
#define POLL_GAP 100
#define POLL_GAPD 0
#define TOK_DELAY 250
#define LATE_SM 1
#define UMAX 40
#define VD1 6
#define VS1 4
#define VST 17
struct AMaps { CUtensorMap w16[3], wo32; };
__global__ void __launch_bounds__(512, 1)
acore_kernel(const __grid_constant__ AMaps M, const __nv_bfloat16* __restrict__ mem0, int sync_b) {
  extern __shared__ __align__(1024) unsigned char smem_raw[];
  const uint32_t sb = smem_u32(smem_raw);
  GTS(24);
  if (threadIdx.x == 0) {
    uint32_t smid; asm volatile("mov.u32 %0, %%smid;" : "=r"(smid));
    g_tpc[(smid >> 1) & 127] = blockIdx.x - CL_SIZE < 3 * CL_SIZE && blockIdx.x % CL_SIZE >= 12 ? 1 : 2;
    __threadfence();
    asm volatile("griddepcontrol.launch_dependents;");
  }
  const int lane0 = threadIdx.x & 31;
#define LANE_INIT() int lane; asm volatile("mov.u32 %0, %%laneid;" : "=r"(lane))
  const int warp = __shfl_sync(~0u, (threadIdx.x >> 5) & 3, 0);
  const int cl = blockIdx.x / CL_SIZE;
  const uint32_t rank = blockIdx.x - cl * CL_SIZE;
  const int nh = cl >= 1 && cl <= 3 ? 4 : 5;
  const int nA = 3 * nh;
  const int wg = __shfl_sync(~0u, (int)rank < nA ? threadIdx.x >> 7 : 4, 0);
  const int head = (cl < 4 ? (cl ? 1 + 4 * cl : 0) : 5 * cl - 3) + rank / 3;
  const int t3 = rank % 3;
  const int col0 = head * DH + t3 * 64;
  const uint32_t bar = sb + OFF_BAR;
  const uint32_t rb0 = SMEM0;
  const uint16_t mcmask = (uint16_t)((1u << nA) - 1);
  const uint32_t nxt = sb + ((t3 == 2 ? -2 : 1) << 24), prv = sb + ((t3 == 0 ? 2 : -1) << 24);
  const int ig = (int)rank - (nA - 4);

  if (threadIdx.x == 0) {
    if (mapa(sb, nA - 1) != rb0 + ((nA - 1) << 24) || mapa(sb, 0) != rb0 || mapa(sb, 1) != rb0 + (1u << 24) || sb != SMEM0 + (rank << 24)) FAIL();
    for (int i = 0; i < B_NUM; i++)
      mbar_init(bar + 8 * i, i == B_R1 ? 4 * nA : i == B_R2 ? 12 * nA : i == B_MEMFREE ? nA : i == B_LANDFREE ? 4 * nA : i == B_PLFREE || i == B_XFREE ? 2 : 1);
    asm volatile("fence.mbarrier_init.release.cluster;" ::: "memory");
    mbar_expect(bar + 8 * B_W0, (80 + SSV + VST) * 2048);
  }
  __syncthreads();
  if (lane0 == 0) {
    const int w12 = wg * 4 + warp;
    if (w12 < 10) {
#pragma unroll 1
      for (int ks = 4 * w12; ks < 4 * w12 + 4; ks++) {
        const bool ss = is_ss(ks, SSQ);
        tma2d(ss ? sb + OFF_WS + ss_idx(ks, SSQ) * 2048 : sb + STG_Q + rs_idx(ks, SSQ) * 2048, &M.w16[0], col0, ks * 16, bar + 8 * B_W0);
        tma2d(ss ? sb + OFF_WS + (SSQ + ss_idx(ks, SSQ)) * 2048 : sb + STG_K + rs_idx(ks, SSQ) * 2048, &M.w16[1], col0, ks * 16, bar + 8 * B_W0);
        if (is_ss(ks, SSV)) tma2d(sb + OFF_WS + (2 * SSQ + ss_idx(ks, SSV)) * 2048, &M.w16[2], col0, ks * 16, bar + 8 * B_W0);
        else if (rs_idx(ks, SSV) < VST) tma2d(sb + (rs_idx(ks, SSV) < VA ? STG_K + 27 * 2048 : STG_V2 - VA * 2048) + rs_idx(ks, SSV) * 2048, &M.w16[2], col0, ks * 16, bar + 8 * B_W0);
        else tma2d_prefetch(&M.w16[2], col0, ks * 16);
      }
      int c0, c1;
      wo_coord(2 * w12, t3, head, c0, c1);
      tma2d_prefetch(&M.wo32, c0, c1);
      tma2d_prefetch(&M.wo32, c0, c1 + 32);
    }
  }
  static_assert(40 - SSV - VST <= 10, "staging");
  if (lane0 < 2 && wg < 2) {
    const int u = 4 * (wg ? (lane0 ? 6 + t3 : 9) : (lane0 ? 3 + t3 : t3)) + warp;
    const int li = (u >= nA) + (u >= 2 * nA) + (u >= 3 * nA);
    sts32(sb + OFF_TAB + (wg * 4 + warp) * 8 + lane0 * 4,
          rb0 + ((u - li * nA) << 24) + OFF_TILE + LAND(li + (u >= 36 ? t3 : 0)) + (rank / 3) * 256 + 8 * (B_RS + li));
  }
  __syncthreads();
  GTS(25);

  auto issue_tok = [&](int sc, int fb, int rel = -1, uint32_t ph = 0) {
    if (sync_b) wait_cnt(&g_xready[sc][0], 32);
    if (rel >= 0) mbar_waitu(bar + 8 * rel, ph);
    bulk_g2s_mc_e(sb + OFF_TILE + ig * TILE_GRP + TILE_SBO, &g_xn[0][0] + uni(sc * (32 * DM)) + ig * 5120, 10240, bar + 8 * (fb + ig), mcmask);
  };
#define POLL(d, q) _Pragma("unroll") for (int k = 0; k < NCL; k++) \
      asm volatile("ld.relaxed.gpu.global.v2.b32 {%0,%1}, [%2];" : "=r"(d[k].x), "=r"(d[k].y) : "l"(q + k * 2560) : "memory")
#define L3(L, a, b, c) lop3<L>(a, b, c)
#define TAGS(L, d) L3(L, L3(L, L3(L, d[0].x, d[0].y, d[1].x), L3(L, d[1].y, d[2].x, d[2].y), L3(L, d[3].x, d[3].y, d[4].x)), L3(L, d[4].y, d[5].x, d[5].y), L3(L, d[6].x, d[6].y, d[6].y))
    auto deliver = [&](uint2* pa, const uint32_t* gq, int u, int c, int dc, int ds, int step, bool first, int lane) {
      const uint32_t off = uni(OFF_TILE + ((u * 205) >> 11) * (TILE_GRP - TILE_SBO) + u * 256 + dc * LAND_F), boff = uni(OFF_BAR + 8 * (B_F1 + ((u * 205) >> 11)));
      const uint32_t* mi = &g_part[4][0][0][0] + uni((c * NCL + cl) * 2560 + u * 64);
      mbar_waitu(bar + 8 * B_LANDFREE, step & 1);
      int n = 0;
      while (true) {
        const bool ok = __all_sync(~0u, ((step & 2 ? ~TAGS(0xFE, pa) : TAGS(0x80, pa)) & 1) != 0);
        if (ok) break;
        if (++n > SPIN_LIMIT) FAIL();
        POLL(pa, gq);
      }
      if (warp == 0 && first) { TS(19); TSV(10, n); }
      const uint32_t w0 = hadd2bf(hadd2bf(hadd2bf(pa[0].x, pa[1].x), hadd2bf(pa[2].x, pa[3].x)), hadd2bf(hadd2bf(pa[4].x, pa[5].x), pa[6].x));
      const uint32_t w1 = hadd2bf(hadd2bf(hadd2bf(pa[0].y, pa[1].y), hadd2bf(pa[2].y, pa[3].y)), hadd2bf(hadd2bf(pa[4].y, pa[5].y), pa[6].y));
      if (u < ds) {
        const uint32_t da = SMEM0 + off + lane * 8, db = SMEM0 + boff;
#pragma unroll
        for (int d = 0; d < 12; d++) st_async_v2((d << 24) + da, w0, w1, (d << 24) + db);
#pragma unroll
        for (int d = 12; d < 15; d++) st_async_v2_if(nA == 15, (d << 24) + da, w0, w1, (d << 24) + db);
      } else {
        *reinterpret_cast<uint2*>(const_cast<uint32_t*>(gq) + ((4 - 2 * (step & 1)) * NCL + cl) * 2560) = make_uint2(w0, w1);
        asm volatile("fence.proxy.async.global;" ::: "memory");
        __syncwarp();
        bulk_g2s_mc_e(sb + off, mi, 256, sb + boff, mcmask);
      }
    };
#define REL(b, g) mbar_arrive_remote_if(lane == 0, rb0 + ((nA - 4 + (g)) << 24) + OFF_BAR + 8 * (b))

  if (wg < 2) {
    asm volatile("setmaxnreg.inc.sync.aligned.u32 160;");
    LANE_INIT();
    uint32_t W[4 * (40 - SSQ)];
    mbar_waitw(bar + 8 * B_W0, 0);
    GTS(26);
    load_w<40 - SSQ>(W, sb + (wg ? STG_K : STG_Q), warp, lane);
    fence_async();
    bar_sync(1, 384);
    cluster_sync_all();
    const uint32_t wbase = wg * SSQ;
    GTS(27);
#pragma unroll 1
    for (int step = -1; step < NSTEP; step++) {
      const uint32_t par = step & 1;
      asm volatile("" : "+r"(lane));
      const bool dual = is_dual(step), has_next = step + 1 < NSTEP;
#define QK_SA (sb + OFF_QK + wg * 15360 + (2 * warp + ((lane >> 3) & 1)) * 128 + (lane & 7) * 16)
#define QK_F (wg ? -5120 : 5120)
#define QK_S12 ((wg ? (lane >> 4) : 1 + 2 * (lane >> 4)) * 1024)
#define QK_S34 ((wg ? 2 + (lane >> 4) : 2 - 2 * (lane >> 4)) * 1024)
      if (step >= 0) {
        if (dual) {
          float acc[24];
          mbar_waitu(bar + 8 * (B_F1 + 0), par);
          if (wg + warp == 0) { TS(0); TSN(1); }
          CFENCE(); wg_fence(); proj<48, SSQ, 0, 0, 10>(acc, W, wbase); wg_commit();
          mbar_waitu(bar + 8 * (B_F1 + 1), par);
          CFENCE(); wg_fence(); proj<48, SSQ, 0, 10, 20>(acc, W, wbase); wg_commit();
          mbar_waitu(bar + 8 * (B_F1 + 2), par);
          CFENCE(); wg_fence(); proj<48, SSQ, 0, 20, 30>(acc, W, wbase); wg_commit();
          mbar_waitu2(bar + 8 * (B_F1 + 3), bar + 8 * B_PLFREE, par);
          if (wg + warp == 0) TS(2);
          CFENCE(); wg_fence(); proj<48, SSQ, 0, 30, 40>(acc, W, wbase); wg_commit();
          bar_arrive(N_VGO, 384);
          const uint32_t sa = QK_SA, s0 = sa + 4096 + (lane >> 4) * QK_F, s1 = sa + QK_F + QK_S12, s2 = sa + QK_F + QK_S34;
          wg_wait<0>();
          if (wg + warp == 0) TS(3);
          stsm4t(s0, pack2(acc[0], acc[1]), pack2(acc[2], acc[3]), pack2(acc[20], acc[21]), pack2(acc[22], acc[23]));
          stsm4t(s1, pack2(acc[4], acc[5]), pack2(acc[6], acc[7]), pack2(acc[8], acc[9]), pack2(acc[10], acc[11]));
          stsm4t(s2, pack2(acc[12], acc[13]), pack2(acc[14], acc[15]), pack2(acc[16], acc[17]), pack2(acc[18], acc[19]));
        } else {
          float acc[4];
          mbar_waitu(bar + 8 * (B_F1 + 0), par);
          if (wg + warp == 0) { TS(0); TSN(1); }
          CFENCE(); wg_fence(); proj<8, SSQ, 0, 0, 10>(acc, W, wbase); wg_commit();
          mbar_waitu(bar + 8 * (B_F1 + 1), par);
          CFENCE(); wg_fence(); proj<8, SSQ, 0, 10, 20>(acc, W, wbase); wg_commit();
          mbar_waitu(bar + 8 * (B_F1 + 2), par);
          CFENCE(); wg_fence(); proj<8, SSQ, 0, 20, 30>(acc, W, wbase); wg_commit();
          mbar_waitu2(bar + 8 * (B_F1 + 3), bar + 8 * B_PLFREE, par);
          if (wg + warp == 0) TS(2);
          CFENCE(); wg_fence(); proj<8, SSQ, 0, 30, 40>(acc, W, wbase); wg_commit();
          bar_arrive(N_VGO, 384);
          const uint32_t s0 = QK_SA + 4096;
          wg_wait<0>();
          if (wg + warp == 0) TS(3);
          stsm2t(s0, pack2(acc[0], acc[1]), pack2(acc[2], acc[3]));
        }
        fence_async();
        bar_sync(N_QK, 256);
        if (wg == 0 || dual) {
          float s[20];
          const uint32_t ab = wg * 192, bb = wg * -320;
          wg_fence();
          MM<40>::ss2<dlo(OFF_QK, 128), dhi(1024, 0), dlo(OFF_QK + 15360, 128), dhi(1024, 0), 0>(s, ab, bb);
          MM<40>::ss2<dlo(OFF_QK + 256, 128), dhi(1024, 0), dlo(OFF_QK + 15360 + 256, 128), dhi(1024, 0), 1>(s, ab, bb);
          MM<40>::ss2<dlo(OFF_QK + 512, 128), dhi(1024, 0), dlo(OFF_QK + 15360 + 512, 128), dhi(1024, 0), 1>(s, ab, bb);
          MM<40>::ss2<dlo(OFF_QK + 768, 128), dhi(1024, 0), dlo(OFF_QK + 15360 + 768, 128), dhi(1024, 0), 1>(s, ab, bb);
          wg_commit();
          bar_arrive(N_SISS, 384);
          const int rw = (warp - wg) & 3;
          const uint32_t bo = OFF_BAR + 8 * (B_SB + 3 * wg + rw), lo = OFF_PL + wg * PL_SZ + rw * 1792;
          const uint32_t km = wg ? 640 : 512;
          uint32_t l16 = lo + lane * 16, l4 = lo + lane * 4;
          mbar_expect_if(lane == 0 && rw < 3, sb + bo, rw < 2 ? 1792 : 1280);
          asm volatile("" : "+r"(l16), "+r"(l4));
          if (rw == 2) {
            wg_wait<0>();
            if (wg == 0) TSD(4, __float_as_uint(s[0]));
            {
              const uint32_t w0 = pack2(s[0], s[1]), w1 = pack2(s[4], s[5]), w2 = pack2(s[8], s[9]), w3 = pack2(s[12], s[13]), w4 = pack2(s[16], s[17]);
              st_async_v4(nxt + 896 + l16, w0, w1, w2, w3, nxt + bo);
              st_async_v4(prv + l16, w0, w1, w2, w3, prv + bo);
              st_async_b32(nxt + 896 + 768 + l4, w4, nxt + bo);
              st_async_b32(prv + 768 + l4, w4, prv + bo);
            }
            bar_arrive(N_SDONE, 256);
            mbar_waitu(sb + bo, (step - wg * LAG) & 1);
            if (wg == 0) TS(5);
            float x[10];
            {
              const uint4 a = lds128(sb + l16), b = lds128(sb + 896 + l16);
              const uint32_t c = lds32(sb + 768 + l4), d = lds32(sb + 896 + 768 + l4);
              const uint32_t e0 = hadd2bf(a.x, b.x), e1 = hadd2bf(a.y, b.y), e2 = hadd2bf(a.z, b.z), e3 = hadd2bf(a.w, b.w), e4 = hadd2bf(c, d);
              x[0] = s[0] + bf_lo(e0); x[1] = s[1] + bf_hi(e0); x[2] = s[4] + bf_lo(e1); x[3] = s[5] + bf_hi(e1); x[4] = s[8] + bf_lo(e2);
              x[5] = s[9] + bf_hi(e2); x[6] = s[12] + bf_lo(e3); x[7] = s[13] + bf_hi(e3); x[8] = s[16] + bf_lo(e4); x[9] = s[17] + bf_hi(e4);
            }
            float m0 = fmaxf(fmaxf(fmaxf(x[0], x[1]), fmaxf(x[2], x[3])), fmaxf(fmaxf(x[4], x[5]), fmaxf(fmaxf(x[6], x[7]), fmaxf(x[8], x[9]))));
            m0 = fmaxf(m0, __shfl_xor_sync(~0u, m0, 1));
            sts32(sb + l4 + 1152 - km, 0u);
            m0 = fmaxf(m0, __shfl_xor_sync(~0u, m0, 2));
            m0 *= -SL2;
#pragma unroll
            for (int j = 0; j < 5; j++) {
              x[2 * j] = ex2(fmaf(x[2 * j], SL2, m0)); x[2 * j + 1] = ex2(fmaf(x[2 * j + 1], SL2, m0));
              sts32(sb + l4 + (j < 4 ? j * 128 : km), pack2(x[2 * j], x[2 * j + 1]));
            }
            float l = ((x[0] + x[1]) + (x[2] + x[3])) + ((x[4] + x[5]) + ((x[6] + x[7]) + (x[8] + x[9])));
            l += __shfl_xor_sync(~0u, l, 1);
            fence_async();
            sts32(sb + OFF_INV + wg * 64 + (lane >> 1) * 4, __float_as_uint(l));
            bar_arrive(N_PM, dual ? 224 : 192);
            if (wg == 0) TS(6);
          } else if (rw < 2) {
            const bool w1 = rw == 1;
            const uint32_t l8 = lo + 512 + lane * 8;
            uint32_t tw[7];
            wg_wait<0>();
            bar_arrive(N_SDONE, 256);
            tw[0] = pack2(s[0], s[1]); tw[1] = pack2(s[4], s[5]); tw[2] = pack2(s[8], s[9]); tw[3] = pack2(s[16], s[17]);
            tw[4] = w1 ? pack2(s[6], s[7]) : pack2(s[12], s[13]); tw[5] = pack2(s[2], s[3]); tw[6] = pack2(s[18], s[19]);
            { const uint32_t t0 = clock32(); while (clock32() - t0 < TOK_DELAY) {} }
            st_async_v4(nxt + 896 + l16, tw[0], tw[1], tw[2], tw[3], nxt + bo);
            st_async_v4(prv + l16, tw[0], tw[1], tw[2], tw[3], prv + bo);
            st_async_v2(nxt + 896 + l8, tw[5], tw[6], nxt + bo);
            st_async_v2(prv + l8, tw[5], tw[6], prv + bo);
            st_async_b32(nxt + 896 + 768 + l4, tw[4], nxt + bo);
            st_async_b32(prv + 768 + l4, tw[4], prv + bo);
            mbar_waitu(sb + bo, (step - wg * LAG) & 1);
            const uint4 a = lds128(sb + l16), b = lds128(sb + 896 + l16);
            const uint2 e = lds64(sb + l8), f = lds64(sb + 896 + l8);
            const uint32_t c = lds32(sb + 768 + l4), d = lds32(sb + 896 + 768 + l4);
            sts128(sb + l16, hadd2bf(hadd2bf(a.x, b.x), tw[0]), hadd2bf(hadd2bf(a.y, b.y), tw[1]), hadd2bf(hadd2bf(a.z, b.z), tw[2]), hadd2bf(hadd2bf(a.w, b.w), tw[3]));
            sts64(sb + l8, hadd2bf(hadd2bf(e.x, f.x), tw[5]), hadd2bf(hadd2bf(e.y, f.y), tw[6]));
            sts32(sb + 768 + l4, hadd2bf(hadd2bf(c, d), tw[4]));
            bar_arrive(N_PX, dual ? 256 : 192);
            if (wg + warp == 0) TS(9);
          } else {
            wg_wait<0>();
            if (wg == 0) {
              mbar_expect_if(lane < 3 && has_next, bar + 8 * (lane == 2 ? B_OPEER : B_WOF + lane), lane == 2 ? (dual ? 4096 : 2048) : lane ? 8192 : 20480);
              auto fetch = [&](int i, int n, uint32_t dst, int mb) {
                int c0, c1; wo_coord(i, t3, head, c0, c1);
                tma2d_e(dst, &M.wo32, c0, c1, bar + 8 * mb); if (n == 2) tma2d_e(dst + 4096, &M.wo32, c0, c1 + 32, bar + 8 * mb);
              };
              bar_sync(N_G3, 160);
              if (has_next) {
                fetch(0, 2, sb + OFF_WT, B_WTF);
                mbar_arrive_remote_if(lane < 2, (lane ? nxt : prv) + OFF_BAR + 8 * B_XFREE);
              }
              bar_sync(N_SDONE, 256);
              if (has_next) {
                fetch(15, 1, sb + OFF_QK, B_WOF); fetch(16, 2, sb + OFF_QK + 4096, B_WOF); fetch(18, 2, sb + OFF_QK + 12288, B_WOF);
                mbar_waitu(bar + 8 * B_XFREE, par);
              }
              bar_arrive(N_PM, dual ? 224 : 192);
              bar_sync(N_VDONE, 160);
              mbar_arrive_remote_if(lane < nA && has_next, rb0 + (lane << 24) + OFF_BAR + 8 * B_MEMFREE);
              if (has_next) mbar_waitu(bar + 8 * B_WTF, par);
            } else {
              bar_arrive(N_SDONE, 256);
              if ((unsigned)ig < 3) issue_tok(sched_l(step + 1), B_F2, B_R1, (step - LAG) & 1);
            }
          }
        } else {
          bar_arrive(N_SISS, 384);
          bar_arrive(N_SDONE, 256);
        }
        if (has_next) {
          if (step == 0) mbar_waitw(bar + 8 * B_W0, 1);
          const uint32_t r1 = rb0 + ((nA - 1) << 24) + OFF_BAR + 8 * B_R1;
          if (dual) wo_phase<16>(sb, wg, warp, lane, par, r1); else wo_phase<8>(sb, wg, warp, lane, par, r1);
          bar_arrive(N_C, 288);
          if (warp == 0) TS(7 + wg);
        }
      }
      if (has_next) {
        float acc[16];
        mbar_waitu(bar + 8 * B_F2, par ^ 1);
        wg_fence(); proj<32, SSQ, 1, 0, 10>(acc, W, wbase); wg_commit();
        mbar_waitu(bar + 8 * (B_F2 + 1), par ^ 1);
        wg_fence(); proj<32, SSQ, 1, 10, 14>(acc, W, wbase); wg_commit();
        wg_wait<1>(); REL(B_R2, 0);
        wg_fence(); proj<32, SSQ, 1, 14, 20>(acc, W, wbase); wg_commit();
        mbar_waitu(bar + 8 * (B_F2 + 2), par ^ 1);
        wg_fence(); proj<32, SSQ, 1, 20, 24>(acc, W, wbase); wg_commit();
        wg_wait<1>(); REL(B_R2, 1);
        wg_fence(); proj<32, SSQ, 1, 24, 30>(acc, W, wbase); wg_commit();
        mbar_waitu(bar + 8 * (B_F2 + 3), par ^ 1);
        wg_fence(); proj<32, SSQ, 1, 30, 34>(acc, W, wbase); wg_commit();
        wg_wait<1>(); REL(B_R2, 2);
        wg_fence(); proj<32, SSQ, 1, 34, 40>(acc, W, wbase); wg_commit();
        const uint32_t sa = QK_SA, s1 = sa + QK_S12, s2 = sa + QK_S34;
        wg_wait<0>(); REL(B_R2, 3);
        if (warp == 0) TS(11 + wg);
        stsm4t(s1, pack2(acc[0], acc[1]), pack2(acc[2], acc[3]), pack2(acc[4], acc[5]), pack2(acc[6], acc[7]));
        stsm4t(s2, pack2(acc[8], acc[9]), pack2(acc[10], acc[11]), pack2(acc[12], acc[13]), pack2(acc[14], acc[15]));
      }
    }
    GTS(28);
    cluster_sync_all();
  } else if (wg == 2) {
    asm volatile("setmaxnreg.inc.sync.aligned.u32 160;");
    LANE_INIT();
    uint32_t W[4 * (40 - SSV)];
    mbar_waitw(bar + 8 * B_W0, 0);
    load_w<VA>(W, sb + STG_K + 27 * 2048, warp, lane);
    load_w<VST - VA>(W + 4 * VA, sb + STG_V2, warp, lane);
    fence_async();
    bar_sync(1, 384);
    if (lane == 0) {
      if (warp == 0) {
        mbar_expect(bar + 8 * B_W1, (40 - SSV - VST) * 2048);
#pragma unroll 1
        for (int ks = 0; ks < 40; ks++)
          if (!is_ss(ks, SSV) && rs_idx(ks, SSV) >= VST) tma2d(sb + OFF_QK + (rs_idx(ks, SSV) - VST) * 2048, &M.w16[2], col0, ks * 16, bar + 8 * B_W1);
      } else {
        if (warp == 1) mbar_expect(bar + 8 * B_W0, 26 * 2048);
#pragma unroll 1
        for (int i = warp - 1; i < 13; i += 3) { int c0, c1; wo_coord(i + 2, t3, head, c0, c1); tma2d(sb + OFF_WO + i * 4096, &M.wo32, c0, c1, bar + 8 * B_W0); }
      }
    }
    __syncwarp();
#pragma unroll
    for (int i = 0; i < 5; i++) {
      const int t = i * 128 + warp * 32 + lane;
      const uint4 v = *reinterpret_cast<const uint4*>(mem0 + ((t >> 1) & 7) * DM + (t >> 4) * 16 + ((t ^ (t >> 3)) & 1) * 8);
      sts128(sb + OFF_TILE + (t / 160) * (TILE_GRP - TILE_SBO) + t * 16, v.x, v.y, v.z, v.w);
    }
    mbar_waitw(bar + 8 * B_W1, 0);
    load_w<40 - SSV - VST>(W + 4 * VST, sb + OFF_QK, warp, lane);
    fence_async();
    mbar_arrive_if(lane == 0, bar + 8 * (B_F1 + warp));
    mbar_expect_if(lane == 0, bar + 8 * (B_F2 + warp), 10240);
    mbar_arrive_if(warp == 3 && lane < 2, bar + 8 * B_PLFREE);
    cluster_sync_all();
    uint32_t vl[8];
    constexpr uint32_t wbase = 2 * SSQ;
    {
      float v[16];
      mbar_waitw4(bar + 8 * B_F2, 0);
      wg_fence(); proj<32, SSV, 1, 0, 40>(v, W, wbase); wg_commit();
      wg_wait<0>();
      mbar_arrive_remote_if(lane < 4, rb0 + ((nA - 4 + lane) << 24) + OFF_BAR + 8 * B_R2);
#pragma unroll
      for (int j = 0; j < 8; j++) vl[j] = pack2v(v[2 * j], v[2 * j + 1]);
      if (warp == 0 && (unsigned)ig < 3) issue_tok(1, B_F2, B_R2, 0);
    }
#pragma unroll 1
    for (int step = 0; step < NSTEP; step++) {
      const uint32_t par = step & 1;
      asm volatile("" : "+r"(lane));
      const bool dual = is_dual(step), has_next = step + 1 < NSTEP;
      mbar_expect_if(lane == 0 && has_next, bar + 8 * (B_F2 + warp), 10240);
      if (warp == 0 && ig == 3 && has_next && sync_b) wait_cnt(&g_xready[sched_l(step + 1)][0], 32);
      bar_sync(N_VGO, 384);
      CFENCE();
#define F1_BYTES (is_dual(step + 1) ? 15360 : 2560)
#define ARM() do { \
        mbar_expect_if(lane == 0 && has_next, bar + 8 * (B_F1 + warp), F1_BYTES); \
        mbar_expect_if(lane == 0 && has_next && warp * nA + (int)rank < 40, bar + 8 * (B_RS + warp), (warp * nA + (int)rank >= 36 ? nA : nh) * (dual ? 512 : 256)); } while (0)
#define O_ADDR() uint32_t oa = sb + OFF_O + (lane >> 4) * PL_SZ + warp * 256 + (lane & 15) * 16, xo = (lane >> 4) * 1024 + warp * 256 + (lane & 15) * 16; \
        asm volatile("" : "+r"(oa), "+r"(xo))
#define O_READY(act) do { if (has_next) { const uint4 ov = lds128(oa); \
        if (act) { st_async_v4(nxt + OFF_XL + xo, ov.x, ov.y, ov.z, ov.w, nxt + OFF_BAR + 8 * B_OPEER); \
                   st_async_v4(prv + OFF_XF + xo, ov.x, ov.y, ov.z, ov.w, prv + OFF_BAR + 8 * B_OPEER); } \
        fence_async(); bar_arrive(N_O, 384); } \
        if (warp == 0) TS(15); } while (0)
#define TOK_L3() if (warp == 0 && ig == 3 && has_next) { mbar_waitu(bar + 8 * B_R1, par); \
        bulk_g2s_mc_e(sb + OFF_TILE + 3 * TILE_GRP + TILE_SBO, &g_xn[0][0] + uni(sched_l(step + 1) * (32 * DM)) + 3 * 5120, 10240, bar + 8 * (B_F2 + 3), mcmask); }
#define OX_SA (sb + OFF_PL + (lane & 7) * 128 + (((warp * 2 + ((lane >> 3) & 1)) ^ (lane & 7)) << 4))
      if (dual) {
        uint32_t vf[8], vm[4], vn[8];
        {
          float v[24];
          wg_fence(); proj<48, SSV, 0, 30, 30 + VD1, 30>(v, W, wbase); wg_commit();
          ARM();
          bar_sync(N_SISS, 384);
          wg_fence(); proj<48, SSV, 0, 30 + VD1, 40, 30>(v, W, wbase); wg_commit();
          proj<48, SSV, 0, 0, 3, 30>(v, W, wbase); wg_commit();
          wg_wait<1>(); bar_arrive(N_G3, 160);
          wg_fence(); proj<48, SSV, 0, 3, 10, 30>(v, W, wbase); wg_commit();
          proj<48, SSV, 0, 10, 13, 30>(v, W, wbase); wg_commit();
          wg_wait<1>(); REL(B_R1, 0);
          wg_fence(); proj<48, SSV, 0, 13, 20, 30>(v, W, wbase); wg_commit();
          proj<48, SSV, 0, 20, 23, 30>(v, W, wbase); wg_commit();
          wg_wait<1>(); REL(B_R1, 1);
          wg_fence(); proj<48, SSV, 0, 23, 30, 30>(v, W, wbase); wg_commit();
          wg_wait<0>(); REL(B_R1, 2);
          bar_arrive(N_VDONE, 160);
          if (warp == 0) TS(14);
#pragma unroll
          for (int j = 4; j < 8; j++) vf[j] = pack2v(v[4 + 2 * j], v[5 + 2 * j]);
          keep4(vf + 4, lane);
          vm[0] = pack2v(v[0], v[1]); vm[1] = pack2v(v[2], v[3]); vm[2] = pack2v(v[20], v[21]); vm[3] = pack2v(v[22], v[23]);
          keep4(vm, lane);
#pragma unroll
          for (int j = 0; j < 4; j++) vf[j] = pack2v(v[4 + 2 * j], v[5 + 2 * j]);
          keep4(vf, lane);
        }
        {
          float o[8];
          O_ADDR();
          bar_sync(N_PM, 224);
          wg_fence();
          MM<8>::rs<dlo(OFF_PL + 3584, 128), dhi(896, 0), 0>(o, vl[0], vl[1], vl[2], vl[3]);
          MM<8>::rs<dlo(OFF_PL + PL_SZ + 3584, 128), dhi(896, 0), 0>(o + 4, vf[0], vf[1], vf[2], vf[3]);
          MM<8>::rs<dlo(OFF_PL + 3584 + 256, 128), dhi(896, 0), 1>(o, vl[4], vl[5], vl[6], vl[7]);
          MM<8>::rs<dlo(OFF_PL + PL_SZ + 3584 + 256, 128), dhi(896, 0), 1>(o + 4, vf[4], vf[5], vf[6], vf[7]);
          MM<8>::rs<dlo(OFF_PL + 3584 + 512, 128), dhi(896, 0), 1>(o, vm[0], vm[1], vm[2], vm[3]);
          MM<8>::rs<dlo(OFF_PL + PL_SZ + 3584 + 512, 128), dhi(896, 0), 1>(o + 4, vm[0], vm[1], vm[2], vm[3]);
          wg_commit();
          const uint4 il = lds128(sb + OFF_INV + (lane & 3) * 16), jf = lds128(sb + OFF_INV + 64 + (lane & 3) * 16);
          const float i0 = rcpf(__uint_as_float(il.x) + __uint_as_float(il.y)), i1 = rcpf(__uint_as_float(il.z) + __uint_as_float(il.w));
          const float j0 = rcpf(__uint_as_float(jf.x) + __uint_as_float(jf.y)), j1 = rcpf(__uint_as_float(jf.z) + __uint_as_float(jf.w));
          wg_wait<0>();
          stsm4t(oa, pack2(o[0] * i0, o[1] * i1), pack2(o[2] * i0, o[3] * i1), pack2(o[4] * j0, o[5] * j1), pack2(o[6] * j0, o[7] * j1));
          O_READY(true);
          TOK_L3();
        }
        {
          float v[16];
          bar_sync(N_TURN, 256);
          mbar_waitu(bar + 8 * B_F2, par ^ 1);
          wg_fence(); proj<32, SSV, 1, 0, 10>(v, W, wbase); wg_commit();
          mbar_waitu(bar + 8 * (B_F2 + 1), par ^ 1);
          wg_fence(); proj<32, SSV, 1, 10, 14>(v, W, wbase); wg_commit();
          wg_wait<1>(); REL(B_R2, 0);
          wg_fence(); proj<32, SSV, 1, 14, 20>(v, W, wbase); wg_commit();
          mbar_waitu(bar + 8 * (B_F2 + 2), par ^ 1);
          wg_fence(); proj<32, SSV, 1, 20, 24>(v, W, wbase); wg_commit();
          wg_wait<1>(); REL(B_R2, 1);
          wg_fence(); proj<32, SSV, 1, 24, 30>(v, W, wbase); wg_commit();
          mbar_waitu(bar + 8 * (B_F2 + 3), par ^ 1);
          wg_fence(); proj<32, SSV, 1, 30, 34>(v, W, wbase); wg_commit();
          wg_wait<1>(); REL(B_R2, 2);
          wg_fence(); proj<32, SSV, 1, 34, 40>(v, W, wbase); wg_commit();
          wg_wait<0>(); REL(B_R2, 3);
#pragma unroll
          for (int j = 0; j < 8; j++) vn[j] = pack2v(v[2 * j], v[2 * j + 1]);
          keep4(vn, lane); keep4(vn + 4, lane);
          if (warp == 0) TS(18);
        }
        uint32_t ow[16];
        bar_sync(N_P, 256);
        fence_async();
#define PV16(i, off, va) { float o[8]; wg_fence(); \
          MM<16>::rs<dlo(OFF_PL + (off), 128), dhi(896, 0), 0>(o, va[0], va[1], va[2], va[3]); \
          MM<16>::rs<dlo(OFF_PL + (off) + 256, 128), dhi(896, 0), 1>(o, va[4], va[5], va[6], va[7]); \
          MM<16>::rs<dlo(OFF_PL + (off) + 512, 128), dhi(896, 0), 1>(o, vm[0], vm[1], vm[2], vm[3]); \
          wg_commit(); wg_wait<0>(); \
          _Pragma("unroll") for (int j = 0; j < 4; j++) ow[4 * (i) + j] = pack2v(o[2 * j], o[2 * j + 1]); \
          keep4(ow + 4 * (i), lane); }
        PV16(0, 0, vl) PV16(1, 1792, vl) PV16(2, PL_SZ, vf) PV16(3, PL_SZ + 1792, vf)
        const uint32_t s1 = OX_SA + (lane < 16 ? 3072 : 0), s2 = OX_SA + (lane < 16 ? 2048 : 1024);
        bar_sync(N_V, 128);
        stsm4t(s1, ow[0], ow[1], ow[2], ow[3]);
        stsm4t(s2, ow[4], ow[5], ow[6], ow[7]);
        stsm4t(s1 + PL_SZ, ow[8], ow[9], ow[10], ow[11]);
        stsm4t(s2 + PL_SZ, ow[12], ow[13], ow[14], ow[15]);
#pragma unroll
        for (int j = 0; j < 8; j++) vl[j] = vn[j];
      } else {
        uint32_t vm[4], vn[8];
        {
          float v[4];
          wg_fence(); proj<8, SSV, 0, 30, 40, 30>(v, W, wbase); wg_commit();
          proj<8, SSV, 0, 0, VS1, 30>(v, W, wbase); wg_commit();
          ARM();
          bar_sync(N_SISS, 384);
          wg_wait<1>(); bar_arrive(N_G3, 160);
          wg_fence(); proj<8, SSV, 0, VS1, 30, 30>(v, W, wbase); wg_commit();
          if (has_next) { mbar_waitu2(bar + 8 * B_F2, bar + 8 * (B_F2 + 1), par ^ 1); mbar_waitu(bar + 8 * (B_F2 + 2), par ^ 1); }
          wg_wait<0>();
          bar_arrive(N_VDONE, 160);
          vm[0] = pack2v(v[0], v[1]); vm[1] = pack2v(v[2], v[3]); vm[2] = pack2v(v[1], v[0]); vm[3] = pack2v(v[3], v[2]);
        }
        float v[16];
        {
          wg_fence(); proj<32, SSV, 1, 0, 30>(v, W, wbase); wg_commit();
          {
            float o[4];
            O_ADDR();
            bar_sync(N_PM, 192);
            if (warp == 0) TS(14);
            wg_fence();
            MM<8>::rs<dlo(OFF_PL + 3584, 128), dhi(896, 0), 0>(o, vl[0], vl[1], vl[2], vl[3]);
            MM<8>::rs<dlo(OFF_PL + 3584 + 256, 128), dhi(896, 0), 1>(o, vl[4], vl[5], vl[6], vl[7]);
            MM<8>::rs<dlo(OFF_PL + 3584 + 512, 128), dhi(896, 0), 1>(o, vm[0], vm[1], vm[2], vm[3]);
            wg_commit();
            const uint4 il = lds128(sb + OFF_INV + (lane & 3) * 16);
            const float i0 = rcpf(__uint_as_float(il.x) + __uint_as_float(il.y)), i1 = rcpf(__uint_as_float(il.z) + __uint_as_float(il.w));
            wg_wait<0>();
            stsm2t(oa, pack2(o[0] * i0, o[1] * i1), pack2(o[2] * i0, o[3] * i1));
            O_READY(lane < 16);
            TOK_L3();
          }
          if (has_next) {
            mbar_arrive_remote_if(lane < 3, rb0 + ((nA - 4 + lane) << 24) + OFF_BAR + 8 * B_R2);
            bar_sync(N_TURN, 256);
            mbar_waitu(bar + 8 * (B_F2 + 3), par ^ 1);
          }
          wg_fence(); proj<32, SSV, 1, 30, 40>(v, W, wbase); wg_commit();
          wg_wait<0>();
          if (has_next) REL(B_R2, 3);
#pragma unroll
          for (int j = 0; j < 8; j++) vn[j] = pack2v(v[2 * j], v[2 * j + 1]);
          keep4(vn, lane); keep4(vn + 4, lane);
          if (warp == 0) TS(18);
        }
        float o[16];
        bar_sync(N_P, 256);
        fence_async();
        wg_fence();
        MM<32>::rs<dlo(OFF_PL, 128), dhi(896, 0), 0>(o, vl[0], vl[1], vl[2], vl[3]);
        MM<32>::rs<dlo(OFF_PL + 256, 128), dhi(896, 0), 1>(o, vl[4], vl[5], vl[6], vl[7]);
        MM<32>::rs<dlo(OFF_PL + 512, 128), dhi(896, 0), 1>(o, vm[0], vm[1], vm[2], vm[3]);
        wg_commit();
        const uint32_t s1 = OX_SA + (lane < 16 ? 3072 : 0), s2 = OX_SA + (lane < 16 ? 2048 : 1024);
        wg_wait<0>();
        bar_sync(N_V, 128);
        stsm4t(s1, pack2(o[0], o[1]), pack2(o[2], o[3]), pack2(o[4], o[5]), pack2(o[6], o[7]));
        stsm4t(s2, pack2(o[8], o[9]), pack2(o[10], o[11]), pack2(o[12], o[13]), pack2(o[14], o[15]));
#pragma unroll
        for (int j = 0; j < 8; j++) vl[j] = vn[j];
      }
      bar_arrive(N_OX, 160);
      if (warp == 0) TS(16);
    }
    cluster_sync_all();
  } else {
    asm volatile("setmaxnreg.dec.sync.aligned.u32 32;");
    if (wg > 3) return;
    LANE_INIT();
    struct RsJob { uint32_t* gp; uint32_t la, mb; int n; };
    auto rs_prep = [&](int step, int s, int c) {
      RsJob j;
      const int u = s * nA + rank;
      j.gp = &g_part[0][0][0][0] + (uint32_t)((((step & 1) * 2 + c) * NCL + cl) * 2560 + u * 64 + (lane >> 2) * 8 + (lane & 3));
      j.la = sb + OFF_TILE + c * LAND_F + LAND(s) + lane * 8;
      j.mb = bar + 8 * (B_RS + s);
      j.n = u >= 40 ? 0 : u >= 36 ? 3 : 1;
      asm volatile("" : "+l"(j.gp), "+r"(j.la));
      return j;
    };
    auto rs_sum = [&](RsJob j, int step) {
      if (j.n) {
        auto five = [&](uint32_t la) {
          uint2 p[5];
#pragma unroll
          for (int i = 0; i < 4; i++) p[i] = lds64(la + i * 256);
          asm volatile("{\n.reg .pred q;\nsetp.eq.s32 q, %3, 5;\nmov.u32 %0, 0;\nmov.u32 %1, 0;\n@q ld.shared.v2.b32 {%0,%1}, [%2];\n}"
                       : "=r"(p[4].x), "=r"(p[4].y) : "r"(la + 1024), "r"(nh) : "memory");
          return make_uint2(hadd2bf(hadd2bf(p[0].x, p[1].x), hadd2bf(hadd2bf(p[2].x, p[3].x), p[4].x)),
                            hadd2bf(hadd2bf(p[0].y, p[1].y), hadd2bf(hadd2bf(p[2].y, p[3].y), p[4].y)));
        };
        const uint32_t tag = ((step >> 1) & 1) ^ 1;
        mbar_waitw(j.mb, step & 1);
        uint2 t = five(j.la);
        if (j.n > 1) {
          const uint2 a = five(j.la + (nh == 5 ? 1280 : TILE_GRP - 1280)), b = five(j.la + TILE_GRP);
          t.x = hadd2bf(t.x, hadd2bf(a.x, b.x)); t.y = hadd2bf(t.y, hadd2bf(a.y, b.y));
        }
        const uint32_t t0 = (movm(t.x) & ~1u) | tag, t1 = (movm(t.y) & ~1u) | tag;
        asm volatile("st.relaxed.gpu.global.b32 [%0], %1;" :: "l"(j.gp), "r"(lane & 16 ? t1 : t0) : "memory");
        asm volatile("st.relaxed.gpu.global.b32 [%0], %1;" :: "l"(j.gp + 4), "r"(lane & 16 ? t0 : t1) : "memory");
      }
    };
    if (warp * nA + (int)rank < 40) {
#pragma unroll
      for (int e = LAG; e < LAG + 2; e++)
        if ((e >> 1) & 1) *reinterpret_cast<uint2*>(&g_part[(e & 1) * 2 + 1][cl][warp * nA + rank][lane * 2]) = make_uint2(1u, 1u);
      __threadfence();
    }
    cluster_sync_all();
    if (warp == 2 && ig >= 0) issue_tok(0, B_F2);
#pragma unroll 1
    for (int step = 0; step < NSTEP; step++) {
      const uint32_t par = step & 1;
      asm volatile("" : "+r"(lane));
      const bool dual = is_dual(step), has_next = step + 1 < NSTEP;
      {
        bar_sync(N_PX, dual ? 256 : 192);
        if (dual || warp >= 2) tok_softmax(sb, dual ? warp : warp - 2, lane);
        bar_arrive(N_P, 256);
        asm volatile("" : "+r"(lane));
        if (has_next) {
          if (step + 2 == LAG && lane < 20) asm volatile("prefetch.global.L2 [%0];" :: "l"(mem0 + (warp * 20 + lane) * 64));
          const int nw = ig >= 0 ? 3 : 4, j0 = warp < nw ? warp : 8;
          const int sh = dual ? 1 : 0;
          rs_sum(rs_prep(step, j0 >> sh, j0 & sh), step);
          if (warp == 0) TS(17);
          if (dual) rs_sum(rs_prep(step, (j0 + nw) >> 1, (j0 + nw) & 1), step);
          if (warp == 0) { bar_sync(N_C, 288); }
          mbar_arrive_remote_if(lane < nA, rb0 + (lane << 24) + OFF_BAR + 8 * B_LANDFREE);
          const uint32_t gap = dual ? POLL_GAPD : POLL_GAP;
          if (gap) { const uint32_t t0 = clock32(); while (clock32() - t0 < gap) {} }
#pragma unroll 1
          for (int j = j0; j < (dual ? 8 : 4); j += nw) {
            const int u = (j >> sh) * nA + rank, c = j & sh;
            if (u < UMAX && (c || step + 1 != NSEG)) {
              const uint32_t* gq = &g_part[0][0][0][0] + (uint32_t)((par * 2 + c) * NCL * 2560 + u * 64 + lane * 2);
              uint2 pa[NCL];
              POLL(pa, gq);
              deliver(pa, gq, u, c, step + 1 < NSEG ? c : 0, dual ? DS_DUAL : DS_SINGLE, step, j == 0, lane);
            }
            if (warp == 0 && j == 0) TS(13);
          }
          if (warp >= nw && (is_dual(step + 1) || (ig < 3 && step + 2 < NSTEP))) {
            issue_tok(is_dual(step + 1) ? sched_f(step + 1) : sched_l(step + 2), is_dual(step + 1) ? B_F1 : B_F2, B_R2, par ^ 1);
          }
          if (step + 1 == LAG && UMAX) {
            uint4 v[5];
#pragma unroll
            for (int i = 0; i < 5; i++) { const int t = warp * 160 + i * 32 + lane; v[i] = *reinterpret_cast<const uint4*>(mem0 + ((t >> 1) & 7) * DM + (t >> 4) * 16 + ((t ^ (t >> 3)) & 1) * 8); }
            mbar_waitu(bar + 8 * B_LANDFREE, par);
#pragma unroll
            for (int i = 0; i < 5; i++)
              st_async_v4(sb + OFF_TILE + LAND_F + warp * TILE_GRP + (i * 32 + lane) * 16, v[i].x, v[i].y, v[i].z, v[i].w, bar + 8 * (B_F1 + warp));
          }
        }
      }
      if (warp == 3) {
        unsigned char* o0 = g_o + uni(step % RO * (96 * 8192) + (head * 3 + t3) * (dual ? 8192 : 4096));
        bar_sync(N_OX, 160);
        fence_async();
        bulk_s2g_es(o0, sb + OFF_PL, 4096);
        if (dual) bulk_s2g_es(o0 + 4096, sb + OFF_PL + PL_SZ, 4096);
        asm volatile("cp.async.bulk.commit_group;" ::: "memory");
        asm volatile("cp.async.bulk.wait_group.read 0;" ::: "memory");
        __syncwarp();
        mbar_arrive_remote_if(lane < 2, (lane ? nxt : prv) + OFF_BAR + 8 * B_PLFREE);
        asm volatile("cp.async.bulk.wait_group 0;" ::: "memory");
        asm volatile("fence.proxy.async.global;" ::: "memory");
        __syncwarp();
        if (lane == 0) red_release(&g_f[F_O + (head * 3 + t3) / 5][step], 1u);
        __syncwarp();
      }
    }
    cluster_sync_all();
  }
}

__device__ __forceinline__ float gelu2(float x) {
  const float u = x * fmaf(x * x, 0.7978845608028654f * 0.044715f, 0.7978845608028654f);
  float t; asm("tanh.approx.f32 %0, %1;" : "=f"(t) : "f"(u));
  return fmaf(x, t, x); }

struct BParams {
  CUtensorMap wmap[5];
  CUtensorMap wo16;
  const __nv_bfloat16* x;
  __nv_bfloat16* out;
};
#define BO_O 0
#define BO_RES (6 * 8192)
#define OP_RES 63488
#define BO_STG (BO_RES + 2 * OP_RES)
#define BO_RING_OP (BO_STG + 16384)
#define OP_SLOT 12288
#define NS_OP 3
#define BO_H 81920
#define BO_W1 (BO_H + 16384)
#define BO_RING_MLP (BO_W1 + 81920)
#define BO_BAR 229376
#define BO_BOX (BO_BAR + 248)
#define BO_CARRY (BO_BAR + 512)
#define BO_STAT (BO_CARRY + 2048)
#define B_SMEM (BO_STAT + 256)
static_assert(B_SMEM <= 232448 && BO_RING_OP + NS_OP * OP_SLOT == BO_BAR && BO_RING_MLP + 3 * 16384 == BO_BAR && 2 * 83968 <= BO_RING_MLP, "smem");
enum { BB_W = 0, BB_FULL = 2, BB_TMP = BB_FULL + 3, BB_OFULL = BB_FULL + 5, BB_SFREE = BB_OFULL,
       BB_STAT = BB_SFREE + 6, BB_ZFREE, BB_DONE = BB_ZFREE + 3,
       BB_EMPTY, BB_START = BB_EMPTY, BB_USED = BB_EMPTY + 2, BB_NUM = BB_USED + 3 };
enum { NB_PP = 1, NB_H = 3, NB_END = 4, NB_END2 = 5, NB_STAGED = 6, NB_FREE = 8, NB_EARLY = 10, NB_LAST = 11 };

#define ACC32(d) ACC16(d), ACC16((d + 16))
#define R32S "{%0,%1,%2,%3,%4,%5,%6,%7,%8,%9,%10,%11,%12,%13,%14,%15,%16,%17,%18,%19,%20,%21,%22,%23,%24,%25,%26,%27,%28,%29,%30,%31}"
template <int N, bool H = false> struct BM;
#define DEF_BM(N, H, T, ACCM, RS_, I0, I1, I2, I3, I4, I5, I6)                                                                          \
  template <> struct BM<N, H> {                                                                                                      \
    template <int BO, int ACC> static __device__ __forceinline__ void rs(float* d, const uint32_t* a, uint32_t blo) {             \
      asm volatile("{\n.reg .b32 m;\n.reg .b64 b;\nadd.u32 m, %" #I4 ", %" #I5 ";\nmov.b64 b, {m, 0x40000040};\n"                 \
                   "wgmma.mma_async.sync.aligned.m64n" #N "k16.f32." T "." T " " RS_ ", {%" #I0 ",%" #I1 ",%" #I2 ",%" #I3 "}, b, %" #I6 ", 1, 1, 0;\n}" \
                   : ACCM(d) : "r"(a[0]), "r"(a[1]), "r"(a[2]), "r"(a[3]), "r"(blo), "n"(BO), "n"(ACC)); }                        \
    template <int AO, int BO, int ACC> static __device__ __forceinline__ void ss(float* d, uint32_t alo, uint32_t blo) {          \
      asm volatile("{\n.reg .b32 l, m;\n.reg .b64 a, b;\nadd.u32 l, %" #I0 ", %" #I1 ";\nadd.u32 m, %" #I2 ", %" #I3 ";\n"        \
                   "mov.b64 a, {l, 0x40000040};\nmov.b64 b, {m, 0x40000040};\n"                                                   \
                   "wgmma.mma_async.sync.aligned.m64n" #N "k16.f32." T "." T " " RS_ ", a, b, %" #I4 ", 1, 1, 1, 0;\n}"             \
                   : ACCM(d) : "r"(alo), "n"(AO), "r"(blo), "n"(BO), "n"(ACC)); }                                                 \
  };
DEF_BM(32, false, "bf16", ACC16, R16S, 16, 17, 18, 19, 20, 21, 22)
DEF_BM(64, false, "bf16", ACC32, R32S, 32, 33, 34, 35, 36, 37, 38)
DEF_BM(32, true, "f16", ACC16, R16S, 16, 17, 18, 19, 20, 21, 22)
DEF_BM(64, true, "f16", ACC32, R32S, 32, 33, 34, 35, 36, 37, 38)
#define DESC_LO(off) (((SMEM0 + (off)) >> 4) | (1u << 16))

__device__ __forceinline__ uint32_t ld_relaxed(const uint32_t* p) { uint32_t v; asm volatile("ld.relaxed.gpu.global.b32 %0, [%1];" : "=r"(v) : "l"(p) : "memory"); return v; }
__device__ __forceinline__ int fmask(int r) { return (r < NSEG) | ((r >= LAG && r < NSTEP) << 1); }
__device__ __forceinline__ int bmask(int r) { return (r <= NSEG) | ((r >= LAG) << 1); }
__device__ __forceinline__ uint32_t rtarget(int mask) { return mask == 3 ? 64 : 32; }
__device__ __forceinline__ void warp_signal(uint32_t* p, int lane) {
  __syncwarp();
  asm volatile("{\n.reg .pred q;\nsetp.eq.u32 q, %1, 0;\n@q red.release.gpu.global.add.u32 [%0], 1;\n}" :: "l"(p), "r"(lane) : "memory");
}
__device__ __forceinline__ uint32_t pack2h(float lo, float hi) { uint32_t r; asm("cvt.rn.f16x2.f32 %0, %1, %2;" : "=r"(r) : "f"(hi), "f"(lo)); return r; }
template <bool H> __device__ __forceinline__ uint32_t pk(float lo, float hi) { return H ? pack2h(lo, hi) : pack2(lo, hi); }
template <int N, bool H> __device__ __forceinline__ void stage_out(const float* d, uint32_t dst, int warp, int lane) {
  const uint32_t sa = dst + ((lane >> 4) * 8 + (lane & 7)) * 128 + (((2 * warp + ((lane >> 3) & 1)) ^ (lane & 7)) << 4);
#pragma unroll
  for (int m = 0; m < N / 16; m++)
    stsm4t(sa + m * 2048, pk<H>(d[8 * m], d[8 * m + 1]), pk<H>(d[8 * m + 2], d[8 * m + 3]), pk<H>(d[8 * m + 4], d[8 * m + 5]), pk<H>(d[8 * m + 6], d[8 * m + 7]));
}
template <int N> __device__ __forceinline__ void acc_live(float* d) {
#pragma unroll
  for (int i = 0; i < N / 2; i++) asm volatile("" : "+f"(d[i]) :: "memory");
}
struct Ring {
  uint32_t sl, ph;
  template <int NS> __device__ __forceinline__ void step() { if (++sl == NS) { sl = 0; ph ^= 1; } }
};

#define LOCKSTEP 0
#define KOFF(x) (((x) >> 2) * (N * 8) + ((x) & 3) * 2)
template <int N, int P>
__device__ __forceinline__ void op_pass(const uint32_t* W, uint32_t bar, uint32_t alo, uint32_t blo, uint32_t xlo, bool x2, Ring& rg, int wg, int warp, int lane, int r) {
  float acc[N / 2];
  const uint32_t tlo = DESC_LO(BO_RING_OP) + uni(rg.sl) * (OP_SLOT / 16);
  if (P == 0) mbar_waitu(bar + 8 * BB_OFULL, r & 1);
  CTS(5 * P);
  if (!LOCKSTEP || P > 1 || P == wg) bar_sync(NB_PP + wg, 256);
  wg_fence();
#define OP_R(x) BM<N>::template rs<KOFF(4 * (x >> 1) + (x & 1)), (x != 0)>(acc, W + 32 * P + 4 * x, blo);
#define OP_S(x) BM<N>::template ss<(6 * P + x) * 128, KOFF(4 * (x >> 1) + 2 + (x & 1)), 1>(acc, alo, blo);
#define OP_T(x) BM<N>::template ss<x * 128, KOFF(14 + x), 1>(acc, tlo, blo);
  OP_R(0) OP_S(0) OP_R(1) OP_S(1) OP_R(2) OP_S(2) OP_R(3) OP_S(3)
  if (P == 0) mbar_waitu(bar + 8 * (BB_OFULL + 1), r & 1);
  if (P == 4) wg_commit();
  OP_R(4) OP_S(4) OP_R(5) OP_S(5)
  if (P == 1 && x2) BM<N>::template ss<30 * 128, KOFF(20), 1>(acc, alo, xlo);
  if (P == 4) { wg_commit(); wg_wait<1>(); bar_arrive(NB_EARLY, 288); CTS(21); wg_fence(); }
  mbar_waitu(bar + 8 * (BB_FULL + rg.sl), rg.ph);
  OP_R(6) OP_T(0) OP_R(7) OP_T(1)
  if (P == 0) mbar_waitu(bar + 8 * (BB_OFULL + 2), r & 1);
  OP_T(2) OP_T(3)
  if (P == 0) BM<N>::template rs<KOFF(20), 1>(acc, W + 160, xlo);
  OP_T(4) OP_T(5)
  wg_commit();
  if (!LOCKSTEP || P) bar_arrive(NB_PP + 1 - wg, 256);
  CTS(5 * P + 2);
  bar_sync(NB_FREE + wg, 160);
  wg_wait<0>();
  acc_live<N>(acc);
  if (P == 4) bar_arrive(NB_LAST, 288);
  mbar_arrive_if(lane == 0, bar + 8 * (BB_USED + rg.sl));
  CTS(5 * P + 3);
  stage_out<N, false>(acc, SMEM0 + BO_STG + wg * 8192, warp, lane);
  bar_arrive(NB_STAGED + wg, 160);
  CTS(5 * P + 4);
  rg.step<NS_OP>(); rg.step<NS_OP>();
}
template <int N>
__device__ __forceinline__ void op_round(const uint32_t* W, uint32_t bar, uint32_t alo, uint32_t blo, uint32_t xlo, bool x2, Ring& rg, int wg, int warp, int lane, int r) {
  op_pass<N, 0>(W, bar, alo, blo, xlo, x2, rg, wg, warp, lane, r);
  op_pass<N, 1>(W, bar, alo, blo, xlo, x2, rg, wg, warp, lane, r);
  op_pass<N, 2>(W, bar, alo, blo, xlo, x2, rg, wg, warp, lane, r);
  op_pass<N, 3>(W, bar, alo, blo, xlo, x2, rg, wg, warp, lane, r);
  op_pass<N, 4>(W, bar, alo, blo, xlo, x2, rg, wg, warp, lane, r);
}
__device__ __forceinline__ void carry_in(uint32_t sb, int wg, int warp, int lane) {
  const int row = (lane >> 1) & 3;
  if (lane < 16) {
    const uint4 v = lds128(sb + BO_CARRY + (wg * 4 + warp) * 256 + lane * 16);
    sts128(sb + BO_H + wg * 8192 + (lane >> 3) * 4096 + row * 128 + (((2 * warp + (lane & 1)) ^ row) << 4), v.x, v.y, v.z, v.w);
  }
  __syncwarp();
}
#define STAGGER 0
template <int N, int Z>
__device__ __forceinline__ void p1_pair(float* acc, const uint32_t* W, uint32_t bar, uint32_t alo, uint32_t blo, int lane, int r) {
  mbar_waitu(bar + 8 * (BB_FULL + Z), r & 1);
  CTS(40 + Z);
  wg_fence();
#define P1_B(k) \
  BM<N, true>::template rs<(2 * Z % 3) * 1024 + k * 512, (2 * Z + k != 0)>(acc, W + 16 * Z + 8 * k, blo); \
  BM<N, true>::template ss<BO_W1 / 16 + (2 * Z + k) * 512, (2 * Z % 3) * 1024 + k * 512 + 4, 1>(acc, alo, blo); \
  BM<N, true>::template rs<(2 * Z % 3) * 1024 + k * 512 + 2, 1>(acc, W + 16 * Z + 8 * k + 4, blo); \
  BM<N, true>::template ss<BO_W1 / 16 + (2 * Z + k) * 512 + 128, (2 * Z % 3) * 1024 + k * 512 + 6, 1>(acc, alo, blo);
  P1_B(0)
  if (Z == 1 || Z == 2) { wg_commit(); wg_wait<1>(); mbar_arrive_if(lane == 0, bar + 8 * (BB_EMPTY + Z - 1)); wg_fence(); }
  P1_B(1)
  wg_commit();
}
template <int N>
__device__ __forceinline__ void phase1(const uint32_t* W, uint32_t sb, uint32_t alo, int half, int wg, int warp, int lane, int off, int r) {
  float acc[N / 2];
  const uint32_t bar = sb + BO_BAR, blo = DESC_LO(BO_RING_MLP) + half * 256;
  CTS(30);
  p1_pair<N, 0>(acc, W, bar, alo, blo, lane, r);
  p1_pair<N, 1>(acc, W, bar, alo, blo, lane, r);
  p1_pair<N, 2>(acc, W, bar, alo, blo, lane, r);
  mbar_waitu(bar + 8 * (BB_SFREE + 4 + wg), (r + 1) & 1);
  carry_in(sb, wg, warp, lane);
  if (STAGGER && wg) bar_sync(NB_PP + 1, 256);
  p1_pair<N, 3>(acc, W, bar, alo, blo, lane, r);
  p1_pair<N, 4>(acc, W, bar, alo, blo, lane, r);
  if (STAGGER && !wg) bar_arrive(NB_PP + 1, 256);
  const int c = (lane >> 3) & 1, i0 = (lane >> 4) * 8 + (lane & 7) + off;
  uint32_t a0 = sb + BO_H + wg * 8192 + half * 4096 + i0 * 128 + (((2 * warp + c) ^ (i0 & 7)) << 4);
  uint32_t a1 = i0 >= 16 ? sb + BO_CARRY + (wg * 4 + warp) * 256 + half * 128 + (i0 - 16) * 32 + c * 16 : a0 + 2048, a3 = a1 + (i0 >= 16 ? 128 : 4096);
  asm volatile("" : "+r"(a0), "+r"(a1), "+r"(a3));
  mbar_waitu(bar + 8 * BB_STAT, r & 1);
  const uint32_t sa = sb + BO_STAT + half * 128 + (lane & 3) * 32;
  uint4 t[2] = {lds128(sa), lds128(sa + 16)};
  wg_wait<0>();
  acc_live<N>(acc);
  CTS(32);
#pragma unroll
  for (int m = 0; m < N / 16; m++) {
    const float s0 = __uint_as_float(t[m & 1].x), s1 = __uint_as_float(t[m & 1].y), s2 = __uint_as_float(t[m & 1].z), s3 = __uint_as_float(t[m & 1].w);
    float* d = acc + 8 * m;
    d[0] *= s0; d[1] *= s1; d[2] *= s0; d[3] *= s1; d[4] *= s2; d[5] *= s3; d[6] *= s2; d[7] *= s3;
    if (m + 2 < N / 16) t[m & 1] = lds128(sa + 128 + m * 16);
#pragma unroll
    for (int j = 0; j < 8; j++) d[j] = gelu2(d[j]);
  }
#pragma unroll
  for (int m = 0; m < N / 16; m++)
    stsm4t(m == 1 ? a1 : m == 3 ? a3 : a0 + m * 2048, pack2(acc[8 * m], acc[8 * m + 1]), pack2(acc[8 * m + 2], acc[8 * m + 3]), pack2(acc[8 * m + 4], acc[8 * m + 5]), pack2(acc[8 * m + 6], acc[8 * m + 7]));
}
template <int N, int P>
__device__ __forceinline__ void p2_pass(const uint32_t* W, uint32_t bar, uint32_t alo, uint32_t blo, int wg, int warp, int lane, int r) {
  float acc[N / 2];
  CTS(5 * P);
  if (P || wg) bar_sync(NB_PP + wg, 256);
  wg_fence();
  BM<N>::template rs<0, 0>(acc, W + 80 + 16 * P, blo);      BM<N>::template ss<P * 1024, 512, 1>(acc, alo, blo);
  BM<N>::template rs<2, 1>(acc, W + 84 + 16 * P, blo);      BM<N>::template ss<P * 1024 + 128, 514, 1>(acc, alo, blo);
  BM<N>::template rs<4, 1>(acc, W + 88 + 16 * P, blo);      BM<N>::template ss<P * 1024 + 512, 516, 1>(acc, alo, blo);
  BM<N>::template rs<6, 1>(acc, W + 92 + 16 * P, blo);      BM<N>::template ss<P * 1024 + 640, 518, 1>(acc, alo, blo);
  wg_commit();
  if (P < 4 || !wg) bar_arrive(NB_PP + 1 - wg, 256);
  CTS(5 * P + 2);
  if (P == 2 || P == 3) mbar_waitu(bar + 8 * (BB_SFREE + 2 * (P - 2) + wg), r & 1);
  wg_wait<0>();
  acc_live<N>(acc);
  if (P == 4) bar_sync(NB_H, 256);
  CTS(5 * P + 3);
  stage_out<N, true>(acc, SMEM0 + (P == 4 ? BO_H : BO_RING_MLP + (2 - (P & 1)) * 16384) + wg * 8192, warp, lane);
  bar_arrive(NB_STAGED + (P == 4 ? 4 : 2 * (P & 1)) + wg, 160);
  CTS(5 * P + 4);
}
template <int N>
__device__ __forceinline__ void phase2(const uint32_t* W, uint32_t bar, uint32_t alo, uint32_t blo, int wg, int warp, int lane, int r) {
  p2_pass<N, 0>(W, bar, alo, blo, wg, warp, lane, r);
  p2_pass<N, 1>(W, bar, alo, blo, wg, warp, lane, r);
  p2_pass<N, 2>(W, bar, alo, blo, wg, warp, lane, r);
  p2_pass<N, 3>(W, bar, alo, blo, wg, warp, lane, r);
  p2_pass<N, 4>(W, bar, alo, blo, wg, warp, lane, r);
}

__device__ __forceinline__ void ldg4(uint32_t* v, const void* p) {
  asm volatile("ld.relaxed.gpu.global.v4.u32 {%0,%1,%2,%3}, [%4];" : "=r"(v[0]), "=r"(v[1]), "=r"(v[2]), "=r"(v[3]) : "l"(p) : "memory"); }
__device__ __forceinline__ void stg4(void* p, const uint32_t* v) {
  asm volatile("st.global.v4.u32 [%0], {%1,%2,%3,%4};" :: "l"(p), "r"(v[0]), "r"(v[1]), "r"(v[2]), "r"(v[3]) : "memory"); }
struct RowPtr {
  unsigned char *p, *q, *t;
  __device__ __forceinline__ void ld(uint32_t* v, int o) const {
    ldg4(v, p + o); ldg4(v + 4, q + o);
    asm volatile("ld.relaxed.gpu.global.v2.u32 {%0,%1}, [%2];" : "=r"(v[8]), "=r"(v[9]) : "l"(t + o) : "memory");
  }
  __device__ __forceinline__ void st(const uint32_t* w, int o) const {
    stg4(p + o, w); stg4(q + o, w + 4);
    asm volatile("st.global.v2.u32 [%0], {%1,%2};" :: "l"(t + o), "r"(w[8]), "r"(w[9]) : "memory");
  }
};
__device__ __forceinline__ RowPtr row_img(int r, int n, int lane) {
  unsigned char* b = &g_acc[0][r % RD][n * 128];
  unsigned char* p = b + (uint32_t)((lane >> 3) * 8192 + (((lane ^ n) & 7) << 4));
  return {p, p + 32768, b + (uint32_t)(65536 + (lane >> 4) * 8192 + ((((lane >> 1) ^ n) & 7) << 4) + (lane & 1) * 8)};
}
__device__ __forceinline__ RowPtr row_ext(const void* lin, bool xn, int layer, int tok, int lane) {
  unsigned char* b = xn ? reinterpret_cast<unsigned char*>(&g_xn[layer][0]) + (uint32_t)((tok >> 5) * 40960 + ((tok >> 3) & 3) * 2560 + (tok & 7) * 32)
                        : (unsigned char*)lin + (uint32_t)(tok * 1280);
  const uint32_t o = (lane >> 1) * 256 + ((lane ^ (tok >> 2)) & 1) * 16;
  return {b + (uint32_t)(xn ? o + (lane >= 20 ? 7680 : 0) : lane * 16),
          b + (uint32_t)(xn ? o + 4096 + 7680 + (lane >= 8 ? 7680 : 0) + (lane >= 28 ? 7680 : 0) : lane * 16 + 512),
          b + (uint32_t)(xn ? (lane >> 2) * 256 + ((lane & 3) ^ ((tok >> 1) & 2)) * 8 + 8192 + 3 * 7680 : lane * 8 + 1024)};
}
__device__ __forceinline__ float2 h2f(uint32_t w) {
  float2 f; asm("{\n.reg .f16 l, h;\nmov.b32 {l, h}, %2;\ncvt.f32.f16 %0, l;\ncvt.f32.f16 %1, h;\n}" : "=f"(f.x), "=f"(f.y) : "r"(w)); return f; }
__device__ __forceinline__ float rsq(float x) { float y; asm("rsqrt.approx.ftz.f32 %0, %1;" : "=f"(y) : "f"(x)); return y; }
__device__ __forceinline__ void red_if(uint32_t v, const void* a) {
  asm volatile("{\n.reg .pred q;\nsetp.ne.u32 q, %1, 0;\n@q red.relaxed.gpu.global.add.u32 [%0], %1;\n}" :: "l"(a), "r"(v) : "memory"); }
__device__ __forceinline__ uint32_t dep0(uint32_t w, int lane) { uint32_t z; asm volatile("shr.b32 %0, %1, %2;" : "=r"(z) : "r"(w), "r"(lane + 32)); return z; }
__device__ __forceinline__ int lane_of(uint32_t w) {
  int lane; asm volatile("{\n.reg .u32 t;\nmov.u32 t, %%laneid;\nshr.u32 %0, %1, 20;\nadd.u32 %0, %0, t;\n}" : "=r"(lane) : "r"(w)); return lane; }
#define BUF (RD * TILE_B)
__device__ __forceinline__ int await(uint32_t v, const uint32_t* p, uint32_t target, bool lazy) {
  int n = 0;
  while (!__all_sync(~0u, v >= target)) {
    if (lazy) __nanosleep(200);
    if (++n > SPIN_LIMIT) FAIL();
    v = ld_relaxed(p);
  }
  asm volatile("fence.acquire.gpu;" ::: "memory");
  return lane_of(v);
}
template <int W> __device__ __forceinline__ void sum2(float& s, float& q, int lane) {
  const bool up = lane & (W / 2);
  float e = (up ? q : s) + __shfl_xor_sync(~0u, up ? s : q, W / 2);
#pragma unroll
  for (int o = W / 4; o; o >>= 1) e += __shfl_xor_sync(~0u, e, o);
  const float f = __shfl_xor_sync(~0u, e, W / 2);
  s = up ? f : e; q = up ? e : f;
}
template <int TYPE>
__device__ __forceinline__ void rrow(int r, int row, int tok, int lane, const uint32_t* go, int role, const __nv_bfloat16* x) {
  const int half = TYPE ? 0 : row >> 5;
  float v[20];
  float2 st = make_float2(1.f, 0.f);
  {
    uint32_t a[10], c[10], u[10], sh = 16;
    if (TYPE == 2) row_img(r + RD - ((row & 31) < 2), (row & 32) + ((row - 2) & 31), lane).ld(u, 4 * BUF);
    else row_ext(x, half, 1, tok, lane).ld(u, 0);
    if (TYPE == 2 || (TYPE == 0 && half))
      asm volatile("ld.relaxed.gpu.global.v2.f32 {%0,%1}, [%2];" : "=f"(st.x), "=f"(st.y) : "l"(g_stat + tok) : "memory");
    RowPtr ap = row_img(r, row, lane);
    const uint32_t g0 = TYPE != 3 ? ld_relaxed(go) : 0;
    if (TYPE == 2) {
      ap.ld(c, 2 * BUF);
      uint32_t z = dep0(c[9], lane);
#pragma unroll
      for (int i = 0; i < 10; i++) {
        const float2 g = h2f(u[i] | z), h = h2f(c[i] | z);
        v[2 * i] = fmaf(h.x, 0.5f, g.x * st.x); v[2 * i + 1] = fmaf(h.y, 0.5f, g.y * st.x);
        if (i & 1) z = dep0(__float_as_uint(v[2 * i]) | __float_as_uint(v[2 * i + 1]), lane);
      }
    }
    if (TYPE != 3) {
      asm volatile("" : "+l"(ap.p), "+l"(ap.t));
      ap.q = ap.p + 32768;
      lane = await(g0, go, NOP * NW12 * NW34, false); BTS2(r, 8 + 2 * TYPE); RTS(0);
      ap.ld(a, TYPE ? 3 * BUF : 0);
    }
    if (TYPE == 0) {
      ap.ld(c, BUF);
      const uint32_t one = 0x3f803f80u | dep0(c[9], lane);
#pragma unroll
      for (int i = 0; i < 10; i++) asm volatile("fma.rn.bf16x2 %0, %0, %1, %2;" : "+r"(a[i]) : "r"(one), "r"(c[i]));
      sh |= dep0(a[9], lane);
    }
    const float k = TYPE == 2 ? __uint_as_float(0x3f000000u | dep0(a[9], lane)) : 0.f;
#pragma unroll
    for (int i = 0; i < 10; i++) {
      if (TYPE == 2) { const float2 h = h2f(a[i]); v[2 * i] = fmaf(h.x, k, v[2 * i]); v[2 * i + 1] = fmaf(h.y, k, v[2 * i + 1]); continue; }
      float p = __uint_as_float(u[i] << sh), q = __uint_as_float(u[i] & (0xffffu << sh));
      if (TYPE == 0) { p = fmaf(p, st.x, bf_lo(a[i])); q = fmaf(q, st.x, bf_hi(a[i])); }
      v[2 * i] = p; v[2 * i + 1] = q;
    }
  }
  RTSD(1, v[19]);
  float s = 0.f, q = 0.f;
#pragma unroll
  for (int i = 0; i < 5; i++) {
    s += (v[4 * i] + v[4 * i + 1]) + (v[4 * i + 2] + v[4 * i + 3]);
    q += fmaf(v[4 * i], v[4 * i], v[4 * i + 1] * v[4 * i + 1]) + fmaf(v[4 * i + 2], v[4 * i + 2], v[4 * i + 3] * v[4 * i + 3]);
  }
  sum2<32>(s, q, lane);
  const float mean = s * (1.f / DM), var = fmaxf(q * (1.f / DM) - mean * mean, 0.f), rs = rsq(var + 1e-5f), k = TYPE ? rs : 2.f * rs, mr = -mean * k;
  RTSD(2, rs);
  uint32_t w[10];
#pragma unroll
  for (int i = 0; i < 10; i++) w[i] = pk<TYPE == 0>(fmaf(v[2 * i], k, mr), fmaf(v[2 * i + 1], k, mr));
  if (TYPE) row_ext(nullptr, true, TYPE == 2, tok, lane).st(w, 0);
  else {
    row_img(r, row, lane).st(w, 4 * BUF);
    row_img(r + ((row & 31) >= 30), (row & 32) + ((row + 2) & 31), lane).st(w, 2 * BUF);
    if (lane == 1) g_st2[0][r % RD][row] = (__float_as_uint(0.5f * rsq(fmaf(var * rs, rs, 1e-5f))) & ~127u) | (r + 1);
  }
  if (TYPE != 3 && lane == 0) g_stat[tok] = make_float2((var + 1e-5f) * rs * (TYPE ? 1.f : 0.5f), mean + st.y);
}
__device__ __forceinline__ void r2rows(int r, int row, int lane) {
  const int n = row + (lane >> 4);
  const unsigned char* ap = &g_acc[2][r % RD][0] + (uint32_t)(n * 128 + ((lane >> 3) & 1) * 8192 + (((lane ^ n) & 7) << 4));
  uint32_t a[20];
#pragma unroll
  for (int i = 0; i < 5; i++) ldg4(a + 4 * i, ap + i * 16384);
  const uint32_t z = dep0(a[19], lane);
  float s = 0.f, q = 0.f, q2 = 0.f;
#pragma unroll
  for (int i = 0; i < 20; i++) { const float2 h = h2f(a[i] | z); s += h.x + h.y; q = fmaf(h.x, h.x, q); q2 = fmaf(h.y, h.y, q2); }
  q += q2;
  sum2<16>(s, q, lane);
  const float mean = s * (0.5f / DM), rs = rsq(fmaxf(q * (0.25f / DM) - mean * mean, 0.f) + 1e-5f);
  if ((lane & 15) == 0) asm volatile("st.relaxed.gpu.global.u32 [%0], %1;" :: "l"(&g_st2[1][r % RD][n]), "r"((__float_as_uint(0.5f * rs) & ~127u) | (r + 1)) : "memory");
}
__device__ __forceinline__ void r3rows(int r, int row, int tok, int lane, __nv_bfloat16* out) {
  const int n = row + (lane >> 4), m = 32 + ((n - 2) & 31);
  const unsigned char* ap = &g_acc[0][r % RD][0] + (uint32_t)(n * 128 + ((lane >> 3) & 1) * 8192 + (((lane ^ n) & 7) << 4));
  const unsigned char* zp = &g_acc[4][(r + RD - (row == 32)) % RD][0] + (uint32_t)(m * 128 + ((lane >> 3) & 1) * 8192 + (((lane ^ m) & 7) << 4));
  unsigned char* op = reinterpret_cast<unsigned char*>(out) + (uint32_t)((tok + (lane >> 4)) * 1280 + (lane & 15) * 16);
  float2 st;
  asm volatile("ld.relaxed.gpu.global.v2.f32 {%0,%1}, [%2];" : "=f"(st.x), "=f"(st.y) : "l"(g_stat + tok + (lane >> 4)) : "memory");
#pragma unroll 1
  for (int i0 = 0; i0 < 3; i0++) {
    uint32_t a[8], c[8], u[8];
#pragma unroll
    for (int i = 0; i < 2; i++) { ldg4(a + 4 * i, ap + 3 * BUF + i * 16384); ldg4(c + 4 * i, ap + 2 * BUF + i * 16384); ldg4(u + 4 * i, zp + i * 16384); }
    uint32_t z = dep0(u[7], lane);
#pragma unroll
    for (int i = 0; i < 8; i++) {
      const float2 h = h2f(a[i] | z), e = h2f(c[i] | z), g = h2f(u[i] | z);
      a[i] = pack2(fmaf(h.x + e.x, 0.5f, fmaf(g.x, st.x, st.y)), fmaf(h.y + e.y, 0.5f, fmaf(g.y, st.x, st.y)));
      if (i & 1) z = dep0(a[i], lane);
    }
    if (i0 < 2) stg4(op, a);
    stg4(op + 256, a + 4);
    ap += 32768 >> i0; zp += 32768 >> i0; op += 512 >> i0;
  }
}
template <int TYPE>
__device__ __forceinline__ void rloop(int row, int cp, int role, const __nv_bfloat16* x, __nv_bfloat16* out) {
  constexpr int ST = TYPE == 4 ? 2 : TYPE;
  const int r0 = row & 32 ? LAG : 0;
  uint32_t v = 0;
#pragma unroll 1
  for (int r = r0; r < r0 + NSEG + (TYPE > 0); r++) {
    const int tok = (r - r0) * 32 + (row & 31) - (TYPE ? 2 : 0);
    const bool valid = TYPE == 0 || (unsigned)tok < S_LEN;
    const uint32_t* go = &g_f[F_R1 + 4 * ST + cp][r];
    const uint32_t* first = TYPE == 2 ? &g_f[F_R2 + cp][r] : TYPE ? go : (const uint32_t*)&g_xready[NSEG + r - r0][0];
    if constexpr (TYPE == 1 || TYPE == 4) {
      const int lane = await(v, go, NOP * NW12 * NW34, false);
      BTS2(r, 8 + 2 * ST); RTS(0);
      if (TYPE == 1) { r2rows(r, row, lane); BTS2(r, 11); continue; }
      if (valid) r3rows(r, row, tok, lane, out);
    } else {
      if (TYPE || row >= 32) await(v, first, TYPE ? NOP * NW12 * NW34 : 32, true);
      if (valid) rrow<TYPE>(r, row, tok, lane_of(r), go, role, x);
    }
    const int lane = lane_of(r);
    const void* f = lane ? (const void*)&g_xready[NSEG + (tok >> 5)][0] : (const void*)&g_f[TYPE ? F_DONE : F_Z][r];
    asm volatile("" : "+l"(f));
    __syncwarp();
    RTS(3);
    v = ld_relaxed(first + (TYPE ? 1 : 8));
    asm volatile("fence.release.gpu;" ::: "memory");
    RTS(4);
    red_if(lane == 0 || (TYPE == 2 && lane == 1 && valid) ? (TYPE & 5 ? 2 : 1) : 0, f);
    RTS(5);
    RTS_OUT();
    BTS2(r, 9 + 2 * ST);
  }
}

#define SINGLE_OP 3
#define SINGLE_W 0
#define W_DELAY 0
#define BULK_ADD(T, dst, src, len) asm volatile("{\n.reg .pred e;\nelect.sync _|e, 0xffffffff;\n@e cp.reduce.async.bulk.global.shared::cta.bulk_group.add.noftz." T " [%0], [%1], %2;\n}" \
                                               :: "l"(dst), "r"(src), "r"(len) : "memory")
#define COMMIT() asm volatile("cp.async.bulk.commit_group;" ::: "memory")
#define DRAINED(n) do { asm volatile("cp.async.bulk.wait_group.read " #n ";" ::: "memory"); __syncwarp(); } while (0)
#define WRITTEN() do { asm volatile("cp.async.bulk.wait_group 0;\nfence.proxy.async.global;" ::: "memory"); __syncwarp(); } while (0)
__device__ __forceinline__ void wait_flags(const uint32_t* p, uint32_t target) {
  int n = 0;
  while (!__all_sync(~0u, ld_relaxed(p) >= target)) { if (++n > SPIN_LIMIT) FAIL(); }
  asm volatile("fence.acquire.gpu;" ::: "memory");
  asm volatile("fence.proxy.async.global;" ::: "memory");
}
__global__ void __launch_bounds__(512, 1) bworker_kernel(const __grid_constant__ BParams P) {
  extern __shared__ __align__(1024) unsigned char smem_raw[];
  const uint32_t sb = SMEM0, bar = sb + BO_BAR;
  const int wg = __shfl_sync(~0u, threadIdx.x >> 7, 0), warp = __shfl_sync(~0u, (threadIdx.x >> 5) & 3, 0);
  if (threadIdx.x == 0) {
    if (smem_u32(smem_raw) != SMEM0) FAIL();
    uint32_t smid; asm volatile("mov.u32 %0, %%smid;" : "=r"(smid));
    const uint32_t nb = ld_relaxed(&g_tpc[(smid >> 1) & 127]);
    const bool single = nb > 1, far = nb == 0 && (smid < 64 || smid >= 124);
    int kind = far || (single && atomicAdd(&g_f[F_MISC][35], 1u) < SINGLE_OP) ? 0 : single ? 1 + SINGLE_W : 1;
    int rc = single || (smid >> 1) == 16 || (smid >> 1) == 63 ? 1 : far ? 2 : 0;
    uint32_t i, o;
    while ((i = atomicAdd(&g_f[F_MISC][32 + kind], 1u)) >= (kind == 0 ? NOP : kind == 1 ? NW12 : NW34)) kind = (kind + 1) % 3;
    while ((o = atomicAdd(&g_f[F_MISC][36 + rc], 1u)) >= (rc == 0 ? 16 : rc == 1 ? 8 : 12)) rc = (rc + 1) % 3;
    sts64(sb + BO_BOX, i + (kind == 0 ? 0 : kind == 1 ? NOP : NOP + NW12), o + (rc ? 8 + 8 * rc : 0));
    for (int k = 0; k < BB_NUM; k++) mbar_init(bar + 8 * k, k >= BB_USED ? 4 : k >= BB_EMPTY ? 8 : k >= BB_ZFREE && kind ? 2 : 1);
    asm volatile("fence.mbarrier_init.release.cluster;" ::: "memory");
  }
  if (threadIdx.x < 128) sts128(sb + BO_CARRY + threadIdx.x * 16, 0u, 0u, 0u, 0u);
  fence_async();
  __syncthreads();
  const int role = uni(lds32(sb + BO_BOX));
  const bool op = role < NOP, w12 = role < NOP + NW12;
  const int j = op ? role : w12 ? role - NOP : role - NOP - NW12;
  const int rot = op ? (j ? 2 * ((j + 1) % 5) : 0) : 2 * (j % 5);
  if (wg == 3) {
    asm volatile("setmaxnreg.dec.sync.aligned.u32 24;");
    LANE_INIT();
    if (warp < 2) {
      auto announce = [&](int r) {
        const uint32_t* f = &g_f[(op ? F_R1 : w12 ? F_R2 : F_R3) + (lane & 3)][r];
        asm volatile("" : "+l"(f));
        if (warp == 0) { mbar_arrive_if(lane == 0, bar + 8 * BB_DONE); return; }
        mbar_waitw(bar + 8 * BB_DONE, r & 1);
        PTS(60);
        asm volatile("fence.release.gpu;" ::: "memory");
        red_if(lane >= 4 ? 0 : op ? NW12 * NW34 : w12 ? NOP * NW34 : NOP * NW12, f);
        PTS(61);
        BTS(r, 4);
      };
      if (op) {
        int mt = rot + warp;
        bar_arrive(NB_FREE + warp, 160);
#pragma unroll 1
        for (int r = 0; r < NSTEP; r++) {
          const uint32_t len = fmask(r) == 3 ? 8192 : 4096;
          unsigned char* acc = &g_acc[j & 1][r % RD][fmask(r) == 2 ? 4096 : 0];
#pragma unroll 1
          for (int p = 0; p < 5; p++) {
            bar_sync(NB_STAGED + warp, 160);
            PTS(50 + 2 * p + warp);
            fence_async();
            BULK_ADD("bf16", acc + mt * 8192, sb + BO_STG + warp * 8192, len);
            COMMIT();
            PTS(64 + 50 + 2 * p + warp);
            mt = mt >= 8 ? mt - 8 : mt + 2;
            DRAINED(0);
            bar_arrive(NB_FREE + warp, 160);
          }
          WRITTEN();
          announce(r);
        }
      } else {
#pragma unroll 1
        for (int r = 0; r < NR; r++) {
          const uint32_t len = bmask(r) == 3 ? 8192 : 4096;
          unsigned char* acc = &g_acc[w12 ? 2 : 3][r % RD][bmask(r) == 2 ? 4096 : 0];
          int mt = rot + warp;
#pragma unroll 1
          for (int p = 0; p < 5; p++) {
            bar_sync(NB_STAGED + (p == 4 ? 4 : 2 * (p & 1)) + warp, 160);
            PTS(50 + 2 * p + warp);
            fence_async();
            BULK_ADD("f16", acc + mt * 8192, sb + (p == 4 ? BO_H : BO_RING_MLP + (2 - (p & 1)) * 16384) + warp * 8192, len);
            COMMIT();
            PTS(64 + 50 + 2 * p + warp);
            mt = mt >= 8 ? mt - 8 : mt + 2;
            if (p == 4) break;
            DRAINED(1);
            mbar_arrive_if(lane == 0, bar + 8 * (p == 1 || p == 2 ? BB_SFREE + 2 * (p - 1) + warp : BB_ZFREE + (p >> 1)));
            if (p == 3) { DRAINED(0); mbar_arrive_if(lane == 0, bar + 8 * (BB_ZFREE + 2)); }
          }
          WRITTEN();
          mbar_arrive_if(lane == 0, bar + 8 * (BB_SFREE + 4 + warp));
          announce(r);
        }
      }
    } else {
      if (op && warp == 2) {
        unsigned char* wt = g_wt + j * (10 * OP_SLOT);
#pragma unroll 1
        for (int m0 = 0; m0 < 10; m0 += 3) {
          const int nu = m0 < 9 ? 9 : 3;
          mbar_expect_if(lane == 0, bar + 8 * BB_TMP, nu * 4096);
#pragma unroll 1
          for (int k = 0; k < nu; k++) tma2d_e(sb + BO_RING_OP + k * 4096, &P.wmap[0], (m0 + k / 3) * 64, 320 * j + 224 + 32 * (k % 3), bar + 8 * BB_TMP);
          mbar_waitw(bar + 8 * BB_TMP, m0 & 1);
          bulk_s2g_e(wt + m0 * OP_SLOT, sb + BO_RING_OP, nu * 4096);
          COMMIT();
          WRITTEN();
        }
        asm volatile("fence.acq_rel.gpu;" ::: "memory");
        int sl = 0, ph = 1, mt = rot;
#pragma unroll 1
        for (int r = -1; r < NSTEP; r++) {
#pragma unroll 1
          for (int n = r < 0 ? 7 : 0; n < (r + 1 < NSTEP ? 10 : 7); n++) {
            mbar_waitw(bar + 8 * (BB_USED + sl), ph);
            mbar_expect_if(lane == 0, bar + 8 * (BB_FULL + sl), OP_SLOT);
            bulk_g2s_e(sb + BO_RING_OP + sl * OP_SLOT, wt + mt * OP_SLOT, OP_SLOT, bar + 8 * (BB_FULL + sl));
            if (++sl == 3) { sl = 0; ph ^= 1; }
            mt = mt == 9 ? 0 : mt + 1;
          }
        }
      } else if (op) {
        mbar_waitw(bar + 8 * BB_START, 0);
#pragma unroll 1
        for (int r = 0; r < NSTEP; r++) {
          const int rb = r - RD + 2;
          const uint32_t len = fmask(r) == 3 ? 8192 : 4096;
          const unsigned char* src = g_o + (uint32_t)(r % RO * (96 * 8192) + 5 * j * len);
          wait_flags(lane < 2 ? &g_f[F_O + (lane ? NOP : j)][r] : rb >= 0 ? &g_f[F_DONE][rb] : &g_f[F_MISC][0],
                     lane < 2 ? (lane ? 1 : 5) : rb >= 0 ? rtarget(bmask(rb)) : NBC * 8);
          PTS1(35);
          if (r) bar_sync(NB_EARLY, 288);
          if (r == LAG) bar_sync(NB_LAST, 288);
          mbar_expect_if(lane < 3, bar + 8 * (BB_OFULL + lane), 2 * len);
          bulk_g2s_e(sb + BO_O, src, 2 * len, bar + 8 * BB_OFULL);
          PTS(62); PTS1(38);
          if (r && r != LAG) bar_sync(NB_LAST, 288);
          bulk_g2s_e(sb + BO_O + 2 * len, src + 2 * len, 2 * len, bar + 8 * (BB_OFULL + 1));
          bulk_g2s_e(sb + BO_O + 4 * len, src + 4 * len, len, bar + 8 * (BB_OFULL + 2));
          bulk_g2s_e(sb + BO_O + 5 * len, src + (95 - 5 * j) * len, len, bar + 8 * (BB_OFULL + 2));
          PTS1(64 + 35);
          BTS(r, 0);
        }
      } else if (warp == 2) {
#pragma unroll 1
        for (int r = 0; r < NR; r++) {
          const int mk = w12 ? fmask(r) : bmask(r);
          if (mk) {
            const unsigned char* src = &g_acc[w12 ? 4 : 2][r % RD][mk == 2 ? 4096 : 0];
            wait_flags(w12 ? &g_f[F_Z][r] : lane && r >= 2 ? &g_f[F_R3 + (j & 3)][r - 2] : &g_f[F_R2 + (j & 3)][r], w12 ? rtarget(mk) : NOP * NW12 * NW34);
#pragma unroll 1
            for (int z = 0; z < 5; z++) {
              const uint32_t fb = bar + 8 * (BB_FULL + z), dst = sb + BO_RING_MLP + 2 * z % 3 * 16384 + (mk == 2 ? 4096 : 0);
              mbar_waitw(bar + 8 * (z < 3 ? BB_ZFREE + z : BB_EMPTY + z - 3), (r + (z < 3)) & 1);
              if (z == 0) PTS(62);
              mbar_expect_if(lane == 0, fb, mk == 3 ? 16384 : 8192);
              bulk_g2s_e(dst, src + z * 16384, mk == 3 ? 16384 : 4096, fb);
              if (mk != 3) bulk_g2s_e(dst + 8192, src + z * 16384 + 8192, 4096, fb);
              if (z == 0) BTS(r, 0);
            }
          }
          if (!w12) {
#pragma unroll 1
            for (int c = j; c < 120; c += NW34) bulk_s2g_e(&g_acc[c < 80 ? c / 40 : 3][(r + (c < 80 ? 0 : 2)) % RD][c % 40 * 2048], sb + BO_CARRY, 2048);
            COMMIT();
            WRITTEN();
          }
          mbar_waitw(bar + 8 * BB_DONE, (r + 1) & 1);
          mbar_arrive_if(lane == 0, bar + 8 * BB_DONE);
        }
      } else {
#pragma unroll 1
        for (int r = 0; r < (w12 ? NSTEP : NR); r++) {
          const bool idle = !((w12 ? fmask(r) : bmask(r)) >> (lane >> 4) & 1);
          uint32_t t0, t1;
          int n = 0;
          mbar_waitw(bar + 8 * BB_FULL, r & 1);
          do {
            asm volatile("ld.relaxed.gpu.global.v2.u32 {%0,%1}, [%2];" : "=r"(t0), "=r"(t1) : "l"(&g_st2[!w12][r % RD][2 * lane]) : "memory");
            if (++n > SPIN_LIMIT) FAIL();
          } while (!__all_sync(~0u, idle || (((t0 ^ (r + 1)) | (t1 ^ (r + 1))) & 127) == 0));
          sts64(sb + BO_STAT + (lane >> 4) * 128 + (lane & 3) * 32 + ((lane >> 2) & 3) * 8, t0, t1);
          __syncwarp();
          mbar_arrive_if(lane == 0, bar + 8 * BB_STAT);
          PTS(63);
        }
      }
    }
    bar_arrive(NB_END, 512);
  } else if (wg == 2) {
    asm volatile("setmaxnreg.dec.sync.aligned.u32 40;");
    const int ord = uni(lds32(sb + BO_BOX + 4));
    const int gw = ord < 16 ? warp * 16 + ord : ord < 24 ? 48 + warp * 8 + ord : 72 + warp * 12 + ord, row = gw < 64 ? gw : gw < 96 ? gw - 64 : gw < 128 ? 2 * gw - 192 : 2 * gw - 224;
#pragma unroll 1
    for (int t = gw; t < S_LEN; t = row < 32 ? S_LEN : t < 4 * NBC ? 4 * NBC + (gw < 64 ? gw - 32 : gw - 80) : t + 64) {
      const int lane = lane_of(t);
      if (lane < 20 && t + 128 < S_LEN) asm volatile("prefetch.global.L2 [%0];" :: "l"(P.x + (t + (t < 4 * NBC ? 4 * NBC : 128)) * DM + (lane >> 1) * 64));
      rrow<3>(0, 0, t, lane, nullptr, role, P.x);
      __syncwarp();
      asm volatile("fence.release.gpu;" ::: "memory");
      red_if(lane == 0, &g_xready[t >> 5][0]);
    }
    if (gw < 64) rloop<0>(row, gw & 3, role, P.x, P.out);
    else if (gw < 96) rloop<2>(row, gw & 3, role, P.x, P.out);
    else if (gw < 128) rloop<1>(row, gw & 3, role, P.x, P.out);
    else rloop<4>(row, gw & 3, role, P.x, P.out);
    asm volatile("griddepcontrol.wait;" ::: "memory");
    const int t = threadIdx.x & 127;
    for (int i = (blockIdx.x * 128 + t) * 4; i < 4 * NCL * 2560; i += NBC * 512)
      *reinterpret_cast<uint4*>(&g_part[0][0][0][0] + i) = make_uint4(0u, 0u, 0u, 0u);
    bar_sync(NB_END, 512);
    if (t == 0) {
      uint32_t n;
      asm volatile("atom.acq_rel.gpu.global.add.u32 %0, [%1], 1;" : "=r"(n) : "l"(&g_f[F_MISC][64]) : "memory");
      sts32(sb + BO_BOX, n);
    }
    bar_sync(NB_END2, 128);
    if (lds32(sb + BO_BOX) == NBC - 1) {
      for (int i = t; i < F_NUM * 24; i += 128) reinterpret_cast<uint4*>(&g_f[0][0])[i] = make_uint4(0u, 0u, 0u, 0u);
      g_xready[t][0] = 0; g_tpc[t] = 0;
    }
  } else {
    asm volatile("setmaxnreg.inc.sync.aligned.u32 224;");
    LANE_INIT();
    for (int i = blockIdx.x * 256 + threadIdx.x; i < 2 * (RD + 1) * TILE_B / 16; i += NBC * 256)
      reinterpret_cast<uint4*>(&g_acc[i < 2 * RD * TILE_B / 16 ? 0 : 1][0][0])[i] = make_uint4(0u, 0u, 0u, 0u);
    warp_signal(&g_f[F_MISC][0], lane);
    const int mt0 = (rot + wg) % 10;
    auto boxes = [&](int ss) {
      const int nb = op && ss ? 3 : 4;
      const uint32_t base = sb + (ss ? BO_RES + wg * OP_RES : wg * 83968);
      mbar_expect_if(warp == 0 && lane == 0, bar + 8 * (BB_W + wg), nb * 20480 + (op ? 2048 : 0));
      bar_sync(NB_H, 256);
      if (warp < nb) {
#pragma unroll 1
        for (int i = warp; i < 5 * nb; i += nb) {
          const int p = op ? i / nb : (i - 10) >> 1, mt = (mt0 + 2 * p) % 10;
          const bool first = !op && i < 10;
          tma2d_e(op || !ss ? base + i * 4096 : sb + (first ? BO_W1 : -81920) + (2 * i + wg) * 4096, &P.wmap[op ? 0 : (w12 ? 1 : 3) + !first], first ? 128 * j + 64 * wg : mt * 64,
                  op ? 320 * j + 64 * warp + 32 * ss : first ? 64 * i + 32 * ss : 128 * j + 32 * (i & 1) + 64 * ss, bar + 8 * (BB_W + wg));
        }
      }
      if (op && warp == 3) tma2d_e(base + nb * 20480, &P.wo16, (mt0 + 2 * ss) % 10 * 64, 95 * 64 + (j + 1) / 5 * 16, bar + 8 * (BB_W + wg));
      mbar_waitw(bar + 8 * (BB_W + wg), ss);
    };
    if (W_DELAY) __nanosleep(W_DELAY);
    uint32_t W[164];
    boxes(0);
    load_w<41>(W, sb + wg * 83968, warp, lane);
    fence_async();
    boxes(1);
    if (!op) {
      float cs[2] = {0.f, 0.f};
      const uint32_t a0 = sb + BO_W1 + wg * 4096 + ((lane >> 4) * 8 + (lane & 7)) * 128 + (((warp * 2 + ((lane >> 3) & 1)) ^ (lane & 7)) << 4);
#pragma unroll
      for (int i = 0; i < 80; i++) cs[i & 1] += bf_lo(W[i]) + bf_hi(W[i]);
#pragma unroll 1
      for (int i = 0; i < 40; i++) {
        uint32_t t[4];
        const uint32_t ad = a0 + (i % 20 >> 1) * 8192 + (i & 1) * 2048;
        ldsm4t(t[0], t[1], t[2], t[3], ad);
#pragma unroll
        for (int k = 0; k < 4; k++) {
          if (i < 20) cs[k & 1] += bf_lo(t[k]) + bf_hi(t[k]);
          t[k] = pack2h(bf_lo(t[k]) - cs[k & 1], bf_hi(t[k]) - cs[k & 1]);
        }
        if (i >= 20) stsm4t(ad, t[0], t[1], t[2], t[3]);
        if (i == 19) {
#pragma unroll
          for (int k = 0; k < 2; k++) { cs[k] += __shfl_xor_sync(~0u, cs[k], 1); cs[k] += __shfl_xor_sync(~0u, cs[k], 2); cs[k] *= 1.f / DM; }
        }
      }
      const uint32_t z = dep0(__float_as_uint(cs[0]), lane);
#pragma unroll
      for (int i = 0; i < 80; i++) W[i] = pack2h(bf_lo(W[i] | z) - cs[i & 1], bf_hi(W[i] | z) - cs[i & 1]);
      fence_async();
      bar_sync(NB_H, 256);
    }
    const uint32_t alo = uni((SMEM0 + (op ? BO_RES + wg * OP_RES : wg * 4096)) >> 4);
    if (op) {
      Ring rg = {(uint32_t)wg, 0};
      mbar_arrive_if(lane == 0, bar + 8 * BB_START);
      if (wg) bar_arrive(NB_PP, 256);
      const uint32_t blo = DESC_LO(BO_O), xlo = blo + (j + 1) / 5 * 2;
#pragma unroll 1
      for (int r = 0; r < NSTEP; r++) {
        asm volatile("" : "+r"(lane));
        if (fmask(r) == 3) op_round<64>(W, bar, alo, blo, xlo, j == 0, rg, wg, warp, lane, r);
        else op_round<32>(W, bar, alo, blo, xlo, j == 0, rg, wg, warp, lane, r);
        if (warp == 0) BTS(r, 2 + wg);
      }
    } else {
      const int q4 = (128 * j + 64 * wg + 16 * warp) / 160, off = w12 ? (0x0413 >> (4 * q4)) & 7 : 0;
#pragma unroll 1
      for (int r = 0; r < NR; r++) {
        asm volatile("" : "+r"(lane));
        const int bm = bmask(r), fm = w12 ? fmask(r) : bm;
        if (fm == 3) phase1<64>(W, sb, alo, 0, wg, warp, lane, off, r);
        else if (fm) phase1<32>(W, sb, alo, fm >> 1, wg, warp, lane, off, r);
        else { mbar_waitu(bar + 8 * (BB_SFREE + 4 + wg), (r + 1) & 1); carry_in(sb, wg, warp, lane); }
        CTS(33);
        fence_async();
        bar_sync(NB_H, 256);
        if (wg + warp == 0) BTS(r, 1);
        if (bm == 3) phase2<64>(W, bar, alo, DESC_LO(BO_H), wg, warp, lane, r);
        else phase2<32>(W, bar, alo, uni(DESC_LO(BO_H) + (bm >> 1) * 256), wg, warp, lane, r);
        if (warp == 0) BTS(r, 2 + wg);
      }
    }
    CTS_OUT();
    bar_arrive(NB_END, 512);
  }
}

typedef CUresult (*EncodeFn)(CUtensorMap*, CUtensorMapDataType, cuuint32_t, void*, const cuuint64_t*, const cuuint64_t*, const cuuint32_t*,
                             const cuuint32_t*, CUtensorMapInterleave, CUtensorMapSwizzle, CUtensorMapL2promotion, CUtensorMapFloatOOBfill);
static void make_map(EncodeFn fn, CUtensorMap* tm, const void* ptr, uint64_t cols, uint64_t rows, uint32_t bc, uint32_t br) {
  cuuint64_t dims[2] = {cols, rows}; cuuint64_t strides[1] = {cols * 2}; cuuint32_t box[2] = {bc, br}; cuuint32_t es[2] = {1, 1};
  fn(tm, CU_TENSOR_MAP_DATA_TYPE_BFLOAT16, 2, const_cast<void*>(ptr), dims, strides, box, es, CU_TENSOR_MAP_INTERLEAVE_NONE,
     CU_TENSOR_MAP_SWIZZLE_128B, CU_TENSOR_MAP_L2_PROMOTION_L2_256B, CU_TENSOR_MAP_FLOAT_OOB_FILL_NONE);
}
#define dbg_a_only 0
extern "C" void kernel_launch(void* const* d_in, const int* in_sizes, int n_in, void* d_out, int out_size) {
  void* fnp = nullptr; cudaDriverEntryPointQueryResult qr;
  cudaGetDriverEntryPoint("cuTensorMapEncodeTiled", &fnp, cudaEnableDefault, &qr);
  EncodeFn fn = (EncodeFn)fnp;
  cudaStream_t st = cudaStreamPerThread;
  cudaFuncSetAttribute(bworker_kernel, cudaFuncAttributeMaxDynamicSharedMemorySize, B_SMEM);
  {
    AMaps M;
    for (int i = 0; i < 3; i++) make_map(fn, &M.w16[i], d_in[2 + i], HD, DM, 64, 16);
    make_map(fn, &M.wo32, d_in[5], DM, HD, 64, 32);
    cudaFuncSetAttribute(acore_kernel, cudaFuncAttributeMaxDynamicSharedMemorySize, A_SMEM);
    cudaFuncSetAttribute(acore_kernel, cudaFuncAttributeNonPortableClusterSizeAllowed, 1);
    cudaLaunchConfig_t cfg = {};
    cfg.gridDim = dim3(CL_SIZE * NCL); cfg.blockDim = dim3(512); cfg.dynamicSmemBytes = A_SMEM; cfg.stream = st;
    cudaLaunchAttribute at[1]; at[0].id = cudaLaunchAttributeClusterDimension;
    at[0].val.clusterDim.x = CL_SIZE; at[0].val.clusterDim.y = 1; at[0].val.clusterDim.z = 1;
    cfg.attrs = at; cfg.numAttrs = 1;
    cudaLaunchKernelEx(&cfg, acore_kernel, M, (const __nv_bfloat16*)d_in[1], dbg_a_only ? 0 : 1);
  }
  if (!dbg_a_only) {
    BParams P;
    make_map(fn, &P.wmap[0], d_in[5], DM, HD, 64, 32);
    make_map(fn, &P.wo16, d_in[5], DM, HD, 64, 16);
    make_map(fn, &P.wmap[1], d_in[8], DM, DM, 64, 32);
    make_map(fn, &P.wmap[2], d_in[9], DM, DM, 64, 32);
    make_map(fn, &P.wmap[3], d_in[10], FF, DM, 64, 32);
    make_map(fn, &P.wmap[4], d_in[11], DM, FF, 64, 32);
    P.x = (const __nv_bfloat16*)d_in[0];
    P.out = (__nv_bfloat16*)d_out;
    cudaLaunchConfig_t cfg = {};
    cfg.gridDim = dim3(NBC); cfg.blockDim = dim3(512); cfg.dynamicSmemBytes = B_SMEM; cfg.stream = st;
    cudaLaunchAttribute at[1]; at[0].id = cudaLaunchAttributeProgrammaticStreamSerialization; at[0].val.programmaticStreamSerializationAllowed = 1;
    cfg.attrs = at; cfg.numAttrs = 1;
    cudaLaunchKernelEx(&cfg, bworker_kernel, P);
  }
}
```

```cpp
#include <cuda_runtime.h>
#include <cuda_bf16.h>
#include <cuda.h>
#include <stdint.h>

#define S_LEN 2048
#define DM 640
#define NH 32
#define DH 192
#define HD 6144
#define NSEG 64
#define FF 1536

__device__ __forceinline__ uint32_t smem_u32(const void* p) { return (uint32_t)__cvta_generic_to_shared(p); }
__device__ __forceinline__ uint32_t mapa(uint32_t a, uint32_t r) {
  uint32_t o; asm volatile("mapa.shared::cluster.u32 %0, %1, %2;" : "=r"(o) : "r"(a), "r"(r)); return o; }
__device__ __forceinline__ void mbar_init(uint32_t b, uint32_t c) {
  asm volatile("mbarrier.init.shared::cta.b64 [%0], %1;" :: "r"(b), "r"(c) : "memory"); }
__device__ __forceinline__ void mbar_expect(uint32_t b, uint32_t tx) {
  asm volatile("mbarrier.arrive.expect_tx.shared::cta.b64 _, [%0], %1;" :: "r"(b), "r"(tx) : "memory"); }
__device__ __forceinline__ void mbar_arrive(uint32_t b) {
  asm volatile("mbarrier.arrive.shared::cta.b64 _, [%0];" :: "r"(b) : "memory"); }
__device__ __forceinline__ void mbar_arrive_remote(uint32_t rb) {
  asm volatile("mbarrier.arrive.relaxed.cluster.shared::cluster.b64 _, [%0];" :: "r"(rb) : "memory"); }
__device__ __forceinline__ void mbar_expect_if(bool p, uint32_t b, uint32_t tx) {
  asm volatile("{\n.reg .pred q;\nsetp.ne.u32 q, %2, 0;\n@q mbarrier.arrive.expect_tx.shared::cta.b64 _, [%0], %1;\n}" :: "r"(b), "r"(tx), "r"((uint32_t)p) : "memory"); }
__device__ __forceinline__ void mbar_arrive_if(bool p, uint32_t b) {
  asm volatile("{\n.reg .pred q;\nsetp.ne.u32 q, %1, 0;\n@q mbarrier.arrive.shared::cta.b64 _, [%0];\n}" :: "r"(b), "r"((uint32_t)p) : "memory"); }
__device__ __forceinline__ void mbar_arrive_remote_if(bool p, uint32_t rb) {
  asm volatile("{\n.reg .pred q;\nsetp.ne.u32 q, %1, 0;\n@q mbarrier.arrive.relaxed.cluster.shared::cluster.b64 _, [%0];\n}" :: "r"(rb), "r"((uint32_t)p) : "memory"); }
__device__ __forceinline__ void sts32_if(bool p, uint32_t a, uint32_t v) {
  asm volatile("{\n.reg .pred q;\nsetp.ne.u32 q, %2, 0;\n@q st.shared.b32 [%0], %1;\n}" :: "r"(a), "r"(v), "r"((uint32_t)p) : "memory"); }
__device__ __forceinline__ void sts128z_if(bool p, uint32_t a) {
  asm volatile("{\n.reg .pred q;\nsetp.ne.u32 q, %1, 0;\n@q st.shared.v4.b32 [%0], {0,0,0,0};\n}" :: "r"(a), "r"((uint32_t)p) : "memory"); }
__device__ __forceinline__ bool mbar_try(uint32_t b, uint32_t ph) {
  uint32_t ok;
  asm volatile("{\n.reg .pred p;\nmbarrier.try_wait.parity.shared::cta.b64 p, [%1], %2;\nselp.u32 %0, 1, 0, p;\n}"
               : "=r"(ok) : "r"(b), "r"(ph) : "memory");
  return ok; }
__device__ __forceinline__ bool mbar_test(uint32_t b, uint32_t ph) {
  uint32_t ok;
  asm volatile("{\n.reg .pred p;\nmbarrier.test_wait.parity.shared::cta.b64 p, [%1], %2;\nselp.u32 %0, 1, 0, p;\n}"
               : "=r"(ok) : "r"(b), "r"(ph) : "memory");
  return ok; }
#define SPIN_LIMIT 4000000
#define FAIL() asm volatile("st.global.u32 [%0], 0;" :: "l"(8ull) : "memory")
#define CFENCE() asm volatile("fence.proxy.async::generic.acquire.sync_restrict::shared::cluster.cluster;" ::: "memory")
__device__ __forceinline__ void mbar_wait(uint32_t b, uint32_t ph) {
  int n = 0;
  while (!mbar_try(b, ph)) { if (++n > SPIN_LIMIT) FAIL(); } }
#define TIMEOUT_ACT "@!p st.shared.u32 [%0+1], 0;"
#define WAIT_HINT ", 20000"
#define WAIT_LIM "200000"
__device__ __forceinline__ void mbar_slow(uint32_t b, uint32_t ph) {
  asm volatile("{\n.reg .pred p, q;\n.reg .u32 n;\nmov.u32 n, 0;\n"
               "WL:\nmbarrier.try_wait.parity.shared::cta.b64 p, [%0], %1" WAIT_HINT ";\nadd.u32 n, n, 1;\nsetp.lt.and.u32 q, n, " WAIT_LIM ", !p;\n@q bra.uni WL;\n"
               TIMEOUT_ACT "\n}" :: "r"(b), "r"(ph) : "memory"); }
__device__ __forceinline__ void mbar_waitw(uint32_t b, uint32_t ph) {
  asm volatile("{\n.reg .pred p, q;\n.reg .u32 n;\nmbarrier.try_wait.parity.shared::cta.b64 p, [%0], %1;\n@p bra.uni WD;\nmov.u32 n, 0;\n"
               "WL:\nmbarrier.try_wait.parity.shared::cta.b64 p, [%0], %1" WAIT_HINT ";\nadd.u32 n, n, 1;\nsetp.lt.and.u32 q, n, " WAIT_LIM ", !p;\n@q bra.uni WL;\n"
               TIMEOUT_ACT "\nWD:\n}" :: "r"(b), "r"(ph) : "memory"); }
__device__ __forceinline__ void mbar_waitw2(uint32_t b0, uint32_t b1, uint32_t ph) {
  uint32_t ok;
  asm volatile("{\n.reg .pred p, r;\nmbarrier.try_wait.parity.shared::cta.b64 p, [%1], %3;\nmbarrier.try_wait.parity.shared::cta.b64 r, [%2], %3;\n"
               "and.pred p, p, r;\nselp.u32 %0, 1, 0, p;\n}" : "=r"(ok) : "r"(b0), "r"(b1), "r"(ph) : "memory");
  if (__builtin_expect(!__all_sync(~0u, ok), 0)) { mbar_slow(b0, ph); mbar_slow(b1, ph); }
}
__device__ __forceinline__ void mbar_waitu(uint32_t b, uint32_t ph) {
  asm volatile("{\n.reg .pred p;\nmbarrier.try_wait.parity.shared::cta.b64 p, [%0], %1;\n@p bra.uni WD;\n"
               "WL:\nmbarrier.try_wait.parity.shared::cta.b64 p, [%0], %1" WAIT_HINT ";\n@!p bra.uni WL;\nWD:\n}" :: "r"(b), "r"(ph) : "memory"); }
__device__ __forceinline__ void mbar_waitu2(uint32_t b0, uint32_t b1, uint32_t ph) {
  asm volatile("{\n.reg .pred p, r;\nWL:\nmbarrier.try_wait.parity.shared::cta.b64 p, [%0], %2;\nmbarrier.try_wait.parity.shared::cta.b64 r, [%1], %2;\n"
               "and.pred p, p, r;\n@!p bra.uni WL;\n}" :: "r"(b0), "r"(b1), "r"(ph) : "memory"); }
__device__ __forceinline__ void mbar_waitw4(uint32_t b, uint32_t ph) { mbar_waitw2(b, b + 8, ph); mbar_waitw2(b + 16, b + 24, ph); }
__device__ __forceinline__ uint32_t clock32() { uint32_t t; asm volatile("mov.u32 %0, %%clock;" : "=r"(t) :: "memory"); return t; }
template <int L> __device__ __forceinline__ uint32_t lop3(uint32_t a, uint32_t b, uint32_t c) {
  uint32_t r; asm("lop3.b32 %0, %1, %2, %3, %4;" : "=r"(r) : "r"(a), "r"(b), "r"(c), "n"(L)); return r; }
__device__ __forceinline__ void st_async_v2_if(bool p, uint32_t a, uint32_t v0, uint32_t v1, uint32_t mb) {
  asm volatile("{\n.reg .pred q;\nsetp.ne.u32 q, %4, 0;\n@q st.async.weak.shared::cluster.mbarrier::complete_tx::bytes.v2.b32 [%0], {%1,%2}, [%3];\n}"
               :: "r"(a), "r"(v0), "r"(v1), "r"(mb), "r"((uint32_t)p) : "memory"); }
__device__ __forceinline__ void keep4(const uint32_t* r, int lane) {
  asm volatile("{\n.reg .pred q;\nsetp.lt.s32 q, %4, 0;\n@q st.shared.v4.b32 [%4], {%0,%1,%2,%3};\n}" :: "r"(r[0]), "r"(r[1]), "r"(r[2]), "r"(r[3]), "r"(lane) : "memory"); }
__device__ __forceinline__ uint32_t uni(uint32_t x) { return __shfl_sync(~0u, x, 0); }
__device__ __forceinline__ void bulk_g2s_mc_e(uint32_t dst, const void* src, uint32_t bytes, uint32_t mb, uint16_t mask) {
  asm volatile("{\n.reg .pred e;\nelect.sync _|e, 0xffffffff;\n"
               "@e cp.async.bulk.shared::cluster.global.mbarrier::complete_tx::bytes.multicast::cluster [%0], [%1], %2, [%3], %4;\n}"
               :: "r"(dst), "l"(src), "r"(bytes), "r"(mb), "h"(mask) : "memory"); }
__device__ __forceinline__ void bulk_s2g_e(void* dst, uint32_t src, uint32_t bytes) {
  asm volatile("{\n.reg .pred e;\nelect.sync _|e, 0xffffffff;\n@e cp.async.bulk.global.shared::cta.bulk_group [%0], [%1], %2;\n}"
               :: "l"(dst), "r"(src), "r"(bytes) : "memory"); }
__device__ __forceinline__ void bulk_g2s_e(uint32_t dst, const void* src, uint32_t bytes, uint32_t mb) {
  asm volatile("{\n.reg .pred e;\nelect.sync _|e, 0xffffffff;\n@e cp.async.bulk.shared::cluster.global.mbarrier::complete_tx::bytes [%0], [%1], %2, [%3];\n}"
               :: "r"(dst), "l"(src), "r"(bytes), "r"(mb) : "memory"); }
#define STREAM_HINT 1
__device__ __forceinline__ void bulk_s2g_es(void* dst, uint32_t src, uint32_t bytes) {
  asm volatile("{\n.reg .pred e;\n.reg .b64 pol;\ncreatepolicy.fractional.L2::evict_first.b64 pol;\nelect.sync _|e, 0xffffffff;\n"
               "@e cp.async.bulk.global.shared::cta.bulk_group.L2::cache_hint [%0], [%1], %2, pol;\n}" :: "l"(dst), "r"(src), "r"(bytes) : "memory");
}
__device__ __forceinline__ void bulk_g2s_es(uint32_t dst, const void* src, uint32_t bytes, uint32_t mb) {
  asm volatile("{\n.reg .pred e;\n.reg .b64 pol;\ncreatepolicy.fractional.L2::evict_first.b64 pol;\nelect.sync _|e, 0xffffffff;\n"
               "@e cp.async.bulk.shared::cluster.global.mbarrier::complete_tx::bytes.L2::cache_hint [%0], [%1], %2, [%3], pol;\n}"
               :: "r"(dst), "l"(src), "r"(bytes), "r"(mb) : "memory"); }
__device__ __forceinline__ void tma2d_e(uint32_t dst, const CUtensorMap* tm, int c0, int c1, uint32_t mb) {
  asm volatile("{\n.reg .pred e;\nelect.sync _|e, 0xffffffff;\n"
               "@e cp.async.bulk.tensor.2d.shared::cluster.global.mbarrier::complete_tx::bytes [%0], [%1, {%3, %4}], [%2];\n}"
               :: "r"(dst), "l"((uint64_t)tm), "r"(mb), "r"(c0), "r"(c1) : "memory"); }
__device__ __forceinline__ uint32_t hadd2bf(uint32_t a, uint32_t b) {
  uint32_t r; asm("add.rn.bf16x2 %0, %1, %2;" : "=r"(r) : "r"(a), "r"(b)); return r; }
__device__ __forceinline__ void cluster_sync_all() {
  asm volatile("barrier.cluster.arrive.release.aligned;\nbarrier.cluster.wait.acquire.aligned;" ::: "memory"); }
__device__ __forceinline__ void bar_arrive(int id, int n) { asm volatile("bar.arrive %0, %1;" :: "r"(id), "r"(n) : "memory"); }
__device__ __forceinline__ void bar_arrive_dep(int id, int n, uint32_t dep) {
  asm volatile("{\n.reg .u32 t;\nand.b32 t, %2, 0;\nadd.u32 t, t, %0;\nbar.sync t, %1;\n}" :: "r"(id), "r"(n), "r"(dep) : "memory"); }
__device__ __forceinline__ void bar_sync(int id, int n) { asm volatile("bar.sync %0, %1;" :: "r"(id), "r"(n) : "memory"); }
__device__ __forceinline__ void fence_async() { asm volatile("fence.proxy.async.shared::cta;" ::: "memory"); }
__device__ __forceinline__ void st_async_b32(uint32_t a, uint32_t v, uint32_t mb) {
  asm volatile("st.async.weak.shared::cluster.mbarrier::complete_tx::bytes.b32 [%0], %1, [%2];" :: "r"(a), "r"(v), "r"(mb) : "memory"); }
__device__ __forceinline__ void st_async_v2(uint32_t a, uint32_t v0, uint32_t v1, uint32_t mb) {
  asm volatile("st.async.weak.shared::cluster.mbarrier::complete_tx::bytes.v2.b32 [%0], {%1,%2}, [%3];" :: "r"(a), "r"(v0), "r"(v1), "r"(mb) : "memory"); }
__device__ __forceinline__ void st_async_v4(uint32_t a, uint32_t v0, uint32_t v1, uint32_t v2, uint32_t v3, uint32_t mb) {
  asm volatile("st.async.weak.shared::cluster.mbarrier::complete_tx::bytes.v4.b32 [%0], {%1,%2,%3,%4}, [%5];" :: "r"(a), "r"(v0), "r"(v1), "r"(v2), "r"(v3), "r"(mb) : "memory"); }
__device__ __forceinline__ void ldsm4(uint32_t& r0, uint32_t& r1, uint32_t& r2, uint32_t& r3, uint32_t a) {
  asm volatile("ldmatrix.sync.aligned.m8n8.x4.shared.b16 {%0,%1,%2,%3}, [%4];" : "=r"(r0), "=r"(r1), "=r"(r2), "=r"(r3) : "r"(a) : "memory"); }
__device__ __forceinline__ void ldsm4t(uint32_t& r0, uint32_t& r1, uint32_t& r2, uint32_t& r3, uint32_t a) {
  asm volatile("ldmatrix.sync.aligned.m8n8.x4.trans.shared.b16 {%0,%1,%2,%3}, [%4];" : "=r"(r0), "=r"(r1), "=r"(r2), "=r"(r3) : "r"(a) : "memory"); }
__device__ __forceinline__ void stsm2t(uint32_t a, uint32_t r0, uint32_t r1) {
  asm volatile("stmatrix.sync.aligned.m8n8.x2.trans.shared.b16 [%0], {%1,%2};" :: "r"(a), "r"(r0), "r"(r1) : "memory"); }
__device__ __forceinline__ void stsm4t(uint32_t a, uint32_t r0, uint32_t r1, uint32_t r2, uint32_t r3) {
  asm volatile("stmatrix.sync.aligned.m8n8.x4.trans.shared.b16 [%0], {%1,%2,%3,%4};" :: "r"(a), "r"(r0), "r"(r1), "r"(r2), "r"(r3) : "memory"); }
__device__ __forceinline__ uint32_t movm(uint32_t a) {
  uint32_t d; asm volatile("movmatrix.sync.aligned.m8n8.trans.b16 %0, %1;" : "=r"(d) : "r"(a)); return d; }
__device__ __forceinline__ void mma16816(float* d, uint32_t a0, uint32_t a1, uint32_t a2, uint32_t a3, uint32_t b0, uint32_t b1) {
  asm("mma.sync.aligned.m16n8k16.row.col.f32.bf16.bf16.f32 {%0,%1,%2,%3}, {%4,%5,%6,%7}, {%8,%9}, {%0,%1,%2,%3};"
               : "+f"(d[0]), "+f"(d[1]), "+f"(d[2]), "+f"(d[3]) : "r"(a0), "r"(a1), "r"(a2), "r"(a3), "r"(b0), "r"(b1)); }
__device__ __forceinline__ void mma16816v(float* d, uint32_t a0, uint32_t a1, uint32_t a2, uint32_t a3, uint32_t b0, uint32_t b1) {
  asm volatile("mma.sync.aligned.m16n8k16.row.col.f32.bf16.bf16.f32 {%0,%1,%2,%3}, {%4,%5,%6,%7}, {%8,%9}, {%0,%1,%2,%3};"
               : "+f"(d[0]), "+f"(d[1]), "+f"(d[2]), "+f"(d[3]) : "r"(a0), "r"(a1), "r"(a2), "r"(a3), "r"(b0), "r"(b1)); }
__device__ __forceinline__ uint32_t pack2(float lo, float hi) {
  uint32_t r; asm("cvt.rn.bf16x2.f32 %0, %1, %2;" : "=r"(r) : "f"(hi), "f"(lo)); return r; }
__device__ __forceinline__ uint32_t pack2v(float lo, float hi) {
  uint32_t r; asm volatile("cvt.rn.bf16x2.f32 %0, %1, %2;" : "=r"(r) : "f"(hi), "f"(lo)); return r; }
__device__ __forceinline__ float bf_lo(uint32_t w) { return __uint_as_float(w << 16); }
__device__ __forceinline__ float bf_hi(uint32_t w) { return __uint_as_float(w & 0xffff0000u); }
__device__ __forceinline__ uint4 lds128(uint32_t a) {
  uint4 v; asm volatile("ld.shared.v4.b32 {%0,%1,%2,%3}, [%4];" : "=r"(v.x), "=r"(v.y), "=r"(v.z), "=r"(v.w) : "r"(a) : "memory"); return v; }
__device__ __forceinline__ uint4 lds128_nv(uint32_t a) {
  uint4 v; asm volatile("ld.shared.v4.b32 {%0,%1,%2,%3}, [%4];" : "=r"(v.x), "=r"(v.y), "=r"(v.z), "=r"(v.w) : "r"(a)); return v; }
__device__ __forceinline__ void st_async_v2_nm(uint32_t a, uint32_t v0, uint32_t v1, uint32_t mb) {
  asm volatile("st.async.weak.shared::cluster.mbarrier::complete_tx::bytes.v2.b32 [%0], {%1,%2}, [%3];" :: "r"(a), "r"(v0), "r"(v1), "r"(mb)); }
__device__ __forceinline__ float rcpf(float x) { float y; asm("rcp.approx.ftz.f32 %0, %1;" : "=f"(y) : "f"(x)); return y; }
__device__ __forceinline__ void sts64(uint32_t a, uint32_t x, uint32_t y) { asm volatile("st.shared.v2.b32 [%0], {%1,%2};" :: "r"(a), "r"(x), "r"(y) : "memory"); }
__device__ __forceinline__ float ex2(float x) { float y; asm("ex2.approx.ftz.f32 %0, %1;" : "=f"(y) : "f"(x)); return y; }
__device__ __forceinline__ uint32_t lds32(uint32_t a) {
  uint32_t v; asm volatile("ld.shared.b32 %0, [%1];" : "=r"(v) : "r"(a) : "memory"); return v; }
__device__ __forceinline__ uint2 lds64(uint32_t a) {
  uint2 v; asm volatile("ld.shared.v2.b32 {%0,%1}, [%2];" : "=r"(v.x), "=r"(v.y) : "r"(a) : "memory"); return v; }
__device__ __forceinline__ void sts128(uint32_t a, uint32_t x, uint32_t y, uint32_t z, uint32_t w) {
  asm volatile("st.shared.v4.b32 [%0], {%1,%2,%3,%4};" :: "r"(a), "r"(x), "r"(y), "r"(z), "r"(w) : "memory"); }
__device__ __forceinline__ void sts32(uint32_t a, uint32_t x) { asm volatile("st.shared.b32 [%0], %1;" :: "r"(a), "r"(x) : "memory"); }
__device__ __forceinline__ void tma2d(uint32_t dst, const CUtensorMap* tm, int c0, int c1, uint32_t mb) {
  asm volatile("cp.async.bulk.tensor.2d.shared::cluster.global.mbarrier::complete_tx::bytes [%0], [%1, {%3, %4}], [%2];"
               :: "r"(dst), "l"((uint64_t)tm), "r"(mb), "r"(c0), "r"(c1) : "memory"); }
__device__ __forceinline__ void tma2d_prefetch(const CUtensorMap* tm, int c0, int c1) {
  asm volatile("cp.async.bulk.prefetch.tensor.2d.L2.global.tile [%0, {%1, %2}];" :: "l"((uint64_t)tm), "r"(c0), "r"(c1) : "memory"); }
__device__ __forceinline__ void bulk_g2s_mc(uint32_t dst, const void* src, uint32_t bytes, uint32_t mb, uint16_t mask) {
  asm volatile("cp.async.bulk.shared::cluster.global.mbarrier::complete_tx::bytes.multicast::cluster [%0], [%1], %2, [%3], %4;"
               :: "r"(dst), "l"(src), "r"(bytes), "r"(mb), "h"(mask) : "memory"); }
__device__ __forceinline__ void bulk_s2g(void* dst, uint32_t src, uint32_t bytes) {
  asm volatile("cp.async.bulk.global.shared::cta.bulk_group [%0], [%1], %2;" :: "l"(dst), "r"(src), "r"(bytes) : "memory"); }
__device__ __forceinline__ void wg_fence() { asm volatile("wgmma.fence.sync.aligned;" ::: "memory"); }
__device__ __forceinline__ void wg_commit() { asm volatile("wgmma.commit_group.sync.aligned;" ::: "memory"); }
template <int N> __device__ __forceinline__ void wg_wait() { asm volatile("wgmma.wait_group.sync.aligned %0;" :: "n"(N) : "memory"); }
__device__ __forceinline__ uint64_t mkdesc(uint32_t addr, uint32_t lbo, uint32_t sbo, uint32_t swz) {
  return (uint64_t)((addr & 0x3FFFF) >> 4) | ((uint64_t)(lbo >> 4) << 16) | ((uint64_t)(sbo >> 4) << 32) | ((uint64_t)swz << 62); }

#define ACC4(d) "+f"(d[0]),"+f"(d[1]),"+f"(d[2]),"+f"(d[3])
#define ACC8(d) ACC4(d), ACC4((d + 4))
#define ACC16(d) ACC8(d), ACC8((d + 8))
#define ACC20(d) ACC16(d), ACC4((d + 16))
#define ACC24(d) ACC16(d), ACC8((d + 16))
#define SMEM0 0x400
__host__ __device__ constexpr uint32_t dlo(uint32_t off, uint32_t lbo) { return ((SMEM0 + off) >> 4) | ((lbo >> 4) << 16); }
__host__ __device__ constexpr uint32_t dhi(uint32_t sbo, uint32_t swz) { return (sbo >> 4) | (swz << 30); }
#define R4S "{%0,%1,%2,%3}"
#define R8S "{%0,%1,%2,%3,%4,%5,%6,%7}"
#define R16S "{%0,%1,%2,%3,%4,%5,%6,%7,%8,%9,%10,%11,%12,%13,%14,%15}"
#define R20S "{%0,%1,%2,%3,%4,%5,%6,%7,%8,%9,%10,%11,%12,%13,%14,%15,%16,%17,%18,%19}"
#define R24S "{%0,%1,%2,%3,%4,%5,%6,%7,%8,%9,%10,%11,%12,%13,%14,%15,%16,%17,%18,%19,%20,%21,%22,%23}"
#define ACC32(d) ACC16(d), ACC16((d + 16))
#define R32S "{%0,%1,%2,%3,%4,%5,%6,%7,%8,%9,%10,%11,%12,%13,%14,%15,%16,%17,%18,%19,%20,%21,%22,%23,%24,%25,%26,%27,%28,%29,%30,%31}"
struct Dsc {
  uint64_t b; uint32_t e;
  __device__ __forceinline__ Dsc operator+(uint32_t o) const { return {b + o, e}; }
};
template <int K> __device__ __forceinline__ uint32_t fresh(int i) {
  uint32_t e; asm volatile("{\n.reg .u32 t;\nadd.u32 t, %1, %2;\nshr.u32 %0, t, %3;\n}" : "=r"(e) : "r"(i), "n"((256 << K) + 1), "n"(8 + K)); return e; }
template <int N, bool H = false> struct MM;
#define DEF_MM(N, H, T, ACCM, RS_, I0, I1, I2, I3, I4, I5, I6, I7)                                                                \
  template <> struct MM<N, H> {                                                                                                   \
    template <uint32_t BLO, int ACC>                                                                                              \
    static __device__ __forceinline__ void rs(float* d, const uint32_t* a, Dsc b0) {                                              \
      asm volatile("{\n.reg .b64 b;\nmad.wide.u32 b, %" #I7 ", %" #I5 ", %" #I4 ";\n"                                             \
                   "wgmma.mma_async.sync.aligned.m64n" #N "k16.f32." T "." T " " RS_ ", {%" #I0 ",%" #I1 ",%" #I2 ",%" #I3 "}, b, %" #I6 ", 1, 1, 0;\n}" \
                   : ACCM(d) : "r"(a[0]), "r"(a[1]), "r"(a[2]), "r"(a[3]), "l"(b0.b), "n"(BLO), "n"(ACC), "r"(b0.e)); }           \
    template <uint32_t ALO, uint32_t BLO, int ACC, int TA = 1>                                                                    \
    static __device__ __forceinline__ void ss(float* d, Dsc a0, Dsc b0) {                                                         \
      asm volatile("{\n.reg .b64 a, b;\nmad.wide.u32 a, %" #I6 ", %" #I1 ", %" #I0 ";\nmad.wide.u32 b, %" #I6 ", %" #I3 ", %" #I2 ";\n" \
                   "wgmma.mma_async.sync.aligned.m64n" #N "k16.f32." T "." T " " RS_ ", a, b, %" #I4 ", 1, 1, %" #I5 ", 0;\n}"    \
                   : ACCM(d) : "l"(a0.b), "n"(ALO), "l"(b0.b), "n"(BLO), "n"(ACC), "n"(TA), "r"(b0.e)); }                         \
  };
DEF_MM(8, false, "bf16", ACC4, R4S, 4, 5, 6, 7, 8, 9, 10, 11)
DEF_MM(16, false, "bf16", ACC8, R8S, 8, 9, 10, 11, 12, 13, 14, 15)
DEF_MM(32, false, "bf16", ACC16, R16S, 16, 17, 18, 19, 20, 21, 22, 23)
DEF_MM(40, false, "bf16", ACC20, R20S, 20, 21, 22, 23, 24, 25, 26, 27)
DEF_MM(48, false, "bf16", ACC24, R24S, 24, 25, 26, 27, 28, 29, 30, 31)
DEF_MM(64, false, "bf16", ACC32, R32S, 32, 33, 34, 35, 36, 37, 38, 39)
DEF_MM(32, true, "f16", ACC16, R16S, 16, 17, 18, 19, 20, 21, 22, 23)
DEF_MM(64, true, "f16", ACC32, R32S, 32, 33, 34, 35, 36, 37, 38, 39)

#define LAG 10
#define NSTEP (NSEG + LAG)
#define NR (NSTEP + 1)
__device__ __align__(1024) __nv_bfloat16 g_xn[2][S_LEN * DM];
#define RO 16
static_assert(RO > LAG + 1, "ring");
__device__ __align__(1024) unsigned char g_o[RO * 96 * 8192];
__device__ __align__(1024) uint32_t g_part[6][7][40][64];
#define RD 16
#define TILE_B 81920
__device__ __align__(1024) float2 g_stat[S_LEN];
__device__ __align__(1024) uint32_t g_st2[2][RD][64];
__device__ __align__(1024) unsigned char g_acc[5][RD][TILE_B];
#define NOP 19
#define NW12 5
#define NW34 12
#define NBC (NOP + NW12 + NW34)
__device__ __align__(1024) unsigned char g_wt[NOP * 10 * 12288];
enum { F_O = 0, F_R1 = NOP + 1, F_R2 = F_R1 + 4, F_R3 = F_R2 + 4, F_Z = F_R3 + 4, F_DONE, F_MISC, F_NUM };
__device__ __align__(128) uint32_t g_f[F_NUM][96];
__device__ __align__(128) int g_xready[129][8];
__device__ uint32_t g_tpc[128];
#define TS(i)
#define TSV(i, v)
#define TSN(i)
#define TSD(i, dep)
#define BTS(k, i)
#define BTS2(k, i)
#define RTS(i)
#define RTSD(i, dep)
#define RTS_OUT()
#define CTS(i)
#define PTS(i)
#define PTS1(i)
#define CTS_OUT()
#define GTS(i)

#define CL_SIZE 15
#define NCL 7
#define SSQ 13
#define SSV 16
#define PL_SZ 5376
#define TILE_SBO 2560
#define TILE_GRP 15360
#define WS_SZ ((2 * SSQ + SSV) * 2048)
#define OFF_QK (OFF_WO + 26 * 2048)
#define LAYOUT 2
#define OFF_TILE 0
#define OFF_WS (4 * TILE_GRP)
#define OFF_WO (OFF_WS + WS_SZ)
#define OFF_PL (OFF_QK + 20480)
#define OFF_BAR (OFF_PL + 2 * PL_SZ)
#define STG_Q OFF_TILE
#define STG_K OFF_WO
#define VA 14
#define STG_V2 (OFF_TILE + 27 * 2048)
#define OFF_O (OFF_PL + 4352)
#define LAND(k) (((k) >> 1) * TILE_GRP + ((k) & 1) * 1280)
#define LAND_F (5 * TILE_SBO)
#define OFF_XL (OFF_TILE + 3 * TILE_GRP)
#define OFF_XF (OFF_XL + LAND_F)
#define OFF_WT ((OFF_XL + TILE_SBO + 1023) & ~1023)
#define OFF_TAB (OFF_BAR + 240)
#define OFF_INV (OFF_TAB + 64)
#define OFF_TS (OFF_INV + 128)
#define A_SMEM 232448
static_assert(WS_SZ + 72 * 1024 + 2 * PL_SZ + 4 * TILE_GRP + 512 == A_SMEM && OFF_WS % 1024 == 0 && OFF_WO % 1024 == 0 && SSQ == 13, "smem map");
enum { B_W0 = 0, B_W1, B_F1, B_F2 = B_F1 + 4, B_R1 = B_F2 + 4, B_R2, B_MEMFREE, B_LANDFREE, B_OPEER, B_PLFREE, B_XFREE, B_SB, B_WOF = B_SB + 6, B_WTF, B_RS, B_NUM = B_RS + 4 };
static_assert(B_NUM <= 30, "barriers");
enum { N_C = 0, N_SISS, N_QK, N_V, N_PM, N_TURN, N_PI, N_VGO, N_O, N_PX, N_AB, N_SDONE, N_VDONE, N_G3, N_P, N_OX };

__device__ __forceinline__ bool is_dual(int j) { return j >= LAG && j < NSEG; }
__device__ __forceinline__ int sched_l(int j) { return j < NSEG ? j : NSEG + j - LAG; }
__device__ __forceinline__ int sched_f(int j) { return NSEG + j - LAG; }
__device__ __forceinline__ void wait_cnt(const int* p, int target) {
  int v, n = 0;
  do {
    asm volatile("ld.relaxed.gpu.global.b32 %0, [%1];" : "=r"(v) : "l"(p) : "memory");
    if (v >= target) break;
    __nanosleep(100);
    if (++n > SPIN_LIMIT) FAIL();
  } while (true);
  asm volatile("fence.acquire.gpu;" ::: "memory");
  asm volatile("fence.proxy.async.global;" ::: "memory");
}
__device__ __forceinline__ void red_release(void* p, uint32_t v) { asm volatile("red.release.gpu.global.add.u32 [%0], %1;" :: "l"(p), "r"(v) : "memory"); }
__device__ __forceinline__ void red_relaxed(void* p, uint32_t v) { asm volatile("red.relaxed.gpu.global.add.u32 [%0], %1;" :: "l"(p), "r"(v) : "memory"); }
#define VMASK 0xa5294a5294ull
__host__ __device__ constexpr int popc40(unsigned long long m) { int c = 0; for (; m; m &= m - 1) c++; return c; }
static_assert(popc40(VMASK) == SSV, "mask");
__host__ __device__ constexpr int ss_idx(int ks, int n) { return n == SSV ? popc40(VMASK & ((1ull << ks) - 1)) : ks * n / 40; }
__host__ __device__ constexpr bool is_ss(int ks, int n) { return ss_idx(ks + 1, n) != ss_idx(ks, n); }
__host__ __device__ constexpr int rs_idx(int ks, int n) { return ks - ss_idx(ks, n); }

#define SL2 (0.07216878364870322f * 1.4426950408889634f)

#define SUM_LOOP 0
struct Desc { Dsc tile, unit, k1, pl, p; };
__device__ __forceinline__ Desc make_desc(const uint64_t* h, uint32_t u, uint32_t e) {
  return {{h[0], e}, {h[1] + u * 128, e}, {h[2], e}, {h[3], e}, {h[4], e}};
}
template <int N, int NSS, int RG, int KS, int K1, int K0 = 0>
__device__ __forceinline__ void proj(float* acc, const uint32_t* W, const Desc& D) {
  if constexpr (KS < K1) {
    constexpr uint32_t BLO = dlo(OFF_TILE + (KS / 10) * TILE_GRP + RG * TILE_SBO + (KS % 10) * 256, 128);
    if constexpr (is_ss(KS, NSS)) MM<N>::template ss<dlo(OFF_WS + ss_idx(KS, NSS) * 2048, 0), BLO, (KS != K0)>(acc, D.unit, D.tile);
    else MM<N>::template rs<BLO, (KS != K0)>(acc, W + rs_idx(KS, NSS) * 4, D.tile);
    proj<N, NSS, RG, KS + 1, K1, K0>(acc, W, D);
  }
}
template <int N>
__device__ __forceinline__ void load_w(uint32_t* W, uint32_t stage, int warp, int lane) {
  const int kr = (lane >> 4) * 8 + (lane & 7);
  const int cb = warp * 2 + ((lane >> 3) & 1);
  const uint32_t a0 = stage + kr * 128 + ((cb ^ (lane & 7)) << 4);
#pragma unroll
  for (int i = 0; i < N; i++) ldsm4t(W[4 * i], W[4 * i + 1], W[4 * i + 2], W[4 * i + 3], a0 + i * 2048);
}
template <int N, int G, int U, int OS, int ACC>
__device__ __forceinline__ void wo4(float* d, const Desc& D) {
  constexpr uint32_t WA = (U >= 4 ? OFF_WO + (U - 4) * 2048 : OFF_WT) - G * SSQ * 2048, OB = OS == 0 ? OFF_O : OS == 1 ? OFF_XL : OFF_XF;
  Dsc b = OS ? D.k1 : D.pl;
  b.e = fresh<(U < 16 ? U / 4 : U / 8 - 2) + (N == 8 ? 4 : 0)>(D.unit.e);
  MM<N>::template ss<dlo(WA, 0), dlo(OB, 128), ACC>(d, D.unit, b);
  MM<N>::template ss<dlo(WA + 2048, 0), dlo(OB + 256, 128), 1>(d, D.unit, b);
  MM<N>::template ss<dlo(WA + 4096, 0), dlo(OB + 512, 128), 1>(d, D.unit, b);
  MM<N>::template ss<dlo(WA + 6144, 0), dlo(OB + 768, 128), 1>(d, D.unit, b);
}
__device__ __forceinline__ void wo_coord(int i, int t3, int head, int& c0, int& c1) {
  const int g = i >> 1;
  const int blk = g == 0 ? 9 : (g < 4 ? g - 1 : (g - 4) >> 1) * 3 + t3;
  int sl = g < 4 ? t3 : (g & 1) ? t3 + 1 : t3 + 2;
  if (sl >= 3) sl -= 3;
  c0 = blk * 64; c1 = head * DH + sl * 64 + (i & 1) * 32;
}
__device__ __forceinline__ void tok_softmax(uint32_t sb, int job, int lane) {
  const bool w1 = job & 1;
  const int dg = (lane >> 2) - (lane & 3) * 2;
  const uint32_t lo = sb + OFF_PL + (job >> 1) * PL_SZ + (job & 1) * 1792, l8 = lo + 512 + lane * 8, pa = lo + lane * 4;
  const uint32_t km = job & 2 ? 640 : 512;
  float x[14];
  {
    const uint4 a = lds128(lo + lane * 16);
    const uint2 e = lds64(l8);
    const uint32_t c = lds32(768 + pa);
    x[0] = bf_lo(a.x); x[1] = bf_hi(a.x); x[2] = bf_lo(a.y); x[3] = bf_hi(a.y); x[4] = bf_lo(a.z); x[5] = bf_hi(a.z); x[6] = bf_lo(a.w); x[7] = bf_hi(a.w);
    x[8] = bf_lo(c); x[9] = bf_hi(c); x[10] = bf_lo(e.x); x[11] = bf_hi(e.x); x[12] = bf_lo(e.y); x[13] = bf_hi(e.y);
  }
  if (dg < 0) { x[8] = -INFINITY; if (w1) x[4] = -INFINITY; else x[10] = -INFINITY; }
  if (dg < 1) { x[9] = -INFINITY; if (w1) x[5] = -INFINITY; else x[11] = -INFINITY; }
  const float m4 = fmaxf(x[8], x[9]);
  float m0 = fmaxf(fmaxf(fmaxf(x[0], x[1]), fmaxf(x[2], x[3])), fmaxf(fmaxf(x[4], x[5]), fmaxf(x[6], x[7])));
  float m1 = fmaxf(fmaxf(x[10], x[11]), fmaxf(x[12], x[13]));
  if (w1) m1 = fmaxf(m1, m4); else m0 = fmaxf(m0, m4);
  m0 = fmaxf(m0, __shfl_xor_sync(~0u, m0, 1)); m1 = fmaxf(m1, __shfl_xor_sync(~0u, m1, 1));
  sts32(pa + (w1 ? 384 : 896 + 128), 0u); sts32(pa + 1152 - km, 0u); sts32(pa + 896 + 1152 - km, 0u); sts64(l8 + 896 - 256, 0u, 0u);
  m0 = fmaxf(m0, __shfl_xor_sync(~0u, m0, 2)); m1 = fmaxf(m1, __shfl_xor_sync(~0u, m1, 2));
  m0 *= -SL2; m1 *= -SL2;
#pragma unroll
  for (int j = 0; j < 14; j++) x[j] = ex2(fmaf(x[j], SL2, j < 8 ? m0 : j >= 10 ? m1 : w1 ? m1 : m0));
  const float l4s = x[8] + x[9];
  float l0 = ((x[0] + x[1]) + (x[2] + x[3])) + ((x[4] + x[5]) + (x[6] + x[7])), l1 = (x[10] + x[11]) + (x[12] + x[13]);
  if (w1) l1 += l4s; else l0 += l4s;
  l0 += __shfl_xor_sync(~0u, l0, 1); l1 += __shfl_xor_sync(~0u, l1, 1);
  l0 += __shfl_xor_sync(~0u, l0, 2); l1 += __shfl_xor_sync(~0u, l1, 2);
  l0 = rcpf(l0); l1 = rcpf(l1);
#pragma unroll
  for (int j = 0; j < 7; j++) {
    const float iv = j < 4 ? l0 : j > 4 ? l1 : w1 ? l1 : l0;
    sts32(pa + (j < 3 ? j * 128 : j == 3 ? km : j == 4 ? (w1 ? 896 + 128 : 384) : j == 5 ? 896 : 896 + km), pack2(x[2 * j] * iv, x[2 * j + 1] * iv));
  }
}
template <int N>
__device__ __forceinline__ void wo_phase(uint32_t sb, int wg, int warp, int lane, uint32_t par, uint32_t r1, const Desc& D) {
  const uint32_t bar = sb + OFF_BAR;
  float x[N / 2], y[N / 2];
  const uint2 ta = lds64(sb + OFF_TAB + (wg * 4 + warp) * 8);
  uint32_t xa = (ta.x & ~255u) + lane * 8, xb = (ta.x & 0xFF0000FFu) + SMEM0 + OFF_BAR, ya = (ta.y & ~255u) + lane * 8, yb = (ta.y & 0xFF0000FFu) + SMEM0 + OFF_BAR;
  asm volatile("" : "+r"(xa), "+r"(xb), "+r"(ya), "+r"(yb));
  auto scat = [&](uint32_t ad, uint32_t mb, const float* d) {
    st_async_v2(ad, pack2(d[0], d[1]), pack2(d[2], d[3]), mb);
    if (N == 16) st_async_v2(ad + LAND_F, pack2(d[4], d[5]), pack2(d[6], d[7]), mb);
  };
  if (wg == 0) {
    bar_sync(N_O, 384);
    wg_fence(); wo4<N, 0, 4, 0, 0>(x, D); wo4<N, 0, 8, 0, 0>(y, D); wg_commit();
    mbar_waitu(bar + 8 * B_OPEER, par);
    CFENCE(); wg_fence(); wo4<N, 0, 16, 1, 1>(x, D); wo4<N, 0, 20, 2, 1>(x, D); wg_commit();
    wo4<N, 0, 24, 1, 1>(y, D); wg_commit();
    mbar_waitu2(bar + 8 * B_WOF, bar + 8 * B_MEMFREE, par);
    wg_fence(); wo4<N, 0, 28, 2, 1>(y, D); wg_commit();
    bar_arrive(N_AB, 256);
    wg_wait<2>(); scat(xa, xb, x);
    wg_wait<0>(); scat(ya, yb, y);
  } else {
    bar_sync(N_O, 384);
    wg_fence(); wo4<N, 1, 0, 0, 0>(x, D); wg_commit(); wo4<N, 1, 12, 0, 0>(y, D); wg_commit();
    wg_wait<1>(); mbar_arrive_remote_if(lane == 0, r1);
    mbar_waitu(bar + 8 * B_MEMFREE, par);
    scat(xa, xb, x);
    bar_sync(N_AB, 256);
    CFENCE(); wg_fence(); wo4<N, 1, 32, 1, 1>(y, D); wo4<N, 1, 36, 2, 1>(y, D); wg_commit();
    bar_arrive(N_TURN, 256);
    wg_wait<0>(); scat(ya, yb, y);
  }
}
#define DS_DUAL 10
#define DS_SINGLE 20
#define POLL_GAP 100
#define POLL_GAPD 0
#define TOK_DELAY 250
#define LATE_SM 1
#define UMAX 40
#define VD1 6
#define VS1 4
#define VST 17
struct AMaps { CUtensorMap w16[3], wo32; uint64_t d[5]; };
__global__ void __launch_bounds__(512, 1)
acore_kernel(const __grid_constant__ AMaps M, const __nv_bfloat16* __restrict__ mem0, int sync_b) {
  extern __shared__ __align__(1024) unsigned char smem_raw[];
  const uint32_t sb = smem_u32(smem_raw);
  GTS(24);
  if (threadIdx.x == 0) {
    uint32_t smid; asm volatile("mov.u32 %0, %%smid;" : "=r"(smid));
    g_tpc[(smid >> 1) & 127] = blockIdx.x - CL_SIZE < 3 * CL_SIZE && blockIdx.x % CL_SIZE >= 12 ? 1 : 2;
    __threadfence();
    asm volatile("griddepcontrol.launch_dependents;");
  }
  const int lane0 = threadIdx.x & 31;
#define LANE_INIT() int lane; asm volatile("mov.u32 %0, %%laneid;" : "=r"(lane))
  const int warp = __shfl_sync(~0u, (threadIdx.x >> 5) & 3, 0);
  const int cl = blockIdx.x / CL_SIZE;
  const uint32_t rank = blockIdx.x - cl * CL_SIZE;
  const int nh = cl >= 1 && cl <= 3 ? 4 : 5;
  const int nA = 3 * nh;
  const int wg = __shfl_sync(~0u, (int)rank < nA ? threadIdx.x >> 7 : 4, 0);
  const int head = (cl < 4 ? (cl ? 1 + 4 * cl : 0) : 5 * cl - 3) + rank / 3;
  const int t3 = rank % 3;
  const int col0 = head * DH + t3 * 64;
  const uint32_t bar = sb + OFF_BAR;
  const uint32_t rb0 = SMEM0;
  const uint16_t mcmask = (uint16_t)((1u << nA) - 1);
  const uint32_t nxt = sb + ((t3 == 2 ? -2 : 1) << 24), prv = sb + ((t3 == 0 ? 2 : -1) << 24);
  const int ig = (int)rank - (nA - 4);

  if (threadIdx.x == 0) {
    if (mapa(sb, nA - 1) != rb0 + ((nA - 1) << 24) || mapa(sb, 0) != rb0 || mapa(sb, 1) != rb0 + (1u << 24) || sb != SMEM0 + (rank << 24)) FAIL();
    for (int i = 0; i < B_NUM; i++)
      mbar_init(bar + 8 * i, i == B_R1 ? 4 * nA : i == B_R2 ? 12 * nA : i == B_MEMFREE ? nA : i == B_LANDFREE ? 4 * nA : i == B_PLFREE || i == B_XFREE ? 2 : 1);
    asm volatile("fence.mbarrier_init.release.cluster;" ::: "memory");
    mbar_expect(bar + 8 * B_W0, (80 + SSV + VST) * 2048);
  }
  __syncthreads();
  if (lane0 == 0) {
    const int w12 = wg * 4 + warp;
    if (w12 < 10) {
#pragma unroll 1
      for (int ks = 4 * w12; ks < 4 * w12 + 4; ks++) {
        const bool ss = is_ss(ks, SSQ);
        tma2d(ss ? sb + OFF_WS + ss_idx(ks, SSQ) * 2048 : sb + STG_Q + rs_idx(ks, SSQ) * 2048, &M.w16[0], col0, ks * 16, bar + 8 * B_W0);
        tma2d(ss ? sb + OFF_WS + (SSQ + ss_idx(ks, SSQ)) * 2048 : sb + STG_K + rs_idx(ks, SSQ) * 2048, &M.w16[1], col0, ks * 16, bar + 8 * B_W0);
        if (is_ss(ks, SSV)) tma2d(sb + OFF_WS + (2 * SSQ + ss_idx(ks, SSV)) * 2048, &M.w16[2], col0, ks * 16, bar + 8 * B_W0);
        else if (rs_idx(ks, SSV) < VST) tma2d(sb + (rs_idx(ks, SSV) < VA ? STG_K + 27 * 2048 : STG_V2 - VA * 2048) + rs_idx(ks, SSV) * 2048, &M.w16[2], col0, ks * 16, bar + 8 * B_W0);
        else tma2d_prefetch(&M.w16[2], col0, ks * 16);
      }
      int c0, c1;
      wo_coord(2 * w12, t3, head, c0, c1);
      tma2d_prefetch(&M.wo32, c0, c1);
      tma2d_prefetch(&M.wo32, c0, c1 + 32);
    }
  }
  static_assert(40 - SSV - VST <= 10, "staging");
  if (lane0 < 2 && wg < 2) {
    const int u = 4 * (wg ? (lane0 ? 6 + t3 : 9) : (lane0 ? 3 + t3 : t3)) + warp;
    const int li = (u >= nA) + (u >= 2 * nA) + (u >= 3 * nA);
    sts32(sb + OFF_TAB + (wg * 4 + warp) * 8 + lane0 * 4,
          rb0 + ((u - li * nA) << 24) + OFF_TILE + LAND(li + (u >= 36 ? t3 : 0)) + (rank / 3) * 256 + 8 * (B_RS + li));
  }
  __syncthreads();
  GTS(25);

  auto issue_tok = [&](int sc, int fb, int rel = -1, uint32_t ph = 0) {
    if (sync_b) wait_cnt(&g_xready[sc][0], 32);
    if (rel >= 0) mbar_waitu(bar + 8 * rel, ph);
    bulk_g2s_mc_e(sb + OFF_TILE + ig * TILE_GRP + TILE_SBO, &g_xn[0][0] + uni(sc * (32 * DM)) + ig * 5120, 10240, bar + 8 * (fb + ig), mcmask);
  };
#define POLL(d, q) _Pragma("unroll") for (int k = 0; k < NCL; k++) \
      asm volatile("ld.relaxed.gpu.global.v2.b32 {%0,%1}, [%2];" : "=r"(d[k].x), "=r"(d[k].y) : "l"(q + k * 2560) : "memory")
#define L3(L, a, b, c) lop3<L>(a, b, c)
#define TAGS(L, d) L3(L, L3(L, L3(L, d[0].x, d[0].y, d[1].x), L3(L, d[1].y, d[2].x, d[2].y), L3(L, d[3].x, d[3].y, d[4].x)), L3(L, d[4].y, d[5].x, d[5].y), L3(L, d[6].x, d[6].y, d[6].y))
    auto deliver = [&](uint2* pa, const uint32_t* gq, int u, int c, int dc, int ds, int step, bool first, int lane) {
      const uint32_t off = uni(OFF_TILE + ((u * 205) >> 11) * (TILE_GRP - TILE_SBO) + u * 256 + dc * LAND_F), boff = uni(OFF_BAR + 8 * (B_F1 + ((u * 205) >> 11)));
      const uint32_t* mi = &g_part[4][0][0][0] + uni((c * NCL + cl) * 2560 + u * 64);
      mbar_waitu(bar + 8 * B_LANDFREE, step & 1);
      int n = 0;
      while (true) {
        const bool ok = __all_sync(~0u, ((step & 2 ? ~TAGS(0xFE, pa) : TAGS(0x80, pa)) & 1) != 0);
        if (ok) break;
        if (++n > SPIN_LIMIT) FAIL();
        POLL(pa, gq);
      }
      if (warp == 0 && first) { TS(19); TSV(10, n); }
      const uint32_t w0 = hadd2bf(hadd2bf(hadd2bf(pa[0].x, pa[1].x), hadd2bf(pa[2].x, pa[3].x)), hadd2bf(hadd2bf(pa[4].x, pa[5].x), pa[6].x));
      const uint32_t w1 = hadd2bf(hadd2bf(hadd2bf(pa[0].y, pa[1].y), hadd2bf(pa[2].y, pa[3].y)), hadd2bf(hadd2bf(pa[4].y, pa[5].y), pa[6].y));
      if (u < ds) {
        const uint32_t da = SMEM0 + off + lane * 8, db = SMEM0 + boff;
#pragma unroll
        for (int d = 0; d < 12; d++) st_async_v2((d << 24) + da, w0, w1, (d << 24) + db);
#pragma unroll
        for (int d = 12; d < 15; d++) st_async_v2_if(nA == 15, (d << 24) + da, w0, w1, (d << 24) + db);
      } else {
        *reinterpret_cast<uint2*>(const_cast<uint32_t*>(gq) + ((4 - 2 * (step & 1)) * NCL + cl) * 2560) = make_uint2(w0, w1);
        asm volatile("fence.proxy.async.global;" ::: "memory");
        __syncwarp();
        bulk_g2s_mc_e(sb + off, mi, 256, sb + boff, mcmask);
      }
    };
#define REL(b, g) mbar_arrive_remote_if(lane == 0, rb0 + ((nA - 4 + (g)) << 24) + OFF_BAR + 8 * (b))

  if (wg < 2) {
    asm volatile("setmaxnreg.inc.sync.aligned.u32 160;");
    LANE_INIT();
    uint32_t W[4 * (40 - SSQ)];
    mbar_waitw(bar + 8 * B_W0, 0);
    GTS(26);
    load_w<40 - SSQ>(W, sb + (wg ? STG_K : STG_Q), warp, lane);
    fence_async();
    bar_sync(1, 384);
    cluster_sync_all();
#define DESC(k) const Desc D = make_desc(M.d, min(wg, 2) * SSQ, fresh<k>(step))
    GTS(27);
#pragma unroll 1
    for (int step = -1; step < NSTEP; step++) {
      const uint32_t par = step & 1;
      asm volatile("" : "+r"(lane));
      const bool dual = is_dual(step), has_next = step + 1 < NSTEP;
#define QK_SA (sb + OFF_QK + wg * 15360 + (2 * warp + ((lane >> 3) & 1)) * 128 + (lane & 7) * 16)
#define QK_F (wg ? -5120 : 5120)
#define QK_S12 ((wg ? (lane >> 4) : 1 + 2 * (lane >> 4)) * 1024)
#define QK_S34 ((wg ? 2 + (lane >> 4) : 2 - 2 * (lane >> 4)) * 1024)
      if (step >= 0) {
        if (dual) {
          DESC(0);
          float acc[24];
          mbar_waitu(bar + 8 * (B_F1 + 0), par);
          if (wg + warp == 0) { TS(0); TSN(1); }
          CFENCE(); wg_fence(); proj<48, SSQ, 0, 0, 10>(acc, W, D); wg_commit();
          mbar_waitu(bar + 8 * (B_F1 + 1), par);
          CFENCE(); wg_fence(); proj<48, SSQ, 0, 10, 20>(acc, W, D); wg_commit();
          mbar_waitu(bar + 8 * (B_F1 + 2), par);
          CFENCE(); wg_fence(); proj<48, SSQ, 0, 20, 30>(acc, W, D); wg_commit();
          mbar_waitu2(bar + 8 * (B_F1 + 3), bar + 8 * B_PLFREE, par);
          if (wg + warp == 0) TS(2);
          CFENCE(); wg_fence(); proj<48, SSQ, 0, 30, 40>(acc, W, D); wg_commit();
          bar_arrive(N_VGO, 384);
          const uint32_t sa = QK_SA, s0 = sa + 4096 + (lane >> 4) * QK_F, s1 = sa + QK_F + QK_S12, s2 = sa + QK_F + QK_S34;
          wg_wait<0>();
          if (wg + warp == 0) TS(3);
          stsm4t(s0, pack2(acc[0], acc[1]), pack2(acc[2], acc[3]), pack2(acc[20], acc[21]), pack2(acc[22], acc[23]));
          stsm4t(s1, pack2(acc[4], acc[5]), pack2(acc[6], acc[7]), pack2(acc[8], acc[9]), pack2(acc[10], acc[11]));
          stsm4t(s2, pack2(acc[12], acc[13]), pack2(acc[14], acc[15]), pack2(acc[16], acc[17]), pack2(acc[18], acc[19]));
        } else {
          DESC(1);
          float acc[4];
          mbar_waitu(bar + 8 * (B_F1 + 0), par);
          if (wg + warp == 0) { TS(0); TSN(1); }
          CFENCE(); wg_fence(); proj<8, SSQ, 0, 0, 10>(acc, W, D); wg_commit();
          mbar_waitu(bar + 8 * (B_F1 + 1), par);
          CFENCE(); wg_fence(); proj<8, SSQ, 0, 10, 20>(acc, W, D); wg_commit();
          mbar_waitu(bar + 8 * (B_F1 + 2), par);
          CFENCE(); wg_fence(); proj<8, SSQ, 0, 20, 30>(acc, W, D); wg_commit();
          mbar_waitu2(bar + 8 * (B_F1 + 3), bar + 8 * B_PLFREE, par);
          if (wg + warp == 0) TS(2);
          CFENCE(); wg_fence(); proj<8, SSQ, 0, 30, 40>(acc, W, D); wg_commit();
          bar_arrive(N_VGO, 384);
          const uint32_t s0 = QK_SA + 4096;
          wg_wait<0>();
          if (wg + warp == 0) TS(3);
          stsm2t(s0, pack2(acc[0], acc[1]), pack2(acc[2], acc[3]));
        }
        fence_async();
        bar_sync(N_QK, 256);
        if (wg == 0 || dual) {
          float s[20];
          DESC(2);
          const Dsc ab = D.k1 + wg * 192, bb = D.k1 + (1 - wg) * 320;
          wg_fence();
          MM<40>::ss<dlo(OFF_QK, 128), dlo(OFF_QK + 10240, 128), 0, 0>(s, ab, bb);
          MM<40>::ss<dlo(OFF_QK + 256, 128), dlo(OFF_QK + 10240 + 256, 128), 1, 0>(s, ab, bb);
          MM<40>::ss<dlo(OFF_QK + 512, 128), dlo(OFF_QK + 10240 + 512, 128), 1, 0>(s, ab, bb);
          MM<40>::ss<dlo(OFF_QK + 768, 128), dlo(OFF_QK + 10240 + 768, 128), 1, 0>(s, ab, bb);
          wg_commit();
          bar_arrive(N_SISS, 384);
          const int rw = (warp - wg) & 3;
          const uint32_t bo = OFF_BAR + 8 * (B_SB + 3 * wg + rw), lo = OFF_PL + wg * PL_SZ + rw * 1792;
          const uint32_t km = wg ? 640 : 512;
          uint32_t l16 = lo + lane * 16, l4 = lo + lane * 4;
          mbar_expect_if(lane == 0 && rw < 3, sb + bo, rw < 2 ? 1792 : 1280);
          asm volatile("" : "+r"(l16), "+r"(l4));
          if (rw == 2) {
            wg_wait<0>();
            if (wg == 0) TSD(4, __float_as_uint(s[0]));
            {
              const uint32_t w0 = pack2(s[0], s[1]), w1 = pack2(s[4], s[5]), w2 = pack2(s[8], s[9]), w3 = pack2(s[12], s[13]), w4 = pack2(s[16], s[17]);
              st_async_v4(nxt + 896 + l16, w0, w1, w2, w3, nxt + bo);
              st_async_v4(prv + l16, w0, w1, w2, w3, prv + bo);
              st_async_b32(nxt + 896 + 768 + l4, w4, nxt + bo);
              st_async_b32(prv + 768 + l4, w4, prv + bo);
            }
            bar_arrive(N_SDONE, 256);
            mbar_waitu(sb + bo, (step - wg * LAG) & 1);
            if (wg == 0) TS(5);
            float x[10];
            {
              const uint4 a = lds128(sb + l16), b = lds128(sb + 896 + l16);
              const uint32_t c = lds32(sb + 768 + l4), d = lds32(sb + 896 + 768 + l4);
              const uint32_t e0 = hadd2bf(a.x, b.x), e1 = hadd2bf(a.y, b.y), e2 = hadd2bf(a.z, b.z), e3 = hadd2bf(a.w, b.w), e4 = hadd2bf(c, d);
              x[0] = s[0] + bf_lo(e0); x[1] = s[1] + bf_hi(e0); x[2] = s[4] + bf_lo(e1); x[3] = s[5] + bf_hi(e1); x[4] = s[8] + bf_lo(e2);
              x[5] = s[9] + bf_hi(e2); x[6] = s[12] + bf_lo(e3); x[7] = s[13] + bf_hi(e3); x[8] = s[16] + bf_lo(e4); x[9] = s[17] + bf_hi(e4);
            }
            float m0 = fmaxf(fmaxf(fmaxf(x[0], x[1]), fmaxf(x[2], x[3])), fmaxf(fmaxf(x[4], x[5]), fmaxf(fmaxf(x[6], x[7]), fmaxf(x[8], x[9]))));
            m0 = fmaxf(m0, __shfl_xor_sync(~0u, m0, 1));
            sts32(sb + l4 + 1152 - km, 0u);
            m0 = fmaxf(m0, __shfl_xor_sync(~0u, m0, 2));
            m0 *= -SL2;
#pragma unroll
            for (int j = 0; j < 5; j++) {
              x[2 * j] = ex2(fmaf(x[2 * j], SL2, m0)); x[2 * j + 1] = ex2(fmaf(x[2 * j + 1], SL2, m0));
              sts32(sb + l4 + (j < 4 ? j * 128 : km), pack2(x[2 * j], x[2 * j + 1]));
            }
            float l = ((x[0] + x[1]) + (x[2] + x[3])) + ((x[4] + x[5]) + ((x[6] + x[7]) + (x[8] + x[9])));
            l += __shfl_xor_sync(~0u, l, 1);
            fence_async();
            sts32(sb + OFF_INV + wg * 64 + (lane >> 1) * 4, __float_as_uint(l));
            bar_arrive(N_PM, dual ? 224 : 192);
            if (wg == 0) TS(6);
          } else if (rw < 2) {
            const bool w1 = rw == 1;
            const uint32_t l8 = lo + 512 + lane * 8;
            uint32_t tw[7];
            wg_wait<0>();
            bar_arrive(N_SDONE, 256);
            tw[0] = pack2(s[0], s[1]); tw[1] = pack2(s[4], s[5]); tw[2] = pack2(s[8], s[9]); tw[3] = pack2(s[16], s[17]);
            tw[4] = w1 ? pack2(s[6], s[7]) : pack2(s[12], s[13]); tw[5] = pack2(s[2], s[3]); tw[6] = pack2(s[18], s[19]);
            { const uint32_t t0 = clock32(); while (clock32() - t0 < TOK_DELAY) {} }
            st_async_v4(nxt + 896 + l16, tw[0], tw[1], tw[2], tw[3], nxt + bo);
            st_async_v4(prv + l16, tw[0], tw[1], tw[2], tw[3], prv + bo);
            st_async_v2(nxt + 896 + l8, tw[5], tw[6], nxt + bo);
            st_async_v2(prv + l8, tw[5], tw[6], prv + bo);
            st_async_b32(nxt + 896 + 768 + l4, tw[4], nxt + bo);
            st_async_b32(prv + 768 + l4, tw[4], prv + bo);
            mbar_waitu(sb + bo, (step - wg * LAG) & 1);
            const uint4 a = lds128(sb + l16), b = lds128(sb + 896 + l16);
            const uint2 e = lds64(sb + l8), f = lds64(sb + 896 + l8);
            const uint32_t c = lds32(sb + 768 + l4), d = lds32(sb + 896 + 768 + l4);
            sts128(sb + l16, hadd2bf(hadd2bf(a.x, b.x), tw[0]), hadd2bf(hadd2bf(a.y, b.y), tw[1]), hadd2bf(hadd2bf(a.z, b.z), tw[2]), hadd2bf(hadd2bf(a.w, b.w), tw[3]));
            sts64(sb + l8, hadd2bf(hadd2bf(e.x, f.x), tw[5]), hadd2bf(hadd2bf(e.y, f.y), tw[6]));
            sts32(sb + 768 + l4, hadd2bf(hadd2bf(c, d), tw[4]));
            bar_arrive(N_PX, dual ? 256 : 192);
            if (wg + warp == 0) TS(9);
          } else {
            wg_wait<0>();
            if (wg == 0) {
              mbar_expect_if(lane < 3 && has_next, bar + 8 * (lane == 2 ? B_OPEER : B_WOF + lane), lane == 2 ? (dual ? 4096 : 2048) : lane ? 8192 : 20480);
              auto fetch = [&](int i, int n, uint32_t dst, int mb) {
                int c0, c1; wo_coord(i, t3, head, c0, c1);
                tma2d_e(dst, &M.wo32, c0, c1, bar + 8 * mb); if (n == 2) tma2d_e(dst + 4096, &M.wo32, c0, c1 + 32, bar + 8 * mb);
              };
              bar_sync(N_G3, 160);
              if (has_next) {
                fetch(0, 2, sb + OFF_WT, B_WTF);
                mbar_arrive_remote_if(lane < 2, (lane ? nxt : prv) + OFF_BAR + 8 * B_XFREE);
              }
              bar_sync(N_SDONE, 256);
              if (has_next) {
                fetch(15, 1, sb + OFF_QK, B_WOF); fetch(16, 2, sb + OFF_QK + 4096, B_WOF); fetch(18, 2, sb + OFF_QK + 12288, B_WOF);
                mbar_waitu(bar + 8 * B_XFREE, par);
              }
              bar_arrive(N_PM, dual ? 224 : 192);
              bar_sync(N_VDONE, 160);
              mbar_arrive_remote_if(lane < nA && has_next, rb0 + (lane << 24) + OFF_BAR + 8 * B_MEMFREE);
              if (has_next) mbar_waitu(bar + 8 * B_WTF, par);
            } else {
              bar_arrive(N_SDONE, 256);
              if ((unsigned)ig < 3) issue_tok(sched_l(step + 1), B_F2, B_R1, (step - LAG) & 1);
            }
          }
        } else {
          bar_arrive(N_SISS, 384);
          bar_arrive(N_SDONE, 256);
        }
        if (has_next) {
          if (step == 0) mbar_waitw(bar + 8 * B_W0, 1);
          const uint32_t r1 = rb0 + ((nA - 1) << 24) + OFF_BAR + 8 * B_R1;
          if (dual) { DESC(3); wo_phase<16>(sb, wg, warp, lane, par, r1, D); } else { DESC(4); wo_phase<8>(sb, wg, warp, lane, par, r1, D); }
          bar_arrive(N_C, 288);
          if (warp == 0) TS(7 + wg);
        }
      }
      if (has_next) {
        DESC(5);
        float acc[16];
        mbar_waitu(bar + 8 * B_F2, par ^ 1);
        wg_fence(); proj<32, SSQ, 1, 0, 10>(acc, W, D); wg_commit();
        mbar_waitu(bar + 8 * (B_F2 + 1), par ^ 1);
        wg_fence(); proj<32, SSQ, 1, 10, 14>(acc, W, D); wg_commit();
        wg_wait<1>(); REL(B_R2, 0);
        wg_fence(); proj<32, SSQ, 1, 14, 20>(acc, W, D); wg_commit();
        mbar_waitu(bar + 8 * (B_F2 + 2), par ^ 1);
        wg_fence(); proj<32, SSQ, 1, 20, 24>(acc, W, D); wg_commit();
        wg_wait<1>(); REL(B_R2, 1);
        wg_fence(); proj<32, SSQ, 1, 24, 30>(acc, W, D); wg_commit();
        mbar_waitu(bar + 8 * (B_F2 + 3), par ^ 1);
        wg_fence(); proj<32, SSQ, 1, 30, 34>(acc, W, D); wg_commit();
        wg_wait<1>(); REL(B_R2, 2);
        wg_fence(); proj<32, SSQ, 1, 34, 40>(acc, W, D); wg_commit();
        const uint32_t sa = QK_SA, s1 = sa + QK_S12, s2 = sa + QK_S34;
        wg_wait<0>(); REL(B_R2, 3);
        if (warp == 0) TS(11 + wg);
        stsm4t(s1, pack2(acc[0], acc[1]), pack2(acc[2], acc[3]), pack2(acc[4], acc[5]), pack2(acc[6], acc[7]));
        stsm4t(s2, pack2(acc[8], acc[9]), pack2(acc[10], acc[11]), pack2(acc[12], acc[13]), pack2(acc[14], acc[15]));
      }
    }
    GTS(28);
    cluster_sync_all();
  } else if (wg == 2) {
    asm volatile("setmaxnreg.inc.sync.aligned.u32 160;");
    LANE_INIT();
    uint32_t W[4 * (40 - SSV)];
    mbar_waitw(bar + 8 * B_W0, 0);
    load_w<VA>(W, sb + STG_K + 27 * 2048, warp, lane);
    load_w<VST - VA>(W + 4 * VA, sb + STG_V2, warp, lane);
    fence_async();
    bar_sync(1, 384);
    if (lane == 0) {
      if (warp == 0) {
        mbar_expect(bar + 8 * B_W1, (40 - SSV - VST) * 2048);
#pragma unroll 1
        for (int ks = 0; ks < 40; ks++)
          if (!is_ss(ks, SSV) && rs_idx(ks, SSV) >= VST) tma2d(sb + OFF_QK + (rs_idx(ks, SSV) - VST) * 2048, &M.w16[2], col0, ks * 16, bar + 8 * B_W1);
      } else {
        if (warp == 1) mbar_expect(bar + 8 * B_W0, 26 * 2048);
#pragma unroll 1
        for (int i = warp - 1; i < 13; i += 3) { int c0, c1; wo_coord(i + 2, t3, head, c0, c1); tma2d(sb + OFF_WO + i * 4096, &M.wo32, c0, c1, bar + 8 * B_W0); }
      }
    }
    __syncwarp();
#pragma unroll
    for (int i = 0; i < 5; i++) {
      const int t = i * 128 + warp * 32 + lane;
      const uint4 v = *reinterpret_cast<const uint4*>(mem0 + ((t >> 1) & 7) * DM + (t >> 4) * 16 + ((t ^ (t >> 3)) & 1) * 8);
      sts128(sb + OFF_TILE + (t / 160) * (TILE_GRP - TILE_SBO) + t * 16, v.x, v.y, v.z, v.w);
    }
    mbar_waitw(bar + 8 * B_W1, 0);
    load_w<40 - SSV - VST>(W + 4 * VST, sb + OFF_QK, warp, lane);
    fence_async();
    mbar_arrive_if(lane == 0, bar + 8 * (B_F1 + warp));
    mbar_expect_if(lane == 0, bar + 8 * (B_F2 + warp), 10240);
    mbar_arrive_if(warp == 3 && lane < 2, bar + 8 * B_PLFREE);
    cluster_sync_all();
    uint32_t vl[8];
    {
      const int step = warp;
      DESC(0);
      float v[16];
      mbar_waitw4(bar + 8 * B_F2, 0);
      wg_fence(); proj<32, SSV, 1, 0, 40>(v, W, D); wg_commit();
      wg_wait<0>();
      mbar_arrive_remote_if(lane < 4, rb0 + ((nA - 4 + lane) << 24) + OFF_BAR + 8 * B_R2);
#pragma unroll
      for (int j = 0; j < 8; j++) vl[j] = pack2v(v[2 * j], v[2 * j + 1]);
      if (warp == 0 && (unsigned)ig < 3) issue_tok(1, B_F2, B_R2, 0);
    }
#pragma unroll 1
    for (int step = 0; step < NSTEP; step++) {
      const uint32_t par = step & 1;
      asm volatile("" : "+r"(lane));
      const bool dual = is_dual(step), has_next = step + 1 < NSTEP;
      mbar_expect_if(lane == 0 && has_next, bar + 8 * (B_F2 + warp), 10240);
      if (warp == 0 && ig == 3 && has_next && sync_b) wait_cnt(&g_xready[sched_l(step + 1)][0], 32);
      bar_sync(N_VGO, 384);
      CFENCE();
#define F1_BYTES (is_dual(step + 1) ? 15360 : 2560)
#define ARM() do { \
        mbar_expect_if(lane == 0 && has_next, bar + 8 * (B_F1 + warp), F1_BYTES); \
        mbar_expect_if(lane == 0 && has_next && warp * nA + (int)rank < 40, bar + 8 * (B_RS + warp), (warp * nA + (int)rank >= 36 ? nA : nh) * (dual ? 512 : 256)); } while (0)
#define O_ADDR() uint32_t oa = sb + OFF_O + (lane >> 4) * PL_SZ + warp * 256 + (lane & 15) * 16, xo = (lane >> 4) * 1024 + warp * 256 + (lane & 15) * 16; \
        asm volatile("" : "+r"(oa), "+r"(xo))
#define O_READY(act) do { if (has_next) { const uint4 ov = lds128(oa); \
        if (act) { st_async_v4(nxt + OFF_XL + xo, ov.x, ov.y, ov.z, ov.w, nxt + OFF_BAR + 8 * B_OPEER); \
                   st_async_v4(prv + OFF_XF + xo, ov.x, ov.y, ov.z, ov.w, prv + OFF_BAR + 8 * B_OPEER); } \
        fence_async(); bar_arrive(N_O, 384); } \
        if (warp == 0) TS(15); } while (0)
#define TOK_L3() if (warp == 0 && ig == 3 && has_next) { mbar_waitu(bar + 8 * B_R1, par); \
        bulk_g2s_mc_e(sb + OFF_TILE + 3 * TILE_GRP + TILE_SBO, &g_xn[0][0] + uni(sched_l(step + 1) * (32 * DM)) + 3 * 5120, 10240, bar + 8 * (B_F2 + 3), mcmask); }
#define OX_SA (sb + OFF_PL + (lane & 7) * 128 + (((warp * 2 + ((lane >> 3) & 1)) ^ (lane & 7)) << 4))
      if (dual) {
        uint32_t vf[8], vm[4], vn[8];
        {
          DESC(0);
          float v[24];
          wg_fence(); proj<48, SSV, 0, 30, 30 + VD1, 30>(v, W, D); wg_commit();
          ARM();
          bar_sync(N_SISS, 384);
          wg_fence(); proj<48, SSV, 0, 30 + VD1, 40, 30>(v, W, D); wg_commit();
          proj<48, SSV, 0, 0, 3, 30>(v, W, D); wg_commit();
          wg_wait<1>(); bar_arrive(N_G3, 160);
          wg_fence(); proj<48, SSV, 0, 3, 10, 30>(v, W, D); wg_commit();
          proj<48, SSV, 0, 10, 13, 30>(v, W, D); wg_commit();
          wg_wait<1>(); REL(B_R1, 0);
          wg_fence(); proj<48, SSV, 0, 13, 20, 30>(v, W, D); wg_commit();
          proj<48, SSV, 0, 20, 23, 30>(v, W, D); wg_commit();
          wg_wait<1>(); REL(B_R1, 1);
          wg_fence(); proj<48, SSV, 0, 23, 30, 30>(v, W, D); wg_commit();
          wg_wait<0>(); REL(B_R1, 2);
          bar_arrive(N_VDONE, 160);
          if (warp == 0) TS(14);
#pragma unroll
          for (int j = 4; j < 8; j++) vf[j] = pack2v(v[4 + 2 * j], v[5 + 2 * j]);
          keep4(vf + 4, lane);
          vm[0] = pack2v(v[0], v[1]); vm[1] = pack2v(v[2], v[3]); vm[2] = pack2v(v[20], v[21]); vm[3] = pack2v(v[22], v[23]);
          keep4(vm, lane);
#pragma unroll
          for (int j = 0; j < 4; j++) vf[j] = pack2v(v[4 + 2 * j], v[5 + 2 * j]);
          keep4(vf, lane);
        }
        {
          DESC(1);
          float o[8];
          O_ADDR();
          bar_sync(N_PM, 224);
          wg_fence();
          MM<8>::rs<dlo(OFF_PL + 3584, 128), 0>(o, vl, D.p);
          MM<8>::rs<dlo(OFF_PL + PL_SZ + 3584, 128), 0>(o + 4, vf, D.p);
          MM<8>::rs<dlo(OFF_PL + 3584 + 256, 128), 1>(o, vl + 4, D.p);
          MM<8>::rs<dlo(OFF_PL + PL_SZ + 3584 + 256, 128), 1>(o + 4, vf + 4, D.p);
          MM<8>::rs<dlo(OFF_PL + 3584 + 512, 128), 1>(o, vm, D.p);
          MM<8>::rs<dlo(OFF_PL + PL_SZ + 3584 + 512, 128), 1>(o + 4, vm, D.p);
          wg_commit();
          const uint4 il = lds128(sb + OFF_INV + (lane & 3) * 16), jf = lds128(sb + OFF_INV + 64 + (lane & 3) * 16);
          const float i0 = rcpf(__uint_as_float(il.x) + __uint_as_float(il.y)), i1 = rcpf(__uint_as_float(il.z) + __uint_as_float(il.w));
          const float j0 = rcpf(__uint_as_float(jf.x) + __uint_as_float(jf.y)), j1 = rcpf(__uint_as_float(jf.z) + __uint_as_float(jf.w));
          wg_wait<0>();
          stsm4t(oa, pack2(o[0] * i0, o[1] * i1), pack2(o[2] * i0, o[3] * i1), pack2(o[4] * j0, o[5] * j1), pack2(o[6] * j0, o[7] * j1));
          O_READY(true);
          TOK_L3();
        }
        {
          DESC(2);
          float v[16];
          bar_sync(N_TURN, 256);
          mbar_waitu(bar + 8 * B_F2, par ^ 1);
          wg_fence(); proj<32, SSV, 1, 0, 10>(v, W, D); wg_commit();
          mbar_waitu(bar + 8 * (B_F2 + 1), par ^ 1);
          wg_fence(); proj<32, SSV, 1, 10, 14>(v, W, D); wg_commit();
          wg_wait<1>(); REL(B_R2, 0);
          wg_fence(); proj<32, SSV, 1, 14, 20>(v, W, D); wg_commit();
          mbar_waitu(bar + 8 * (B_F2 + 2), par ^ 1);
          wg_fence(); proj<32, SSV, 1, 20, 24>(v, W, D); wg_commit();
          wg_wait<1>(); REL(B_R2, 1);
          wg_fence(); proj<32, SSV, 1, 24, 30>(v, W, D); wg_commit();
          mbar_waitu(bar + 8 * (B_F2 + 3), par ^ 1);
          wg_fence(); proj<32, SSV, 1, 30, 34>(v, W, D); wg_commit();
          wg_wait<1>(); REL(B_R2, 2);
          wg_fence(); proj<32, SSV, 1, 34, 40>(v, W, D); wg_commit();
          wg_wait<0>(); REL(B_R2, 3);
#pragma unroll
          for (int j = 0; j < 8; j++) vn[j] = pack2v(v[2 * j], v[2 * j + 1]);
          keep4(vn, lane); keep4(vn + 4, lane);
          if (warp == 0) TS(18);
        }
        DESC(3);
        uint32_t ow[16];
        bar_sync(N_P, 256);
        fence_async();
#define PV16(i, off, va) { float o[8]; wg_fence(); \
          MM<16>::rs<dlo(OFF_PL + (off), 128), 0>(o, va, D.p); \
          MM<16>::rs<dlo(OFF_PL + (off) + 256, 128), 1>(o, va + 4, D.p); \
          MM<16>::rs<dlo(OFF_PL + (off) + 512, 128), 1>(o, vm, D.p); \
          wg_commit(); wg_wait<0>(); \
          _Pragma("unroll") for (int j = 0; j < 4; j++) ow[4 * (i) + j] = pack2v(o[2 * j], o[2 * j + 1]); \
          keep4(ow + 4 * (i), lane); }
        PV16(0, 0, vl) PV16(1, 1792, vl) PV16(2, PL_SZ, vf) PV16(3, PL_SZ + 1792, vf)
        const uint32_t s1 = OX_SA + (lane < 16 ? 3072 : 0), s2 = OX_SA + (lane < 16 ? 2048 : 1024);
        bar_sync(N_V, 128);
        stsm4t(s1, ow[0], ow[1], ow[2], ow[3]);
        stsm4t(s2, ow[4], ow[5], ow[6], ow[7]);
        stsm4t(s1 + PL_SZ, ow[8], ow[9], ow[10], ow[11]);
        stsm4t(s2 + PL_SZ, ow[12], ow[13], ow[14], ow[15]);
#pragma unroll
        for (int j = 0; j < 8; j++) vl[j] = vn[j];
      } else {
        uint32_t vm[4], vn[8];
        {
          DESC(4);
          float v[4];
          wg_fence(); proj<8, SSV, 0, 30, 40, 30>(v, W, D); wg_commit();
          proj<8, SSV, 0, 0, VS1, 30>(v, W, D); wg_commit();
          ARM();
          bar_sync(N_SISS, 384);
          wg_wait<1>(); bar_arrive(N_G3, 160);
          wg_fence(); proj<8, SSV, 0, VS1, 30, 30>(v, W, D); wg_commit();
          if (has_next) { mbar_waitu2(bar + 8 * B_F2, bar + 8 * (B_F2 + 1), par ^ 1); mbar_waitu(bar + 8 * (B_F2 + 2), par ^ 1); }
          wg_wait<0>();
          bar_arrive(N_VDONE, 160);
          vm[0] = pack2v(v[0], v[1]); vm[1] = pack2v(v[2], v[3]); vm[2] = pack2v(v[1], v[0]); vm[3] = pack2v(v[3], v[2]);
        }
        DESC(5);
        float v[16];
        {
          wg_fence(); proj<32, SSV, 1, 0, 30>(v, W, D); wg_commit();
          {
            float o[4];
            O_ADDR();
            bar_sync(N_PM, 192);
            if (warp == 0) TS(14);
            wg_fence();
            MM<8>::rs<dlo(OFF_PL + 3584, 128), 0>(o, vl, D.p);
            MM<8>::rs<dlo(OFF_PL + 3584 + 256, 128), 1>(o, vl + 4, D.p);
            MM<8>::rs<dlo(OFF_PL + 3584 + 512, 128), 1>(o, vm, D.p);
            wg_commit();
            const uint4 il = lds128(sb + OFF_INV + (lane & 3) * 16);
            const float i0 = rcpf(__uint_as_float(il.x) + __uint_as_float(il.y)), i1 = rcpf(__uint_as_float(il.z) + __uint_as_float(il.w));
            wg_wait<0>();
            stsm2t(oa, pack2(o[0] * i0, o[1] * i1), pack2(o[2] * i0, o[3] * i1));
            O_READY(lane < 16);
            TOK_L3();
          }
          if (has_next) {
            mbar_arrive_remote_if(lane < 3, rb0 + ((nA - 4 + lane) << 24) + OFF_BAR + 8 * B_R2);
            bar_sync(N_TURN, 256);
            mbar_waitu(bar + 8 * (B_F2 + 3), par ^ 1);
          }
          wg_fence(); proj<32, SSV, 1, 30, 40>(v, W, D); wg_commit();
          wg_wait<0>();
          if (has_next) REL(B_R2, 3);
#pragma unroll
          for (int j = 0; j < 8; j++) vn[j] = pack2v(v[2 * j], v[2 * j + 1]);
          keep4(vn, lane); keep4(vn + 4, lane);
          if (warp == 0) TS(18);
        }
        float o[16];
        bar_sync(N_P, 256);
        fence_async();
        wg_fence();
        MM<32>::rs<dlo(OFF_PL, 128), 0>(o, vl, D.p);
        MM<32>::rs<dlo(OFF_PL + 256, 128), 1>(o, vl + 4, D.p);
        MM<32>::rs<dlo(OFF_PL + 512, 128), 1>(o, vm, D.p);
        wg_commit();
        const uint32_t s1 = OX_SA + (lane < 16 ? 3072 : 0), s2 = OX_SA + (lane < 16 ? 2048 : 1024);
        wg_wait<0>();
        bar_sync(N_V, 128);
        stsm4t(s1, pack2(o[0], o[1]), pack2(o[2], o[3]), pack2(o[4], o[5]), pack2(o[6], o[7]));
        stsm4t(s2, pack2(o[8], o[9]), pack2(o[10], o[11]), pack2(o[12], o[13]), pack2(o[14], o[15]));
#pragma unroll
        for (int j = 0; j < 8; j++) vl[j] = vn[j];
      }
      bar_arrive(N_OX, 160);
      if (warp == 0) TS(16);
    }
    cluster_sync_all();
  } else {
    asm volatile("setmaxnreg.dec.sync.aligned.u32 32;");
    if (wg > 3) return;
    LANE_INIT();
    struct RsJob { uint32_t* gp; uint32_t la, mb; int n; };
    auto rs_prep = [&](int step, int s, int c) {
      RsJob j;
      const int u = s * nA + rank;
      j.gp = &g_part[0][0][0][0] + (uint32_t)((((step & 1) * 2 + c) * NCL + cl) * 2560 + u * 64 + (lane >> 2) * 8 + (lane & 3));
      j.la = sb + OFF_TILE + c * LAND_F + LAND(s) + lane * 8;
      j.mb = bar + 8 * (B_RS + s);
      j.n = u >= 40 ? 0 : u >= 36 ? 3 : 1;
      asm volatile("" : "+l"(j.gp), "+r"(j.la));
      return j;
    };
    auto rs_sum = [&](RsJob j, int step) {
      if (j.n) {
        auto five = [&](uint32_t la) {
          uint2 p[5];
#pragma unroll
          for (int i = 0; i < 4; i++) p[i] = lds64(la + i * 256);
          asm volatile("{\n.reg .pred q;\nsetp.eq.s32 q, %3, 5;\nmov.u32 %0, 0;\nmov.u32 %1, 0;\n@q ld.shared.v2.b32 {%0,%1}, [%2];\n}"
                       : "=r"(p[4].x), "=r"(p[4].y) : "r"(la + 1024), "r"(nh) : "memory");
          return make_uint2(hadd2bf(hadd2bf(p[0].x, p[1].x), hadd2bf(hadd2bf(p[2].x, p[3].x), p[4].x)),
                            hadd2bf(hadd2bf(p[0].y, p[1].y), hadd2bf(hadd2bf(p[2].y, p[3].y), p[4].y)));
        };
        const uint32_t tag = ((step >> 1) & 1) ^ 1;
        mbar_waitw(j.mb, step & 1);
        uint2 t = five(j.la);
        if (j.n > 1) {
          const uint2 a = five(j.la + (nh == 5 ? 1280 : TILE_GRP - 1280)), b = five(j.la + TILE_GRP);
          t.x = hadd2bf(t.x, hadd2bf(a.x, b.x)); t.y = hadd2bf(t.y, hadd2bf(a.y, b.y));
        }
        const uint32_t t0 = (movm(t.x) & ~1u) | tag, t1 = (movm(t.y) & ~1u) | tag;
        asm volatile("st.relaxed.gpu.global.b32 [%0], %1;" :: "l"(j.gp), "r"(lane & 16 ? t1 : t0) : "memory");
        asm volatile("st.relaxed.gpu.global.b32 [%0], %1;" :: "l"(j.gp + 4), "r"(lane & 16 ? t0 : t1) : "memory");
      }
    };
    if (warp * nA + (int)rank < 40) {
#pragma unroll
      for (int e = LAG; e < LAG + 2; e++)
        if ((e >> 1) & 1) *reinterpret_cast<uint2*>(&g_part[(e & 1) * 2 + 1][cl][warp * nA + rank][lane * 2]) = make_uint2(1u, 1u);
      __threadfence();
    }
    cluster_sync_all();
    if (warp == 2 && ig >= 0) issue_tok(0, B_F2);
#pragma unroll 1
    for (int step = 0; step < NSTEP; step++) {
      const uint32_t par = step & 1;
      asm volatile("" : "+r"(lane));
      const bool dual = is_dual(step), has_next = step + 1 < NSTEP;
      {
        bar_sync(N_PX, dual ? 256 : 192);
        if (dual || warp >= 2) tok_softmax(sb, dual ? warp : warp - 2, lane);
        bar_arrive(N_P, 256);
        asm volatile("" : "+r"(lane));
        if (has_next) {
          if (step + 2 == LAG && lane < 20) asm volatile("prefetch.global.L2 [%0];" :: "l"(mem0 + (warp * 20 + lane) * 64));
          const int nw = ig >= 0 ? 3 : 4, j0 = warp < nw ? warp : 8;
          const int sh = dual ? 1 : 0;
          rs_sum(rs_prep(step, j0 >> sh, j0 & sh), step);
          if (warp == 0) TS(17);
          if (dual) rs_sum(rs_prep(step, (j0 + nw) >> 1, (j0 + nw) & 1), step);
          if (warp == 0) { bar_sync(N_C, 288); }
          mbar_arrive_remote_if(lane < nA, rb0 + (lane << 24) + OFF_BAR + 8 * B_LANDFREE);
          const uint32_t gap = dual ? POLL_GAPD : POLL_GAP;
          if (gap) { const uint32_t t0 = clock32(); while (clock32() - t0 < gap) {} }
#pragma unroll 1
          for (int j = j0; j < (dual ? 8 : 4); j += nw) {
            const int u = (j >> sh) * nA + rank, c = j & sh;
            if (u < UMAX && (c || step + 1 != NSEG)) {
              const uint32_t* gq = &g_part[0][0][0][0] + (uint32_t)((par * 2 + c) * NCL * 2560 + u * 64 + lane * 2);
              uint2 pa[NCL];
              POLL(pa, gq);
              deliver(pa, gq, u, c, step + 1 < NSEG ? c : 0, dual ? DS_DUAL : DS_SINGLE, step, j == 0, lane);
            }
            if (warp == 0 && j == 0) TS(13);
          }
          if (warp >= nw && (is_dual(step + 1) || (ig < 3 && step + 2 < NSTEP))) {
            issue_tok(is_dual(step + 1) ? sched_f(step + 1) : sched_l(step + 2), is_dual(step + 1) ? B_F1 : B_F2, B_R2, par ^ 1);
          }
          if (step + 1 == LAG && UMAX) {
            uint4 v[5];
#pragma unroll
            for (int i = 0; i < 5; i++) { const int t = warp * 160 + i * 32 + lane; v[i] = *reinterpret_cast<const uint4*>(mem0 + ((t >> 1) & 7) * DM + (t >> 4) * 16 + ((t ^ (t >> 3)) & 1) * 8); }
            mbar_waitu(bar + 8 * B_LANDFREE, par);
#pragma unroll
            for (int i = 0; i < 5; i++)
              st_async_v4(sb + OFF_TILE + LAND_F + warp * TILE_GRP + (i * 32 + lane) * 16, v[i].x, v[i].y, v[i].z, v[i].w, bar + 8 * (B_F1 + warp));
          }
        }
      }
      if (warp == 3) {
        unsigned char* o0 = g_o + uni(step % RO * (96 * 8192) + (head * 3 + t3) * (dual ? 8192 : 4096));
        bar_sync(N_OX, 160);
        fence_async();
        bulk_s2g_es(o0, sb + OFF_PL, 4096);
        if (dual) bulk_s2g_es(o0 + 4096, sb + OFF_PL + PL_SZ, 4096);
        asm volatile("cp.async.bulk.commit_group;" ::: "memory");
        asm volatile("cp.async.bulk.wait_group.read 0;" ::: "memory");
        __syncwarp();
        mbar_arrive_remote_if(lane < 2, (lane ? nxt : prv) + OFF_BAR + 8 * B_PLFREE);
        asm volatile("cp.async.bulk.wait_group 0;" ::: "memory");
        asm volatile("fence.proxy.async.global;" ::: "memory");
        __syncwarp();
        if (lane == 0) red_release(&g_f[F_O + (head * 3 + t3) / 5][step], 1u);
        __syncwarp();
      }
    }
    cluster_sync_all();
  }
}

__device__ __forceinline__ float gelu2(float x) {
  const float u = x * fmaf(x * x, 0.7978845608028654f * 0.044715f, 0.7978845608028654f);
  float t; asm("tanh.approx.f32 %0, %1;" : "=f"(t) : "f"(u));
  return fmaf(x, t, x); }

struct BParams {
  CUtensorMap wmap[5];
  CUtensorMap wo16;
  const __nv_bfloat16* x;
  __nv_bfloat16* out;
  uint64_t desc;
};
#define BO_O 0
#define BO_RES (6 * 8192)
#define OP_RES 63488
#define BO_STG (BO_RES + 2 * OP_RES)
#define BO_RING_OP (BO_STG + 16384)
#define OP_SLOT 12288
#define NS_OP 3
#define BO_H 81920
#define BO_W1 (BO_H + 16384)
#define BO_RING_MLP (BO_W1 + 81920)
#define BO_BAR 229376
#define BO_BOX (BO_BAR + 248)
#define BO_CARRY (BO_BAR + 512)
#define BO_STAT (BO_CARRY + 2048)
#define B_SMEM (BO_STAT + 256)
static_assert(B_SMEM <= 232448 && BO_RING_OP + NS_OP * OP_SLOT == BO_BAR && BO_RING_MLP + 3 * 16384 == BO_BAR && 2 * 83968 <= BO_RING_MLP, "smem");
enum { BB_W = 0, BB_FULL = 2, BB_TMP = BB_FULL + 3, BB_OFULL = BB_FULL + 5, BB_SFREE = BB_OFULL,
       BB_STAT = BB_SFREE + 6, BB_ZFREE, BB_DONE = BB_ZFREE + 3,
       BB_EMPTY, BB_START = BB_EMPTY, BB_USED = BB_EMPTY + 2, BB_NUM = BB_USED + 3 };
enum { NB_PP = 1, NB_H = 3, NB_END = 4, NB_END2 = 5, NB_STAGED = 6, NB_FREE = 8, NB_EARLY = 10, NB_LAST = 11 };

#define DESC_LO(off) (((SMEM0 + (off)) >> 4) | (1u << 16))

__device__ __forceinline__ uint32_t ld_relaxed(const uint32_t* p) { uint32_t v; asm volatile("ld.relaxed.gpu.global.b32 %0, [%1];" : "=r"(v) : "l"(p) : "memory"); return v; }
__device__ __forceinline__ int fmask(int r) { return (r < NSEG) | ((r >= LAG && r < NSTEP) << 1); }
__device__ __forceinline__ int bmask(int r) { return (r <= NSEG) | ((r >= LAG) << 1); }
__device__ __forceinline__ uint32_t rtarget(int mask) { return mask == 3 ? 64 : 32; }
__device__ __forceinline__ void warp_signal(uint32_t* p, int lane) {
  __syncwarp();
  asm volatile("{\n.reg .pred q;\nsetp.eq.u32 q, %1, 0;\n@q red.release.gpu.global.add.u32 [%0], 1;\n}" :: "l"(p), "r"(lane) : "memory");
}
__device__ __forceinline__ uint32_t pack2h(float lo, float hi) { uint32_t r; asm("cvt.rn.f16x2.f32 %0, %1, %2;" : "=r"(r) : "f"(hi), "f"(lo)); return r; }
template <bool H> __device__ __forceinline__ uint32_t pk(float lo, float hi) { return H ? pack2h(lo, hi) : pack2(lo, hi); }
template <int N, bool H> __device__ __forceinline__ void stage_out(const float* d, uint32_t dst, int warp, int lane) {
  const uint32_t sa = dst + ((lane >> 4) * 8 + (lane & 7)) * 128 + (((2 * warp + ((lane >> 3) & 1)) ^ (lane & 7)) << 4);
#pragma unroll
  for (int m = 0; m < N / 16; m++)
    stsm4t(sa + m * 2048, pk<H>(d[8 * m], d[8 * m + 1]), pk<H>(d[8 * m + 2], d[8 * m + 3]), pk<H>(d[8 * m + 4], d[8 * m + 5]), pk<H>(d[8 * m + 6], d[8 * m + 7]));
}
template <int N> __device__ __forceinline__ void acc_live(float* d) {
#pragma unroll
  for (int i = 0; i < N / 2; i++) asm volatile("" : "+f"(d[i]) :: "memory");
}
struct Ring {
  uint32_t sl, ph;
  template <int NS> __device__ __forceinline__ void step() { if (++sl == NS) { sl = 0; ph ^= 1; } }
};

#define LOCKSTEP 0
#define KOFF(x) (DESC_LO(BO_O) + ((x) >> 2) * (N * 8) + ((x) & 3) * 2)
template <int N, int P>
__device__ __forceinline__ void op_pass(const uint32_t* W, uint32_t bar, Dsc alo, Dsc blo, Dsc xlo, bool x2, Ring& rg, int wg, int warp, int lane, int r) {
  float acc[N / 2];
  blo.e = xlo.e = fresh<P + N / 64 * 5>(r);
  const Dsc tlo = blo + uni(rg.sl) * (OP_SLOT / 16);
  if (P == 0) mbar_waitu(bar + 8 * BB_OFULL, r & 1);
  CTS(5 * P);
  if (!LOCKSTEP || P > 1 || P == wg) bar_sync(NB_PP + wg, 256);
  wg_fence();
#define OP_R(x) MM<N>::template rs<KOFF(4 * (x >> 1) + (x & 1)), (x != 0)>(acc, W + 32 * P + 4 * x, blo);
#define OP_S(x) MM<N>::template ss<DESC_LO(BO_RES) + (6 * P + x) * 128, KOFF(4 * (x >> 1) + 2 + (x & 1)), 1>(acc, alo, blo);
#define OP_T(x) MM<N>::template ss<DESC_LO(BO_RING_OP) + x * 128, KOFF(14 + x), 1>(acc, tlo, blo);
  OP_R(0) OP_S(0) OP_R(1) OP_S(1) OP_R(2) OP_S(2) OP_R(3) OP_S(3)
  if (P == 0) mbar_waitu(bar + 8 * (BB_OFULL + 1), r & 1);
  if (P == 4) wg_commit();
  OP_R(4) OP_S(4) OP_R(5) OP_S(5)
  if (P == 1 && x2) MM<N>::template ss<DESC_LO(BO_RES) + 30 * 128, KOFF(20), 1>(acc, alo, xlo);
  if (P == 4) { wg_commit(); wg_wait<1>(); bar_arrive(NB_EARLY, 288); CTS(21); wg_fence(); }
  mbar_waitu(bar + 8 * (BB_FULL + rg.sl), rg.ph);
  OP_R(6) OP_T(0) OP_R(7) OP_T(1)
  if (P == 0) mbar_waitu(bar + 8 * (BB_OFULL + 2), r & 1);
  OP_T(2) OP_T(3)
  if (P == 0) MM<N>::template rs<KOFF(20), 1>(acc, W + 160, xlo);
  OP_T(4) OP_T(5)
  wg_commit();
  if (!LOCKSTEP || P) bar_arrive(NB_PP + 1 - wg, 256);
  CTS(5 * P + 2);
  bar_sync(NB_FREE + wg, 160);
  wg_wait<0>();
  acc_live<N>(acc);
  if (P == 4) bar_arrive(NB_LAST, 288);
  mbar_arrive_if(lane == 0, bar + 8 * (BB_USED + rg.sl));
  CTS(5 * P + 3);
  stage_out<N, false>(acc, SMEM0 + BO_STG + wg * 8192, warp, lane);
  bar_arrive(NB_STAGED + wg, 160);
  CTS(5 * P + 4);
  rg.step<NS_OP>(); rg.step<NS_OP>();
}
template <int N>
__device__ __forceinline__ void op_round(const uint32_t* W, uint32_t bar, Dsc alo, Dsc blo, Dsc xlo, bool x2, Ring& rg, int wg, int warp, int lane, int r) {
  op_pass<N, 0>(W, bar, alo, blo, xlo, x2, rg, wg, warp, lane, r);
  op_pass<N, 1>(W, bar, alo, blo, xlo, x2, rg, wg, warp, lane, r);
  op_pass<N, 2>(W, bar, alo, blo, xlo, x2, rg, wg, warp, lane, r);
  op_pass<N, 3>(W, bar, alo, blo, xlo, x2, rg, wg, warp, lane, r);
  op_pass<N, 4>(W, bar, alo, blo, xlo, x2, rg, wg, warp, lane, r);
}
__device__ __forceinline__ void carry_in(uint32_t sb, int wg, int warp, int lane) {
  const int row = (lane >> 1) & 3;
  if (lane < 16) {
    const uint4 v = lds128(sb + BO_CARRY + (wg * 4 + warp) * 256 + lane * 16);
    sts128(sb + BO_H + wg * 8192 + (lane >> 3) * 4096 + row * 128 + (((2 * warp + (lane & 1)) ^ row) << 4), v.x, v.y, v.z, v.w);
  }
  __syncwarp();
}
#define STAGGER 0
template <int N, int Z>
__device__ __forceinline__ void p1_pair(float* acc, const uint32_t* W, uint32_t bar, Dsc alo, Dsc blo, int lane, int r) {
  blo.e = fresh<10 + Z / 3 + N / 64 * 2>(r);
  mbar_waitu(bar + 8 * (BB_FULL + Z), r & 1);
  CTS(40 + Z);
  wg_fence();
#define P1_B(k) \
  MM<N, true>::template rs<DESC_LO(BO_RING_MLP) + (2 * Z % 3) * 1024 + k * 512, (2 * Z + k != 0)>(acc, W + 16 * Z + 8 * k, blo); \
  MM<N, true>::template ss<DESC_LO(BO_W1) + (2 * Z + k) * 512, DESC_LO(BO_RING_MLP) + (2 * Z % 3) * 1024 + k * 512 + 4, 1>(acc, alo, blo); \
  MM<N, true>::template rs<DESC_LO(BO_RING_MLP) + (2 * Z % 3) * 1024 + k * 512 + 2, 1>(acc, W + 16 * Z + 8 * k + 4, blo); \
  MM<N, true>::template ss<DESC_LO(BO_W1) + (2 * Z + k) * 512 + 128, DESC_LO(BO_RING_MLP) + (2 * Z % 3) * 1024 + k * 512 + 6, 1>(acc, alo, blo);
  P1_B(0)
  if (Z == 1 || Z == 2) { wg_commit(); wg_wait<1>(); mbar_arrive_if(lane == 0, bar + 8 * (BB_EMPTY + Z - 1)); wg_fence(); }
  P1_B(1)
  wg_commit();
}
template <int N>
__device__ __forceinline__ void phase1(const uint32_t* W, uint32_t sb, Dsc alo, Dsc blo, int half, int wg, int warp, int lane, int off, int r) {
  float acc[N / 2];
  const uint32_t bar = sb + BO_BAR;
  CTS(30);
  p1_pair<N, 0>(acc, W, bar, alo, blo, lane, r);
  p1_pair<N, 1>(acc, W, bar, alo, blo, lane, r);
  p1_pair<N, 2>(acc, W, bar, alo, blo, lane, r);
  mbar_waitu(bar + 8 * (BB_SFREE + 4 + wg), (r + 1) & 1);
  carry_in(sb, wg, warp, lane);
  if (STAGGER && wg) bar_sync(NB_PP + 1, 256);
  p1_pair<N, 3>(acc, W, bar, alo, blo, lane, r);
  p1_pair<N, 4>(acc, W, bar, alo, blo, lane, r);
  if (STAGGER && !wg) bar_arrive(NB_PP + 1, 256);
  const int c = (lane >> 3) & 1, i0 = (lane >> 4) * 8 + (lane & 7) + off;
  uint32_t a0 = sb + BO_H + wg * 8192 + half * 4096 + i0 * 128 + (((2 * warp + c) ^ (i0 & 7)) << 4);
  uint32_t a1 = i0 >= 16 ? sb + BO_CARRY + (wg * 4 + warp) * 256 + half * 128 + (i0 - 16) * 32 + c * 16 : a0 + 2048, a3 = a1 + (i0 >= 16 ? 128 : 4096);
  asm volatile("" : "+r"(a0), "+r"(a1), "+r"(a3));
  mbar_waitu(bar + 8 * BB_STAT, r & 1);
  const uint32_t sa = sb + BO_STAT + half * 128 + (lane & 3) * 32;
  uint4 t[2] = {lds128(sa), lds128(sa + 16)};
  wg_wait<0>();
  acc_live<N>(acc);
  CTS(32);
#pragma unroll
  for (int m = 0; m < N / 16; m++) {
    const float s0 = __uint_as_float(t[m & 1].x), s1 = __uint_as_float(t[m & 1].y), s2 = __uint_as_float(t[m & 1].z), s3 = __uint_as_float(t[m & 1].w);
    float* d = acc + 8 * m;
    d[0] *= s0; d[1] *= s1; d[2] *= s0; d[3] *= s1; d[4] *= s2; d[5] *= s3; d[6] *= s2; d[7] *= s3;
    if (m + 2 < N / 16) t[m & 1] = lds128(sa + 128 + m * 16);
#pragma unroll
    for (int j = 0; j < 8; j++) d[j] = gelu2(d[j]);
  }
#pragma unroll
  for (int m = 0; m < N / 16; m++)
    stsm4t(m == 1 ? a1 : m == 3 ? a3 : a0 + m * 2048, pack2(acc[8 * m], acc[8 * m + 1]), pack2(acc[8 * m + 2], acc[8 * m + 3]), pack2(acc[8 * m + 4], acc[8 * m + 5]), pack2(acc[8 * m + 6], acc[8 * m + 7]));
}
template <int N, int P>
__device__ __forceinline__ void p2_pass(const uint32_t* W, uint32_t bar, Dsc alo, Dsc blo, int wg, int warp, int lane, int r) {
  float acc[N / 2];
  blo.e = fresh<P + N / 64 * 5>(r);
  CTS(5 * P);
  if (P || wg) bar_sync(NB_PP + wg, 256);
  wg_fence();
  MM<N>::template rs<DESC_LO(BO_H) + 0, 0>(acc, W + 80 + 16 * P, blo); MM<N>::template ss<DESC_LO(0) + P * 1024, DESC_LO(BO_H) + 512, 1>(acc, alo, blo);
  MM<N>::template rs<DESC_LO(BO_H) + 2, 1>(acc, W + 84 + 16 * P, blo); MM<N>::template ss<DESC_LO(0) + P * 1024 + 128, DESC_LO(BO_H) + 514, 1>(acc, alo, blo);
  MM<N>::template rs<DESC_LO(BO_H) + 4, 1>(acc, W + 88 + 16 * P, blo); MM<N>::template ss<DESC_LO(0) + P * 1024 + 512, DESC_LO(BO_H) + 516, 1>(acc, alo, blo);
  MM<N>::template rs<DESC_LO(BO_H) + 6, 1>(acc, W + 92 + 16 * P, blo); MM<N>::template ss<DESC_LO(0) + P * 1024 + 640, DESC_LO(BO_H) + 518, 1>(acc, alo, blo);
  wg_commit();
  if (P < 4 || !wg) bar_arrive(NB_PP + 1 - wg, 256);
  CTS(5 * P + 2);
  if (P == 2 || P == 3) mbar_waitu(bar + 8 * (BB_SFREE + 2 * (P - 2) + wg), r & 1);
  wg_wait<0>();
  acc_live<N>(acc);
  if (P == 4) bar_sync(NB_H, 256);
  CTS(5 * P + 3);
  stage_out<N, true>(acc, SMEM0 + (P == 4 ? BO_H : BO_RING_MLP + (2 - (P & 1)) * 16384) + wg * 8192, warp, lane);
  bar_arrive(NB_STAGED + (P == 4 ? 4 : 2 * (P & 1)) + wg, 160);
  CTS(5 * P + 4);
}
template <int N>
__device__ __forceinline__ void phase2(const uint32_t* W, uint32_t bar, Dsc alo, Dsc blo, int wg, int warp, int lane, int r) {
  p2_pass<N, 0>(W, bar, alo, blo, wg, warp, lane, r);
  p2_pass<N, 1>(W, bar, alo, blo, wg, warp, lane, r);
  p2_pass<N, 2>(W, bar, alo, blo, wg, warp, lane, r);
  p2_pass<N, 3>(W, bar, alo, blo, wg, warp, lane, r);
  p2_pass<N, 4>(W, bar, alo, blo, wg, warp, lane, r);
}

__device__ __forceinline__ void ldg4(uint32_t* v, const void* p) {
  asm volatile("ld.relaxed.gpu.global.v4.u32 {%0,%1,%2,%3}, [%4];" : "=r"(v[0]), "=r"(v[1]), "=r"(v[2]), "=r"(v[3]) : "l"(p) : "memory"); }
__device__ __forceinline__ void stg4(void* p, const uint32_t* v) {
  asm volatile("st.global.v4.u32 [%0], {%1,%2,%3,%4};" :: "l"(p), "r"(v[0]), "r"(v[1]), "r"(v[2]), "r"(v[3]) : "memory"); }
struct RowPtr {
  unsigned char *p, *q, *t;
  __device__ __forceinline__ void ld(uint32_t* v, int o) const {
    ldg4(v, p + o); ldg4(v + 4, q + o);
    asm volatile("ld.relaxed.gpu.global.v2.u32 {%0,%1}, [%2];" : "=r"(v[8]), "=r"(v[9]) : "l"(t + o) : "memory");
  }
  __device__ __forceinline__ void st(const uint32_t* w, int o) const {
    stg4(p + o, w); stg4(q + o, w + 4);
    asm volatile("st.global.v2.u32 [%0], {%1,%2};" :: "l"(t + o), "r"(w[8]), "r"(w[9]) : "memory");
  }
};
__device__ __forceinline__ RowPtr row_img(int r, int n, int lane) {
  unsigned char* b = &g_acc[0][r % RD][n * 128];
  unsigned char* p = b + (uint32_t)((lane >> 3) * 8192 + (((lane ^ n) & 7) << 4));
  return {p, p + 32768, b + (uint32_t)(65536 + (lane >> 4) * 8192 + ((((lane >> 1) ^ n) & 7) << 4) + (lane & 1) * 8)};
}
__device__ __forceinline__ RowPtr row_ext(const void* lin, bool xn, int layer, int tok, int lane) {
  unsigned char* b = xn ? reinterpret_cast<unsigned char*>(&g_xn[layer][0]) + (uint32_t)((tok >> 5) * 40960 + ((tok >> 3) & 3) * 2560 + (tok & 7) * 32)
                        : (unsigned char*)lin + (uint32_t)(tok * 1280);
  const uint32_t o = (lane >> 1) * 256 + ((lane ^ (tok >> 2)) & 1) * 16;
  return {b + (uint32_t)(xn ? o + (lane >= 20 ? 7680 : 0) : lane * 16),
          b + (uint32_t)(xn ? o + 4096 + 7680 + (lane >= 8 ? 7680 : 0) + (lane >= 28 ? 7680 : 0) : lane * 16 + 512),
          b + (uint32_t)(xn ? (lane >> 2) * 256 + ((lane & 3) ^ ((tok >> 1) & 2)) * 8 + 8192 + 3 * 7680 : lane * 8 + 1024)};
}
__device__ __forceinline__ float2 h2f(uint32_t w) {
  float2 f; asm("{\n.reg .f16 l, h;\nmov.b32 {l, h}, %2;\ncvt.f32.f16 %0, l;\ncvt.f32.f16 %1, h;\n}" : "=f"(f.x), "=f"(f.y) : "r"(w)); return f; }
__device__ __forceinline__ float rsq(float x) { float y; asm("rsqrt.approx.ftz.f32 %0, %1;" : "=f"(y) : "f"(x)); return y; }
__device__ __forceinline__ void red_if(uint32_t v, const void* a) {
  asm volatile("{\n.reg .pred q;\nsetp.ne.u32 q, %1, 0;\n@q red.relaxed.gpu.global.add.u32 [%0], %1;\n}" :: "l"(a), "r"(v) : "memory"); }
__device__ __forceinline__ uint32_t dep0(uint32_t w, int lane) { uint32_t z; asm volatile("shr.b32 %0, %1, %2;" : "=r"(z) : "r"(w), "r"(lane + 32)); return z; }
__device__ __forceinline__ int lane_of(uint32_t w) {
  int lane; asm volatile("{\n.reg .u32 t;\nmov.u32 t, %%laneid;\nshr.u32 %0, %1, 20;\nadd.u32 %0, %0, t;\n}" : "=r"(lane) : "r"(w)); return lane; }
#define BUF (RD * TILE_B)
__device__ __forceinline__ int await(uint32_t v, const uint32_t* p, uint32_t target, bool lazy) {
  int n = 0;
  while (!__all_sync(~0u, v >= target)) {
    if (lazy) __nanosleep(200);
    if (++n > SPIN_LIMIT) FAIL();
    v = ld_relaxed(p);
  }
  asm volatile("fence.acquire.gpu;" ::: "memory");
  return lane_of(v);
}
template <int W> __device__ __forceinline__ void sum2(float& s, float& q, int lane) {
  const bool up = lane & (W / 2);
  float e = (up ? q : s) + __shfl_xor_sync(~0u, up ? s : q, W / 2);
#pragma unroll
  for (int o = W / 4; o; o >>= 1) e += __shfl_xor_sync(~0u, e, o);
  const float f = __shfl_xor_sync(~0u, e, W / 2);
  s = up ? f : e; q = up ? e : f;
}
template <int TYPE>
__device__ __forceinline__ void rrow(int r, int row, int tok, int lane, const uint32_t* go, int role, const __nv_bfloat16* x) {
  const int half = TYPE ? 0 : row >> 5;
  float v[20];
  float2 st = make_float2(1.f, 0.f);
  {
    uint32_t a[10], c[10], u[10], sh = 16;
    if (TYPE == 2) row_img(r + RD - ((row & 31) < 2), (row & 32) + ((row - 2) & 31), lane).ld(u, 4 * BUF);
    else row_ext(x, half, 1, tok, lane).ld(u, 0);
    if (TYPE == 2 || (TYPE == 0 && half))
      asm volatile("ld.relaxed.gpu.global.v2.f32 {%0,%1}, [%2];" : "=f"(st.x), "=f"(st.y) : "l"(g_stat + tok) : "memory");
    RowPtr ap = row_img(r, row, lane);
    const uint32_t g0 = TYPE != 3 ? ld_relaxed(go) : 0;
    if (TYPE == 2) {
      ap.ld(c, 2 * BUF);
      uint32_t z = dep0(c[9], lane);
#pragma unroll
      for (int i = 0; i < 10; i++) {
        const float2 g = h2f(u[i] | z), h = h2f(c[i] | z);
        v[2 * i] = fmaf(h.x, 0.5f, g.x * st.x); v[2 * i + 1] = fmaf(h.y, 0.5f, g.y * st.x);
        if (i & 1) z = dep0(__float_as_uint(v[2 * i]) | __float_as_uint(v[2 * i + 1]), lane);
      }
    }
    if (TYPE != 3) {
      asm volatile("" : "+l"(ap.p), "+l"(ap.t));
      ap.q = ap.p + 32768;
      lane = await(g0, go, NOP * NW12 * NW34, false); BTS2(r, 8 + 2 * TYPE); RTS(0);
      ap.ld(a, TYPE ? 3 * BUF : 0);
    }
    if (TYPE == 0) {
      ap.ld(c, BUF);
      const uint32_t one = 0x3f803f80u | dep0(c[9], lane);
#pragma unroll
      for (int i = 0; i < 10; i++) asm volatile("fma.rn.bf16x2 %0, %0, %1, %2;" : "+r"(a[i]) : "r"(one), "r"(c[i]));
      sh |= dep0(a[9], lane);
    }
    const float k = TYPE == 2 ? __uint_as_float(0x3f000000u | dep0(a[9], lane)) : 0.f;
#pragma unroll
    for (int i = 0; i < 10; i++) {
      if (TYPE == 2) { const float2 h = h2f(a[i]); v[2 * i] = fmaf(h.x, k, v[2 * i]); v[2 * i + 1] = fmaf(h.y, k, v[2 * i + 1]); continue; }
      float p = __uint_as_float(u[i] << sh), q = __uint_as_float(u[i] & (0xffffu << sh));
      if (TYPE == 0) { p = fmaf(p, st.x, bf_lo(a[i])); q = fmaf(q, st.x, bf_hi(a[i])); }
      v[2 * i] = p; v[2 * i + 1] = q;
    }
  }
  RTSD(1, v[19]);
  float s = 0.f, q = 0.f;
#pragma unroll
  for (int i = 0; i < 5; i++) {
    s += (v[4 * i] + v[4 * i + 1]) + (v[4 * i + 2] + v[4 * i + 3]);
    q += fmaf(v[4 * i], v[4 * i], v[4 * i + 1] * v[4 * i + 1]) + fmaf(v[4 * i + 2], v[4 * i + 2], v[4 * i + 3] * v[4 * i + 3]);
  }
  sum2<32>(s, q, lane);
  const float mean = s * (1.f / DM), var = fmaxf(q * (1.f / DM) - mean * mean, 0.f), rs = rsq(var + 1e-5f), k = TYPE ? rs : 2.f * rs, mr = -mean * k;
  RTSD(2, rs);
  uint32_t w[10];
#pragma unroll
  for (int i = 0; i < 10; i++) w[i] = pk<TYPE == 0>(fmaf(v[2 * i], k, mr), fmaf(v[2 * i + 1], k, mr));
  if (TYPE) row_ext(nullptr, true, TYPE == 2, tok, lane).st(w, 0);
  else {
    row_img(r, row, lane).st(w, 4 * BUF);
    row_img(r + ((row & 31) >= 30), (row & 32) + ((row + 2) & 31), lane).st(w, 2 * BUF);
    if (lane == 1) g_st2[0][r % RD][row] = (__float_as_uint(0.5f * rsq(fmaf(var * rs, rs, 1e-5f))) & ~127u) | (r + 1);
  }
  if (TYPE != 3 && lane == 0) g_stat[tok] = make_float2((var + 1e-5f) * rs * (TYPE ? 1.f : 0.5f), mean + st.y);
}
__device__ __forceinline__ void r2rows(int r, int row, int lane) {
  const int n = row + (lane >> 4);
  const unsigned char* ap = &g_acc[2][r % RD][0] + (uint32_t)(n * 128 + ((lane >> 3) & 1) * 8192 + (((lane ^ n) & 7) << 4));
  uint32_t a[20];
#pragma unroll
  for (int i = 0; i < 5; i++) ldg4(a + 4 * i, ap + i * 16384);
  const uint32_t z = dep0(a[19], lane);
  float s = 0.f, q = 0.f, q2 = 0.f;
#pragma unroll
  for (int i = 0; i < 20; i++) { const float2 h = h2f(a[i] | z); s += h.x + h.y; q = fmaf(h.x, h.x, q); q2 = fmaf(h.y, h.y, q2); }
  q += q2;
  sum2<16>(s, q, lane);
  const float mean = s * (0.5f / DM), rs = rsq(fmaxf(q * (0.25f / DM) - mean * mean, 0.f) + 1e-5f);
  if ((lane & 15) == 0) asm volatile("st.relaxed.gpu.global.u32 [%0], %1;" :: "l"(&g_st2[1][r % RD][n]), "r"((__float_as_uint(0.5f * rs) & ~127u) | (r + 1)) : "memory");
}
__device__ __forceinline__ void r3rows(int r, int row, int tok, int lane, __nv_bfloat16* out) {
  const int n = row + (lane >> 4), m = 32 + ((n - 2) & 31);
  const unsigned char* ap = &g_acc[0][r % RD][0] + (uint32_t)(n * 128 + ((lane >> 3) & 1) * 8192 + (((lane ^ n) & 7) << 4));
  const unsigned char* zp = &g_acc[4][(r + RD - (row == 32)) % RD][0] + (uint32_t)(m * 128 + ((lane >> 3) & 1) * 8192 + (((lane ^ m) & 7) << 4));
  unsigned char* op = reinterpret_cast<unsigned char*>(out) + (uint32_t)((tok + (lane >> 4)) * 1280 + (lane & 15) * 16);
  float2 st;
  asm volatile("ld.relaxed.gpu.global.v2.f32 {%0,%1}, [%2];" : "=f"(st.x), "=f"(st.y) : "l"(g_stat + tok + (lane >> 4)) : "memory");
#pragma unroll 1
  for (int i0 = 0; i0 < 3; i0++) {
    uint32_t a[8], c[8], u[8];
#pragma unroll
    for (int i = 0; i < 2; i++) { ldg4(a + 4 * i, ap + 3 * BUF + i * 16384); ldg4(c + 4 * i, ap + 2 * BUF + i * 16384); ldg4(u + 4 * i, zp + i * 16384); }
    uint32_t z = dep0(u[7], lane);
#pragma unroll
    for (int i = 0; i < 8; i++) {
      const float2 h = h2f(a[i] | z), e = h2f(c[i] | z), g = h2f(u[i] | z);
      a[i] = pack2(fmaf(h.x + e.x, 0.5f, fmaf(g.x, st.x, st.y)), fmaf(h.y + e.y, 0.5f, fmaf(g.y, st.x, st.y)));
      if (i & 1) z = dep0(a[i], lane);
    }
    if (i0 < 2) stg4(op, a);
    stg4(op + 256, a + 4);
    ap += 32768 >> i0; zp += 32768 >> i0; op += 512 >> i0;
  }
}
template <int TYPE>
__device__ __forceinline__ void rloop(int row, int cp, int role, const __nv_bfloat16* x, __nv_bfloat16* out) {
  constexpr int ST = TYPE == 4 ? 2 : TYPE;
  const int r0 = row & 32 ? LAG : 0;
  uint32_t v = 0;
#pragma unroll 1
  for (int r = r0; r < r0 + NSEG + (TYPE > 0); r++) {
    const int tok = (r - r0) * 32 + (row & 31) - (TYPE ? 2 : 0);
    const bool valid = TYPE == 0 || (unsigned)tok < S_LEN;
    const uint32_t* go = &g_f[F_R1 + 4 * ST + cp][r];
    const uint32_t* first = TYPE == 2 ? &g_f[F_R2 + cp][r] : TYPE ? go : (const uint32_t*)&g_xready[NSEG + r - r0][0];
    if constexpr (TYPE == 1 || TYPE == 4) {
      const int lane = await(v, go, NOP * NW12 * NW34, false);
      BTS2(r, 8 + 2 * ST); RTS(0);
      if (TYPE == 1) { r2rows(r, row, lane); BTS2(r, 11); continue; }
      if (valid) r3rows(r, row, tok, lane, out);
    } else {
      if (TYPE || row >= 32) await(v, first, TYPE ? NOP * NW12 * NW34 : 32, true);
      if (valid) rrow<TYPE>(r, row, tok, lane_of(r), go, role, x);
    }
    const int lane = lane_of(r);
    const void* f = lane ? (const void*)&g_xready[NSEG + (tok >> 5)][0] : (const void*)&g_f[TYPE ? F_DONE : F_Z][r];
    asm volatile("" : "+l"(f));
    __syncwarp();
    RTS(3);
    v = ld_relaxed(first + (TYPE ? 1 : 8));
    asm volatile("fence.release.gpu;" ::: "memory");
    RTS(4);
    red_if(lane == 0 || (TYPE == 2 && lane == 1 && valid) ? (TYPE & 5 ? 2 : 1) : 0, f);
    RTS(5);
    RTS_OUT();
    BTS2(r, 9 + 2 * ST);
  }
}

#define SINGLE_OP 3
#define SINGLE_W 0
#define W_DELAY 0
#define BULK_ADD(T, dst, src, len) asm volatile("{\n.reg .pred e;\nelect.sync _|e, 0xffffffff;\n@e cp.reduce.async.bulk.global.shared::cta.bulk_group.add.noftz." T " [%0], [%1], %2;\n}" \
                                               :: "l"(dst), "r"(src), "r"(len) : "memory")
#define COMMIT() asm volatile("cp.async.bulk.commit_group;" ::: "memory")
#define DRAINED(n) do { asm volatile("cp.async.bulk.wait_group.read " #n ";" ::: "memory"); __syncwarp(); } while (0)
#define WRITTEN() do { asm volatile("cp.async.bulk.wait_group 0;\nfence.proxy.async.global;" ::: "memory"); __syncwarp(); } while (0)
__device__ __forceinline__ void wait_flags(const uint32_t* p, uint32_t target) {
  int n = 0;
  while (!__all_sync(~0u, ld_relaxed(p) >= target)) { if (++n > SPIN_LIMIT) FAIL(); }
  asm volatile("fence.acquire.gpu;" ::: "memory");
  asm volatile("fence.proxy.async.global;" ::: "memory");
}
__global__ void __launch_bounds__(512, 1) bworker_kernel(const __grid_constant__ BParams P) {
  extern __shared__ __align__(1024) unsigned char smem_raw[];
  const uint32_t sb = SMEM0, bar = sb + BO_BAR;
  const int wg = __shfl_sync(~0u, threadIdx.x >> 7, 0), warp = __shfl_sync(~0u, (threadIdx.x >> 5) & 3, 0);
  if (threadIdx.x == 0) {
    if (smem_u32(smem_raw) != SMEM0) FAIL();
    uint32_t smid; asm volatile("mov.u32 %0, %%smid;" : "=r"(smid));
    const uint32_t nb = ld_relaxed(&g_tpc[(smid >> 1) & 127]);
    const bool single = nb > 1, far = nb == 0 && (smid < 64 || smid >= 124);
    int kind = far || (single && atomicAdd(&g_f[F_MISC][35], 1u) < SINGLE_OP) ? 0 : single ? 1 + SINGLE_W : 1;
    int rc = single || (smid >> 1) == 16 || (smid >> 1) == 63 ? 1 : far ? 2 : 0;
    uint32_t i, o;
    while ((i = atomicAdd(&g_f[F_MISC][32 + kind], 1u)) >= (kind == 0 ? NOP : kind == 1 ? NW12 : NW34)) kind = (kind + 1) % 3;
    while ((o = atomicAdd(&g_f[F_MISC][36 + rc], 1u)) >= (rc == 0 ? 16 : rc == 1 ? 8 : 12)) rc = (rc + 1) % 3;
    sts64(sb + BO_BOX, i + (kind == 0 ? 0 : kind == 1 ? NOP : NOP + NW12), o + (rc ? 8 + 8 * rc : 0));
    for (int k = 0; k < BB_NUM; k++) mbar_init(bar + 8 * k, k >= BB_USED ? 4 : k >= BB_EMPTY ? 8 : k >= BB_ZFREE && kind ? 2 : 1);
    asm volatile("fence.mbarrier_init.release.cluster;" ::: "memory");
  }
  if (threadIdx.x < 128) sts128(sb + BO_CARRY + threadIdx.x * 16, 0u, 0u, 0u, 0u);
  fence_async();
  __syncthreads();
  const int role = uni(lds32(sb + BO_BOX));
  const bool op = role < NOP, w12 = role < NOP + NW12;
  const int j = op ? role : w12 ? role - NOP : role - NOP - NW12;
  const int rot = op ? (j ? 2 * ((j + 1) % 5) : 0) : 2 * (j % 5);
  if (wg == 3) {
    asm volatile("setmaxnreg.dec.sync.aligned.u32 24;");
    LANE_INIT();
    if (warp < 2) {
      auto announce = [&](int r) {
        const uint32_t* f = &g_f[(op ? F_R1 : w12 ? F_R2 : F_R3) + (lane & 3)][r];
        asm volatile("" : "+l"(f));
        if (warp == 0) { mbar_arrive_if(lane == 0, bar + 8 * BB_DONE); return; }
        mbar_waitw(bar + 8 * BB_DONE, r & 1);
        PTS(60);
        asm volatile("fence.release.gpu;" ::: "memory");
        red_if(lane >= 4 ? 0 : op ? NW12 * NW34 : w12 ? NOP * NW34 : NOP * NW12, f);
        PTS(61);
        BTS(r, 4);
      };
      if (op) {
        int mt = rot + warp;
        bar_arrive(NB_FREE + warp, 160);
#pragma unroll 1
        for (int r = 0; r < NSTEP; r++) {
          const uint32_t len = fmask(r) == 3 ? 8192 : 4096;
          unsigned char* acc = &g_acc[j & 1][r % RD][fmask(r) == 2 ? 4096 : 0];
#pragma unroll 1
          for (int p = 0; p < 5; p++) {
            bar_sync(NB_STAGED + warp, 160);
            PTS(50 + 2 * p + warp);
            fence_async();
            BULK_ADD("bf16", acc + mt * 8192, sb + BO_STG + warp * 8192, len);
            COMMIT();
            PTS(64 + 50 + 2 * p + warp);
            mt = mt >= 8 ? mt - 8 : mt + 2;
            DRAINED(0);
            bar_arrive(NB_FREE + warp, 160);
          }
          WRITTEN();
          announce(r);
        }
      } else {
#pragma unroll 1
        for (int r = 0; r < NR; r++) {
          const uint32_t len = bmask(r) == 3 ? 8192 : 4096;
          unsigned char* acc = &g_acc[w12 ? 2 : 3][r % RD][bmask(r) == 2 ? 4096 : 0];
          int mt = rot + warp;
#pragma unroll 1
          for (int p = 0; p < 5; p++) {
            bar_sync(NB_STAGED + (p == 4 ? 4 : 2 * (p & 1)) + warp, 160);
            PTS(50 + 2 * p + warp);
            fence_async();
            BULK_ADD("f16", acc + mt * 8192, sb + (p == 4 ? BO_H : BO_RING_MLP + (2 - (p & 1)) * 16384) + warp * 8192, len);
            COMMIT();
            PTS(64 + 50 + 2 * p + warp);
            mt = mt >= 8 ? mt - 8 : mt + 2;
            if (p == 4) break;
            DRAINED(1);
            mbar_arrive_if(lane == 0, bar + 8 * (p == 1 || p == 2 ? BB_SFREE + 2 * (p - 1) + warp : BB_ZFREE + (p >> 1)));
            if (p == 3) { DRAINED(0); mbar_arrive_if(lane == 0, bar + 8 * (BB_ZFREE + 2)); }
          }
          WRITTEN();
          mbar_arrive_if(lane == 0, bar + 8 * (BB_SFREE + 4 + warp));
          announce(r);
        }
      }
    } else {
      if (op && warp == 2) {
        unsigned char* wt = g_wt + j * (10 * OP_SLOT);
#pragma unroll 1
        for (int m0 = 0; m0 < 10; m0 += 3) {
          const int nu = m0 < 9 ? 9 : 3;
          mbar_expect_if(lane == 0, bar + 8 * BB_TMP, nu * 4096);
#pragma unroll 1
          for (int k = 0; k < nu; k++) tma2d_e(sb + BO_RING_OP + k * 4096, &P.wmap[0], (m0 + k / 3) * 64, 320 * j + 224 + 32 * (k % 3), bar + 8 * BB_TMP);
          mbar_waitw(bar + 8 * BB_TMP, m0 & 1);
          bulk_s2g_e(wt + m0 * OP_SLOT, sb + BO_RING_OP, nu * 4096);
          COMMIT();
          WRITTEN();
        }
        asm volatile("fence.acq_rel.gpu;" ::: "memory");
        int sl = 0, ph = 1, mt = rot;
#pragma unroll 1
        for (int r = -1; r < NSTEP; r++) {
#pragma unroll 1
          for (int n = r < 0 ? 7 : 0; n < (r + 1 < NSTEP ? 10 : 7); n++) {
            mbar_waitw(bar + 8 * (BB_USED + sl), ph);
            mbar_expect_if(lane == 0, bar + 8 * (BB_FULL + sl), OP_SLOT);
            bulk_g2s_e(sb + BO_RING_OP + sl * OP_SLOT, wt + mt * OP_SLOT, OP_SLOT, bar + 8 * (BB_FULL + sl));
            if (++sl == 3) { sl = 0; ph ^= 1; }
            mt = mt == 9 ? 0 : mt + 1;
          }
        }
      } else if (op) {
        mbar_waitw(bar + 8 * BB_START, 0);
#pragma unroll 1
        for (int r = 0; r < NSTEP; r++) {
          const int rb = r - RD + 2;
          const uint32_t len = fmask(r) == 3 ? 8192 : 4096;
          const unsigned char* src = g_o + (uint32_t)(r % RO * (96 * 8192) + 5 * j * len);
          wait_flags(lane < 2 ? &g_f[F_O + (lane ? NOP : j)][r] : rb >= 0 ? &g_f[F_DONE][rb] : &g_f[F_MISC][0],
                     lane < 2 ? (lane ? 1 : 5) : rb >= 0 ? rtarget(bmask(rb)) : NBC * 8);
          PTS1(35);
          if (r) bar_sync(NB_EARLY, 288);
          if (r == LAG) bar_sync(NB_LAST, 288);
          mbar_expect_if(lane < 3, bar + 8 * (BB_OFULL + lane), 2 * len);
          bulk_g2s_e(sb + BO_O, src, 2 * len, bar + 8 * BB_OFULL);
          PTS(62); PTS1(38);
          if (r && r != LAG) bar_sync(NB_LAST, 288);
          bulk_g2s_e(sb + BO_O + 2 * len, src + 2 * len, 2 * len, bar + 8 * (BB_OFULL + 1));
          bulk_g2s_e(sb + BO_O + 4 * len, src + 4 * len, len, bar + 8 * (BB_OFULL + 2));
          bulk_g2s_e(sb + BO_O + 5 * len, src + (95 - 5 * j) * len, len, bar + 8 * (BB_OFULL + 2));
          PTS1(64 + 35);
          BTS(r, 0);
        }
      } else if (warp == 2) {
#pragma unroll 1
        for (int r = 0; r < NR; r++) {
          const int mk = w12 ? fmask(r) : bmask(r);
          if (mk) {
            const unsigned char* src = &g_acc[w12 ? 4 : 2][r % RD][mk == 2 ? 4096 : 0];
            wait_flags(w12 ? &g_f[F_Z][r] : lane && r >= 2 ? &g_f[F_R3 + (j & 3)][r - 2] : &g_f[F_R2 + (j & 3)][r], w12 ? rtarget(mk) : NOP * NW12 * NW34);
#pragma unroll 1
            for (int z = 0; z < 5; z++) {
              const uint32_t fb = bar + 8 * (BB_FULL + z), dst = sb + BO_RING_MLP + 2 * z % 3 * 16384 + (mk == 2 ? 4096 : 0);
              mbar_waitw(bar + 8 * (z < 3 ? BB_ZFREE + z : BB_EMPTY + z - 3), (r + (z < 3)) & 1);
              if (z == 0) PTS(62);
              mbar_expect_if(lane == 0, fb, mk == 3 ? 16384 : 8192);
              bulk_g2s_e(dst, src + z * 16384, mk == 3 ? 16384 : 4096, fb);
              if (mk != 3) bulk_g2s_e(dst + 8192, src + z * 16384 + 8192, 4096, fb);
              if (z == 0) BTS(r, 0);
            }
          }
          if (!w12) {
#pragma unroll 1
            for (int c = j; c < 120; c += NW34) bulk_s2g_e(&g_acc[c < 80 ? c / 40 : 3][(r + (c < 80 ? 0 : 2)) % RD][c % 40 * 2048], sb + BO_CARRY, 2048);
            COMMIT();
            WRITTEN();
          }
          mbar_waitw(bar + 8 * BB_DONE, (r + 1) & 1);
          mbar_arrive_if(lane == 0, bar + 8 * BB_DONE);
        }
      } else {
#pragma unroll 1
        for (int r = 0; r < (w12 ? NSTEP : NR); r++) {
          const bool idle = !((w12 ? fmask(r) : bmask(r)) >> (lane >> 4) & 1);
          uint32_t t0, t1;
          int n = 0;
          mbar_waitw(bar + 8 * BB_FULL, r & 1);
          do {
            asm volatile("ld.relaxed.gpu.global.v2.u32 {%0,%1}, [%2];" : "=r"(t0), "=r"(t1) : "l"(&g_st2[!w12][r % RD][2 * lane]) : "memory");
            if (++n > SPIN_LIMIT) FAIL();
          } while (!__all_sync(~0u, idle || (((t0 ^ (r + 1)) | (t1 ^ (r + 1))) & 127) == 0));
          sts64(sb + BO_STAT + (lane >> 4) * 128 + (lane & 3) * 32 + ((lane >> 2) & 3) * 8, t0, t1);
          __syncwarp();
          mbar_arrive_if(lane == 0, bar + 8 * BB_STAT);
          PTS(63);
        }
      }
    }
    bar_arrive(NB_END, 512);
  } else if (wg == 2) {
    asm volatile("setmaxnreg.dec.sync.aligned.u32 40;");
    const int ord = uni(lds32(sb + BO_BOX + 4));
    const int gw = ord < 16 ? warp * 16 + ord : ord < 24 ? 48 + warp * 8 + ord : 72 + warp * 12 + ord, row = gw < 64 ? gw : gw < 96 ? gw - 64 : gw < 128 ? 2 * gw - 192 : 2 * gw - 224;
#pragma unroll 1
    for (int t = gw; t < S_LEN; t = row < 32 ? S_LEN : t < 4 * NBC ? 4 * NBC + (gw < 64 ? gw - 32 : gw - 80) : t + 64) {
      const int lane = lane_of(t);
      if (lane < 20 && t + 128 < S_LEN) asm volatile("prefetch.global.L2 [%0];" :: "l"(P.x + (t + (t < 4 * NBC ? 4 * NBC : 128)) * DM + (lane >> 1) * 64));
      rrow<3>(0, 0, t, lane, nullptr, role, P.x);
      __syncwarp();
      asm volatile("fence.release.gpu;" ::: "memory");
      red_if(lane == 0, &g_xready[t >> 5][0]);
    }
    if (gw < 64) rloop<0>(row, gw & 3, role, P.x, P.out);
    else if (gw < 96) rloop<2>(row, gw & 3, role, P.x, P.out);
    else if (gw < 128) rloop<1>(row, gw & 3, role, P.x, P.out);
    else rloop<4>(row, gw & 3, role, P.x, P.out);
    asm volatile("griddepcontrol.wait;" ::: "memory");
    const int t = threadIdx.x & 127;
    for (int i = (blockIdx.x * 128 + t) * 4; i < 4 * NCL * 2560; i += NBC * 512)
      *reinterpret_cast<uint4*>(&g_part[0][0][0][0] + i) = make_uint4(0u, 0u, 0u, 0u);
    bar_sync(NB_END, 512);
    if (t == 0) {
      uint32_t n;
      asm volatile("atom.acq_rel.gpu.global.add.u32 %0, [%1], 1;" : "=r"(n) : "l"(&g_f[F_MISC][64]) : "memory");
      sts32(sb + BO_BOX, n);
    }
    bar_sync(NB_END2, 128);
    if (lds32(sb + BO_BOX) == NBC - 1) {
      for (int i = t; i < F_NUM * 24; i += 128) reinterpret_cast<uint4*>(&g_f[0][0])[i] = make_uint4(0u, 0u, 0u, 0u);
      g_xready[t][0] = 0; g_tpc[t] = 0;
    }
  } else {
    asm volatile("setmaxnreg.inc.sync.aligned.u32 224;");
    LANE_INIT();
    for (int i = blockIdx.x * 256 + threadIdx.x; i < 2 * (RD + 1) * TILE_B / 16; i += NBC * 256)
      reinterpret_cast<uint4*>(&g_acc[i < 2 * RD * TILE_B / 16 ? 0 : 1][0][0])[i] = make_uint4(0u, 0u, 0u, 0u);
    warp_signal(&g_f[F_MISC][0], lane);
    const int mt0 = (rot + wg) % 10;
    auto boxes = [&](int ss) {
      const int nb = op && ss ? 3 : 4;
      const uint32_t base = sb + (ss ? BO_RES + wg * OP_RES : wg * 83968);
      mbar_expect_if(warp == 0 && lane == 0, bar + 8 * (BB_W + wg), nb * 20480 + (op ? 2048 : 0));
      bar_sync(NB_H, 256);
      if (warp < nb) {
#pragma unroll 1
        for (int i = warp; i < 5 * nb; i += nb) {
          const int p = op ? i / nb : (i - 10) >> 1, mt = (mt0 + 2 * p) % 10;
          const bool first = !op && i < 10;
          tma2d_e(op || !ss ? base + i * 4096 : sb + (first ? BO_W1 : -81920) + (2 * i + wg) * 4096, &P.wmap[op ? 0 : (w12 ? 1 : 3) + !first], first ? 128 * j + 64 * wg : mt * 64,
                  op ? 320 * j + 64 * warp + 32 * ss : first ? 64 * i + 32 * ss : 128 * j + 32 * (i & 1) + 64 * ss, bar + 8 * (BB_W + wg));
        }
      }
      if (op && warp == 3) tma2d_e(base + nb * 20480, &P.wo16, (mt0 + 2 * ss) % 10 * 64, 95 * 64 + (j + 1) / 5 * 16, bar + 8 * (BB_W + wg));
      mbar_waitw(bar + 8 * (BB_W + wg), ss);
    };
    if (W_DELAY) __nanosleep(W_DELAY);
    uint32_t W[164];
    boxes(0);
    load_w<41>(W, sb + wg * 83968, warp, lane);
    fence_async();
    boxes(1);
    if (!op) {
      float cs[2] = {0.f, 0.f};
      const uint32_t a0 = sb + BO_W1 + wg * 4096 + ((lane >> 4) * 8 + (lane & 7)) * 128 + (((warp * 2 + ((lane >> 3) & 1)) ^ (lane & 7)) << 4);
#pragma unroll
      for (int i = 0; i < 80; i++) cs[i & 1] += bf_lo(W[i]) + bf_hi(W[i]);
#pragma unroll 1
      for (int i = 0; i < 40; i++) {
        uint32_t t[4];
        const uint32_t ad = a0 + (i % 20 >> 1) * 8192 + (i & 1) * 2048;
        ldsm4t(t[0], t[1], t[2], t[3], ad);
#pragma unroll
        for (int k = 0; k < 4; k++) {
          if (i < 20) cs[k & 1] += bf_lo(t[k]) + bf_hi(t[k]);
          t[k] = pack2h(bf_lo(t[k]) - cs[k & 1], bf_hi(t[k]) - cs[k & 1]);
        }
        if (i >= 20) stsm4t(ad, t[0], t[1], t[2], t[3]);
        if (i == 19) {
#pragma unroll
          for (int k = 0; k < 2; k++) { cs[k] += __shfl_xor_sync(~0u, cs[k], 1); cs[k] += __shfl_xor_sync(~0u, cs[k], 2); cs[k] *= 1.f / DM; }
        }
      }
      const uint32_t z = dep0(__float_as_uint(cs[0]), lane);
#pragma unroll
      for (int i = 0; i < 80; i++) W[i] = pack2h(bf_lo(W[i] | z) - cs[i & 1], bf_hi(W[i] | z) - cs[i & 1]);
      fence_async();
      bar_sync(NB_H, 256);
    }
    const Dsc blo = {P.desc, 1}, alo = blo + wg * (op ? OP_RES / 16 : 256);
    if (op) {
      Ring rg = {(uint32_t)wg, 0};
      mbar_arrive_if(lane == 0, bar + 8 * BB_START);
      if (wg) bar_arrive(NB_PP, 256);
      const Dsc xlo = blo + (j + 1) / 5 * 2;
#pragma unroll 1
      for (int r = 0; r < NSTEP; r++) {
        asm volatile("" : "+r"(lane));
        if (fmask(r) == 3) op_round<64>(W, bar, alo, blo, xlo, j == 0, rg, wg, warp, lane, r);
        else op_round<32>(W, bar, alo, blo, xlo, j == 0, rg, wg, warp, lane, r);
        if (warp == 0) BTS(r, 2 + wg);
      }
    } else {
      const int q4 = (128 * j + 64 * wg + 16 * warp) / 160, off = w12 ? (0x0413 >> (4 * q4)) & 7 : 0;
#pragma unroll 1
      for (int r = 0; r < NR; r++) {
        asm volatile("" : "+r"(lane));
        const int bm = bmask(r), fm = w12 ? fmask(r) : bm;
        if (fm == 3) phase1<64>(W, sb, alo, blo, 0, wg, warp, lane, off, r);
        else if (fm) phase1<32>(W, sb, alo, blo + (fm >> 1) * 256, fm >> 1, wg, warp, lane, off, r);
        else { mbar_waitu(bar + 8 * (BB_SFREE + 4 + wg), (r + 1) & 1); carry_in(sb, wg, warp, lane); }
        CTS(33);
        fence_async();
        bar_sync(NB_H, 256);
        if (wg + warp == 0) BTS(r, 1);
        if (bm == 3) phase2<64>(W, bar, alo, blo, wg, warp, lane, r);
        else phase2<32>(W, bar, alo, blo + (bm >> 1) * 256, wg, warp, lane, r);
        if (warp == 0) BTS(r, 2 + wg);
      }
    }
    CTS_OUT();
    bar_arrive(NB_END, 512);
  }
}

typedef CUresult (*EncodeFn)(CUtensorMap*, CUtensorMapDataType, cuuint32_t, void*, const cuuint64_t*, const cuuint64_t*, const cuuint32_t*,
                             const cuuint32_t*, CUtensorMapInterleave, CUtensorMapSwizzle, CUtensorMapL2promotion, CUtensorMapFloatOOBfill);
static void make_map(EncodeFn fn, CUtensorMap* tm, const void* ptr, uint64_t cols, uint64_t rows, uint32_t bc, uint32_t br) {
  cuuint64_t dims[2] = {cols, rows}; cuuint64_t strides[1] = {cols * 2}; cuuint32_t box[2] = {bc, br}; cuuint32_t es[2] = {1, 1};
  fn(tm, CU_TENSOR_MAP_DATA_TYPE_BFLOAT16, 2, const_cast<void*>(ptr), dims, strides, box, es, CU_TENSOR_MAP_INTERLEAVE_NONE,
     CU_TENSOR_MAP_SWIZZLE_128B, CU_TENSOR_MAP_L2_PROMOTION_L2_256B, CU_TENSOR_MAP_FLOAT_OOB_FILL_NONE);
}
#define dbg_a_only 0
extern "C" void kernel_launch(void* const* d_in, const int* in_sizes, int n_in, void* d_out, int out_size) {
  void* fnp = nullptr; cudaDriverEntryPointQueryResult qr;
  cudaGetDriverEntryPoint("cuTensorMapEncodeTiled", &fnp, cudaEnableDefault, &qr);
  EncodeFn fn = (EncodeFn)fnp;
  cudaStream_t st = cudaStreamPerThread;
  cudaFuncSetAttribute(bworker_kernel, cudaFuncAttributeMaxDynamicSharedMemorySize, B_SMEM);
  {
    AMaps M;
    for (int i = 0; i < 3; i++) make_map(fn, &M.w16[i], d_in[2 + i], HD, DM, 64, 16);
    make_map(fn, &M.wo32, d_in[5], DM, HD, 64, 32);
    const uint32_t hi[5] = {dhi(TILE_SBO, 3), dhi(1024, 1), dhi(1024, 0), dhi(PL_SZ, 0), dhi(896, 0)};
    for (int i = 0; i < 5; i++) M.d[i] = (uint64_t)hi[i] << 32;
    cudaFuncSetAttribute(acore_kernel, cudaFuncAttributeMaxDynamicSharedMemorySize, A_SMEM);
    cudaFuncSetAttribute(acore_kernel, cudaFuncAttributeNonPortableClusterSizeAllowed, 1);
    cudaLaunchConfig_t cfg = {};
    cfg.gridDim = dim3(CL_SIZE * NCL); cfg.blockDim = dim3(512); cfg.dynamicSmemBytes = A_SMEM; cfg.stream = st;
    cudaLaunchAttribute at[1]; at[0].id = cudaLaunchAttributeClusterDimension;
    at[0].val.clusterDim.x = CL_SIZE; at[0].val.clusterDim.y = 1; at[0].val.clusterDim.z = 1;
    cfg.attrs = at; cfg.numAttrs = 1;
    cudaLaunchKernelEx(&cfg, acore_kernel, M, (const __nv_bfloat16*)d_in[1], dbg_a_only ? 0 : 1);
  }
  if (!dbg_a_only) {
    BParams P;
    make_map(fn, &P.wmap[0], d_in[5], DM, HD, 64, 32);
    make_map(fn, &P.wo16, d_in[5], DM, HD, 64, 16);
    make_map(fn, &P.wmap[1], d_in[8], DM, DM, 64, 32);
    make_map(fn, &P.wmap[2], d_in[9], DM, DM, 64, 32);
    make_map(fn, &P.wmap[3], d_in[10], FF, DM, 64, 32);
    make_map(fn, &P.wmap[4], d_in[11], DM, FF, 64, 32);
    P.x = (const __nv_bfloat16*)d_in[0];
    P.out = (__nv_bfloat16*)d_out;
    P.desc = (uint64_t)dhi(1024, 1) << 32;
    cudaLaunchConfig_t cfg = {};
    cfg.gridDim = dim3(NBC); cfg.blockDim = dim3(512); cfg.dynamicSmemBytes = B_SMEM; cfg.stream = st;
    cudaLaunchAttribute at[1]; at[0].id = cudaLaunchAttributeProgrammaticStreamSerialization; at[0].val.programmaticStreamSerializationAllowed = 1;
    cfg.attrs = at; cfg.numAttrs = 1;
    cudaLaunchKernelEx(&cfg, bworker_kernel, P);
  }
}
```

```cpp
#include <cuda_runtime.h>
#include <cuda_bf16.h>
#include <cuda.h>
#include <stdint.h>

#define S_LEN 2048
#define DM 640
#define NH 32
#define DH 192
#define HD 6144
#define NSEG 64
#define FF 1536

__device__ __forceinline__ uint32_t smem_u32(const void* p) { return (uint32_t)__cvta_generic_to_shared(p); }
__device__ __forceinline__ uint32_t mapa(uint32_t a, uint32_t r) {
  uint32_t o; asm volatile("mapa.shared::cluster.u32 %0, %1, %2;" : "=r"(o) : "r"(a), "r"(r)); return o; }
__device__ __forceinline__ void mbar_init(uint32_t b, uint32_t c) {
  asm volatile("mbarrier.init.shared::cta.b64 [%0], %1;" :: "r"(b), "r"(c) : "memory"); }
__device__ __forceinline__ void mbar_expect(uint32_t b, uint32_t tx) {
  asm volatile("mbarrier.arrive.expect_tx.shared::cta.b64 _, [%0], %1;" :: "r"(b), "r"(tx) : "memory"); }
__device__ __forceinline__ void mbar_arrive(uint32_t b) {
  asm volatile("mbarrier.arrive.shared::cta.b64 _, [%0];" :: "r"(b) : "memory"); }
__device__ __forceinline__ void mbar_arrive_remote(uint32_t rb) {
  asm volatile("mbarrier.arrive.relaxed.cluster.shared::cluster.b64 _, [%0];" :: "r"(rb) : "memory"); }
__device__ __forceinline__ void mbar_expect_if(bool p, uint32_t b, uint32_t tx) {
  asm volatile("{\n.reg .pred q;\nsetp.ne.u32 q, %2, 0;\n@q mbarrier.arrive.expect_tx.shared::cta.b64 _, [%0], %1;\n}" :: "r"(b), "r"(tx), "r"((uint32_t)p) : "memory"); }
__device__ __forceinline__ void mbar_arrive_if(bool p, uint32_t b) {
  asm volatile("{\n.reg .pred q;\nsetp.ne.u32 q, %1, 0;\n@q mbarrier.arrive.shared::cta.b64 _, [%0];\n}" :: "r"(b), "r"((uint32_t)p) : "memory"); }
__device__ __forceinline__ void mbar_arrive_remote_if(bool p, uint32_t rb) {
  asm volatile("{\n.reg .pred q;\nsetp.ne.u32 q, %1, 0;\n@q mbarrier.arrive.relaxed.cluster.shared::cluster.b64 _, [%0];\n}" :: "r"(rb), "r"((uint32_t)p) : "memory"); }
__device__ __forceinline__ void sts32_if(bool p, uint32_t a, uint32_t v) {
  asm volatile("{\n.reg .pred q;\nsetp.ne.u32 q, %2, 0;\n@q st.shared.b32 [%0], %1;\n}" :: "r"(a), "r"(v), "r"((uint32_t)p) : "memory"); }
__device__ __forceinline__ void sts128z_if(bool p, uint32_t a) {
  asm volatile("{\n.reg .pred q;\nsetp.ne.u32 q, %1, 0;\n@q st.shared.v4.b32 [%0], {0,0,0,0};\n}" :: "r"(a), "r"((uint32_t)p) : "memory"); }
__device__ __forceinline__ bool mbar_try(uint32_t b, uint32_t ph) {
  uint32_t ok;
  asm volatile("{\n.reg .pred p;\nmbarrier.try_wait.parity.shared::cta.b64 p, [%1], %2;\nselp.u32 %0, 1, 0, p;\n}"
               : "=r"(ok) : "r"(b), "r"(ph) : "memory");
  return ok; }
__device__ __forceinline__ bool mbar_test(uint32_t b, uint32_t ph) {
  uint32_t ok;
  asm volatile("{\n.reg .pred p;\nmbarrier.test_wait.parity.shared::cta.b64 p, [%1], %2;\nselp.u32 %0, 1, 0, p;\n}"
               : "=r"(ok) : "r"(b), "r"(ph) : "memory");
  return ok; }
#define SPIN_LIMIT 4000000
#define FAIL() asm volatile("st.global.u32 [%0], 0;" :: "l"(8ull) : "memory")
#define CFENCE() asm volatile("fence.proxy.async::generic.acquire.sync_restrict::shared::cluster.cluster;" ::: "memory")
__device__ __forceinline__ void mbar_wait(uint32_t b, uint32_t ph) {
  int n = 0;
  while (!mbar_try(b, ph)) { if (++n > SPIN_LIMIT) FAIL(); } }
#define TIMEOUT_ACT "@!p st.shared.u32 [%0+1], 0;"
#define WAIT_HINT ", 20000"
#define WAIT_LIM "200000"
__device__ __forceinline__ void mbar_slow(uint32_t b, uint32_t ph) {
  asm volatile("{\n.reg .pred p, q;\n.reg .u32 n;\nmov.u32 n, 0;\n"
               "WL:\nmbarrier.try_wait.parity.shared::cta.b64 p, [%0], %1" WAIT_HINT ";\nadd.u32 n, n, 1;\nsetp.lt.and.u32 q, n, " WAIT_LIM ", !p;\n@q bra.uni WL;\n"
               TIMEOUT_ACT "\n}" :: "r"(b), "r"(ph) : "memory"); }
__device__ __forceinline__ void mbar_waitw(uint32_t b, uint32_t ph) {
  asm volatile("{\n.reg .pred p, q;\n.reg .u32 n;\nmbarrier.try_wait.parity.shared::cta.b64 p, [%0], %1;\n@p bra.uni WD;\nmov.u32 n, 0;\n"
               "WL:\nmbarrier.try_wait.parity.shared::cta.b64 p, [%0], %1" WAIT_HINT ";\nadd.u32 n, n, 1;\nsetp.lt.and.u32 q, n, " WAIT_LIM ", !p;\n@q bra.uni WL;\n"
               TIMEOUT_ACT "\nWD:\n}" :: "r"(b), "r"(ph) : "memory"); }
__device__ __forceinline__ void mbar_waitw2(uint32_t b0, uint32_t b1, uint32_t ph) {
  uint32_t ok;
  asm volatile("{\n.reg .pred p, r;\nmbarrier.try_wait.parity.shared::cta.b64 p, [%1], %3;\nmbarrier.try_wait.parity.shared::cta.b64 r, [%2], %3;\n"
               "and.pred p, p, r;\nselp.u32 %0, 1, 0, p;\n}" : "=r"(ok) : "r"(b0), "r"(b1), "r"(ph) : "memory");
  if (__builtin_expect(!__all_sync(~0u, ok), 0)) { mbar_slow(b0, ph); mbar_slow(b1, ph); }
}
__device__ __forceinline__ void mbar_waitu(uint32_t b, uint32_t ph) {
  asm volatile("{\n.reg .pred p;\nmbarrier.try_wait.parity.shared::cta.b64 p, [%0], %1;\n@p bra.uni WD;\n"
               "WL:\nmbarrier.try_wait.parity.shared::cta.b64 p, [%0], %1" WAIT_HINT ";\n@!p bra.uni WL;\nWD:\n}" :: "r"(b), "r"(ph) : "memory"); }
__device__ __forceinline__ void mbar_waitu2(uint32_t b0, uint32_t b1, uint32_t ph) {
  asm volatile("{\n.reg .pred p, r;\nWL:\nmbarrier.try_wait.parity.shared::cta.b64 p, [%0], %2;\nmbarrier.try_wait.parity.shared::cta.b64 r, [%1], %2;\n"
               "and.pred p, p, r;\n@!p bra.uni WL;\n}" :: "r"(b0), "r"(b1), "r"(ph) : "memory"); }
__device__ __forceinline__ void mbar_waitw4(uint32_t b, uint32_t ph) { mbar_waitw2(b, b + 8, ph); mbar_waitw2(b + 16, b + 24, ph); }
__device__ __forceinline__ uint32_t clock32() { uint32_t t; asm volatile("mov.u32 %0, %%clock;" : "=r"(t) :: "memory"); return t; }
template <int L> __device__ __forceinline__ uint32_t lop3(uint32_t a, uint32_t b, uint32_t c) {
  uint32_t r; asm("lop3.b32 %0, %1, %2, %3, %4;" : "=r"(r) : "r"(a), "r"(b), "r"(c), "n"(L)); return r; }
__device__ __forceinline__ void st_async_v2_if(bool p, uint32_t a, uint32_t v0, uint32_t v1, uint32_t mb) {
  asm volatile("{\n.reg .pred q;\nsetp.ne.u32 q, %4, 0;\n@q st.async.weak.shared::cluster.mbarrier::complete_tx::bytes.v2.b32 [%0], {%1,%2}, [%3];\n}"
               :: "r"(a), "r"(v0), "r"(v1), "r"(mb), "r"((uint32_t)p) : "memory"); }
__device__ __forceinline__ void keep4(const uint32_t* r, int lane) {
  asm volatile("{\n.reg .pred q;\nsetp.lt.s32 q, %4, 0;\n@q st.shared.v4.b32 [%4], {%0,%1,%2,%3};\n}" :: "r"(r[0]), "r"(r[1]), "r"(r[2]), "r"(r[3]), "r"(lane) : "memory"); }
__device__ __forceinline__ uint32_t uni(uint32_t x) { return __shfl_sync(~0u, x, 0); }
__device__ __forceinline__ void bulk_g2s_mc_e(uint32_t dst, const void* src, uint32_t bytes, uint32_t mb, uint16_t mask) {
  asm volatile("{\n.reg .pred e;\nelect.sync _|e, 0xffffffff;\n"
               "@e cp.async.bulk.shared::cluster.global.mbarrier::complete_tx::bytes.multicast::cluster [%0], [%1], %2, [%3], %4;\n}"
               :: "r"(dst), "l"(src), "r"(bytes), "r"(mb), "h"(mask) : "memory"); }
__device__ __forceinline__ void bulk_s2g_e(void* dst, uint32_t src, uint32_t bytes) {
  asm volatile("{\n.reg .pred e;\nelect.sync _|e, 0xffffffff;\n@e cp.async.bulk.global.shared::cta.bulk_group [%0], [%1], %2;\n}"
               :: "l"(dst), "r"(src), "r"(bytes) : "memory"); }
__device__ __forceinline__ void bulk_g2s_e(uint32_t dst, const void* src, uint32_t bytes, uint32_t mb) {
  asm volatile("{\n.reg .pred e;\nelect.sync _|e, 0xffffffff;\n@e cp.async.bulk.shared::cluster.global.mbarrier::complete_tx::bytes [%0], [%1], %2, [%3];\n}"
               :: "r"(dst), "l"(src), "r"(bytes), "r"(mb) : "memory"); }
#define STREAM_HINT 1
__device__ __forceinline__ void bulk_s2g_es(void* dst, uint32_t src, uint32_t bytes) {
  asm volatile("{\n.reg .pred e;\n.reg .b64 pol;\ncreatepolicy.fractional.L2::evict_first.b64 pol;\nelect.sync _|e, 0xffffffff;\n"
               "@e cp.async.bulk.global.shared::cta.bulk_group.L2::cache_hint [%0], [%1], %2, pol;\n}" :: "l"(dst), "r"(src), "r"(bytes) : "memory");
}
__device__ __forceinline__ void bulk_g2s_es(uint32_t dst, const void* src, uint32_t bytes, uint32_t mb) {
  asm volatile("{\n.reg .pred e;\n.reg .b64 pol;\ncreatepolicy.fractional.L2::evict_first.b64 pol;\nelect.sync _|e, 0xffffffff;\n"
               "@e cp.async.bulk.shared::cluster.global.mbarrier::complete_tx::bytes.L2::cache_hint [%0], [%1], %2, [%3], pol;\n}"
               :: "r"(dst), "l"(src), "r"(bytes), "r"(mb) : "memory"); }
__device__ __forceinline__ void tma2d_e(uint32_t dst, const CUtensorMap* tm, int c0, int c1, uint32_t mb) {
  asm volatile("{\n.reg .pred e;\nelect.sync _|e, 0xffffffff;\n"
               "@e cp.async.bulk.tensor.2d.shared::cluster.global.mbarrier::complete_tx::bytes [%0], [%1, {%3, %4}], [%2];\n}"
               :: "r"(dst), "l"((uint64_t)tm), "r"(mb), "r"(c0), "r"(c1) : "memory"); }
__device__ __forceinline__ uint32_t hadd2bf(uint32_t a, uint32_t b) {
  uint32_t r; asm("add.rn.bf16x2 %0, %1, %2;" : "=r"(r) : "r"(a), "r"(b)); return r; }
__device__ __forceinline__ void cluster_sync_all() {
  asm volatile("barrier.cluster.arrive.release.aligned;\nbarrier.cluster.wait.acquire.aligned;" ::: "memory"); }
__device__ __forceinline__ void bar_arrive(int id, int n) { asm volatile("bar.arrive %0, %1;" :: "r"(id), "r"(n) : "memory"); }
__device__ __forceinline__ void bar_arrive_dep(int id, int n, uint32_t dep) {
  asm volatile("{\n.reg .u32 t;\nand.b32 t, %2, 0;\nadd.u32 t, t, %0;\nbar.sync t, %1;\n}" :: "r"(id), "r"(n), "r"(dep) : "memory"); }
__device__ __forceinline__ void bar_sync(int id, int n) { asm volatile("bar.sync %0, %1;" :: "r"(id), "r"(n) : "memory"); }
__device__ __forceinline__ void fence_async() { asm volatile("fence.proxy.async.shared::cta;" ::: "memory"); }
__device__ __forceinline__ void st_async_b32(uint32_t a, uint32_t v, uint32_t mb) {
  asm volatile("st.async.weak.shared::cluster.mbarrier::complete_tx::bytes.b32 [%0], %1, [%2];" :: "r"(a), "r"(v), "r"(mb) : "memory"); }
__device__ __forceinline__ void st_async_v2(uint32_t a, uint32_t v0, uint32_t v1, uint32_t mb) {
  asm volatile("st.async.weak.shared::cluster.mbarrier::complete_tx::bytes.v2.b32 [%0], {%1,%2}, [%3];" :: "r"(a), "r"(v0), "r"(v1), "r"(mb) : "memory"); }
__device__ __forceinline__ void st_async_v4(uint32_t a, uint32_t v0, uint32_t v1, uint32_t v2, uint32_t v3, uint32_t mb) {
  asm volatile("st.async.weak.shared::cluster.mbarrier::complete_tx::bytes.v4.b32 [%0], {%1,%2,%3,%4}, [%5];" :: "r"(a), "r"(v0), "r"(v1), "r"(v2), "r"(v3), "r"(mb) : "memory"); }
__device__ __forceinline__ void ldsm4(uint32_t& r0, uint32_t& r1, uint32_t& r2, uint32_t& r3, uint32_t a) {
  asm volatile("ldmatrix.sync.aligned.m8n8.x4.shared.b16 {%0,%1,%2,%3}, [%4];" : "=r"(r0), "=r"(r1), "=r"(r2), "=r"(r3) : "r"(a) : "memory"); }
__device__ __forceinline__ void ldsm4t(uint32_t& r0, uint32_t& r1, uint32_t& r2, uint32_t& r3, uint32_t a) {
  asm volatile("ldmatrix.sync.aligned.m8n8.x4.trans.shared.b16 {%0,%1,%2,%3}, [%4];" : "=r"(r0), "=r"(r1), "=r"(r2), "=r"(r3) : "r"(a) : "memory"); }
__device__ __forceinline__ void stsm2t(uint32_t a, uint32_t r0, uint32_t r1) {
  asm volatile("stmatrix.sync.aligned.m8n8.x2.trans.shared.b16 [%0], {%1,%2};" :: "r"(a), "r"(r0), "r"(r1) : "memory"); }
__device__ __forceinline__ void stsm4t(uint32_t a, uint32_t r0, uint32_t r1, uint32_t r2, uint32_t r3) {
  asm volatile("stmatrix.sync.aligned.m8n8.x4.trans.shared.b16 [%0], {%1,%2,%3,%4};" :: "r"(a), "r"(r0), "r"(r1), "r"(r2), "r"(r3) : "memory"); }
__device__ __forceinline__ uint32_t movm(uint32_t a) {
  uint32_t d; asm volatile("movmatrix.sync.aligned.m8n8.trans.b16 %0, %1;" : "=r"(d) : "r"(a)); return d; }
__device__ __forceinline__ void mma16816(float* d, uint32_t a0, uint32_t a1, uint32_t a2, uint32_t a3, uint32_t b0, uint32_t b1) {
  asm("mma.sync.aligned.m16n8k16.row.col.f32.bf16.bf16.f32 {%0,%1,%2,%3}, {%4,%5,%6,%7}, {%8,%9}, {%0,%1,%2,%3};"
               : "+f"(d[0]), "+f"(d[1]), "+f"(d[2]), "+f"(d[3]) : "r"(a0), "r"(a1), "r"(a2), "r"(a3), "r"(b0), "r"(b1)); }
__device__ __forceinline__ void mma16816v(float* d, uint32_t a0, uint32_t a1, uint32_t a2, uint32_t a3, uint32_t b0, uint32_t b1) {
  asm volatile("mma.sync.aligned.m16n8k16.row.col.f32.bf16.bf16.f32 {%0,%1,%2,%3}, {%4,%5,%6,%7}, {%8,%9}, {%0,%1,%2,%3};"
               : "+f"(d[0]), "+f"(d[1]), "+f"(d[2]), "+f"(d[3]) : "r"(a0), "r"(a1), "r"(a2), "r"(a3), "r"(b0), "r"(b1)); }
__device__ __forceinline__ uint32_t pack2(float lo, float hi) {
  uint32_t r; asm("cvt.rn.bf16x2.f32 %0, %1, %2;" : "=r"(r) : "f"(hi), "f"(lo)); return r; }
__device__ __forceinline__ uint32_t pack2v(float lo, float hi) {
  uint32_t r; asm volatile("cvt.rn.bf16x2.f32 %0, %1, %2;" : "=r"(r) : "f"(hi), "f"(lo)); return r; }
__device__ __forceinline__ float bf_lo(uint32_t w) { return __uint_as_float(w << 16); }
__device__ __forceinline__ float bf_hi(uint32_t w) { return __uint_as_float(w & 0xffff0000u); }
__device__ __forceinline__ uint4 lds128(uint32_t a) {
  uint4 v; asm volatile("ld.shared.v4.b32 {%0,%1,%2,%3}, [%4];" : "=r"(v.x), "=r"(v.y), "=r"(v.z), "=r"(v.w) : "r"(a) : "memory"); return v; }
__device__ __forceinline__ uint4 lds128_nv(uint32_t a) {
  uint4 v; asm volatile("ld.shared.v4.b32 {%0,%1,%2,%3}, [%4];" : "=r"(v.x), "=r"(v.y), "=r"(v.z), "=r"(v.w) : "r"(a)); return v; }
__device__ __forceinline__ void st_async_v2_nm(uint32_t a, uint32_t v0, uint32_t v1, uint32_t mb) {
  asm volatile("st.async.weak.shared::cluster.mbarrier::complete_tx::bytes.v2.b32 [%0], {%1,%2}, [%3];" :: "r"(a), "r"(v0), "r"(v1), "r"(mb)); }
__device__ __forceinline__ float rcpf(float x) { float y; asm("rcp.approx.ftz.f32 %0, %1;" : "=f"(y) : "f"(x)); return y; }
__device__ __forceinline__ void sts64(uint32_t a, uint32_t x, uint32_t y) { asm volatile("st.shared.v2.b32 [%0], {%1,%2};" :: "r"(a), "r"(x), "r"(y) : "memory"); }
__device__ __forceinline__ float ex2(float x) { float y; asm("ex2.approx.ftz.f32 %0, %1;" : "=f"(y) : "f"(x)); return y; }
__device__ __forceinline__ uint32_t lds32(uint32_t a) {
  uint32_t v; asm volatile("ld.shared.b32 %0, [%1];" : "=r"(v) : "r"(a) : "memory"); return v; }
__device__ __forceinline__ uint2 lds64(uint32_t a) {
  uint2 v; asm volatile("ld.shared.v2.b32 {%0,%1}, [%2];" : "=r"(v.x), "=r"(v.y) : "r"(a) : "memory"); return v; }
__device__ __forceinline__ void sts128(uint32_t a, uint32_t x, uint32_t y, uint32_t z, uint32_t w) {
  asm volatile("st.shared.v4.b32 [%0], {%1,%2,%3,%4};" :: "r"(a), "r"(x), "r"(y), "r"(z), "r"(w) : "memory"); }
__device__ __forceinline__ void sts32(uint32_t a, uint32_t x) { asm volatile("st.shared.b32 [%0], %1;" :: "r"(a), "r"(x) : "memory"); }
__device__ __forceinline__ void tma2d(uint32_t dst, const CUtensorMap* tm, int c0, int c1, uint32_t mb) {
  asm volatile("cp.async.bulk.tensor.2d.shared::cluster.global.mbarrier::complete_tx::bytes [%0], [%1, {%3, %4}], [%2];"
               :: "r"(dst), "l"((uint64_t)tm), "r"(mb), "r"(c0), "r"(c1) : "memory"); }
__device__ __forceinline__ void tma2d_prefetch(const CUtensorMap* tm, int c0, int c1) {
  asm volatile("cp.async.bulk.prefetch.tensor.2d.L2.global.tile [%0, {%1, %2}];" :: "l"((uint64_t)tm), "r"(c0), "r"(c1) : "memory"); }
__device__ __forceinline__ void bulk_g2s_mc(uint32_t dst, const void* src, uint32_t bytes, uint32_t mb, uint16_t mask) {
  asm volatile("cp.async.bulk.shared::cluster.global.mbarrier::complete_tx::bytes.multicast::cluster [%0], [%1], %2, [%3], %4;"
               :: "r"(dst), "l"(src), "r"(bytes), "r"(mb), "h"(mask) : "memory"); }
__device__ __forceinline__ void bulk_s2g(void* dst, uint32_t src, uint32_t bytes) {
  asm volatile("cp.async.bulk.global.shared::cta.bulk_group [%0], [%1], %2;" :: "l"(dst), "r"(src), "r"(bytes) : "memory"); }
__device__ __forceinline__ void wg_fence() { asm volatile("wgmma.fence.sync.aligned;" ::: "memory"); }
__device__ __forceinline__ void wg_commit() { asm volatile("wgmma.commit_group.sync.aligned;" ::: "memory"); }
template <int N> __device__ __forceinline__ void wg_wait() { asm volatile("wgmma.wait_group.sync.aligned %0;" :: "n"(N) : "memory"); }
__device__ __forceinline__ uint64_t mkdesc(uint32_t addr, uint32_t lbo, uint32_t sbo, uint32_t swz) {
  return (uint64_t)((addr & 0x3FFFF) >> 4) | ((uint64_t)(lbo >> 4) << 16) | ((uint64_t)(sbo >> 4) << 32) | ((uint64_t)swz << 62); }

#define ACC4(d) "+f"(d[0]),"+f"(d[1]),"+f"(d[2]),"+f"(d[3])
#define ACC8(d) ACC4(d), ACC4((d + 4))
#define ACC16(d) ACC8(d), ACC8((d + 8))
#define ACC20(d) ACC16(d), ACC4((d + 16))
#define ACC24(d) ACC16(d), ACC8((d + 16))
#define SMEM0 0x400
__host__ __device__ constexpr uint32_t dlo(uint32_t off, uint32_t lbo) { return ((SMEM0 + off) >> 4) | ((lbo >> 4) << 16); }
__host__ __device__ constexpr uint32_t dhi(uint32_t sbo, uint32_t swz) { return (sbo >> 4) | (swz << 30); }
#define R4S "{%0,%1,%2,%3}"
#define R8S "{%0,%1,%2,%3,%4,%5,%6,%7}"
#define R16S "{%0,%1,%2,%3,%4,%5,%6,%7,%8,%9,%10,%11,%12,%13,%14,%15}"
#define R20S "{%0,%1,%2,%3,%4,%5,%6,%7,%8,%9,%10,%11,%12,%13,%14,%15,%16,%17,%18,%19}"
#define R24S "{%0,%1,%2,%3,%4,%5,%6,%7,%8,%9,%10,%11,%12,%13,%14,%15,%16,%17,%18,%19,%20,%21,%22,%23}"
#define ACC32(d) ACC16(d), ACC16((d + 16))
#define R32S "{%0,%1,%2,%3,%4,%5,%6,%7,%8,%9,%10,%11,%12,%13,%14,%15,%16,%17,%18,%19,%20,%21,%22,%23,%24,%25,%26,%27,%28,%29,%30,%31}"
struct Dsc {
  uint64_t b; uint32_t e;
  __device__ __forceinline__ Dsc operator+(uint32_t o) const { return {b + o, e}; }
};
template <int K> __device__ __forceinline__ uint32_t fresh(int i) {
  uint32_t e; asm volatile("{\n.reg .u32 t;\nadd.u32 t, %1, %2;\nshr.u32 %0, t, %3;\n}" : "=r"(e) : "r"(i), "n"((256 << K) + 1), "n"(8 + K)); return e; }
template <int N, bool H = false> struct MM;
#define DEF_MM(N, H, T, ACCM, RS_, I0, I1, I2, I3, I4, I5, I6, I7)                                                                \
  template <> struct MM<N, H> {                                                                                                   \
    template <uint32_t BLO, int ACC>                                                                                              \
    static __device__ __forceinline__ void rs(float* d, const uint32_t* a, Dsc b0) {                                              \
      asm volatile("{\n.reg .b64 b;\nmad.wide.u32 b, %" #I7 ", %" #I5 ", %" #I4 ";\n"                                             \
                   "wgmma.mma_async.sync.aligned.m64n" #N "k16.f32." T "." T " " RS_ ", {%" #I0 ",%" #I1 ",%" #I2 ",%" #I3 "}, b, %" #I6 ", 1, 1, 0;\n}" \
                   : ACCM(d) : "r"(a[0]), "r"(a[1]), "r"(a[2]), "r"(a[3]), "l"(b0.b), "n"(BLO), "n"(ACC), "r"(b0.e)); }           \
    template <uint32_t ALO, uint32_t BLO, int ACC, int TA = 1>                                                                    \
    static __device__ __forceinline__ void ss(float* d, Dsc a0, Dsc b0) {                                                         \
      asm volatile("{\n.reg .b64 a, b;\nmad.wide.u32 a, %" #I6 ", %" #I1 ", %" #I0 ";\nmad.wide.u32 b, %" #I6 ", %" #I3 ", %" #I2 ";\n" \
                   "wgmma.mma_async.sync.aligned.m64n" #N "k16.f32." T "." T " " RS_ ", a, b, %" #I4 ", 1, 1, %" #I5 ", 0;\n}"    \
                   : ACCM(d) : "l"(a0.b), "n"(ALO), "l"(b0.b), "n"(BLO), "n"(ACC), "n"(TA), "r"(b0.e)); }                         \
  };
DEF_MM(8, false, "bf16", ACC4, R4S, 4, 5, 6, 7, 8, 9, 10, 11)
DEF_MM(16, false, "bf16", ACC8, R8S, 8, 9, 10, 11, 12, 13, 14, 15)
DEF_MM(32, false, "bf16", ACC16, R16S, 16, 17, 18, 19, 20, 21, 22, 23)
DEF_MM(40, false, "bf16", ACC20, R20S, 20, 21, 22, 23, 24, 25, 26, 27)
DEF_MM(48, false, "bf16", ACC24, R24S, 24, 25, 26, 27, 28, 29, 30, 31)
DEF_MM(64, false, "bf16", ACC32, R32S, 32, 33, 34, 35, 36, 37, 38, 39)
DEF_MM(32, true, "f16", ACC16, R16S, 16, 17, 18, 19, 20, 21, 22, 23)
DEF_MM(64, true, "f16", ACC32, R32S, 32, 33, 34, 35, 36, 37, 38, 39)

#define LAG 10
#define NSTEP (NSEG + LAG)
#define NR (NSTEP + 1)
__device__ __align__(1024) __nv_bfloat16 g_xn[2][S_LEN * DM];
#define RO 16
static_assert(RO > LAG + 1, "ring");
__device__ __align__(1024) unsigned char g_o[RO * 96 * 8192];
__device__ __align__(1024) uint32_t g_part[6][7][40][64];
#define RD 16
#define TILE_B 81920
__device__ __align__(1024) float2 g_stat[S_LEN];
__device__ __align__(1024) uint32_t g_st2[2][RD][64];
__device__ __align__(1024) unsigned char g_acc[5][RD][TILE_B];
#define NOP 19
#define NW12 5
#define NW34 12
#define NBC (NOP + NW12 + NW34)
__device__ __align__(1024) unsigned char g_wt[NOP * 10 * 12288];
enum { F_O = 0, F_R1 = NOP + 1, F_R2 = F_R1 + 4, F_R3 = F_R2 + 4, F_Z = F_R3 + 4, F_DONE, F_MISC, F_NUM };
__device__ __align__(128) uint32_t g_f[F_NUM][96];
__device__ __align__(128) int g_xready[129][8];
__device__ uint32_t g_tpc[128];
#define TS(i)
#define TSV(i, v)
#define TSN(i)
#define TSD(i, dep)
#define BTS(k, i)
#define BTS2(k, i)
#define RTS(i)
#define RTSD(i, dep)
#define RTS_OUT()
#define CTS(i)
#define PTS(i)
#define PTS1(i)
#define CTS_OUT()
#define GTS(i)

#define CL_SIZE 15
#define NCL 7
#define SSQ 13
#define SSV 16
#define PL_SZ 5376
#define TILE_SBO 2560
#define TILE_GRP 15360
#define WS_SZ ((2 * SSQ + SSV) * 2048)
#define OFF_QK (OFF_WO + 26 * 2048)
#define LAYOUT 2
#define OFF_TILE 0
#define OFF_WS (4 * TILE_GRP)
#define OFF_WO (OFF_WS + WS_SZ)
#define OFF_PL (OFF_QK + 20480)
#define OFF_BAR (OFF_PL + 2 * PL_SZ)
#define STG_Q OFF_TILE
#define STG_K OFF_WO
#define VA 14
#define STG_V2 (OFF_TILE + 27 * 2048)
#define OFF_O (OFF_PL + 4352)
#define LAND(k) (((k) >> 1) * TILE_GRP + ((k) & 1) * 1280)
#define LAND_F (5 * TILE_SBO)
#define OFF_XL (OFF_TILE + 3 * TILE_GRP)
#define OFF_XF (OFF_XL + LAND_F)
#define OFF_WT ((OFF_XL + TILE_SBO + 1023) & ~1023)
#define OFF_TAB (OFF_BAR + 240)
#define OFF_INV (OFF_TAB + 64)
#define OFF_TS (OFF_INV + 128)
#define A_SMEM 232448
static_assert(WS_SZ + 72 * 1024 + 2 * PL_SZ + 4 * TILE_GRP + 512 == A_SMEM && OFF_WS % 1024 == 0 && OFF_WO % 1024 == 0 && SSQ == 13, "smem map");
enum { B_W0 = 0, B_W1, B_F1, B_F2 = B_F1 + 4, B_R1 = B_F2 + 4, B_R2, B_MEMFREE, B_LANDFREE, B_OPEER, B_PLFREE, B_XFREE, B_SB, B_WOF = B_SB + 6, B_WTF, B_RS, B_NUM = B_RS + 4 };
static_assert(B_NUM <= 30, "barriers");
enum { N_C = 0, N_SISS, N_QK, N_V, N_PM, N_TURN, N_PI, N_VGO, N_O, N_PX, N_AB, N_SDONE, N_VDONE, N_G3, N_P, N_OX };

__device__ __forceinline__ bool is_dual(int j) { return j >= LAG && j < NSEG; }
__device__ __forceinline__ int sched_l(int j) { return j < NSEG ? j : NSEG + j - LAG; }
__device__ __forceinline__ int sched_f(int j) { return NSEG + j - LAG; }
__device__ __forceinline__ void wait_cnt(const int* p, int target) {
  int v, n = 0;
  do {
    asm volatile("ld.relaxed.gpu.global.b32 %0, [%1];" : "=r"(v) : "l"(p) : "memory");
    if (v >= target) break;
    __nanosleep(100);
    if (++n > SPIN_LIMIT) FAIL();
  } while (true);
  asm volatile("fence.acquire.gpu;" ::: "memory");
  asm volatile("fence.proxy.async.global;" ::: "memory");
}
__device__ __forceinline__ void red_release(void* p, uint32_t v) { asm volatile("red.release.gpu.global.add.u32 [%0], %1;" :: "l"(p), "r"(v) : "memory"); }
__device__ __forceinline__ void red_relaxed(void* p, uint32_t v) { asm volatile("red.relaxed.gpu.global.add.u32 [%0], %1;" :: "l"(p), "r"(v) : "memory"); }
#define VMASK 0xa5294a5294ull
__host__ __device__ constexpr int popc40(unsigned long long m) { int c = 0; for (; m; m &= m - 1) c++; return c; }
static_assert(popc40(VMASK) == SSV, "mask");
__host__ __device__ constexpr int ss_idx(int ks, int n) { return n == SSV ? popc40(VMASK & ((1ull << ks) - 1)) : ks * n / 40; }
__host__ __device__ constexpr bool is_ss(int ks, int n) { return ss_idx(ks + 1, n) != ss_idx(ks, n); }
__host__ __device__ constexpr int rs_idx(int ks, int n) { return ks - ss_idx(ks, n); }

#define SL2 (0.07216878364870322f * 1.4426950408889634f)

#define SUM_LOOP 0
struct Desc { Dsc tile, unit, k1, pl, p; };
__device__ __forceinline__ Desc make_desc(const uint64_t* h, uint32_t u, uint32_t e) {
  return {{h[0], e}, {h[1] + u * 128, e}, {h[2], e}, {h[3], e}, {h[4], e}};
}
template <int N, int NSS, int RG, int KS, int K1, int K0 = 0>
__device__ __forceinline__ void proj(float* acc, const uint32_t* W, const Desc& D) {
  if constexpr (KS < K1) {
    constexpr uint32_t BLO = dlo(OFF_TILE + (KS / 10) * TILE_GRP + RG * TILE_SBO + (KS % 10) * 256, 128);
    if constexpr (is_ss(KS, NSS)) MM<N>::template ss<dlo(OFF_WS + ss_idx(KS, NSS) * 2048, 0), BLO, (KS != K0)>(acc, D.unit, D.tile);
    else MM<N>::template rs<BLO, (KS != K0)>(acc, W + rs_idx(KS, NSS) * 4, D.tile);
    proj<N, NSS, RG, KS + 1, K1, K0>(acc, W, D);
  }
}
#define VST 17
template <int KS>
__device__ __forceinline__ void ld_rest(uint32_t* W, const uint32_t* p) {
  if constexpr (KS < 40) {
    if constexpr (!is_ss(KS, SSV) && rs_idx(KS, SSV) >= VST) {
#pragma unroll
      for (int i = 0; i < 4; i++) W[4 * rs_idx(KS, SSV) + i] = __ldg(p + (KS * 16 + (i >> 1) * 8) * (HD / 2) + (i & 1) * 4);
    }
    ld_rest<KS + 1>(W, p);
  }
}
template <int N>
__device__ __forceinline__ void load_w(uint32_t* W, uint32_t stage, int warp, int lane) {
  const int kr = (lane >> 4) * 8 + (lane & 7);
  const int cb = warp * 2 + ((lane >> 3) & 1);
  const uint32_t a0 = stage + kr * 128 + ((cb ^ (lane & 7)) << 4);
#pragma unroll
  for (int i = 0; i < N; i++) ldsm4t(W[4 * i], W[4 * i + 1], W[4 * i + 2], W[4 * i + 3], a0 + i * 2048);
}
template <int N, int G, int U, int OS, int ACC>
__device__ __forceinline__ void wo4(float* d, const Desc& D) {
  constexpr uint32_t WA = (U >= 4 ? OFF_WO + (U - 4) * 2048 : OFF_WT) - G * SSQ * 2048, OB = OS == 0 ? OFF_O : OS == 1 ? OFF_XL : OFF_XF;
  Dsc b = OS ? D.k1 : D.pl;
  b.e = fresh<(U < 16 ? U / 4 : U / 8 - 2) + (N == 8 ? 4 : 0)>(D.unit.e);
  MM<N>::template ss<dlo(WA, 0), dlo(OB, 128), ACC>(d, D.unit, b);
  MM<N>::template ss<dlo(WA + 2048, 0), dlo(OB + 256, 128), 1>(d, D.unit, b);
  MM<N>::template ss<dlo(WA + 4096, 0), dlo(OB + 512, 128), 1>(d, D.unit, b);
  MM<N>::template ss<dlo(WA + 6144, 0), dlo(OB + 768, 128), 1>(d, D.unit, b);
}
__device__ __forceinline__ void wo_coord(int i, int t3, int head, int& c0, int& c1) {
  const int g = i >> 1;
  const int blk = g == 0 ? 9 : (g < 4 ? g - 1 : (g - 4) >> 1) * 3 + t3;
  int sl = g < 4 ? t3 : (g & 1) ? t3 + 1 : t3 + 2;
  if (sl >= 3) sl -= 3;
  c0 = blk * 64; c1 = head * DH + sl * 64 + (i & 1) * 32;
}
__device__ __forceinline__ void tok_softmax(uint32_t sb, int job, int lane) {
  const bool w1 = job & 1;
  const int dg = (lane >> 2) - (lane & 3) * 2;
  const uint32_t lo = sb + OFF_PL + (job >> 1) * PL_SZ + (job & 1) * 1792, l8 = lo + 512 + lane * 8, pa = lo + lane * 4;
  const uint32_t km = job & 2 ? 640 : 512;
  float x[14];
  {
    const uint4 a = lds128(lo + lane * 16);
    const uint2 e = lds64(l8);
    const uint32_t c = lds32(768 + pa);
    x[0] = bf_lo(a.x); x[1] = bf_hi(a.x); x[2] = bf_lo(a.y); x[3] = bf_hi(a.y); x[4] = bf_lo(a.z); x[5] = bf_hi(a.z); x[6] = bf_lo(a.w); x[7] = bf_hi(a.w);
    x[8] = bf_lo(c); x[9] = bf_hi(c); x[10] = bf_lo(e.x); x[11] = bf_hi(e.x); x[12] = bf_lo(e.y); x[13] = bf_hi(e.y);
  }
  if (dg < 0) { x[8] = -INFINITY; if (w1) x[4] = -INFINITY; else x[10] = -INFINITY; }
  if (dg < 1) { x[9] = -INFINITY; if (w1) x[5] = -INFINITY; else x[11] = -INFINITY; }
  const float m4 = fmaxf(x[8], x[9]);
  float m0 = fmaxf(fmaxf(fmaxf(x[0], x[1]), fmaxf(x[2], x[3])), fmaxf(fmaxf(x[4], x[5]), fmaxf(x[6], x[7])));
  float m1 = fmaxf(fmaxf(x[10], x[11]), fmaxf(x[12], x[13]));
  if (w1) m1 = fmaxf(m1, m4); else m0 = fmaxf(m0, m4);
  m0 = fmaxf(m0, __shfl_xor_sync(~0u, m0, 1)); m1 = fmaxf(m1, __shfl_xor_sync(~0u, m1, 1));
  sts32(pa + (w1 ? 384 : 896 + 128), 0u); sts32(pa + 1152 - km, 0u); sts32(pa + 896 + 1152 - km, 0u); sts64(l8 + 896 - 256, 0u, 0u);
  m0 = fmaxf(m0, __shfl_xor_sync(~0u, m0, 2)); m1 = fmaxf(m1, __shfl_xor_sync(~0u, m1, 2));
  m0 *= -SL2; m1 *= -SL2;
#pragma unroll
  for (int j = 0; j < 14; j++) x[j] = ex2(fmaf(x[j], SL2, j < 8 ? m0 : j >= 10 ? m1 : w1 ? m1 : m0));
  const float l4s = x[8] + x[9];
  float l0 = ((x[0] + x[1]) + (x[2] + x[3])) + ((x[4] + x[5]) + (x[6] + x[7])), l1 = (x[10] + x[11]) + (x[12] + x[13]);
  if (w1) l1 += l4s; else l0 += l4s;
  l0 += __shfl_xor_sync(~0u, l0, 1); l1 += __shfl_xor_sync(~0u, l1, 1);
  l0 += __shfl_xor_sync(~0u, l0, 2); l1 += __shfl_xor_sync(~0u, l1, 2);
  l0 = rcpf(l0); l1 = rcpf(l1);
#pragma unroll
  for (int j = 0; j < 7; j++) {
    const float iv = j < 4 ? l0 : j > 4 ? l1 : w1 ? l1 : l0;
    sts32(pa + (j < 3 ? j * 128 : j == 3 ? km : j == 4 ? (w1 ? 896 + 128 : 384) : j == 5 ? 896 : 896 + km), pack2(x[2 * j] * iv, x[2 * j + 1] * iv));
  }
}
template <int N>
__device__ __forceinline__ void wo_phase(uint32_t sb, int wg, int warp, int lane, uint32_t par, uint32_t r1, const Desc& D) {
  const uint32_t bar = sb + OFF_BAR;
  float x[N / 2], y[N / 2];
  const uint2 ta = lds64(sb + OFF_TAB + (wg * 4 + warp) * 8);
  uint32_t xa = (ta.x & ~255u) + lane * 8, xb = (ta.x & 0xFF0000FFu) + SMEM0 + OFF_BAR, ya = (ta.y & ~255u) + lane * 8, yb = (ta.y & 0xFF0000FFu) + SMEM0 + OFF_BAR;
  asm volatile("" : "+r"(xa), "+r"(xb), "+r"(ya), "+r"(yb));
  auto scat = [&](uint32_t ad, uint32_t mb, const float* d) {
    st_async_v2(ad, pack2(d[0], d[1]), pack2(d[2], d[3]), mb);
    if (N == 16) st_async_v2(ad + LAND_F, pack2(d[4], d[5]), pack2(d[6], d[7]), mb);
  };
  if (wg == 0) {
    bar_sync(N_O, 384);
    wg_fence(); wo4<N, 0, 4, 0, 0>(x, D); wo4<N, 0, 8, 0, 0>(y, D); wg_commit();
    mbar_waitu(bar + 8 * B_OPEER, par);
    CFENCE(); wg_fence(); wo4<N, 0, 16, 1, 1>(x, D); wo4<N, 0, 20, 2, 1>(x, D); wg_commit();
    wo4<N, 0, 24, 1, 1>(y, D); wg_commit();
    mbar_waitu2(bar + 8 * B_WOF, bar + 8 * B_MEMFREE, par);
    wg_fence(); wo4<N, 0, 28, 2, 1>(y, D); wg_commit();
    bar_arrive(N_AB, 256);
    wg_wait<2>(); scat(xa, xb, x);
    wg_wait<0>(); scat(ya, yb, y);
  } else {
    bar_sync(N_O, 384);
    wg_fence(); wo4<N, 1, 0, 0, 0>(x, D); wg_commit(); wo4<N, 1, 12, 0, 0>(y, D); wg_commit();
    wg_wait<1>(); mbar_arrive_remote_if(lane == 0, r1);
    mbar_waitu(bar + 8 * B_MEMFREE, par);
    scat(xa, xb, x);
    bar_sync(N_AB, 256);
    CFENCE(); wg_fence(); wo4<N, 1, 32, 1, 1>(y, D); wo4<N, 1, 36, 2, 1>(y, D); wg_commit();
    bar_arrive(N_TURN, 256);
    wg_wait<0>(); scat(ya, yb, y);
  }
}
#define DS_DUAL 10
#define DS_SINGLE 20
#define POLL_GAP 100
#define POLL_GAPD 0
#define TOK_DELAY 250
#define LATE_SM 1
#define UMAX 40
#define VD1 6
#define VS1 4
struct AMaps { CUtensorMap w16[3], wo32; uint64_t d[5]; const __nv_bfloat16* wv; };
__global__ void __launch_bounds__(512, 1)
acore_kernel(const __grid_constant__ AMaps M, const __nv_bfloat16* __restrict__ mem0, int sync_b) {
  extern __shared__ __align__(1024) unsigned char smem_raw[];
  const uint32_t sb = smem_u32(smem_raw);
  GTS(24);
  if (threadIdx.x == 480) {
    uint32_t smid; asm volatile("mov.u32 %0, %%smid;" : "=r"(smid));
    g_tpc[(smid >> 1) & 127] = blockIdx.x - CL_SIZE < 3 * CL_SIZE && blockIdx.x % CL_SIZE >= 12 ? 1 : 2;
    asm volatile("griddepcontrol.launch_dependents;");
  }
  const int lane0 = threadIdx.x & 31;
#define LANE_INIT() int lane; asm volatile("mov.u32 %0, %%laneid;" : "=r"(lane))
  const int warp = __shfl_sync(~0u, (threadIdx.x >> 5) & 3, 0);
  const int cl = blockIdx.x / CL_SIZE;
  const uint32_t rank = blockIdx.x - cl * CL_SIZE;
  const int nh = cl >= 1 && cl <= 3 ? 4 : 5;
  const int nA = 3 * nh;
  const int wg = __shfl_sync(~0u, (int)rank < nA ? threadIdx.x >> 7 : 4, 0);
  const int head = (cl < 4 ? (cl ? 1 + 4 * cl : 0) : 5 * cl - 3) + rank / 3;
  const int t3 = rank % 3;
  const int col0 = head * DH + t3 * 64;
  const uint32_t bar = sb + OFF_BAR;
  const uint32_t rb0 = SMEM0;
  const uint16_t mcmask = (uint16_t)((1u << nA) - 1);
  const uint32_t nxt = sb + ((t3 == 2 ? -2 : 1) << 24), prv = sb + ((t3 == 0 ? 2 : -1) << 24);
  const int ig = (int)rank - (nA - 4);

  if (threadIdx.x == 0) {
    if (mapa(sb, nA - 1) != rb0 + ((nA - 1) << 24) || mapa(sb, 0) != rb0 || mapa(sb, 1) != rb0 + (1u << 24) || sb != SMEM0 + (rank << 24)) FAIL();
    for (int i = 0; i < B_NUM; i++)
      mbar_init(bar + 8 * i, i == B_R1 ? 4 * nA : i == B_R2 ? 12 * nA : i == B_MEMFREE ? nA : i == B_LANDFREE ? 4 * nA : i == B_PLFREE || i == B_XFREE ? 2 : 1);
    asm volatile("fence.mbarrier_init.release.cluster;" ::: "memory");
    mbar_expect(bar + 8 * B_W0, (80 + SSV + VST) * 2048);
  }
  __syncthreads();
  if (lane0 == 0) {
    const int w12 = wg * 4 + warp;
    if (w12 < 10) {
#pragma unroll 1
      for (int ks = 4 * w12; ks < 4 * w12 + 4; ks++) {
        const bool ss = is_ss(ks, SSQ);
        tma2d(ss ? sb + OFF_WS + ss_idx(ks, SSQ) * 2048 : sb + STG_Q + rs_idx(ks, SSQ) * 2048, &M.w16[0], col0, ks * 16, bar + 8 * B_W0);
        tma2d(ss ? sb + OFF_WS + (SSQ + ss_idx(ks, SSQ)) * 2048 : sb + STG_K + rs_idx(ks, SSQ) * 2048, &M.w16[1], col0, ks * 16, bar + 8 * B_W0);
        if (is_ss(ks, SSV)) tma2d(sb + OFF_WS + (2 * SSQ + ss_idx(ks, SSV)) * 2048, &M.w16[2], col0, ks * 16, bar + 8 * B_W0);
        else if (rs_idx(ks, SSV) < VST) tma2d(sb + (rs_idx(ks, SSV) < VA ? STG_K + 27 * 2048 : STG_V2 - VA * 2048) + rs_idx(ks, SSV) * 2048, &M.w16[2], col0, ks * 16, bar + 8 * B_W0);
      }
    }
  }
  if (lane0 < 2 && wg < 2) {
    const int u = 4 * (wg ? (lane0 ? 6 + t3 : 9) : (lane0 ? 3 + t3 : t3)) + warp;
    const int li = (u >= nA) + (u >= 2 * nA) + (u >= 3 * nA);
    sts32(sb + OFF_TAB + (wg * 4 + warp) * 8 + lane0 * 4,
          rb0 + ((u - li * nA) << 24) + OFF_TILE + LAND(li + (u >= 36 ? t3 : 0)) + (rank / 3) * 256 + 8 * (B_RS + li));
  }
  __syncthreads();
  GTS(25);

  auto issue_tok = [&](int sc, int fb, int rel = -1, uint32_t ph = 0) {
    if (sync_b) wait_cnt(&g_xready[sc][0], 32);
    if (rel >= 0) mbar_waitu(bar + 8 * rel, ph);
    bulk_g2s_mc_e(sb + OFF_TILE + ig * TILE_GRP + TILE_SBO, &g_xn[0][0] + uni(sc * (32 * DM)) + ig * 5120, 10240, bar + 8 * (fb + ig), mcmask);
  };
#define POLL(d, q) _Pragma("unroll") for (int k = 0; k < NCL; k++) \
      asm volatile("ld.relaxed.gpu.global.v2.b32 {%0,%1}, [%2];" : "=r"(d[k].x), "=r"(d[k].y) : "l"(q + k * 2560) : "memory")
#define L3(L, a, b, c) lop3<L>(a, b, c)
#define TAGS(L, d) L3(L, L3(L, L3(L, d[0].x, d[0].y, d[1].x), L3(L, d[1].y, d[2].x, d[2].y), L3(L, d[3].x, d[3].y, d[4].x)), L3(L, d[4].y, d[5].x, d[5].y), L3(L, d[6].x, d[6].y, d[6].y))
    auto deliver = [&](uint2* pa, const uint32_t* gq, int u, int c, int dc, int ds, int step, bool first, int lane) {
      const uint32_t off = uni(OFF_TILE + ((u * 205) >> 11) * (TILE_GRP - TILE_SBO) + u * 256 + dc * LAND_F), boff = uni(OFF_BAR + 8 * (B_F1 + ((u * 205) >> 11)));
      const uint32_t* mi = &g_part[4][0][0][0] + uni((c * NCL + cl) * 2560 + u * 64);
      mbar_waitu(bar + 8 * B_LANDFREE, step & 1);
      int n = 0;
      while (true) {
        const bool ok = __all_sync(~0u, ((step & 2 ? ~TAGS(0xFE, pa) : TAGS(0x80, pa)) & 1) != 0);
        if (ok) break;
        if (++n > SPIN_LIMIT) FAIL();
        POLL(pa, gq);
      }
      if (warp == 0 && first) { TS(19); TSV(10, n); }
      const uint32_t w0 = hadd2bf(hadd2bf(hadd2bf(pa[0].x, pa[1].x), hadd2bf(pa[2].x, pa[3].x)), hadd2bf(hadd2bf(pa[4].x, pa[5].x), pa[6].x));
      const uint32_t w1 = hadd2bf(hadd2bf(hadd2bf(pa[0].y, pa[1].y), hadd2bf(pa[2].y, pa[3].y)), hadd2bf(hadd2bf(pa[4].y, pa[5].y), pa[6].y));
      if (u < ds) {
        const uint32_t da = SMEM0 + off + lane * 8, db = SMEM0 + boff;
#pragma unroll
        for (int d = 0; d < 12; d++) st_async_v2((d << 24) + da, w0, w1, (d << 24) + db);
#pragma unroll
        for (int d = 12; d < 15; d++) st_async_v2_if(nA == 15, (d << 24) + da, w0, w1, (d << 24) + db);
      } else {
        *reinterpret_cast<uint2*>(const_cast<uint32_t*>(gq) + ((4 - 2 * (step & 1)) * NCL + cl) * 2560) = make_uint2(w0, w1);
        asm volatile("fence.proxy.async.global;" ::: "memory");
        __syncwarp();
        bulk_g2s_mc_e(sb + off, mi, 256, sb + boff, mcmask);
      }
    };
#define REL(b, g) mbar_arrive_remote_if(lane == 0, rb0 + ((nA - 4 + (g)) << 24) + OFF_BAR + 8 * (b))

  if (wg < 2) {
    asm volatile("setmaxnreg.inc.sync.aligned.u32 160;");
    LANE_INIT();
    uint32_t W[4 * (40 - SSQ)];
    mbar_waitw(bar + 8 * B_W0, 0);
    GTS(26);
    load_w<40 - SSQ>(W, sb + (wg ? STG_K : STG_Q), warp, lane);
    fence_async();
    bar_sync(1, 384);
    cluster_sync_all();
#define DESC(k) const Desc D = make_desc(M.d, min(wg, 2) * SSQ, fresh<k>(step))
    GTS(27);
#pragma unroll 1
    for (int step = -1; step < NSTEP; step++) {
      const uint32_t par = step & 1;
      asm volatile("" : "+r"(lane));
      const bool dual = is_dual(step), has_next = step + 1 < NSTEP;
#define QK_SA (sb + OFF_QK + wg * 15360 + (2 * warp + ((lane >> 3) & 1)) * 128 + (lane & 7) * 16)
#define QK_F (wg ? -5120 : 5120)
#define QK_S12 ((wg ? (lane >> 4) : 1 + 2 * (lane >> 4)) * 1024)
#define QK_S34 ((wg ? 2 + (lane >> 4) : 2 - 2 * (lane >> 4)) * 1024)
      if (step >= 0) {
        if (dual) {
          DESC(0);
          float acc[24];
          mbar_waitu(bar + 8 * (B_F1 + 0), par);
          if (wg + warp == 0) { TS(0); TSN(1); }
          CFENCE(); wg_fence(); proj<48, SSQ, 0, 0, 10>(acc, W, D); wg_commit();
          mbar_waitu(bar + 8 * (B_F1 + 1), par);
          CFENCE(); wg_fence(); proj<48, SSQ, 0, 10, 20>(acc, W, D); wg_commit();
          mbar_waitu(bar + 8 * (B_F1 + 2), par);
          CFENCE(); wg_fence(); proj<48, SSQ, 0, 20, 30>(acc, W, D); wg_commit();
          mbar_waitu2(bar + 8 * (B_F1 + 3), bar + 8 * B_PLFREE, par);
          if (wg + warp == 0) TS(2);
          CFENCE(); wg_fence(); proj<48, SSQ, 0, 30, 40>(acc, W, D); wg_commit();
          bar_arrive(N_VGO, 384);
          const uint32_t sa = QK_SA, s0 = sa + 4096 + (lane >> 4) * QK_F, s1 = sa + QK_F + QK_S12, s2 = sa + QK_F + QK_S34;
          wg_wait<0>();
          if (wg + warp == 0) TS(3);
          stsm4t(s0, pack2(acc[0], acc[1]), pack2(acc[2], acc[3]), pack2(acc[20], acc[21]), pack2(acc[22], acc[23]));
          stsm4t(s1, pack2(acc[4], acc[5]), pack2(acc[6], acc[7]), pack2(acc[8], acc[9]), pack2(acc[10], acc[11]));
          stsm4t(s2, pack2(acc[12], acc[13]), pack2(acc[14], acc[15]), pack2(acc[16], acc[17]), pack2(acc[18], acc[19]));
        } else {
          DESC(1);
          float acc[4];
          mbar_waitu(bar + 8 * (B_F1 + 0), par);
          if (wg + warp == 0) { TS(0); TSN(1); }
          CFENCE(); wg_fence(); proj<8, SSQ, 0, 0, 10>(acc, W, D); wg_commit();
          mbar_waitu(bar + 8 * (B_F1 + 1), par);
          CFENCE(); wg_fence(); proj<8, SSQ, 0, 10, 20>(acc, W, D); wg_commit();
          mbar_waitu(bar + 8 * (B_F1 + 2), par);
          CFENCE(); wg_fence(); proj<8, SSQ, 0, 20, 30>(acc, W, D); wg_commit();
          mbar_waitu2(bar + 8 * (B_F1 + 3), bar + 8 * B_PLFREE, par);
          if (wg + warp == 0) TS(2);
          CFENCE(); wg_fence(); proj<8, SSQ, 0, 30, 40>(acc, W, D); wg_commit();
          bar_arrive(N_VGO, 384);
          const uint32_t s0 = QK_SA + 4096;
          wg_wait<0>();
          if (wg + warp == 0) TS(3);
          stsm2t(s0, pack2(acc[0], acc[1]), pack2(acc[2], acc[3]));
        }
        fence_async();
        bar_sync(N_QK, 256);
        if (wg == 0 || dual) {
          float s[20];
          DESC(2);
          const Dsc ab = D.k1 + wg * 192, bb = D.k1 + (1 - wg) * 320;
          wg_fence();
          MM<40>::ss<dlo(OFF_QK, 128), dlo(OFF_QK + 10240, 128), 0, 0>(s, ab, bb);
          MM<40>::ss<dlo(OFF_QK + 256, 128), dlo(OFF_QK + 10240 + 256, 128), 1, 0>(s, ab, bb);
          MM<40>::ss<dlo(OFF_QK + 512, 128), dlo(OFF_QK + 10240 + 512, 128), 1, 0>(s, ab, bb);
          MM<40>::ss<dlo(OFF_QK + 768, 128), dlo(OFF_QK + 10240 + 768, 128), 1, 0>(s, ab, bb);
          wg_commit();
          bar_arrive(N_SISS, 384);
          const int rw = (warp - wg) & 3;
          const uint32_t bo = OFF_BAR + 8 * (B_SB + 3 * wg + rw), lo = OFF_PL + wg * PL_SZ + rw * 1792;
          const uint32_t km = wg ? 640 : 512;
          uint32_t l16 = lo + lane * 16, l4 = lo + lane * 4;
          mbar_expect_if(lane == 0 && rw < 3, sb + bo, rw < 2 ? 1792 : 1280);
          asm volatile("" : "+r"(l16), "+r"(l4));
          if (rw == 2) {
            wg_wait<0>();
            if (wg == 0) TSD(4, __float_as_uint(s[0]));
            {
              const uint32_t w0 = pack2(s[0], s[1]), w1 = pack2(s[4], s[5]), w2 = pack2(s[8], s[9]), w3 = pack2(s[12], s[13]), w4 = pack2(s[16], s[17]);
              st_async_v4(nxt + 896 + l16, w0, w1, w2, w3, nxt + bo);
              st_async_v4(prv + l16, w0, w1, w2, w3, prv + bo);
              st_async_b32(nxt + 896 + 768 + l4, w4, nxt + bo);
              st_async_b32(prv + 768 + l4, w4, prv + bo);
            }
            bar_arrive(N_SDONE, 256);
            mbar_waitu(sb + bo, (step - wg * LAG) & 1);
            if (wg == 0) TS(5);
            float x[10];
            {
              const uint4 a = lds128(sb + l16), b = lds128(sb + 896 + l16);
              const uint32_t c = lds32(sb + 768 + l4), d = lds32(sb + 896 + 768 + l4);
              const uint32_t e0 = hadd2bf(a.x, b.x), e1 = hadd2bf(a.y, b.y), e2 = hadd2bf(a.z, b.z), e3 = hadd2bf(a.w, b.w), e4 = hadd2bf(c, d);
              x[0] = s[0] + bf_lo(e0); x[1] = s[1] + bf_hi(e0); x[2] = s[4] + bf_lo(e1); x[3] = s[5] + bf_hi(e1); x[4] = s[8] + bf_lo(e2);
              x[5] = s[9] + bf_hi(e2); x[6] = s[12] + bf_lo(e3); x[7] = s[13] + bf_hi(e3); x[8] = s[16] + bf_lo(e4); x[9] = s[17] + bf_hi(e4);
            }
            float m0 = fmaxf(fmaxf(fmaxf(x[0], x[1]), fmaxf(x[2], x[3])), fmaxf(fmaxf(x[4], x[5]), fmaxf(fmaxf(x[6], x[7]), fmaxf(x[8], x[9]))));
            m0 = fmaxf(m0, __shfl_xor_sync(~0u, m0, 1));
            sts32(sb + l4 + 1152 - km, 0u);
            m0 = fmaxf(m0, __shfl_xor_sync(~0u, m0, 2));
            m0 *= -SL2;
#pragma unroll
            for (int j = 0; j < 5; j++) {
              x[2 * j] = ex2(fmaf(x[2 * j], SL2, m0)); x[2 * j + 1] = ex2(fmaf(x[2 * j + 1], SL2, m0));
              sts32(sb + l4 + (j < 4 ? j * 128 : km), pack2(x[2 * j], x[2 * j + 1]));
            }
            float l = ((x[0] + x[1]) + (x[2] + x[3])) + ((x[4] + x[5]) + ((x[6] + x[7]) + (x[8] + x[9])));
            l += __shfl_xor_sync(~0u, l, 1);
            fence_async();
            sts32(sb + OFF_INV + wg * 64 + (lane >> 1) * 4, __float_as_uint(l));
            bar_arrive(N_PM, dual ? 224 : 192);
            if (wg == 0) TS(6);
          } else if (rw < 2) {
            const bool w1 = rw == 1;
            const uint32_t l8 = lo + 512 + lane * 8;
            uint32_t tw[7];
            wg_wait<0>();
            bar_arrive(N_SDONE, 256);
            tw[0] = pack2(s[0], s[1]); tw[1] = pack2(s[4], s[5]); tw[2] = pack2(s[8], s[9]); tw[3] = pack2(s[16], s[17]);
            tw[4] = w1 ? pack2(s[6], s[7]) : pack2(s[12], s[13]); tw[5] = pack2(s[2], s[3]); tw[6] = pack2(s[18], s[19]);
            { const uint32_t t0 = clock32(); while (clock32() - t0 < TOK_DELAY) {} }
            st_async_v4(nxt + 896 + l16, tw[0], tw[1], tw[2], tw[3], nxt + bo);
            st_async_v4(prv + l16, tw[0], tw[1], tw[2], tw[3], prv + bo);
            st_async_v2(nxt + 896 + l8, tw[5], tw[6], nxt + bo);
            st_async_v2(prv + l8, tw[5], tw[6], prv + bo);
            st_async_b32(nxt + 896 + 768 + l4, tw[4], nxt + bo);
            st_async_b32(prv + 768 + l4, tw[4], prv + bo);
            mbar_waitu(sb + bo, (step - wg * LAG) & 1);
            const uint4 a = lds128(sb + l16), b = lds128(sb + 896 + l16);
            const uint2 e = lds64(sb + l8), f = lds64(sb + 896 + l8);
            const uint32_t c = lds32(sb + 768 + l4), d = lds32(sb + 896 + 768 + l4);
            sts128(sb + l16, hadd2bf(hadd2bf(a.x, b.x), tw[0]), hadd2bf(hadd2bf(a.y, b.y), tw[1]), hadd2bf(hadd2bf(a.z, b.z), tw[2]), hadd2bf(hadd2bf(a.w, b.w), tw[3]));
            sts64(sb + l8, hadd2bf(hadd2bf(e.x, f.x), tw[5]), hadd2bf(hadd2bf(e.y, f.y), tw[6]));
            sts32(sb + 768 + l4, hadd2bf(hadd2bf(c, d), tw[4]));
            bar_arrive(N_PX, dual ? 256 : 192);
            if (wg + warp == 0) TS(9);
          } else {
            wg_wait<0>();
            if (wg == 0) {
              mbar_expect_if(lane < 3 && has_next, bar + 8 * (lane == 2 ? B_OPEER : B_WOF + lane), lane == 2 ? (dual ? 4096 : 2048) : lane ? 8192 : 20480);
              auto fetch = [&](int i, int n, uint32_t dst, int mb) {
                int c0, c1; wo_coord(i, t3, head, c0, c1);
                tma2d_e(dst, &M.wo32, c0, c1, bar + 8 * mb); if (n == 2) tma2d_e(dst + 4096, &M.wo32, c0, c1 + 32, bar + 8 * mb);
              };
              bar_sync(N_G3, 160);
              if (has_next) {
                fetch(0, 2, sb + OFF_WT, B_WTF);
                mbar_arrive_remote_if(lane < 2, (lane ? nxt : prv) + OFF_BAR + 8 * B_XFREE);
              }
              bar_sync(N_SDONE, 256);
              if (has_next) {
                fetch(15, 1, sb + OFF_QK, B_WOF); fetch(16, 2, sb + OFF_QK + 4096, B_WOF); fetch(18, 2, sb + OFF_QK + 12288, B_WOF);
                mbar_waitu(bar + 8 * B_XFREE, par);
              }
              bar_arrive(N_PM, dual ? 224 : 192);
              bar_sync(N_VDONE, 160);
              mbar_arrive_remote_if(lane < nA && has_next, rb0 + (lane << 24) + OFF_BAR + 8 * B_MEMFREE);
              if (has_next) mbar_waitu(bar + 8 * B_WTF, par);
            } else {
              bar_arrive(N_SDONE, 256);
              if ((unsigned)ig < 3) issue_tok(sched_l(step + 1), B_F2, B_R1, (step - LAG) & 1);
            }
          }
        } else {
          bar_arrive(N_SISS, 384);
          bar_arrive(N_SDONE, 256);
        }
        if (has_next) {
          if (step == 0) mbar_waitw(bar + 8 * B_W1, 0);
          const uint32_t r1 = rb0 + ((nA - 1) << 24) + OFF_BAR + 8 * B_R1;
          if (dual) { DESC(3); wo_phase<16>(sb, wg, warp, lane, par, r1, D); } else { DESC(4); wo_phase<8>(sb, wg, warp, lane, par, r1, D); }
          bar_arrive(N_C, 288);
          if (warp == 0) TS(7 + wg);
        }
      }
      if (has_next) {
        DESC(5);
        float acc[16];
        mbar_waitu(bar + 8 * B_F2, par ^ 1);
        wg_fence(); proj<32, SSQ, 1, 0, 10>(acc, W, D); wg_commit();
        mbar_waitu(bar + 8 * (B_F2 + 1), par ^ 1);
        wg_fence(); proj<32, SSQ, 1, 10, 14>(acc, W, D); wg_commit();
        wg_wait<1>(); REL(B_R2, 0);
        wg_fence(); proj<32, SSQ, 1, 14, 20>(acc, W, D); wg_commit();
        mbar_waitu(bar + 8 * (B_F2 + 2), par ^ 1);
        wg_fence(); proj<32, SSQ, 1, 20, 24>(acc, W, D); wg_commit();
        wg_wait<1>(); REL(B_R2, 1);
        wg_fence(); proj<32, SSQ, 1, 24, 30>(acc, W, D); wg_commit();
        mbar_waitu(bar + 8 * (B_F2 + 3), par ^ 1);
        wg_fence(); proj<32, SSQ, 1, 30, 34>(acc, W, D); wg_commit();
        wg_wait<1>(); REL(B_R2, 2);
        wg_fence(); proj<32, SSQ, 1, 34, 40>(acc, W, D); wg_commit();
        const uint32_t sa = QK_SA, s1 = sa + QK_S12, s2 = sa + QK_S34;
        wg_wait<0>(); REL(B_R2, 3);
        if (warp == 0) TS(11 + wg);
        stsm4t(s1, pack2(acc[0], acc[1]), pack2(acc[2], acc[3]), pack2(acc[4], acc[5]), pack2(acc[6], acc[7]));
        stsm4t(s2, pack2(acc[8], acc[9]), pack2(acc[10], acc[11]), pack2(acc[12], acc[13]), pack2(acc[14], acc[15]));
      }
    }
    GTS(28);
    cluster_sync_all();
  } else if (wg == 2) {
    asm volatile("setmaxnreg.inc.sync.aligned.u32 160;");
    LANE_INIT();
    uint32_t W[4 * (40 - SSV)];
    ld_rest<0>(W, reinterpret_cast<const uint32_t*>(M.wv + (lane >> 2) * HD + col0 + warp * 16) + (lane & 3));
    uint4 m0[5];
#pragma unroll
    for (int i = 0; i < 5; i++) {
      const int t = i * 128 + warp * 32 + lane;
      m0[i] = __ldg(reinterpret_cast<const uint4*>(mem0 + ((t >> 1) & 7) * DM + (t >> 4) * 16 + ((t ^ (t >> 3)) & 1) * 8));
    }
    mbar_waitw(bar + 8 * B_W0, 0);
    load_w<VA>(W, sb + STG_K + 27 * 2048, warp, lane);
    load_w<VST - VA>(W + 4 * VA, sb + STG_V2, warp, lane);
    fence_async();
    mbar_expect_if(warp + lane == 0, bar + 8 * B_W1, 26 * 2048);
    bar_sync(1, 384);
#pragma unroll
    for (int i = 0; i < 5; i++) {
      const int t = i * 128 + warp * 32 + lane;
      sts128(sb + OFF_TILE + (t / 160) * (TILE_GRP - TILE_SBO) + t * 16, m0[i].x, m0[i].y, m0[i].z, m0[i].w);
    }
#pragma unroll
    for (int i = 4 * VST; i < 4 * (40 - SSV); i++) W[i] = movm(W[i]);
    fence_async();
    mbar_arrive_if(lane == 0, bar + 8 * (B_F1 + warp));
    mbar_expect_if(lane == 0, bar + 8 * (B_F2 + warp), 10240);
    mbar_arrive_if(warp == 3 && lane < 2, bar + 8 * B_PLFREE);
    cluster_sync_all();
    uint32_t vl[8];
    {
      const int step = warp;
      DESC(0);
      float v[16];
      mbar_waitw4(bar + 8 * B_F2, 0);
      wg_fence(); proj<32, SSV, 1, 0, 40>(v, W, D); wg_commit();
      wg_wait<0>();
      mbar_arrive_remote_if(lane < 4, rb0 + ((nA - 4 + lane) << 24) + OFF_BAR + 8 * B_R2);
#pragma unroll
      for (int j = 0; j < 8; j++) vl[j] = pack2v(v[2 * j], v[2 * j + 1]);
      if (warp == 0 && (unsigned)ig < 3) issue_tok(1, B_F2, B_R2, 0);
    }
#pragma unroll 1
    for (int step = 0; step < NSTEP; step++) {
      const uint32_t par = step & 1;
      asm volatile("" : "+r"(lane));
      const bool dual = is_dual(step), has_next = step + 1 < NSTEP;
      mbar_expect_if(lane == 0 && has_next, bar + 8 * (B_F2 + warp), 10240);
      if (warp == 0 && ig == 3 && has_next && sync_b) wait_cnt(&g_xready[sched_l(step + 1)][0], 32);
      bar_sync(N_VGO, 384);
      CFENCE();
#define F1_BYTES (is_dual(step + 1) ? 15360 : 2560)
#define ARM() do { \
        mbar_expect_if(lane == 0 && has_next, bar + 8 * (B_F1 + warp), F1_BYTES); \
        mbar_expect_if(lane == 0 && has_next && warp * nA + (int)rank < 40, bar + 8 * (B_RS + warp), (warp * nA + (int)rank >= 36 ? nA : nh) * (dual ? 512 : 256)); } while (0)
#define O_ADDR() uint32_t oa = sb + OFF_O + (lane >> 4) * PL_SZ + warp * 256 + (lane & 15) * 16, xo = (lane >> 4) * 1024 + warp * 256 + (lane & 15) * 16; \
        asm volatile("" : "+r"(oa), "+r"(xo))
#define O_READY(act) do { if (has_next) { const uint4 ov = lds128(oa); \
        if (act) { st_async_v4(nxt + OFF_XL + xo, ov.x, ov.y, ov.z, ov.w, nxt + OFF_BAR + 8 * B_OPEER); \
                   st_async_v4(prv + OFF_XF + xo, ov.x, ov.y, ov.z, ov.w, prv + OFF_BAR + 8 * B_OPEER); } \
        fence_async(); bar_arrive(N_O, 384); } \
        if (warp == 0) TS(15); } while (0)
#define TOK_L3() if (warp == 0 && ig == 3 && has_next) { mbar_waitu(bar + 8 * B_R1, par); \
        bulk_g2s_mc_e(sb + OFF_TILE + 3 * TILE_GRP + TILE_SBO, &g_xn[0][0] + uni(sched_l(step + 1) * (32 * DM)) + 3 * 5120, 10240, bar + 8 * (B_F2 + 3), mcmask); }
#define OX_SA (sb + OFF_PL + (lane & 7) * 128 + (((warp * 2 + ((lane >> 3) & 1)) ^ (lane & 7)) << 4))
      if (dual) {
        uint32_t vf[8], vm[4], vn[8];
        {
          DESC(0);
          float v[24];
          wg_fence(); proj<48, SSV, 0, 30, 30 + VD1, 30>(v, W, D); wg_commit();
          ARM();
          bar_sync(N_SISS, 384);
          wg_fence(); proj<48, SSV, 0, 30 + VD1, 40, 30>(v, W, D); wg_commit();
          proj<48, SSV, 0, 0, 3, 30>(v, W, D); wg_commit();
          wg_wait<1>(); bar_arrive(N_G3, 160);
          wg_fence(); proj<48, SSV, 0, 3, 10, 30>(v, W, D); wg_commit();
          proj<48, SSV, 0, 10, 13, 30>(v, W, D); wg_commit();
          wg_wait<1>(); REL(B_R1, 0);
          wg_fence(); proj<48, SSV, 0, 13, 20, 30>(v, W, D); wg_commit();
          proj<48, SSV, 0, 20, 23, 30>(v, W, D); wg_commit();
          wg_wait<1>(); REL(B_R1, 1);
          wg_fence(); proj<48, SSV, 0, 23, 30, 30>(v, W, D); wg_commit();
          wg_wait<0>(); REL(B_R1, 2);
          bar_arrive(N_VDONE, 160);
          if (warp == 0) TS(14);
#pragma unroll
          for (int j = 4; j < 8; j++) vf[j] = pack2v(v[4 + 2 * j], v[5 + 2 * j]);
          keep4(vf + 4, lane);
          vm[0] = pack2v(v[0], v[1]); vm[1] = pack2v(v[2], v[3]); vm[2] = pack2v(v[20], v[21]); vm[3] = pack2v(v[22], v[23]);
          keep4(vm, lane);
#pragma unroll
          for (int j = 0; j < 4; j++) vf[j] = pack2v(v[4 + 2 * j], v[5 + 2 * j]);
          keep4(vf, lane);
        }
        {
          DESC(1);
          float o[8];
          O_ADDR();
          bar_sync(N_PM, 224);
          wg_fence();
          MM<8>::rs<dlo(OFF_PL + 3584, 128), 0>(o, vl, D.p);
          MM<8>::rs<dlo(OFF_PL + PL_SZ + 3584, 128), 0>(o + 4, vf, D.p);
          MM<8>::rs<dlo(OFF_PL + 3584 + 256, 128), 1>(o, vl + 4, D.p);
          MM<8>::rs<dlo(OFF_PL + PL_SZ + 3584 + 256, 128), 1>(o + 4, vf + 4, D.p);
          MM<8>::rs<dlo(OFF_PL + 3584 + 512, 128), 1>(o, vm, D.p);
          MM<8>::rs<dlo(OFF_PL + PL_SZ + 3584 + 512, 128), 1>(o + 4, vm, D.p);
          wg_commit();
          const uint4 il = lds128(sb + OFF_INV + (lane & 3) * 16), jf = lds128(sb + OFF_INV + 64 + (lane & 3) * 16);
          const float i0 = rcpf(__uint_as_float(il.x) + __uint_as_float(il.y)), i1 = rcpf(__uint_as_float(il.z) + __uint_as_float(il.w));
          const float j0 = rcpf(__uint_as_float(jf.x) + __uint_as_float(jf.y)), j1 = rcpf(__uint_as_float(jf.z) + __uint_as_float(jf.w));
          wg_wait<0>();
          stsm4t(oa, pack2(o[0] * i0, o[1] * i1), pack2(o[2] * i0, o[3] * i1), pack2(o[4] * j0, o[5] * j1), pack2(o[6] * j0, o[7] * j1));
          O_READY(true);
          TOK_L3();
        }
        {
          DESC(2);
          float v[16];
          bar_sync(N_TURN, 256);
          mbar_waitu(bar + 8 * B_F2, par ^ 1);
          wg_fence(); proj<32, SSV, 1, 0, 10>(v, W, D); wg_commit();
          mbar_waitu(bar + 8 * (B_F2 + 1), par ^ 1);
          wg_fence(); proj<32, SSV, 1, 10, 14>(v, W, D); wg_commit();
          wg_wait<1>(); REL(B_R2, 0);
          wg_fence(); proj<32, SSV, 1, 14, 20>(v, W, D); wg_commit();
          mbar_waitu(bar + 8 * (B_F2 + 2), par ^ 1);
          wg_fence(); proj<32, SSV, 1, 20, 24>(v, W, D); wg_commit();
          wg_wait<1>(); REL(B_R2, 1);
          wg_fence(); proj<32, SSV, 1, 24, 30>(v, W, D); wg_commit();
          mbar_waitu(bar + 8 * (B_F2 + 3), par ^ 1);
          wg_fence(); proj<32, SSV, 1, 30, 34>(v, W, D); wg_commit();
          wg_wait<1>(); REL(B_R2, 2);
          wg_fence(); proj<32, SSV, 1, 34, 40>(v, W, D); wg_commit();
          wg_wait<0>(); REL(B_R2, 3);
#pragma unroll
          for (int j = 0; j < 8; j++) vn[j] = pack2v(v[2 * j], v[2 * j + 1]);
          keep4(vn, lane); keep4(vn + 4, lane);
          if (warp == 0) TS(18);
        }
        DESC(3);
        uint32_t ow[16];
        bar_sync(N_P, 256);
        fence_async();
#define PV16(i, off, va) { float o[8]; wg_fence(); \
          MM<16>::rs<dlo(OFF_PL + (off), 128), 0>(o, va, D.p); \
          MM<16>::rs<dlo(OFF_PL + (off) + 256, 128), 1>(o, va + 4, D.p); \
          MM<16>::rs<dlo(OFF_PL + (off) + 512, 128), 1>(o, vm, D.p); \
          wg_commit(); wg_wait<0>(); \
          _Pragma("unroll") for (int j = 0; j < 4; j++) ow[4 * (i) + j] = pack2v(o[2 * j], o[2 * j + 1]); \
          keep4(ow + 4 * (i), lane); }
        PV16(0, 0, vl) PV16(1, 1792, vl) PV16(2, PL_SZ, vf) PV16(3, PL_SZ + 1792, vf)
        const uint32_t s1 = OX_SA + (lane < 16 ? 3072 : 0), s2 = OX_SA + (lane < 16 ? 2048 : 1024);
        bar_sync(N_V, 128);
        stsm4t(s1, ow[0], ow[1], ow[2], ow[3]);
        stsm4t(s2, ow[4], ow[5], ow[6], ow[7]);
        stsm4t(s1 + PL_SZ, ow[8], ow[9], ow[10], ow[11]);
        stsm4t(s2 + PL_SZ, ow[12], ow[13], ow[14], ow[15]);
#pragma unroll
        for (int j = 0; j < 8; j++) vl[j] = vn[j];
      } else {
        uint32_t vm[4], vn[8];
        {
          DESC(4);
          float v[4];
          wg_fence(); proj<8, SSV, 0, 30, 40, 30>(v, W, D); wg_commit();
          proj<8, SSV, 0, 0, VS1, 30>(v, W, D); wg_commit();
          ARM();
          bar_sync(N_SISS, 384);
          wg_wait<1>(); bar_arrive(N_G3, 160);
          wg_fence(); proj<8, SSV, 0, VS1, 30, 30>(v, W, D); wg_commit();
          if (has_next) { mbar_waitu2(bar + 8 * B_F2, bar + 8 * (B_F2 + 1), par ^ 1); mbar_waitu(bar + 8 * (B_F2 + 2), par ^ 1); }
          wg_wait<0>();
          bar_arrive(N_VDONE, 160);
          vm[0] = pack2v(v[0], v[1]); vm[1] = pack2v(v[2], v[3]); vm[2] = pack2v(v[1], v[0]); vm[3] = pack2v(v[3], v[2]);
        }
        DESC(5);
        float v[16];
        {
          wg_fence(); proj<32, SSV, 1, 0, 30>(v, W, D); wg_commit();
          {
            float o[4];
            O_ADDR();
            bar_sync(N_PM, 192);
            if (warp == 0) TS(14);
            wg_fence();
            MM<8>::rs<dlo(OFF_PL + 3584, 128), 0>(o, vl, D.p);
            MM<8>::rs<dlo(OFF_PL + 3584 + 256, 128), 1>(o, vl + 4, D.p);
            MM<8>::rs<dlo(OFF_PL + 3584 + 512, 128), 1>(o, vm, D.p);
            wg_commit();
            const uint4 il = lds128(sb + OFF_INV + (lane & 3) * 16);
            const float i0 = rcpf(__uint_as_float(il.x) + __uint_as_float(il.y)), i1 = rcpf(__uint_as_float(il.z) + __uint_as_float(il.w));
            wg_wait<0>();
            stsm2t(oa, pack2(o[0] * i0, o[1] * i1), pack2(o[2] * i0, o[3] * i1));
            O_READY(lane < 16);
            TOK_L3();
          }
          if (has_next) {
            mbar_arrive_remote_if(lane < 3, rb0 + ((nA - 4 + lane) << 24) + OFF_BAR + 8 * B_R2);
            bar_sync(N_TURN, 256);
            mbar_waitu(bar + 8 * (B_F2 + 3), par ^ 1);
          }
          wg_fence(); proj<32, SSV, 1, 30, 40>(v, W, D); wg_commit();
          wg_wait<0>();
          if (has_next) REL(B_R2, 3);
#pragma unroll
          for (int j = 0; j < 8; j++) vn[j] = pack2v(v[2 * j], v[2 * j + 1]);
          keep4(vn, lane); keep4(vn + 4, lane);
          if (warp == 0) TS(18);
        }
        float o[16];
        bar_sync(N_P, 256);
        fence_async();
        wg_fence();
        MM<32>::rs<dlo(OFF_PL, 128), 0>(o, vl, D.p);
        MM<32>::rs<dlo(OFF_PL + 256, 128), 1>(o, vl + 4, D.p);
        MM<32>::rs<dlo(OFF_PL + 512, 128), 1>(o, vm, D.p);
        wg_commit();
        const uint32_t s1 = OX_SA + (lane < 16 ? 3072 : 0), s2 = OX_SA + (lane < 16 ? 2048 : 1024);
        wg_wait<0>();
        bar_sync(N_V, 128);
        stsm4t(s1, pack2(o[0], o[1]), pack2(o[2], o[3]), pack2(o[4], o[5]), pack2(o[6], o[7]));
        stsm4t(s2, pack2(o[8], o[9]), pack2(o[10], o[11]), pack2(o[12], o[13]), pack2(o[14], o[15]));
#pragma unroll
        for (int j = 0; j < 8; j++) vl[j] = vn[j];
      }
      bar_arrive(N_OX, 160);
      if (warp == 0) TS(16);
    }
    cluster_sync_all();
  } else {
    asm volatile("setmaxnreg.dec.sync.aligned.u32 32;");
    if (wg > 3) return;
    LANE_INIT();
    struct RsJob { uint32_t* gp; uint32_t la, mb; int n; };
    auto rs_prep = [&](int step, int s, int c) {
      RsJob j;
      const int u = s * nA + rank;
      j.gp = &g_part[0][0][0][0] + (uint32_t)((((step & 1) * 2 + c) * NCL + cl) * 2560 + u * 64 + (lane >> 2) * 8 + (lane & 3));
      j.la = sb + OFF_TILE + c * LAND_F + LAND(s) + lane * 8;
      j.mb = bar + 8 * (B_RS + s);
      j.n = u >= 40 ? 0 : u >= 36 ? 3 : 1;
      asm volatile("" : "+l"(j.gp), "+r"(j.la));
      return j;
    };
    auto rs_sum = [&](RsJob j, int step) {
      if (j.n) {
        auto five = [&](uint32_t la) {
          uint2 p[5];
#pragma unroll
          for (int i = 0; i < 4; i++) p[i] = lds64(la + i * 256);
          asm volatile("{\n.reg .pred q;\nsetp.eq.s32 q, %3, 5;\nmov.u32 %0, 0;\nmov.u32 %1, 0;\n@q ld.shared.v2.b32 {%0,%1}, [%2];\n}"
                       : "=r"(p[4].x), "=r"(p[4].y) : "r"(la + 1024), "r"(nh) : "memory");
          return make_uint2(hadd2bf(hadd2bf(p[0].x, p[1].x), hadd2bf(hadd2bf(p[2].x, p[3].x), p[4].x)),
                            hadd2bf(hadd2bf(p[0].y, p[1].y), hadd2bf(hadd2bf(p[2].y, p[3].y), p[4].y)));
        };
        const uint32_t tag = ((step >> 1) & 1) ^ 1;
        mbar_waitw(j.mb, step & 1);
        uint2 t = five(j.la);
        if (j.n > 1) {
          const uint2 a = five(j.la + (nh == 5 ? 1280 : TILE_GRP - 1280)), b = five(j.la + TILE_GRP);
          t.x = hadd2bf(t.x, hadd2bf(a.x, b.x)); t.y = hadd2bf(t.y, hadd2bf(a.y, b.y));
        }
        const uint32_t t0 = (movm(t.x) & ~1u) | tag, t1 = (movm(t.y) & ~1u) | tag;
        asm volatile("st.relaxed.gpu.global.b32 [%0], %1;" :: "l"(j.gp), "r"(lane & 16 ? t1 : t0) : "memory");
        asm volatile("st.relaxed.gpu.global.b32 [%0], %1;" :: "l"(j.gp + 4), "r"(lane & 16 ? t0 : t1) : "memory");
      }
    };
    if (warp * nA + (int)rank < 40) {
#pragma unroll
      for (int e = LAG; e < LAG + 2; e++)
        if ((e >> 1) & 1) *reinterpret_cast<uint2*>(&g_part[(e & 1) * 2 + 1][cl][warp * nA + rank][lane * 2]) = make_uint2(1u, 1u);
      __threadfence();
    }
    cluster_sync_all();
    if (warp == 2 && ig >= 0) issue_tok(0, B_F2);
    if (warp != 2) {
#pragma unroll 1
      for (int i = min(warp, 2); i < 20; i += 3) {
        int c0, c1; wo_coord(i, t3, head, c0, c1);
        if (i >= 2 && i < 15) tma2d_e(sb + OFF_WO + (i - 2) * 4096, &M.wo32, c0, c1, bar + 8 * B_W1);
        else if (lane == 0) tma2d_prefetch(&M.wo32, c0, c1);
        __syncwarp();
      }
    }
#pragma unroll 1
    for (int step = 0; step < NSTEP; step++) {
      const uint32_t par = step & 1;
      asm volatile("" : "+r"(lane));
      const bool dual = is_dual(step), has_next = step + 1 < NSTEP;
      {
        bar_sync(N_PX, dual ? 256 : 192);
        if (dual || warp >= 2) tok_softmax(sb, dual ? warp : warp - 2, lane);
        bar_arrive(N_P, 256);
        asm volatile("" : "+r"(lane));
        if (has_next) {
          if (step + 2 == LAG && lane < 20) asm volatile("prefetch.global.L2 [%0];" :: "l"(mem0 + (warp * 20 + lane) * 64));
          const int nw = ig >= 0 ? 3 : 4, j0 = warp < nw ? warp : 8;
          const int sh = dual ? 1 : 0;
          rs_sum(rs_prep(step, j0 >> sh, j0 & sh), step);
          if (warp == 0) TS(17);
          if (dual) rs_sum(rs_prep(step, (j0 + nw) >> 1, (j0 + nw) & 1), step);
          if (warp == 0) { bar_sync(N_C, 288); }
          mbar_arrive_remote_if(lane < nA, rb0 + (lane << 24) + OFF_BAR + 8 * B_LANDFREE);
          const uint32_t gap = dual ? POLL_GAPD : POLL_GAP;
          if (gap) { const uint32_t t0 = clock32(); while (clock32() - t0 < gap) {} }
#pragma unroll 1
          for (int j = j0; j < (dual ? 8 : 4); j += nw) {
            const int u = (j >> sh) * nA + rank, c = j & sh;
            if (u < UMAX && (c || step + 1 != NSEG)) {
              const uint32_t* gq = &g_part[0][0][0][0] + (uint32_t)((par * 2 + c) * NCL * 2560 + u * 64 + lane * 2);
              uint2 pa[NCL];
              POLL(pa, gq);
              deliver(pa, gq, u, c, step + 1 < NSEG ? c : 0, dual ? DS_DUAL : DS_SINGLE, step, j == 0, lane);
            }
            if (warp == 0 && j == 0) TS(13);
          }
          if (warp >= nw && (is_dual(step + 1) || (ig < 3 && step + 2 < NSTEP))) {
            issue_tok(is_dual(step + 1) ? sched_f(step + 1) : sched_l(step + 2), is_dual(step + 1) ? B_F1 : B_F2, B_R2, par ^ 1);
          }
          if (step + 1 == LAG && UMAX) {
            uint4 v[5];
#pragma unroll
            for (int i = 0; i < 5; i++) { const int t = warp * 160 + i * 32 + lane; v[i] = *reinterpret_cast<const uint4*>(mem0 + ((t >> 1) & 7) * DM + (t >> 4) * 16 + ((t ^ (t >> 3)) & 1) * 8); }
            mbar_waitu(bar + 8 * B_LANDFREE, par);
#pragma unroll
            for (int i = 0; i < 5; i++)
              st_async_v4(sb + OFF_TILE + LAND_F + warp * TILE_GRP + (i * 32 + lane) * 16, v[i].x, v[i].y, v[i].z, v[i].w, bar + 8 * (B_F1 + warp));
          }
        }
      }
      if (warp == 3) {
        unsigned char* o0 = g_o + uni(step % RO * (96 * 8192) + (head * 3 + t3) * (dual ? 8192 : 4096));
        bar_sync(N_OX, 160);
        fence_async();
        bulk_s2g_es(o0, sb + OFF_PL, 4096);
        if (dual) bulk_s2g_es(o0 + 4096, sb + OFF_PL + PL_SZ, 4096);
        asm volatile("cp.async.bulk.commit_group;" ::: "memory");
        asm volatile("cp.async.bulk.wait_group.read 0;" ::: "memory");
        __syncwarp();
        mbar_arrive_remote_if(lane < 2, (lane ? nxt : prv) + OFF_BAR + 8 * B_PLFREE);
        asm volatile("cp.async.bulk.wait_group 0;" ::: "memory");
        asm volatile("fence.proxy.async.global;" ::: "memory");
        __syncwarp();
        if (lane == 0) red_release(&g_f[F_O + (head * 3 + t3) / 5][step], 1u);
        __syncwarp();
      }
    }
    cluster_sync_all();
  }
}

__device__ __forceinline__ float gelu2(float x) {
  const float u = x * fmaf(x * x, 0.7978845608028654f * 0.044715f, 0.7978845608028654f);
  float t; asm("tanh.approx.f32 %0, %1;" : "=f"(t) : "f"(u));
  return fmaf(x, t, x); }

struct BParams {
  CUtensorMap wmap[5];
  CUtensorMap wo16;
  const __nv_bfloat16* x;
  __nv_bfloat16* out;
  uint64_t desc;
};
#define BO_O 0
#define BO_RES (6 * 8192)
#define OP_RES 63488
#define BO_STG (BO_RES + 2 * OP_RES)
#define BO_RING_OP (BO_STG + 16384)
#define OP_SLOT 12288
#define NS_OP 3
#define BO_H 81920
#define BO_W1 (BO_H + 16384)
#define BO_RING_MLP (BO_W1 + 81920)
#define BO_BAR 229376
#define BO_BOX (BO_BAR + 248)
#define BO_CARRY (BO_BAR + 512)
#define BO_STAT (BO_CARRY + 2048)
#define B_SMEM (BO_STAT + 256)
static_assert(B_SMEM <= 232448 && BO_RING_OP + NS_OP * OP_SLOT == BO_BAR && BO_RING_MLP + 3 * 16384 == BO_BAR && 2 * 83968 <= BO_RING_MLP, "smem");
enum { BB_W = 0, BB_FULL = 2, BB_TMP = BB_FULL + 3, BB_OFULL = BB_FULL + 5, BB_SFREE = BB_OFULL,
       BB_STAT = BB_SFREE + 6, BB_ZFREE, BB_DONE = BB_ZFREE + 3,
       BB_EMPTY, BB_START = BB_EMPTY, BB_USED = BB_EMPTY + 2, BB_NUM = BB_USED + 3 };
enum { NB_PP = 1, NB_H = 3, NB_END = 4, NB_END2 = 5, NB_STAGED = 6, NB_FREE = 8, NB_EARLY = 10, NB_LAST = 11 };

#define DESC_LO(off) (((SMEM0 + (off)) >> 4) | (1u << 16))

__device__ __forceinline__ uint32_t ld_relaxed(const uint32_t* p) { uint32_t v; asm volatile("ld.relaxed.gpu.global.b32 %0, [%1];" : "=r"(v) : "l"(p) : "memory"); return v; }
__device__ __forceinline__ int fmask(int r) { return (r < NSEG) | ((r >= LAG && r < NSTEP) << 1); }
__device__ __forceinline__ int bmask(int r) { return (r <= NSEG) | ((r >= LAG) << 1); }
__device__ __forceinline__ uint32_t rtarget(int mask) { return mask == 3 ? 64 : 32; }
__device__ __forceinline__ void warp_signal(uint32_t* p, int lane) {
  __syncwarp();
  asm volatile("{\n.reg .pred q;\nsetp.eq.u32 q, %1, 0;\n@q red.release.gpu.global.add.u32 [%0], 1;\n}" :: "l"(p), "r"(lane) : "memory");
}
__device__ __forceinline__ uint32_t pack2h(float lo, float hi) { uint32_t r; asm("cvt.rn.f16x2.f32 %0, %1, %2;" : "=r"(r) : "f"(hi), "f"(lo)); return r; }
template <bool H> __device__ __forceinline__ uint32_t pk(float lo, float hi) { return H ? pack2h(lo, hi) : pack2(lo, hi); }
template <int N, bool H> __device__ __forceinline__ void stage_out(const float* d, uint32_t dst, int warp, int lane) {
  const uint32_t sa = dst + ((lane >> 4) * 8 + (lane & 7)) * 128 + (((2 * warp + ((lane >> 3) & 1)) ^ (lane & 7)) << 4);
#pragma unroll
  for (int m = 0; m < N / 16; m++)
    stsm4t(sa + m * 2048, pk<H>(d[8 * m], d[8 * m + 1]), pk<H>(d[8 * m + 2], d[8 * m + 3]), pk<H>(d[8 * m + 4], d[8 * m + 5]), pk<H>(d[8 * m + 6], d[8 * m + 7]));
}
template <int N> __device__ __forceinline__ void acc_live(float* d) {
#pragma unroll
  for (int i = 0; i < N / 2; i++) asm volatile("" : "+f"(d[i]) :: "memory");
}
struct Ring {
  uint32_t sl, ph;
  template <int NS> __device__ __forceinline__ void step() { if (++sl == NS) { sl = 0; ph ^= 1; } }
};

#define LOCKSTEP 0
#define KOFF(x) (DESC_LO(BO_O) + ((x) >> 2) * (N * 8) + ((x) & 3) * 2)
template <int N, int P>
__device__ __forceinline__ void op_pass(const uint32_t* W, uint32_t bar, Dsc alo, Dsc blo, Dsc xlo, bool x2, Ring& rg, int wg, int warp, int lane, int r) {
  float acc[N / 2];
  blo.e = xlo.e = fresh<P + N / 64 * 5>(r);
  const Dsc tlo = blo + uni(rg.sl) * (OP_SLOT / 16);
  if (P == 0) mbar_waitu(bar + 8 * BB_OFULL, r & 1);
  CTS(5 * P);
  if (!LOCKSTEP || P > 1 || P == wg) bar_sync(NB_PP + wg, 256);
  wg_fence();
#define OP_R(x) MM<N>::template rs<KOFF(4 * (x >> 1) + (x & 1)), (x != 0)>(acc, W + 32 * P + 4 * x, blo);
#define OP_S(x) MM<N>::template ss<DESC_LO(BO_RES) + (6 * P + x) * 128, KOFF(4 * (x >> 1) + 2 + (x & 1)), 1>(acc, alo, blo);
#define OP_T(x) MM<N>::template ss<DESC_LO(BO_RING_OP) + x * 128, KOFF(14 + x), 1>(acc, tlo, blo);
  OP_R(0) OP_S(0) OP_R(1) OP_S(1) OP_R(2) OP_S(2) OP_R(3) OP_S(3)
  if (P == 0) mbar_waitu(bar + 8 * (BB_OFULL + 1), r & 1);
  if (P == 4) wg_commit();
  OP_R(4) OP_S(4) OP_R(5) OP_S(5)
  if (P == 1 && x2) MM<N>::template ss<DESC_LO(BO_RES) + 30 * 128, KOFF(20), 1>(acc, alo, xlo);
  if (P == 4) { wg_commit(); wg_wait<1>(); bar_arrive(NB_EARLY, 288); CTS(21); wg_fence(); }
  mbar_waitu(bar + 8 * (BB_FULL + rg.sl), rg.ph);
  OP_R(6) OP_T(0) OP_R(7) OP_T(1)
  if (P == 0) mbar_waitu(bar + 8 * (BB_OFULL + 2), r & 1);
  OP_T(2) OP_T(3)
  if (P == 0) MM<N>::template rs<KOFF(20), 1>(acc, W + 160, xlo);
  OP_T(4) OP_T(5)
  wg_commit();
  if (!LOCKSTEP || P) bar_arrive(NB_PP + 1 - wg, 256);
  CTS(5 * P + 2);
  bar_sync(NB_FREE + wg, 160);
  wg_wait<0>();
  acc_live<N>(acc);
  if (P == 4) bar_arrive(NB_LAST, 288);
  mbar_arrive_if(lane == 0, bar + 8 * (BB_USED + rg.sl));
  CTS(5 * P + 3);
  stage_out<N, false>(acc, SMEM0 + BO_STG + wg * 8192, warp, lane);
  bar_arrive(NB_STAGED + wg, 160);
  CTS(5 * P + 4);
  rg.step<NS_OP>(); rg.step<NS_OP>();
}
template <int N>
__device__ __forceinline__ void op_round(const uint32_t* W, uint32_t bar, Dsc alo, Dsc blo, Dsc xlo, bool x2, Ring& rg, int wg, int warp, int lane, int r) {
  op_pass<N, 0>(W, bar, alo, blo, xlo, x2, rg, wg, warp, lane, r);
  op_pass<N, 1>(W, bar, alo, blo, xlo, x2, rg, wg, warp, lane, r);
  op_pass<N, 2>(W, bar, alo, blo, xlo, x2, rg, wg, warp, lane, r);
  op_pass<N, 3>(W, bar, alo, blo, xlo, x2, rg, wg, warp, lane, r);
  op_pass<N, 4>(W, bar, alo, blo, xlo, x2, rg, wg, warp, lane, r);
}
__device__ __forceinline__ void carry_in(uint32_t sb, int wg, int warp, int lane) {
  const int row = (lane >> 1) & 3;
  if (lane < 16) {
    const uint4 v = lds128(sb + BO_CARRY + (wg * 4 + warp) * 256 + lane * 16);
    sts128(sb + BO_H + wg * 8192 + (lane >> 3) * 4096 + row * 128 + (((2 * warp + (lane & 1)) ^ row) << 4), v.x, v.y, v.z, v.w);
  }
  __syncwarp();
}
#define STAGGER 0
template <int N, int Z>
__device__ __forceinline__ void p1_pair(float* acc, const uint32_t* W, uint32_t bar, Dsc alo, Dsc blo, int lane, int r) {
  blo.e = fresh<10 + Z / 3 + N / 64 * 2>(r);
  mbar_waitu(bar + 8 * (BB_FULL + Z), r & 1);
  CTS(40 + Z);
  wg_fence();
#define P1_B(k) \
  MM<N, true>::template rs<DESC_LO(BO_RING_MLP) + (2 * Z % 3) * 1024 + k * 512, (2 * Z + k != 0)>(acc, W + 16 * Z + 8 * k, blo); \
  MM<N, true>::template ss<DESC_LO(BO_W1) + (2 * Z + k) * 512, DESC_LO(BO_RING_MLP) + (2 * Z % 3) * 1024 + k * 512 + 4, 1>(acc, alo, blo); \
  MM<N, true>::template rs<DESC_LO(BO_RING_MLP) + (2 * Z % 3) * 1024 + k * 512 + 2, 1>(acc, W + 16 * Z + 8 * k + 4, blo); \
  MM<N, true>::template ss<DESC_LO(BO_W1) + (2 * Z + k) * 512 + 128, DESC_LO(BO_RING_MLP) + (2 * Z % 3) * 1024 + k * 512 + 6, 1>(acc, alo, blo);
  P1_B(0)
  if (Z == 1 || Z == 2) { wg_commit(); wg_wait<1>(); mbar_arrive_if(lane == 0, bar + 8 * (BB_EMPTY + Z - 1)); wg_fence(); }
  P1_B(1)
  wg_commit();
}
template <int N>
__device__ __forceinline__ void phase1(const uint32_t* W, uint32_t sb, Dsc alo, Dsc blo, int half, int wg, int warp, int lane, int off, int r) {
  float acc[N / 2];
  const uint32_t bar = sb + BO_BAR;
  CTS(30);
  p1_pair<N, 0>(acc, W, bar, alo, blo, lane, r);
  p1_pair<N, 1>(acc, W, bar, alo, blo, lane, r);
  p1_pair<N, 2>(acc, W, bar, alo, blo, lane, r);
  mbar_waitu(bar + 8 * (BB_SFREE + 4 + wg), (r + 1) & 1);
  carry_in(sb, wg, warp, lane);
  if (STAGGER && wg) bar_sync(NB_PP + 1, 256);
  p1_pair<N, 3>(acc, W, bar, alo, blo, lane, r);
  p1_pair<N, 4>(acc, W, bar, alo, blo, lane, r);
  if (STAGGER && !wg) bar_arrive(NB_PP + 1, 256);
  const int c = (lane >> 3) & 1, i0 = (lane >> 4) * 8 + (lane & 7) + off;
  uint32_t a0 = sb + BO_H + wg * 8192 + half * 4096 + i0 * 128 + (((2 * warp + c) ^ (i0 & 7)) << 4);
  uint32_t a1 = i0 >= 16 ? sb + BO_CARRY + (wg * 4 + warp) * 256 + half * 128 + (i0 - 16) * 32 + c * 16 : a0 + 2048, a3 = a1 + (i0 >= 16 ? 128 : 4096);
  asm volatile("" : "+r"(a0), "+r"(a1), "+r"(a3));
  mbar_waitu(bar + 8 * BB_STAT, r & 1);
  const uint32_t sa = sb + BO_STAT + half * 128 + (lane & 3) * 32;
  uint4 t[2] = {lds128(sa), lds128(sa + 16)};
  wg_wait<0>();
  acc_live<N>(acc);
  CTS(32);
#pragma unroll
  for (int m = 0; m < N / 16; m++) {
    const float s0 = __uint_as_float(t[m & 1].x), s1 = __uint_as_float(t[m & 1].y), s2 = __uint_as_float(t[m & 1].z), s3 = __uint_as_float(t[m & 1].w);
    float* d = acc + 8 * m;
    d[0] *= s0; d[1] *= s1; d[2] *= s0; d[3] *= s1; d[4] *= s2; d[5] *= s3; d[6] *= s2; d[7] *= s3;
    if (m + 2 < N / 16) t[m & 1] = lds128(sa + 128 + m * 16);
#pragma unroll
    for (int j = 0; j < 8; j++) d[j] = gelu2(d[j]);
  }
#pragma unroll
  for (int m = 0; m < N / 16; m++)
    stsm4t(m == 1 ? a1 : m == 3 ? a3 : a0 + m * 2048, pack2(acc[8 * m], acc[8 * m + 1]), pack2(acc[8 * m + 2], acc[8 * m + 3]), pack2(acc[8 * m + 4], acc[8 * m + 5]), pack2(acc[8 * m + 6], acc[8 * m + 7]));
}
template <int N, int P>
__device__ __forceinline__ void p2_pass(const uint32_t* W, uint32_t bar, Dsc alo, Dsc blo, int wg, int warp, int lane, int r) {
  float acc[N / 2];
  blo.e = fresh<P + N / 64 * 5>(r);
  CTS(5 * P);
  if (P || wg) bar_sync(NB_PP + wg, 256);
  wg_fence();
  MM<N>::template rs<DESC_LO(BO_H) + 0, 0>(acc, W + 80 + 16 * P, blo); MM<N>::template ss<DESC_LO(0) + P * 1024, DESC_LO(BO_H) + 512, 1>(acc, alo, blo);
  MM<N>::template rs<DESC_LO(BO_H) + 2, 1>(acc, W + 84 + 16 * P, blo); MM<N>::template ss<DESC_LO(0) + P * 1024 + 128, DESC_LO(BO_H) + 514, 1>(acc, alo, blo);
  MM<N>::template rs<DESC_LO(BO_H) + 4, 1>(acc, W + 88 + 16 * P, blo); MM<N>::template ss<DESC_LO(0) + P * 1024 + 512, DESC_LO(BO_H) + 516, 1>(acc, alo, blo);
  MM<N>::template rs<DESC_LO(BO_H) + 6, 1>(acc, W + 92 + 16 * P, blo); MM<N>::template ss<DESC_LO(0) + P * 1024 + 640, DESC_LO(BO_H) + 518, 1>(acc, alo, blo);
  wg_commit();
  if (P < 4 || !wg) bar_arrive(NB_PP + 1 - wg, 256);
  CTS(5 * P + 2);
  if (P == 2 || P == 3) mbar_waitu(bar + 8 * (BB_SFREE + 2 * (P - 2) + wg), r & 1);
  wg_wait<0>();
  acc_live<N>(acc);
  if (P == 4) bar_sync(NB_H, 256);
  CTS(5 * P + 3);
  stage_out<N, true>(acc, SMEM0 + (P == 4 ? BO_H : BO_RING_MLP + (2 - (P & 1)) * 16384) + wg * 8192, warp, lane);
  bar_arrive(NB_STAGED + (P == 4 ? 4 : 2 * (P & 1)) + wg, 160);
  CTS(5 * P + 4);
}
template <int N>
__device__ __forceinline__ void phase2(const uint32_t* W, uint32_t bar, Dsc alo, Dsc blo, int wg, int warp, int lane, int r) {
  p2_pass<N, 0>(W, bar, alo, blo, wg, warp, lane, r);
  p2_pass<N, 1>(W, bar, alo, blo, wg, warp, lane, r);
  p2_pass<N, 2>(W, bar, alo, blo, wg, warp, lane, r);
  p2_pass<N, 3>(W, bar, alo, blo, wg, warp, lane, r);
  p2_pass<N, 4>(W, bar, alo, blo, wg, warp, lane, r);
}

__device__ __forceinline__ void ldg4(uint32_t* v, const void* p) {
  asm volatile("ld.relaxed.gpu.global.v4.u32 {%0,%1,%2,%3}, [%4];" : "=r"(v[0]), "=r"(v[1]), "=r"(v[2]), "=r"(v[3]) : "l"(p) : "memory"); }
__device__ __forceinline__ void stg4(void* p, const uint32_t* v) {
  asm volatile("st.global.v4.u32 [%0], {%1,%2,%3,%4};" :: "l"(p), "r"(v[0]), "r"(v[1]), "r"(v[2]), "r"(v[3]) : "memory"); }
struct RowPtr {
  unsigned char *p, *q, *t;
  __device__ __forceinline__ void ld(uint32_t* v, int o) const {
    ldg4(v, p + o); ldg4(v + 4, q + o);
    asm volatile("ld.relaxed.gpu.global.v2.u32 {%0,%1}, [%2];" : "=r"(v[8]), "=r"(v[9]) : "l"(t + o) : "memory");
  }
  __device__ __forceinline__ void st(const uint32_t* w, int o) const {
    stg4(p + o, w); stg4(q + o, w + 4);
    asm volatile("st.global.v2.u32 [%0], {%1,%2};" :: "l"(t + o), "r"(w[8]), "r"(w[9]) : "memory");
  }
};
__device__ __forceinline__ RowPtr row_img(int r, int n, int lane) {
  unsigned char* b = &g_acc[0][r % RD][n * 128];
  unsigned char* p = b + (uint32_t)((lane >> 3) * 8192 + (((lane ^ n) & 7) << 4));
  return {p, p + 32768, b + (uint32_t)(65536 + (lane >> 4) * 8192 + ((((lane >> 1) ^ n) & 7) << 4) + (lane & 1) * 8)};
}
__device__ __forceinline__ RowPtr row_ext(const void* lin, bool xn, int layer, int tok, int lane) {
  unsigned char* b = xn ? reinterpret_cast<unsigned char*>(&g_xn[layer][0]) + (uint32_t)((tok >> 5) * 40960 + ((tok >> 3) & 3) * 2560 + (tok & 7) * 32)
                        : (unsigned char*)lin + (uint32_t)(tok * 1280);
  const uint32_t o = (lane >> 1) * 256 + ((lane ^ (tok >> 2)) & 1) * 16;
  return {b + (uint32_t)(xn ? o + (lane >= 20 ? 7680 : 0) : lane * 16),
          b + (uint32_t)(xn ? o + 4096 + 7680 + (lane >= 8 ? 7680 : 0) + (lane >= 28 ? 7680 : 0) : lane * 16 + 512),
          b + (uint32_t)(xn ? (lane >> 2) * 256 + ((lane & 3) ^ ((tok >> 1) & 2)) * 8 + 8192 + 3 * 7680 : lane * 8 + 1024)};
}
__device__ __forceinline__ float2 h2f(uint32_t w) {
  float2 f; asm("{\n.reg .f16 l, h;\nmov.b32 {l, h}, %2;\ncvt.f32.f16 %0, l;\ncvt.f32.f16 %1, h;\n}" : "=f"(f.x), "=f"(f.y) : "r"(w)); return f; }
__device__ __forceinline__ float rsq(float x) { float y; asm("rsqrt.approx.ftz.f32 %0, %1;" : "=f"(y) : "f"(x)); return y; }
__device__ __forceinline__ void red_if(uint32_t v, const void* a) {
  asm volatile("{\n.reg .pred q;\nsetp.ne.u32 q, %1, 0;\n@q red.relaxed.gpu.global.add.u32 [%0], %1;\n}" :: "l"(a), "r"(v) : "memory"); }
__device__ __forceinline__ uint32_t dep0(uint32_t w, int lane) { uint32_t z; asm volatile("shr.b32 %0, %1, %2;" : "=r"(z) : "r"(w), "r"(lane + 32)); return z; }
__device__ __forceinline__ int lane_of(uint32_t w) {
  int lane; asm volatile("{\n.reg .u32 t;\nmov.u32 t, %%laneid;\nshr.u32 %0, %1, 20;\nadd.u32 %0, %0, t;\n}" : "=r"(lane) : "r"(w)); return lane; }
#define BUF (RD * TILE_B)
__device__ __forceinline__ int await(uint32_t v, const uint32_t* p, uint32_t target, bool lazy) {
  int n = 0;
  while (!__all_sync(~0u, v >= target)) {
    if (lazy) __nanosleep(200);
    if (++n > SPIN_LIMIT) FAIL();
    v = ld_relaxed(p);
  }
  asm volatile("fence.acquire.gpu;" ::: "memory");
  return lane_of(v);
}
template <int W> __device__ __forceinline__ void sum2(float& s, float& q, int lane) {
  const bool up = lane & (W / 2);
  float e = (up ? q : s) + __shfl_xor_sync(~0u, up ? s : q, W / 2);
#pragma unroll
  for (int o = W / 4; o; o >>= 1) e += __shfl_xor_sync(~0u, e, o);
  const float f = __shfl_xor_sync(~0u, e, W / 2);
  s = up ? f : e; q = up ? e : f;
}
template <int TYPE>
__device__ __forceinline__ void rrow(int r, int row, int tok, int lane, const uint32_t* go, int role, const __nv_bfloat16* x) {
  const int half = TYPE ? 0 : row >> 5;
  float v[20];
  float2 st = make_float2(1.f, 0.f);
  {
    uint32_t a[10], c[10], u[10], sh = 16;
    if (TYPE == 2) row_img(r + RD - ((row & 31) < 2), (row & 32) + ((row - 2) & 31), lane).ld(u, 4 * BUF);
    else row_ext(x, half, 1, tok, lane).ld(u, 0);
    if (TYPE == 2 || (TYPE == 0 && half))
      asm volatile("ld.relaxed.gpu.global.v2.f32 {%0,%1}, [%2];" : "=f"(st.x), "=f"(st.y) : "l"(g_stat + tok) : "memory");
    RowPtr ap = row_img(r, row, lane);
    const uint32_t g0 = TYPE != 3 ? ld_relaxed(go) : 0;
    if (TYPE == 2) {
      ap.ld(c, 2 * BUF);
      uint32_t z = dep0(c[9], lane);
#pragma unroll
      for (int i = 0; i < 10; i++) {
        const float2 g = h2f(u[i] | z), h = h2f(c[i] | z);
        v[2 * i] = fmaf(h.x, 0.5f, g.x * st.x); v[2 * i + 1] = fmaf(h.y, 0.5f, g.y * st.x);
        if (i & 1) z = dep0(__float_as_uint(v[2 * i]) | __float_as_uint(v[2 * i + 1]), lane);
      }
    }
    if (TYPE != 3) {
      asm volatile("" : "+l"(ap.p), "+l"(ap.t));
      ap.q = ap.p + 32768;
      lane = await(g0, go, NOP * NW12 * NW34, false); BTS2(r, 8 + 2 * TYPE); RTS(0);
      ap.ld(a, TYPE ? 3 * BUF : 0);
    }
    if (TYPE == 0) {
      ap.ld(c, BUF);
      const uint32_t one = 0x3f803f80u | dep0(c[9], lane);
#pragma unroll
      for (int i = 0; i < 10; i++) asm volatile("fma.rn.bf16x2 %0, %0, %1, %2;" : "+r"(a[i]) : "r"(one), "r"(c[i]));
      sh |= dep0(a[9], lane);
    }
    const float k = TYPE == 2 ? __uint_as_float(0x3f000000u | dep0(a[9], lane)) : 0.f;
#pragma unroll
    for (int i = 0; i < 10; i++) {
      if (TYPE == 2) { const float2 h = h2f(a[i]); v[2 * i] = fmaf(h.x, k, v[2 * i]); v[2 * i + 1] = fmaf(h.y, k, v[2 * i + 1]); continue; }
      float p = __uint_as_float(u[i] << sh), q = __uint_as_float(u[i] & (0xffffu << sh));
      if (TYPE == 0) { p = fmaf(p, st.x, bf_lo(a[i])); q = fmaf(q, st.x, bf_hi(a[i])); }
      v[2 * i] = p; v[2 * i + 1] = q;
    }
  }
  RTSD(1, v[19]);
  float s = 0.f, q = 0.f;
#pragma unroll
  for (int i = 0; i < 5; i++) {
    s += (v[4 * i] + v[4 * i + 1]) + (v[4 * i + 2] + v[4 * i + 3]);
    q += fmaf(v[4 * i], v[4 * i], v[4 * i + 1] * v[4 * i + 1]) + fmaf(v[4 * i + 2], v[4 * i + 2], v[4 * i + 3] * v[4 * i + 3]);
  }
  sum2<32>(s, q, lane);
  const float mean = s * (1.f / DM), var = fmaxf(q * (1.f / DM) - mean * mean, 0.f), rs = rsq(var + 1e-5f), k = TYPE ? rs : 2.f * rs, mr = -mean * k;
  RTSD(2, rs);
  uint32_t w[10];
#pragma unroll
  for (int i = 0; i < 10; i++) w[i] = pk<TYPE == 0>(fmaf(v[2 * i], k, mr), fmaf(v[2 * i + 1], k, mr));
  if (TYPE) row_ext(nullptr, true, TYPE == 2, tok, lane).st(w, 0);
  else {
    row_img(r, row, lane).st(w, 4 * BUF);
    row_img(r + ((row & 31) >= 30), (row & 32) + ((row + 2) & 31), lane).st(w, 2 * BUF);
    if (lane == 1) g_st2[0][r % RD][row] = (__float_as_uint(0.5f * rsq(fmaf(var * rs, rs, 1e-5f))) & ~127u) | (r + 1);
  }
  if (TYPE != 3 && lane == 0) g_stat[tok] = make_float2((var + 1e-5f) * rs * (TYPE ? 1.f : 0.5f), mean + st.y);
}
__device__ __forceinline__ void r2rows(int r, int row, int lane) {
  const int n = row + (lane >> 4);
  const unsigned char* ap = &g_acc[2][r % RD][0] + (uint32_t)(n * 128 + ((lane >> 3) & 1) * 8192 + (((lane ^ n) & 7) << 4));
  uint32_t a[20];
#pragma unroll
  for (int i = 0; i < 5; i++) ldg4(a + 4 * i, ap + i * 16384);
  const uint32_t z = dep0(a[19], lane);
  float s = 0.f, q = 0.f, q2 = 0.f;
#pragma unroll
  for (int i = 0; i < 20; i++) { const float2 h = h2f(a[i] | z); s += h.x + h.y; q = fmaf(h.x, h.x, q); q2 = fmaf(h.y, h.y, q2); }
  q += q2;
  sum2<16>(s, q, lane);
  const float mean = s * (0.5f / DM), rs = rsq(fmaxf(q * (0.25f / DM) - mean * mean, 0.f) + 1e-5f);
  if ((lane & 15) == 0) asm volatile("st.relaxed.gpu.global.u32 [%0], %1;" :: "l"(&g_st2[1][r % RD][n]), "r"((__float_as_uint(0.5f * rs) & ~127u) | (r + 1)) : "memory");
}
__device__ __forceinline__ void r3rows(int r, int row, int tok, int lane, __nv_bfloat16* out) {
  const int n = row + (lane >> 4), m = 32 + ((n - 2) & 31);
  const unsigned char* ap = &g_acc[0][r % RD][0] + (uint32_t)(n * 128 + ((lane >> 3) & 1) * 8192 + (((lane ^ n) & 7) << 4));
  const unsigned char* zp = &g_acc[4][(r + RD - (row == 32)) % RD][0] + (uint32_t)(m * 128 + ((lane >> 3) & 1) * 8192 + (((lane ^ m) & 7) << 4));
  unsigned char* op = reinterpret_cast<unsigned char*>(out) + (uint32_t)((tok + (lane >> 4)) * 1280 + (lane & 15) * 16);
  float2 st;
  asm volatile("ld.relaxed.gpu.global.v2.f32 {%0,%1}, [%2];" : "=f"(st.x), "=f"(st.y) : "l"(g_stat + tok + (lane >> 4)) : "memory");
#pragma unroll 1
  for (int i0 = 0; i0 < 3; i0++) {
    uint32_t a[8], c[8], u[8];
#pragma unroll
    for (int i = 0; i < 2; i++) { ldg4(a + 4 * i, ap + 3 * BUF + i * 16384); ldg4(c + 4 * i, ap + 2 * BUF + i * 16384); ldg4(u + 4 * i, zp + i * 16384); }
    uint32_t z = dep0(u[7], lane);
#pragma unroll
    for (int i = 0; i < 8; i++) {
      const float2 h = h2f(a[i] | z), e = h2f(c[i] | z), g = h2f(u[i] | z);
      a[i] = pack2(fmaf(h.x + e.x, 0.5f, fmaf(g.x, st.x, st.y)), fmaf(h.y + e.y, 0.5f, fmaf(g.y, st.x, st.y)));
      if (i & 1) z = dep0(a[i], lane);
    }
    if (i0 < 2) stg4(op, a);
    stg4(op + 256, a + 4);
    ap += 32768 >> i0; zp += 32768 >> i0; op += 512 >> i0;
  }
}
template <int TYPE>
__device__ __forceinline__ void rloop(int row, int cp, int role, const __nv_bfloat16* x, __nv_bfloat16* out) {
  constexpr int ST = TYPE == 4 ? 2 : TYPE;
  const int r0 = row & 32 ? LAG : 0;
  uint32_t v = 0;
#pragma unroll 1
  for (int r = r0; r < r0 + NSEG + (TYPE > 0); r++) {
    const int tok = (r - r0) * 32 + (row & 31) - (TYPE ? 2 : 0);
    const bool valid = TYPE == 0 || (unsigned)tok < S_LEN;
    const uint32_t* go = &g_f[F_R1 + 4 * ST + cp][r];
    const uint32_t* first = TYPE == 2 ? &g_f[F_R2 + cp][r] : TYPE ? go : (const uint32_t*)&g_xready[NSEG + r - r0][0];
    if constexpr (TYPE == 1 || TYPE == 4) {
      const int lane = await(v, go, NOP * NW12 * NW34, false);
      BTS2(r, 8 + 2 * ST); RTS(0);
      if (TYPE == 1) { r2rows(r, row, lane); BTS2(r, 11); continue; }
      if (valid) r3rows(r, row, tok, lane, out);
    } else {
      if (TYPE || row >= 32) await(v, first, TYPE ? NOP * NW12 * NW34 : 32, true);
      if (valid) rrow<TYPE>(r, row, tok, lane_of(r), go, role, x);
    }
    const int lane = lane_of(r);
    const void* f = lane ? (const void*)&g_xready[NSEG + (tok >> 5)][0] : (const void*)&g_f[TYPE ? F_DONE : F_Z][r];
    asm volatile("" : "+l"(f));
    __syncwarp();
    RTS(3);
    v = ld_relaxed(first + (TYPE ? 1 : 8));
    asm volatile("fence.release.gpu;" ::: "memory");
    RTS(4);
    red_if(lane == 0 || (TYPE == 2 && lane == 1 && valid) ? (TYPE & 5 ? 2 : 1) : 0, f);
    RTS(5);
    RTS_OUT();
    BTS2(r, 9 + 2 * ST);
  }
}

#define SINGLE_OP 3
#define SINGLE_W 0
#define W_DELAY 0
#define BULK_ADD(T, dst, src, len) asm volatile("{\n.reg .pred e;\nelect.sync _|e, 0xffffffff;\n@e cp.reduce.async.bulk.global.shared::cta.bulk_group.add.noftz." T " [%0], [%1], %2;\n}" \
                                               :: "l"(dst), "r"(src), "r"(len) : "memory")
#define COMMIT() asm volatile("cp.async.bulk.commit_group;" ::: "memory")
#define DRAINED(n) do { asm volatile("cp.async.bulk.wait_group.read " #n ";" ::: "memory"); __syncwarp(); } while (0)
#define WRITTEN() do { asm volatile("cp.async.bulk.wait_group 0;\nfence.proxy.async.global;" ::: "memory"); __syncwarp(); } while (0)
__device__ __forceinline__ void wait_flags(const uint32_t* p, uint32_t target) {
  int n = 0;
  while (!__all_sync(~0u, ld_relaxed(p) >= target)) { if (++n > SPIN_LIMIT) FAIL(); }
  asm volatile("fence.acquire.gpu;" ::: "memory");
  asm volatile("fence.proxy.async.global;" ::: "memory");
}
__global__ void __launch_bounds__(512, 1) bworker_kernel(const __grid_constant__ BParams P) {
  extern __shared__ __align__(1024) unsigned char smem_raw[];
  const uint32_t sb = SMEM0, bar = sb + BO_BAR;
  const int wg = __shfl_sync(~0u, threadIdx.x >> 7, 0), warp = __shfl_sync(~0u, (threadIdx.x >> 5) & 3, 0);
  if (threadIdx.x == 0) {
    if (smem_u32(smem_raw) != SMEM0) FAIL();
    uint32_t smid; asm volatile("mov.u32 %0, %%smid;" : "=r"(smid));
    const uint32_t nb = ld_relaxed(&g_tpc[(smid >> 1) & 127]);
    const bool single = nb > 1, far = nb == 0 && (smid < 64 || smid >= 124);
    int kind = far || (single && atomicAdd(&g_f[F_MISC][35], 1u) < SINGLE_OP) ? 0 : single ? 1 + SINGLE_W : 1;
    int rc = single || (smid >> 1) == 16 || (smid >> 1) == 63 ? 1 : far ? 2 : 0;
    uint32_t i = atomicAdd(&g_f[F_MISC][32 + kind], 1u), o = atomicAdd(&g_f[F_MISC][36 + rc], 1u);
    while (i >= (kind == 0 ? NOP : kind == 1 ? NW12 : NW34)) { kind = (kind + 1) % 3; i = atomicAdd(&g_f[F_MISC][32 + kind], 1u); }
    while (o >= (rc == 0 ? 16 : rc == 1 ? 8 : 12)) { rc = (rc + 1) % 3; o = atomicAdd(&g_f[F_MISC][36 + rc], 1u); }
    sts64(sb + BO_BOX, i + (kind == 0 ? 0 : kind == 1 ? NOP : NOP + NW12), o + (rc ? 8 + 8 * rc : 0));
    for (int k = 0; k < BB_NUM; k++) mbar_init(bar + 8 * k, k >= BB_USED ? 4 : k >= BB_EMPTY ? 8 : k >= BB_ZFREE && kind ? 2 : 1);
    asm volatile("fence.mbarrier_init.release.cluster;" ::: "memory");
  }
  if (threadIdx.x < 128) sts128(sb + BO_CARRY + threadIdx.x * 16, 0u, 0u, 0u, 0u);
  auto ln0 = [&](int t) {
    const int lane = lane_of(t);
    if (lane < 20 && t + 128 < S_LEN) asm volatile("prefetch.global.L2 [%0];" :: "l"(P.x + (t + (t < 4 * NBC ? 4 * NBC : 128)) * DM + (lane >> 1) * 64));
    rrow<3>(0, 0, t, lane, nullptr, 0, P.x);
    __syncwarp();
    asm volatile("fence.release.gpu;" ::: "memory");
    red_if(lane == 0, &g_xready[t >> 5][0]);
  };
  if (wg == 2) ln0(blockIdx.x * 4 + warp);
  fence_async();
  __syncthreads();
  const int role = uni(lds32(sb + BO_BOX));
  if (threadIdx.x < 32) BTS(94, 1);
  const bool op = role < NOP, w12 = role < NOP + NW12;
  const int j = op ? role : w12 ? role - NOP : role - NOP - NW12;
  const int rot = op ? (j ? 2 * ((j + 1) % 5) : 0) : 2 * (j % 5);
  if (wg == 3) {
    asm volatile("setmaxnreg.dec.sync.aligned.u32 24;");
    LANE_INIT();
    if (warp < 2) {
      auto announce = [&](int r) {
        const uint32_t* f = &g_f[(op ? F_R1 : w12 ? F_R2 : F_R3) + (lane & 3)][r];
        asm volatile("" : "+l"(f));
        if (warp == 0) { mbar_arrive_if(lane == 0, bar + 8 * BB_DONE); return; }
        mbar_waitw(bar + 8 * BB_DONE, r & 1);
        PTS(60);
        asm volatile("fence.release.gpu;" ::: "memory");
        red_if(lane >= 4 ? 0 : op ? NW12 * NW34 : w12 ? NOP * NW34 : NOP * NW12, f);
        PTS(61);
        BTS(r, 4);
      };
      if (op) {
        int mt = rot + warp;
        bar_arrive(NB_FREE + warp, 160);
#pragma unroll 1
        for (int r = 0; r < NSTEP; r++) {
          const uint32_t len = fmask(r) == 3 ? 8192 : 4096;
          unsigned char* acc = &g_acc[j & 1][r % RD][fmask(r) == 2 ? 4096 : 0];
#pragma unroll 1
          for (int p = 0; p < 5; p++) {
            bar_sync(NB_STAGED + warp, 160);
            PTS(50 + 2 * p + warp);
            fence_async();
            BULK_ADD("bf16", acc + mt * 8192, sb + BO_STG + warp * 8192, len);
            COMMIT();
            PTS(64 + 50 + 2 * p + warp);
            mt = mt >= 8 ? mt - 8 : mt + 2;
            DRAINED(0);
            bar_arrive(NB_FREE + warp, 160);
          }
          WRITTEN();
          announce(r);
        }
      } else {
#pragma unroll 1
        for (int r = 0; r < NR; r++) {
          const uint32_t len = bmask(r) == 3 ? 8192 : 4096;
          unsigned char* acc = &g_acc[w12 ? 2 : 3][r % RD][bmask(r) == 2 ? 4096 : 0];
          int mt = rot + warp;
#pragma unroll 1
          for (int p = 0; p < 5; p++) {
            bar_sync(NB_STAGED + (p == 4 ? 4 : 2 * (p & 1)) + warp, 160);
            PTS(50 + 2 * p + warp);
            fence_async();
            BULK_ADD("f16", acc + mt * 8192, sb + (p == 4 ? BO_H : BO_RING_MLP + (2 - (p & 1)) * 16384) + warp * 8192, len);
            COMMIT();
            PTS(64 + 50 + 2 * p + warp);
            mt = mt >= 8 ? mt - 8 : mt + 2;
            if (p == 4) break;
            DRAINED(1);
            mbar_arrive_if(lane == 0, bar + 8 * (p == 1 || p == 2 ? BB_SFREE + 2 * (p - 1) + warp : BB_ZFREE + (p >> 1)));
            if (p == 3) { DRAINED(0); mbar_arrive_if(lane == 0, bar + 8 * (BB_ZFREE + 2)); }
          }
          WRITTEN();
          mbar_arrive_if(lane == 0, bar + 8 * (BB_SFREE + 4 + warp));
          announce(r);
        }
      }
    } else {
      if (op && warp == 2) {
        unsigned char* wt = g_wt + j * (10 * OP_SLOT);
#pragma unroll 1
        for (int m0 = 0; m0 < 10; m0 += 3) {
          const int nu = m0 < 9 ? 9 : 3;
          mbar_expect_if(lane == 0, bar + 8 * BB_TMP, nu * 4096);
#pragma unroll 1
          for (int k = 0; k < nu; k++) tma2d_e(sb + BO_RING_OP + k * 4096, &P.wmap[0], (m0 + k / 3) * 64, 320 * j + 224 + 32 * (k % 3), bar + 8 * BB_TMP);
          mbar_waitw(bar + 8 * BB_TMP, m0 & 1);
          bulk_s2g_e(wt + m0 * OP_SLOT, sb + BO_RING_OP, nu * 4096);
          COMMIT();
          WRITTEN();
        }
        asm volatile("fence.acq_rel.gpu;" ::: "memory");
        int sl = 0, ph = 1, mt = rot;
#pragma unroll 1
        for (int r = -1; r < NSTEP; r++) {
#pragma unroll 1
          for (int n = r < 0 ? 7 : 0; n < (r + 1 < NSTEP ? 10 : 7); n++) {
            mbar_waitw(bar + 8 * (BB_USED + sl), ph);
            mbar_expect_if(lane == 0, bar + 8 * (BB_FULL + sl), OP_SLOT);
            bulk_g2s_e(sb + BO_RING_OP + sl * OP_SLOT, wt + mt * OP_SLOT, OP_SLOT, bar + 8 * (BB_FULL + sl));
            if (++sl == 3) { sl = 0; ph ^= 1; }
            mt = mt == 9 ? 0 : mt + 1;
          }
        }
      } else if (op) {
        mbar_waitw(bar + 8 * BB_START, 0);
#pragma unroll 1
        for (int r = 0; r < NSTEP; r++) {
          const int rb = r - RD + 2;
          const uint32_t len = fmask(r) == 3 ? 8192 : 4096;
          const unsigned char* src = g_o + (uint32_t)(r % RO * (96 * 8192) + 5 * j * len);
          wait_flags(lane < 2 ? &g_f[F_O + (lane ? NOP : j)][r] : rb >= 0 ? &g_f[F_DONE][rb] : &g_f[F_MISC][0],
                     lane < 2 ? (lane ? 1 : 5) : rb >= 0 ? rtarget(bmask(rb)) : NBC * 8);
          PTS1(35);
          if (r) bar_sync(NB_EARLY, 288);
          if (r == LAG) bar_sync(NB_LAST, 288);
          mbar_expect_if(lane < 3, bar + 8 * (BB_OFULL + lane), 2 * len);
          bulk_g2s_e(sb + BO_O, src, 2 * len, bar + 8 * BB_OFULL);
          PTS(62); PTS1(38);
          if (r && r != LAG) bar_sync(NB_LAST, 288);
          bulk_g2s_e(sb + BO_O + 2 * len, src + 2 * len, 2 * len, bar + 8 * (BB_OFULL + 1));
          bulk_g2s_e(sb + BO_O + 4 * len, src + 4 * len, len, bar + 8 * (BB_OFULL + 2));
          bulk_g2s_e(sb + BO_O + 5 * len, src + (95 - 5 * j) * len, len, bar + 8 * (BB_OFULL + 2));
          PTS1(64 + 35);
          BTS(r, 0);
        }
      } else if (warp == 2) {
#pragma unroll 1
        for (int r = 0; r < NR; r++) {
          const int mk = w12 ? fmask(r) : bmask(r);
          if (mk) {
            const unsigned char* src = &g_acc[w12 ? 4 : 2][r % RD][mk == 2 ? 4096 : 0];
            wait_flags(w12 ? &g_f[F_Z][r] : lane && r >= 2 ? &g_f[F_R3 + (j & 3)][r - 2] : &g_f[F_R2 + (j & 3)][r], w12 ? rtarget(mk) : NOP * NW12 * NW34);
#pragma unroll 1
            for (int z = 0; z < 5; z++) {
              const uint32_t fb = bar + 8 * (BB_FULL + z), dst = sb + BO_RING_MLP + 2 * z % 3 * 16384 + (mk == 2 ? 4096 : 0);
              mbar_waitw(bar + 8 * (z < 3 ? BB_ZFREE + z : BB_EMPTY + z - 3), (r + (z < 3)) & 1);
              if (z == 0) PTS(62);
              mbar_expect_if(lane == 0, fb, mk == 3 ? 16384 : 8192);
              bulk_g2s_e(dst, src + z * 16384, mk == 3 ? 16384 : 4096, fb);
              if (mk != 3) bulk_g2s_e(dst + 8192, src + z * 16384 + 8192, 4096, fb);
              if (z == 0) BTS(r, 0);
            }
          }
          if (!w12) {
#pragma unroll 1
            for (int c = j; c < 120; c += NW34) bulk_s2g_e(&g_acc[c < 80 ? c / 40 : 3][(r + (c < 80 ? 0 : 2)) % RD][c % 40 * 2048], sb + BO_CARRY, 2048);
            COMMIT();
            WRITTEN();
          }
          mbar_waitw(bar + 8 * BB_DONE, (r + 1) & 1);
          mbar_arrive_if(lane == 0, bar + 8 * BB_DONE);
        }
      } else {
#pragma unroll 1
        for (int r = 0; r < (w12 ? NSTEP : NR); r++) {
          const bool idle = !((w12 ? fmask(r) : bmask(r)) >> (lane >> 4) & 1);
          uint32_t t0, t1;
          int n = 0;
          mbar_waitw(bar + 8 * BB_FULL, r & 1);
          do {
            asm volatile("ld.relaxed.gpu.global.v2.u32 {%0,%1}, [%2];" : "=r"(t0), "=r"(t1) : "l"(&g_st2[!w12][r % RD][2 * lane]) : "memory");
            if (++n > SPIN_LIMIT) FAIL();
          } while (!__all_sync(~0u, idle || (((t0 ^ (r + 1)) | (t1 ^ (r + 1))) & 127) == 0));
          sts64(sb + BO_STAT + (lane >> 4) * 128 + (lane & 3) * 32 + ((lane >> 2) & 3) * 8, t0, t1);
          __syncwarp();
          mbar_arrive_if(lane == 0, bar + 8 * BB_STAT);
          PTS(63);
        }
      }
    }
    bar_arrive(NB_END, 512);
  } else if (wg == 2) {
    asm volatile("setmaxnreg.dec.sync.aligned.u32 40;");
    const int ord = uni(lds32(sb + BO_BOX + 4));
    const int gw = ord < 16 ? warp * 16 + ord : ord < 24 ? 48 + warp * 8 + ord : 72 + warp * 12 + ord, row = gw < 64 ? gw : gw < 96 ? gw - 64 : gw < 128 ? 2 * gw - 192 : 2 * gw - 224;
    if (row >= 32) {
#pragma unroll 1
      for (int t = 4 * NBC + (gw < 64 ? gw - 32 : gw - 80); t < S_LEN; t += 64) ln0(t);
    }
    if (gw < 64) rloop<0>(row, gw & 3, role, P.x, P.out);
    else if (gw < 96) rloop<2>(row, gw & 3, role, P.x, P.out);
    else if (gw < 128) rloop<1>(row, gw & 3, role, P.x, P.out);
    else rloop<4>(row, gw & 3, role, P.x, P.out);
    asm volatile("griddepcontrol.wait;" ::: "memory");
    const int t = threadIdx.x & 127;
    for (int i = (blockIdx.x * 128 + t) * 4; i < 4 * NCL * 2560; i += NBC * 512)
      *reinterpret_cast<uint4*>(&g_part[0][0][0][0] + i) = make_uint4(0u, 0u, 0u, 0u);
    bar_sync(NB_END, 512);
    if (t == 0) {
      uint32_t n;
      asm volatile("atom.acq_rel.gpu.global.add.u32 %0, [%1], 1;" : "=r"(n) : "l"(&g_f[F_MISC][64]) : "memory");
      sts32(sb + BO_BOX, n);
    }
    bar_sync(NB_END2, 128);
    if (lds32(sb + BO_BOX) == NBC - 1) {
      for (int i = t; i < F_NUM * 24; i += 128) reinterpret_cast<uint4*>(&g_f[0][0])[i] = make_uint4(0u, 0u, 0u, 0u);
      g_xready[t][0] = 0; g_tpc[t] = 0;
    }
  } else {
    asm volatile("setmaxnreg.inc.sync.aligned.u32 224;");
    LANE_INIT();
    for (int i = blockIdx.x * 256 + threadIdx.x; i < 2 * (RD + 1) * TILE_B / 16; i += NBC * 256)
      reinterpret_cast<uint4*>(&g_acc[i < 2 * RD * TILE_B / 16 ? 0 : 1][0][0])[i] = make_uint4(0u, 0u, 0u, 0u);
    warp_signal(&g_f[F_MISC][0], lane);
    const int mt0 = (rot + wg) % 10;
    auto boxes = [&](int ss) {
      const int nb = op && ss ? 3 : 4;
      const uint32_t base = sb + (ss ? BO_RES + wg * OP_RES : wg * 83968);
      mbar_expect_if(warp == 0 && lane == 0, bar + 8 * (BB_W + wg), nb * 20480 + (op ? 2048 : 0));
      bar_sync(NB_H, 256);
      if (warp < nb) {
#pragma unroll 1
        for (int i = warp; i < 5 * nb; i += nb) {
          const int p = op ? i / nb : (i - 10) >> 1, mt = (mt0 + 2 * p) % 10;
          const bool first = !op && i < 10;
          tma2d_e(op || !ss ? base + i * 4096 : sb + (first ? BO_W1 : -81920) + (2 * i + wg) * 4096, &P.wmap[op ? 0 : (w12 ? 1 : 3) + !first], first ? 128 * j + 64 * wg : mt * 64,
                  op ? 320 * j + 64 * warp + 32 * ss : first ? 64 * i + 32 * ss : 128 * j + 32 * (i & 1) + 64 * ss, bar + 8 * (BB_W + wg));
        }
      }
      if (op && warp == 3) tma2d_e(base + nb * 20480, &P.wo16, (mt0 + 2 * ss) % 10 * 64, 95 * 64 + (j + 1) / 5 * 16, bar + 8 * (BB_W + wg));
      mbar_waitw(bar + 8 * (BB_W + wg), ss);
    };
    if (W_DELAY) __nanosleep(W_DELAY);
    uint32_t W[164];
    boxes(0);
    load_w<41>(W, sb + wg * 83968, warp, lane);
    fence_async();
    boxes(1);
    if (!op) {
      float cs[2] = {0.f, 0.f};
      const uint32_t a0 = sb + BO_W1 + wg * 4096 + ((lane >> 4) * 8 + (lane & 7)) * 128 + (((warp * 2 + ((lane >> 3) & 1)) ^ (lane & 7)) << 4);
#pragma unroll
      for (int i = 0; i < 80; i++) cs[i & 1] += bf_lo(W[i]) + bf_hi(W[i]);
#pragma unroll 1
      for (int i = 0; i < 40; i++) {
        uint32_t t[4];
        const uint32_t ad = a0 + (i % 20 >> 1) * 8192 + (i & 1) * 2048;
        ldsm4t(t[0], t[1], t[2], t[3], ad);
#pragma unroll
        for (int k = 0; k < 4; k++) {
          if (i < 20) cs[k & 1] += bf_lo(t[k]) + bf_hi(t[k]);
          t[k] = pack2h(bf_lo(t[k]) - cs[k & 1], bf_hi(t[k]) - cs[k & 1]);
        }
        if (i >= 20) stsm4t(ad, t[0], t[1], t[2], t[3]);
        if (i == 19) {
#pragma unroll
          for (int k = 0; k < 2; k++) { cs[k] += __shfl_xor_sync(~0u, cs[k], 1); cs[k] += __shfl_xor_sync(~0u, cs[k], 2); cs[k] *= 1.f / DM; }
        }
      }
      const uint32_t z = dep0(__float_as_uint(cs[0]), lane);
#pragma unroll
      for (int i = 0; i < 80; i++) W[i] = pack2h(bf_lo(W[i] | z) - cs[i & 1], bf_hi(W[i] | z) - cs[i & 1]);
      fence_async();
      bar_sync(NB_H, 256);
    }
    if (warp == 0) BTS(94, 6 + wg);
    const Dsc blo = {P.desc, 1}, alo = blo + wg * (op ? OP_RES / 16 : 256);
    if (op) {
      Ring rg = {(uint32_t)wg, 0};
      mbar_arrive_if(lane == 0, bar + 8 * BB_START);
      if (wg) bar_arrive(NB_PP, 256);
      const Dsc xlo = blo + (j + 1) / 5 * 2;
#pragma unroll 1
      for (int r = 0; r < NSTEP; r++) {
        asm volatile("" : "+r"(lane));
        if (fmask(r) == 3) op_round<64>(W, bar, alo, blo, xlo, j == 0, rg, wg, warp, lane, r);
        else op_round<32>(W, bar, alo, blo, xlo, j == 0, rg, wg, warp, lane, r);
        if (warp == 0) BTS(r, 2 + wg);
      }
    } else {
      const int q4 = (128 * j + 64 * wg + 16 * warp) / 160, off = w12 ? (0x0413 >> (4 * q4)) & 7 : 0;
#pragma unroll 1
      for (int r = 0; r < NR; r++) {
        asm volatile("" : "+r"(lane));
        const int bm = bmask(r), fm = w12 ? fmask(r) : bm;
        if (fm == 3) phase1<64>(W, sb, alo, blo, 0, wg, warp, lane, off, r);
        else if (fm) phase1<32>(W, sb, alo, blo + (fm >> 1) * 256, fm >> 1, wg, warp, lane, off, r);
        else { mbar_waitu(bar + 8 * (BB_SFREE + 4 + wg), (r + 1) & 1); carry_in(sb, wg, warp, lane); }
        CTS(33);
        fence_async();
        bar_sync(NB_H, 256);
        if (wg + warp == 0) BTS(r, 1);
        if (bm == 3) phase2<64>(W, bar, alo, blo, wg, warp, lane, r);
        else phase2<32>(W, bar, alo, blo + (bm >> 1) * 256, wg, warp, lane, r);
        if (warp == 0) BTS(r, 2 + wg);
      }
    }
    CTS_OUT();
    bar_arrive(NB_END, 512);
  }
}

typedef CUresult (*EncodeFn)(CUtensorMap*, CUtensorMapDataType, cuuint32_t, void*, const cuuint64_t*, const cuuint64_t*, const cuuint32_t*,
                             const cuuint32_t*, CUtensorMapInterleave, CUtensorMapSwizzle, CUtensorMapL2promotion, CUtensorMapFloatOOBfill);
static void make_map(EncodeFn fn, CUtensorMap* tm, const void* ptr, uint64_t cols, uint64_t rows, uint32_t bc, uint32_t br) {
  cuuint64_t dims[2] = {cols, rows}; cuuint64_t strides[1] = {cols * 2}; cuuint32_t box[2] = {bc, br}; cuuint32_t es[2] = {1, 1};
  fn(tm, CU_TENSOR_MAP_DATA_TYPE_BFLOAT16, 2, const_cast<void*>(ptr), dims, strides, box, es, CU_TENSOR_MAP_INTERLEAVE_NONE,
     CU_TENSOR_MAP_SWIZZLE_128B, CU_TENSOR_MAP_L2_PROMOTION_L2_256B, CU_TENSOR_MAP_FLOAT_OOB_FILL_NONE);
}
#define dbg_a_only 0
extern "C" void kernel_launch(void* const* d_in, const int* in_sizes, int n_in, void* d_out, int out_size) {
  void* fnp = nullptr; cudaDriverEntryPointQueryResult qr;
  cudaGetDriverEntryPoint("cuTensorMapEncodeTiled", &fnp, cudaEnableDefault, &qr);
  EncodeFn fn = (EncodeFn)fnp;
  cudaStream_t st = cudaStreamPerThread;
  cudaFuncSetAttribute(bworker_kernel, cudaFuncAttributeMaxDynamicSharedMemorySize, B_SMEM);
  {
    AMaps M;
    for (int i = 0; i < 3; i++) make_map(fn, &M.w16[i], d_in[2 + i], HD, DM, 64, 16);
    M.wv = (const __nv_bfloat16*)d_in[4];
    make_map(fn, &M.wo32, d_in[5], DM, HD, 64, 32);
    const uint32_t hi[5] = {dhi(TILE_SBO, 3), dhi(1024, 1), dhi(1024, 0), dhi(PL_SZ, 0), dhi(896, 0)};
    for (int i = 0; i < 5; i++) M.d[i] = (uint64_t)hi[i] << 32;
    cudaFuncSetAttribute(acore_kernel, cudaFuncAttributeMaxDynamicSharedMemorySize, A_SMEM);
    cudaFuncSetAttribute(acore_kernel, cudaFuncAttributeNonPortableClusterSizeAllowed, 1);
    cudaLaunchConfig_t cfg = {};
    cfg.gridDim = dim3(CL_SIZE * NCL); cfg.blockDim = dim3(512); cfg.dynamicSmemBytes = A_SMEM; cfg.stream = st;
    cudaLaunchAttribute at[1]; at[0].id = cudaLaunchAttributeClusterDimension;
    at[0].val.clusterDim.x = CL_SIZE; at[0].val.clusterDim.y = 1; at[0].val.clusterDim.z = 1;
    cfg.attrs = at; cfg.numAttrs = 1;
    cudaLaunchKernelEx(&cfg, acore_kernel, M, (const __nv_bfloat16*)d_in[1], dbg_a_only ? 0 : 1);
  }
  if (!dbg_a_only) {
    BParams P;
    make_map(fn, &P.wmap[0], d_in[5], DM, HD, 64, 32);
    make_map(fn, &P.wo16, d_in[5], DM, HD, 64, 16);
    make_map(fn, &P.wmap[1], d_in[8], DM, DM, 64, 32);
    make_map(fn, &P.wmap[2], d_in[9], DM, DM, 64, 32);
    make_map(fn, &P.wmap[3], d_in[10], FF, DM, 64, 32);
    make_map(fn, &P.wmap[4], d_in[11], DM, FF, 64, 32);
    P.x = (const __nv_bfloat16*)d_in[0];
    P.out = (__nv_bfloat16*)d_out;
    P.desc = (uint64_t)dhi(1024, 1) << 32;
    cudaLaunchConfig_t cfg = {};
    cfg.gridDim = dim3(NBC); cfg.blockDim = dim3(512); cfg.dynamicSmemBytes = B_SMEM; cfg.stream = st;
    cudaLaunchAttribute at[1]; at[0].id = cudaLaunchAttributeProgrammaticStreamSerialization; at[0].val.programmaticStreamSerializationAllowed = 1;
    cfg.attrs = at; cfg.numAttrs = 1;
    cudaLaunchKernelEx(&cfg, bworker_kernel, P);
  }
}
```

```cpp
#include <cuda_runtime.h>
#include <cuda_bf16.h>
#include <cuda.h>
#include <stdint.h>

#define S_LEN 2048
#define DM 640
#define NH 32
#define DH 192
#define HD 6144
#define NSEG 64
#define FF 1536

__device__ __forceinline__ uint32_t smem_u32(const void* p) { return (uint32_t)__cvta_generic_to_shared(p); }
__device__ __forceinline__ uint32_t mapa(uint32_t a, uint32_t r) {
  uint32_t o; asm volatile("mapa.shared::cluster.u32 %0, %1, %2;" : "=r"(o) : "r"(a), "r"(r)); return o; }
__device__ __forceinline__ void mbar_init(uint32_t b, uint32_t c) {
  asm volatile("mbarrier.init.shared::cta.b64 [%0], %1;" :: "r"(b), "r"(c) : "memory"); }
__device__ __forceinline__ void mbar_expect(uint32_t b, uint32_t tx) {
  asm volatile("mbarrier.arrive.expect_tx.shared::cta.b64 _, [%0], %1;" :: "r"(b), "r"(tx) : "memory"); }
__device__ __forceinline__ void mbar_arrive(uint32_t b) {
  asm volatile("mbarrier.arrive.shared::cta.b64 _, [%0];" :: "r"(b) : "memory"); }
__device__ __forceinline__ void mbar_arrive_remote(uint32_t rb) {
  asm volatile("mbarrier.arrive.relaxed.cluster.shared::cluster.b64 _, [%0];" :: "r"(rb) : "memory"); }
__device__ __forceinline__ void mbar_expect_if(bool p, uint32_t b, uint32_t tx) {
  asm volatile("{\n.reg .pred q;\nsetp.ne.u32 q, %2, 0;\n@q mbarrier.arrive.expect_tx.shared::cta.b64 _, [%0], %1;\n}" :: "r"(b), "r"(tx), "r"((uint32_t)p) : "memory"); }
__device__ __forceinline__ void mbar_arrive_if(bool p, uint32_t b) {
  asm volatile("{\n.reg .pred q;\nsetp.ne.u32 q, %1, 0;\n@q mbarrier.arrive.shared::cta.b64 _, [%0];\n}" :: "r"(b), "r"((uint32_t)p) : "memory"); }
__device__ __forceinline__ void mbar_arrive_remote_if(bool p, uint32_t rb) {
  asm volatile("{\n.reg .pred q;\nsetp.ne.u32 q, %1, 0;\n@q mbarrier.arrive.relaxed.cluster.shared::cluster.b64 _, [%0];\n}" :: "r"(rb), "r"((uint32_t)p) : "memory"); }
__device__ __forceinline__ void sts32_if(bool p, uint32_t a, uint32_t v) {
  asm volatile("{\n.reg .pred q;\nsetp.ne.u32 q, %2, 0;\n@q st.shared.b32 [%0], %1;\n}" :: "r"(a), "r"(v), "r"((uint32_t)p) : "memory"); }
__device__ __forceinline__ void sts128z_if(bool p, uint32_t a) {
  asm volatile("{\n.reg .pred q;\nsetp.ne.u32 q, %1, 0;\n@q st.shared.v4.b32 [%0], {0,0,0,0};\n}" :: "r"(a), "r"((uint32_t)p) : "memory"); }
__device__ __forceinline__ bool mbar_try(uint32_t b, uint32_t ph) {
  uint32_t ok;
  asm volatile("{\n.reg .pred p;\nmbarrier.try_wait.parity.shared::cta.b64 p, [%1], %2;\nselp.u32 %0, 1, 0, p;\n}"
               : "=r"(ok) : "r"(b), "r"(ph) : "memory");
  return ok; }
__device__ __forceinline__ bool mbar_test(uint32_t b, uint32_t ph) {
  uint32_t ok;
  asm volatile("{\n.reg .pred p;\nmbarrier.test_wait.parity.shared::cta.b64 p, [%1], %2;\nselp.u32 %0, 1, 0, p;\n}"
               : "=r"(ok) : "r"(b), "r"(ph) : "memory");
  return ok; }
#define SPIN_LIMIT 4000000
#define FAIL() asm volatile("st.global.u32 [%0], 0;" :: "l"(8ull) : "memory")
#define CFENCE() asm volatile("fence.proxy.async::generic.acquire.sync_restrict::shared::cluster.cluster;" ::: "memory")
__device__ __forceinline__ void mbar_wait(uint32_t b, uint32_t ph) {
  int n = 0;
  while (!mbar_try(b, ph)) { if (++n > SPIN_LIMIT) FAIL(); } }
#define TIMEOUT_ACT "@!p st.shared.u32 [%0+1], 0;"
#define WAIT_HINT ", 20000"
#define WAIT_LIM "200000"
__device__ __forceinline__ void mbar_slow(uint32_t b, uint32_t ph) {
  asm volatile("{\n.reg .pred p, q;\n.reg .u32 n;\nmov.u32 n, 0;\n"
               "WL:\nmbarrier.try_wait.parity.shared::cta.b64 p, [%0], %1" WAIT_HINT ";\nadd.u32 n, n, 1;\nsetp.lt.and.u32 q, n, " WAIT_LIM ", !p;\n@q bra.uni WL;\n"
               TIMEOUT_ACT "\n}" :: "r"(b), "r"(ph) : "memory"); }
__device__ __forceinline__ void mbar_waitw(uint32_t b, uint32_t ph) {
  asm volatile("{\n.reg .pred p, q;\n.reg .u32 n;\nmbarrier.try_wait.parity.shared::cta.b64 p, [%0], %1;\n@p bra.uni WD;\nmov.u32 n, 0;\n"
               "WL:\nmbarrier.try_wait.parity.shared::cta.b64 p, [%0], %1" WAIT_HINT ";\nadd.u32 n, n, 1;\nsetp.lt.and.u32 q, n, " WAIT_LIM ", !p;\n@q bra.uni WL;\n"
               TIMEOUT_ACT "\nWD:\n}" :: "r"(b), "r"(ph) : "memory"); }
__device__ __forceinline__ void mbar_waitw2(uint32_t b0, uint32_t b1, uint32_t ph) {
  uint32_t ok;
  asm volatile("{\n.reg .pred p, r;\nmbarrier.try_wait.parity.shared::cta.b64 p, [%1], %3;\nmbarrier.try_wait.parity.shared::cta.b64 r, [%2], %3;\n"
               "and.pred p, p, r;\nselp.u32 %0, 1, 0, p;\n}" : "=r"(ok) : "r"(b0), "r"(b1), "r"(ph) : "memory");
  if (__builtin_expect(!__all_sync(~0u, ok), 0)) { mbar_slow(b0, ph); mbar_slow(b1, ph); }
}
__device__ __forceinline__ void mbar_waitu(uint32_t b, uint32_t ph) {
  asm volatile("{\n.reg .pred p;\nmbarrier.try_wait.parity.shared::cta.b64 p, [%0], %1;\n@p bra.uni WD;\n"
               "WL:\nmbarrier.try_wait.parity.shared::cta.b64 p, [%0], %1" WAIT_HINT ";\n@!p bra.uni WL;\nWD:\n}" :: "r"(b), "r"(ph) : "memory"); }
__device__ __forceinline__ void mbar_waitu2(uint32_t b0, uint32_t b1, uint32_t ph) {
  asm volatile("{\n.reg .pred p, r;\nWL:\nmbarrier.try_wait.parity.shared::cta.b64 p, [%0], %2;\nmbarrier.try_wait.parity.shared::cta.b64 r, [%1], %2;\n"
               "and.pred p, p, r;\n@!p bra.uni WL;\n}" :: "r"(b0), "r"(b1), "r"(ph) : "memory"); }
__device__ __forceinline__ void mbar_waitw4(uint32_t b, uint32_t ph) { mbar_waitw2(b, b + 8, ph); mbar_waitw2(b + 16, b + 24, ph); }
__device__ __forceinline__ uint32_t clock32() { uint32_t t; asm volatile("mov.u32 %0, %%clock;" : "=r"(t) :: "memory"); return t; }
template <int L> __device__ __forceinline__ uint32_t lop3(uint32_t a, uint32_t b, uint32_t c) {
  uint32_t r; asm("lop3.b32 %0, %1, %2, %3, %4;" : "=r"(r) : "r"(a), "r"(b), "r"(c), "n"(L)); return r; }
__device__ __forceinline__ void st_async_v2_if(bool p, uint32_t a, uint32_t v0, uint32_t v1, uint32_t mb) {
  asm volatile("{\n.reg .pred q;\nsetp.ne.u32 q, %4, 0;\n@q st.async.weak.shared::cluster.mbarrier::complete_tx::bytes.v2.b32 [%0], {%1,%2}, [%3];\n}"
               :: "r"(a), "r"(v0), "r"(v1), "r"(mb), "r"((uint32_t)p) : "memory"); }
__device__ __forceinline__ void keep4(const uint32_t* r, int lane) {
  asm volatile("{\n.reg .pred q;\nsetp.lt.s32 q, %4, 0;\n@q st.shared.v4.b32 [%4], {%0,%1,%2,%3};\n}" :: "r"(r[0]), "r"(r[1]), "r"(r[2]), "r"(r[3]), "r"(lane) : "memory"); }
__device__ __forceinline__ uint32_t uni(uint32_t x) { return __shfl_sync(~0u, x, 0); }
__device__ __forceinline__ void bulk_g2s_mc_e(uint32_t dst, const void* src, uint32_t bytes, uint32_t mb, uint16_t mask) {
  asm volatile("{\n.reg .pred e;\nelect.sync _|e, 0xffffffff;\n"
               "@e cp.async.bulk.shared::cluster.global.mbarrier::complete_tx::bytes.multicast::cluster [%0], [%1], %2, [%3], %4;\n}"
               :: "r"(dst), "l"(src), "r"(bytes), "r"(mb), "h"(mask) : "memory"); }
__device__ __forceinline__ void bulk_s2g_e(void* dst, uint32_t src, uint32_t bytes) {
  asm volatile("{\n.reg .pred e;\nelect.sync _|e, 0xffffffff;\n@e cp.async.bulk.global.shared::cta.bulk_group [%0], [%1], %2;\n}"
               :: "l"(dst), "r"(src), "r"(bytes) : "memory"); }
__device__ __forceinline__ void bulk_g2s_e(uint32_t dst, const void* src, uint32_t bytes, uint32_t mb) {
  asm volatile("{\n.reg .pred e;\nelect.sync _|e, 0xffffffff;\n@e cp.async.bulk.shared::cluster.global.mbarrier::complete_tx::bytes [%0], [%1], %2, [%3];\n}"
               :: "r"(dst), "l"(src), "r"(bytes), "r"(mb) : "memory"); }
#define STREAM_HINT 1
__device__ __forceinline__ void bulk_s2g_es(void* dst, uint32_t src, uint32_t bytes) {
  asm volatile("{\n.reg .pred e;\n.reg .b64 pol;\ncreatepolicy.fractional.L2::evict_first.b64 pol;\nelect.sync _|e, 0xffffffff;\n"
               "@e cp.async.bulk.global.shared::cta.bulk_group.L2::cache_hint [%0], [%1], %2, pol;\n}" :: "l"(dst), "r"(src), "r"(bytes) : "memory");
}
__device__ __forceinline__ void bulk_g2s_es(uint32_t dst, const void* src, uint32_t bytes, uint32_t mb) {
  asm volatile("{\n.reg .pred e;\n.reg .b64 pol;\ncreatepolicy.fractional.L2::evict_first.b64 pol;\nelect.sync _|e, 0xffffffff;\n"
               "@e cp.async.bulk.shared::cluster.global.mbarrier::complete_tx::bytes.L2::cache_hint [%0], [%1], %2, [%3], pol;\n}"
               :: "r"(dst), "l"(src), "r"(bytes), "r"(mb) : "memory"); }
__device__ __forceinline__ void tma2d_e(uint32_t dst, const CUtensorMap* tm, int c0, int c1, uint32_t mb) {
  asm volatile("{\n.reg .pred e;\nelect.sync _|e, 0xffffffff;\n"
               "@e cp.async.bulk.tensor.2d.shared::cluster.global.mbarrier::complete_tx::bytes [%0], [%1, {%3, %4}], [%2];\n}"
               :: "r"(dst), "l"((uint64_t)tm), "r"(mb), "r"(c0), "r"(c1) : "memory"); }
__device__ __forceinline__ uint32_t hadd2bf(uint32_t a, uint32_t b) {
  uint32_t r; asm("add.rn.bf16x2 %0, %1, %2;" : "=r"(r) : "r"(a), "r"(b)); return r; }
__device__ __forceinline__ void cluster_sync_all() {
  asm volatile("barrier.cluster.arrive.release.aligned;\nbarrier.cluster.wait.acquire.aligned;" ::: "memory"); }
__device__ __forceinline__ void bar_arrive(int id, int n) { asm volatile("bar.arrive %0, %1;" :: "r"(id), "r"(n) : "memory"); }
__device__ __forceinline__ void bar_arrive_dep(int id, int n, uint32_t dep) {
  asm volatile("{\n.reg .u32 t;\nand.b32 t, %2, 0;\nadd.u32 t, t, %0;\nbar.sync t, %1;\n}" :: "r"(id), "r"(n), "r"(dep) : "memory"); }
__device__ __forceinline__ void bar_sync(int id, int n) { asm volatile("bar.sync %0, %1;" :: "r"(id), "r"(n) : "memory"); }
__device__ __forceinline__ void fence_async() { asm volatile("fence.proxy.async.shared::cta;" ::: "memory"); }
__device__ __forceinline__ void st_async_b32(uint32_t a, uint32_t v, uint32_t mb) {
  asm volatile("st.async.weak.shared::cluster.mbarrier::complete_tx::bytes.b32 [%0], %1, [%2];" :: "r"(a), "r"(v), "r"(mb) : "memory"); }
__device__ __forceinline__ void st_async_v2(uint32_t a, uint32_t v0, uint32_t v1, uint32_t mb) {
  asm volatile("st.async.weak.shared::cluster.mbarrier::complete_tx::bytes.v2.b32 [%0], {%1,%2}, [%3];" :: "r"(a), "r"(v0), "r"(v1), "r"(mb) : "memory"); }
__device__ __forceinline__ void st_async_v4(uint32_t a, uint32_t v0, uint32_t v1, uint32_t v2, uint32_t v3, uint32_t mb) {
  asm volatile("st.async.weak.shared::cluster.mbarrier::complete_tx::bytes.v4.b32 [%0], {%1,%2,%3,%4}, [%5];" :: "r"(a), "r"(v0), "r"(v1), "r"(v2), "r"(v3), "r"(mb) : "memory"); }
__device__ __forceinline__ void ldsm4(uint32_t& r0, uint32_t& r1, uint32_t& r2, uint32_t& r3, uint32_t a) {
  asm volatile("ldmatrix.sync.aligned.m8n8.x4.shared.b16 {%0,%1,%2,%3}, [%4];" : "=r"(r0), "=r"(r1), "=r"(r2), "=r"(r3) : "r"(a) : "memory"); }
__device__ __forceinline__ void ldsm4t(uint32_t& r0, uint32_t& r1, uint32_t& r2, uint32_t& r3, uint32_t a) {
  asm volatile("ldmatrix.sync.aligned.m8n8.x4.trans.shared.b16 {%0,%1,%2,%3}, [%4];" : "=r"(r0), "=r"(r1), "=r"(r2), "=r"(r3) : "r"(a) : "memory"); }
__device__ __forceinline__ void stsm2t(uint32_t a, uint32_t r0, uint32_t r1) {
  asm volatile("stmatrix.sync.aligned.m8n8.x2.trans.shared.b16 [%0], {%1,%2};" :: "r"(a), "r"(r0), "r"(r1) : "memory"); }
__device__ __forceinline__ void stsm4t(uint32_t a, uint32_t r0, uint32_t r1, uint32_t r2, uint32_t r3) {
  asm volatile("stmatrix.sync.aligned.m8n8.x4.trans.shared.b16 [%0], {%1,%2,%3,%4};" :: "r"(a), "r"(r0), "r"(r1), "r"(r2), "r"(r3) : "memory"); }
__device__ __forceinline__ uint32_t movm(uint32_t a) {
  uint32_t d; asm volatile("movmatrix.sync.aligned.m8n8.trans.b16 %0, %1;" : "=r"(d) : "r"(a)); return d; }
__device__ __forceinline__ void mma16816(float* d, uint32_t a0, uint32_t a1, uint32_t a2, uint32_t a3, uint32_t b0, uint32_t b1) {
  asm("mma.sync.aligned.m16n8k16.row.col.f32.bf16.bf16.f32 {%0,%1,%2,%3}, {%4,%5,%6,%7}, {%8,%9}, {%0,%1,%2,%3};"
               : "+f"(d[0]), "+f"(d[1]), "+f"(d[2]), "+f"(d[3]) : "r"(a0), "r"(a1), "r"(a2), "r"(a3), "r"(b0), "r"(b1)); }
__device__ __forceinline__ void mma16816v(float* d, uint32_t a0, uint32_t a1, uint32_t a2, uint32_t a3, uint32_t b0, uint32_t b1) {
  asm volatile("mma.sync.aligned.m16n8k16.row.col.f32.bf16.bf16.f32 {%0,%1,%2,%3}, {%4,%5,%6,%7}, {%8,%9}, {%0,%1,%2,%3};"
               : "+f"(d[0]), "+f"(d[1]), "+f"(d[2]), "+f"(d[3]) : "r"(a0), "r"(a1), "r"(a2), "r"(a3), "r"(b0), "r"(b1)); }
__device__ __forceinline__ uint32_t pack2(float lo, float hi) {
  uint32_t r; asm("cvt.rn.bf16x2.f32 %0, %1, %2;" : "=r"(r) : "f"(hi), "f"(lo)); return r; }
__device__ __forceinline__ uint32_t pack2v(float lo, float hi) {
  uint32_t r; asm volatile("cvt.rn.bf16x2.f32 %0, %1, %2;" : "=r"(r) : "f"(hi), "f"(lo)); return r; }
__device__ __forceinline__ float bf_lo(uint32_t w) { return __uint_as_float(w << 16); }
__device__ __forceinline__ float bf_hi(uint32_t w) { return __uint_as_float(w & 0xffff0000u); }
__device__ __forceinline__ uint4 lds128(uint32_t a) {
  uint4 v; asm volatile("ld.shared.v4.b32 {%0,%1,%2,%3}, [%4];" : "=r"(v.x), "=r"(v.y), "=r"(v.z), "=r"(v.w) : "r"(a) : "memory"); return v; }
__device__ __forceinline__ uint4 lds128_nv(uint32_t a) {
  uint4 v; asm volatile("ld.shared.v4.b32 {%0,%1,%2,%3}, [%4];" : "=r"(v.x), "=r"(v.y), "=r"(v.z), "=r"(v.w) : "r"(a)); return v; }
__device__ __forceinline__ void st_async_v2_nm(uint32_t a, uint32_t v0, uint32_t v1, uint32_t mb) {
  asm volatile("st.async.weak.shared::cluster.mbarrier::complete_tx::bytes.v2.b32 [%0], {%1,%2}, [%3];" :: "r"(a), "r"(v0), "r"(v1), "r"(mb)); }
__device__ __forceinline__ float rcpf(float x) { float y; asm("rcp.approx.ftz.f32 %0, %1;" : "=f"(y) : "f"(x)); return y; }
__device__ __forceinline__ void sts64(uint32_t a, uint32_t x, uint32_t y) { asm volatile("st.shared.v2.b32 [%0], {%1,%2};" :: "r"(a), "r"(x), "r"(y) : "memory"); }
__device__ __forceinline__ float ex2(float x) { float y; asm("ex2.approx.ftz.f32 %0, %1;" : "=f"(y) : "f"(x)); return y; }
__device__ __forceinline__ uint32_t lds32(uint32_t a) {
  uint32_t v; asm volatile("ld.shared.b32 %0, [%1];" : "=r"(v) : "r"(a) : "memory"); return v; }
__device__ __forceinline__ uint2 lds64(uint32_t a) {
  uint2 v; asm volatile("ld.shared.v2.b32 {%0,%1}, [%2];" : "=r"(v.x), "=r"(v.y) : "r"(a) : "memory"); return v; }
__device__ __forceinline__ void sts128(uint32_t a, uint32_t x, uint32_t y, uint32_t z, uint32_t w) {
  asm volatile("st.shared.v4.b32 [%0], {%1,%2,%3,%4};" :: "r"(a), "r"(x), "r"(y), "r"(z), "r"(w) : "memory"); }
__device__ __forceinline__ void sts32(uint32_t a, uint32_t x) { asm volatile("st.shared.b32 [%0], %1;" :: "r"(a), "r"(x) : "memory"); }
__device__ __forceinline__ void tma2d(uint32_t dst, const CUtensorMap* tm, int c0, int c1, uint32_t mb) {
  asm volatile("cp.async.bulk.tensor.2d.shared::cluster.global.mbarrier::complete_tx::bytes [%0], [%1, {%3, %4}], [%2];"
               :: "r"(dst), "l"((uint64_t)tm), "r"(mb), "r"(c0), "r"(c1) : "memory"); }
__device__ __forceinline__ void tma2d_prefetch(const CUtensorMap* tm, int c0, int c1) {
  asm volatile("cp.async.bulk.prefetch.tensor.2d.L2.global.tile [%0, {%1, %2}];" :: "l"((uint64_t)tm), "r"(c0), "r"(c1) : "memory"); }
__device__ __forceinline__ void bulk_g2s_mc(uint32_t dst, const void* src, uint32_t bytes, uint32_t mb, uint16_t mask) {
  asm volatile("cp.async.bulk.shared::cluster.global.mbarrier::complete_tx::bytes.multicast::cluster [%0], [%1], %2, [%3], %4;"
               :: "r"(dst), "l"(src), "r"(bytes), "r"(mb), "h"(mask) : "memory"); }
__device__ __forceinline__ void bulk_s2g(void* dst, uint32_t src, uint32_t bytes) {
  asm volatile("cp.async.bulk.global.shared::cta.bulk_group [%0], [%1], %2;" :: "l"(dst), "r"(src), "r"(bytes) : "memory"); }
__device__ __forceinline__ void wg_fence() { asm volatile("wgmma.fence.sync.aligned;" ::: "memory"); }
__device__ __forceinline__ void wg_commit() { asm volatile("wgmma.commit_group.sync.aligned;" ::: "memory"); }
template <int N> __device__ __forceinline__ void wg_wait() { asm volatile("wgmma.wait_group.sync.aligned %0;" :: "n"(N) : "memory"); }
__device__ __forceinline__ uint64_t mkdesc(uint32_t addr, uint32_t lbo, uint32_t sbo, uint32_t swz) {
  return (uint64_t)((addr & 0x3FFFF) >> 4) | ((uint64_t)(lbo >> 4) << 16) | ((uint64_t)(sbo >> 4) << 32) | ((uint64_t)swz << 62); }

#define ACC4(d) "+f"(d[0]),"+f"(d[1]),"+f"(d[2]),"+f"(d[3])
#define ACC8(d) ACC4(d), ACC4((d + 4))
#define ACC16(d) ACC8(d), ACC8((d + 8))
#define ACC20(d) ACC16(d), ACC4((d + 16))
#define ACC24(d) ACC16(d), ACC8((d + 16))
#define SMEM0 0x400
__host__ __device__ constexpr uint32_t dlo(uint32_t off, uint32_t lbo) { return ((SMEM0 + off) >> 4) | ((lbo >> 4) << 16); }
__host__ __device__ constexpr uint32_t dhi(uint32_t sbo, uint32_t swz) { return (sbo >> 4) | (swz << 30); }
#define R4S "{%0,%1,%2,%3}"
#define R8S "{%0,%1,%2,%3,%4,%5,%6,%7}"
#define R16S "{%0,%1,%2,%3,%4,%5,%6,%7,%8,%9,%10,%11,%12,%13,%14,%15}"
#define R20S "{%0,%1,%2,%3,%4,%5,%6,%7,%8,%9,%10,%11,%12,%13,%14,%15,%16,%17,%18,%19}"
#define R24S "{%0,%1,%2,%3,%4,%5,%6,%7,%8,%9,%10,%11,%12,%13,%14,%15,%16,%17,%18,%19,%20,%21,%22,%23}"
#define ACC32(d) ACC16(d), ACC16((d + 16))
#define R32S "{%0,%1,%2,%3,%4,%5,%6,%7,%8,%9,%10,%11,%12,%13,%14,%15,%16,%17,%18,%19,%20,%21,%22,%23,%24,%25,%26,%27,%28,%29,%30,%31}"
struct Dsc {
  uint64_t b; uint32_t e;
  __device__ __forceinline__ Dsc operator+(uint32_t o) const { return {b + o, e}; }
};
template <int K> __device__ __forceinline__ uint32_t fresh(int i) {
  uint32_t e; asm volatile("{\n.reg .u32 t;\nadd.u32 t, %1, %2;\nshr.u32 %0, t, %3;\n}" : "=r"(e) : "r"(i), "n"((256 << K) + 1), "n"(8 + K)); return e; }
template <int N, bool H = false> struct MM;
#define DEF_MM(N, H, T, ACCM, RS_, I0, I1, I2, I3, I4, I5, I6, I7)                                                                \
  template <> struct MM<N, H> {                                                                                                   \
    template <uint32_t BLO, int ACC>                                                                                              \
    static __device__ __forceinline__ void rs(float* d, const uint32_t* a, Dsc b0) {                                              \
      asm volatile("{\n.reg .b64 b;\nmad.wide.u32 b, %" #I7 ", %" #I5 ", %" #I4 ";\n"                                             \
                   "wgmma.mma_async.sync.aligned.m64n" #N "k16.f32." T "." T " " RS_ ", {%" #I0 ",%" #I1 ",%" #I2 ",%" #I3 "}, b, %" #I6 ", 1, 1, 0;\n}" \
                   : ACCM(d) : "r"(a[0]), "r"(a[1]), "r"(a[2]), "r"(a[3]), "l"(b0.b), "n"(BLO), "n"(ACC), "r"(b0.e)); }           \
    template <uint32_t ALO, uint32_t BLO, int ACC, int TA = 1>                                                                    \
    static __device__ __forceinline__ void ss(float* d, Dsc a0, Dsc b0) {                                                         \
      asm volatile("{\n.reg .b64 a, b;\nmad.wide.u32 a, %" #I6 ", %" #I1 ", %" #I0 ";\nmad.wide.u32 b, %" #I6 ", %" #I3 ", %" #I2 ";\n" \
                   "wgmma.mma_async.sync.aligned.m64n" #N "k16.f32." T "." T " " RS_ ", a, b, %" #I4 ", 1, 1, %" #I5 ", 0;\n}"    \
                   : ACCM(d) : "l"(a0.b), "n"(ALO), "l"(b0.b), "n"(BLO), "n"(ACC), "n"(TA), "r"(b0.e)); }                         \
  };
DEF_MM(8, false, "bf16", ACC4, R4S, 4, 5, 6, 7, 8, 9, 10, 11)
DEF_MM(16, false, "bf16", ACC8, R8S, 8, 9, 10, 11, 12, 13, 14, 15)
DEF_MM(32, false, "bf16", ACC16, R16S, 16, 17, 18, 19, 20, 21, 22, 23)
DEF_MM(40, false, "bf16", ACC20, R20S, 20, 21, 22, 23, 24, 25, 26, 27)
DEF_MM(48, false, "bf16", ACC24, R24S, 24, 25, 26, 27, 28, 29, 30, 31)
DEF_MM(64, false, "bf16", ACC32, R32S, 32, 33, 34, 35, 36, 37, 38, 39)
DEF_MM(32, true, "f16", ACC16, R16S, 16, 17, 18, 19, 20, 21, 22, 23)
DEF_MM(64, true, "f16", ACC32, R32S, 32, 33, 34, 35, 36, 37, 38, 39)

#define LAG 10
#define NSTEP (NSEG + LAG)
#define NR (NSTEP + 1)
__device__ __align__(1024) __nv_bfloat16 g_xn[2][S_LEN * DM];
#define RO 16
static_assert(RO > LAG + 1, "ring");
__device__ __align__(1024) unsigned char g_o[RO * 96 * 8192];
__device__ __align__(1024) uint32_t g_part[6][7][40][64];
#define RD 16
#define TILE_B 81920
__device__ __align__(1024) float2 g_stat[S_LEN];
__device__ __align__(1024) uint32_t g_st2[2][RD][64];
__device__ __align__(1024) unsigned char g_acc[5][RD][TILE_B];
#define NOP 19
#define NW12 5
#define NW34 12
#define NBC (NOP + NW12 + NW34)
__device__ __align__(1024) unsigned char g_wt[NOP * 10 * 12288];
enum { F_O = 0, F_R1 = NOP + 1, F_R2 = F_R1 + 4, F_R3 = F_R2 + 4, F_Z = F_R3 + 4, F_DONE, F_MISC, F_NUM };
__device__ __align__(128) uint32_t g_f[F_NUM][96];
__device__ __align__(128) int g_xready[129][8];
__device__ uint32_t g_tpc[128];
#define TS(i)
#define TSV(i, v)
#define TSN(i)
#define TSD(i, dep)
#define BTS(k, i)
#define BTS2(k, i)
#define RTS(i)
#define RTSD(i, dep)
#define RTS_OUT()
#define CTS(i)
#define PTS(i)
#define PTS1(i)
#define CTS_OUT()
#define GTS(i)

#define CL_SIZE 15
#define NCL 7
#define SSQ 13
#define SSV 16
#define PL_SZ 5376
#define TILE_SBO 2560
#define TILE_GRP 15360
#define WS_SZ ((2 * SSQ + SSV) * 2048)
#define OFF_QK (OFF_WO + 26 * 2048)
#define LAYOUT 2
#define OFF_TILE 0
#define OFF_WS (4 * TILE_GRP)
#define OFF_WO (OFF_WS + WS_SZ)
#define OFF_PL (OFF_QK + 20480)
#define OFF_BAR (OFF_PL + 2 * PL_SZ)
#define STG_Q OFF_TILE
#define STG_K OFF_WO
#define VA 14
#define STG_V2 (OFF_TILE + 27 * 2048)
#define OFF_O (OFF_PL + 4352)
#define LAND(k) (((k) >> 1) * TILE_GRP + ((k) & 1) * 1280)
#define LAND_F (5 * TILE_SBO)
#define OFF_XL (OFF_TILE + 3 * TILE_GRP)
#define OFF_XF (OFF_XL + LAND_F)
#define OFF_WT ((OFF_XL + TILE_SBO + 1023) & ~1023)
#define OFF_TAB (OFF_BAR + 240)
#define OFF_INV (OFF_TAB + 64)
#define OFF_TS (OFF_INV + 128)
#define A_SMEM 232448
static_assert(WS_SZ + 72 * 1024 + 2 * PL_SZ + 4 * TILE_GRP + 512 == A_SMEM && OFF_WS % 1024 == 0 && OFF_WO % 1024 == 0 && SSQ == 13, "smem map");
enum { B_W0 = 0, B_W1, B_F1, B_F2 = B_F1 + 4, B_R1 = B_F2 + 4, B_R2, B_MEMFREE, B_LANDFREE, B_OPEER, B_PLFREE, B_XFREE, B_SB, B_WOF = B_SB + 6, B_WTF, B_RS, B_NUM = B_RS + 4 };
static_assert(B_NUM <= 30, "barriers");
enum { N_C = 0, N_SISS, N_QK, N_V, N_PM, N_TURN, N_PI, N_VGO, N_O, N_PX, N_AB, N_SDONE, N_VDONE, N_G3, N_P, N_OX };

__device__ __forceinline__ bool is_dual(int j) { return j >= LAG && j < NSEG; }
__device__ __forceinline__ int sched_l(int j) { return j < NSEG ? j : NSEG + j - LAG; }
__device__ __forceinline__ int sched_f(int j) { return NSEG + j - LAG; }
__device__ __forceinline__ void wait_cnt(const int* p, int target) {
  int v, n = 0;
  do {
    asm volatile("ld.relaxed.gpu.global.b32 %0, [%1];" : "=r"(v) : "l"(p) : "memory");
    if (v >= target) break;
    __nanosleep(100);
    if (++n > SPIN_LIMIT) FAIL();
  } while (true);
  asm volatile("fence.acquire.gpu;" ::: "memory");
  asm volatile("fence.proxy.async.global;" ::: "memory");
}
__device__ __forceinline__ void red_release(void* p, uint32_t v) { asm volatile("red.release.gpu.global.add.u32 [%0], %1;" :: "l"(p), "r"(v) : "memory"); }
__device__ __forceinline__ void red_relaxed(void* p, uint32_t v) { asm volatile("red.relaxed.gpu.global.add.u32 [%0], %1;" :: "l"(p), "r"(v) : "memory"); }
#define VMASK 0xa5294a5294ull
__host__ __device__ constexpr int popc40(unsigned long long m) { int c = 0; for (; m; m &= m - 1) c++; return c; }
static_assert(popc40(VMASK) == SSV, "mask");
__host__ __device__ constexpr int ss_idx(int ks, int n) { return n == SSV ? popc40(VMASK & ((1ull << ks) - 1)) : ks * n / 40; }
__host__ __device__ constexpr bool is_ss(int ks, int n) { return ss_idx(ks + 1, n) != ss_idx(ks, n); }
__host__ __device__ constexpr int rs_idx(int ks, int n) { return ks - ss_idx(ks, n); }

#define SL2 (0.07216878364870322f * 1.4426950408889634f)

#define SUM_LOOP 0
struct Desc { Dsc tile, unit, k1, pl, p; };
__device__ __forceinline__ Desc make_desc(const uint64_t* h, uint32_t u, uint32_t e) {
  return {{h[0], e}, {h[1] + u * 128, e}, {h[2], e}, {h[3], e}, {h[4], e}};
}
template <int N, int NSS, int RG, int KS, int K1, int K0 = 0>
__device__ __forceinline__ void proj(float* acc, const uint32_t* W, const Desc& D) {
  if constexpr (KS < K1) {
    constexpr uint32_t BLO = dlo(OFF_TILE + (KS / 10) * TILE_GRP + RG * TILE_SBO + (KS % 10) * 256, 128);
    if constexpr (is_ss(KS, NSS)) MM<N>::template ss<dlo(OFF_WS + ss_idx(KS, NSS) * 2048, 0), BLO, (KS != K0)>(acc, D.unit, D.tile);
    else MM<N>::template rs<BLO, (KS != K0)>(acc, W + rs_idx(KS, NSS) * 4, D.tile);
    proj<N, NSS, RG, KS + 1, K1, K0>(acc, W, D);
  }
}
#define VST 17
template <int KS>
__device__ __forceinline__ void ld_rest(uint32_t* W, const uint32_t* p) {
  if constexpr (KS < 40) {
    if constexpr (!is_ss(KS, SSV) && rs_idx(KS, SSV) >= VST) {
#pragma unroll
      for (int i = 0; i < 4; i++) W[4 * rs_idx(KS, SSV) + i] = __ldg(p + (KS * 16 + (i >> 1) * 8) * (HD / 2) + (i & 1) * 4);
    }
    ld_rest<KS + 1>(W, p);
  }
}
template <int N>
__device__ __forceinline__ void load_w(uint32_t* W, uint32_t stage, int warp, int lane) {
  const int kr = (lane >> 4) * 8 + (lane & 7);
  const int cb = warp * 2 + ((lane >> 3) & 1);
  const uint32_t a0 = stage + kr * 128 + ((cb ^ (lane & 7)) << 4);
#pragma unroll
  for (int i = 0; i < N; i++) ldsm4t(W[4 * i], W[4 * i + 1], W[4 * i + 2], W[4 * i + 3], a0 + i * 2048);
}
template <int N, int G, int U, int OS, int ACC>
__device__ __forceinline__ void wo4(float* d, const Desc& D) {
  constexpr uint32_t WA = (U >= 4 ? OFF_WO + (U - 4) * 2048 : OFF_WT) - G * SSQ * 2048, OB = OS == 0 ? OFF_O : OS == 1 ? OFF_XL : OFF_XF;
  Dsc b = OS ? D.k1 : D.pl;
  b.e = fresh<(U < 16 ? U / 4 : U / 8 - 2) + (N == 8 ? 4 : 0)>(D.unit.e);
  MM<N>::template ss<dlo(WA, 0), dlo(OB, 128), ACC>(d, D.unit, b);
  MM<N>::template ss<dlo(WA + 2048, 0), dlo(OB + 256, 128), 1>(d, D.unit, b);
  MM<N>::template ss<dlo(WA + 4096, 0), dlo(OB + 512, 128), 1>(d, D.unit, b);
  MM<N>::template ss<dlo(WA + 6144, 0), dlo(OB + 768, 128), 1>(d, D.unit, b);
}
__device__ __forceinline__ void wo_coord(int i, int t3, int head, int& c0, int& c1) {
  const int g = i >> 1;
  const int blk = g == 0 ? 9 : (g < 4 ? g - 1 : (g - 4) >> 1) * 3 + t3;
  int sl = g < 4 ? t3 : (g & 1) ? t3 + 1 : t3 + 2;
  if (sl >= 3) sl -= 3;
  c0 = blk * 64; c1 = head * DH + sl * 64 + (i & 1) * 32;
}
__device__ __forceinline__ void tok_softmax(uint32_t sb, int job, int lane) {
  const bool w1 = job & 1;
  const int dg = (lane >> 2) - (lane & 3) * 2;
  const uint32_t lo = sb + OFF_PL + (job >> 1) * PL_SZ + (job & 1) * 1792, l8 = lo + 512 + lane * 8, pa = lo + lane * 4;
  const uint32_t km = job & 2 ? 640 : 512;
  float x[14];
  {
    const uint4 a = lds128(lo + lane * 16);
    const uint2 e = lds64(l8);
    const uint32_t c = lds32(768 + pa);
    x[0] = bf_lo(a.x); x[1] = bf_hi(a.x); x[2] = bf_lo(a.y); x[3] = bf_hi(a.y); x[4] = bf_lo(a.z); x[5] = bf_hi(a.z); x[6] = bf_lo(a.w); x[7] = bf_hi(a.w);
    x[8] = bf_lo(c); x[9] = bf_hi(c); x[10] = bf_lo(e.x); x[11] = bf_hi(e.x); x[12] = bf_lo(e.y); x[13] = bf_hi(e.y);
  }
  if (dg < 0) { x[8] = -INFINITY; if (w1) x[4] = -INFINITY; else x[10] = -INFINITY; }
  if (dg < 1) { x[9] = -INFINITY; if (w1) x[5] = -INFINITY; else x[11] = -INFINITY; }
  const float m4 = fmaxf(x[8], x[9]);
  float m0 = fmaxf(fmaxf(fmaxf(x[0], x[1]), fmaxf(x[2], x[3])), fmaxf(fmaxf(x[4], x[5]), fmaxf(x[6], x[7])));
  float m1 = fmaxf(fmaxf(x[10], x[11]), fmaxf(x[12], x[13]));
  if (w1) m1 = fmaxf(m1, m4); else m0 = fmaxf(m0, m4);
  m0 = fmaxf(m0, __shfl_xor_sync(~0u, m0, 1)); m1 = fmaxf(m1, __shfl_xor_sync(~0u, m1, 1));
  sts32(pa + (w1 ? 384 : 896 + 128), 0u); sts32(pa + 1152 - km, 0u); sts32(pa + 896 + 1152 - km, 0u); sts64(l8 + 896 - 256, 0u, 0u);
  m0 = fmaxf(m0, __shfl_xor_sync(~0u, m0, 2)); m1 = fmaxf(m1, __shfl_xor_sync(~0u, m1, 2));
  m0 *= -SL2; m1 *= -SL2;
#pragma unroll
  for (int j = 0; j < 14; j++) x[j] = ex2(fmaf(x[j], SL2, j < 8 ? m0 : j >= 10 ? m1 : w1 ? m1 : m0));
  const float l4s = x[8] + x[9];
  float l0 = ((x[0] + x[1]) + (x[2] + x[3])) + ((x[4] + x[5]) + (x[6] + x[7])), l1 = (x[10] + x[11]) + (x[12] + x[13]);
  if (w1) l1 += l4s; else l0 += l4s;
  l0 += __shfl_xor_sync(~0u, l0, 1); l1 += __shfl_xor_sync(~0u, l1, 1);
  l0 += __shfl_xor_sync(~0u, l0, 2); l1 += __shfl_xor_sync(~0u, l1, 2);
  l0 = rcpf(l0); l1 = rcpf(l1);
#pragma unroll
  for (int j = 0; j < 7; j++) {
    const float iv = j < 4 ? l0 : j > 4 ? l1 : w1 ? l1 : l0;
    sts32(pa + (j < 3 ? j * 128 : j == 3 ? km : j == 4 ? (w1 ? 896 + 128 : 384) : j == 5 ? 896 : 896 + km), pack2(x[2 * j] * iv, x[2 * j + 1] * iv));
  }
}
template <int N>
__device__ __forceinline__ void wo_phase(uint32_t sb, int wg, int warp, int lane, uint32_t par, uint32_t r1, const Desc& D) {
  const uint32_t bar = sb + OFF_BAR;
  float x[N / 2], y[N / 2];
  const uint2 ta = lds64(sb + OFF_TAB + (wg * 4 + warp) * 8);
  uint32_t xa = (ta.x & ~255u) + lane * 8, xb = (ta.x & 0xFF0000FFu) + SMEM0 + OFF_BAR, ya = (ta.y & ~255u) + lane * 8, yb = (ta.y & 0xFF0000FFu) + SMEM0 + OFF_BAR;
  asm volatile("" : "+r"(xa), "+r"(xb), "+r"(ya), "+r"(yb));
  auto scat = [&](uint32_t ad, uint32_t mb, const float* d) {
    st_async_v2(ad, pack2(d[0], d[1]), pack2(d[2], d[3]), mb);
    if (N == 16) st_async_v2(ad + LAND_F, pack2(d[4], d[5]), pack2(d[6], d[7]), mb);
  };
  if (wg == 0) {
    bar_sync(N_O, 384);
    wg_fence(); wo4<N, 0, 4, 0, 0>(x, D); wo4<N, 0, 8, 0, 0>(y, D); wg_commit();
    mbar_waitu(bar + 8 * B_OPEER, par);
    CFENCE(); wg_fence(); wo4<N, 0, 16, 1, 1>(x, D); wo4<N, 0, 20, 2, 1>(x, D); wg_commit();
    wo4<N, 0, 24, 1, 1>(y, D); wg_commit();
    mbar_waitu2(bar + 8 * B_WOF, bar + 8 * B_MEMFREE, par);
    wg_fence(); wo4<N, 0, 28, 2, 1>(y, D); wg_commit();
    bar_arrive(N_AB, 256);
    wg_wait<2>(); scat(xa, xb, x);
    wg_wait<0>(); scat(ya, yb, y);
  } else {
    bar_sync(N_O, 384);
    wg_fence(); wo4<N, 1, 0, 0, 0>(x, D); wg_commit(); wo4<N, 1, 12, 0, 0>(y, D); wg_commit();
    wg_wait<1>(); mbar_arrive_remote_if(lane == 0, r1);
    mbar_waitu(bar + 8 * B_MEMFREE, par);
    scat(xa, xb, x);
    bar_sync(N_AB, 256);
    CFENCE(); wg_fence(); wo4<N, 1, 32, 1, 1>(y, D); wo4<N, 1, 36, 2, 1>(y, D); wg_commit();
    bar_arrive(N_TURN, 256);
    wg_wait<0>(); scat(ya, yb, y);
  }
}
#define DS_DUAL 10
#define DS_SINGLE 20
#define POLL_GAP 100
#define POLL_GAPD 0
#define TOK_DELAY 250
#define LATE_SM 1
#define UMAX 40
#define VD1 6
#define VS1 4
struct AMaps { CUtensorMap w16[3], wo32; uint64_t d[5]; const __nv_bfloat16* wv; };
__global__ void __launch_bounds__(512, 1)
acore_kernel(const __grid_constant__ AMaps M, const __nv_bfloat16* __restrict__ mem0, int sync_b) {
  extern __shared__ __align__(1024) unsigned char smem_raw[];
  const uint32_t sb = smem_u32(smem_raw);
  GTS(24);
  if (threadIdx.x == 480) {
    uint32_t smid; asm volatile("mov.u32 %0, %%smid;" : "=r"(smid));
    g_tpc[(smid >> 1) & 127] = blockIdx.x - CL_SIZE < 3 * CL_SIZE && blockIdx.x % CL_SIZE >= 12 ? 1 : 2;
    asm volatile("griddepcontrol.launch_dependents;");
  }
  const int lane0 = threadIdx.x & 31;
#define LANE_INIT() int lane; asm volatile("mov.u32 %0, %%laneid;" : "=r"(lane))
  const int warp = __shfl_sync(~0u, (threadIdx.x >> 5) & 3, 0);
  const int cl = blockIdx.x / CL_SIZE;
  const uint32_t rank = blockIdx.x - cl * CL_SIZE;
  const int nh = cl >= 1 && cl <= 3 ? 4 : 5;
  const int nA = 3 * nh;
  const int wg = __shfl_sync(~0u, (int)rank < nA ? threadIdx.x >> 7 : 4, 0);
  const int head = (cl < 4 ? (cl ? 1 + 4 * cl : 0) : 5 * cl - 3) + rank / 3;
  const int t3 = rank % 3;
  const int col0 = head * DH + t3 * 64;
  const uint32_t bar = sb + OFF_BAR;
  const uint32_t rb0 = SMEM0;
  const uint16_t mcmask = (uint16_t)((1u << nA) - 1);
  const uint32_t nxt = sb + ((t3 == 2 ? -2 : 1) << 24), prv = sb + ((t3 == 0 ? 2 : -1) << 24);
  const int ig = (int)rank - (nA - 4);

  if (threadIdx.x == 0) {
    if (mapa(sb, nA - 1) != rb0 + ((nA - 1) << 24) || mapa(sb, 0) != rb0 || mapa(sb, 1) != rb0 + (1u << 24) || sb != SMEM0 + (rank << 24)) FAIL();
    for (int i = 0; i < B_NUM; i++)
      mbar_init(bar + 8 * i, i == B_R1 ? 4 * nA : i == B_R2 ? 12 * nA : i == B_MEMFREE ? nA : i == B_LANDFREE ? 4 * nA : i == B_PLFREE || i == B_XFREE ? 2 : 1);
    asm volatile("fence.mbarrier_init.release.cluster;" ::: "memory");
    mbar_expect(bar + 8 * B_W0, (80 + SSV + VST) * 2048);
  }
  __syncthreads();
  if (lane0 == 0) {
    const int w12 = wg * 4 + warp;
    if (w12 < 10) {
#pragma unroll 1
      for (int ks = 4 * w12; ks < 4 * w12 + 4; ks++) {
        const bool ss = is_ss(ks, SSQ);
        tma2d(ss ? sb + OFF_WS + ss_idx(ks, SSQ) * 2048 : sb + STG_Q + rs_idx(ks, SSQ) * 2048, &M.w16[0], col0, ks * 16, bar + 8 * B_W0);
        tma2d(ss ? sb + OFF_WS + (SSQ + ss_idx(ks, SSQ)) * 2048 : sb + STG_K + rs_idx(ks, SSQ) * 2048, &M.w16[1], col0, ks * 16, bar + 8 * B_W0);
        if (is_ss(ks, SSV)) tma2d(sb + OFF_WS + (2 * SSQ + ss_idx(ks, SSV)) * 2048, &M.w16[2], col0, ks * 16, bar + 8 * B_W0);
        else if (rs_idx(ks, SSV) < VST) tma2d(sb + (rs_idx(ks, SSV) < VA ? STG_K + 27 * 2048 : STG_V2 - VA * 2048) + rs_idx(ks, SSV) * 2048, &M.w16[2], col0, ks * 16, bar + 8 * B_W0);
      }
    }
  }
  if (lane0 < 2 && wg < 2) {
    const int u = 4 * (wg ? (lane0 ? 6 + t3 : 9) : (lane0 ? 3 + t3 : t3)) + warp;
    const int li = (u >= nA) + (u >= 2 * nA) + (u >= 3 * nA);
    sts32(sb + OFF_TAB + (wg * 4 + warp) * 8 + lane0 * 4,
          rb0 + ((u - li * nA) << 24) + OFF_TILE + LAND(li + (u >= 36 ? t3 : 0)) + (rank / 3) * 256 + 8 * (B_RS + li));
  }
  __syncthreads();
  GTS(25);

  auto issue_tok = [&](int sc, int fb, int rel = -1, uint32_t ph = 0) {
    if (sync_b) wait_cnt(&g_xready[sc][0], 32);
    if (rel >= 0) mbar_waitu(bar + 8 * rel, ph);
    bulk_g2s_mc_e(sb + OFF_TILE + ig * TILE_GRP + TILE_SBO, &g_xn[0][0] + uni(sc * (32 * DM)) + ig * 5120, 10240, bar + 8 * (fb + ig), mcmask);
  };
#define POLL(d, q) _Pragma("unroll") for (int k = 0; k < NCL; k++) \
      asm volatile("ld.relaxed.gpu.global.v2.b32 {%0,%1}, [%2];" : "=r"(d[k].x), "=r"(d[k].y) : "l"(q + k * 2560) : "memory")
#define L3(L, a, b, c) lop3<L>(a, b, c)
#define TAGS(L, d) L3(L, L3(L, L3(L, d[0].x, d[0].y, d[1].x), L3(L, d[1].y, d[2].x, d[2].y), L3(L, d[3].x, d[3].y, d[4].x)), L3(L, d[4].y, d[5].x, d[5].y), L3(L, d[6].x, d[6].y, d[6].y))
    auto deliver = [&](uint2* pa, const uint32_t* gq, int u, int c, int dc, int ds, int step, bool first, int lane) {
      const uint32_t off = uni(OFF_TILE + ((u * 205) >> 11) * (TILE_GRP - TILE_SBO) + u * 256 + dc * LAND_F), boff = uni(OFF_BAR + 8 * (B_F1 + ((u * 205) >> 11)));
      const uint32_t* mi = &g_part[4][0][0][0] + uni((c * NCL + cl) * 2560 + u * 64);
      mbar_waitu(bar + 8 * B_LANDFREE, step & 1);
      int n = 0;
      while (true) {
        const bool ok = __all_sync(~0u, ((step & 2 ? ~TAGS(0xFE, pa) : TAGS(0x80, pa)) & 1) != 0);
        if (ok) break;
        if (++n > SPIN_LIMIT) FAIL();
        POLL(pa, gq);
      }
      if (warp == 0 && first) { TS(19); TSV(10, n); }
      const uint32_t w0 = hadd2bf(hadd2bf(hadd2bf(pa[0].x, pa[1].x), hadd2bf(pa[2].x, pa[3].x)), hadd2bf(hadd2bf(pa[4].x, pa[5].x), pa[6].x));
      const uint32_t w1 = hadd2bf(hadd2bf(hadd2bf(pa[0].y, pa[1].y), hadd2bf(pa[2].y, pa[3].y)), hadd2bf(hadd2bf(pa[4].y, pa[5].y), pa[6].y));
      if (u < ds) {
        const uint32_t da = SMEM0 + off + lane * 8, db = SMEM0 + boff;
#pragma unroll
        for (int d = 0; d < 12; d++) st_async_v2((d << 24) + da, w0, w1, (d << 24) + db);
#pragma unroll
        for (int d = 12; d < 15; d++) st_async_v2_if(nA == 15, (d << 24) + da, w0, w1, (d << 24) + db);
      } else {
        *reinterpret_cast<uint2*>(const_cast<uint32_t*>(gq) + ((4 - 2 * (step & 1)) * NCL + cl) * 2560) = make_uint2(w0, w1);
        asm volatile("fence.proxy.async.global;" ::: "memory");
        __syncwarp();
        bulk_g2s_mc_e(sb + off, mi, 256, sb + boff, mcmask);
      }
    };
#define REL(b, g) mbar_arrive_remote_if(lane == 0, rb0 + ((nA - 4 + (g)) << 24) + OFF_BAR + 8 * (b))

  if (wg < 2) {
    asm volatile("setmaxnreg.inc.sync.aligned.u32 160;");
    LANE_INIT();
    uint32_t W[4 * (40 - SSQ)];
    mbar_waitw(bar + 8 * B_W0, 0);
    GTS(26);
    load_w<40 - SSQ>(W, sb + (wg ? STG_K : STG_Q), warp, lane);
    fence_async();
    bar_sync(1, 384);
    cluster_sync_all();
#define DESC(k) const Desc D = make_desc(M.d, min(wg, 2) * SSQ, fresh<k>(step))
    GTS(27);
#pragma unroll 1
    for (int step = -1; step < NSTEP; step++) {
      const uint32_t par = step & 1;
      asm volatile("" : "+r"(lane));
      const bool dual = is_dual(step), has_next = step + 1 < NSTEP;
#define QK_SA (sb + OFF_QK + wg * 15360 + (2 * warp + ((lane >> 3) & 1)) * 128 + (lane & 7) * 16)
#define QK_F (wg ? -5120 : 5120)
#define QK_S12 ((wg ? (lane >> 4) : 1 + 2 * (lane >> 4)) * 1024)
#define QK_S34 ((wg ? 2 + (lane >> 4) : 2 - 2 * (lane >> 4)) * 1024)
      if (step >= 0) {
        if (dual) {
          DESC(0);
          float acc[24];
          mbar_waitu(bar + 8 * (B_F1 + 0), par);
          if (wg + warp == 0) { TS(0); TSN(1); }
          CFENCE(); wg_fence(); proj<48, SSQ, 0, 0, 10>(acc, W, D); wg_commit();
          mbar_waitu(bar + 8 * (B_F1 + 1), par);
          CFENCE(); wg_fence(); proj<48, SSQ, 0, 10, 20>(acc, W, D); wg_commit();
          mbar_waitu(bar + 8 * (B_F1 + 2), par);
          CFENCE(); wg_fence(); proj<48, SSQ, 0, 20, 30>(acc, W, D); wg_commit();
          mbar_waitu2(bar + 8 * (B_F1 + 3), bar + 8 * B_PLFREE, par);
          if (wg + warp == 0) TS(2);
          CFENCE(); wg_fence(); proj<48, SSQ, 0, 30, 40>(acc, W, D); wg_commit();
          bar_arrive(N_VGO, 384);
          const uint32_t sa = QK_SA, s0 = sa + 4096 + (lane >> 4) * QK_F, s1 = sa + QK_F + QK_S12, s2 = sa + QK_F + QK_S34;
          wg_wait<0>();
          if (wg + warp == 0) TS(3);
          stsm4t(s0, pack2(acc[0], acc[1]), pack2(acc[2], acc[3]), pack2(acc[20], acc[21]), pack2(acc[22], acc[23]));
          stsm4t(s1, pack2(acc[4], acc[5]), pack2(acc[6], acc[7]), pack2(acc[8], acc[9]), pack2(acc[10], acc[11]));
          stsm4t(s2, pack2(acc[12], acc[13]), pack2(acc[14], acc[15]), pack2(acc[16], acc[17]), pack2(acc[18], acc[19]));
        } else {
          DESC(1);
          float acc[4];
          mbar_waitu(bar + 8 * (B_F1 + 0), par);
          if (wg + warp == 0) { TS(0); TSN(1); }
          CFENCE(); wg_fence(); proj<8, SSQ, 0, 0, 10>(acc, W, D); wg_commit();
          mbar_waitu(bar + 8 * (B_F1 + 1), par);
          CFENCE(); wg_fence(); proj<8, SSQ, 0, 10, 20>(acc, W, D); wg_commit();
          mbar_waitu(bar + 8 * (B_F1 + 2), par);
          CFENCE(); wg_fence(); proj<8, SSQ, 0, 20, 30>(acc, W, D); wg_commit();
          mbar_waitu2(bar + 8 * (B_F1 + 3), bar + 8 * B_PLFREE, par);
          if (wg + warp == 0) TS(2);
          CFENCE(); wg_fence(); proj<8, SSQ, 0, 30, 40>(acc, W, D); wg_commit();
          bar_arrive(N_VGO, 384);
          const uint32_t s0 = QK_SA + 4096;
          wg_wait<0>();
          if (wg + warp == 0) TS(3);
          stsm2t(s0, pack2(acc[0], acc[1]), pack2(acc[2], acc[3]));
        }
        fence_async();
        bar_sync(N_QK, 256);
        if (wg == 0 || dual) {
          float s[20];
          DESC(2);
          const Dsc ab = D.k1 + wg * 192, bb = D.k1 + (1 - wg) * 320;
          wg_fence();
          MM<40>::ss<dlo(OFF_QK, 128), dlo(OFF_QK + 10240, 128), 0, 0>(s, ab, bb);
          MM<40>::ss<dlo(OFF_QK + 256, 128), dlo(OFF_QK + 10240 + 256, 128), 1, 0>(s, ab, bb);
          MM<40>::ss<dlo(OFF_QK + 512, 128), dlo(OFF_QK + 10240 + 512, 128), 1, 0>(s, ab, bb);
          MM<40>::ss<dlo(OFF_QK + 768, 128), dlo(OFF_QK + 10240 + 768, 128), 1, 0>(s, ab, bb);
          wg_commit();
          bar_arrive(N_SISS, 384);
          const int rw = (warp - wg) & 3;
          const uint32_t bo = OFF_BAR + 8 * (B_SB + 3 * wg + rw), lo = OFF_PL + wg * PL_SZ + rw * 1792;
          const uint32_t km = wg ? 640 : 512;
          uint32_t l16 = lo + lane * 16, l4 = lo + lane * 4;
          mbar_expect_if(lane == 0 && rw < 3, sb + bo, rw < 2 ? 1792 : 1280);
          asm volatile("" : "+r"(l16), "+r"(l4));
          if (rw == 2) {
            wg_wait<0>();
            if (wg == 0) TSD(4, __float_as_uint(s[0]));
            {
              const uint32_t w0 = pack2(s[0], s[1]), w1 = pack2(s[4], s[5]), w2 = pack2(s[8], s[9]), w3 = pack2(s[12], s[13]), w4 = pack2(s[16], s[17]);
              st_async_v4(nxt + 896 + l16, w0, w1, w2, w3, nxt + bo);
              st_async_v4(prv + l16, w0, w1, w2, w3, prv + bo);
              st_async_b32(nxt + 896 + 768 + l4, w4, nxt + bo);
              st_async_b32(prv + 768 + l4, w4, prv + bo);
            }
            bar_arrive(N_SDONE, 256);
            mbar_waitu(sb + bo, (step - wg * LAG) & 1);
            if (wg == 0) TS(5);
            float x[10];
            {
              const uint4 a = lds128(sb + l16), b = lds128(sb + 896 + l16);
              const uint32_t c = lds32(sb + 768 + l4), d = lds32(sb + 896 + 768 + l4);
              const uint32_t e0 = hadd2bf(a.x, b.x), e1 = hadd2bf(a.y, b.y), e2 = hadd2bf(a.z, b.z), e3 = hadd2bf(a.w, b.w), e4 = hadd2bf(c, d);
              x[0] = s[0] + bf_lo(e0); x[1] = s[1] + bf_hi(e0); x[2] = s[4] + bf_lo(e1); x[3] = s[5] + bf_hi(e1); x[4] = s[8] + bf_lo(e2);
              x[5] = s[9] + bf_hi(e2); x[6] = s[12] + bf_lo(e3); x[7] = s[13] + bf_hi(e3); x[8] = s[16] + bf_lo(e4); x[9] = s[17] + bf_hi(e4);
            }
            float m0 = fmaxf(fmaxf(fmaxf(x[0], x[1]), fmaxf(x[2], x[3])), fmaxf(fmaxf(x[4], x[5]), fmaxf(fmaxf(x[6], x[7]), fmaxf(x[8], x[9]))));
            m0 = fmaxf(m0, __shfl_xor_sync(~0u, m0, 1));
            sts32(sb + l4 + 1152 - km, 0u);
            m0 = fmaxf(m0, __shfl_xor_sync(~0u, m0, 2));
            m0 *= -SL2;
#pragma unroll
            for (int j = 0; j < 5; j++) {
              x[2 * j] = ex2(fmaf(x[2 * j], SL2, m0)); x[2 * j + 1] = ex2(fmaf(x[2 * j + 1], SL2, m0));
              sts32(sb + l4 + (j < 4 ? j * 128 : km), pack2(x[2 * j], x[2 * j + 1]));
            }
            float l = ((x[0] + x[1]) + (x[2] + x[3])) + ((x[4] + x[5]) + ((x[6] + x[7]) + (x[8] + x[9])));
            l += __shfl_xor_sync(~0u, l, 1);
            fence_async();
            sts32(sb + OFF_INV + wg * 64 + (lane >> 1) * 4, __float_as_uint(l));
            bar_arrive(N_PM, dual ? 224 : 192);
            if (wg == 0) TS(6);
          } else if (rw < 2) {
            const bool w1 = rw == 1;
            const uint32_t l8 = lo + 512 + lane * 8;
            uint32_t tw[7];
            wg_wait<0>();
            bar_arrive(N_SDONE, 256);
            tw[0] = pack2(s[0], s[1]); tw[1] = pack2(s[4], s[5]); tw[2] = pack2(s[8], s[9]); tw[3] = pack2(s[16], s[17]);
            tw[4] = w1 ? pack2(s[6], s[7]) : pack2(s[12], s[13]); tw[5] = pack2(s[2], s[3]); tw[6] = pack2(s[18], s[19]);
            { const uint32_t t0 = clock32(); while (clock32() - t0 < TOK_DELAY) {} }
            st_async_v4(nxt + 896 + l16, tw[0], tw[1], tw[2], tw[3], nxt + bo);
            st_async_v4(prv + l16, tw[0], tw[1], tw[2], tw[3], prv + bo);
            st_async_v2(nxt + 896 + l8, tw[5], tw[6], nxt + bo);
            st_async_v2(prv + l8, tw[5], tw[6], prv + bo);
            st_async_b32(nxt + 896 + 768 + l4, tw[4], nxt + bo);
            st_async_b32(prv + 768 + l4, tw[4], prv + bo);
            mbar_waitu(sb + bo, (step - wg * LAG) & 1);
            const uint4 a = lds128(sb + l16), b = lds128(sb + 896 + l16);
            const uint2 e = lds64(sb + l8), f = lds64(sb + 896 + l8);
            const uint32_t c = lds32(sb + 768 + l4), d = lds32(sb + 896 + 768 + l4);
            sts128(sb + l16, hadd2bf(hadd2bf(a.x, b.x), tw[0]), hadd2bf(hadd2bf(a.y, b.y), tw[1]), hadd2bf(hadd2bf(a.z, b.z), tw[2]), hadd2bf(hadd2bf(a.w, b.w), tw[3]));
            sts64(sb + l8, hadd2bf(hadd2bf(e.x, f.x), tw[5]), hadd2bf(hadd2bf(e.y, f.y), tw[6]));
            sts32(sb + 768 + l4, hadd2bf(hadd2bf(c, d), tw[4]));
            bar_arrive(N_PX, dual ? 256 : 192);
            if (wg + warp == 0) TS(9);
          } else {
            wg_wait<0>();
            if (wg == 0) {
              mbar_expect_if(lane < 3 && has_next, bar + 8 * (lane == 2 ? B_OPEER : B_WOF + lane), lane == 2 ? (dual ? 4096 : 2048) : lane ? 8192 : 20480);
              auto fetch = [&](int i, int n, uint32_t dst, int mb) {
                int c0, c1; wo_coord(i, t3, head, c0, c1);
                tma2d_e(dst, &M.wo32, c0, c1, bar + 8 * mb); if (n == 2) tma2d_e(dst + 4096, &M.wo32, c0, c1 + 32, bar + 8 * mb);
              };
              bar_sync(N_G3, 160);
              if (has_next) {
                fetch(0, 2, sb + OFF_WT, B_WTF);
                mbar_arrive_remote_if(lane < 2, (lane ? nxt : prv) + OFF_BAR + 8 * B_XFREE);
              }
              bar_sync(N_SDONE, 256);
              if (has_next) {
                fetch(15, 1, sb + OFF_QK, B_WOF); fetch(16, 2, sb + OFF_QK + 4096, B_WOF); fetch(18, 2, sb + OFF_QK + 12288, B_WOF);
                mbar_waitu(bar + 8 * B_XFREE, par);
              }
              bar_arrive(N_PM, dual ? 224 : 192);
              bar_sync(N_VDONE, 160);
              mbar_arrive_remote_if(lane < nA && has_next, rb0 + (lane << 24) + OFF_BAR + 8 * B_MEMFREE);
              if (has_next) mbar_waitu(bar + 8 * B_WTF, par);
            } else {
              bar_arrive(N_SDONE, 256);
              if ((unsigned)ig < 3) issue_tok(sched_l(step + 1), B_F2, B_R1, (step - LAG) & 1);
            }
          }
        } else {
          bar_arrive(N_SISS, 384);
          bar_arrive(N_SDONE, 256);
        }
        if (has_next) {
          if (step == 0) mbar_waitw(bar + 8 * B_W1, 0);
          const uint32_t r1 = rb0 + ((nA - 1) << 24) + OFF_BAR + 8 * B_R1;
          if (dual) { DESC(3); wo_phase<16>(sb, wg, warp, lane, par, r1, D); } else { DESC(4); wo_phase<8>(sb, wg, warp, lane, par, r1, D); }
          bar_arrive(N_C, 288);
          if (warp == 0) TS(7 + wg);
        }
      }
      if (has_next) {
        DESC(5);
        float acc[16];
        mbar_waitu(bar + 8 * B_F2, par ^ 1);
        wg_fence(); proj<32, SSQ, 1, 0, 10>(acc, W, D); wg_commit();
        mbar_waitu(bar + 8 * (B_F2 + 1), par ^ 1);
        wg_fence(); proj<32, SSQ, 1, 10, 14>(acc, W, D); wg_commit();
        wg_wait<1>(); REL(B_R2, 0);
        wg_fence(); proj<32, SSQ, 1, 14, 20>(acc, W, D); wg_commit();
        mbar_waitu(bar + 8 * (B_F2 + 2), par ^ 1);
        wg_fence(); proj<32, SSQ, 1, 20, 24>(acc, W, D); wg_commit();
        wg_wait<1>(); REL(B_R2, 1);
        wg_fence(); proj<32, SSQ, 1, 24, 30>(acc, W, D); wg_commit();
        mbar_waitu(bar + 8 * (B_F2 + 3), par ^ 1);
        wg_fence(); proj<32, SSQ, 1, 30, 34>(acc, W, D); wg_commit();
        wg_wait<1>(); REL(B_R2, 2);
        wg_fence(); proj<32, SSQ, 1, 34, 40>(acc, W, D); wg_commit();
        const uint32_t sa = QK_SA, s1 = sa + QK_S12, s2 = sa + QK_S34;
        wg_wait<0>(); REL(B_R2, 3);
        if (warp == 0) TS(11 + wg);
        stsm4t(s1, pack2(acc[0], acc[1]), pack2(acc[2], acc[3]), pack2(acc[4], acc[5]), pack2(acc[6], acc[7]));
        stsm4t(s2, pack2(acc[8], acc[9]), pack2(acc[10], acc[11]), pack2(acc[12], acc[13]), pack2(acc[14], acc[15]));
      }
    }
    GTS(28);
    cluster_sync_all();
  } else if (wg == 2) {
    asm volatile("setmaxnreg.inc.sync.aligned.u32 160;");
    LANE_INIT();
    uint32_t W[4 * (40 - SSV)];
    ld_rest<0>(W, reinterpret_cast<const uint32_t*>(M.wv + (lane >> 2) * HD + col0 + warp * 16) + (lane & 3));
    uint4 m0[5];
#pragma unroll
    for (int i = 0; i < 5; i++) {
      const int t = i * 128 + warp * 32 + lane;
      m0[i] = __ldg(reinterpret_cast<const uint4*>(mem0 + ((t >> 1) & 7) * DM + (t >> 4) * 16 + ((t ^ (t >> 3)) & 1) * 8));
    }
    mbar_waitw(bar + 8 * B_W0, 0);
    load_w<VA>(W, sb + STG_K + 27 * 2048, warp, lane);
    load_w<VST - VA>(W + 4 * VA, sb + STG_V2, warp, lane);
    fence_async();
    mbar_expect_if(warp + lane == 0, bar + 8 * B_W1, 26 * 2048);
    bar_sync(1, 384);
#pragma unroll
    for (int i = 0; i < 5; i++) {
      const int t = i * 128 + warp * 32 + lane;
      sts128(sb + OFF_TILE + (t / 160) * (TILE_GRP - TILE_SBO) + t * 16, m0[i].x, m0[i].y, m0[i].z, m0[i].w);
    }
#pragma unroll
    for (int i = 4 * VST; i < 4 * (40 - SSV); i++) W[i] = movm(W[i]);
    fence_async();
    mbar_arrive_if(lane == 0, bar + 8 * (B_F1 + warp));
    mbar_expect_if(lane == 0, bar + 8 * (B_F2 + warp), 10240);
    mbar_arrive_if(warp == 3 && lane < 2, bar + 8 * B_PLFREE);
    cluster_sync_all();
    uint32_t vl[8];
    {
      const int step = warp;
      DESC(0);
      float v[16];
      mbar_waitw4(bar + 8 * B_F2, 0);
      wg_fence(); proj<32, SSV, 1, 0, 40>(v, W, D); wg_commit();
      wg_wait<0>();
      mbar_arrive_remote_if(lane < 4, rb0 + ((nA - 4 + lane) << 24) + OFF_BAR + 8 * B_R2);
#pragma unroll
      for (int j = 0; j < 8; j++) vl[j] = pack2v(v[2 * j], v[2 * j + 1]);
      if (warp == 0 && (unsigned)ig < 3) issue_tok(1, B_F2, B_R2, 0);
    }
#pragma unroll 1
    for (int step = 0; step < NSTEP; step++) {
      const uint32_t par = step & 1;
      asm volatile("" : "+r"(lane));
      const bool dual = is_dual(step), has_next = step + 1 < NSTEP;
      mbar_expect_if(lane == 0 && has_next, bar + 8 * (B_F2 + warp), 10240);
      if (warp == 0 && ig == 3 && has_next && sync_b) wait_cnt(&g_xready[sched_l(step + 1)][0], 32);
      bar_sync(N_VGO, 384);
      CFENCE();
#define F1_BYTES (is_dual(step + 1) ? 15360 : 2560)
#define ARM() do { \
        mbar_expect_if(lane == 0 && has_next, bar + 8 * (B_F1 + warp), F1_BYTES); \
        mbar_expect_if(lane == 0 && has_next && warp * nA + (int)rank < 40, bar + 8 * (B_RS + warp), (warp * nA + (int)rank >= 36 ? nA : nh) * (dual ? 512 : 256)); } while (0)
#define O_ADDR() uint32_t oa = sb + OFF_O + (lane >> 4) * PL_SZ + warp * 256 + (lane & 15) * 16, xo = (lane >> 4) * 1024 + warp * 256 + (lane & 15) * 16; \
        asm volatile("" : "+r"(oa), "+r"(xo))
#define O_READY(act) do { if (has_next) { const uint4 ov = lds128(oa); \
        if (act) { st_async_v4(nxt + OFF_XL + xo, ov.x, ov.y, ov.z, ov.w, nxt + OFF_BAR + 8 * B_OPEER); \
                   st_async_v4(prv + OFF_XF + xo, ov.x, ov.y, ov.z, ov.w, prv + OFF_BAR + 8 * B_OPEER); } \
        fence_async(); bar_arrive(N_O, 384); } \
        if (warp == 0) TS(15); } while (0)
#define TOK_L3() if (warp == 0 && ig == 3 && has_next) { mbar_waitu(bar + 8 * B_R1, par); \
        bulk_g2s_mc_e(sb + OFF_TILE + 3 * TILE_GRP + TILE_SBO, &g_xn[0][0] + uni(sched_l(step + 1) * (32 * DM)) + 3 * 5120, 10240, bar + 8 * (B_F2 + 3), mcmask); }
#define OX_SA (sb + OFF_PL + (lane & 7) * 128 + (((warp * 2 + ((lane >> 3) & 1)) ^ (lane & 7)) << 4))
      if (dual) {
        uint32_t vf[8], vm[4], vn[8];
        {
          DESC(0);
          float v[24];
          wg_fence(); proj<48, SSV, 0, 30, 30 + VD1, 30>(v, W, D); wg_commit();
          ARM();
          bar_sync(N_SISS, 384);
          wg_fence(); proj<48, SSV, 0, 30 + VD1, 40, 30>(v, W, D); wg_commit();
          proj<48, SSV, 0, 0, 3, 30>(v, W, D); wg_commit();
          wg_wait<1>(); bar_arrive(N_G3, 160);
          wg_fence(); proj<48, SSV, 0, 3, 10, 30>(v, W, D); wg_commit();
          proj<48, SSV, 0, 10, 13, 30>(v, W, D); wg_commit();
          wg_wait<1>(); REL(B_R1, 0);
          wg_fence(); proj<48, SSV, 0, 13, 20, 30>(v, W, D); wg_commit();
          proj<48, SSV, 0, 20, 23, 30>(v, W, D); wg_commit();
          wg_wait<1>(); REL(B_R1, 1);
          wg_fence(); proj<48, SSV, 0, 23, 30, 30>(v, W, D); wg_commit();
          wg_wait<0>(); REL(B_R1, 2);
          bar_arrive(N_VDONE, 160);
          if (warp == 0) TS(14);
#pragma unroll
          for (int j = 4; j < 8; j++) vf[j] = pack2v(v[4 + 2 * j], v[5 + 2 * j]);
          keep4(vf + 4, lane);
          vm[0] = pack2v(v[0], v[1]); vm[1] = pack2v(v[2], v[3]); vm[2] = pack2v(v[20], v[21]); vm[3] = pack2v(v[22], v[23]);
          keep4(vm, lane);
#pragma unroll
          for (int j = 0; j < 4; j++) vf[j] = pack2v(v[4 + 2 * j], v[5 + 2 * j]);
          keep4(vf, lane);
        }
        {
          DESC(1);
          float o[8];
          O_ADDR();
          bar_sync(N_PM, 224);
          wg_fence();
          MM<8>::rs<dlo(OFF_PL + 3584, 128), 0>(o, vl, D.p);
          MM<8>::rs<dlo(OFF_PL + PL_SZ + 3584, 128), 0>(o + 4, vf, D.p);
          MM<8>::rs<dlo(OFF_PL + 3584 + 256, 128), 1>(o, vl + 4, D.p);
          MM<8>::rs<dlo(OFF_PL + PL_SZ + 3584 + 256, 128), 1>(o + 4, vf + 4, D.p);
          MM<8>::rs<dlo(OFF_PL + 3584 + 512, 128), 1>(o, vm, D.p);
          MM<8>::rs<dlo(OFF_PL + PL_SZ + 3584 + 512, 128), 1>(o + 4, vm, D.p);
          wg_commit();
          const uint4 il = lds128(sb + OFF_INV + (lane & 3) * 16), jf = lds128(sb + OFF_INV + 64 + (lane & 3) * 16);
          const float i0 = rcpf(__uint_as_float(il.x) + __uint_as_float(il.y)), i1 = rcpf(__uint_as_float(il.z) + __uint_as_float(il.w));
          const float j0 = rcpf(__uint_as_float(jf.x) + __uint_as_float(jf.y)), j1 = rcpf(__uint_as_float(jf.z) + __uint_as_float(jf.w));
          wg_wait<0>();
          stsm4t(oa, pack2(o[0] * i0, o[1] * i1), pack2(o[2] * i0, o[3] * i1), pack2(o[4] * j0, o[5] * j1), pack2(o[6] * j0, o[7] * j1));
          O_READY(true);
          TOK_L3();
        }
        {
          DESC(2);
          float v[16];
          bar_sync(N_TURN, 256);
          mbar_waitu(bar + 8 * B_F2, par ^ 1);
          wg_fence(); proj<32, SSV, 1, 0, 10>(v, W, D); wg_commit();
          mbar_waitu(bar + 8 * (B_F2 + 1), par ^ 1);
          wg_fence(); proj<32, SSV, 1, 10, 14>(v, W, D); wg_commit();
          wg_wait<1>(); REL(B_R2, 0);
          wg_fence(); proj<32, SSV, 1, 14, 20>(v, W, D); wg_commit();
          mbar_waitu(bar + 8 * (B_F2 + 2), par ^ 1);
          wg_fence(); proj<32, SSV, 1, 20, 24>(v, W, D); wg_commit();
          wg_wait<1>(); REL(B_R2, 1);
          wg_fence(); proj<32, SSV, 1, 24, 30>(v, W, D); wg_commit();
          mbar_waitu(bar + 8 * (B_F2 + 3), par ^ 1);
          wg_fence(); proj<32, SSV, 1, 30, 34>(v, W, D); wg_commit();
          wg_wait<1>(); REL(B_R2, 2);
          wg_fence(); proj<32, SSV, 1, 34, 40>(v, W, D); wg_commit();
          wg_wait<0>(); REL(B_R2, 3);
#pragma unroll
          for (int j = 0; j < 8; j++) vn[j] = pack2v(v[2 * j], v[2 * j + 1]);
          keep4(vn, lane); keep4(vn + 4, lane);
          if (warp == 0) TS(18);
        }
        DESC(3);
        uint32_t ow[16];
        bar_sync(N_P, 256);
        fence_async();
#define PV16(i, off, va) { float o[8]; wg_fence(); \
          MM<16>::rs<dlo(OFF_PL + (off), 128), 0>(o, va, D.p); \
          MM<16>::rs<dlo(OFF_PL + (off) + 256, 128), 1>(o, va + 4, D.p); \
          MM<16>::rs<dlo(OFF_PL + (off) + 512, 128), 1>(o, vm, D.p); \
          wg_commit(); wg_wait<0>(); \
          _Pragma("unroll") for (int j = 0; j < 4; j++) ow[4 * (i) + j] = pack2v(o[2 * j], o[2 * j + 1]); \
          keep4(ow + 4 * (i), lane); }
        PV16(0, 0, vl) PV16(1, 1792, vl) PV16(2, PL_SZ, vf) PV16(3, PL_SZ + 1792, vf)
        const uint32_t s1 = OX_SA + (lane < 16 ? 3072 : 0), s2 = OX_SA + (lane < 16 ? 2048 : 1024);
        bar_sync(N_V, 128);
        stsm4t(s1, ow[0], ow[1], ow[2], ow[3]);
        stsm4t(s2, ow[4], ow[5], ow[6], ow[7]);
        stsm4t(s1 + PL_SZ, ow[8], ow[9], ow[10], ow[11]);
        stsm4t(s2 + PL_SZ, ow[12], ow[13], ow[14], ow[15]);
#pragma unroll
        for (int j = 0; j < 8; j++) vl[j] = vn[j];
      } else {
        uint32_t vm[4], vn[8];
        {
          DESC(4);
          float v[4];
          wg_fence(); proj<8, SSV, 0, 30, 40, 30>(v, W, D); wg_commit();
          proj<8, SSV, 0, 0, VS1, 30>(v, W, D); wg_commit();
          ARM();
          bar_sync(N_SISS, 384);
          wg_wait<1>(); bar_arrive(N_G3, 160);
          wg_fence(); proj<8, SSV, 0, VS1, 30, 30>(v, W, D); wg_commit();
          if (has_next) { mbar_waitu2(bar + 8 * B_F2, bar + 8 * (B_F2 + 1), par ^ 1); mbar_waitu(bar + 8 * (B_F2 + 2), par ^ 1); }
          wg_wait<0>();
          bar_arrive(N_VDONE, 160);
          vm[0] = pack2v(v[0], v[1]); vm[1] = pack2v(v[2], v[3]); vm[2] = pack2v(v[1], v[0]); vm[3] = pack2v(v[3], v[2]);
        }
        DESC(5);
        float v[16];
        {
          wg_fence(); proj<32, SSV, 1, 0, 30>(v, W, D); wg_commit();
          {
            float o[4];
            O_ADDR();
            bar_sync(N_PM, 192);
            if (warp == 0) TS(14);
            wg_fence();
            MM<8>::rs<dlo(OFF_PL + 3584, 128), 0>(o, vl, D.p);
            MM<8>::rs<dlo(OFF_PL + 3584 + 256, 128), 1>(o, vl + 4, D.p);
            MM<8>::rs<dlo(OFF_PL + 3584 + 512, 128), 1>(o, vm, D.p);
            wg_commit();
            const uint4 il = lds128(sb + OFF_INV + (lane & 3) * 16);
            const float i0 = rcpf(__uint_as_float(il.x) + __uint_as_float(il.y)), i1 = rcpf(__uint_as_float(il.z) + __uint_as_float(il.w));
            wg_wait<0>();
            stsm2t(oa, pack2(o[0] * i0, o[1] * i1), pack2(o[2] * i0, o[3] * i1));
            O_READY(lane < 16);
            TOK_L3();
          }
          if (has_next) {
            mbar_arrive_remote_if(lane < 3, rb0 + ((nA - 4 + lane) << 24) + OFF_BAR + 8 * B_R2);
            bar_sync(N_TURN, 256);
            mbar_waitu(bar + 8 * (B_F2 + 3), par ^ 1);
          }
          wg_fence(); proj<32, SSV, 1, 30, 40>(v, W, D); wg_commit();
          wg_wait<0>();
          if (has_next) REL(B_R2, 3);
#pragma unroll
          for (int j = 0; j < 8; j++) vn[j] = pack2v(v[2 * j], v[2 * j + 1]);
          keep4(vn, lane); keep4(vn + 4, lane);
          if (warp == 0) TS(18);
        }
        float o[16];
        bar_sync(N_P, 256);
        fence_async();
        wg_fence();
        MM<32>::rs<dlo(OFF_PL, 128), 0>(o, vl, D.p);
        MM<32>::rs<dlo(OFF_PL + 256, 128), 1>(o, vl + 4, D.p);
        MM<32>::rs<dlo(OFF_PL + 512, 128), 1>(o, vm, D.p);
        wg_commit();
        const uint32_t s1 = OX_SA + (lane < 16 ? 3072 : 0), s2 = OX_SA + (lane < 16 ? 2048 : 1024);
        wg_wait<0>();
        bar_sync(N_V, 128);
        stsm4t(s1, pack2(o[0], o[1]), pack2(o[2], o[3]), pack2(o[4], o[5]), pack2(o[6], o[7]));
        stsm4t(s2, pack2(o[8], o[9]), pack2(o[10], o[11]), pack2(o[12], o[13]), pack2(o[14], o[15]));
#pragma unroll
        for (int j = 0; j < 8; j++) vl[j] = vn[j];
      }
      bar_arrive(N_OX, 160);
      if (warp == 0) TS(16);
    }
    cluster_sync_all();
  } else {
    asm volatile("setmaxnreg.dec.sync.aligned.u32 32;");
    if (wg > 3) return;
    LANE_INIT();
    struct RsJob { uint32_t* gp; uint32_t la, mb; int n; };
    auto rs_prep = [&](int step, int s, int c) {
      RsJob j;
      const int u = s * nA + rank;
      j.gp = &g_part[0][0][0][0] + (uint32_t)((((step & 1) * 2 + c) * NCL + cl) * 2560 + u * 64 + (lane >> 2) * 8 + (lane & 3));
      j.la = sb + OFF_TILE + c * LAND_F + LAND(s) + lane * 8;
      j.mb = bar + 8 * (B_RS + s);
      j.n = u >= 40 ? 0 : u >= 36 ? 3 : 1;
      asm volatile("" : "+l"(j.gp), "+r"(j.la));
      return j;
    };
    auto rs_sum = [&](RsJob j, int step) {
      if (j.n) {
        auto five = [&](uint32_t la) {
          uint2 p[5];
#pragma unroll
          for (int i = 0; i < 4; i++) p[i] = lds64(la + i * 256);
          asm volatile("{\n.reg .pred q;\nsetp.eq.s32 q, %3, 5;\nmov.u32 %0, 0;\nmov.u32 %1, 0;\n@q ld.shared.v2.b32 {%0,%1}, [%2];\n}"
                       : "=r"(p[4].x), "=r"(p[4].y) : "r"(la + 1024), "r"(nh) : "memory");
          return make_uint2(hadd2bf(hadd2bf(p[0].x, p[1].x), hadd2bf(hadd2bf(p[2].x, p[3].x), p[4].x)),
                            hadd2bf(hadd2bf(p[0].y, p[1].y), hadd2bf(hadd2bf(p[2].y, p[3].y), p[4].y)));
        };
        const uint32_t tag = ((step >> 1) & 1) ^ 1;
        mbar_waitw(j.mb, step & 1);
        uint2 t = five(j.la);
        if (j.n > 1) {
          const uint2 a = five(j.la + (nh == 5 ? 1280 : TILE_GRP - 1280)), b = five(j.la + TILE_GRP);
          t.x = hadd2bf(t.x, hadd2bf(a.x, b.x)); t.y = hadd2bf(t.y, hadd2bf(a.y, b.y));
        }
        const uint32_t t0 = (movm(t.x) & ~1u) | tag, t1 = (movm(t.y) & ~1u) | tag;
        asm volatile("st.relaxed.gpu.global.b32 [%0], %1;" :: "l"(j.gp), "r"(lane & 16 ? t1 : t0) : "memory");
        asm volatile("st.relaxed.gpu.global.b32 [%0], %1;" :: "l"(j.gp + 4), "r"(lane & 16 ? t0 : t1) : "memory");
      }
    };
    if (warp * nA + (int)rank < 40) {
#pragma unroll
      for (int e = LAG; e < LAG + 2; e++)
        if ((e >> 1) & 1) *reinterpret_cast<uint2*>(&g_part[(e & 1) * 2 + 1][cl][warp * nA + rank][lane * 2]) = make_uint2(1u, 1u);
      __threadfence();
    }
    cluster_sync_all();
    if (warp == 2 && ig >= 0) issue_tok(0, B_F2);
    if (warp != 2) {
#pragma unroll 1
      for (int i = min(warp, 2); i < 20; i += 3) {
        int c0, c1; wo_coord(i, t3, head, c0, c1);
        if (i >= 2 && i < 15) tma2d_e(sb + OFF_WO + (i - 2) * 4096, &M.wo32, c0, c1, bar + 8 * B_W1);
        else if (lane == 0) tma2d_prefetch(&M.wo32, c0, c1);
        __syncwarp();
      }
    }
#pragma unroll 1
    for (int step = 0; step < NSTEP; step++) {
      const uint32_t par = step & 1;
      asm volatile("" : "+r"(lane));
      const bool dual = is_dual(step), has_next = step + 1 < NSTEP;
      {
        bar_sync(N_PX, dual ? 256 : 192);
        if (dual || warp >= 2) tok_softmax(sb, dual ? warp : warp - 2, lane);
        bar_arrive(N_P, 256);
        asm volatile("" : "+r"(lane));
        if (has_next) {
          if (step + 2 == LAG && lane < 20) asm volatile("prefetch.global.L2 [%0];" :: "l"(mem0 + (warp * 20 + lane) * 64));
          const int nw = ig >= 0 ? 3 : 4, j0 = warp < nw ? warp : 8;
          const int sh = dual ? 1 : 0;
          rs_sum(rs_prep(step, j0 >> sh, j0 & sh), step);
          if (warp == 0) TS(17);
          if (dual) rs_sum(rs_prep(step, (j0 + nw) >> 1, (j0 + nw) & 1), step);
          if (warp == 0) { bar_sync(N_C, 288); }
          mbar_arrive_remote_if(lane < nA, rb0 + (lane << 24) + OFF_BAR + 8 * B_LANDFREE);
          const uint32_t gap = dual ? POLL_GAPD : POLL_GAP;
          if (gap) { const uint32_t t0 = clock32(); while (clock32() - t0 < gap) {} }
#pragma unroll 1
          for (int j = j0; j < (dual ? 8 : 4); j += nw) {
            const int u = (j >> sh) * nA + rank, c = j & sh;
            if (u < UMAX && (c || step + 1 != NSEG)) {
              const uint32_t* gq = &g_part[0][0][0][0] + (uint32_t)((par * 2 + c) * NCL * 2560 + u * 64 + lane * 2);
              uint2 pa[NCL];
              POLL(pa, gq);
              deliver(pa, gq, u, c, step + 1 < NSEG ? c : 0, dual ? DS_DUAL : DS_SINGLE, step, j == 0, lane);
            }
            if (warp == 0 && j == 0) TS(13);
          }
          if (warp >= nw && (is_dual(step + 1) || (ig < 3 && step + 2 < NSTEP))) {
            issue_tok(is_dual(step + 1) ? sched_f(step + 1) : sched_l(step + 2), is_dual(step + 1) ? B_F1 : B_F2, B_R2, par ^ 1);
          }
          if (step + 1 == LAG && UMAX) {
            uint4 v[5];
#pragma unroll
            for (int i = 0; i < 5; i++) { const int t = warp * 160 + i * 32 + lane; v[i] = *reinterpret_cast<const uint4*>(mem0 + ((t >> 1) & 7) * DM + (t >> 4) * 16 + ((t ^ (t >> 3)) & 1) * 8); }
            mbar_waitu(bar + 8 * B_LANDFREE, par);
#pragma unroll
            for (int i = 0; i < 5; i++)
              st_async_v4(sb + OFF_TILE + LAND_F + warp * TILE_GRP + (i * 32 + lane) * 16, v[i].x, v[i].y, v[i].z, v[i].w, bar + 8 * (B_F1 + warp));
          }
        }
      }
      if (warp == 3) {
        unsigned char* o0 = g_o + uni(step % RO * (96 * 8192) + (head * 3 + t3) * (dual ? 8192 : 4096));
        bar_sync(N_OX, 160);
        fence_async();
        bulk_s2g_es(o0, sb + OFF_PL, 4096);
        if (dual) bulk_s2g_es(o0 + 4096, sb + OFF_PL + PL_SZ, 4096);
        asm volatile("cp.async.bulk.commit_group;" ::: "memory");
        asm volatile("cp.async.bulk.wait_group.read 0;" ::: "memory");
        __syncwarp();
        mbar_arrive_remote_if(lane < 2, (lane ? nxt : prv) + OFF_BAR + 8 * B_PLFREE);
        asm volatile("cp.async.bulk.wait_group 0;" ::: "memory");
        asm volatile("fence.proxy.async.global;" ::: "memory");
        __syncwarp();
        if (lane == 0) red_release(&g_f[F_O + (head * 3 + t3) / 5][step], 1u);
        __syncwarp();
      }
    }
    cluster_sync_all();
  }
}

__device__ __forceinline__ float gelu2(float x) {
  const float u = x * fmaf(x * x, 0.7978845608028654f * 0.044715f, 0.7978845608028654f);
  float t; asm("tanh.approx.f32 %0, %1;" : "=f"(t) : "f"(u));
  return fmaf(x, t, x); }

struct BParams {
  CUtensorMap wmap[5];
  CUtensorMap wo16;
  const __nv_bfloat16* x;
  __nv_bfloat16* out;
  uint64_t desc;
};
#define BO_O 0
#define BO_RES (6 * 8192)
#define OP_RES 63488
#define BO_STG (BO_RES + 2 * OP_RES)
#define BO_RING_OP (BO_STG + 16384)
#define OP_SLOT 12288
#define NS_OP 3
#define BO_H 81920
#define BO_W1 (BO_H + 16384)
#define BO_RING_MLP (BO_W1 + 81920)
#define BO_BAR 229376
#define BO_BOX (BO_BAR + 248)
#define BO_CARRY (BO_BAR + 512)
#define BO_STAT (BO_CARRY + 2048)
#define B_SMEM (BO_STAT + 256)
static_assert(B_SMEM <= 232448 && BO_RING_OP + NS_OP * OP_SLOT == BO_BAR && BO_RING_MLP + 3 * 16384 == BO_BAR && 2 * 83968 <= BO_RING_MLP, "smem");
enum { BB_W = 0, BB_FULL = 2, BB_TMP = BB_FULL + 3, BB_OFULL = BB_FULL + 5, BB_SFREE = BB_OFULL,
       BB_STAT = BB_SFREE + 6, BB_ZFREE, BB_DONE = BB_ZFREE + 3,
       BB_EMPTY, BB_START = BB_EMPTY, BB_USED = BB_EMPTY + 2, BB_NUM = BB_USED + 3 };
enum { NB_PP = 1, NB_H = 3, NB_END = 4, NB_END2 = 5, NB_STAGED = 6, NB_FREE = 8, NB_EARLY = 10, NB_LAST = 11 };

#define DESC_LO(off) (((SMEM0 + (off)) >> 4) | (1u << 16))

__device__ __forceinline__ uint32_t ld_relaxed(const uint32_t* p) { uint32_t v; asm volatile("ld.relaxed.gpu.global.b32 %0, [%1];" : "=r"(v) : "l"(p) : "memory"); return v; }
__device__ __forceinline__ int fmask(int r) { return (r < NSEG) | ((r >= LAG && r < NSTEP) << 1); }
__device__ __forceinline__ int bmask(int r) { return (r <= NSEG) | ((r >= LAG) << 1); }
__device__ __forceinline__ uint32_t rtarget(int mask) { return mask == 3 ? 64 : 32; }
__device__ __forceinline__ void warp_signal(uint32_t* p, int lane) {
  __syncwarp();
  asm volatile("{\n.reg .pred q;\nsetp.eq.u32 q, %1, 0;\n@q red.release.gpu.global.add.u32 [%0], 1;\n}" :: "l"(p), "r"(lane) : "memory");
}
__device__ __forceinline__ uint32_t pack2h(float lo, float hi) { uint32_t r; asm("cvt.rn.f16x2.f32 %0, %1, %2;" : "=r"(r) : "f"(hi), "f"(lo)); return r; }
template <bool H> __device__ __forceinline__ uint32_t pk(float lo, float hi) { return H ? pack2h(lo, hi) : pack2(lo, hi); }
template <int N, bool H> __device__ __forceinline__ void stage_out(const float* d, uint32_t dst, int warp, int lane) {
  const uint32_t sa = dst + ((lane >> 4) * 8 + (lane & 7)) * 128 + (((2 * warp + ((lane >> 3) & 1)) ^ (lane & 7)) << 4);
#pragma unroll
  for (int m = 0; m < N / 16; m++)
    stsm4t(sa + m * 2048, pk<H>(d[8 * m], d[8 * m + 1]), pk<H>(d[8 * m + 2], d[8 * m + 3]), pk<H>(d[8 * m + 4], d[8 * m + 5]), pk<H>(d[8 * m + 6], d[8 * m + 7]));
}
template <int N> __device__ __forceinline__ void acc_live(float* d) {
#pragma unroll
  for (int i = 0; i < N / 2; i++) asm volatile("" : "+f"(d[i]) :: "memory");
}
struct Ring {
  uint32_t sl, ph;
  template <int NS> __device__ __forceinline__ void step() { if (++sl == NS) { sl = 0; ph ^= 1; } }
};

#define LOCKSTEP 0
#define KOFF(x) (DESC_LO(BO_O) + ((x) >> 2) * (N * 8) + ((x) & 3) * 2)
template <int N, int P>
__device__ __forceinline__ void op_pass(const uint32_t* W, uint32_t bar, Dsc alo, Dsc blo, Dsc xlo, bool x2, Ring& rg, int wg, int warp, int lane, int r) {
  float acc[N / 2];
  blo.e = xlo.e = fresh<P + N / 64 * 5>(r);
  const Dsc tlo = blo + uni(rg.sl) * (OP_SLOT / 16);
  if (P == 0) mbar_waitu(bar + 8 * BB_OFULL, r & 1);
  CTS(5 * P);
  if (!LOCKSTEP || P > 1 || P == wg) bar_sync(NB_PP + wg, 256);
  wg_fence();
#define OP_R(x) MM<N>::template rs<KOFF(4 * (x >> 1) + (x & 1)), (x != 0)>(acc, W + 32 * P + 4 * x, blo);
#define OP_S(x) MM<N>::template ss<DESC_LO(BO_RES) + (6 * P + x) * 128, KOFF(4 * (x >> 1) + 2 + (x & 1)), 1>(acc, alo, blo);
#define OP_T(x) MM<N>::template ss<DESC_LO(BO_RING_OP) + x * 128, KOFF(14 + x), 1>(acc, tlo, blo);
  OP_R(0) OP_S(0) OP_R(1) OP_S(1) OP_R(2) OP_S(2) OP_R(3) OP_S(3)
  if (P == 0) mbar_waitu(bar + 8 * (BB_OFULL + 1), r & 1);
  if (P == 4) wg_commit();
  OP_R(4) OP_S(4) OP_R(5) OP_S(5)
  if (P == 1 && x2) MM<N>::template ss<DESC_LO(BO_RES) + 30 * 128, KOFF(20), 1>(acc, alo, xlo);
  if (P == 4) { wg_commit(); wg_wait<1>(); bar_arrive(NB_EARLY, 288); CTS(21); wg_fence(); }
  mbar_waitu(bar + 8 * (BB_FULL + rg.sl), rg.ph);
  OP_R(6) OP_T(0) OP_R(7) OP_T(1)
  if (P == 0) mbar_waitu(bar + 8 * (BB_OFULL + 2), r & 1);
  OP_T(2) OP_T(3)
  if (P == 0) MM<N>::template rs<KOFF(20), 1>(acc, W + 160, xlo);
  OP_T(4) OP_T(5)
  wg_commit();
  if (!LOCKSTEP || P) bar_arrive(NB_PP + 1 - wg, 256);
  CTS(5 * P + 2);
  bar_sync(NB_FREE + wg, 160);
  wg_wait<0>();
  acc_live<N>(acc);
  if (P == 4) bar_arrive(NB_LAST, 288);
  mbar_arrive_if(lane == 0, bar + 8 * (BB_USED + rg.sl));
  CTS(5 * P + 3);
  stage_out<N, false>(acc, SMEM0 + BO_STG + wg * 8192, warp, lane);
  bar_arrive(NB_STAGED + wg, 160);
  CTS(5 * P + 4);
  rg.step<NS_OP>(); rg.step<NS_OP>();
}
template <int N>
__device__ __forceinline__ void op_round(const uint32_t* W, uint32_t bar, Dsc alo, Dsc blo, Dsc xlo, bool x2, Ring& rg, int wg, int warp, int lane, int r) {
  op_pass<N, 0>(W, bar, alo, blo, xlo, x2, rg, wg, warp, lane, r);
  op_pass<N, 1>(W, bar, alo, blo, xlo, x2, rg, wg, warp, lane, r);
  op_pass<N, 2>(W, bar, alo, blo, xlo, x2, rg, wg, warp, lane, r);
  op_pass<N, 3>(W, bar, alo, blo, xlo, x2, rg, wg, warp, lane, r);
  op_pass<N, 4>(W, bar, alo, blo, xlo, x2, rg, wg, warp, lane, r);
}
__device__ __forceinline__ void carry_in(uint32_t sb, int wg, int warp, int lane) {
  const int row = (lane >> 1) & 3;
  if (lane < 16) {
    const uint4 v = lds128(sb + BO_CARRY + (wg * 4 + warp) * 256 + lane * 16);
    sts128(sb + BO_H + wg * 8192 + (lane >> 3) * 4096 + row * 128 + (((2 * warp + (lane & 1)) ^ row) << 4), v.x, v.y, v.z, v.w);
  }
  __syncwarp();
}
#define STAGGER 0
template <int N, int Z>
__device__ __forceinline__ void p1_pair(float* acc, const uint32_t* W, uint32_t bar, Dsc alo, Dsc blo, int lane, int r) {
  blo.e = fresh<10 + Z / 3 + N / 64 * 2>(r);
  mbar_waitu(bar + 8 * (BB_FULL + Z), r & 1);
  CTS(40 + Z);
  wg_fence();
#define P1_B(k) \
  MM<N, true>::template rs<DESC_LO(BO_RING_MLP) + (2 * Z % 3) * 1024 + k * 512, (2 * Z + k != 0)>(acc, W + 16 * Z + 8 * k, blo); \
  MM<N, true>::template ss<DESC_LO(BO_W1) + (2 * Z + k) * 512, DESC_LO(BO_RING_MLP) + (2 * Z % 3) * 1024 + k * 512 + 4, 1>(acc, alo, blo); \
  MM<N, true>::template rs<DESC_LO(BO_RING_MLP) + (2 * Z % 3) * 1024 + k * 512 + 2, 1>(acc, W + 16 * Z + 8 * k + 4, blo); \
  MM<N, true>::template ss<DESC_LO(BO_W1) + (2 * Z + k) * 512 + 128, DESC_LO(BO_RING_MLP) + (2 * Z % 3) * 1024 + k * 512 + 6, 1>(acc, alo, blo);
  P1_B(0)
  if (Z == 1 || Z == 2) { wg_commit(); wg_wait<1>(); mbar_arrive_if(lane == 0, bar + 8 * (BB_EMPTY + Z - 1)); wg_fence(); }
  P1_B(1)
  wg_commit();
}
template <int N>
__device__ __forceinline__ void phase1(const uint32_t* W, uint32_t sb, Dsc alo, Dsc blo, int half, int wg, int warp, int lane, int off, int r) {
  float acc[N / 2];
  const uint32_t bar = sb + BO_BAR;
  CTS(30);
  p1_pair<N, 0>(acc, W, bar, alo, blo, lane, r);
  p1_pair<N, 1>(acc, W, bar, alo, blo, lane, r);
  p1_pair<N, 2>(acc, W, bar, alo, blo, lane, r);
  mbar_waitu(bar + 8 * (BB_SFREE + 4 + wg), (r + 1) & 1);
  carry_in(sb, wg, warp, lane);
  if (STAGGER && wg) bar_sync(NB_PP + 1, 256);
  p1_pair<N, 3>(acc, W, bar, alo, blo, lane, r);
  p1_pair<N, 4>(acc, W, bar, alo, blo, lane, r);
  if (STAGGER && !wg) bar_arrive(NB_PP + 1, 256);
  const int c = (lane >> 3) & 1, i0 = (lane >> 4) * 8 + (lane & 7) + off;
  uint32_t a0 = sb + BO_H + wg * 8192 + half * 4096 + i0 * 128 + (((2 * warp + c) ^ (i0 & 7)) << 4);
  uint32_t a1 = i0 >= 16 ? sb + BO_CARRY + (wg * 4 + warp) * 256 + half * 128 + (i0 - 16) * 32 + c * 16 : a0 + 2048, a3 = a1 + (i0 >= 16 ? 128 : 4096);
  asm volatile("" : "+r"(a0), "+r"(a1), "+r"(a3));
  mbar_waitu(bar + 8 * BB_STAT, r & 1);
  const uint32_t sa = sb + BO_STAT + half * 128 + (lane & 3) * 32;
  uint4 t[2] = {lds128(sa), lds128(sa + 16)};
  wg_wait<0>();
  acc_live<N>(acc);
  CTS(32);
#pragma unroll
  for (int m = 0; m < N / 16; m++) {
    const float s0 = __uint_as_float(t[m & 1].x), s1 = __uint_as_float(t[m & 1].y), s2 = __uint_as_float(t[m & 1].z), s3 = __uint_as_float(t[m & 1].w);
    float* d = acc + 8 * m;
    d[0] *= s0; d[1] *= s1; d[2] *= s0; d[3] *= s1; d[4] *= s2; d[5] *= s3; d[6] *= s2; d[7] *= s3;
    if (m + 2 < N / 16) t[m & 1] = lds128(sa + 128 + m * 16);
#pragma unroll
    for (int j = 0; j < 8; j++) d[j] = gelu2(d[j]);
  }
#pragma unroll
  for (int m = 0; m < N / 16; m++)
    stsm4t(m == 1 ? a1 : m == 3 ? a3 : a0 + m * 2048, pack2(acc[8 * m], acc[8 * m + 1]), pack2(acc[8 * m + 2], acc[8 * m + 3]), pack2(acc[8 * m + 4], acc[8 * m + 5]), pack2(acc[8 * m + 6], acc[8 * m + 7]));
}
template <int N, int P>
__device__ __forceinline__ void p2_mma(float* acc, const uint32_t* W, Dsc alo, Dsc blo, int r) {
  blo.e = fresh<P + N / 64 * 5>(r);
  MM<N>::template rs<DESC_LO(BO_H), 0>(acc, W + 80 + 16 * P, blo);     MM<N>::template ss<DESC_LO(0) + P * 1024, DESC_LO(BO_H) + 512, 1>(acc, alo, blo);
  MM<N>::template rs<DESC_LO(BO_H) + 2, 1>(acc, W + 84 + 16 * P, blo); MM<N>::template ss<DESC_LO(0) + P * 1024 + 128, DESC_LO(BO_H) + 514, 1>(acc, alo, blo);
  MM<N>::template rs<DESC_LO(BO_H) + 4, 1>(acc, W + 88 + 16 * P, blo); MM<N>::template ss<DESC_LO(0) + P * 1024 + 512, DESC_LO(BO_H) + 516, 1>(acc, alo, blo);
  MM<N>::template rs<DESC_LO(BO_H) + 6, 1>(acc, W + 92 + 16 * P, blo); MM<N>::template ss<DESC_LO(0) + P * 1024 + 640, DESC_LO(BO_H) + 518, 1>(acc, alo, blo);
}
template <int N, int P, int T>
__device__ __forceinline__ void p2_pass(const uint32_t* W, uint32_t bar, Dsc alo, Dsc blo, int wg, int warp, int lane, int r) {
  float acc[N / 2], ac2[N / 2];
  CTS(5 * P);
  if (P || wg) bar_sync(NB_PP + wg, 256);
  wg_fence();
  p2_mma<N, P>(acc, W, alo, blo, r);
  wg_commit();
  if constexpr (T == 2) { p2_mma<N, P + 1>(ac2, W, alo, blo, r); wg_commit(); }
  if (P < 4 || !wg) bar_arrive(NB_PP + 1 - wg, 256);
  CTS(5 * P + 2);
  if (T == 1 && (P == 2 || P == 3)) mbar_waitu(bar + 8 * (BB_SFREE + 2 * (P - 2) + wg), r & 1);
  wg_wait<T - 1>();
  acc_live<N>(acc);
  if (P == 4) bar_sync(NB_H, 256);
  CTS(5 * P + 3);
  constexpr int K = P / T & 1;
  stage_out<N, true>(acc, SMEM0 + (P == 4 ? BO_H : BO_RING_MLP + (2 - K) * 16384) + wg * 8192, warp, lane);
  if constexpr (T == 2) {
    wg_wait<0>();
    acc_live<N>(ac2);
    stage_out<N, true>(ac2, SMEM0 + BO_RING_MLP + (2 - K) * 16384 + wg * 8192 + 4096, warp, lane);
  }
  bar_arrive(NB_STAGED + (P == 4 ? 4 : 2 * K) + wg, 160);
  CTS(5 * P + 4);
}
template <int N>
__device__ __forceinline__ void phase2(const uint32_t* W, uint32_t bar, Dsc alo, Dsc blo, int wg, int warp, int lane, int r) {
  if constexpr (N == 64) {
    p2_pass<N, 0, 1>(W, bar, alo, blo, wg, warp, lane, r);
    p2_pass<N, 1, 1>(W, bar, alo, blo, wg, warp, lane, r);
    p2_pass<N, 2, 1>(W, bar, alo, blo, wg, warp, lane, r);
    p2_pass<N, 3, 1>(W, bar, alo, blo, wg, warp, lane, r);
  } else {
    p2_pass<N, 0, 2>(W, bar, alo, blo, wg, warp, lane, r);
    p2_pass<N, 2, 2>(W, bar, alo, blo, wg, warp, lane, r);
  }
  p2_pass<N, 4, 1>(W, bar, alo, blo, wg, warp, lane, r);
}

__device__ __forceinline__ void ldg4(uint32_t* v, const void* p) {
  asm volatile("ld.relaxed.gpu.global.v4.u32 {%0,%1,%2,%3}, [%4];" : "=r"(v[0]), "=r"(v[1]), "=r"(v[2]), "=r"(v[3]) : "l"(p) : "memory"); }
__device__ __forceinline__ void stg4(void* p, const uint32_t* v) {
  asm volatile("st.global.v4.u32 [%0], {%1,%2,%3,%4};" :: "l"(p), "r"(v[0]), "r"(v[1]), "r"(v[2]), "r"(v[3]) : "memory"); }
struct RowPtr {
  unsigned char *p, *q, *t;
  __device__ __forceinline__ void ld(uint32_t* v, int o) const {
    ldg4(v, p + o); ldg4(v + 4, q + o);
    asm volatile("ld.relaxed.gpu.global.v2.u32 {%0,%1}, [%2];" : "=r"(v[8]), "=r"(v[9]) : "l"(t + o) : "memory");
  }
  __device__ __forceinline__ void st(const uint32_t* w, int o) const {
    stg4(p + o, w); stg4(q + o, w + 4);
    asm volatile("st.global.v2.u32 [%0], {%1,%2};" :: "l"(t + o), "r"(w[8]), "r"(w[9]) : "memory");
  }
};
__device__ __forceinline__ RowPtr row_img(int r, int n, int lane) {
  unsigned char* b = &g_acc[0][r % RD][n * 128];
  unsigned char* p = b + (uint32_t)((lane >> 3) * 8192 + (((lane ^ n) & 7) << 4));
  return {p, p + 32768, b + (uint32_t)(65536 + (lane >> 4) * 8192 + ((((lane >> 1) ^ n) & 7) << 4) + (lane & 1) * 8)};
}
__device__ __forceinline__ RowPtr row_ext(const void* lin, bool xn, int layer, int tok, int lane) {
  unsigned char* b = xn ? reinterpret_cast<unsigned char*>(&g_xn[layer][0]) + (uint32_t)((tok >> 5) * 40960 + ((tok >> 3) & 3) * 2560 + (tok & 7) * 32)
                        : (unsigned char*)lin + (uint32_t)(tok * 1280);
  const uint32_t o = (lane >> 1) * 256 + ((lane ^ (tok >> 2)) & 1) * 16;
  return {b + (uint32_t)(xn ? o + (lane >= 20 ? 7680 : 0) : lane * 16),
          b + (uint32_t)(xn ? o + 4096 + 7680 + (lane >= 8 ? 7680 : 0) + (lane >= 28 ? 7680 : 0) : lane * 16 + 512),
          b + (uint32_t)(xn ? (lane >> 2) * 256 + ((lane & 3) ^ ((tok >> 1) & 2)) * 8 + 8192 + 3 * 7680 : lane * 8 + 1024)};
}
__device__ __forceinline__ float2 h2f(uint32_t w) {
  float2 f; asm("{\n.reg .f16 l, h;\nmov.b32 {l, h}, %2;\ncvt.f32.f16 %0, l;\ncvt.f32.f16 %1, h;\n}" : "=f"(f.x), "=f"(f.y) : "r"(w)); return f; }
__device__ __forceinline__ float rsq(float x) { float y; asm("rsqrt.approx.ftz.f32 %0, %1;" : "=f"(y) : "f"(x)); return y; }
__device__ __forceinline__ void red_if(uint32_t v, const void* a) {
  asm volatile("{\n.reg .pred q;\nsetp.ne.u32 q, %1, 0;\n@q red.relaxed.gpu.global.add.u32 [%0], %1;\n}" :: "l"(a), "r"(v) : "memory"); }
__device__ __forceinline__ uint32_t dep0(uint32_t w, int lane) { uint32_t z; asm volatile("shr.b32 %0, %1, %2;" : "=r"(z) : "r"(w), "r"(lane + 32)); return z; }
__device__ __forceinline__ int lane_of(uint32_t w) {
  int lane; asm volatile("{\n.reg .u32 t;\nmov.u32 t, %%laneid;\nshr.u32 %0, %1, 20;\nadd.u32 %0, %0, t;\n}" : "=r"(lane) : "r"(w)); return lane; }
#define BUF (RD * TILE_B)
__device__ __forceinline__ int await(uint32_t v, const uint32_t* p, uint32_t target, bool lazy) {
  int n = 0;
  while (!__all_sync(~0u, v >= target)) {
    if (lazy) __nanosleep(200);
    if (++n > SPIN_LIMIT) FAIL();
    v = ld_relaxed(p);
  }
  asm volatile("fence.acquire.gpu;" ::: "memory");
  return lane_of(v);
}
template <int W> __device__ __forceinline__ void sum2(float& s, float& q, int lane) {
  const bool up = lane & (W / 2);
  float e = (up ? q : s) + __shfl_xor_sync(~0u, up ? s : q, W / 2);
#pragma unroll
  for (int o = W / 4; o; o >>= 1) e += __shfl_xor_sync(~0u, e, o);
  const float f = __shfl_xor_sync(~0u, e, W / 2);
  s = up ? f : e; q = up ? e : f;
}
template <int TYPE>
__device__ __forceinline__ void rrow(int r, int row, int tok, int lane, const uint32_t* go, int role, const __nv_bfloat16* x) {
  const int half = TYPE ? 0 : row >> 5;
  float v[20];
  float2 st = make_float2(1.f, 0.f);
  {
    uint32_t a[10], c[10], u[10], sh = 16;
    if (TYPE == 2) row_img(r + RD - ((row & 31) < 2), (row & 32) + ((row - 2) & 31), lane).ld(u, 4 * BUF);
    else row_ext(x, half, 1, tok, lane).ld(u, 0);
    if (TYPE == 2 || (TYPE == 0 && half))
      asm volatile("ld.relaxed.gpu.global.v2.f32 {%0,%1}, [%2];" : "=f"(st.x), "=f"(st.y) : "l"(g_stat + tok) : "memory");
    RowPtr ap = row_img(r, row, lane);
    const uint32_t g0 = TYPE != 3 ? ld_relaxed(go) : 0;
    if (TYPE == 2) {
      ap.ld(c, 2 * BUF);
      uint32_t z = dep0(c[9], lane);
#pragma unroll
      for (int i = 0; i < 10; i++) {
        const float2 g = h2f(u[i] | z), h = h2f(c[i] | z);
        v[2 * i] = fmaf(h.x, 0.5f, g.x * st.x); v[2 * i + 1] = fmaf(h.y, 0.5f, g.y * st.x);
        if (i & 1) z = dep0(__float_as_uint(v[2 * i]) | __float_as_uint(v[2 * i + 1]), lane);
      }
    }
    if (TYPE != 3) {
      asm volatile("" : "+l"(ap.p), "+l"(ap.t));
      ap.q = ap.p + 32768;
      lane = await(g0, go, NOP * NW12 * NW34, false); BTS2(r, 8 + 2 * TYPE); RTS(0);
      ap.ld(a, TYPE ? 3 * BUF : 0);
    }
    if (TYPE == 0) {
      ap.ld(c, BUF);
      const uint32_t one = 0x3f803f80u | dep0(c[9], lane);
#pragma unroll
      for (int i = 0; i < 10; i++) asm volatile("fma.rn.bf16x2 %0, %0, %1, %2;" : "+r"(a[i]) : "r"(one), "r"(c[i]));
      sh |= dep0(a[9], lane);
    }
    const float k = TYPE == 2 ? __uint_as_float(0x3f000000u | dep0(a[9], lane)) : 0.f;
#pragma unroll
    for (int i = 0; i < 10; i++) {
      if (TYPE == 2) { const float2 h = h2f(a[i]); v[2 * i] = fmaf(h.x, k, v[2 * i]); v[2 * i + 1] = fmaf(h.y, k, v[2 * i + 1]); continue; }
      float p = __uint_as_float(u[i] << sh), q = __uint_as_float(u[i] & (0xffffu << sh));
      if (TYPE == 0) { p = fmaf(p, st.x, bf_lo(a[i])); q = fmaf(q, st.x, bf_hi(a[i])); }
      v[2 * i] = p; v[2 * i + 1] = q;
    }
  }
  RTSD(1, v[19]);
  float s = 0.f, q = 0.f;
#pragma unroll
  for (int i = 0; i < 5; i++) {
    s += (v[4 * i] + v[4 * i + 1]) + (v[4 * i + 2] + v[4 * i + 3]);
    q += fmaf(v[4 * i], v[4 * i], v[4 * i + 1] * v[4 * i + 1]) + fmaf(v[4 * i + 2], v[4 * i + 2], v[4 * i + 3] * v[4 * i + 3]);
  }
  sum2<32>(s, q, lane);
  const float mean = s * (1.f / DM), var = fmaxf(q * (1.f / DM) - mean * mean, 0.f), rs = rsq(var + 1e-5f), k = TYPE ? rs : 2.f * rs, mr = -mean * k;
  RTSD(2, rs);
  uint32_t w[10];
#pragma unroll
  for (int i = 0; i < 10; i++) w[i] = pk<TYPE == 0>(fmaf(v[2 * i], k, mr), fmaf(v[2 * i + 1], k, mr));
  if (TYPE) row_ext(nullptr, true, TYPE == 2, tok, lane).st(w, 0);
  else {
    row_img(r, row, lane).st(w, 4 * BUF);
    row_img(r + ((row & 31) >= 30), (row & 32) + ((row + 2) & 31), lane).st(w, 2 * BUF);
    if (lane == 1) g_st2[0][r % RD][row] = (__float_as_uint(0.5f * rsq(fmaf(var * rs, rs, 1e-5f))) & ~127u) | (r + 1);
  }
  if (TYPE != 3 && lane == 0) g_stat[tok] = make_float2((var + 1e-5f) * rs * (TYPE ? 1.f : 0.5f), mean + st.y);
}
__device__ __forceinline__ void r2rows(int r, int row, int lane) {
  const int n = row + (lane >> 4);
  const unsigned char* ap = &g_acc[2][r % RD][0] + (uint32_t)(n * 128 + ((lane >> 3) & 1) * 8192 + (((lane ^ n) & 7) << 4));
  uint32_t a[20];
#pragma unroll
  for (int i = 0; i < 5; i++) ldg4(a + 4 * i, ap + i * 16384);
  const uint32_t z = dep0(a[19], lane);
  float s = 0.f, q = 0.f, q2 = 0.f;
#pragma unroll
  for (int i = 0; i < 20; i++) { const float2 h = h2f(a[i] | z); s += h.x + h.y; q = fmaf(h.x, h.x, q); q2 = fmaf(h.y, h.y, q2); }
  q += q2;
  sum2<16>(s, q, lane);
  const float mean = s * (0.5f / DM), rs = rsq(fmaxf(q * (0.25f / DM) - mean * mean, 0.f) + 1e-5f);
  if ((lane & 15) == 0) asm volatile("st.relaxed.gpu.global.u32 [%0], %1;" :: "l"(&g_st2[1][r % RD][n]), "r"((__float_as_uint(0.5f * rs) & ~127u) | (r + 1)) : "memory");
}
__device__ __forceinline__ void r3rows(int r, int row, int tok, int lane, __nv_bfloat16* out) {
  const int n = row + (lane >> 4), m = 32 + ((n - 2) & 31);
  const unsigned char* ap = &g_acc[0][r % RD][0] + (uint32_t)(n * 128 + ((lane >> 3) & 1) * 8192 + (((lane ^ n) & 7) << 4));
  const unsigned char* zp = &g_acc[4][(r + RD - (row == 32)) % RD][0] + (uint32_t)(m * 128 + ((lane >> 3) & 1) * 8192 + (((lane ^ m) & 7) << 4));
  unsigned char* op = reinterpret_cast<unsigned char*>(out) + (uint32_t)((tok + (lane >> 4)) * 1280 + (lane & 15) * 16);
  float2 st;
  asm volatile("ld.relaxed.gpu.global.v2.f32 {%0,%1}, [%2];" : "=f"(st.x), "=f"(st.y) : "l"(g_stat + tok + (lane >> 4)) : "memory");
#pragma unroll 1
  for (int i0 = 0; i0 < 3; i0++) {
    uint32_t a[8], c[8], u[8];
#pragma unroll
    for (int i = 0; i < 2; i++) { ldg4(a + 4 * i, ap + 3 * BUF + i * 16384); ldg4(c + 4 * i, ap + 2 * BUF + i * 16384); ldg4(u + 4 * i, zp + i * 16384); }
    uint32_t z = dep0(u[7], lane);
#pragma unroll
    for (int i = 0; i < 8; i++) {
      const float2 h = h2f(a[i] | z), e = h2f(c[i] | z), g = h2f(u[i] | z);
      a[i] = pack2(fmaf(h.x + e.x, 0.5f, fmaf(g.x, st.x, st.y)), fmaf(h.y + e.y, 0.5f, fmaf(g.y, st.x, st.y)));
      if (i & 1) z = dep0(a[i], lane);
    }
    if (i0 < 2) stg4(op, a);
    stg4(op + 256, a + 4);
    ap += 32768 >> i0; zp += 32768 >> i0; op += 512 >> i0;
  }
}
template <int TYPE>
__device__ __forceinline__ void rloop(int row, int cp, int role, const __nv_bfloat16* x, __nv_bfloat16* out) {
  constexpr int ST = TYPE == 4 ? 2 : TYPE;
  const int r0 = row & 32 ? LAG : 0;
  uint32_t v = 0;
#pragma unroll 1
  for (int r = r0; r < r0 + NSEG + (TYPE > 0); r++) {
    const int tok = (r - r0) * 32 + (row & 31) - (TYPE ? 2 : 0);
    const bool valid = TYPE == 0 || (unsigned)tok < S_LEN;
    const uint32_t* go = &g_f[F_R1 + 4 * ST + cp][r];
    const uint32_t* first = TYPE == 2 ? &g_f[F_R2 + cp][r] : TYPE ? go : (const uint32_t*)&g_xready[NSEG + r - r0][0];
    if constexpr (TYPE == 1 || TYPE == 4) {
      const int lane = await(v, go, NOP * NW12 * NW34, false);
      BTS2(r, 8 + 2 * ST); RTS(0);
      if (TYPE == 1) { r2rows(r, row, lane); BTS2(r, 11); continue; }
      if (valid) r3rows(r, row, tok, lane, out);
    } else {
      if (TYPE || row >= 32) await(v, first, TYPE ? NOP * NW12 * NW34 : 32, true);
      if (valid) rrow<TYPE>(r, row, tok, lane_of(r), go, role, x);
    }
    if (TYPE == 4 && r + RD - 2 >= NSTEP) { v = 0; BTS2(r, 13); continue; }
    const int lane = lane_of(r);
    const void* f = lane ? (const void*)&g_xready[NSEG + (tok >> 5)][0] : (const void*)&g_f[TYPE ? F_DONE : F_Z][r];
    asm volatile("" : "+l"(f));
    __syncwarp();
    RTS(3);
    v = ld_relaxed(first + (TYPE ? 1 : 8));
    asm volatile("fence.release.gpu;" ::: "memory");
    RTS(4);
    red_if(lane == 0 || (TYPE == 2 && lane == 1 && valid) ? (TYPE & 5 ? 2 : 1) : 0, f);
    RTS(5);
    RTS_OUT();
    BTS2(r, 9 + 2 * ST);
  }
}

#define SINGLE_OP 3
#define SINGLE_W 0
#define W_DELAY 0
#define BULK_ADD(T, dst, src, len) asm volatile("{\n.reg .pred e;\nelect.sync _|e, 0xffffffff;\n@e cp.reduce.async.bulk.global.shared::cta.bulk_group.add.noftz." T " [%0], [%1], %2;\n}" \
                                               :: "l"(dst), "r"(src), "r"(len) : "memory")
#define COMMIT() asm volatile("cp.async.bulk.commit_group;" ::: "memory")
#define DRAINED(n) do { asm volatile("cp.async.bulk.wait_group.read " #n ";" ::: "memory"); __syncwarp(); } while (0)
#define WRITTEN() do { asm volatile("cp.async.bulk.wait_group 0;\nfence.proxy.async.global;" ::: "memory"); __syncwarp(); } while (0)
__device__ __forceinline__ void wait_flags(const uint32_t* p, uint32_t target) {
  int n = 0;
  while (!__all_sync(~0u, ld_relaxed(p) >= target)) { if (++n > SPIN_LIMIT) FAIL(); }
  asm volatile("fence.acquire.gpu;" ::: "memory");
  asm volatile("fence.proxy.async.global;" ::: "memory");
}
__global__ void __launch_bounds__(512, 1) bworker_kernel(const __grid_constant__ BParams P) {
  extern __shared__ __align__(1024) unsigned char smem_raw[];
  const uint32_t sb = SMEM0, bar = sb + BO_BAR;
  const int wg = __shfl_sync(~0u, threadIdx.x >> 7, 0), warp = __shfl_sync(~0u, (threadIdx.x >> 5) & 3, 0);
  if (threadIdx.x == 0) {
    if (smem_u32(smem_raw) != SMEM0) FAIL();
    uint32_t smid; asm volatile("mov.u32 %0, %%smid;" : "=r"(smid));
    const uint32_t nb = ld_relaxed(&g_tpc[(smid >> 1) & 127]);
    const bool single = nb > 1, far = nb == 0 && (smid < 64 || smid >= 124);
    int kind = far || (single && atomicAdd(&g_f[F_MISC][35], 1u) < SINGLE_OP) ? 0 : single ? 1 + SINGLE_W : 1;
    int rc = single || (smid >> 1) == 16 || (smid >> 1) == 63 ? 1 : far ? 2 : 0;
    uint32_t i = atomicAdd(&g_f[F_MISC][32 + kind], 1u), o = atomicAdd(&g_f[F_MISC][36 + rc], 1u);
    while (i >= (kind == 0 ? NOP : kind == 1 ? NW12 : NW34)) { kind = (kind + 1) % 3; i = atomicAdd(&g_f[F_MISC][32 + kind], 1u); }
    while (o >= (rc == 0 ? 16 : rc == 1 ? 8 : 12)) { rc = (rc + 1) % 3; o = atomicAdd(&g_f[F_MISC][36 + rc], 1u); }
    sts64(sb + BO_BOX, i + (kind == 0 ? 0 : kind == 1 ? NOP : NOP + NW12), o + (rc ? 8 + 8 * rc : 0));
    for (int k = 0; k < BB_NUM; k++) mbar_init(bar + 8 * k, k >= BB_USED ? 4 : k >= BB_EMPTY ? 8 : k >= BB_ZFREE && kind ? 2 : 1);
    asm volatile("fence.mbarrier_init.release.cluster;" ::: "memory");
  }
  if (threadIdx.x < 128) sts128(sb + BO_CARRY + threadIdx.x * 16, 0u, 0u, 0u, 0u);
  auto ln0 = [&](int t) {
    const int lane = lane_of(t);
    if (lane < 20 && t + 128 < S_LEN) asm volatile("prefetch.global.L2 [%0];" :: "l"(P.x + (t + (t < 4 * NBC ? 4 * NBC : 128)) * DM + (lane >> 1) * 64));
    rrow<3>(0, 0, t, lane, nullptr, 0, P.x);
    __syncwarp();
    asm volatile("fence.release.gpu;" ::: "memory");
    red_if(lane == 0, &g_xready[t >> 5][0]);
  };
  if (wg == 2) ln0(blockIdx.x * 4 + warp);
  fence_async();
  __syncthreads();
  const int role = uni(lds32(sb + BO_BOX));
  if (threadIdx.x < 32) BTS(94, 1);
  const bool op = role < NOP, w12 = role < NOP + NW12;
  const int j = op ? role : w12 ? role - NOP : role - NOP - NW12;
  const int rot = op ? (j ? 2 * ((j + 1) % 5) : 0) : 2 * (j % 5);
  if (wg == 3) {
    asm volatile("setmaxnreg.dec.sync.aligned.u32 24;");
    LANE_INIT();
    if (warp < 2) {
      auto announce = [&](int r) {
        const uint32_t* f = &g_f[(op ? F_R1 : w12 ? F_R2 : F_R3) + (lane & 3)][r];
        asm volatile("" : "+l"(f));
        if (warp == 0) { mbar_arrive_if(lane == 0, bar + 8 * BB_DONE); return; }
        mbar_waitw(bar + 8 * BB_DONE, r & 1);
        PTS(60);
        asm volatile("fence.release.gpu;" ::: "memory");
        red_if(lane >= 4 ? 0 : op ? NW12 * NW34 : w12 ? NOP * NW34 : NOP * NW12, f);
        PTS(61);
        BTS(r, 4);
      };
      if (op) {
        int mt = rot + warp;
        bar_arrive(NB_FREE + warp, 160);
#pragma unroll 1
        for (int r = 0; r < NSTEP; r++) {
          const uint32_t len = fmask(r) == 3 ? 8192 : 4096;
          unsigned char* acc = &g_acc[j & 1][r % RD][fmask(r) == 2 ? 4096 : 0];
#pragma unroll 1
          for (int p = 0; p < 5; p++) {
            bar_sync(NB_STAGED + warp, 160);
            PTS(50 + 2 * p + warp);
            fence_async();
            BULK_ADD("bf16", acc + mt * 8192, sb + BO_STG + warp * 8192, len);
            COMMIT();
            PTS(64 + 50 + 2 * p + warp);
            mt = mt >= 8 ? mt - 8 : mt + 2;
            DRAINED(0);
            bar_arrive(NB_FREE + warp, 160);
          }
          WRITTEN();
          announce(r);
        }
      } else {
#pragma unroll 1
        for (int r = 0; r < NR; r++) {
          const uint32_t len = bmask(r) == 3 ? 8192 : 4096;
          unsigned char* acc = &g_acc[w12 ? 2 : 3][r % RD][bmask(r) == 2 ? 4096 : 0];
          int mt = rot + warp;
          const bool pairs = len != 8192;
#pragma unroll 1
          for (int p = pairs ? 2 : 0; p < 5; p++) {
            const uint32_t src = sb + (p == 4 ? BO_H : BO_RING_MLP + (2 - (p & 1)) * 16384) + warp * 8192;
            bar_sync(NB_STAGED + (p == 4 ? 4 : 2 * (p & 1)) + warp, 160);
            PTS(50 + 2 * p + warp);
            fence_async();
            BULK_ADD("f16", acc + mt * 8192, src, len);
            mt = mt >= 8 ? mt - 8 : mt + 2;
            if (pairs && p < 4) { BULK_ADD("f16", acc + mt * 8192, src + 4096, len); mt = mt >= 8 ? mt - 8 : mt + 2; }
            COMMIT();
            PTS(64 + 50 + 2 * p + warp);
            if (p == 4 && !pairs) break;
            DRAINED(1);
            mbar_arrive_if(lane == 0, bar + 8 * (p == 1 || p == 2 ? BB_SFREE + 2 * (p - 1) + warp : BB_ZFREE + (p >> 1)));
            mbar_arrive_if(lane < 2 && pairs && p == 2, bar + 8 * (lane ? BB_SFREE + warp : BB_ZFREE));
            if (p == 3 && !pairs) { DRAINED(0); mbar_arrive_if(lane == 0, bar + 8 * (BB_ZFREE + 2)); }
          }
          WRITTEN();
          mbar_arrive_if(lane == 0, bar + 8 * (BB_SFREE + 4 + warp));
          announce(r);
        }
      }
    } else {
      if (op && warp == 2) {
        unsigned char* wt = g_wt + j * (10 * OP_SLOT);
#pragma unroll 1
        for (int m0 = 0; m0 < 10; m0 += 3) {
          const int nu = m0 < 9 ? 9 : 3;
          mbar_expect_if(lane == 0, bar + 8 * BB_TMP, nu * 4096);
#pragma unroll 1
          for (int k = 0; k < nu; k++) tma2d_e(sb + BO_RING_OP + k * 4096, &P.wmap[0], (m0 + k / 3) * 64, 320 * j + 224 + 32 * (k % 3), bar + 8 * BB_TMP);
          mbar_waitw(bar + 8 * BB_TMP, m0 & 1);
          bulk_s2g_e(wt + m0 * OP_SLOT, sb + BO_RING_OP, nu * 4096);
          COMMIT();
          WRITTEN();
        }
        asm volatile("fence.acq_rel.gpu;" ::: "memory");
        int sl = 0, ph = 1, mt = rot;
#pragma unroll 1
        for (int r = -1; r < NSTEP; r++) {
#pragma unroll 1
          for (int n = r < 0 ? 7 : 0; n < (r + 1 < NSTEP ? 10 : 7); n++) {
            mbar_waitw(bar + 8 * (BB_USED + sl), ph);
            mbar_expect_if(lane == 0, bar + 8 * (BB_FULL + sl), OP_SLOT);
            bulk_g2s_e(sb + BO_RING_OP + sl * OP_SLOT, wt + mt * OP_SLOT, OP_SLOT, bar + 8 * (BB_FULL + sl));
            if (++sl == 3) { sl = 0; ph ^= 1; }
            mt = mt == 9 ? 0 : mt + 1;
          }
        }
      } else if (op) {
        mbar_waitw(bar + 8 * BB_START, 0);
#pragma unroll 1
        for (int r = 0; r < NSTEP; r++) {
          const int rb = r - RD + 2;
          const uint32_t len = fmask(r) == 3 ? 8192 : 4096;
          const unsigned char* src = g_o + (uint32_t)(r % RO * (96 * 8192) + 5 * j * len);
          wait_flags(lane < 2 ? &g_f[F_O + (lane ? NOP : j)][r] : rb >= 0 ? &g_f[F_DONE][rb] : &g_f[F_MISC][0],
                     lane < 2 ? (lane ? 1 : 5) : rb >= 0 ? rtarget(bmask(rb)) : NBC * 8);
          PTS1(35);
          if (r) bar_sync(NB_EARLY, 288);
          if (r == LAG) bar_sync(NB_LAST, 288);
          mbar_expect_if(lane < 3, bar + 8 * (BB_OFULL + lane), 2 * len);
          bulk_g2s_e(sb + BO_O, src, 2 * len, bar + 8 * BB_OFULL);
          PTS(62); PTS1(38);
          if (r && r != LAG) bar_sync(NB_LAST, 288);
          bulk_g2s_e(sb + BO_O + 2 * len, src + 2 * len, 2 * len, bar + 8 * (BB_OFULL + 1));
          bulk_g2s_e(sb + BO_O + 4 * len, src + 4 * len, len, bar + 8 * (BB_OFULL + 2));
          bulk_g2s_e(sb + BO_O + 5 * len, src + (95 - 5 * j) * len, len, bar + 8 * (BB_OFULL + 2));
          PTS1(64 + 35);
          BTS(r, 0);
        }
      } else if (warp == 2) {
#pragma unroll 1
        for (int r = 0; r < NR; r++) {
          const int mk = w12 ? fmask(r) : bmask(r);
          if (mk) {
            const unsigned char* src = &g_acc[w12 ? 4 : 2][r % RD][mk == 2 ? 4096 : 0];
            wait_flags(w12 ? &g_f[F_Z][r] : lane && r >= 2 ? &g_f[F_R3 + (j & 3)][r - 2] : &g_f[F_R2 + (j & 3)][r], w12 ? rtarget(mk) : NOP * NW12 * NW34);
#pragma unroll 1
            for (int z = 0; z < 5; z++) {
              const uint32_t fb = bar + 8 * (BB_FULL + z), dst = sb + BO_RING_MLP + 2 * z % 3 * 16384 + (mk == 2 ? 4096 : 0);
              mbar_waitw(bar + 8 * (z < 3 ? BB_ZFREE + z : BB_EMPTY + z - 3), (r + (z < 3)) & 1);
              if (z == 0) PTS(62);
              mbar_expect_if(lane == 0, fb, mk == 3 ? 16384 : 8192);
              bulk_g2s_e(dst, src + z * 16384, mk == 3 ? 16384 : 4096, fb);
              if (mk != 3) bulk_g2s_e(dst + 8192, src + z * 16384 + 8192, 4096, fb);
              if (z == 0) BTS(r, 0);
            }
          }
          if (!w12) {
#pragma unroll 1
            for (int c = j; c < 120; c += NW34) bulk_s2g_e(&g_acc[c < 80 ? c / 40 : 3][(r + (c < 80 ? 0 : 2)) % RD][c % 40 * 2048], sb + BO_CARRY, 2048);
            COMMIT();
            WRITTEN();
          }
          mbar_waitw(bar + 8 * BB_DONE, (r + 1) & 1);
          mbar_arrive_if(lane == 0, bar + 8 * BB_DONE);
        }
      } else {
#pragma unroll 1
        for (int r = 0; r < (w12 ? NSTEP : NR); r++) {
          const bool idle = !((w12 ? fmask(r) : bmask(r)) >> (lane >> 4) & 1);
          uint32_t t0, t1;
          int n = 0;
          mbar_waitw(bar + 8 * BB_FULL, r & 1);
          do {
            asm volatile("ld.relaxed.gpu.global.v2.u32 {%0,%1}, [%2];" : "=r"(t0), "=r"(t1) : "l"(&g_st2[!w12][r % RD][2 * lane]) : "memory");
            if (++n > SPIN_LIMIT) FAIL();
          } while (!__all_sync(~0u, idle || (((t0 ^ (r + 1)) | (t1 ^ (r + 1))) & 127) == 0));
          sts64(sb + BO_STAT + (lane >> 4) * 128 + (lane & 3) * 32 + ((lane >> 2) & 3) * 8, t0, t1);
          __syncwarp();
          mbar_arrive_if(lane == 0, bar + 8 * BB_STAT);
          PTS(63);
        }
      }
    }
    bar_arrive(NB_END, 512);
  } else if (wg == 2) {
    asm volatile("setmaxnreg.dec.sync.aligned.u32 40;");
    const int ord = uni(lds32(sb + BO_BOX + 4));
    const int gw = ord < 16 ? warp * 16 + ord : ord < 24 ? 48 + warp * 8 + ord : 72 + warp * 12 + ord, row = gw < 64 ? gw : gw < 96 ? gw - 64 : gw < 128 ? 2 * gw - 192 : 2 * gw - 224;
    if (row >= 32) {
#pragma unroll 1
      for (int t = 4 * NBC + (gw < 64 ? gw - 32 : gw - 80); t < S_LEN; t += 64) ln0(t);
    }
    if (gw < 64) rloop<0>(row, gw & 3, role, P.x, P.out);
    else if (gw < 96) rloop<2>(row, gw & 3, role, P.x, P.out);
    else if (gw < 128) rloop<1>(row, gw & 3, role, P.x, P.out);
    else rloop<4>(row, gw & 3, role, P.x, P.out);
    asm volatile("griddepcontrol.wait;" ::: "memory");
    const int t = threadIdx.x & 127;
    for (int i = (blockIdx.x * 128 + t) * 4; i < 4 * NCL * 2560; i += NBC * 512)
      *reinterpret_cast<uint4*>(&g_part[0][0][0][0] + i) = make_uint4(0u, 0u, 0u, 0u);
    bar_sync(NB_END, 512);
    if (t == 0) {
      uint32_t n;
      asm volatile("atom.acq_rel.gpu.global.add.u32 %0, [%1], 1;" : "=r"(n) : "l"(&g_f[F_MISC][64]) : "memory");
      sts32(sb + BO_BOX, n);
    }
    bar_sync(NB_END2, 128);
    if (lds32(sb + BO_BOX) == NBC - 1) {
      for (int i = t; i < F_NUM * 24; i += 128) reinterpret_cast<uint4*>(&g_f[0][0])[i] = make_uint4(0u, 0u, 0u, 0u);
      g_xready[t][0] = 0; g_tpc[t] = 0;
    }
  } else {
    asm volatile("setmaxnreg.inc.sync.aligned.u32 224;");
    LANE_INIT();
    for (int i = blockIdx.x * 256 + threadIdx.x; i < 2 * (RD + 1) * TILE_B / 16; i += NBC * 256)
      reinterpret_cast<uint4*>(&g_acc[i < 2 * RD * TILE_B / 16 ? 0 : 1][0][0])[i] = make_uint4(0u, 0u, 0u, 0u);
    warp_signal(&g_f[F_MISC][0], lane);
    const int mt0 = (rot + wg) % 10;
    auto boxes = [&](int ss) {
      const int nb = op && ss ? 3 : 4;
      const uint32_t base = sb + (ss ? BO_RES + wg * OP_RES : wg * 83968);
      mbar_expect_if(warp == 0 && lane == 0, bar + 8 * (BB_W + wg), nb * 20480 + (op ? 2048 : 0));
      bar_sync(NB_H, 256);
      if (warp < nb) {
#pragma unroll 1
        for (int i = warp; i < 5 * nb; i += nb) {
          const int p = op ? i / nb : (i - 10) >> 1, mt = (mt0 + 2 * p) % 10;
          const bool first = !op && i < 10;
          tma2d_e(op || !ss ? base + i * 4096 : sb + (first ? BO_W1 : -81920) + (2 * i + wg) * 4096, &P.wmap[op ? 0 : (w12 ? 1 : 3) + !first], first ? 128 * j + 64 * wg : mt * 64,
                  op ? 320 * j + 64 * warp + 32 * ss : first ? 64 * i + 32 * ss : 128 * j + 32 * (i & 1) + 64 * ss, bar + 8 * (BB_W + wg));
        }
      }
      if (op && warp == 3) tma2d_e(base + nb * 20480, &P.wo16, (mt0 + 2 * ss) % 10 * 64, 95 * 64 + (j + 1) / 5 * 16, bar + 8 * (BB_W + wg));
      mbar_waitw(bar + 8 * (BB_W + wg), ss);
    };
    if (W_DELAY) __nanosleep(W_DELAY);
    uint32_t W[164];
    boxes(0);
    load_w<41>(W, sb + wg * 83968, warp, lane);
    fence_async();
    boxes(1);
    if (!op) {
      float cs[2] = {0.f, 0.f};
      const uint32_t a0 = sb + BO_W1 + wg * 4096 + ((lane >> 4) * 8 + (lane & 7)) * 128 + (((warp * 2 + ((lane >> 3) & 1)) ^ (lane & 7)) << 4);
#pragma unroll
      for (int i = 0; i < 80; i++) cs[i & 1] += bf_lo(W[i]) + bf_hi(W[i]);
#pragma unroll 1
      for (int i = 0; i < 40; i++) {
        uint32_t t[4];
        const uint32_t ad = a0 + (i % 20 >> 1) * 8192 + (i & 1) * 2048;
        ldsm4t(t[0], t[1], t[2], t[3], ad);
#pragma unroll
        for (int k = 0; k < 4; k++) {
          if (i < 20) cs[k & 1] += bf_lo(t[k]) + bf_hi(t[k]);
          t[k] = pack2h(bf_lo(t[k]) - cs[k & 1], bf_hi(t[k]) - cs[k & 1]);
        }
        if (i >= 20) stsm4t(ad, t[0], t[1], t[2], t[3]);
        if (i == 19) {
#pragma unroll
          for (int k = 0; k < 2; k++) { cs[k] += __shfl_xor_sync(~0u, cs[k], 1); cs[k] += __shfl_xor_sync(~0u, cs[k], 2); cs[k] *= 1.f / DM; }
        }
      }
      const uint32_t z = dep0(__float_as_uint(cs[0]), lane);
#pragma unroll
      for (int i = 0; i < 80; i++) W[i] = pack2h(bf_lo(W[i] | z) - cs[i & 1], bf_hi(W[i] | z) - cs[i & 1]);
      fence_async();
      bar_sync(NB_H, 256);
    }
    if (warp == 0) BTS(94, 6 + wg);
    const Dsc blo = {P.desc, 1}, alo = blo + wg * (op ? OP_RES / 16 : 256);
    if (op) {
      Ring rg = {(uint32_t)wg, 0};
      mbar_arrive_if(lane == 0, bar + 8 * BB_START);
      if (wg) bar_arrive(NB_PP, 256);
      const Dsc xlo = blo + (j + 1) / 5 * 2;
#pragma unroll 1
      for (int r = 0; r < NSTEP; r++) {
        asm volatile("" : "+r"(lane));
        if (fmask(r) == 3) op_round<64>(W, bar, alo, blo, xlo, j == 0, rg, wg, warp, lane, r);
        else op_round<32>(W, bar, alo, blo, xlo, j == 0, rg, wg, warp, lane, r);
        if (warp == 0) BTS(r, 2 + wg);
      }
    } else {
      const int q4 = (128 * j + 64 * wg + 16 * warp) / 160, off = w12 ? (0x0413 >> (4 * q4)) & 7 : 0;
#pragma unroll 1
      for (int r = 0; r < NR; r++) {
        asm volatile("" : "+r"(lane));
        const int bm = bmask(r), fm = w12 ? fmask(r) : bm;
        if (fm == 3) phase1<64>(W, sb, alo, blo, 0, wg, warp, lane, off, r);
        else if (fm) phase1<32>(W, sb, alo, blo + (fm >> 1) * 256, fm >> 1, wg, warp, lane, off, r);
        else { mbar_waitu(bar + 8 * (BB_SFREE + 4 + wg), (r + 1) & 1); carry_in(sb, wg, warp, lane); }
        CTS(33);
        fence_async();
        bar_sync(NB_H, 256);
        if (wg + warp == 0) BTS(r, 1);
        if (bm == 3) phase2<64>(W, bar, alo, blo, wg, warp, lane, r);
        else phase2<32>(W, bar, alo, blo + (bm >> 1) * 256, wg, warp, lane, r);
        if (warp == 0) BTS(r, 2 + wg);
      }
    }
    CTS_OUT();
    bar_arrive(NB_END, 512);
  }
}

typedef CUresult (*EncodeFn)(CUtensorMap*, CUtensorMapDataType, cuuint32_t, void*, const cuuint64_t*, const cuuint64_t*, const cuuint32_t*,
                             const cuuint32_t*, CUtensorMapInterleave, CUtensorMapSwizzle, CUtensorMapL2promotion, CUtensorMapFloatOOBfill);
static void make_map(EncodeFn fn, CUtensorMap* tm, const void* ptr, uint64_t cols, uint64_t rows, uint32_t bc, uint32_t br) {
  cuuint64_t dims[2] = {cols, rows}; cuuint64_t strides[1] = {cols * 2}; cuuint32_t box[2] = {bc, br}; cuuint32_t es[2] = {1, 1};
  fn(tm, CU_TENSOR_MAP_DATA_TYPE_BFLOAT16, 2, const_cast<void*>(ptr), dims, strides, box, es, CU_TENSOR_MAP_INTERLEAVE_NONE,
     CU_TENSOR_MAP_SWIZZLE_128B, CU_TENSOR_MAP_L2_PROMOTION_L2_256B, CU_TENSOR_MAP_FLOAT_OOB_FILL_NONE);
}
#define dbg_a_only 0
extern "C" void kernel_launch(void* const* d_in, const int* in_sizes, int n_in, void* d_out, int out_size) {
  void* fnp = nullptr; cudaDriverEntryPointQueryResult qr;
  cudaGetDriverEntryPoint("cuTensorMapEncodeTiled", &fnp, cudaEnableDefault, &qr);
  EncodeFn fn = (EncodeFn)fnp;
  cudaStream_t st = cudaStreamPerThread;
  cudaFuncSetAttribute(bworker_kernel, cudaFuncAttributeMaxDynamicSharedMemorySize, B_SMEM);
  {
    AMaps M;
    for (int i = 0; i < 3; i++) make_map(fn, &M.w16[i], d_in[2 + i], HD, DM, 64, 16);
    M.wv = (const __nv_bfloat16*)d_in[4];
    make_map(fn, &M.wo32, d_in[5], DM, HD, 64, 32);
    const uint32_t hi[5] = {dhi(TILE_SBO, 3), dhi(1024, 1), dhi(1024, 0), dhi(PL_SZ, 0), dhi(896, 0)};
    for (int i = 0; i < 5; i++) M.d[i] = (uint64_t)hi[i] << 32;
    cudaFuncSetAttribute(acore_kernel, cudaFuncAttributeMaxDynamicSharedMemorySize, A_SMEM);
    cudaFuncSetAttribute(acore_kernel, cudaFuncAttributeNonPortableClusterSizeAllowed, 1);
    cudaLaunchConfig_t cfg = {};
    cfg.gridDim = dim3(CL_SIZE * NCL); cfg.blockDim = dim3(512); cfg.dynamicSmemBytes = A_SMEM; cfg.stream = st;
    cudaLaunchAttribute at[1]; at[0].id = cudaLaunchAttributeClusterDimension;
    at[0].val.clusterDim.x = CL_SIZE; at[0].val.clusterDim.y = 1; at[0].val.clusterDim.z = 1;
    cfg.attrs = at; cfg.numAttrs = 1;
    cudaLaunchKernelEx(&cfg, acore_kernel, M, (const __nv_bfloat16*)d_in[1], dbg_a_only ? 0 : 1);
  }
  if (!dbg_a_only) {
    BParams P;
    make_map(fn, &P.wmap[0], d_in[5], DM, HD, 64, 32);
    make_map(fn, &P.wo16, d_in[5], DM, HD, 64, 16);
    make_map(fn, &P.wmap[1], d_in[8], DM, DM, 64, 32);
    make_map(fn, &P.wmap[2], d_in[9], DM, DM, 64, 32);
    make_map(fn, &P.wmap[3], d_in[10], FF, DM, 64, 32);
    make_map(fn, &P.wmap[4], d_in[11], DM, FF, 64, 32);
    P.x = (const __nv_bfloat16*)d_in[0];
    P.out = (__nv_bfloat16*)d_out;
    P.desc = (uint64_t)dhi(1024, 1) << 32;
    cudaLaunchConfig_t cfg = {};
    cfg.gridDim = dim3(NBC); cfg.blockDim = dim3(512); cfg.dynamicSmemBytes = B_SMEM; cfg.stream = st;
    cudaLaunchAttribute at[1]; at[0].id = cudaLaunchAttributeProgrammaticStreamSerialization; at[0].val.programmaticStreamSerializationAllowed = 1;
    cfg.attrs = at; cfg.numAttrs = 1;
    cudaLaunchKernelEx(&cfg, bworker_kernel, P);
  }
}
```

```cpp
#include <cuda_runtime.h>
#include <cuda_bf16.h>
#include <cuda.h>
#include <stdint.h>

#define S_LEN 2048
#define DM 640
#define NH 32
#define DH 192
#define HD 6144
#define NSEG 64
#define FF 1536

__device__ __forceinline__ uint32_t smem_u32(const void* p) { return (uint32_t)__cvta_generic_to_shared(p); }
__device__ __forceinline__ uint32_t mapa(uint32_t a, uint32_t r) {
  uint32_t o; asm volatile("mapa.shared::cluster.u32 %0, %1, %2;" : "=r"(o) : "r"(a), "r"(r)); return o; }
__device__ __forceinline__ void mbar_init(uint32_t b, uint32_t c) {
  asm volatile("mbarrier.init.shared::cta.b64 [%0], %1;" :: "r"(b), "r"(c) : "memory"); }
__device__ __forceinline__ void mbar_expect(uint32_t b, uint32_t tx) {
  asm volatile("mbarrier.arrive.expect_tx.shared::cta.b64 _, [%0], %1;" :: "r"(b), "r"(tx) : "memory"); }
__device__ __forceinline__ void mbar_arrive(uint32_t b) {
  asm volatile("mbarrier.arrive.shared::cta.b64 _, [%0];" :: "r"(b) : "memory"); }
__device__ __forceinline__ void mbar_arrive_remote(uint32_t rb) {
  asm volatile("mbarrier.arrive.relaxed.cluster.shared::cluster.b64 _, [%0];" :: "r"(rb) : "memory"); }
__device__ __forceinline__ void mbar_expect_if(bool p, uint32_t b, uint32_t tx) {
  asm volatile("{\n.reg .pred q;\nsetp.ne.u32 q, %2, 0;\n@q mbarrier.arrive.expect_tx.shared::cta.b64 _, [%0], %1;\n}" :: "r"(b), "r"(tx), "r"((uint32_t)p) : "memory"); }
__device__ __forceinline__ void mbar_arrive_if(bool p, uint32_t b) {
  asm volatile("{\n.reg .pred q;\nsetp.ne.u32 q, %1, 0;\n@q mbarrier.arrive.shared::cta.b64 _, [%0];\n}" :: "r"(b), "r"((uint32_t)p) : "memory"); }
__device__ __forceinline__ void mbar_arrive_remote_if(bool p, uint32_t rb) {
  asm volatile("{\n.reg .pred q;\nsetp.ne.u32 q, %1, 0;\n@q mbarrier.arrive.relaxed.cluster.shared::cluster.b64 _, [%0];\n}" :: "r"(rb), "r"((uint32_t)p) : "memory"); }
__device__ __forceinline__ void sts32_if(bool p, uint32_t a, uint32_t v) {
  asm volatile("{\n.reg .pred q;\nsetp.ne.u32 q, %2, 0;\n@q st.shared.b32 [%0], %1;\n}" :: "r"(a), "r"(v), "r"((uint32_t)p) : "memory"); }
__device__ __forceinline__ void sts128z_if(bool p, uint32_t a) {
  asm volatile("{\n.reg .pred q;\nsetp.ne.u32 q, %1, 0;\n@q st.shared.v4.b32 [%0], {0,0,0,0};\n}" :: "r"(a), "r"((uint32_t)p) : "memory"); }
__device__ __forceinline__ bool mbar_try(uint32_t b, uint32_t ph) {
  uint32_t ok;
  asm volatile("{\n.reg .pred p;\nmbarrier.try_wait.parity.shared::cta.b64 p, [%1], %2;\nselp.u32 %0, 1, 0, p;\n}"
               : "=r"(ok) : "r"(b), "r"(ph) : "memory");
  return ok; }
__device__ __forceinline__ bool mbar_test(uint32_t b, uint32_t ph) {
  uint32_t ok;
  asm volatile("{\n.reg .pred p;\nmbarrier.test_wait.parity.shared::cta.b64 p, [%1], %2;\nselp.u32 %0, 1, 0, p;\n}"
               : "=r"(ok) : "r"(b), "r"(ph) : "memory");
  return ok; }
#define SPIN_LIMIT 4000000
#define FAIL() asm volatile("st.global.u32 [%0], 0;" :: "l"(8ull) : "memory")
#define CFENCE() asm volatile("fence.proxy.async::generic.acquire.sync_restrict::shared::cluster.cluster;" ::: "memory")
__device__ __forceinline__ void mbar_wait(uint32_t b, uint32_t ph) {
  int n = 0;
  while (!mbar_try(b, ph)) { if (++n > SPIN_LIMIT) FAIL(); } }
#define TIMEOUT_ACT "@!p st.shared.u32 [%0+1], 0;"
#define WAIT_HINT ", 20000"
#define WAIT_LIM "200000"
__device__ __forceinline__ void mbar_slow(uint32_t b, uint32_t ph) {
  asm volatile("{\n.reg .pred p, q;\n.reg .u32 n;\nmov.u32 n, 0;\n"
               "WL:\nmbarrier.try_wait.parity.shared::cta.b64 p, [%0], %1" WAIT_HINT ";\nadd.u32 n, n, 1;\nsetp.lt.and.u32 q, n, " WAIT_LIM ", !p;\n@q bra.uni WL;\n"
               TIMEOUT_ACT "\n}" :: "r"(b), "r"(ph) : "memory"); }
__device__ __forceinline__ void mbar_waitw(uint32_t b, uint32_t ph) {
  asm volatile("{\n.reg .pred p, q;\n.reg .u32 n;\nmbarrier.try_wait.parity.shared::cta.b64 p, [%0], %1;\n@p bra.uni WD;\nmov.u32 n, 0;\n"
               "WL:\nmbarrier.try_wait.parity.shared::cta.b64 p, [%0], %1" WAIT_HINT ";\nadd.u32 n, n, 1;\nsetp.lt.and.u32 q, n, " WAIT_LIM ", !p;\n@q bra.uni WL;\n"
               TIMEOUT_ACT "\nWD:\n}" :: "r"(b), "r"(ph) : "memory"); }
__device__ __forceinline__ void mbar_waitw2(uint32_t b0, uint32_t b1, uint32_t ph) {
  uint32_t ok;
  asm volatile("{\n.reg .pred p, r;\nmbarrier.try_wait.parity.shared::cta.b64 p, [%1], %3;\nmbarrier.try_wait.parity.shared::cta.b64 r, [%2], %3;\n"
               "and.pred p, p, r;\nselp.u32 %0, 1, 0, p;\n}" : "=r"(ok) : "r"(b0), "r"(b1), "r"(ph) : "memory");
  if (__builtin_expect(!__all_sync(~0u, ok), 0)) { mbar_slow(b0, ph); mbar_slow(b1, ph); }
}
__device__ __forceinline__ void mbar_waitu(uint32_t b, uint32_t ph) {
  asm volatile("{\n.reg .pred p;\nmbarrier.try_wait.parity.shared::cta.b64 p, [%0], %1;\n@p bra.uni WD;\n"
               "WL:\nmbarrier.try_wait.parity.shared::cta.b64 p, [%0], %1" WAIT_HINT ";\n@!p bra.uni WL;\nWD:\n}" :: "r"(b), "r"(ph) : "memory"); }
__device__ __forceinline__ void mbar_waitu2(uint32_t b0, uint32_t b1, uint32_t ph) {
  asm volatile("{\n.reg .pred p, r;\nWL:\nmbarrier.try_wait.parity.shared::cta.b64 p, [%0], %2;\nmbarrier.try_wait.parity.shared::cta.b64 r, [%1], %2;\n"
               "and.pred p, p, r;\n@!p bra.uni WL;\n}" :: "r"(b0), "r"(b1), "r"(ph) : "memory"); }
__device__ __forceinline__ void mbar_waitw4(uint32_t b, uint32_t ph) { mbar_waitw2(b, b + 8, ph); mbar_waitw2(b + 16, b + 24, ph); }
__device__ __forceinline__ uint32_t clock32() { uint32_t t; asm volatile("mov.u32 %0, %%clock;" : "=r"(t) :: "memory"); return t; }
template <int L> __device__ __forceinline__ uint32_t lop3(uint32_t a, uint32_t b, uint32_t c) {
  uint32_t r; asm("lop3.b32 %0, %1, %2, %3, %4;" : "=r"(r) : "r"(a), "r"(b), "r"(c), "n"(L)); return r; }
__device__ __forceinline__ void st_async_v2_if(bool p, uint32_t a, uint32_t v0, uint32_t v1, uint32_t mb) {
  asm volatile("{\n.reg .pred q;\nsetp.ne.u32 q, %4, 0;\n@q st.async.weak.shared::cluster.mbarrier::complete_tx::bytes.v2.b32 [%0], {%1,%2}, [%3];\n}"
               :: "r"(a), "r"(v0), "r"(v1), "r"(mb), "r"((uint32_t)p) : "memory"); }
__device__ __forceinline__ void keep4(const uint32_t* r, int lane) {
  asm volatile("{\n.reg .pred q;\nsetp.lt.s32 q, %4, 0;\n@q st.shared.v4.b32 [%4], {%0,%1,%2,%3};\n}" :: "r"(r[0]), "r"(r[1]), "r"(r[2]), "r"(r[3]), "r"(lane) : "memory"); }
__device__ __forceinline__ void fence_sched(int i) {
  asm volatile("{\n.reg .pred q;\nsetp.gt.s32 q, %0, 4096;\n@q st.shared.u32 [%0], 0;\n}" :: "r"(i) : "memory"); }
__device__ __forceinline__ uint32_t hmax2bf(uint32_t a, uint32_t b) { uint32_t r; asm("max.bf16x2 %0, %1, %2;" : "=r"(r) : "r"(a), "r"(b)); return r; }
__device__ __forceinline__ uint32_t uni(uint32_t x) { return __shfl_sync(~0u, x, 0); }
__device__ __forceinline__ void bulk_g2s_mc_e(uint32_t dst, const void* src, uint32_t bytes, uint32_t mb, uint16_t mask) {
  asm volatile("{\n.reg .pred e;\nelect.sync _|e, 0xffffffff;\n"
               "@e cp.async.bulk.shared::cluster.global.mbarrier::complete_tx::bytes.multicast::cluster [%0], [%1], %2, [%3], %4;\n}"
               :: "r"(dst), "l"(src), "r"(bytes), "r"(mb), "h"(mask) : "memory"); }
__device__ __forceinline__ void bulk_s2g_e(void* dst, uint32_t src, uint32_t bytes) {
  asm volatile("{\n.reg .pred e;\nelect.sync _|e, 0xffffffff;\n@e cp.async.bulk.global.shared::cta.bulk_group [%0], [%1], %2;\n}"
               :: "l"(dst), "r"(src), "r"(bytes) : "memory"); }
__device__ __forceinline__ void bulk_g2s_e(uint32_t dst, const void* src, uint32_t bytes, uint32_t mb) {
  asm volatile("{\n.reg .pred e;\nelect.sync _|e, 0xffffffff;\n@e cp.async.bulk.shared::cluster.global.mbarrier::complete_tx::bytes [%0], [%1], %2, [%3];\n}"
               :: "r"(dst), "l"(src), "r"(bytes), "r"(mb) : "memory"); }
#define STREAM_HINT 1
__device__ __forceinline__ void bulk_s2g_es(void* dst, uint32_t src, uint32_t bytes) {
  asm volatile("{\n.reg .pred e;\n.reg .b64 pol;\ncreatepolicy.fractional.L2::evict_first.b64 pol;\nelect.sync _|e, 0xffffffff;\n"
               "@e cp.async.bulk.global.shared::cta.bulk_group.L2::cache_hint [%0], [%1], %2, pol;\n}" :: "l"(dst), "r"(src), "r"(bytes) : "memory");
}
__device__ __forceinline__ void bulk_g2s_es(uint32_t dst, const void* src, uint32_t bytes, uint32_t mb) {
  asm volatile("{\n.reg .pred e;\n.reg .b64 pol;\ncreatepolicy.fractional.L2::evict_first.b64 pol;\nelect.sync _|e, 0xffffffff;\n"
               "@e cp.async.bulk.shared::cluster.global.mbarrier::complete_tx::bytes.L2::cache_hint [%0], [%1], %2, [%3], pol;\n}"
               :: "r"(dst), "l"(src), "r"(bytes), "r"(mb) : "memory"); }
__device__ __forceinline__ void tma2d_e(uint32_t dst, const CUtensorMap* tm, int c0, int c1, uint32_t mb) {
  asm volatile("{\n.reg .pred e;\nelect.sync _|e, 0xffffffff;\n"
               "@e cp.async.bulk.tensor.2d.shared::cluster.global.mbarrier::complete_tx::bytes [%0], [%1, {%3, %4}], [%2];\n}"
               :: "r"(dst), "l"((uint64_t)tm), "r"(mb), "r"(c0), "r"(c1) : "memory"); }
__device__ __forceinline__ uint32_t hadd2bf(uint32_t a, uint32_t b) {
  uint32_t r; asm("add.rn.bf16x2 %0, %1, %2;" : "=r"(r) : "r"(a), "r"(b)); return r; }
__device__ __forceinline__ void cluster_sync_all() {
  asm volatile("barrier.cluster.arrive.release.aligned;\nbarrier.cluster.wait.acquire.aligned;" ::: "memory"); }
__device__ __forceinline__ void bar_arrive(int id, int n) { asm volatile("bar.arrive %0, %1;" :: "r"(id), "r"(n) : "memory"); }
__device__ __forceinline__ void bar_arrive_dep(int id, int n, uint32_t dep) {
  asm volatile("{\n.reg .u32 t;\nand.b32 t, %2, 0;\nadd.u32 t, t, %0;\nbar.sync t, %1;\n}" :: "r"(id), "r"(n), "r"(dep) : "memory"); }
__device__ __forceinline__ void bar_sync(int id, int n) { asm volatile("bar.sync %0, %1;" :: "r"(id), "r"(n) : "memory"); }
__device__ __forceinline__ void fence_async() { asm volatile("fence.proxy.async.shared::cta;" ::: "memory"); }
__device__ __forceinline__ void st_async_b32(uint32_t a, uint32_t v, uint32_t mb) {
  asm volatile("st.async.weak.shared::cluster.mbarrier::complete_tx::bytes.b32 [%0], %1, [%2];" :: "r"(a), "r"(v), "r"(mb) : "memory"); }
__device__ __forceinline__ void st_async_v2(uint32_t a, uint32_t v0, uint32_t v1, uint32_t mb) {
  asm volatile("st.async.weak.shared::cluster.mbarrier::complete_tx::bytes.v2.b32 [%0], {%1,%2}, [%3];" :: "r"(a), "r"(v0), "r"(v1), "r"(mb) : "memory"); }
__device__ __forceinline__ void st_async_v4(uint32_t a, uint32_t v0, uint32_t v1, uint32_t v2, uint32_t v3, uint32_t mb) {
  asm volatile("st.async.weak.shared::cluster.mbarrier::complete_tx::bytes.v4.b32 [%0], {%1,%2,%3,%4}, [%5];" :: "r"(a), "r"(v0), "r"(v1), "r"(v2), "r"(v3), "r"(mb) : "memory"); }
__device__ __forceinline__ void ldsm4(uint32_t& r0, uint32_t& r1, uint32_t& r2, uint32_t& r3, uint32_t a) {
  asm volatile("ldmatrix.sync.aligned.m8n8.x4.shared.b16 {%0,%1,%2,%3}, [%4];" : "=r"(r0), "=r"(r1), "=r"(r2), "=r"(r3) : "r"(a) : "memory"); }
__device__ __forceinline__ void ldsm4t(uint32_t& r0, uint32_t& r1, uint32_t& r2, uint32_t& r3, uint32_t a) {
  asm volatile("ldmatrix.sync.aligned.m8n8.x4.trans.shared.b16 {%0,%1,%2,%3}, [%4];" : "=r"(r0), "=r"(r1), "=r"(r2), "=r"(r3) : "r"(a) : "memory"); }
__device__ __forceinline__ void stsm2t(uint32_t a, uint32_t r0, uint32_t r1) {
  asm volatile("stmatrix.sync.aligned.m8n8.x2.trans.shared.b16 [%0], {%1,%2};" :: "r"(a), "r"(r0), "r"(r1) : "memory"); }
__device__ __forceinline__ void stsm4t(uint32_t a, uint32_t r0, uint32_t r1, uint32_t r2, uint32_t r3) {
  asm volatile("stmatrix.sync.aligned.m8n8.x4.trans.shared.b16 [%0], {%1,%2,%3,%4};" :: "r"(a), "r"(r0), "r"(r1), "r"(r2), "r"(r3) : "memory"); }
__device__ __forceinline__ uint32_t movm(uint32_t a) {
  uint32_t d; asm volatile("movmatrix.sync.aligned.m8n8.trans.b16 %0, %1;" : "=r"(d) : "r"(a)); return d; }
__device__ __forceinline__ void mma16816(float* d, uint32_t a0, uint32_t a1, uint32_t a2, uint32_t a3, uint32_t b0, uint32_t b1) {
  asm("mma.sync.aligned.m16n8k16.row.col.f32.bf16.bf16.f32 {%0,%1,%2,%3}, {%4,%5,%6,%7}, {%8,%9}, {%0,%1,%2,%3};"
               : "+f"(d[0]), "+f"(d[1]), "+f"(d[2]), "+f"(d[3]) : "r"(a0), "r"(a1), "r"(a2), "r"(a3), "r"(b0), "r"(b1)); }
__device__ __forceinline__ void mma16816v(float* d, uint32_t a0, uint32_t a1, uint32_t a2, uint32_t a3, uint32_t b0, uint32_t b1) {
  asm volatile("mma.sync.aligned.m16n8k16.row.col.f32.bf16.bf16.f32 {%0,%1,%2,%3}, {%4,%5,%6,%7}, {%8,%9}, {%0,%1,%2,%3};"
               : "+f"(d[0]), "+f"(d[1]), "+f"(d[2]), "+f"(d[3]) : "r"(a0), "r"(a1), "r"(a2), "r"(a3), "r"(b0), "r"(b1)); }
__device__ __forceinline__ uint32_t pack2(float lo, float hi) {
  uint32_t r; asm("cvt.rn.bf16x2.f32 %0, %1, %2;" : "=r"(r) : "f"(hi), "f"(lo)); return r; }
__device__ __forceinline__ uint32_t pack2v(float lo, float hi) {
  uint32_t r; asm volatile("cvt.rn.bf16x2.f32 %0, %1, %2;" : "=r"(r) : "f"(hi), "f"(lo)); return r; }
__device__ __forceinline__ float bf_lo(uint32_t w) { return __uint_as_float(w << 16); }
__device__ __forceinline__ float bf_hi(uint32_t w) { return __uint_as_float(w & 0xffff0000u); }
__device__ __forceinline__ uint4 lds128(uint32_t a) {
  uint4 v; asm volatile("ld.shared.v4.b32 {%0,%1,%2,%3}, [%4];" : "=r"(v.x), "=r"(v.y), "=r"(v.z), "=r"(v.w) : "r"(a) : "memory"); return v; }
__device__ __forceinline__ uint4 lds128_nv(uint32_t a) {
  uint4 v; asm volatile("ld.shared.v4.b32 {%0,%1,%2,%3}, [%4];" : "=r"(v.x), "=r"(v.y), "=r"(v.z), "=r"(v.w) : "r"(a)); return v; }
__device__ __forceinline__ void st_async_v2_nm(uint32_t a, uint32_t v0, uint32_t v1, uint32_t mb) {
  asm volatile("st.async.weak.shared::cluster.mbarrier::complete_tx::bytes.v2.b32 [%0], {%1,%2}, [%3];" :: "r"(a), "r"(v0), "r"(v1), "r"(mb)); }
__device__ __forceinline__ float rcpf(float x) { float y; asm("rcp.approx.ftz.f32 %0, %1;" : "=f"(y) : "f"(x)); return y; }
__device__ __forceinline__ void sts64(uint32_t a, uint32_t x, uint32_t y) { asm volatile("st.shared.v2.b32 [%0], {%1,%2};" :: "r"(a), "r"(x), "r"(y) : "memory"); }
__device__ __forceinline__ float ex2(float x) { float y; asm("ex2.approx.ftz.f32 %0, %1;" : "=f"(y) : "f"(x)); return y; }
__device__ __forceinline__ uint32_t lds32(uint32_t a) {
  uint32_t v; asm volatile("ld.shared.b32 %0, [%1];" : "=r"(v) : "r"(a) : "memory"); return v; }
__device__ __forceinline__ uint2 lds64(uint32_t a) {
  uint2 v; asm volatile("ld.shared.v2.b32 {%0,%1}, [%2];" : "=r"(v.x), "=r"(v.y) : "r"(a) : "memory"); return v; }
__device__ __forceinline__ void sts128(uint32_t a, uint32_t x, uint32_t y, uint32_t z, uint32_t w) {
  asm volatile("st.shared.v4.b32 [%0], {%1,%2,%3,%4};" :: "r"(a), "r"(x), "r"(y), "r"(z), "r"(w) : "memory"); }
__device__ __forceinline__ void sts32(uint32_t a, uint32_t x) { asm volatile("st.shared.b32 [%0], %1;" :: "r"(a), "r"(x) : "memory"); }
__device__ __forceinline__ void tma2d(uint32_t dst, const CUtensorMap* tm, int c0, int c1, uint32_t mb) {
  asm volatile("cp.async.bulk.tensor.2d.shared::cluster.global.mbarrier::complete_tx::bytes [%0], [%1, {%3, %4}], [%2];"
               :: "r"(dst), "l"((uint64_t)tm), "r"(mb), "r"(c0), "r"(c1) : "memory"); }
__device__ __forceinline__ void tma2d_prefetch(const CUtensorMap* tm, int c0, int c1) {
  asm volatile("cp.async.bulk.prefetch.tensor.2d.L2.global.tile [%0, {%1, %2}];" :: "l"((uint64_t)tm), "r"(c0), "r"(c1) : "memory"); }
__device__ __forceinline__ void bulk_g2s_mc(uint32_t dst, const void* src, uint32_t bytes, uint32_t mb, uint16_t mask) {
  asm volatile("cp.async.bulk.shared::cluster.global.mbarrier::complete_tx::bytes.multicast::cluster [%0], [%1], %2, [%3], %4;"
               :: "r"(dst), "l"(src), "r"(bytes), "r"(mb), "h"(mask) : "memory"); }
__device__ __forceinline__ void bulk_s2g(void* dst, uint32_t src, uint32_t bytes) {
  asm volatile("cp.async.bulk.global.shared::cta.bulk_group [%0], [%1], %2;" :: "l"(dst), "r"(src), "r"(bytes) : "memory"); }
__device__ __forceinline__ void wg_fence() { asm volatile("wgmma.fence.sync.aligned;" ::: "memory"); }
__device__ __forceinline__ void wg_commit() { asm volatile("wgmma.commit_group.sync.aligned;" ::: "memory"); }
template <int N> __device__ __forceinline__ void wg_wait() { asm volatile("wgmma.wait_group.sync.aligned %0;" :: "n"(N) : "memory"); }
__device__ __forceinline__ uint64_t mkdesc(uint32_t addr, uint32_t lbo, uint32_t sbo, uint32_t swz) {
  return (uint64_t)((addr & 0x3FFFF) >> 4) | ((uint64_t)(lbo >> 4) << 16) | ((uint64_t)(sbo >> 4) << 32) | ((uint64_t)swz << 62); }

#define ACC4(d) "+f"(d[0]),"+f"(d[1]),"+f"(d[2]),"+f"(d[3])
#define ACC8(d) ACC4(d), ACC4((d + 4))
#define ACC16(d) ACC8(d), ACC8((d + 8))
#define ACC20(d) ACC16(d), ACC4((d + 16))
#define ACC24(d) ACC16(d), ACC8((d + 16))
#define SMEM0 0x400
__host__ __device__ constexpr uint32_t dlo(uint32_t off, uint32_t lbo) { return ((SMEM0 + off) >> 4) | ((lbo >> 4) << 16); }
__host__ __device__ constexpr uint32_t dhi(uint32_t sbo, uint32_t swz) { return (sbo >> 4) | (swz << 30); }
#define R4S "{%0,%1,%2,%3}"
#define R8S "{%0,%1,%2,%3,%4,%5,%6,%7}"
#define R16S "{%0,%1,%2,%3,%4,%5,%6,%7,%8,%9,%10,%11,%12,%13,%14,%15}"
#define R20S "{%0,%1,%2,%3,%4,%5,%6,%7,%8,%9,%10,%11,%12,%13,%14,%15,%16,%17,%18,%19}"
#define R24S "{%0,%1,%2,%3,%4,%5,%6,%7,%8,%9,%10,%11,%12,%13,%14,%15,%16,%17,%18,%19,%20,%21,%22,%23}"
#define ACC32(d) ACC16(d), ACC16((d + 16))
#define R32S "{%0,%1,%2,%3,%4,%5,%6,%7,%8,%9,%10,%11,%12,%13,%14,%15,%16,%17,%18,%19,%20,%21,%22,%23,%24,%25,%26,%27,%28,%29,%30,%31}"
struct Dsc {
  uint64_t b; uint32_t e;
  __device__ __forceinline__ Dsc operator+(uint32_t o) const { return {b + o, e}; }
};
template <int K> __device__ __forceinline__ uint32_t fresh(int i) {
  uint32_t e; asm volatile("{\n.reg .u32 t;\nadd.u32 t, %1, %2;\nshr.u32 %0, t, %3;\n}" : "=r"(e) : "r"(i), "n"((256 << K) + 1), "n"(8 + K)); return e; }
template <int N, bool H = false> struct MM;
#define DEF_MM(N, H, T, ACCM, RS_, I0, I1, I2, I3, I4, I5, I6, I7)                                                                \
  template <> struct MM<N, H> {                                                                                                   \
    template <uint32_t BLO, int ACC>                                                                                              \
    static __device__ __forceinline__ void rs(float* d, const uint32_t* a, Dsc b0) {                                              \
      asm volatile("{\n.reg .b64 b;\nmad.wide.u32 b, %" #I7 ", %" #I5 ", %" #I4 ";\n"                                             \
                   "wgmma.mma_async.sync.aligned.m64n" #N "k16.f32." T "." T " " RS_ ", {%" #I0 ",%" #I1 ",%" #I2 ",%" #I3 "}, b, %" #I6 ", 1, 1, 0;\n}" \
                   : ACCM(d) : "r"(a[0]), "r"(a[1]), "r"(a[2]), "r"(a[3]), "l"(b0.b), "n"(BLO), "n"(ACC), "r"(b0.e)); }           \
    template <uint32_t ALO, uint32_t BLO, int ACC, int TA = 1>                                                                    \
    static __device__ __forceinline__ void ss(float* d, Dsc a0, Dsc b0) {                                                         \
      asm volatile("{\n.reg .b64 a, b;\nmad.wide.u32 a, %" #I6 ", %" #I1 ", %" #I0 ";\nmad.wide.u32 b, %" #I6 ", %" #I3 ", %" #I2 ";\n" \
                   "wgmma.mma_async.sync.aligned.m64n" #N "k16.f32." T "." T " " RS_ ", a, b, %" #I4 ", 1, 1, %" #I5 ", 0;\n}"    \
                   : ACCM(d) : "l"(a0.b), "n"(ALO), "l"(b0.b), "n"(BLO), "n"(ACC), "n"(TA), "r"(b0.e)); }                         \
  };
DEF_MM(8, false, "bf16", ACC4, R4S, 4, 5, 6, 7, 8, 9, 10, 11)
DEF_MM(16, false, "bf16", ACC8, R8S, 8, 9, 10, 11, 12, 13, 14, 15)
DEF_MM(32, false, "bf16", ACC16, R16S, 16, 17, 18, 19, 20, 21, 22, 23)
DEF_MM(40, false, "bf16", ACC20, R20S, 20, 21, 22, 23, 24, 25, 26, 27)
DEF_MM(48, false, "bf16", ACC24, R24S, 24, 25, 26, 27, 28, 29, 30, 31)
DEF_MM(64, false, "bf16", ACC32, R32S, 32, 33, 34, 35, 36, 37, 38, 39)
DEF_MM(32, true, "f16", ACC16, R16S, 16, 17, 18, 19, 20, 21, 22, 23)
DEF_MM(64, true, "f16", ACC32, R32S, 32, 33, 34, 35, 36, 37, 38, 39)

#define LAG 10
#define NSTEP (NSEG + LAG)
#define NR (NSTEP + 1)
__device__ __align__(1024) __nv_bfloat16 g_xn[2][S_LEN * DM];
#define RO 16
static_assert(RO > LAG + 1, "ring");
__device__ __align__(1024) unsigned char g_o[RO * 96 * 8192];
__device__ __align__(1024) uint32_t g_part[6][7][40][64];
#define RD 16
#define TILE_B 81920
__device__ __align__(1024) float2 g_stat[S_LEN];
__device__ __align__(1024) uint32_t g_st2[2][RD][64];
__device__ __align__(1024) unsigned char g_acc[5][RD][TILE_B];
#define NOP 19
#define NW12 5
#define NW34 12
#define NBC (NOP + NW12 + NW34)
__device__ __align__(1024) unsigned char g_wt[NOP * 10 * 12288];
enum { F_O = 0, F_R1 = NOP + 1, F_R2 = F_R1 + 4, F_R3 = F_R2 + 4, F_Z = F_R3 + 4, F_DONE, F_MISC, F_NUM };
__device__ __align__(128) uint32_t g_f[F_NUM][96];
__device__ __align__(128) int g_xready[129][8];
__device__ uint32_t g_tpc[128];
#define TS(i)
#define TSV(i, v)
#define TSN(i)
#define TSD(i, dep)
#define BTS(k, i)
#define BTS2(k, i)
#define RTS(i)
#define RTSD(i, dep)
#define RTS_OUT()
#define CTS(i)
#define PTS(i)
#define PTS1(i)
#define CTS_OUT()
#define GTS(i)

#define CL_SIZE 15
#define NCL 7
#define SSQ 13
#define SSV 16
#define PL_SZ 5376
#define TILE_SBO 2560
#define TILE_GRP 15360
#define WS_SZ ((2 * SSQ + SSV) * 2048)
#define OFF_QK (OFF_WO + 26 * 2048)
#define LAYOUT 2
#define OFF_TILE 0
#define OFF_WS (4 * TILE_GRP)
#define OFF_WO (OFF_WS + WS_SZ)
#define OFF_PL (OFF_QK + 20480)
#define OFF_BAR (OFF_PL + 2 * PL_SZ)
#define STG_Q OFF_TILE
#define STG_K OFF_WO
#define VA 14
#define STG_V2 (OFF_TILE + 27 * 2048)
#define OFF_O (OFF_PL + 4352)
#define LAND(k) (((k) >> 1) * TILE_GRP + ((k) & 1) * 1280)
#define LAND_F (5 * TILE_SBO)
#define OFF_XL (OFF_TILE + 3 * TILE_GRP)
#define OFF_XF (OFF_XL + LAND_F)
#define OFF_WT ((OFF_XL + TILE_SBO + 1023) & ~1023)
#define OFF_TAB (OFF_BAR + 240)
#define OFF_INV (OFF_TAB + 64)
#define OFF_TS (OFF_INV + 128)
#define A_SMEM 232448
static_assert(WS_SZ + 72 * 1024 + 2 * PL_SZ + 4 * TILE_GRP + 512 == A_SMEM && OFF_WS % 1024 == 0 && OFF_WO % 1024 == 0 && SSQ == 13, "smem map");
enum { B_W0 = 0, B_W1, B_F1, B_F2 = B_F1 + 4, B_R1 = B_F2 + 4, B_R2, B_MEMFREE, B_LANDFREE, B_OPEER, B_PLFREE, B_XFREE, B_SB, B_WOF = B_SB + 6, B_WTF, B_RS, B_NUM = B_RS + 4 };
static_assert(B_NUM <= 30, "barriers");
enum { N_C = 0, N_SISS, N_QK, N_V, N_PM, N_TURN, N_PI, N_VGO, N_O, N_PX, N_AB, N_SDONE, N_VDONE, N_G3, N_P, N_OX };

__device__ __forceinline__ bool is_dual(int j) { return j >= LAG && j < NSEG; }
__device__ __forceinline__ int sched_l(int j) { return j < NSEG ? j : NSEG + j - LAG; }
__device__ __forceinline__ int sched_f(int j) { return NSEG + j - LAG; }
__device__ __forceinline__ void wait_cnt(const int* p, int target) {
  int v, n = 0;
  do {
    asm volatile("ld.relaxed.gpu.global.b32 %0, [%1];" : "=r"(v) : "l"(p) : "memory");
    if (v >= target) break;
    if (++n > SPIN_LIMIT) FAIL();
  } while (true);
  asm volatile("fence.acquire.gpu;" ::: "memory");
  asm volatile("fence.proxy.async.global;" ::: "memory");
}
__device__ __forceinline__ void red_release(void* p, uint32_t v) { asm volatile("red.release.gpu.global.add.u32 [%0], %1;" :: "l"(p), "r"(v) : "memory"); }
__device__ __forceinline__ void red_relaxed(void* p, uint32_t v) { asm volatile("red.relaxed.gpu.global.add.u32 [%0], %1;" :: "l"(p), "r"(v) : "memory"); }
#define VMASK 0xa5294a5294ull
__host__ __device__ constexpr int popc40(unsigned long long m) { int c = 0; for (; m; m &= m - 1) c++; return c; }
static_assert(popc40(VMASK) == SSV, "mask");
__host__ __device__ constexpr int ss_idx(int ks, int n) { return n == SSV ? popc40(VMASK & ((1ull << ks) - 1)) : ks * n / 40; }
__host__ __device__ constexpr bool is_ss(int ks, int n) { return ss_idx(ks + 1, n) != ss_idx(ks, n); }
__host__ __device__ constexpr int rs_idx(int ks, int n) { return ks - ss_idx(ks, n); }

#define SL2 (0.07216878364870322f * 1.4426950408889634f)

#define SUM_LOOP 0
struct Desc { Dsc tile, unit, k1, pl, p; };
__device__ __forceinline__ Desc make_desc(const uint64_t* h, uint32_t u, uint32_t e) {
  return {{h[0], e}, {h[1] + u * 128, e}, {h[2], e}, {h[3], e}, {h[4], e}};
}
template <int N, int NSS, int RG, int KS, int K1, int K0 = 0>
__device__ __forceinline__ void proj(float* acc, const uint32_t* W, const Desc& D) {
  if constexpr (KS < K1) {
    constexpr uint32_t BLO = dlo(OFF_TILE + (KS / 10) * TILE_GRP + RG * TILE_SBO + (KS % 10) * 256, 128);
    if constexpr (is_ss(KS, NSS)) MM<N>::template ss<dlo(OFF_WS + ss_idx(KS, NSS) * 2048, 0), BLO, (KS != K0)>(acc, D.unit, D.tile);
    else MM<N>::template rs<BLO, (KS != K0)>(acc, W + rs_idx(KS, NSS) * 4, D.tile);
    proj<N, NSS, RG, KS + 1, K1, K0>(acc, W, D);
  }
}
#define VST 17
template <int KS>
__device__ __forceinline__ void ld_rest(uint32_t* W, const uint32_t* p) {
  if constexpr (KS < 40) {
    if constexpr (!is_ss(KS, SSV) && rs_idx(KS, SSV) >= VST) {
#pragma unroll
      for (int i = 0; i < 4; i++) W[4 * rs_idx(KS, SSV) + i] = __ldg(p + (KS * 16 + (i >> 1) * 8) * (HD / 2) + (i & 1) * 4);
    }
    ld_rest<KS + 1>(W, p);
  }
}
template <int N>
__device__ __forceinline__ void load_w(uint32_t* W, uint32_t stage, int warp, int lane) {
  const int kr = (lane >> 4) * 8 + (lane & 7);
  const int cb = warp * 2 + ((lane >> 3) & 1);
  const uint32_t a0 = stage + kr * 128 + ((cb ^ (lane & 7)) << 4);
#pragma unroll
  for (int i = 0; i < N; i++) ldsm4t(W[4 * i], W[4 * i + 1], W[4 * i + 2], W[4 * i + 3], a0 + i * 2048);
}
template <int N, int G, int U, int OS, int ACC>
__device__ __forceinline__ void wo4(float* d, const Desc& D) {
  constexpr uint32_t WA = (U >= 4 ? OFF_WO + (U - 4) * 2048 : OFF_WT) - G * SSQ * 2048, OB = OS == 0 ? OFF_O : OS == 1 ? OFF_XL : OFF_XF;
  Dsc b = OS ? D.k1 : D.pl;
  b.e = fresh<(U < 16 ? U / 4 : U / 8 - 2) + (N == 8 ? 4 : 0)>(D.unit.e);
  MM<N>::template ss<dlo(WA, 0), dlo(OB, 128), ACC>(d, D.unit, b);
  MM<N>::template ss<dlo(WA + 2048, 0), dlo(OB + 256, 128), 1>(d, D.unit, b);
  MM<N>::template ss<dlo(WA + 4096, 0), dlo(OB + 512, 128), 1>(d, D.unit, b);
  MM<N>::template ss<dlo(WA + 6144, 0), dlo(OB + 768, 128), 1>(d, D.unit, b);
}
__device__ __forceinline__ void wo_coord(int i, int t3, int head, int& c0, int& c1) {
  const int g = i >> 1;
  const int blk = g == 0 ? 9 : (g < 4 ? g - 1 : (g - 4) >> 1) * 3 + t3;
  int sl = g < 4 ? t3 : (g & 1) ? t3 + 1 : t3 + 2;
  if (sl >= 3) sl -= 3;
  c0 = blk * 64; c1 = head * DH + sl * 64 + (i & 1) * 32;
}
__device__ __forceinline__ void tok_softmax(uint32_t sb, int job, int lane) {
  const bool w1 = job & 1;
  const int dg = (lane >> 2) - (lane & 3) * 2;
  const uint32_t lo = sb + OFF_PL + (job >> 1) * PL_SZ + (job & 1) * 1792, l8 = lo + 512 + lane * 8, pa = lo + lane * 4;
  const uint32_t km = job & 2 ? 640 : 512;
  float x[14];
  {
    const uint4 a = lds128(lo + lane * 16);
    const uint2 e = lds64(l8);
    const uint32_t c = lds32(768 + pa);
    x[0] = bf_lo(a.x); x[1] = bf_hi(a.x); x[2] = bf_lo(a.y); x[3] = bf_hi(a.y); x[4] = bf_lo(a.z); x[5] = bf_hi(a.z); x[6] = bf_lo(a.w); x[7] = bf_hi(a.w);
    x[8] = bf_lo(c); x[9] = bf_hi(c); x[10] = bf_lo(e.x); x[11] = bf_hi(e.x); x[12] = bf_lo(e.y); x[13] = bf_hi(e.y);
  }
  if (dg < 0) { x[8] = -INFINITY; if (w1) x[4] = -INFINITY; else x[10] = -INFINITY; }
  if (dg < 1) { x[9] = -INFINITY; if (w1) x[5] = -INFINITY; else x[11] = -INFINITY; }
  const float m4 = fmaxf(x[8], x[9]);
  float m0 = fmaxf(fmaxf(fmaxf(x[0], x[1]), fmaxf(x[2], x[3])), fmaxf(fmaxf(x[4], x[5]), fmaxf(x[6], x[7])));
  float m1 = fmaxf(fmaxf(x[10], x[11]), fmaxf(x[12], x[13]));
  if (w1) m1 = fmaxf(m1, m4); else m0 = fmaxf(m0, m4);
  m0 = fmaxf(m0, __shfl_xor_sync(~0u, m0, 1)); m1 = fmaxf(m1, __shfl_xor_sync(~0u, m1, 1));
  sts32(pa + (w1 ? 384 : 896 + 128), 0u); sts32(pa + 1152 - km, 0u); sts32(pa + 896 + 1152 - km, 0u); sts64(l8 + 896 - 256, 0u, 0u);
  m0 = fmaxf(m0, __shfl_xor_sync(~0u, m0, 2)); m1 = fmaxf(m1, __shfl_xor_sync(~0u, m1, 2));
  m0 *= -SL2; m1 *= -SL2;
#pragma unroll
  for (int j = 0; j < 14; j++) x[j] = ex2(fmaf(x[j], SL2, j < 8 ? m0 : j >= 10 ? m1 : w1 ? m1 : m0));
  const float l4s = x[8] + x[9];
  float l0 = ((x[0] + x[1]) + (x[2] + x[3])) + ((x[4] + x[5]) + (x[6] + x[7])), l1 = (x[10] + x[11]) + (x[12] + x[13]);
  if (w1) l1 += l4s; else l0 += l4s;
  l0 += __shfl_xor_sync(~0u, l0, 1); l1 += __shfl_xor_sync(~0u, l1, 1);
  l0 += __shfl_xor_sync(~0u, l0, 2); l1 += __shfl_xor_sync(~0u, l1, 2);
  l0 = rcpf(l0); l1 = rcpf(l1);
#pragma unroll
  for (int j = 0; j < 7; j++) {
    const float iv = j < 4 ? l0 : j > 4 ? l1 : w1 ? l1 : l0;
    sts32(pa + (j < 3 ? j * 128 : j == 3 ? km : j == 4 ? (w1 ? 896 + 128 : 384) : j == 5 ? 896 : 896 + km), pack2(x[2 * j] * iv, x[2 * j + 1] * iv));
  }
}
template <int N>
__device__ __forceinline__ void wo_phase(uint32_t sb, int wg, int warp, int lane, uint32_t par, uint32_t r1, const Desc& D) {
  const uint32_t bar = sb + OFF_BAR;
  float x[N / 2], y[N / 2];
  const uint2 ta = lds64(sb + OFF_TAB + (wg * 4 + warp) * 8);
  uint32_t xa = (ta.x & ~255u) + lane * 8, xb = (ta.x & 0xFF0000FFu) + SMEM0 + OFF_BAR, ya = (ta.y & ~255u) + lane * 8, yb = (ta.y & 0xFF0000FFu) + SMEM0 + OFF_BAR;
  asm volatile("" : "+r"(xa), "+r"(xb), "+r"(ya), "+r"(yb));
  auto scat = [&](uint32_t ad, uint32_t mb, const float* d) {
    st_async_v2(ad, pack2(d[0], d[1]), pack2(d[2], d[3]), mb);
    if (N == 16) st_async_v2(ad + LAND_F, pack2(d[4], d[5]), pack2(d[6], d[7]), mb);
  };
  if (wg == 0) {
    bar_sync(N_O, 384);
    wg_fence(); wo4<N, 0, 4, 0, 0>(x, D); wo4<N, 0, 8, 0, 0>(y, D); wg_commit();
    mbar_waitu(bar + 8 * B_OPEER, par);
    CFENCE(); wg_fence(); wo4<N, 0, 16, 1, 1>(x, D); wo4<N, 0, 20, 2, 1>(x, D); wg_commit();
    wo4<N, 0, 24, 1, 1>(y, D); wg_commit();
    mbar_waitu2(bar + 8 * B_WOF, bar + 8 * B_MEMFREE, par);
    wg_fence(); wo4<N, 0, 28, 2, 1>(y, D); wg_commit();
    bar_arrive(N_AB, 256);
    wg_wait<2>(); scat(xa, xb, x);
    wg_wait<0>(); scat(ya, yb, y);
  } else {
    bar_sync(N_O, 384);
    wg_fence(); wo4<N, 1, 0, 0, 0>(x, D); wg_commit(); wo4<N, 1, 12, 0, 0>(y, D); wg_commit();
    wg_wait<1>(); mbar_arrive_remote_if(lane == 0, r1);
    mbar_waitu(bar + 8 * B_MEMFREE, par);
    scat(xa, xb, x);
    bar_sync(N_AB, 256);
    CFENCE(); wg_fence(); wo4<N, 1, 32, 1, 1>(y, D); wo4<N, 1, 36, 2, 1>(y, D); wg_commit();
    bar_arrive(N_TURN, 256);
    wg_wait<0>(); scat(ya, yb, y);
  }
}
#define DS_DUAL 10
#define DS_SINGLE 20
#define POLL_GAP 100
#define POLL_GAPD 0
#define TOK_DELAY 250
#define LATE_SM 1
#define UMAX 40
#define VD1 10
#define VS2 20
#define IG_V 3
#define VS1 4
struct AMaps { CUtensorMap w16[3], wo32; uint64_t d[5]; const __nv_bfloat16* wv; };
__global__ void __launch_bounds__(512, 1)
acore_kernel(const __grid_constant__ AMaps M, const __nv_bfloat16* __restrict__ mem0, int sync_b) {
  extern __shared__ __align__(1024) unsigned char smem_raw[];
  const uint32_t sb = smem_u32(smem_raw);
  GTS(24);
  if (threadIdx.x == 480) {
    uint32_t smid; asm volatile("mov.u32 %0, %%smid;" : "=r"(smid));
    g_tpc[(smid >> 1) & 127] = blockIdx.x - CL_SIZE < 3 * CL_SIZE && blockIdx.x % CL_SIZE >= 12 ? 1 : 2;
    asm volatile("griddepcontrol.launch_dependents;");
  }
  const int lane0 = threadIdx.x & 31;
#define LANE_INIT() int lane; asm volatile("mov.u32 %0, %%laneid;" : "=r"(lane))
  const int warp = __shfl_sync(~0u, (threadIdx.x >> 5) & 3, 0);
  const int cl = blockIdx.x / CL_SIZE;
  const uint32_t rank = blockIdx.x - cl * CL_SIZE;
  const int nh = cl >= 1 && cl <= 3 ? 4 : 5;
  const int nA = 3 * nh;
  const int wg = __shfl_sync(~0u, (int)rank < nA ? threadIdx.x >> 7 : 4, 0);
  const int head = (cl < 4 ? (cl ? 1 + 4 * cl : 0) : 5 * cl - 3) + rank / 3;
  const int t3 = rank % 3;
  const int col0 = head * DH + t3 * 64;
  const uint32_t bar = sb + OFF_BAR;
  const uint32_t rb0 = SMEM0;
  const uint16_t mcmask = (uint16_t)((1u << nA) - 1);
  const uint32_t nxt = sb + ((t3 == 2 ? -2 : 1) << 24), prv = sb + ((t3 == 0 ? 2 : -1) << 24);
  const int ig = (int)rank - (nA - 4);

  if (threadIdx.x == 0) {
    if (mapa(sb, nA - 1) != rb0 + ((nA - 1) << 24) || mapa(sb, 0) != rb0 || mapa(sb, 1) != rb0 + (1u << 24) || sb != SMEM0 + (rank << 24)) FAIL();
    for (int i = 0; i < B_NUM; i++)
      mbar_init(bar + 8 * i, i == B_R1 ? 4 * nA : i == B_R2 ? 12 * nA : i == B_MEMFREE ? nA : i == B_LANDFREE ? 4 * nA : i == B_PLFREE || i == B_XFREE ? 2 : 1);
    asm volatile("fence.mbarrier_init.release.cluster;" ::: "memory");
    mbar_expect(bar + 8 * B_W0, (80 + SSV + VST) * 2048);
  }
  __syncthreads();
  if (lane0 == 0) {
    const int w12 = wg * 4 + warp;
    if (w12 < 10) {
#pragma unroll 1
      for (int ks = 4 * w12; ks < 4 * w12 + 4; ks++) {
        const bool ss = is_ss(ks, SSQ);
        tma2d(ss ? sb + OFF_WS + ss_idx(ks, SSQ) * 2048 : sb + STG_Q + rs_idx(ks, SSQ) * 2048, &M.w16[0], col0, ks * 16, bar + 8 * B_W0);
        tma2d(ss ? sb + OFF_WS + (SSQ + ss_idx(ks, SSQ)) * 2048 : sb + STG_K + rs_idx(ks, SSQ) * 2048, &M.w16[1], col0, ks * 16, bar + 8 * B_W0);
        if (is_ss(ks, SSV)) tma2d(sb + OFF_WS + (2 * SSQ + ss_idx(ks, SSV)) * 2048, &M.w16[2], col0, ks * 16, bar + 8 * B_W0);
        else if (rs_idx(ks, SSV) < VST) tma2d(sb + (rs_idx(ks, SSV) < VA ? STG_K + 27 * 2048 : STG_V2 - VA * 2048) + rs_idx(ks, SSV) * 2048, &M.w16[2], col0, ks * 16, bar + 8 * B_W0);
      }
    }
  }
  if (lane0 < 2 && wg < 2) {
    const int u = 4 * (wg ? (lane0 ? 6 + t3 : 9) : (lane0 ? 3 + t3 : t3)) + warp;
    const int li = (u >= nA) + (u >= 2 * nA) + (u >= 3 * nA);
    sts32(sb + OFF_TAB + (wg * 4 + warp) * 8 + lane0 * 4,
          rb0 + ((u - li * nA) << 24) + OFF_TILE + LAND(li + (u >= 36 ? t3 : 0)) + (rank / 3) * 256 + 8 * (B_RS + li));
  }
  __syncthreads();
  GTS(25);

  auto issue_tok = [&](int sc, int fb, int rel = -1, uint32_t ph = 0) {
    if (sync_b) wait_cnt(&g_xready[sc][0], 32);
    if (rel >= 0) mbar_waitu(bar + 8 * rel, ph);
    bulk_g2s_mc_e(sb + OFF_TILE + ig * TILE_GRP + TILE_SBO, &g_xn[0][0] + uni(sc * (32 * DM)) + ig * 5120, 10240, bar + 8 * (fb + ig), mcmask);
  };
#define POLL(d, q) _Pragma("unroll") for (int k = 0; k < NCL; k++) \
      asm volatile("ld.relaxed.gpu.global.v2.b32 {%0,%1}, [%2];" : "=r"(d[k].x), "=r"(d[k].y) : "l"(q + k * 2560) : "memory")
#define L3(L, a, b, c) lop3<L>(a, b, c)
#define TAGS(L, d) L3(L, L3(L, L3(L, d[0].x, d[0].y, d[1].x), L3(L, d[1].y, d[2].x, d[2].y), L3(L, d[3].x, d[3].y, d[4].x)), L3(L, d[4].y, d[5].x, d[5].y), L3(L, d[6].x, d[6].y, d[6].y))
    auto deliver = [&](uint2* pa, const uint32_t* gq, int u, int c, int dc, int ds, int step, bool first, int lane) {
      const uint32_t off = uni(OFF_TILE + ((u * 205) >> 11) * (TILE_GRP - TILE_SBO) + u * 256 + dc * LAND_F), boff = uni(OFF_BAR + 8 * (B_F1 + ((u * 205) >> 11)));
      const uint32_t* mi = &g_part[4][0][0][0] + uni((c * NCL + cl) * 2560 + u * 64);
      mbar_waitu(bar + 8 * B_LANDFREE, step & 1);
      int n = 0;
      while (true) {
        const bool ok = __all_sync(~0u, ((step & 2 ? ~TAGS(0xFE, pa) : TAGS(0x80, pa)) & 1) != 0);
        if (ok) break;
        if (++n > SPIN_LIMIT) FAIL();
        POLL(pa, gq);
      }
      if (warp == 0 && first) { TS(19); TSV(10, n); }
      const uint32_t w0 = hadd2bf(hadd2bf(hadd2bf(pa[0].x, pa[1].x), hadd2bf(pa[2].x, pa[3].x)), hadd2bf(hadd2bf(pa[4].x, pa[5].x), pa[6].x));
      const uint32_t w1 = hadd2bf(hadd2bf(hadd2bf(pa[0].y, pa[1].y), hadd2bf(pa[2].y, pa[3].y)), hadd2bf(hadd2bf(pa[4].y, pa[5].y), pa[6].y));
      if (u < ds) {
        const uint32_t da = SMEM0 + off + lane * 8, db = SMEM0 + boff;
#pragma unroll
        for (int d = 0; d < 12; d++) st_async_v2((d << 24) + da, w0, w1, (d << 24) + db);
#pragma unroll
        for (int d = 12; d < 15; d++) st_async_v2_if(nA == 15, (d << 24) + da, w0, w1, (d << 24) + db);
      } else {
        *reinterpret_cast<uint2*>(const_cast<uint32_t*>(gq) + ((4 - 2 * (step & 1)) * NCL + cl) * 2560) = make_uint2(w0, w1);
        asm volatile("fence.proxy.async.global;" ::: "memory");
        __syncwarp();
        bulk_g2s_mc_e(sb + off, mi, 256, sb + boff, mcmask);
      }
    };
#define REL(b, g) mbar_arrive_remote_if(lane == 0, rb0 + ((nA - 4 + (g)) << 24) + OFF_BAR + 8 * (b))

  if (wg < 2) {
    asm volatile("setmaxnreg.inc.sync.aligned.u32 160;");
    LANE_INIT();
    uint32_t W[4 * (40 - SSQ)];
    mbar_waitw(bar + 8 * B_W0, 0);
    GTS(26);
    load_w<40 - SSQ>(W, sb + (wg ? STG_K : STG_Q), warp, lane);
    fence_async();
    bar_sync(1, 384);
    cluster_sync_all();
#define DESC(k) const Desc D = make_desc(M.d, min(wg, 2) * SSQ, fresh<k>(step))
    GTS(27);
#pragma unroll 1
    for (int step = -1; step < NSTEP; step++) {
      const uint32_t par = step & 1;
      asm volatile("" : "+r"(lane));
      const bool dual = is_dual(step), has_next = step + 1 < NSTEP;
#define QK_SA (sb + OFF_QK + wg * 15360 + (2 * warp + ((lane >> 3) & 1)) * 128 + (lane & 7) * 16)
#define QK_F (wg ? -5120 : 5120)
#define QK_S12 ((wg ? (lane >> 4) : 1 + 2 * (lane >> 4)) * 1024)
#define QK_S34 ((wg ? 2 + (lane >> 4) : 2 - 2 * (lane >> 4)) * 1024)
      if (step >= 0) {
        if (dual) {
          DESC(0);
          float acc[24];
          mbar_waitu(bar + 8 * (B_F1 + 0), par);
          if (wg + warp == 0) { TS(0); TSN(1); }
          CFENCE(); wg_fence(); proj<48, SSQ, 0, 0, 10>(acc, W, D); wg_commit();
          mbar_waitu(bar + 8 * (B_F1 + 1), par);
          CFENCE(); wg_fence(); proj<48, SSQ, 0, 10, 20>(acc, W, D); wg_commit();
          mbar_waitu(bar + 8 * (B_F1 + 2), par);
          CFENCE(); wg_fence(); proj<48, SSQ, 0, 20, 30>(acc, W, D); wg_commit();
          mbar_waitu(bar + 8 * (B_F1 + 3), par);
          if (wg + warp == 0) TS(2);
          CFENCE(); wg_fence(); proj<48, SSQ, 0, 30, 40>(acc, W, D); wg_commit();
          bar_arrive(N_VGO, 384);
          mbar_waitu(bar + 8 * B_PLFREE, par);
          const uint32_t sa = QK_SA, s0 = sa + 4096 + (lane >> 4) * QK_F, s1 = sa + QK_F + QK_S12, s2 = sa + QK_F + QK_S34;
          wg_wait<0>();
          if (wg + warp == 0) TS(3);
          stsm4t(s0, pack2(acc[0], acc[1]), pack2(acc[2], acc[3]), pack2(acc[20], acc[21]), pack2(acc[22], acc[23]));
          stsm4t(s1, pack2(acc[4], acc[5]), pack2(acc[6], acc[7]), pack2(acc[8], acc[9]), pack2(acc[10], acc[11]));
          stsm4t(s2, pack2(acc[12], acc[13]), pack2(acc[14], acc[15]), pack2(acc[16], acc[17]), pack2(acc[18], acc[19]));
        } else {
          DESC(1);
          float acc[4];
          mbar_waitu(bar + 8 * (B_F1 + 0), par);
          if (wg + warp == 0) { TS(0); TSN(1); }
          CFENCE(); wg_fence(); proj<8, SSQ, 0, 0, 10>(acc, W, D); wg_commit();
          mbar_waitu(bar + 8 * (B_F1 + 1), par);
          CFENCE(); wg_fence(); proj<8, SSQ, 0, 10, 20>(acc, W, D); wg_commit();
          mbar_waitu(bar + 8 * (B_F1 + 2), par);
          CFENCE(); wg_fence(); proj<8, SSQ, 0, 20, 30>(acc, W, D); wg_commit();
          mbar_waitu(bar + 8 * (B_F1 + 3), par);
          if (wg + warp == 0) TS(2);
          CFENCE(); wg_fence(); proj<8, SSQ, 0, 30, 40>(acc, W, D); wg_commit();
          bar_arrive(N_VGO, 384);
          mbar_waitu(bar + 8 * B_PLFREE, par);
          const uint32_t s0 = QK_SA + 4096;
          wg_wait<0>();
          if (wg + warp == 0) TS(3);
          stsm2t(s0, pack2(acc[0], acc[1]), pack2(acc[2], acc[3]));
        }
        fence_async();
        bar_sync(N_QK, 256);
        if (wg == 0 || dual) {
          float s[20];
          DESC(2);
          const Dsc ab = D.k1 + wg * 192, bb = D.k1 + (1 - wg) * 320;
          wg_fence();
          MM<40>::ss<dlo(OFF_QK, 128), dlo(OFF_QK + 10240, 128), 0, 0>(s, ab, bb);
          MM<40>::ss<dlo(OFF_QK + 256, 128), dlo(OFF_QK + 10240 + 256, 128), 1, 0>(s, ab, bb);
          MM<40>::ss<dlo(OFF_QK + 512, 128), dlo(OFF_QK + 10240 + 512, 128), 1, 0>(s, ab, bb);
          MM<40>::ss<dlo(OFF_QK + 768, 128), dlo(OFF_QK + 10240 + 768, 128), 1, 0>(s, ab, bb);
          wg_commit();
          bar_arrive(N_SISS, 384);
          const int rw = (warp - wg) & 3;
          const uint32_t bo = OFF_BAR + 8 * (B_SB + 3 * wg + rw), lo = OFF_PL + wg * PL_SZ + rw * 1792;
          const uint32_t km = wg ? 640 : 512;
          uint32_t l16 = lo + lane * 16, l4 = lo + lane * 4;
          mbar_expect_if(lane == 0 && rw < 3, sb + bo, rw < 2 ? 1792 : 1280);
          asm volatile("" : "+r"(l16), "+r"(l4));
          if (rw == 2) {
            wg_wait<0>();
            if (wg == 0) TSD(4, __float_as_uint(s[0]));
            const uint32_t w0 = pack2(s[0], s[1]), w1 = pack2(s[4], s[5]), w2 = pack2(s[8], s[9]), w3 = pack2(s[12], s[13]), w4 = pack2(s[16], s[17]);
            {
              st_async_v4(nxt + 896 + l16, w0, w1, w2, w3, nxt + bo);
              st_async_v4(prv + l16, w0, w1, w2, w3, prv + bo);
              st_async_b32(nxt + 896 + 768 + l4, w4, nxt + bo);
              st_async_b32(prv + 768 + l4, w4, prv + bo);
            }
            bar_arrive(N_SDONE, 256);
            mbar_waitu(sb + bo, (step - wg * LAG) & 1);
            if (wg == 0) TS(5);
            float x[10], m0;
            {
              const uint4 a = lds128(sb + l16), b = lds128(sb + 896 + l16);
              const uint32_t c = lds32(sb + 768 + l4), d = lds32(sb + 896 + 768 + l4);
              const uint32_t e0 = hadd2bf(hadd2bf(a.x, b.x), w0), e1 = hadd2bf(hadd2bf(a.y, b.y), w1), e2 = hadd2bf(hadd2bf(a.z, b.z), w2),
                             e3 = hadd2bf(hadd2bf(a.w, b.w), w3), e4 = hadd2bf(hadd2bf(c, d), w4);
              const uint32_t em = hmax2bf(hmax2bf(hmax2bf(e0, e1), hmax2bf(e2, e3)), e4);
              m0 = fmaxf(bf_lo(em), bf_hi(em));
              x[0] = bf_lo(e0); x[1] = bf_hi(e0); x[2] = bf_lo(e1); x[3] = bf_hi(e1); x[4] = bf_lo(e2);
              x[5] = bf_hi(e2); x[6] = bf_lo(e3); x[7] = bf_hi(e3); x[8] = bf_lo(e4); x[9] = bf_hi(e4);
            }
            m0 = fmaxf(m0, __shfl_xor_sync(~0u, m0, 1));
            sts32(sb + l4 + 1152 - km, 0u);
            m0 = fmaxf(m0, __shfl_xor_sync(~0u, m0, 2));
            m0 *= -SL2;
#pragma unroll
            for (int j = 0; j < 5; j++) {
              x[2 * j] = ex2(fmaf(x[2 * j], SL2, m0)); x[2 * j + 1] = ex2(fmaf(x[2 * j + 1], SL2, m0));
              sts32(sb + l4 + (j < 4 ? j * 128 : km), pack2(x[2 * j], x[2 * j + 1]));
            }
            float l = ((x[0] + x[1]) + (x[2] + x[3])) + ((x[4] + x[5]) + ((x[6] + x[7]) + (x[8] + x[9])));
            l += __shfl_xor_sync(~0u, l, 1);
            fence_async();
            sts32(sb + OFF_INV + wg * 64 + (lane >> 1) * 4, __float_as_uint(l));
            bar_arrive(N_PM, dual ? 224 : 192);
            if (wg == 0) TS(6);
          } else if (rw < 2) {
            const bool w1 = rw == 1;
            const uint32_t l8 = lo + 512 + lane * 8;
            uint32_t tw[7];
            wg_wait<0>();
            bar_arrive(N_SDONE, 256);
            tw[0] = pack2(s[0], s[1]); tw[1] = pack2(s[4], s[5]); tw[2] = pack2(s[8], s[9]); tw[3] = pack2(s[16], s[17]);
            tw[4] = w1 ? pack2(s[6], s[7]) : pack2(s[12], s[13]); tw[5] = pack2(s[2], s[3]); tw[6] = pack2(s[18], s[19]);
            { const uint32_t t0 = clock32(); while (clock32() - t0 < TOK_DELAY) {} }
            st_async_v4(nxt + 896 + l16, tw[0], tw[1], tw[2], tw[3], nxt + bo);
            st_async_v4(prv + l16, tw[0], tw[1], tw[2], tw[3], prv + bo);
            st_async_v2(nxt + 896 + l8, tw[5], tw[6], nxt + bo);
            st_async_v2(prv + l8, tw[5], tw[6], prv + bo);
            st_async_b32(nxt + 896 + 768 + l4, tw[4], nxt + bo);
            st_async_b32(prv + 768 + l4, tw[4], prv + bo);
            mbar_waitu(sb + bo, (step - wg * LAG) & 1);
            const uint4 a = lds128(sb + l16), b = lds128(sb + 896 + l16);
            const uint2 e = lds64(sb + l8), f = lds64(sb + 896 + l8);
            const uint32_t c = lds32(sb + 768 + l4), d = lds32(sb + 896 + 768 + l4);
            sts128(sb + l16, hadd2bf(hadd2bf(a.x, b.x), tw[0]), hadd2bf(hadd2bf(a.y, b.y), tw[1]), hadd2bf(hadd2bf(a.z, b.z), tw[2]), hadd2bf(hadd2bf(a.w, b.w), tw[3]));
            sts64(sb + l8, hadd2bf(hadd2bf(e.x, f.x), tw[5]), hadd2bf(hadd2bf(e.y, f.y), tw[6]));
            sts32(sb + 768 + l4, hadd2bf(hadd2bf(c, d), tw[4]));
            bar_arrive(N_PX, dual ? 256 : 192);
            if (wg + warp == 0) TS(9);
          } else {
            wg_wait<0>();
            if (wg == 0) {
              mbar_expect_if(lane < 3 && has_next, bar + 8 * (lane == 2 ? B_OPEER : B_WOF + lane), lane == 2 ? (dual ? 4096 : 2048) : lane ? 8192 : 20480);
              auto fetch = [&](int i, int n, uint32_t dst, int mb) {
                int c0, c1; wo_coord(i, t3, head, c0, c1);
                tma2d_e(dst, &M.wo32, c0, c1, bar + 8 * mb); if (n == 2) tma2d_e(dst + 4096, &M.wo32, c0, c1 + 32, bar + 8 * mb);
              };
              bar_sync(N_G3, 160);
              if (has_next) {
                fetch(0, 2, sb + OFF_WT, B_WTF);
                mbar_arrive_remote_if(lane < 2, (lane ? nxt : prv) + OFF_BAR + 8 * B_XFREE);
              }
              bar_sync(N_SDONE, 256);
              if (has_next) {
                fetch(15, 1, sb + OFF_QK, B_WOF); fetch(16, 2, sb + OFF_QK + 4096, B_WOF); fetch(18, 2, sb + OFF_QK + 12288, B_WOF);
                mbar_waitu(bar + 8 * B_XFREE, par);
              }
              bar_arrive(N_PM, dual ? 224 : 192);
              bar_sync(N_VDONE, 160);
              mbar_arrive_remote_if(lane < nA && has_next, rb0 + (lane << 24) + OFF_BAR + 8 * B_MEMFREE);
              if (has_next) mbar_waitu(bar + 8 * B_WTF, par);
            } else {
              bar_arrive(N_SDONE, 256);
              if ((unsigned)ig < IG_V) issue_tok(sched_l(step + 1), B_F2, B_R1, (step - LAG) & 1);
            }
          }
        } else {
          bar_arrive(N_SISS, 384);
          bar_arrive(N_SDONE, 256);
        }
        if (has_next) {
          if (step == 0) mbar_waitw(bar + 8 * B_W1, 0);
          const uint32_t r1 = rb0 + ((nA - 1) << 24) + OFF_BAR + 8 * B_R1;
          if (dual) { DESC(3); wo_phase<16>(sb, wg, warp, lane, par, r1, D); } else { DESC(4); wo_phase<8>(sb, wg, warp, lane, par, r1, D); }
          bar_arrive(N_C, 288);
          if (warp == 0) TS(7 + wg);
        }
      }
      if (has_next) {
        DESC(5);
        float acc[16];
        mbar_waitu(bar + 8 * B_F2, par ^ 1);
        wg_fence(); proj<32, SSQ, 1, 0, 10>(acc, W, D); wg_commit();
        mbar_waitu(bar + 8 * (B_F2 + 1), par ^ 1);
        wg_fence(); proj<32, SSQ, 1, 10, 14>(acc, W, D); wg_commit();
        wg_wait<1>(); REL(B_R2, 0);
        wg_fence(); proj<32, SSQ, 1, 14, 20>(acc, W, D); wg_commit();
        mbar_waitu(bar + 8 * (B_F2 + 2), par ^ 1);
        wg_fence(); proj<32, SSQ, 1, 20, 24>(acc, W, D); wg_commit();
        wg_wait<1>(); REL(B_R2, 1);
        wg_fence(); proj<32, SSQ, 1, 24, 30>(acc, W, D); wg_commit();
        mbar_waitu(bar + 8 * (B_F2 + 3), par ^ 1);
        wg_fence(); proj<32, SSQ, 1, 30, 34>(acc, W, D); wg_commit();
        wg_wait<1>(); REL(B_R2, 2);
        wg_fence(); proj<32, SSQ, 1, 34, 40>(acc, W, D); wg_commit();
        const uint32_t sa = QK_SA, s1 = sa + QK_S12, s2 = sa + QK_S34;
        wg_wait<0>(); REL(B_R2, 3);
        if (warp == 0) TS(11 + wg);
        stsm4t(s1, pack2(acc[0], acc[1]), pack2(acc[2], acc[3]), pack2(acc[4], acc[5]), pack2(acc[6], acc[7]));
        stsm4t(s2, pack2(acc[8], acc[9]), pack2(acc[10], acc[11]), pack2(acc[12], acc[13]), pack2(acc[14], acc[15]));
      }
    }
    GTS(28);
    cluster_sync_all();
  } else if (wg == 2) {
    asm volatile("setmaxnreg.inc.sync.aligned.u32 160;");
    LANE_INIT();
    uint32_t W[4 * (40 - SSV)];
    ld_rest<0>(W, reinterpret_cast<const uint32_t*>(M.wv + (lane >> 2) * HD + col0 + warp * 16) + (lane & 3));
    uint4 m0[5];
#pragma unroll
    for (int i = 0; i < 5; i++) {
      const int t = i * 128 + warp * 32 + lane;
      m0[i] = __ldg(reinterpret_cast<const uint4*>(mem0 + ((t >> 1) & 7) * DM + (t >> 4) * 16 + ((t ^ (t >> 3)) & 1) * 8));
    }
    mbar_waitw(bar + 8 * B_W0, 0);
    load_w<VA>(W, sb + STG_K + 27 * 2048, warp, lane);
    load_w<VST - VA>(W + 4 * VA, sb + STG_V2, warp, lane);
    fence_async();
    mbar_expect_if(warp + lane == 0, bar + 8 * B_W1, 26 * 2048);
    bar_sync(1, 384);
#pragma unroll
    for (int i = 0; i < 5; i++) {
      const int t = i * 128 + warp * 32 + lane;
      sts128(sb + OFF_TILE + (t / 160) * (TILE_GRP - TILE_SBO) + t * 16, m0[i].x, m0[i].y, m0[i].z, m0[i].w);
    }
#pragma unroll
    for (int i = 4 * VST; i < 4 * (40 - SSV); i++) W[i] = movm(W[i]);
    fence_async();
    mbar_arrive_if(lane == 0, bar + 8 * (B_F1 + warp));
    mbar_expect_if(lane == 0, bar + 8 * (B_F2 + warp), 10240);
    mbar_arrive_if(warp == 3 && lane < 2, bar + 8 * B_PLFREE);
    cluster_sync_all();
    uint32_t vl[8];
    {
      const int step = warp;
      DESC(0);
      float v[16];
      mbar_waitw4(bar + 8 * B_F2, 0);
      wg_fence(); proj<32, SSV, 1, 0, 40>(v, W, D); wg_commit();
      wg_wait<0>();
      mbar_arrive_remote_if(lane < 4, rb0 + ((nA - 4 + lane) << 24) + OFF_BAR + 8 * B_R2);
#pragma unroll
      for (int j = 0; j < 8; j++) vl[j] = pack2v(v[2 * j], v[2 * j + 1]);
      if (warp == 0 && (unsigned)ig < 3) issue_tok(1, B_F2, B_R2, 0);
    }
#pragma unroll 1
    for (int step = 0; step < NSTEP; step++) {
      const uint32_t par = step & 1;
      asm volatile("" : "+r"(lane));
      const bool dual = is_dual(step), has_next = step + 1 < NSTEP;
      mbar_expect_if(lane == 0 && has_next, bar + 8 * (B_F2 + warp), 10240);
      if (warp == 0 && ig >= IG_V && dual && sync_b) wait_cnt(&g_xready[sched_l(step + 1)][0], 32);
      bar_sync(N_VGO, 384);
      CFENCE();
#define F1_BYTES (is_dual(step + 1) ? 15360 : 2560)
#define ARM() do { \
        mbar_expect_if(lane == 0 && has_next, bar + 8 * (B_F1 + warp), F1_BYTES); \
        mbar_expect_if(lane == 0 && has_next && warp * nA + (int)rank < 40, bar + 8 * (B_RS + warp), (warp * nA + (int)rank >= 36 ? nA : nh) * (dual ? 512 : 256)); } while (0)
#define O_ADDR() uint32_t oa = sb + OFF_O + (lane >> 4) * PL_SZ + warp * 256 + (lane & 15) * 16, xo = (lane >> 4) * 1024 + warp * 256 + (lane & 15) * 16; \
        asm volatile("" : "+r"(oa), "+r"(xo))
#define O_READY(act) do { if (has_next) { const uint4 ov = lds128(oa); \
        if (act) { st_async_v4(nxt + OFF_XL + xo, ov.x, ov.y, ov.z, ov.w, nxt + OFF_BAR + 8 * B_OPEER); \
                   st_async_v4(prv + OFF_XF + xo, ov.x, ov.y, ov.z, ov.w, prv + OFF_BAR + 8 * B_OPEER); } \
        fence_async(); bar_arrive(N_O, 384); } \
        if (warp == 0) TS(15); } while (0)
#define TOK_L3(g0) if (warp == 0 && ig >= (g0) && has_next) { mbar_waitu(bar + 8 * B_R1, ig == 3 ? par : (step - LAG) & 1); asm volatile("fence.proxy.async.global;" ::: "memory"); \
        bulk_g2s_mc_e(sb + OFF_TILE + ig * TILE_GRP + TILE_SBO, &g_xn[0][0] + uni(sched_l(step + 1) * (32 * DM)) + ig * 5120, 10240, bar + 8 * (B_F2 + ig), mcmask); }
#define OX_SA (sb + OFF_PL + (lane & 7) * 128 + (((warp * 2 + ((lane >> 3) & 1)) ^ (lane & 7)) << 4))
      if (dual) {
        uint32_t vf[8], vm[4], vn[8];
        {
          DESC(0);
          float v[24];
          ARM();
          wg_fence(); proj<48, SSV, 0, 30, 40, 30>(v, W, D); wg_commit();
          proj<48, SSV, 0, 0, VD1 - 10, 30>(v, W, D);
          bar_sync(N_SISS, 384);
          proj<48, SSV, 0, VD1 - 10, VD1 - 7, 30>(v, W, D); wg_commit();
          wg_wait<1>(); bar_arrive(N_G3, 160);
          wg_fence(); proj<48, SSV, 0, VD1 - 7, 10, 30>(v, W, D); wg_commit();
          proj<48, SSV, 0, 10, 13, 30>(v, W, D); wg_commit();
          wg_wait<1>(); REL(B_R1, 0);
          wg_fence(); proj<48, SSV, 0, 13, 20, 30>(v, W, D); wg_commit();
          proj<48, SSV, 0, 20, 23, 30>(v, W, D); wg_commit();
          wg_wait<1>(); REL(B_R1, 1);
          wg_fence(); proj<48, SSV, 0, 23, 30, 30>(v, W, D); wg_commit();
          wg_wait<0>(); REL(B_R1, 2);
          bar_arrive(N_VDONE, 160);
          if (warp == 0) TS(14);
#pragma unroll
          for (int j = 4; j < 8; j++) vf[j] = pack2v(v[4 + 2 * j], v[5 + 2 * j]);
          keep4(vf + 4, lane);
          vm[0] = pack2v(v[0], v[1]); vm[1] = pack2v(v[2], v[3]); vm[2] = pack2v(v[20], v[21]); vm[3] = pack2v(v[22], v[23]);
          keep4(vm, lane);
#pragma unroll
          for (int j = 0; j < 4; j++) vf[j] = pack2v(v[4 + 2 * j], v[5 + 2 * j]);
          keep4(vf, lane);
        }
        {
          DESC(1);
          float o[8];
          O_ADDR();
          bar_sync(N_PM, 224);
          wg_fence();
          MM<8>::rs<dlo(OFF_PL + 3584, 128), 0>(o, vl, D.p);
          MM<8>::rs<dlo(OFF_PL + PL_SZ + 3584, 128), 0>(o + 4, vf, D.p);
          MM<8>::rs<dlo(OFF_PL + 3584 + 256, 128), 1>(o, vl + 4, D.p);
          MM<8>::rs<dlo(OFF_PL + PL_SZ + 3584 + 256, 128), 1>(o + 4, vf + 4, D.p);
          MM<8>::rs<dlo(OFF_PL + 3584 + 512, 128), 1>(o, vm, D.p);
          MM<8>::rs<dlo(OFF_PL + PL_SZ + 3584 + 512, 128), 1>(o + 4, vm, D.p);
          wg_commit();
          fence_sched(step);
          const uint4 il = lds128(sb + OFF_INV + (lane & 3) * 16), jf = lds128(sb + OFF_INV + 64 + (lane & 3) * 16);
          const float i0 = rcpf(__uint_as_float(il.x) + __uint_as_float(il.y)), i1 = rcpf(__uint_as_float(il.z) + __uint_as_float(il.w));
          const float j0 = rcpf(__uint_as_float(jf.x) + __uint_as_float(jf.y)), j1 = rcpf(__uint_as_float(jf.z) + __uint_as_float(jf.w));
          { const uint32_t k4[4] = {__float_as_uint(i0), __float_as_uint(i1), __float_as_uint(j0), __float_as_uint(j1)}; keep4(k4, lane | (oa ^ xo)); }
          wg_wait<0>();
          stsm4t(oa, pack2(o[0] * i0, o[1] * i1), pack2(o[2] * i0, o[3] * i1), pack2(o[4] * j0, o[5] * j1), pack2(o[6] * j0, o[7] * j1));
          O_READY(true);
          TOK_L3(IG_V);
        }
        {
          DESC(2);
          float v[16];
          bar_sync(N_TURN, 256);
          mbar_waitu(bar + 8 * B_F2, par ^ 1);
          wg_fence(); proj<32, SSV, 1, 0, 10>(v, W, D); wg_commit();
          mbar_waitu(bar + 8 * (B_F2 + 1), par ^ 1);
          wg_fence(); proj<32, SSV, 1, 10, 14>(v, W, D); wg_commit();
          wg_wait<1>(); REL(B_R2, 0);
          wg_fence(); proj<32, SSV, 1, 14, 20>(v, W, D); wg_commit();
          mbar_waitu(bar + 8 * (B_F2 + 2), par ^ 1);
          wg_fence(); proj<32, SSV, 1, 20, 24>(v, W, D); wg_commit();
          wg_wait<1>(); REL(B_R2, 1);
          wg_fence(); proj<32, SSV, 1, 24, 30>(v, W, D); wg_commit();
          mbar_waitu(bar + 8 * (B_F2 + 3), par ^ 1);
          wg_fence(); proj<32, SSV, 1, 30, 34>(v, W, D); wg_commit();
          wg_wait<1>(); REL(B_R2, 2);
          wg_fence(); proj<32, SSV, 1, 34, 40>(v, W, D); wg_commit();
          wg_wait<0>(); REL(B_R2, 3);
#pragma unroll
          for (int j = 0; j < 8; j++) vn[j] = pack2v(v[2 * j], v[2 * j + 1]);
          keep4(vn, lane); keep4(vn + 4, lane);
          if (warp == 0) TS(18);
        }
        DESC(3);
        uint32_t ow[16];
        bar_sync(N_P, 256);
        fence_async();
#define PV16(i, off, va) { float o[8]; wg_fence(); \
          MM<16>::rs<dlo(OFF_PL + (off), 128), 0>(o, va, D.p); \
          MM<16>::rs<dlo(OFF_PL + (off) + 256, 128), 1>(o, va + 4, D.p); \
          MM<16>::rs<dlo(OFF_PL + (off) + 512, 128), 1>(o, vm, D.p); \
          wg_commit(); wg_wait<0>(); \
          _Pragma("unroll") for (int j = 0; j < 4; j++) ow[4 * (i) + j] = pack2v(o[2 * j], o[2 * j + 1]); \
          keep4(ow + 4 * (i), lane); }
        PV16(0, 0, vl) PV16(1, 1792, vl) PV16(2, PL_SZ, vf) PV16(3, PL_SZ + 1792, vf)
        const uint32_t s1 = OX_SA + (lane < 16 ? 3072 : 0), s2 = OX_SA + (lane < 16 ? 2048 : 1024);
        bar_sync(N_V, 128);
        stsm4t(s1, ow[0], ow[1], ow[2], ow[3]);
        stsm4t(s2, ow[4], ow[5], ow[6], ow[7]);
        stsm4t(s1 + PL_SZ, ow[8], ow[9], ow[10], ow[11]);
        stsm4t(s2 + PL_SZ, ow[12], ow[13], ow[14], ow[15]);
#pragma unroll
        for (int j = 0; j < 8; j++) vl[j] = vn[j];
      } else {
        uint32_t vm[4], vn[8];
        {
          DESC(4);
          float v[4];
          wg_fence(); proj<8, SSV, 0, 30, 40, 30>(v, W, D); wg_commit();
          proj<8, SSV, 0, 0, VS1, 30>(v, W, D); wg_commit();
          ARM();
          bar_sync(N_SISS, 384);
          wg_wait<1>(); bar_arrive(N_G3, 160);
          wg_fence(); proj<8, SSV, 0, VS1, 30, 30>(v, W, D); wg_commit();
          if (has_next) { mbar_waitu2(bar + 8 * B_F2, bar + 8 * (B_F2 + 1), par ^ 1); mbar_waitu(bar + 8 * (B_F2 + 2), par ^ 1); }
          wg_wait<0>();
          bar_arrive(N_VDONE, 160);
          vm[0] = pack2v(v[0], v[1]); vm[1] = pack2v(v[2], v[3]); vm[2] = pack2v(v[1], v[0]); vm[3] = pack2v(v[3], v[2]);
        }
        DESC(5);
        float v[16];
        {
          wg_fence(); proj<32, SSV, 1, 0, VS2>(v, W, D); wg_commit();
          {
            float o[4];
            O_ADDR();
            bar_sync(N_PM, 192);
            if (warp == 0) TS(14);
            wg_fence();
            MM<8>::rs<dlo(OFF_PL + 3584, 128), 0>(o, vl, D.p);
            MM<8>::rs<dlo(OFF_PL + 3584 + 256, 128), 1>(o, vl + 4, D.p);
            MM<8>::rs<dlo(OFF_PL + 3584 + 512, 128), 1>(o, vm, D.p);
            wg_commit();
            fence_sched(step);
            const uint4 il = lds128(sb + OFF_INV + (lane & 3) * 16);
            const float i0 = rcpf(__uint_as_float(il.x) + __uint_as_float(il.y)), i1 = rcpf(__uint_as_float(il.z) + __uint_as_float(il.w));
            { const uint32_t k4[4] = {__float_as_uint(i0), __float_as_uint(i1), oa, xo}; keep4(k4, lane); }
            wg_wait<0>();
            stsm2t(oa, pack2(o[0] * i0, o[1] * i1), pack2(o[2] * i0, o[3] * i1));
            O_READY(lane < 16);
            TOK_L3(3);
          }
          if (has_next) {
            mbar_arrive_remote_if(lane < VS2 / 10, rb0 + ((nA - 4 + lane) << 24) + OFF_BAR + 8 * B_R2);
            bar_sync(N_TURN, 256);
          }
          if (VS2 < 30) { wg_fence(); proj<32, SSV, 1, VS2, 30>(v, W, D); wg_commit(); }
          if (has_next) mbar_waitu(bar + 8 * (B_F2 + 3), par ^ 1);
          if (VS2 < 30) { wg_wait<0>(); if (has_next) REL(B_R2, 2); }
          wg_fence(); proj<32, SSV, 1, 30, 40>(v, W, D); wg_commit();
          wg_wait<0>();
          if (has_next) REL(B_R2, 3);
#pragma unroll
          for (int j = 0; j < 8; j++) vn[j] = pack2v(v[2 * j], v[2 * j + 1]);
          keep4(vn, lane); keep4(vn + 4, lane);
          if (warp == 0) TS(18);
        }
        float o[16];
        bar_sync(N_P, 256);
        fence_async();
        wg_fence();
        MM<32>::rs<dlo(OFF_PL, 128), 0>(o, vl, D.p);
        MM<32>::rs<dlo(OFF_PL + 256, 128), 1>(o, vl + 4, D.p);
        MM<32>::rs<dlo(OFF_PL + 512, 128), 1>(o, vm, D.p);
        wg_commit();
        const uint32_t s1 = OX_SA + (lane < 16 ? 3072 : 0), s2 = OX_SA + (lane < 16 ? 2048 : 1024);
        wg_wait<0>();
        bar_sync(N_V, 128);
        stsm4t(s1, pack2(o[0], o[1]), pack2(o[2], o[3]), pack2(o[4], o[5]), pack2(o[6], o[7]));
        stsm4t(s2, pack2(o[8], o[9]), pack2(o[10], o[11]), pack2(o[12], o[13]), pack2(o[14], o[15]));
#pragma unroll
        for (int j = 0; j < 8; j++) vl[j] = vn[j];
      }
      bar_arrive(N_OX, 160);
      if (warp == 0) TS(16);
    }
    cluster_sync_all();
  } else {
    asm volatile("setmaxnreg.dec.sync.aligned.u32 32;");
    if (wg > 3) return;
    LANE_INIT();
    struct RsJob { uint32_t* gp; uint32_t la, mb; int n; };
    auto rs_prep = [&](int step, int s, int c) {
      RsJob j;
      const int u = s * nA + rank;
      j.gp = &g_part[0][0][0][0] + (uint32_t)((((step & 1) * 2 + c) * NCL + cl) * 2560 + u * 64 + (lane >> 2) * 8 + (lane & 3));
      j.la = sb + OFF_TILE + c * LAND_F + LAND(s) + lane * 8;
      j.mb = bar + 8 * (B_RS + s);
      j.n = u >= 40 ? 0 : u >= 36 ? 3 : 1;
      asm volatile("" : "+l"(j.gp), "+r"(j.la));
      return j;
    };
    auto rs_sum = [&](RsJob j, int step) {
      if (j.n) {
        auto five = [&](uint32_t la) {
          uint2 p[5];
#pragma unroll
          for (int i = 0; i < 4; i++) p[i] = lds64(la + i * 256);
          asm volatile("{\n.reg .pred q;\nsetp.eq.s32 q, %3, 5;\nmov.u32 %0, 0;\nmov.u32 %1, 0;\n@q ld.shared.v2.b32 {%0,%1}, [%2];\n}"
                       : "=r"(p[4].x), "=r"(p[4].y) : "r"(la + 1024), "r"(nh) : "memory");
          return make_uint2(hadd2bf(hadd2bf(p[0].x, p[1].x), hadd2bf(hadd2bf(p[2].x, p[3].x), p[4].x)),
                            hadd2bf(hadd2bf(p[0].y, p[1].y), hadd2bf(hadd2bf(p[2].y, p[3].y), p[4].y)));
        };
        const uint32_t tag = ((step >> 1) & 1) ^ 1;
        mbar_waitw(j.mb, step & 1);
        uint2 t = five(j.la);
        if (j.n > 1) {
          const uint2 a = five(j.la + (nh == 5 ? 1280 : TILE_GRP - 1280)), b = five(j.la + TILE_GRP);
          t.x = hadd2bf(t.x, hadd2bf(a.x, b.x)); t.y = hadd2bf(t.y, hadd2bf(a.y, b.y));
        }
        const uint32_t t0 = (movm(t.x) & ~1u) | tag, t1 = (movm(t.y) & ~1u) | tag;
        asm volatile("st.relaxed.gpu.global.b32 [%0], %1;" :: "l"(j.gp), "r"(lane & 16 ? t1 : t0) : "memory");
        asm volatile("st.relaxed.gpu.global.b32 [%0], %1;" :: "l"(j.gp + 4), "r"(lane & 16 ? t0 : t1) : "memory");
      }
    };
    if (warp * nA + (int)rank < 40) {
#pragma unroll
      for (int e = LAG; e < LAG + 2; e++)
        if ((e >> 1) & 1) *reinterpret_cast<uint2*>(&g_part[(e & 1) * 2 + 1][cl][warp * nA + rank][lane * 2]) = make_uint2(1u, 1u);
      __threadfence();
    }
    cluster_sync_all();
    if (warp == 2 && ig >= 0) issue_tok(0, B_F2);
    if (warp != 2) {
#pragma unroll 1
      for (int i = min(warp, 2); i < 20; i += 3) {
        int c0, c1; wo_coord(i, t3, head, c0, c1);
        if (i >= 2 && i < 15) tma2d_e(sb + OFF_WO + (i - 2) * 4096, &M.wo32, c0, c1, bar + 8 * B_W1);
        else if (lane == 0) tma2d_prefetch(&M.wo32, c0, c1);
        __syncwarp();
      }
    }
#pragma unroll 1
    for (int step = 0; step < NSTEP; step++) {
      const uint32_t par = step & 1;
      asm volatile("" : "+r"(lane));
      const bool dual = is_dual(step), has_next = step + 1 < NSTEP;
      {
        bar_sync(N_PX, dual ? 256 : 192);
        if (dual || warp >= 2) tok_softmax(sb, dual ? warp : warp - 2, lane);
        bar_arrive(N_P, 256);
        asm volatile("" : "+r"(lane));
        if (has_next) {
          if (step + 2 == LAG && lane < 20) asm volatile("prefetch.global.L2 [%0];" :: "l"(mem0 + (warp * 20 + lane) * 64));
          const int nw = ig >= 0 ? 3 : 4, j0 = warp < nw ? warp : 8;
          const int sh = dual ? 1 : 0;
          rs_sum(rs_prep(step, j0 >> sh, j0 & sh), step);
          if (warp == 0) TS(17);
          if (dual) rs_sum(rs_prep(step, (j0 + nw) >> 1, (j0 + nw) & 1), step);
          if (warp == 0) { bar_sync(N_C, 288); }
          mbar_arrive_remote_if(lane < nA, rb0 + (lane << 24) + OFF_BAR + 8 * B_LANDFREE);
          const uint32_t gap = dual ? POLL_GAPD : POLL_GAP;
          if (gap) { const uint32_t t0 = clock32(); while (clock32() - t0 < gap) {} }
#pragma unroll 1
          for (int j = j0; j < (dual ? 8 : 4); j += nw) {
            const int u = (j >> sh) * nA + rank, c = j & sh;
            if (u < UMAX && (c || step + 1 != NSEG)) {
              const uint32_t* gq = &g_part[0][0][0][0] + (uint32_t)((par * 2 + c) * NCL * 2560 + u * 64 + lane * 2);
              uint2 pa[NCL];
              POLL(pa, gq);
              deliver(pa, gq, u, c, step + 1 < NSEG ? c : 0, dual ? DS_DUAL : DS_SINGLE, step, j == 0, lane);
            }
            if (warp == 0 && j == 0) TS(13);
          }
          if (warp >= nw && (is_dual(step + 1) || (ig < 3 && step + 2 < NSTEP))) {
            issue_tok(is_dual(step + 1) ? sched_f(step + 1) : sched_l(step + 2), is_dual(step + 1) ? B_F1 : B_F2, B_R2, par ^ 1);
          }
          if (step + 1 == LAG && UMAX) {
            uint4 v[5];
#pragma unroll
            for (int i = 0; i < 5; i++) { const int t = warp * 160 + i * 32 + lane; v[i] = *reinterpret_cast<const uint4*>(mem0 + ((t >> 1) & 7) * DM + (t >> 4) * 16 + ((t ^ (t >> 3)) & 1) * 8); }
            mbar_waitu(bar + 8 * B_LANDFREE, par);
#pragma unroll
            for (int i = 0; i < 5; i++)
              st_async_v4(sb + OFF_TILE + LAND_F + warp * TILE_GRP + (i * 32 + lane) * 16, v[i].x, v[i].y, v[i].z, v[i].w, bar + 8 * (B_F1 + warp));
          }
        }
      }
      if (warp == (ig >= 0 && !is_dual(step + 1) ? 2 : 3)) {
        unsigned char* o0 = g_o + uni(step % RO * (96 * 8192) + (head * 3 + t3) * (dual ? 8192 : 4096));
        bar_sync(N_OX, 160);
        fence_async();
        bulk_s2g_es(o0, sb + OFF_PL, 4096);
        if (dual) bulk_s2g_es(o0 + 4096, sb + OFF_PL + PL_SZ, 4096);
        asm volatile("cp.async.bulk.commit_group;" ::: "memory");
        asm volatile("cp.async.bulk.wait_group.read 0;" ::: "memory");
        __syncwarp();
        mbar_arrive_remote_if(lane < 2, (lane ? nxt : prv) + OFF_BAR + 8 * B_PLFREE);
        asm volatile("cp.async.bulk.wait_group 0;" ::: "memory");
        asm volatile("fence.proxy.async.global;" ::: "memory");
        __syncwarp();
        if (lane == 0) red_release(&g_f[F_O + (head * 3 + t3) / 5][step], 1u);
        __syncwarp();
      }
    }
    cluster_sync_all();
  }
}

__device__ __forceinline__ float gelu2(float x) {
  const float u = x * fmaf(x * x, 0.7978845608028654f * 0.044715f, 0.7978845608028654f);
  float t; asm("tanh.approx.f32 %0, %1;" : "=f"(t) : "f"(u));
  return fmaf(x, t, x); }

struct BParams {
  CUtensorMap wmap[5];
  CUtensorMap wo16;
  const __nv_bfloat16* x;
  __nv_bfloat16* out;
  uint64_t desc;
};
#define BO_O 0
#define BO_RES (6 * 8192)
#define OP_RES 63488
#define BO_STG (BO_RES + 2 * OP_RES)
#define BO_RING_OP (BO_STG + 16384)
#define OP_SLOT 12288
#define NS_OP 3
#define BO_H 81920
#define BO_W1 (BO_H + 16384)
#define BO_RING_MLP (BO_W1 + 81920)
#define BO_BAR 229376
#define BO_BOX (BO_BAR + 248)
#define BO_CARRY (BO_BAR + 512)
#define BO_STAT (BO_CARRY + 2048)
#define B_SMEM (BO_STAT + 256)
static_assert(B_SMEM <= 232448 && BO_RING_OP + NS_OP * OP_SLOT == BO_BAR && BO_RING_MLP + 3 * 16384 == BO_BAR && 2 * 83968 <= BO_RING_MLP, "smem");
enum { BB_W = 0, BB_FULL = 2, BB_TMP = BB_FULL + 3, BB_OFULL = BB_FULL + 5, BB_SFREE = BB_OFULL,
       BB_STAT = BB_SFREE + 6, BB_ZFREE, BB_DONE = BB_ZFREE + 3,
       BB_EMPTY, BB_START = BB_EMPTY, BB_USED = BB_EMPTY + 2, BB_NUM = BB_USED + 3 };
enum { NB_PP = 1, NB_H = 3, NB_END = 4, NB_END2 = 5, NB_STAGED = 6, NB_FREE = 8, NB_EARLY = 10, NB_LAST = 11 };

#define DESC_LO(off) (((SMEM0 + (off)) >> 4) | (1u << 16))

__device__ __forceinline__ uint32_t ld_relaxed(const uint32_t* p) { uint32_t v; asm volatile("ld.relaxed.gpu.global.b32 %0, [%1];" : "=r"(v) : "l"(p) : "memory"); return v; }
__device__ __forceinline__ int fmask(int r) { return (r < NSEG) | ((r >= LAG && r < NSTEP) << 1); }
__device__ __forceinline__ int bmask(int r) { return (r <= NSEG) | ((r >= LAG) << 1); }
__device__ __forceinline__ uint32_t rtarget(int mask) { return mask == 3 ? 64 : 32; }
__device__ __forceinline__ void warp_signal(uint32_t* p, int lane) {
  __syncwarp();
  asm volatile("{\n.reg .pred q;\nsetp.eq.u32 q, %1, 0;\n@q red.release.gpu.global.add.u32 [%0], 1;\n}" :: "l"(p), "r"(lane) : "memory");
}
__device__ __forceinline__ uint32_t pack2h(float lo, float hi) { uint32_t r; asm("cvt.rn.f16x2.f32 %0, %1, %2;" : "=r"(r) : "f"(hi), "f"(lo)); return r; }
template <bool H> __device__ __forceinline__ uint32_t pk(float lo, float hi) { return H ? pack2h(lo, hi) : pack2(lo, hi); }
template <int N, bool H> __device__ __forceinline__ void stage_out(const float* d, uint32_t dst, int warp, int lane) {
  const uint32_t sa = dst + ((lane >> 4) * 8 + (lane & 7)) * 128 + (((2 * warp + ((lane >> 3) & 1)) ^ (lane & 7)) << 4);
#pragma unroll
  for (int m = 0; m < N / 16; m++)
    stsm4t(sa + m * 2048, pk<H>(d[8 * m], d[8 * m + 1]), pk<H>(d[8 * m + 2], d[8 * m + 3]), pk<H>(d[8 * m + 4], d[8 * m + 5]), pk<H>(d[8 * m + 6], d[8 * m + 7]));
}
template <int N> __device__ __forceinline__ void acc_live(float* d) {
#pragma unroll
  for (int i = 0; i < N / 2; i++) asm volatile("" : "+f"(d[i]) :: "memory");
}
struct Ring {
  uint32_t sl, ph;
  template <int NS> __device__ __forceinline__ void step() { if (++sl == NS) { sl = 0; ph ^= 1; } }
};

#define LOCKSTEP 0
#define KOFF(x) (DESC_LO(BO_O) + ((x) >> 2) * (N * 8) + ((x) & 3) * 2)
template <int N, int P>
__device__ __forceinline__ void op_pass(const uint32_t* W, uint32_t bar, Dsc alo, Dsc blo, Dsc xlo, bool x2, Ring& rg, int wg, int warp, int lane, int r) {
  float acc[N / 2];
  blo.e = xlo.e = fresh<P + N / 64 * 5>(r);
  const Dsc tlo = blo + uni(rg.sl) * (OP_SLOT / 16);
  if (P == 0) mbar_waitu(bar + 8 * BB_OFULL, r & 1);
  CTS(5 * P);
  if (!LOCKSTEP || P > 1 || P == wg) bar_sync(NB_PP + wg, 256);
  wg_fence();
#define OP_R(x) MM<N>::template rs<KOFF(4 * (x >> 1) + (x & 1)), (x != 0)>(acc, W + 32 * P + 4 * x, blo);
#define OP_S(x) MM<N>::template ss<DESC_LO(BO_RES) + (6 * P + x) * 128, KOFF(4 * (x >> 1) + 2 + (x & 1)), 1>(acc, alo, blo);
#define OP_T(x) MM<N>::template ss<DESC_LO(BO_RING_OP) + x * 128, KOFF(14 + x), 1>(acc, tlo, blo);
  OP_R(0) OP_S(0) OP_R(1) OP_S(1) OP_R(2) OP_S(2) OP_R(3) OP_S(3)
  if (P == 0) mbar_waitu(bar + 8 * (BB_OFULL + 1), r & 1);
  if (P == 4) wg_commit();
  OP_R(4) OP_S(4) OP_R(5) OP_S(5)
  if (P == 1 && x2) MM<N>::template ss<DESC_LO(BO_RES) + 30 * 128, KOFF(20), 1>(acc, alo, xlo);
  if (P == 4) { wg_commit(); wg_wait<1>(); bar_arrive(NB_EARLY, 288); CTS(21); wg_fence(); }
  mbar_waitu(bar + 8 * (BB_FULL + rg.sl), rg.ph);
  OP_R(6) OP_T(0) OP_R(7) OP_T(1)
  if (P == 0) mbar_waitu(bar + 8 * (BB_OFULL + 2), r & 1);
  OP_T(2) OP_T(3)
  if (P == 0) MM<N>::template rs<KOFF(20), 1>(acc, W + 160, xlo);
  OP_T(4) OP_T(5)
  wg_commit();
  if (!LOCKSTEP || P) bar_arrive(NB_PP + 1 - wg, 256);
  CTS(5 * P + 2);
  bar_sync(NB_FREE + wg, 160);
  wg_wait<0>();
  acc_live<N>(acc);
  if (P == 4) bar_arrive(NB_LAST, 288);
  mbar_arrive_if(lane == 0, bar + 8 * (BB_USED + rg.sl));
  CTS(5 * P + 3);
  stage_out<N, false>(acc, SMEM0 + BO_STG + wg * 8192, warp, lane);
  bar_arrive(NB_STAGED + wg, 160);
  CTS(5 * P + 4);
  rg.step<NS_OP>(); rg.step<NS_OP>();
}
template <int N>
__device__ __forceinline__ void op_round(const uint32_t* W, uint32_t bar, Dsc alo, Dsc blo, Dsc xlo, bool x2, Ring& rg, int wg, int warp, int lane, int r) {
  op_pass<N, 0>(W, bar, alo, blo, xlo, x2, rg, wg, warp, lane, r);
  op_pass<N, 1>(W, bar, alo, blo, xlo, x2, rg, wg, warp, lane, r);
  op_pass<N, 2>(W, bar, alo, blo, xlo, x2, rg, wg, warp, lane, r);
  op_pass<N, 3>(W, bar, alo, blo, xlo, x2, rg, wg, warp, lane, r);
  op_pass<N, 4>(W, bar, alo, blo, xlo, x2, rg, wg, warp, lane, r);
}
__device__ __forceinline__ void carry_in(uint32_t sb, int wg, int warp, int lane) {
  const int row = (lane >> 1) & 3;
  if (lane < 16) {
    const uint4 v = lds128(sb + BO_CARRY + (wg * 4 + warp) * 256 + lane * 16);
    sts128(sb + BO_H + wg * 8192 + (lane >> 3) * 4096 + row * 128 + (((2 * warp + (lane & 1)) ^ row) << 4), v.x, v.y, v.z, v.w);
  }
  __syncwarp();
}
#define STAGGER 0
template <int N, int Z>
__device__ __forceinline__ void p1_pair(float* acc, const uint32_t* W, uint32_t bar, Dsc alo, Dsc blo, int lane, int r) {
  blo.e = fresh<10 + Z / 3 + N / 64 * 2>(r);
  mbar_waitu(bar + 8 * (BB_FULL + Z), r & 1);
  CTS(40 + Z);
  wg_fence();
#define P1_B(k) \
  MM<N, true>::template rs<DESC_LO(BO_RING_MLP) + (2 * Z % 3) * 1024 + k * 512, (2 * Z + k != 0)>(acc, W + 16 * Z + 8 * k, blo); \
  MM<N, true>::template ss<DESC_LO(BO_W1) + (2 * Z + k) * 512, DESC_LO(BO_RING_MLP) + (2 * Z % 3) * 1024 + k * 512 + 4, 1>(acc, alo, blo); \
  MM<N, true>::template rs<DESC_LO(BO_RING_MLP) + (2 * Z % 3) * 1024 + k * 512 + 2, 1>(acc, W + 16 * Z + 8 * k + 4, blo); \
  MM<N, true>::template ss<DESC_LO(BO_W1) + (2 * Z + k) * 512 + 128, DESC_LO(BO_RING_MLP) + (2 * Z % 3) * 1024 + k * 512 + 6, 1>(acc, alo, blo);
  P1_B(0)
  if (Z == 1 || Z == 2) { wg_commit(); wg_wait<1>(); mbar_arrive_if(lane == 0, bar + 8 * (BB_EMPTY + Z - 1)); wg_fence(); }
  P1_B(1)
  wg_commit();
}
template <int N>
__device__ __forceinline__ void phase1(const uint32_t* W, uint32_t sb, Dsc alo, Dsc blo, int half, int wg, int warp, int lane, int off, int r) {
  float acc[N / 2];
  const uint32_t bar = sb + BO_BAR;
  CTS(30);
  p1_pair<N, 0>(acc, W, bar, alo, blo, lane, r);
  p1_pair<N, 1>(acc, W, bar, alo, blo, lane, r);
  p1_pair<N, 2>(acc, W, bar, alo, blo, lane, r);
  mbar_waitu(bar + 8 * (BB_SFREE + 4 + wg), (r + 1) & 1);
  carry_in(sb, wg, warp, lane);
  if (STAGGER && wg) bar_sync(NB_PP + 1, 256);
  p1_pair<N, 3>(acc, W, bar, alo, blo, lane, r);
  p1_pair<N, 4>(acc, W, bar, alo, blo, lane, r);
  if (STAGGER && !wg) bar_arrive(NB_PP + 1, 256);
  const int c = (lane >> 3) & 1, i0 = (lane >> 4) * 8 + (lane & 7) + off;
  uint32_t a0 = sb + BO_H + wg * 8192 + half * 4096 + i0 * 128 + (((2 * warp + c) ^ (i0 & 7)) << 4);
  uint32_t a1 = i0 >= 16 ? sb + BO_CARRY + (wg * 4 + warp) * 256 + half * 128 + (i0 - 16) * 32 + c * 16 : a0 + 2048, a3 = a1 + (i0 >= 16 ? 128 : 4096);
  asm volatile("" : "+r"(a0), "+r"(a1), "+r"(a3));
  mbar_waitu(bar + 8 * BB_STAT, r & 1);
  const uint32_t sa = sb + BO_STAT + half * 128 + (lane & 3) * 32;
  uint4 t[2] = {lds128(sa), lds128(sa + 16)};
  wg_wait<0>();
  acc_live<N>(acc);
  CTS(32);
#pragma unroll
  for (int m = 0; m < N / 16; m++) {
    const float s0 = __uint_as_float(t[m & 1].x), s1 = __uint_as_float(t[m & 1].y), s2 = __uint_as_float(t[m & 1].z), s3 = __uint_as_float(t[m & 1].w);
    float* d = acc + 8 * m;
    d[0] *= s0; d[1] *= s1; d[2] *= s0; d[3] *= s1; d[4] *= s2; d[5] *= s3; d[6] *= s2; d[7] *= s3;
    if (m + 2 < N / 16) t[m & 1] = lds128(sa + 128 + m * 16);
#pragma unroll
    for (int j = 0; j < 8; j++) d[j] = gelu2(d[j]);
  }
#pragma unroll
  for (int m = 0; m < N / 16; m++)
    stsm4t(m == 1 ? a1 : m == 3 ? a3 : a0 + m * 2048, pack2(acc[8 * m], acc[8 * m + 1]), pack2(acc[8 * m + 2], acc[8 * m + 3]), pack2(acc[8 * m + 4], acc[8 * m + 5]), pack2(acc[8 * m + 6], acc[8 * m + 7]));
}
template <int N, int P>
__device__ __forceinline__ void p2_mma(float* acc, const uint32_t* W, Dsc alo, Dsc blo, int r) {
  blo.e = fresh<P + N / 64 * 5>(r);
  MM<N>::template rs<DESC_LO(BO_H), 0>(acc, W + 80 + 16 * P, blo);     MM<N>::template ss<DESC_LO(0) + P * 1024, DESC_LO(BO_H) + 512, 1>(acc, alo, blo);
  MM<N>::template rs<DESC_LO(BO_H) + 2, 1>(acc, W + 84 + 16 * P, blo); MM<N>::template ss<DESC_LO(0) + P * 1024 + 128, DESC_LO(BO_H) + 514, 1>(acc, alo, blo);
  MM<N>::template rs<DESC_LO(BO_H) + 4, 1>(acc, W + 88 + 16 * P, blo); MM<N>::template ss<DESC_LO(0) + P * 1024 + 512, DESC_LO(BO_H) + 516, 1>(acc, alo, blo);
  MM<N>::template rs<DESC_LO(BO_H) + 6, 1>(acc, W + 92 + 16 * P, blo); MM<N>::template ss<DESC_LO(0) + P * 1024 + 640, DESC_LO(BO_H) + 518, 1>(acc, alo, blo);
}
template <int N, int P, int T>
__device__ __forceinline__ void p2_pass(const uint32_t* W, uint32_t bar, Dsc alo, Dsc blo, int wg, int warp, int lane, int r) {
  float acc[N / 2], ac2[N / 2];
  CTS(5 * P);
  if (P || wg) bar_sync(NB_PP + wg, 256);
  wg_fence();
  p2_mma<N, P>(acc, W, alo, blo, r);
  wg_commit();
  if constexpr (T == 2) { p2_mma<N, P + 1>(ac2, W, alo, blo, r); wg_commit(); }
  if (P < 4 || !wg) bar_arrive(NB_PP + 1 - wg, 256);
  CTS(5 * P + 2);
  if (T == 1 && (P == 2 || P == 3)) mbar_waitu(bar + 8 * (BB_SFREE + 2 * (P - 2) + wg), r & 1);
  wg_wait<T - 1>();
  acc_live<N>(acc);
  if (P == 4) bar_sync(NB_H, 256);
  CTS(5 * P + 3);
  constexpr int K = P / T & 1;
  stage_out<N, true>(acc, SMEM0 + (P == 4 ? BO_H : BO_RING_MLP + (2 - K) * 16384) + wg * 8192, warp, lane);
  if constexpr (T == 2) {
    wg_wait<0>();
    acc_live<N>(ac2);
    stage_out<N, true>(ac2, SMEM0 + BO_RING_MLP + (2 - K) * 16384 + wg * 8192 + 4096, warp, lane);
  }
  bar_arrive(NB_STAGED + (P == 4 ? 4 : 2 * K) + wg, 160);
  CTS(5 * P + 4);
}
template <int N>
__device__ __forceinline__ void phase2(const uint32_t* W, uint32_t bar, Dsc alo, Dsc blo, int wg, int warp, int lane, int r) {
  if constexpr (N == 64) {
    p2_pass<N, 0, 1>(W, bar, alo, blo, wg, warp, lane, r);
    p2_pass<N, 1, 1>(W, bar, alo, blo, wg, warp, lane, r);
    p2_pass<N, 2, 1>(W, bar, alo, blo, wg, warp, lane, r);
    p2_pass<N, 3, 1>(W, bar, alo, blo, wg, warp, lane, r);
  } else {
    p2_pass<N, 0, 2>(W, bar, alo, blo, wg, warp, lane, r);
    p2_pass<N, 2, 2>(W, bar, alo, blo, wg, warp, lane, r);
  }
  p2_pass<N, 4, 1>(W, bar, alo, blo, wg, warp, lane, r);
}

__device__ __forceinline__ void ldg4(uint32_t* v, const void* p) {
  asm volatile("ld.relaxed.gpu.global.v4.u32 {%0,%1,%2,%3}, [%4];" : "=r"(v[0]), "=r"(v[1]), "=r"(v[2]), "=r"(v[3]) : "l"(p) : "memory"); }
__device__ __forceinline__ void stg4(void* p, const uint32_t* v) {
  asm volatile("st.global.v4.u32 [%0], {%1,%2,%3,%4};" :: "l"(p), "r"(v[0]), "r"(v[1]), "r"(v[2]), "r"(v[3]) : "memory"); }
struct RowPtr {
  unsigned char *p, *q, *t;
  __device__ __forceinline__ void ld(uint32_t* v, int o) const {
    ldg4(v, p + o); ldg4(v + 4, q + o);
    asm volatile("ld.relaxed.gpu.global.v2.u32 {%0,%1}, [%2];" : "=r"(v[8]), "=r"(v[9]) : "l"(t + o) : "memory");
  }
  __device__ __forceinline__ void st(const uint32_t* w, int o) const {
    stg4(p + o, w); stg4(q + o, w + 4);
    asm volatile("st.global.v2.u32 [%0], {%1,%2};" :: "l"(t + o), "r"(w[8]), "r"(w[9]) : "memory");
  }
};
__device__ __forceinline__ RowPtr row_img(int r, int n, int lane) {
  unsigned char* b = &g_acc[0][r % RD][n * 128];
  unsigned char* p = b + (uint32_t)((lane >> 3) * 8192 + (((lane ^ n) & 7) << 4));
  return {p, p + 32768, b + (uint32_t)(65536 + (lane >> 4) * 8192 + ((((lane >> 1) ^ n) & 7) << 4) + (lane & 1) * 8)};
}
__device__ __forceinline__ RowPtr row_ext(const void* lin, bool xn, int layer, int tok, int lane) {
  unsigned char* b = xn ? reinterpret_cast<unsigned char*>(&g_xn[layer][0]) + (uint32_t)((tok >> 5) * 40960 + ((tok >> 3) & 3) * 2560 + (tok & 7) * 32)
                        : (unsigned char*)lin + (uint32_t)(tok * 1280);
  const uint32_t o = (lane >> 1) * 256 + ((lane ^ (tok >> 2)) & 1) * 16;
  return {b + (uint32_t)(xn ? o + (lane >= 20 ? 7680 : 0) : lane * 16),
          b + (uint32_t)(xn ? o + 4096 + 7680 + (lane >= 8 ? 7680 : 0) + (lane >= 28 ? 7680 : 0) : lane * 16 + 512),
          b + (uint32_t)(xn ? (lane >> 2) * 256 + ((lane & 3) ^ ((tok >> 1) & 2)) * 8 + 8192 + 3 * 7680 : lane * 8 + 1024)};
}
__device__ __forceinline__ float2 h2f(uint32_t w) {
  float2 f; asm("{\n.reg .f16 l, h;\nmov.b32 {l, h}, %2;\ncvt.f32.f16 %0, l;\ncvt.f32.f16 %1, h;\n}" : "=f"(f.x), "=f"(f.y) : "r"(w)); return f; }
__device__ __forceinline__ float rsq(float x) { float y; asm("rsqrt.approx.ftz.f32 %0, %1;" : "=f"(y) : "f"(x)); return y; }
__device__ __forceinline__ void red_if(uint32_t v, const void* a) {
  asm volatile("{\n.reg .pred q;\nsetp.ne.u32 q, %1, 0;\n@q red.relaxed.gpu.global.add.u32 [%0], %1;\n}" :: "l"(a), "r"(v) : "memory"); }
__device__ __forceinline__ uint32_t dep0(uint32_t w, int lane) { uint32_t z; asm volatile("shr.b32 %0, %1, %2;" : "=r"(z) : "r"(w), "r"(lane + 32)); return z; }
__device__ __forceinline__ int lane_of(uint32_t w) {
  int lane; asm volatile("{\n.reg .u32 t;\nmov.u32 t, %%laneid;\nshr.u32 %0, %1, 20;\nadd.u32 %0, %0, t;\n}" : "=r"(lane) : "r"(w)); return lane; }
#define BUF (RD * TILE_B)
__device__ __forceinline__ int await(uint32_t v, const uint32_t* p, uint32_t target, bool lazy) {
  int n = 0;
  while (!__all_sync(~0u, v >= target)) {
    if (lazy) __nanosleep(200);
    if (++n > SPIN_LIMIT) FAIL();
    v = ld_relaxed(p);
  }
  asm volatile("fence.acquire.gpu;" ::: "memory");
  return lane_of(v);
}
template <int W> __device__ __forceinline__ void sum2(float& s, float& q, int lane) {
  const bool up = lane & (W / 2);
  float e = (up ? q : s) + __shfl_xor_sync(~0u, up ? s : q, W / 2);
#pragma unroll
  for (int o = W / 4; o; o >>= 1) e += __shfl_xor_sync(~0u, e, o);
  const float f = __shfl_xor_sync(~0u, e, W / 2);
  s = up ? f : e; q = up ? e : f;
}
template <int TYPE>
__device__ __forceinline__ void rrow(int r, int row, int tok, int lane, const uint32_t* go, int role, const __nv_bfloat16* x) {
  const int half = TYPE ? 0 : row >> 5;
  float v[20];
  float2 st = make_float2(1.f, 0.f);
  {
    uint32_t a[10], c[10], u[10], sh = 16;
    if (TYPE == 2) row_img(r + RD - ((row & 31) < 2), (row & 32) + ((row - 2) & 31), lane).ld(u, 4 * BUF);
    else row_ext(x, half, 1, tok, lane).ld(u, 0);
    if (TYPE == 2 || (TYPE == 0 && half))
      asm volatile("ld.relaxed.gpu.global.v2.f32 {%0,%1}, [%2];" : "=f"(st.x), "=f"(st.y) : "l"(g_stat + tok) : "memory");
    RowPtr ap = row_img(r, row, lane);
    const uint32_t g0 = TYPE != 3 ? ld_relaxed(go) : 0;
    if (TYPE == 2) {
      ap.ld(c, 2 * BUF);
      uint32_t z = dep0(c[9], lane);
#pragma unroll
      for (int i = 0; i < 10; i++) {
        const float2 g = h2f(u[i] | z), h = h2f(c[i] | z);
        v[2 * i] = fmaf(h.x, 0.5f, g.x * st.x); v[2 * i + 1] = fmaf(h.y, 0.5f, g.y * st.x);
        if (i & 1) z = dep0(__float_as_uint(v[2 * i]) | __float_as_uint(v[2 * i + 1]), lane);
      }
    }
    if (TYPE != 3) {
      asm volatile("" : "+l"(ap.p), "+l"(ap.t));
      ap.q = ap.p + 32768;
      lane = await(g0, go, NOP * NW12 * NW34, false); BTS2(r, 8 + 2 * TYPE); RTS(0);
      ap.ld(a, TYPE ? 3 * BUF : 0);
    }
    if (TYPE == 0) {
      ap.ld(c, BUF);
      const uint32_t one = 0x3f803f80u | dep0(c[9], lane);
#pragma unroll
      for (int i = 0; i < 10; i++) asm volatile("fma.rn.bf16x2 %0, %0, %1, %2;" : "+r"(a[i]) : "r"(one), "r"(c[i]));
      sh |= dep0(a[9], lane);
    }
    const float k = TYPE == 2 ? __uint_as_float(0x3f000000u | dep0(a[9], lane)) : 0.f;
#pragma unroll
    for (int i = 0; i < 10; i++) {
      if (TYPE == 2) { const float2 h = h2f(a[i]); v[2 * i] = fmaf(h.x, k, v[2 * i]); v[2 * i + 1] = fmaf(h.y, k, v[2 * i + 1]); continue; }
      float p = __uint_as_float(u[i] << sh), q = __uint_as_float(u[i] & (0xffffu << sh));
      if (TYPE == 0) { p = fmaf(p, st.x, bf_lo(a[i])); q = fmaf(q, st.x, bf_hi(a[i])); }
      v[2 * i] = p; v[2 * i + 1] = q;
    }
  }
  RTSD(1, v[19]);
  float s = 0.f, q = 0.f;
#pragma unroll
  for (int i = 0; i < 5; i++) {
    s += (v[4 * i] + v[4 * i + 1]) + (v[4 * i + 2] + v[4 * i + 3]);
    q += fmaf(v[4 * i], v[4 * i], v[4 * i + 1] * v[4 * i + 1]) + fmaf(v[4 * i + 2], v[4 * i + 2], v[4 * i + 3] * v[4 * i + 3]);
  }
  sum2<32>(s, q, lane);
  const float mean = s * (1.f / DM), var = fmaxf(q * (1.f / DM) - mean * mean, 0.f), rs = rsq(var + 1e-5f), k = TYPE ? rs : 2.f * rs, mr = -mean * k;
  RTSD(2, rs);
  uint32_t w[10];
#pragma unroll
  for (int i = 0; i < 10; i++) w[i] = pk<TYPE == 0>(fmaf(v[2 * i], k, mr), fmaf(v[2 * i + 1], k, mr));
  if (TYPE) row_ext(nullptr, true, TYPE == 2, tok, lane).st(w, 0);
  else {
    row_img(r, row, lane).st(w, 4 * BUF);
    row_img(r + ((row & 31) >= 30), (row & 32) + ((row + 2) & 31), lane).st(w, 2 * BUF);
    if (lane == 1) g_st2[0][r % RD][row] = (__float_as_uint(0.5f * rsq(fmaf(var * rs, rs, 1e-5f))) & ~127u) | (r + 1);
  }
  if (TYPE != 3 && lane == 0) g_stat[tok] = make_float2((var + 1e-5f) * rs * (TYPE ? 1.f : 0.5f), mean + st.y);
}
__device__ __forceinline__ void r2rows(int r, int row, int lane) {
  const int n = row + (lane >> 4);
  const unsigned char* ap = &g_acc[2][r % RD][0] + (uint32_t)(n * 128 + ((lane >> 3) & 1) * 8192 + (((lane ^ n) & 7) << 4));
  uint32_t a[20];
#pragma unroll
  for (int i = 0; i < 5; i++) ldg4(a + 4 * i, ap + i * 16384);
  const uint32_t z = dep0(a[19], lane);
  float s = 0.f, q = 0.f, q2 = 0.f;
#pragma unroll
  for (int i = 0; i < 20; i++) { const float2 h = h2f(a[i] | z); s += h.x + h.y; q = fmaf(h.x, h.x, q); q2 = fmaf(h.y, h.y, q2); }
  q += q2;
  sum2<16>(s, q, lane);
  const float mean = s * (0.5f / DM), rs = rsq(fmaxf(q * (0.25f / DM) - mean * mean, 0.f) + 1e-5f);
  if ((lane & 15) == 0) asm volatile("st.relaxed.gpu.global.u32 [%0], %1;" :: "l"(&g_st2[1][r % RD][n]), "r"((__float_as_uint(0.5f * rs) & ~127u) | (r + 1)) : "memory");
}
__device__ __forceinline__ void r3rows(int r, int row, int tok, int lane, __nv_bfloat16* out) {
  const int n = row + (lane >> 4), m = 32 + ((n - 2) & 31);
  const unsigned char* ap = &g_acc[0][r % RD][0] + (uint32_t)(n * 128 + ((lane >> 3) & 1) * 8192 + (((lane ^ n) & 7) << 4));
  const unsigned char* zp = &g_acc[4][(r + RD - (row == 32)) % RD][0] + (uint32_t)(m * 128 + ((lane >> 3) & 1) * 8192 + (((lane ^ m) & 7) << 4));
  unsigned char* op = reinterpret_cast<unsigned char*>(out) + (uint32_t)((tok + (lane >> 4)) * 1280 + (lane & 15) * 16);
  float2 st;
  asm volatile("ld.relaxed.gpu.global.v2.f32 {%0,%1}, [%2];" : "=f"(st.x), "=f"(st.y) : "l"(g_stat + tok + (lane >> 4)) : "memory");
#pragma unroll 1
  for (int i0 = 0; i0 < 3; i0++) {
    uint32_t a[8], c[8], u[8];
#pragma unroll
    for (int i = 0; i < 2; i++) { ldg4(a + 4 * i, ap + 3 * BUF + i * 16384); ldg4(c + 4 * i, ap + 2 * BUF + i * 16384); ldg4(u + 4 * i, zp + i * 16384); }
    uint32_t z = dep0(u[7], lane);
#pragma unroll
    for (int i = 0; i < 8; i++) {
      const float2 h = h2f(a[i] | z), e = h2f(c[i] | z), g = h2f(u[i] | z);
      a[i] = pack2(fmaf(h.x + e.x, 0.5f, fmaf(g.x, st.x, st.y)), fmaf(h.y + e.y, 0.5f, fmaf(g.y, st.x, st.y)));
      if (i & 1) z = dep0(a[i], lane);
    }
    if (i0 < 2) stg4(op, a);
    stg4(op + 256, a + 4);
    ap += 32768 >> i0; zp += 32768 >> i0; op += 512 >> i0;
  }
}
template <int TYPE>
__device__ __forceinline__ void rloop(int row, int cp, int role, const __nv_bfloat16* x, __nv_bfloat16* out) {
  constexpr int ST = TYPE == 4 ? 2 : TYPE;
  const int r0 = row & 32 ? LAG : 0;
  uint32_t v = 0;
#pragma unroll 1
  for (int r = r0; r < r0 + NSEG + (TYPE > 0); r++) {
    const int tok = (r - r0) * 32 + (row & 31) - (TYPE ? 2 : 0);
    const bool valid = TYPE == 0 || (unsigned)tok < S_LEN;
    const uint32_t* go = &g_f[F_R1 + 4 * ST + cp][r];
    const uint32_t* first = TYPE == 2 ? &g_f[F_R2 + cp][r] : TYPE ? go : (const uint32_t*)&g_xready[NSEG + r - r0][0];
    if constexpr (TYPE == 1 || TYPE == 4) {
      const int lane = await(v, go, NOP * NW12 * NW34, false);
      BTS2(r, 8 + 2 * ST); RTS(0);
      if (TYPE == 1) { r2rows(r, row, lane); BTS2(r, 11); continue; }
      if (valid) r3rows(r, row, tok, lane, out);
    } else {
      if (TYPE || row >= 32) await(v, first, TYPE ? NOP * NW12 * NW34 : 32, true);
      if (valid) rrow<TYPE>(r, row, tok, lane_of(r), go, role, x);
    }
    if (TYPE == 4 && r + RD - 2 >= NSTEP) { v = 0; BTS2(r, 13); continue; }
    const int lane = lane_of(r);
    const void* f = lane ? (const void*)&g_xready[NSEG + (tok >> 5)][0] : (const void*)&g_f[TYPE ? F_DONE : F_Z][r];
    asm volatile("" : "+l"(f));
    __syncwarp();
    RTS(3);
    v = ld_relaxed(first + (TYPE ? 1 : 8));
    asm volatile("fence.release.gpu;" ::: "memory");
    RTS(4);
    red_if(lane == 0 || (TYPE == 2 && lane == 1 && valid) ? (TYPE & 5 ? 2 : 1) : 0, f);
    RTS(5);
    RTS_OUT();
    BTS2(r, 9 + 2 * ST);
  }
}

#define SINGLE_OP 3
#define SINGLE_W 0
#define W_DELAY 0
#define BULK_ADD(T, dst, src, len) asm volatile("{\n.reg .pred e;\nelect.sync _|e, 0xffffffff;\n@e cp.reduce.async.bulk.global.shared::cta.bulk_group.add.noftz." T " [%0], [%1], %2;\n}" \
                                               :: "l"(dst), "r"(src), "r"(len) : "memory")
#define COMMIT() asm volatile("cp.async.bulk.commit_group;" ::: "memory")
#define DRAINED(n) do { asm volatile("cp.async.bulk.wait_group.read " #n ";" ::: "memory"); __syncwarp(); } while (0)
#define WRITTEN() do { asm volatile("cp.async.bulk.wait_group 0;\nfence.proxy.async.global;" ::: "memory"); __syncwarp(); } while (0)
__device__ __forceinline__ void wait_flags(const uint32_t* p, uint32_t target) {
  int n = 0;
  while (!__all_sync(~0u, ld_relaxed(p) >= target)) { if (++n > SPIN_LIMIT) FAIL(); }
  asm volatile("fence.acquire.gpu;" ::: "memory");
  asm volatile("fence.proxy.async.global;" ::: "memory");
}
__global__ void __launch_bounds__(512, 1) bworker_kernel(const __grid_constant__ BParams P) {
  extern __shared__ __align__(1024) unsigned char smem_raw[];
  const uint32_t sb = SMEM0, bar = sb + BO_BAR;
  const int wg = __shfl_sync(~0u, threadIdx.x >> 7, 0), warp = __shfl_sync(~0u, (threadIdx.x >> 5) & 3, 0);
  if (threadIdx.x == 0) {
    if (smem_u32(smem_raw) != SMEM0) FAIL();
    uint32_t smid; asm volatile("mov.u32 %0, %%smid;" : "=r"(smid));
    const uint32_t nb = ld_relaxed(&g_tpc[(smid >> 1) & 127]);
    const bool single = nb > 1, far = nb == 0 && (smid < 64 || smid >= 124);
    int kind = far || (single && atomicAdd(&g_f[F_MISC][35], 1u) < SINGLE_OP) ? 0 : single ? 1 + SINGLE_W : 1;
    int rc = single || (smid >> 1) == 16 || (smid >> 1) == 63 ? 1 : far ? 2 : 0;
    uint32_t i = atomicAdd(&g_f[F_MISC][32 + kind], 1u), o = atomicAdd(&g_f[F_MISC][36 + rc], 1u);
    while (i >= (kind == 0 ? NOP : kind == 1 ? NW12 : NW34)) { kind = (kind + 1) % 3; i = atomicAdd(&g_f[F_MISC][32 + kind], 1u); }
    while (o >= (rc == 0 ? 16 : rc == 1 ? 8 : 12)) { rc = (rc + 1) % 3; o = atomicAdd(&g_f[F_MISC][36 + rc], 1u); }
    sts64(sb + BO_BOX, i + (kind == 0 ? 0 : kind == 1 ? NOP : NOP + NW12), o + (rc ? 8 + 8 * rc : 0));
    for (int k = 0; k < BB_NUM; k++) mbar_init(bar + 8 * k, k >= BB_USED ? 4 : k >= BB_EMPTY ? 8 : k >= BB_ZFREE && kind ? 2 : 1);
    asm volatile("fence.mbarrier_init.release.cluster;" ::: "memory");
  }
  if (threadIdx.x < 128) sts128(sb + BO_CARRY + threadIdx.x * 16, 0u, 0u, 0u, 0u);
  auto ln0 = [&](int t) {
    const int lane = lane_of(t);
    if (lane < 20 && t + 128 < S_LEN) asm volatile("prefetch.global.L2 [%0];" :: "l"(P.x + (t + (t < 4 * NBC ? 4 * NBC : 128)) * DM + (lane >> 1) * 64));
    rrow<3>(0, 0, t, lane, nullptr, 0, P.x);
    __syncwarp();
    asm volatile("fence.release.gpu;" ::: "memory");
    red_if(lane == 0, &g_xready[t >> 5][0]);
  };
  if (wg == 2) ln0(blockIdx.x * 4 + warp);
  fence_async();
  __syncthreads();
  const int role = uni(lds32(sb + BO_BOX));
  if (threadIdx.x < 32) BTS(94, 1);
  const bool op = role < NOP, w12 = role < NOP + NW12;
  const int j = op ? role : w12 ? role - NOP : role - NOP - NW12;
  const int rot = op ? (j ? 2 * ((j + 1) % 5) : 0) : 2 * (j % 5);
  if (wg == 3) {
    asm volatile("setmaxnreg.dec.sync.aligned.u32 24;");
    LANE_INIT();
    if (warp < 2) {
      auto announce = [&](int r) {
        const uint32_t* f = &g_f[(op ? F_R1 : w12 ? F_R2 : F_R3) + (lane & 3)][r];
        asm volatile("" : "+l"(f));
        if (warp == 0) { mbar_arrive_if(lane == 0, bar + 8 * BB_DONE); return; }
        mbar_waitw(bar + 8 * BB_DONE, r & 1);
        PTS(60);
        asm volatile("fence.release.gpu;" ::: "memory");
        red_if(lane >= 4 ? 0 : op ? NW12 * NW34 : w12 ? NOP * NW34 : NOP * NW12, f);
        PTS(61);
        BTS(r, 4);
      };
      if (op) {
        int mt = rot + warp;
        bar_arrive(NB_FREE + warp, 160);
#pragma unroll 1
        for (int r = 0; r < NSTEP; r++) {
          const uint32_t len = fmask(r) == 3 ? 8192 : 4096;
          unsigned char* acc = &g_acc[j & 1][r % RD][fmask(r) == 2 ? 4096 : 0];
#pragma unroll 1
          for (int p = 0; p < 5; p++) {
            bar_sync(NB_STAGED + warp, 160);
            PTS(50 + 2 * p + warp);
            fence_async();
            BULK_ADD("bf16", acc + mt * 8192, sb + BO_STG + warp * 8192, len);
            COMMIT();
            PTS(64 + 50 + 2 * p + warp);
            mt = mt >= 8 ? mt - 8 : mt + 2;
            DRAINED(0);
            bar_arrive(NB_FREE + warp, 160);
          }
          WRITTEN();
          announce(r);
        }
      } else {
#pragma unroll 1
        for (int r = 0; r < NR; r++) {
          const uint32_t len = bmask(r) == 3 ? 8192 : 4096;
          unsigned char* acc = &g_acc[w12 ? 2 : 3][r % RD][bmask(r) == 2 ? 4096 : 0];
          int mt = rot + warp;
          const bool pairs = len != 8192;
#pragma unroll 1
          for (int p = pairs ? 2 : 0; p < 5; p++) {
            const uint32_t src = sb + (p == 4 ? BO_H : BO_RING_MLP + (2 - (p & 1)) * 16384) + warp * 8192;
            bar_sync(NB_STAGED + (p == 4 ? 4 : 2 * (p & 1)) + warp, 160);
            PTS(50 + 2 * p + warp);
            fence_async();
            BULK_ADD("f16", acc + mt * 8192, src, len);
            mt = mt >= 8 ? mt - 8 : mt + 2;
            if (pairs && p < 4) { BULK_ADD("f16", acc + mt * 8192, src + 4096, len); mt = mt >= 8 ? mt - 8 : mt + 2; }
            COMMIT();
            PTS(64 + 50 + 2 * p + warp);
            if (p == 4 && !pairs) break;
            DRAINED(1);
            mbar_arrive_if(lane == 0, bar + 8 * (p == 1 || p == 2 ? BB_SFREE + 2 * (p - 1) + warp : BB_ZFREE + (p >> 1)));
            mbar_arrive_if(lane < 2 && pairs && p == 2, bar + 8 * (lane ? BB_SFREE + warp : BB_ZFREE));
            if (p == 3 && !pairs) { DRAINED(0); mbar_arrive_if(lane == 0, bar + 8 * (BB_ZFREE + 2)); }
          }
          WRITTEN();
          mbar_arrive_if(lane == 0, bar + 8 * (BB_SFREE + 4 + warp));
          announce(r);
        }
      }
    } else {
      if (op && warp == 2) {
        unsigned char* wt = g_wt + j * (10 * OP_SLOT);
#pragma unroll 1
        for (int m0 = 0; m0 < 10; m0 += 3) {
          const int nu = m0 < 9 ? 9 : 3;
          mbar_expect_if(lane == 0, bar + 8 * BB_TMP, nu * 4096);
#pragma unroll 1
          for (int k = 0; k < nu; k++) tma2d_e(sb + BO_RING_OP + k * 4096, &P.wmap[0], (m0 + k / 3) * 64, 320 * j + 224 + 32 * (k % 3), bar + 8 * BB_TMP);
          mbar_waitw(bar + 8 * BB_TMP, m0 & 1);
          bulk_s2g_e(wt + m0 * OP_SLOT, sb + BO_RING_OP, nu * 4096);
          COMMIT();
          WRITTEN();
        }
        asm volatile("fence.acq_rel.gpu;" ::: "memory");
        int sl = 0, ph = 1, mt = rot;
#pragma unroll 1
        for (int r = -1; r < NSTEP; r++) {
#pragma unroll 1
          for (int n = r < 0 ? 7 : 0; n < (r + 1 < NSTEP ? 10 : 7); n++) {
            mbar_waitw(bar + 8 * (BB_USED + sl), ph);
            mbar_expect_if(lane == 0, bar + 8 * (BB_FULL + sl), OP_SLOT);
            bulk_g2s_e(sb + BO_RING_OP + sl * OP_SLOT, wt + mt * OP_SLOT, OP_SLOT, bar + 8 * (BB_FULL + sl));
            if (++sl == 3) { sl = 0; ph ^= 1; }
            mt = mt == 9 ? 0 : mt + 1;
          }
        }
      } else if (op) {
        mbar_waitw(bar + 8 * BB_START, 0);
#pragma unroll 1
        for (int r = 0; r < NSTEP; r++) {
          const int rb = r - RD + 2;
          const uint32_t len = fmask(r) == 3 ? 8192 : 4096;
          const unsigned char* src = g_o + (uint32_t)(r % RO * (96 * 8192) + 5 * j * len);
          wait_flags(lane < 2 ? &g_f[F_O + (lane ? NOP : j)][r] : rb >= 0 ? &g_f[F_DONE][rb] : &g_f[F_MISC][0],
                     lane < 2 ? (lane ? 1 : 5) : rb >= 0 ? rtarget(bmask(rb)) : NBC * 8);
          PTS1(35);
          if (r) bar_sync(NB_EARLY, 288);
          if (r == LAG) bar_sync(NB_LAST, 288);
          mbar_expect_if(lane < 3, bar + 8 * (BB_OFULL + lane), 2 * len);
          bulk_g2s_e(sb + BO_O, src, 2 * len, bar + 8 * BB_OFULL);
          PTS(62); PTS1(38);
          if (r && r != LAG) bar_sync(NB_LAST, 288);
          bulk_g2s_e(sb + BO_O + 2 * len, src + 2 * len, 2 * len, bar + 8 * (BB_OFULL + 1));
          bulk_g2s_e(sb + BO_O + 4 * len, src + 4 * len, len, bar + 8 * (BB_OFULL + 2));
          bulk_g2s_e(sb + BO_O + 5 * len, src + (95 - 5 * j) * len, len, bar + 8 * (BB_OFULL + 2));
          PTS1(64 + 35);
          BTS(r, 0);
        }
      } else if (warp == 2) {
#pragma unroll 1
        for (int r = 0; r < NR; r++) {
          const int mk = w12 ? fmask(r) : bmask(r);
          if (mk) {
            const unsigned char* src = &g_acc[w12 ? 4 : 2][r % RD][mk == 2 ? 4096 : 0];
            wait_flags(w12 ? &g_f[F_Z][r] : lane && r >= 2 ? &g_f[F_R3 + (j & 3)][r - 2] : &g_f[F_R2 + (j & 3)][r], w12 ? rtarget(mk) : NOP * NW12 * NW34);
#pragma unroll 1
            for (int z = 0; z < 5; z++) {
              const uint32_t fb = bar + 8 * (BB_FULL + z), dst = sb + BO_RING_MLP + 2 * z % 3 * 16384 + (mk == 2 ? 4096 : 0);
              mbar_waitw(bar + 8 * (z < 3 ? BB_ZFREE + z : BB_EMPTY + z - 3), (r + (z < 3)) & 1);
              if (z == 0) PTS(62);
              mbar_expect_if(lane == 0, fb, mk == 3 ? 16384 : 8192);
              bulk_g2s_e(dst, src + z * 16384, mk == 3 ? 16384 : 4096, fb);
              if (mk != 3) bulk_g2s_e(dst + 8192, src + z * 16384 + 8192, 4096, fb);
              if (z == 0) BTS(r, 0);
            }
          }
          if (!w12) {
#pragma unroll 1
            for (int c = j; c < 120; c += NW34) bulk_s2g_e(&g_acc[c < 80 ? c / 40 : 3][(r + (c < 80 ? 0 : 2)) % RD][c % 40 * 2048], sb + BO_CARRY, 2048);
            COMMIT();
            WRITTEN();
          }
          mbar_waitw(bar + 8 * BB_DONE, (r + 1) & 1);
          mbar_arrive_if(lane == 0, bar + 8 * BB_DONE);
        }
      } else {
#pragma unroll 1
        for (int r = 0; r < (w12 ? NSTEP : NR); r++) {
          const bool idle = !((w12 ? fmask(r) : bmask(r)) >> (lane >> 4) & 1);
          uint32_t t0, t1;
          int n = 0;
          mbar_waitw(bar + 8 * BB_FULL, r & 1);
          do {
            asm volatile("ld.relaxed.gpu.global.v2.u32 {%0,%1}, [%2];" : "=r"(t0), "=r"(t1) : "l"(&g_st2[!w12][r % RD][2 * lane]) : "memory");
            if (++n > SPIN_LIMIT) FAIL();
          } while (!__all_sync(~0u, idle || (((t0 ^ (r + 1)) | (t1 ^ (r + 1))) & 127) == 0));
          sts64(sb + BO_STAT + (lane >> 4) * 128 + (lane & 3) * 32 + ((lane >> 2) & 3) * 8, t0, t1);
          __syncwarp();
          mbar_arrive_if(lane == 0, bar + 8 * BB_STAT);
          PTS(63);
        }
      }
    }
    bar_arrive(NB_END, 512);
  } else if (wg == 2) {
    asm volatile("setmaxnreg.dec.sync.aligned.u32 40;");
    const int ord = uni(lds32(sb + BO_BOX + 4));
    const int gw = ord < 16 ? warp * 16 + ord : ord < 24 ? 48 + warp * 8 + ord : 72 + warp * 12 + ord, row = gw < 64 ? gw : gw < 96 ? gw - 64 : gw < 128 ? 2 * gw - 192 : 2 * gw - 224;
    if (row >= 32) {
#pragma unroll 1
      for (int t = 4 * NBC + (gw < 64 ? gw - 32 : gw - 80); t < S_LEN; t += 64) ln0(t);
    }
    if (gw < 64) rloop<0>(row, gw & 3, role, P.x, P.out);
    else if (gw < 96) rloop<2>(row, gw & 3, role, P.x, P.out);
    else if (gw < 128) rloop<1>(row, gw & 3, role, P.x, P.out);
    else rloop<4>(row, gw & 3, role, P.x, P.out);
    asm volatile("griddepcontrol.wait;" ::: "memory");
    const int t = threadIdx.x & 127;
    for (int i = (blockIdx.x * 128 + t) * 4; i < 4 * NCL * 2560; i += NBC * 512)
      *reinterpret_cast<uint4*>(&g_part[0][0][0][0] + i) = make_uint4(0u, 0u, 0u, 0u);
    bar_sync(NB_END, 512);
    if (t == 0) {
      uint32_t n;
      asm volatile("atom.acq_rel.gpu.global.add.u32 %0, [%1], 1;" : "=r"(n) : "l"(&g_f[F_MISC][64]) : "memory");
      sts32(sb + BO_BOX, n);
    }
    bar_sync(NB_END2, 128);
    if (lds32(sb + BO_BOX) == NBC - 1) {
      for (int i = t; i < F_NUM * 24; i += 128) reinterpret_cast<uint4*>(&g_f[0][0])[i] = make_uint4(0u, 0u, 0u, 0u);
      g_xready[t][0] = 0; g_tpc[t] = 0;
    }
  } else {
    asm volatile("setmaxnreg.inc.sync.aligned.u32 224;");
    LANE_INIT();
    for (int i = blockIdx.x * 256 + threadIdx.x; i < 2 * (RD + 1) * TILE_B / 16; i += NBC * 256)
      reinterpret_cast<uint4*>(&g_acc[i < 2 * RD * TILE_B / 16 ? 0 : 1][0][0])[i] = make_uint4(0u, 0u, 0u, 0u);
    warp_signal(&g_f[F_MISC][0], lane);
    const int mt0 = (rot + wg) % 10;
    auto boxes = [&](int ss) {
      const int nb = op && ss ? 3 : 4;
      const uint32_t base = sb + (ss ? BO_RES + wg * OP_RES : wg * 83968);
      mbar_expect_if(warp == 0 && lane == 0, bar + 8 * (BB_W + wg), nb * 20480 + (op ? 2048 : 0));
      bar_sync(NB_H, 256);
      if (warp < nb) {
#pragma unroll 1
        for (int i = warp; i < 5 * nb; i += nb) {
          const int p = op ? i / nb : (i - 10) >> 1, mt = (mt0 + 2 * p) % 10;
          const bool first = !op && i < 10;
          tma2d_e(op || !ss ? base + i * 4096 : sb + (first ? BO_W1 : -81920) + (2 * i + wg) * 4096, &P.wmap[op ? 0 : (w12 ? 1 : 3) + !first], first ? 128 * j + 64 * wg : mt * 64,
                  op ? 320 * j + 64 * warp + 32 * ss : first ? 64 * i + 32 * ss : 128 * j + 32 * (i & 1) + 64 * ss, bar + 8 * (BB_W + wg));
        }
      }
      if (op && warp == 3) tma2d_e(base + nb * 20480, &P.wo16, (mt0 + 2 * ss) % 10 * 64, 95 * 64 + (j + 1) / 5 * 16, bar + 8 * (BB_W + wg));
      mbar_waitw(bar + 8 * (BB_W + wg), ss);
    };
    if (W_DELAY) __nanosleep(W_DELAY);
    uint32_t W[164];
    boxes(0);
    load_w<41>(W, sb + wg * 83968, warp, lane);
    fence_async();
    boxes(1);
    if (!op) {
      float cs[2] = {0.f, 0.f};
      const uint32_t a0 = sb + BO_W1 + wg * 4096 + ((lane >> 4) * 8 + (lane & 7)) * 128 + (((warp * 2 + ((lane >> 3) & 1)) ^ (lane & 7)) << 4);
#pragma unroll
      for (int i = 0; i < 80; i++) cs[i & 1] += bf_lo(W[i]) + bf_hi(W[i]);
#pragma unroll 1
      for (int i = 0; i < 40; i++) {
        uint32_t t[4];
        const uint32_t ad = a0 + (i % 20 >> 1) * 8192 + (i & 1) * 2048;
        ldsm4t(t[0], t[1], t[2], t[3], ad);
#pragma unroll
        for (int k = 0; k < 4; k++) {
          if (i < 20) cs[k & 1] += bf_lo(t[k]) + bf_hi(t[k]);
          t[k] = pack2h(bf_lo(t[k]) - cs[k & 1], bf_hi(t[k]) - cs[k & 1]);
        }
        if (i >= 20) stsm4t(ad, t[0], t[1], t[2], t[3]);
        if (i == 19) {
#pragma unroll
          for (int k = 0; k < 2; k++) { cs[k] += __shfl_xor_sync(~0u, cs[k], 1); cs[k] += __shfl_xor_sync(~0u, cs[k], 2); cs[k] *= 1.f / DM; }
        }
      }
      const uint32_t z = dep0(__float_as_uint(cs[0]), lane);
#pragma unroll
      for (int i = 0; i < 80; i++) W[i] = pack2h(bf_lo(W[i] | z) - cs[i & 1], bf_hi(W[i] | z) - cs[i & 1]);
      fence_async();
      bar_sync(NB_H, 256);
    }
    if (warp == 0) BTS(94, 6 + wg);
    const Dsc blo = {P.desc, 1}, alo = blo + wg * (op ? OP_RES / 16 : 256);
    if (op) {
      Ring rg = {(uint32_t)wg, 0};
      mbar_arrive_if(lane == 0, bar + 8 * BB_START);
      if (wg) bar_arrive(NB_PP, 256);
      const Dsc xlo = blo + (j + 1) / 5 * 2;
#pragma unroll 1
      for (int r = 0; r < NSTEP; r++) {
        asm volatile("" : "+r"(lane));
        if (fmask(r) == 3) op_round<64>(W, bar, alo, blo, xlo, j == 0, rg, wg, warp, lane, r);
        else op_round<32>(W, bar, alo, blo, xlo, j == 0, rg, wg, warp, lane, r);
        if (warp == 0) BTS(r, 2 + wg);
      }
    } else {
      const int q4 = (128 * j + 64 * wg + 16 * warp) / 160, off = w12 ? (0x0413 >> (4 * q4)) & 7 : 0;
#pragma unroll 1
      for (int r = 0; r < NR; r++) {
        asm volatile("" : "+r"(lane));
        const int bm = bmask(r), fm = w12 ? fmask(r) : bm;
        if (fm == 3) phase1<64>(W, sb, alo, blo, 0, wg, warp, lane, off, r);
        else if (fm) phase1<32>(W, sb, alo, blo + (fm >> 1) * 256, fm >> 1, wg, warp, lane, off, r);
        else { mbar_waitu(bar + 8 * (BB_SFREE + 4 + wg), (r + 1) & 1); carry_in(sb, wg, warp, lane); }
        CTS(33);
        fence_async();
        bar_sync(NB_H, 256);
        if (wg + warp == 0) BTS(r, 1);
        if (bm == 3) phase2<64>(W, bar, alo, blo, wg, warp, lane, r);
        else phase2<32>(W, bar, alo, blo + (bm >> 1) * 256, wg, warp, lane, r);
        if (warp == 0) BTS(r, 2 + wg);
      }
    }
    CTS_OUT();
    bar_arrive(NB_END, 512);
  }
}

typedef CUresult (*EncodeFn)(CUtensorMap*, CUtensorMapDataType, cuuint32_t, void*, const cuuint64_t*, const cuuint64_t*, const cuuint32_t*,
                             const cuuint32_t*, CUtensorMapInterleave, CUtensorMapSwizzle, CUtensorMapL2promotion, CUtensorMapFloatOOBfill);
static void make_map(EncodeFn fn, CUtensorMap* tm, const void* ptr, uint64_t cols, uint64_t rows, uint32_t bc, uint32_t br) {
  cuuint64_t dims[2] = {cols, rows}; cuuint64_t strides[1] = {cols * 2}; cuuint32_t box[2] = {bc, br}; cuuint32_t es[2] = {1, 1};
  fn(tm, CU_TENSOR_MAP_DATA_TYPE_BFLOAT16, 2, const_cast<void*>(ptr), dims, strides, box, es, CU_TENSOR_MAP_INTERLEAVE_NONE,
     CU_TENSOR_MAP_SWIZZLE_128B, CU_TENSOR_MAP_L2_PROMOTION_L2_256B, CU_TENSOR_MAP_FLOAT_OOB_FILL_NONE);
}
#define dbg_a_only 0
extern "C" void kernel_launch(void* const* d_in, const int* in_sizes, int n_in, void* d_out, int out_size) {
  void* fnp = nullptr; cudaDriverEntryPointQueryResult qr;
  cudaGetDriverEntryPoint("cuTensorMapEncodeTiled", &fnp, cudaEnableDefault, &qr);
  EncodeFn fn = (EncodeFn)fnp;
  cudaStream_t st = cudaStreamPerThread;
  cudaFuncSetAttribute(bworker_kernel, cudaFuncAttributeMaxDynamicSharedMemorySize, B_SMEM);
  {
    AMaps M;
    for (int i = 0; i < 3; i++) make_map(fn, &M.w16[i], d_in[2 + i], HD, DM, 64, 16);
    M.wv = (const __nv_bfloat16*)d_in[4];
    make_map(fn, &M.wo32, d_in[5], DM, HD, 64, 32);
    const uint32_t hi[5] = {dhi(TILE_SBO, 3), dhi(1024, 1), dhi(1024, 0), dhi(PL_SZ, 0), dhi(896, 0)};
    for (int i = 0; i < 5; i++) M.d[i] = (uint64_t)hi[i] << 32;
    cudaFuncSetAttribute(acore_kernel, cudaFuncAttributeMaxDynamicSharedMemorySize, A_SMEM);
    cudaFuncSetAttribute(acore_kernel, cudaFuncAttributeNonPortableClusterSizeAllowed, 1);
    cudaLaunchConfig_t cfg = {};
    cfg.gridDim = dim3(CL_SIZE * NCL); cfg.blockDim = dim3(512); cfg.dynamicSmemBytes = A_SMEM; cfg.stream = st;
    cudaLaunchAttribute at[1]; at[0].id = cudaLaunchAttributeClusterDimension;
    at[0].val.clusterDim.x = CL_SIZE; at[0].val.clusterDim.y = 1; at[0].val.clusterDim.z = 1;
    cfg.attrs = at; cfg.numAttrs = 1;
    cudaLaunchKernelEx(&cfg, acore_kernel, M, (const __nv_bfloat16*)d_in[1], dbg_a_only ? 0 : 1);
  }
  if (!dbg_a_only) {
    BParams P;
    make_map(fn, &P.wmap[0], d_in[5], DM, HD, 64, 32);
    make_map(fn, &P.wo16, d_in[5], DM, HD, 64, 16);
    make_map(fn, &P.wmap[1], d_in[8], DM, DM, 64, 32);
    make_map(fn, &P.wmap[2], d_in[9], DM, DM, 64, 32);
    make_map(fn, &P.wmap[3], d_in[10], FF, DM, 64, 32);
    make_map(fn, &P.wmap[4], d_in[11], DM, FF, 64, 32);
    P.x = (const __nv_bfloat16*)d_in[0];
    P.out = (__nv_bfloat16*)d_out;
    P.desc = (uint64_t)dhi(1024, 1) << 32;
    cudaLaunchConfig_t cfg = {};
    cfg.gridDim = dim3(NBC); cfg.blockDim = dim3(512); cfg.dynamicSmemBytes = B_SMEM; cfg.stream = st;
    cudaLaunchAttribute at[1]; at[0].id = cudaLaunchAttributeProgrammaticStreamSerialization; at[0].val.programmaticStreamSerializationAllowed = 1;
    cfg.attrs = at; cfg.numAttrs = 1;
    cudaLaunchKernelEx(&cfg, bworker_kernel, P);
  }
}
```

```cpp
#include <cuda_runtime.h>
#include <cuda_bf16.h>
#include <cuda.h>
#include <stdint.h>

#define S_LEN 2048
#define DM 640
#define NH 32
#define DH 192
#define HD 6144
#define NSEG 64
#define FF 1536

__device__ __forceinline__ uint32_t smem_u32(const void* p) { return (uint32_t)__cvta_generic_to_shared(p); }
__device__ __forceinline__ uint32_t mapa(uint32_t a, uint32_t r) {
  uint32_t o; asm volatile("mapa.shared::cluster.u32 %0, %1, %2;" : "=r"(o) : "r"(a), "r"(r)); return o; }
__device__ __forceinline__ void mbar_init(uint32_t b, uint32_t c) {
  asm volatile("mbarrier.init.shared::cta.b64 [%0], %1;" :: "r"(b), "r"(c) : "memory"); }
__device__ __forceinline__ void mbar_expect(uint32_t b, uint32_t tx) {
  asm volatile("mbarrier.arrive.expect_tx.shared::cta.b64 _, [%0], %1;" :: "r"(b), "r"(tx) : "memory"); }
__device__ __forceinline__ void mbar_arrive(uint32_t b) {
  asm volatile("mbarrier.arrive.shared::cta.b64 _, [%0];" :: "r"(b) : "memory"); }
__device__ __forceinline__ void mbar_arrive_remote(uint32_t rb) {
  asm volatile("mbarrier.arrive.relaxed.cluster.shared::cluster.b64 _, [%0];" :: "r"(rb) : "memory"); }
__device__ __forceinline__ void mbar_expect_if(bool p, uint32_t b, uint32_t tx) {
  asm volatile("{\n.reg .pred q;\nsetp.ne.u32 q, %2, 0;\n@q mbarrier.arrive.expect_tx.shared::cta.b64 _, [%0], %1;\n}" :: "r"(b), "r"(tx), "r"((uint32_t)p) : "memory"); }
__device__ __forceinline__ void mbar_arrive_if(bool p, uint32_t b) {
  asm volatile("{\n.reg .pred q;\nsetp.ne.u32 q, %1, 0;\n@q mbarrier.arrive.shared::cta.b64 _, [%0];\n}" :: "r"(b), "r"((uint32_t)p) : "memory"); }
__device__ __forceinline__ void mbar_arrive_remote_if(bool p, uint32_t rb) {
  asm volatile("{\n.reg .pred q;\nsetp.ne.u32 q, %1, 0;\n@q mbarrier.arrive.relaxed.cluster.shared::cluster.b64 _, [%0];\n}" :: "r"(rb), "r"((uint32_t)p) : "memory"); }
__device__ __forceinline__ void sts32_if(bool p, uint32_t a, uint32_t v) {
  asm volatile("{\n.reg .pred q;\nsetp.ne.u32 q, %2, 0;\n@q st.shared.b32 [%0], %1;\n}" :: "r"(a), "r"(v), "r"((uint32_t)p) : "memory"); }
__device__ __forceinline__ void sts128z_if(bool p, uint32_t a) {
  asm volatile("{\n.reg .pred q;\nsetp.ne.u32 q, %1, 0;\n@q st.shared.v4.b32 [%0], {0,0,0,0};\n}" :: "r"(a), "r"((uint32_t)p) : "memory"); }
__device__ __forceinline__ bool mbar_try(uint32_t b, uint32_t ph) {
  uint32_t ok;
  asm volatile("{\n.reg .pred p;\nmbarrier.try_wait.parity.shared::cta.b64 p, [%1], %2;\nselp.u32 %0, 1, 0, p;\n}"
               : "=r"(ok) : "r"(b), "r"(ph) : "memory");
  return ok; }
__device__ __forceinline__ bool mbar_test(uint32_t b, uint32_t ph) {
  uint32_t ok;
  asm volatile("{\n.reg .pred p;\nmbarrier.test_wait.parity.shared::cta.b64 p, [%1], %2;\nselp.u32 %0, 1, 0, p;\n}"
               : "=r"(ok) : "r"(b), "r"(ph) : "memory");
  return ok; }
#define SPIN_LIMIT 4000000
#define FAIL() asm volatile("st.global.u32 [%0], 0;" :: "l"(8ull) : "memory")
#define CFENCE() asm volatile("fence.proxy.async::generic.acquire.sync_restrict::shared::cluster.cluster;" ::: "memory")
__device__ __forceinline__ void mbar_wait(uint32_t b, uint32_t ph) {
  int n = 0;
  while (!mbar_try(b, ph)) { if (++n > SPIN_LIMIT) FAIL(); } }
#define TIMEOUT_ACT "@!p st.shared.u32 [%0+1], 0;"
#define WAIT_HINT ", 20000"
#define WAIT_LIM "200000"
__device__ __forceinline__ void mbar_slow(uint32_t b, uint32_t ph) {
  asm volatile("{\n.reg .pred p, q;\n.reg .u32 n;\nmov.u32 n, 0;\n"
               "WL:\nmbarrier.try_wait.parity.shared::cta.b64 p, [%0], %1" WAIT_HINT ";\nadd.u32 n, n, 1;\nsetp.lt.and.u32 q, n, " WAIT_LIM ", !p;\n@q bra.uni WL;\n"
               TIMEOUT_ACT "\n}" :: "r"(b), "r"(ph) : "memory"); }
__device__ __forceinline__ void mbar_waitw(uint32_t b, uint32_t ph) {
  asm volatile("{\n.reg .pred p, q;\n.reg .u32 n;\nmbarrier.try_wait.parity.shared::cta.b64 p, [%0], %1;\n@p bra.uni WD;\nmov.u32 n, 0;\n"
               "WL:\nmbarrier.try_wait.parity.shared::cta.b64 p, [%0], %1" WAIT_HINT ";\nadd.u32 n, n, 1;\nsetp.lt.and.u32 q, n, " WAIT_LIM ", !p;\n@q bra.uni WL;\n"
               TIMEOUT_ACT "\nWD:\n}" :: "r"(b), "r"(ph) : "memory"); }
__device__ __forceinline__ void mbar_waitw2(uint32_t b0, uint32_t b1, uint32_t ph) {
  uint32_t ok;
  asm volatile("{\n.reg .pred p, r;\nmbarrier.try_wait.parity.shared::cta.b64 p, [%1], %3;\nmbarrier.try_wait.parity.shared::cta.b64 r, [%2], %3;\n"
               "and.pred p, p, r;\nselp.u32 %0, 1, 0, p;\n}" : "=r"(ok) : "r"(b0), "r"(b1), "r"(ph) : "memory");
  if (__builtin_expect(!__all_sync(~0u, ok), 0)) { mbar_slow(b0, ph); mbar_slow(b1, ph); }
}
__device__ __forceinline__ void mbar_waitu(uint32_t b, uint32_t ph) {
  asm volatile("{\n.reg .pred p;\nmbarrier.try_wait.parity.shared::cta.b64 p, [%0], %1;\n@p bra.uni WD;\n"
               "WL:\nmbarrier.try_wait.parity.shared::cta.b64 p, [%0], %1" WAIT_HINT ";\n@!p bra.uni WL;\nWD:\n}" :: "r"(b), "r"(ph) : "memory"); }
__device__ __forceinline__ void mbar_waitu2(uint32_t b0, uint32_t b1, uint32_t ph) {
  asm volatile("{\n.reg .pred p, r;\nWL:\nmbarrier.try_wait.parity.shared::cta.b64 p, [%0], %2;\nmbarrier.try_wait.parity.shared::cta.b64 r, [%1], %2;\n"
               "and.pred p, p, r;\n@!p bra.uni WL;\n}" :: "r"(b0), "r"(b1), "r"(ph) : "memory"); }
__device__ __forceinline__ void mbar_waitw4(uint32_t b, uint32_t ph) { mbar_waitw2(b, b + 8, ph); mbar_waitw2(b + 16, b + 24, ph); }
__device__ __forceinline__ uint32_t clock32() { uint32_t t; asm volatile("mov.u32 %0, %%clock;" : "=r"(t) :: "memory"); return t; }
template <int L> __device__ __forceinline__ uint32_t lop3(uint32_t a, uint32_t b, uint32_t c) {
  uint32_t r; asm("lop3.b32 %0, %1, %2, %3, %4;" : "=r"(r) : "r"(a), "r"(b), "r"(c), "n"(L)); return r; }
__device__ __forceinline__ void st_async_v2_if(bool p, uint32_t a, uint32_t v0, uint32_t v1, uint32_t mb) {
  asm volatile("{\n.reg .pred q;\nsetp.ne.u32 q, %4, 0;\n@q st.async.weak.shared::cluster.mbarrier::complete_tx::bytes.v2.b32 [%0], {%1,%2}, [%3];\n}"
               :: "r"(a), "r"(v0), "r"(v1), "r"(mb), "r"((uint32_t)p) : "memory"); }
__device__ __forceinline__ void keep4(const uint32_t* r, int lane) {
  asm volatile("{\n.reg .pred q;\nsetp.lt.s32 q, %4, 0;\n@q st.shared.v4.b32 [%4], {%0,%1,%2,%3};\n}" :: "r"(r[0]), "r"(r[1]), "r"(r[2]), "r"(r[3]), "r"(lane) : "memory"); }
__device__ __forceinline__ void fence_sched(int i) {
  asm volatile("{\n.reg .pred q;\nsetp.gt.s32 q, %0, 4096;\n@q st.shared.u32 [%0], 0;\n}" :: "r"(i) : "memory"); }
__device__ __forceinline__ uint32_t hmax2bf(uint32_t a, uint32_t b) { uint32_t r; asm("max.bf16x2 %0, %1, %2;" : "=r"(r) : "r"(a), "r"(b)); return r; }
__device__ __forceinline__ uint32_t uni(uint32_t x) { return __shfl_sync(~0u, x, 0); }
__device__ __forceinline__ void bulk_g2s_mc_e(uint32_t dst, const void* src, uint32_t bytes, uint32_t mb, uint16_t mask) {
  asm volatile("{\n.reg .pred e;\nelect.sync _|e, 0xffffffff;\n"
               "@e cp.async.bulk.shared::cluster.global.mbarrier::complete_tx::bytes.multicast::cluster [%0], [%1], %2, [%3], %4;\n}"
               :: "r"(dst), "l"(src), "r"(bytes), "r"(mb), "h"(mask) : "memory"); }
__device__ __forceinline__ void bulk_s2g_e(void* dst, uint32_t src, uint32_t bytes) {
  asm volatile("{\n.reg .pred e;\nelect.sync _|e, 0xffffffff;\n@e cp.async.bulk.global.shared::cta.bulk_group [%0], [%1], %2;\n}"
               :: "l"(dst), "r"(src), "r"(bytes) : "memory"); }
__device__ __forceinline__ void bulk_g2s_e(uint32_t dst, const void* src, uint32_t bytes, uint32_t mb) {
  asm volatile("{\n.reg .pred e;\nelect.sync _|e, 0xffffffff;\n@e cp.async.bulk.shared::cluster.global.mbarrier::complete_tx::bytes [%0], [%1], %2, [%3];\n}"
               :: "r"(dst), "l"(src), "r"(bytes), "r"(mb) : "memory"); }
#define STREAM_HINT 1
__device__ __forceinline__ void bulk_s2g_es(void* dst, uint32_t src, uint32_t bytes) {
  asm volatile("{\n.reg .pred e;\n.reg .b64 pol;\ncreatepolicy.fractional.L2::evict_first.b64 pol;\nelect.sync _|e, 0xffffffff;\n"
               "@e cp.async.bulk.global.shared::cta.bulk_group.L2::cache_hint [%0], [%1], %2, pol;\n}" :: "l"(dst), "r"(src), "r"(bytes) : "memory");
}
__device__ __forceinline__ void bulk_g2s_es(uint32_t dst, const void* src, uint32_t bytes, uint32_t mb) {
  asm volatile("{\n.reg .pred e;\n.reg .b64 pol;\ncreatepolicy.fractional.L2::evict_first.b64 pol;\nelect.sync _|e, 0xffffffff;\n"
               "@e cp.async.bulk.shared::cluster.global.mbarrier::complete_tx::bytes.L2::cache_hint [%0], [%1], %2, [%3], pol;\n}"
               :: "r"(dst), "l"(src), "r"(bytes), "r"(mb) : "memory"); }
__device__ __forceinline__ void tma2d_e(uint32_t dst, const CUtensorMap* tm, int c0, int c1, uint32_t mb) {
  asm volatile("{\n.reg .pred e;\nelect.sync _|e, 0xffffffff;\n"
               "@e cp.async.bulk.tensor.2d.shared::cluster.global.mbarrier::complete_tx::bytes [%0], [%1, {%3, %4}], [%2];\n}"
               :: "r"(dst), "l"((uint64_t)tm), "r"(mb), "r"(c0), "r"(c1) : "memory"); }
__device__ __forceinline__ uint32_t hadd2bf(uint32_t a, uint32_t b) {
  uint32_t r; asm("add.rn.bf16x2 %0, %1, %2;" : "=r"(r) : "r"(a), "r"(b)); return r; }
__device__ __forceinline__ void cluster_sync_all() {
  asm volatile("barrier.cluster.arrive.release.aligned;\nbarrier.cluster.wait.acquire.aligned;" ::: "memory"); }
__device__ __forceinline__ void bar_arrive(int id, int n) { asm volatile("bar.arrive %0, %1;" :: "r"(id), "r"(n) : "memory"); }
__device__ __forceinline__ void bar_arrive_dep(int id, int n, uint32_t dep) {
  asm volatile("{\n.reg .u32 t;\nand.b32 t, %2, 0;\nadd.u32 t, t, %0;\nbar.sync t, %1;\n}" :: "r"(id), "r"(n), "r"(dep) : "memory"); }
__device__ __forceinline__ void bar_sync(int id, int n) { asm volatile("bar.sync %0, %1;" :: "r"(id), "r"(n) : "memory"); }
__device__ __forceinline__ void fence_async() { asm volatile("fence.proxy.async.shared::cta;" ::: "memory"); }
__device__ __forceinline__ void st_async_b32(uint32_t a, uint32_t v, uint32_t mb) {
  asm volatile("st.async.weak.shared::cluster.mbarrier::complete_tx::bytes.b32 [%0], %1, [%2];" :: "r"(a), "r"(v), "r"(mb) : "memory"); }
__device__ __forceinline__ void st_async_v2(uint32_t a, uint32_t v0, uint32_t v1, uint32_t mb) {
  asm volatile("st.async.weak.shared::cluster.mbarrier::complete_tx::bytes.v2.b32 [%0], {%1,%2}, [%3];" :: "r"(a), "r"(v0), "r"(v1), "r"(mb) : "memory"); }
__device__ __forceinline__ void st_async_v4(uint32_t a, uint32_t v0, uint32_t v1, uint32_t v2, uint32_t v3, uint32_t mb) {
  asm volatile("st.async.weak.shared::cluster.mbarrier::complete_tx::bytes.v4.b32 [%0], {%1,%2,%3,%4}, [%5];" :: "r"(a), "r"(v0), "r"(v1), "r"(v2), "r"(v3), "r"(mb) : "memory"); }
__device__ __forceinline__ void ldsm4(uint32_t& r0, uint32_t& r1, uint32_t& r2, uint32_t& r3, uint32_t a) {
  asm volatile("ldmatrix.sync.aligned.m8n8.x4.shared.b16 {%0,%1,%2,%3}, [%4];" : "=r"(r0), "=r"(r1), "=r"(r2), "=r"(r3) : "r"(a) : "memory"); }
__device__ __forceinline__ void ldsm4t(uint32_t& r0, uint32_t& r1, uint32_t& r2, uint32_t& r3, uint32_t a) {
  asm volatile("ldmatrix.sync.aligned.m8n8.x4.trans.shared.b16 {%0,%1,%2,%3}, [%4];" : "=r"(r0), "=r"(r1), "=r"(r2), "=r"(r3) : "r"(a) : "memory"); }
__device__ __forceinline__ void stsm2t(uint32_t a, uint32_t r0, uint32_t r1) {
  asm volatile("stmatrix.sync.aligned.m8n8.x2.trans.shared.b16 [%0], {%1,%2};" :: "r"(a), "r"(r0), "r"(r1) : "memory"); }
__device__ __forceinline__ void stsm4t(uint32_t a, uint32_t r0, uint32_t r1, uint32_t r2, uint32_t r3) {
  asm volatile("stmatrix.sync.aligned.m8n8.x4.trans.shared.b16 [%0], {%1,%2,%3,%4};" :: "r"(a), "r"(r0), "r"(r1), "r"(r2), "r"(r3) : "memory"); }
__device__ __forceinline__ uint32_t movm(uint32_t a) {
  uint32_t d; asm volatile("movmatrix.sync.aligned.m8n8.trans.b16 %0, %1;" : "=r"(d) : "r"(a)); return d; }
__device__ __forceinline__ void mma16816(float* d, uint32_t a0, uint32_t a1, uint32_t a2, uint32_t a3, uint32_t b0, uint32_t b1) {
  asm("mma.sync.aligned.m16n8k16.row.col.f32.bf16.bf16.f32 {%0,%1,%2,%3}, {%4,%5,%6,%7}, {%8,%9}, {%0,%1,%2,%3};"
               : "+f"(d[0]), "+f"(d[1]), "+f"(d[2]), "+f"(d[3]) : "r"(a0), "r"(a1), "r"(a2), "r"(a3), "r"(b0), "r"(b1)); }
__device__ __forceinline__ void mma16816v(float* d, uint32_t a0, uint32_t a1, uint32_t a2, uint32_t a3, uint32_t b0, uint32_t b1) {
  asm volatile("mma.sync.aligned.m16n8k16.row.col.f32.bf16.bf16.f32 {%0,%1,%2,%3}, {%4,%5,%6,%7}, {%8,%9}, {%0,%1,%2,%3};"
               : "+f"(d[0]), "+f"(d[1]), "+f"(d[2]), "+f"(d[3]) : "r"(a0), "r"(a1), "r"(a2), "r"(a3), "r"(b0), "r"(b1)); }
__device__ __forceinline__ uint32_t pack2(float lo, float hi) {
  uint32_t r; asm("cvt.rn.bf16x2.f32 %0, %1, %2;" : "=r"(r) : "f"(hi), "f"(lo)); return r; }
__device__ __forceinline__ uint32_t pack2v(float lo, float hi) {
  uint32_t r; asm volatile("cvt.rn.bf16x2.f32 %0, %1, %2;" : "=r"(r) : "f"(hi), "f"(lo)); return r; }
__device__ __forceinline__ float bf_lo(uint32_t w) { return __uint_as_float(w << 16); }
__device__ __forceinline__ float bf_hi(uint32_t w) { return __uint_as_float(w & 0xffff0000u); }
__device__ __forceinline__ uint4 lds128(uint32_t a) {
  uint4 v; asm volatile("ld.shared.v4.b32 {%0,%1,%2,%3}, [%4];" : "=r"(v.x), "=r"(v.y), "=r"(v.z), "=r"(v.w) : "r"(a) : "memory"); return v; }
__device__ __forceinline__ uint4 lds128_nv(uint32_t a) {
  uint4 v; asm volatile("ld.shared.v4.b32 {%0,%1,%2,%3}, [%4];" : "=r"(v.x), "=r"(v.y), "=r"(v.z), "=r"(v.w) : "r"(a)); return v; }
__device__ __forceinline__ void st_async_v2_nm(uint32_t a, uint32_t v0, uint32_t v1, uint32_t mb) {
  asm volatile("st.async.weak.shared::cluster.mbarrier::complete_tx::bytes.v2.b32 [%0], {%1,%2}, [%3];" :: "r"(a), "r"(v0), "r"(v1), "r"(mb)); }
__device__ __forceinline__ float rcpf(float x) { float y; asm("rcp.approx.ftz.f32 %0, %1;" : "=f"(y) : "f"(x)); return y; }
__device__ __forceinline__ void sts64(uint32_t a, uint32_t x, uint32_t y) { asm volatile("st.shared.v2.b32 [%0], {%1,%2};" :: "r"(a), "r"(x), "r"(y) : "memory"); }
__device__ __forceinline__ float ex2(float x) { float y; asm("ex2.approx.ftz.f32 %0, %1;" : "=f"(y) : "f"(x)); return y; }
__device__ __forceinline__ uint32_t lds32(uint32_t a) {
  uint32_t v; asm volatile("ld.shared.b32 %0, [%1];" : "=r"(v) : "r"(a) : "memory"); return v; }
__device__ __forceinline__ uint2 lds64(uint32_t a) {
  uint2 v; asm volatile("ld.shared.v2.b32 {%0,%1}, [%2];" : "=r"(v.x), "=r"(v.y) : "r"(a) : "memory"); return v; }
__device__ __forceinline__ void sts128(uint32_t a, uint32_t x, uint32_t y, uint32_t z, uint32_t w) {
  asm volatile("st.shared.v4.b32 [%0], {%1,%2,%3,%4};" :: "r"(a), "r"(x), "r"(y), "r"(z), "r"(w) : "memory"); }
__device__ __forceinline__ void sts32(uint32_t a, uint32_t x) { asm volatile("st.shared.b32 [%0], %1;" :: "r"(a), "r"(x) : "memory"); }
__device__ __forceinline__ void tma2d(uint32_t dst, const CUtensorMap* tm, int c0, int c1, uint32_t mb) {
  asm volatile("cp.async.bulk.tensor.2d.shared::cluster.global.mbarrier::complete_tx::bytes [%0], [%1, {%3, %4}], [%2];"
               :: "r"(dst), "l"((uint64_t)tm), "r"(mb), "r"(c0), "r"(c1) : "memory"); }
__device__ __forceinline__ void tma2d_prefetch(const CUtensorMap* tm, int c0, int c1) {
  asm volatile("cp.async.bulk.prefetch.tensor.2d.L2.global.tile [%0, {%1, %2}];" :: "l"((uint64_t)tm), "r"(c0), "r"(c1) : "memory"); }
__device__ __forceinline__ void bulk_g2s_mc(uint32_t dst, const void* src, uint32_t bytes, uint32_t mb, uint16_t mask) {
  asm volatile("cp.async.bulk.shared::cluster.global.mbarrier::complete_tx::bytes.multicast::cluster [%0], [%1], %2, [%3], %4;"
               :: "r"(dst), "l"(src), "r"(bytes), "r"(mb), "h"(mask) : "memory"); }
__device__ __forceinline__ void bulk_s2g(void* dst, uint32_t src, uint32_t bytes) {
  asm volatile("cp.async.bulk.global.shared::cta.bulk_group [%0], [%1], %2;" :: "l"(dst), "r"(src), "r"(bytes) : "memory"); }
__device__ __forceinline__ void wg_fence() { asm volatile("wgmma.fence.sync.aligned;" ::: "memory"); }
__device__ __forceinline__ void wg_commit() { asm volatile("wgmma.commit_group.sync.aligned;" ::: "memory"); }
template <int N> __device__ __forceinline__ void wg_wait() { asm volatile("wgmma.wait_group.sync.aligned %0;" :: "n"(N) : "memory"); }
__device__ __forceinline__ uint64_t mkdesc(uint32_t addr, uint32_t lbo, uint32_t sbo, uint32_t swz) {
  return (uint64_t)((addr & 0x3FFFF) >> 4) | ((uint64_t)(lbo >> 4) << 16) | ((uint64_t)(sbo >> 4) << 32) | ((uint64_t)swz << 62); }

#define ACC4(d) "+f"(d[0]),"+f"(d[1]),"+f"(d[2]),"+f"(d[3])
#define ACC8(d) ACC4(d), ACC4((d + 4))
#define ACC16(d) ACC8(d), ACC8((d + 8))
#define ACC20(d) ACC16(d), ACC4((d + 16))
#define ACC24(d) ACC16(d), ACC8((d + 16))
#define SMEM0 0x400
__host__ __device__ constexpr uint32_t dlo(uint32_t off, uint32_t lbo) { return ((SMEM0 + off) >> 4) | ((lbo >> 4) << 16); }
__host__ __device__ constexpr uint32_t dhi(uint32_t sbo, uint32_t swz) { return (sbo >> 4) | (swz << 30); }
#define R4S "{%0,%1,%2,%3}"
#define R8S "{%0,%1,%2,%3,%4,%5,%6,%7}"
#define R16S "{%0,%1,%2,%3,%4,%5,%6,%7,%8,%9,%10,%11,%12,%13,%14,%15}"
#define R20S "{%0,%1,%2,%3,%4,%5,%6,%7,%8,%9,%10,%11,%12,%13,%14,%15,%16,%17,%18,%19}"
#define R24S "{%0,%1,%2,%3,%4,%5,%6,%7,%8,%9,%10,%11,%12,%13,%14,%15,%16,%17,%18,%19,%20,%21,%22,%23}"
#define ACC32(d) ACC16(d), ACC16((d + 16))
#define R32S "{%0,%1,%2,%3,%4,%5,%6,%7,%8,%9,%10,%11,%12,%13,%14,%15,%16,%17,%18,%19,%20,%21,%22,%23,%24,%25,%26,%27,%28,%29,%30,%31}"
struct Dsc {
  uint64_t b; uint32_t e;
  __device__ __forceinline__ Dsc operator+(uint32_t o) const { return {b + o, e}; }
};
template <int K> __device__ __forceinline__ uint32_t fresh(int i) {
  uint32_t e; asm volatile("{\n.reg .u32 t;\nadd.u32 t, %1, %2;\nshr.u32 %0, t, %3;\n}" : "=r"(e) : "r"(i), "n"((256 << K) + 1), "n"(8 + K)); return e; }
template <int N, bool H = false> struct MM;
#define DEF_MM(N, H, T, ACCM, RS_, I0, I1, I2, I3, I4, I5, I6, I7)                                                                \
  template <> struct MM<N, H> {                                                                                                   \
    template <uint32_t BLO, int ACC>                                                                                              \
    static __device__ __forceinline__ void rs(float* d, const uint32_t* a, Dsc b0) {                                              \
      asm volatile("{\n.reg .b64 b;\nmad.wide.u32 b, %" #I7 ", %" #I5 ", %" #I4 ";\n"                                             \
                   "wgmma.mma_async.sync.aligned.m64n" #N "k16.f32." T "." T " " RS_ ", {%" #I0 ",%" #I1 ",%" #I2 ",%" #I3 "}, b, %" #I6 ", 1, 1, 0;\n}" \
                   : ACCM(d) : "r"(a[0]), "r"(a[1]), "r"(a[2]), "r"(a[3]), "l"(b0.b), "n"(BLO), "n"(ACC), "r"(b0.e)); }           \
    template <uint32_t ALO, uint32_t BLO, int ACC, int TA = 1>                                                                    \
    static __device__ __forceinline__ void ss(float* d, Dsc a0, Dsc b0) {                                                         \
      asm volatile("{\n.reg .b64 a, b;\nmad.wide.u32 a, %" #I6 ", %" #I1 ", %" #I0 ";\nmad.wide.u32 b, %" #I6 ", %" #I3 ", %" #I2 ";\n" \
                   "wgmma.mma_async.sync.aligned.m64n" #N "k16.f32." T "." T " " RS_ ", a, b, %" #I4 ", 1, 1, %" #I5 ", 0;\n}"    \
                   : ACCM(d) : "l"(a0.b), "n"(ALO), "l"(b0.b), "n"(BLO), "n"(ACC), "n"(TA), "r"(b0.e)); }                         \
  };
DEF_MM(8, false, "bf16", ACC4, R4S, 4, 5, 6, 7, 8, 9, 10, 11)
DEF_MM(16, false, "bf16", ACC8, R8S, 8, 9, 10, 11, 12, 13, 14, 15)
DEF_MM(32, false, "bf16", ACC16, R16S, 16, 17, 18, 19, 20, 21, 22, 23)
DEF_MM(40, false, "bf16", ACC20, R20S, 20, 21, 22, 23, 24, 25, 26, 27)
DEF_MM(48, false, "bf16", ACC24, R24S, 24, 25, 26, 27, 28, 29, 30, 31)
DEF_MM(64, false, "bf16", ACC32, R32S, 32, 33, 34, 35, 36, 37, 38, 39)
DEF_MM(32, true, "f16", ACC16, R16S, 16, 17, 18, 19, 20, 21, 22, 23)
DEF_MM(64, true, "f16", ACC32, R32S, 32, 33, 34, 35, 36, 37, 38, 39)

#define LAG 11
#define NSTEP (NSEG + LAG)
#define NR (NSTEP + 1)
__device__ __align__(1024) __nv_bfloat16 g_xn[2][S_LEN * DM];
#define RO 16
static_assert(RO > LAG + 1, "ring");
__device__ __align__(1024) unsigned char g_o[RO * 96 * 8192];
__device__ __align__(1024) uint32_t g_part[6][7][40][64];
#define RD 16
#define TILE_B 81920
__device__ __align__(1024) float2 g_stat[S_LEN];
__device__ __align__(1024) uint32_t g_st2[2][RD][64];
__device__ __align__(1024) unsigned char g_acc[5][RD][TILE_B];
#define NOP 19
#define NW12 5
#define NW34 12
#define NBC (NOP + NW12 + NW34)
__device__ __align__(1024) unsigned char g_wt[NOP * 10 * 12288];
enum { F_O = 0, F_R1 = NOP + 1, F_R2 = F_R1 + 4, F_R3 = F_R2 + 4, F_Z = F_R3 + 4, F_DONE, F_MISC, F_NUM };
__device__ __align__(128) uint32_t g_f[F_NUM][96];
__device__ __align__(128) int g_xready[129][8];
__device__ uint32_t g_tpc[128];
#define TS(i)
#define TSV(i, v)
#define TSN(i)
#define TSD(i, dep)
#define BTS(k, i)
#define BTS2(k, i)
#define RTS(i)
#define RTSD(i, dep)
#define RTS_OUT()
#define CTS(i)
#define PTS(i)
#define PTS1(i)
#define CTS_OUT()
#define GTS(i)

#define CL_SIZE 15
#define NCL 7
#define SSQ 13
#define SSV 16
#define PL_SZ 5376
#define TILE_SBO 2560
#define TILE_GRP 15360
#define WS_SZ ((2 * SSQ + SSV) * 2048)
#define OFF_QK (OFF_WO + 26 * 2048)
#define LAYOUT 2
#define OFF_TILE 0
#define OFF_WS (4 * TILE_GRP)
#define OFF_WO (OFF_WS + WS_SZ)
#define OFF_PL (OFF_QK + 20480)
#define OFF_BAR (OFF_PL + 2 * PL_SZ)
#define STG_Q OFF_TILE
#define STG_K OFF_WO
#define VA 14
#define STG_V2 (OFF_TILE + 27 * 2048)
#define OFF_O (OFF_PL + 4352)
#define LAND(k) (((k) >> 1) * TILE_GRP + ((k) & 1) * 1280)
#define LAND_F (5 * TILE_SBO)
#define OFF_XL (OFF_TILE + 3 * TILE_GRP)
#define OFF_XF (OFF_XL + LAND_F)
#define OFF_WT ((OFF_XL + TILE_SBO + 1023) & ~1023)
#define OFF_TAB (OFF_BAR + 240)
#define OFF_INV (OFF_TAB + 64)
#define OFF_TS (OFF_INV + 128)
#define A_SMEM 232448
static_assert(WS_SZ + 72 * 1024 + 2 * PL_SZ + 4 * TILE_GRP + 512 == A_SMEM && OFF_WS % 1024 == 0 && OFF_WO % 1024 == 0 && SSQ == 13, "smem map");
enum { B_W0 = 0, B_W1, B_F1, B_F2 = B_F1 + 4, B_R1 = B_F2 + 4, B_R2, B_MEMFREE, B_LANDFREE, B_OPEER, B_PLFREE, B_XFREE, B_SB, B_WOF = B_SB + 6, B_WTF, B_RS, B_NUM = B_RS + 4 };
static_assert(B_NUM <= 30, "barriers");
enum { N_C = 0, N_SISS, N_QK, N_V, N_PM, N_TURN, N_PI, N_VGO, N_O, N_PX, N_AB, N_SDONE, N_VDONE, N_G3, N_P, N_OX };

__device__ __forceinline__ bool is_dual(int j) { return j >= LAG && j < NSEG; }
__device__ __forceinline__ int sched_l(int j) { return j < NSEG ? j : NSEG + j - LAG; }
__device__ __forceinline__ int sched_f(int j) { return NSEG + j - LAG; }
__device__ __forceinline__ void wait_cnt(const int* p, int target) {
  int v, n = 0;
  do {
    asm volatile("ld.relaxed.gpu.global.b32 %0, [%1];" : "=r"(v) : "l"(p) : "memory");
    if (v >= target) break;
    if (++n > SPIN_LIMIT) FAIL();
  } while (true);
  asm volatile("fence.acquire.gpu;" ::: "memory");
  asm volatile("fence.proxy.async.global;" ::: "memory");
}
__device__ __forceinline__ void red_release(void* p, uint32_t v) { asm volatile("red.release.gpu.global.add.u32 [%0], %1;" :: "l"(p), "r"(v) : "memory"); }
__device__ __forceinline__ void red_relaxed(void* p, uint32_t v) { asm volatile("red.relaxed.gpu.global.add.u32 [%0], %1;" :: "l"(p), "r"(v) : "memory"); }
#define VMASK 0xa5294a5294ull
__host__ __device__ constexpr int popc40(unsigned long long m) { int c = 0; for (; m; m &= m - 1) c++; return c; }
static_assert(popc40(VMASK) == SSV, "mask");
__host__ __device__ constexpr int ss_idx(int ks, int n) { return n == SSV ? popc40(VMASK & ((1ull << ks) - 1)) : ks * n / 40; }
__host__ __device__ constexpr bool is_ss(int ks, int n) { return ss_idx(ks + 1, n) != ss_idx(ks, n); }
__host__ __device__ constexpr int rs_idx(int ks, int n) { return ks - ss_idx(ks, n); }

#define SL2 (0.07216878364870322f * 1.4426950408889634f)

#define SUM_LOOP 0
struct Desc { Dsc tile, unit, k1, pl, p; };
__device__ __forceinline__ Desc make_desc(const uint64_t* h, uint32_t u, uint32_t e) {
  return {{h[0], e}, {h[1] + u * 128, e}, {h[2], e}, {h[3], e}, {h[4], e}};
}
template <int N, int NSS, int RG, int KS, int K1, int K0 = 0>
__device__ __forceinline__ void proj(float* acc, const uint32_t* W, const Desc& D) {
  if constexpr (KS < K1) {
    constexpr uint32_t BLO = dlo(OFF_TILE + (KS / 10) * TILE_GRP + RG * TILE_SBO + (KS % 10) * 256, 128);
    if constexpr (is_ss(KS, NSS)) MM<N>::template ss<dlo(OFF_WS + ss_idx(KS, NSS) * 2048, 0), BLO, (KS != K0)>(acc, D.unit, D.tile);
    else MM<N>::template rs<BLO, (KS != K0)>(acc, W + rs_idx(KS, NSS) * 4, D.tile);
    proj<N, NSS, RG, KS + 1, K1, K0>(acc, W, D);
  }
}
#define VST 17
template <int KS>
__device__ __forceinline__ void ld_rest(uint32_t* W, const uint32_t* p) {
  if constexpr (KS < 40) {
    if constexpr (!is_ss(KS, SSV) && rs_idx(KS, SSV) >= VST) {
#pragma unroll
      for (int i = 0; i < 4; i++) W[4 * rs_idx(KS, SSV) + i] = __ldg(p + (KS * 16 + (i >> 1) * 8) * (HD / 2) + (i & 1) * 4);
    }
    ld_rest<KS + 1>(W, p);
  }
}
template <int N>
__device__ __forceinline__ void load_w(uint32_t* W, uint32_t stage, int warp, int lane) {
  const int kr = (lane >> 4) * 8 + (lane & 7);
  const int cb = warp * 2 + ((lane >> 3) & 1);
  const uint32_t a0 = stage + kr * 128 + ((cb ^ (lane & 7)) << 4);
#pragma unroll
  for (int i = 0; i < N; i++) ldsm4t(W[4 * i], W[4 * i + 1], W[4 * i + 2], W[4 * i + 3], a0 + i * 2048);
}
template <int N, int G, int U, int OS, int ACC>
__device__ __forceinline__ void wo4(float* d, const Desc& D) {
  constexpr uint32_t WA = (U >= 4 ? OFF_WO + (U - 4) * 2048 : OFF_WT) - G * SSQ * 2048, OB = OS == 0 ? OFF_O : OS == 1 ? OFF_XL : OFF_XF;
  Dsc b = OS ? D.k1 : D.pl;
  b.e = fresh<(U < 16 ? U / 4 : U / 8 - 2) + (N == 8 ? 4 : 0)>(D.unit.e);
  MM<N>::template ss<dlo(WA, 0), dlo(OB, 128), ACC>(d, D.unit, b);
  MM<N>::template ss<dlo(WA + 2048, 0), dlo(OB + 256, 128), 1>(d, D.unit, b);
  MM<N>::template ss<dlo(WA + 4096, 0), dlo(OB + 512, 128), 1>(d, D.unit, b);
  MM<N>::template ss<dlo(WA + 6144, 0), dlo(OB + 768, 128), 1>(d, D.unit, b);
}
__device__ __forceinline__ void wo_coord(int i, int t3, int head, int& c0, int& c1) {
  const int g = i >> 1;
  const int blk = g == 0 ? 9 : (g < 4 ? g - 1 : (g - 4) >> 1) * 3 + t3;
  int sl = g < 4 ? t3 : (g & 1) ? t3 + 1 : t3 + 2;
  if (sl >= 3) sl -= 3;
  c0 = blk * 64; c1 = head * DH + sl * 64 + (i & 1) * 32;
}
__device__ __forceinline__ void tok_softmax(uint32_t sb, int job, int lane) {
  const bool w1 = job & 1;
  const int dg = (lane >> 2) - (lane & 3) * 2;
  const uint32_t lo = sb + OFF_PL + (job >> 1) * PL_SZ + (job & 1) * 1792, l8 = lo + 512 + lane * 8, pa = lo + lane * 4;
  const uint32_t km = job & 2 ? 640 : 512;
  float x[14];
  {
    const uint4 a = lds128(lo + lane * 16);
    const uint2 e = lds64(l8);
    const uint32_t c = lds32(768 + pa);
    x[0] = bf_lo(a.x); x[1] = bf_hi(a.x); x[2] = bf_lo(a.y); x[3] = bf_hi(a.y); x[4] = bf_lo(a.z); x[5] = bf_hi(a.z); x[6] = bf_lo(a.w); x[7] = bf_hi(a.w);
    x[8] = bf_lo(c); x[9] = bf_hi(c); x[10] = bf_lo(e.x); x[11] = bf_hi(e.x); x[12] = bf_lo(e.y); x[13] = bf_hi(e.y);
  }
  if (dg < 0) { x[8] = -INFINITY; if (w1) x[4] = -INFINITY; else x[10] = -INFINITY; }
  if (dg < 1) { x[9] = -INFINITY; if (w1) x[5] = -INFINITY; else x[11] = -INFINITY; }
  const float m4 = fmaxf(x[8], x[9]);
  float m0 = fmaxf(fmaxf(fmaxf(x[0], x[1]), fmaxf(x[2], x[3])), fmaxf(fmaxf(x[4], x[5]), fmaxf(x[6], x[7])));
  float m1 = fmaxf(fmaxf(x[10], x[11]), fmaxf(x[12], x[13]));
  if (w1) m1 = fmaxf(m1, m4); else m0 = fmaxf(m0, m4);
  m0 = fmaxf(m0, __shfl_xor_sync(~0u, m0, 1)); m1 = fmaxf(m1, __shfl_xor_sync(~0u, m1, 1));
  sts32(pa + (w1 ? 384 : 896 + 128), 0u); sts32(pa + 1152 - km, 0u); sts32(pa + 896 + 1152 - km, 0u); sts64(l8 + 896 - 256, 0u, 0u);
  m0 = fmaxf(m0, __shfl_xor_sync(~0u, m0, 2)); m1 = fmaxf(m1, __shfl_xor_sync(~0u, m1, 2));
  m0 *= -SL2; m1 *= -SL2;
#pragma unroll
  for (int j = 0; j < 14; j++) x[j] = ex2(fmaf(x[j], SL2, j < 8 ? m0 : j >= 10 ? m1 : w1 ? m1 : m0));
  const float l4s = x[8] + x[9];
  float l0 = ((x[0] + x[1]) + (x[2] + x[3])) + ((x[4] + x[5]) + (x[6] + x[7])), l1 = (x[10] + x[11]) + (x[12] + x[13]);
  if (w1) l1 += l4s; else l0 += l4s;
  l0 += __shfl_xor_sync(~0u, l0, 1); l1 += __shfl_xor_sync(~0u, l1, 1);
  l0 += __shfl_xor_sync(~0u, l0, 2); l1 += __shfl_xor_sync(~0u, l1, 2);
  l0 = rcpf(l0); l1 = rcpf(l1);
#pragma unroll
  for (int j = 0; j < 7; j++) {
    const float iv = j < 4 ? l0 : j > 4 ? l1 : w1 ? l1 : l0;
    sts32(pa + (j < 3 ? j * 128 : j == 3 ? km : j == 4 ? (w1 ? 896 + 128 : 384) : j == 5 ? 896 : 896 + km), pack2(x[2 * j] * iv, x[2 * j + 1] * iv));
  }
}
template <int N>
__device__ __forceinline__ void wo_phase(uint32_t sb, int wg, int warp, int lane, uint32_t par, uint32_t r1, const Desc& D) {
  const uint32_t bar = sb + OFF_BAR;
  float x[N / 2], y[N / 2];
  const uint2 ta = lds64(sb + OFF_TAB + (wg * 4 + warp) * 8);
  uint32_t xa = (ta.x & ~255u) + lane * 8, xb = (ta.x & 0xFF0000FFu) + SMEM0 + OFF_BAR, ya = (ta.y & ~255u) + lane * 8, yb = (ta.y & 0xFF0000FFu) + SMEM0 + OFF_BAR;
  asm volatile("" : "+r"(xa), "+r"(xb), "+r"(ya), "+r"(yb));
  auto scat = [&](uint32_t ad, uint32_t mb, const float* d) {
    st_async_v2(ad, pack2(d[0], d[1]), pack2(d[2], d[3]), mb);
    if (N == 16) st_async_v2(ad + LAND_F, pack2(d[4], d[5]), pack2(d[6], d[7]), mb);
  };
  if (wg == 0) {
    bar_sync(N_O, 384);
    wg_fence(); wo4<N, 0, 4, 0, 0>(x, D); wo4<N, 0, 8, 0, 0>(y, D); wg_commit();
    mbar_waitu(bar + 8 * B_OPEER, par);
    CFENCE(); wg_fence(); wo4<N, 0, 16, 1, 1>(x, D); wo4<N, 0, 20, 2, 1>(x, D); wg_commit();
    wo4<N, 0, 24, 1, 1>(y, D); wg_commit();
    mbar_waitu2(bar + 8 * B_WOF, bar + 8 * B_MEMFREE, par);
    wg_fence(); wo4<N, 0, 28, 2, 1>(y, D); wg_commit();
    bar_arrive(N_AB, 256);
    wg_wait<2>(); scat(xa, xb, x);
    wg_wait<0>(); scat(ya, yb, y);
  } else {
    bar_sync(N_O, 384);
    wg_fence(); wo4<N, 1, 0, 0, 0>(x, D); wg_commit(); wo4<N, 1, 12, 0, 0>(y, D); wg_commit();
    wg_wait<1>(); mbar_arrive_remote_if(lane == 0, r1);
    mbar_waitu(bar + 8 * B_MEMFREE, par);
    scat(xa, xb, x);
    bar_sync(N_AB, 256);
    CFENCE(); wg_fence(); wo4<N, 1, 32, 1, 1>(y, D); wo4<N, 1, 36, 2, 1>(y, D); wg_commit();
    bar_arrive(N_TURN, 256);
    wg_wait<0>(); scat(ya, yb, y);
  }
}
#define DS_DUAL 10
#define DS_SINGLE 20
#define POLL_GAP 100
#define POLL_GAPD 0
#define TOK_DELAY 250
#define LATE_SM 1
#define UMAX 40
#define VD1 10
#define VS2 20
#define IG_V 3
#define VS1 4
struct AMaps { CUtensorMap w16[3], wo32; uint64_t d[5]; const __nv_bfloat16* wv; };
__global__ void __launch_bounds__(512, 1)
acore_kernel(const __grid_constant__ AMaps M, const __nv_bfloat16* __restrict__ mem0, int sync_b) {
  extern __shared__ __align__(1024) unsigned char smem_raw[];
  const uint32_t sb = smem_u32(smem_raw);
  GTS(24);
  if (threadIdx.x == 480) {
    uint32_t smid; asm volatile("mov.u32 %0, %%smid;" : "=r"(smid));
    g_tpc[(smid >> 1) & 127] = blockIdx.x - CL_SIZE < 3 * CL_SIZE && blockIdx.x % CL_SIZE >= 12 ? 1 : 2;
    asm volatile("griddepcontrol.launch_dependents;");
  }
  const int lane0 = threadIdx.x & 31;
#define LANE_INIT() int lane; asm volatile("mov.u32 %0, %%laneid;" : "=r"(lane))
  const int warp = __shfl_sync(~0u, (threadIdx.x >> 5) & 3, 0);
  const int cl = blockIdx.x / CL_SIZE;
  const uint32_t rank = blockIdx.x - cl * CL_SIZE;
  const int nh = cl >= 1 && cl <= 3 ? 4 : 5;
  const int nA = 3 * nh;
  const int wg = __shfl_sync(~0u, (int)rank < nA ? threadIdx.x >> 7 : 4, 0);
  const int head = (cl < 4 ? (cl ? 1 + 4 * cl : 0) : 5 * cl - 3) + rank / 3;
  const int t3 = rank % 3;
  const int col0 = head * DH + t3 * 64;
  const uint32_t bar = sb + OFF_BAR;
  const uint32_t rb0 = SMEM0;
  const uint16_t mcmask = (uint16_t)((1u << nA) - 1);
  const uint32_t nxt = sb + ((t3 == 2 ? -2 : 1) << 24), prv = sb + ((t3 == 0 ? 2 : -1) << 24);
  const int ig = (int)rank - (nA - 4);

  if (threadIdx.x == 0) {
    if (mapa(sb, nA - 1) != rb0 + ((nA - 1) << 24) || mapa(sb, 0) != rb0 || mapa(sb, 1) != rb0 + (1u << 24) || sb != SMEM0 + (rank << 24)) FAIL();
    for (int i = 0; i < B_NUM; i++)
      mbar_init(bar + 8 * i, i == B_R1 ? 4 * nA : i == B_R2 ? 12 * nA : i == B_MEMFREE ? nA : i == B_LANDFREE ? 4 * nA : i == B_PLFREE || i == B_XFREE ? 2 : 1);
    asm volatile("fence.mbarrier_init.release.cluster;" ::: "memory");
    mbar_expect(bar + 8 * B_W0, (80 + SSV + VST) * 2048);
  }
  __syncthreads();
  if (lane0 == 0) {
    const int w12 = wg * 4 + warp;
    if (w12 < 10) {
#pragma unroll 1
      for (int ks = 4 * w12; ks < 4 * w12 + 4; ks++) {
        const bool ss = is_ss(ks, SSQ);
        tma2d(ss ? sb + OFF_WS + ss_idx(ks, SSQ) * 2048 : sb + STG_Q + rs_idx(ks, SSQ) * 2048, &M.w16[0], col0, ks * 16, bar + 8 * B_W0);
        tma2d(ss ? sb + OFF_WS + (SSQ + ss_idx(ks, SSQ)) * 2048 : sb + STG_K + rs_idx(ks, SSQ) * 2048, &M.w16[1], col0, ks * 16, bar + 8 * B_W0);
        if (is_ss(ks, SSV)) tma2d(sb + OFF_WS + (2 * SSQ + ss_idx(ks, SSV)) * 2048, &M.w16[2], col0, ks * 16, bar + 8 * B_W0);
        else if (rs_idx(ks, SSV) < VST) tma2d(sb + (rs_idx(ks, SSV) < VA ? STG_K + 27 * 2048 : STG_V2 - VA * 2048) + rs_idx(ks, SSV) * 2048, &M.w16[2], col0, ks * 16, bar + 8 * B_W0);
      }
    }
  }
  if (lane0 < 2 && wg < 2) {
    const int u = 4 * (wg ? (lane0 ? 6 + t3 : 9) : (lane0 ? 3 + t3 : t3)) + warp;
    const int li = (u >= nA) + (u >= 2 * nA) + (u >= 3 * nA);
    sts32(sb + OFF_TAB + (wg * 4 + warp) * 8 + lane0 * 4,
          rb0 + ((u - li * nA) << 24) + OFF_TILE + LAND(li + (u >= 36 ? t3 : 0)) + (rank / 3) * 256 + 8 * (B_RS + li));
  }
  __syncthreads();
  GTS(25);

  auto issue_tok = [&](int sc, int fb, int rel = -1, uint32_t ph = 0) {
    if (sync_b) wait_cnt(&g_xready[sc][0], 32);
    if (rel >= 0) mbar_waitu(bar + 8 * rel, ph);
    bulk_g2s_mc_e(sb + OFF_TILE + ig * TILE_GRP + TILE_SBO, &g_xn[0][0] + uni(sc * (32 * DM)) + ig * 5120, 10240, bar + 8 * (fb + ig), mcmask);
  };
#define POLL(d, q) _Pragma("unroll") for (int k = 0; k < NCL; k++) \
      asm volatile("ld.relaxed.gpu.global.v2.b32 {%0,%1}, [%2];" : "=r"(d[k].x), "=r"(d[k].y) : "l"(q + k * 2560) : "memory")
#define L3(L, a, b, c) lop3<L>(a, b, c)
#define TAGS(L, d) L3(L, L3(L, L3(L, d[0].x, d[0].y, d[1].x), L3(L, d[1].y, d[2].x, d[2].y), L3(L, d[3].x, d[3].y, d[4].x)), L3(L, d[4].y, d[5].x, d[5].y), L3(L, d[6].x, d[6].y, d[6].y))
    auto deliver = [&](uint2* pa, const uint32_t* gq, int u, int c, int dc, int ds, int step, bool first, int lane) {
      const uint32_t off = uni(OFF_TILE + ((u * 205) >> 11) * (TILE_GRP - TILE_SBO) + u * 256 + dc * LAND_F), boff = uni(OFF_BAR + 8 * (B_F1 + ((u * 205) >> 11)));
      const uint32_t* mi = &g_part[4][0][0][0] + uni((c * NCL + cl) * 2560 + u * 64);
      mbar_waitu(bar + 8 * B_LANDFREE, step & 1);
      int n = 0;
      while (true) {
        const bool ok = __all_sync(~0u, ((step & 2 ? ~TAGS(0xFE, pa) : TAGS(0x80, pa)) & 1) != 0);
        if (ok) break;
        if (++n > SPIN_LIMIT) FAIL();
        POLL(pa, gq);
      }
      if (warp == 0 && first) { TS(19); TSV(10, n); }
      const uint32_t w0 = hadd2bf(hadd2bf(hadd2bf(pa[0].x, pa[1].x), hadd2bf(pa[2].x, pa[3].x)), hadd2bf(hadd2bf(pa[4].x, pa[5].x), pa[6].x));
      const uint32_t w1 = hadd2bf(hadd2bf(hadd2bf(pa[0].y, pa[1].y), hadd2bf(pa[2].y, pa[3].y)), hadd2bf(hadd2bf(pa[4].y, pa[5].y), pa[6].y));
      if (u < ds) {
        const uint32_t da = SMEM0 + off + lane * 8, db = SMEM0 + boff;
#pragma unroll
        for (int d = 0; d < 12; d++) st_async_v2((d << 24) + da, w0, w1, (d << 24) + db);
#pragma unroll
        for (int d = 12; d < 15; d++) st_async_v2_if(nA == 15, (d << 24) + da, w0, w1, (d << 24) + db);
      } else {
        *reinterpret_cast<uint2*>(const_cast<uint32_t*>(gq) + ((4 - 2 * (step & 1)) * NCL + cl) * 2560) = make_uint2(w0, w1);
        asm volatile("fence.proxy.async.global;" ::: "memory");
        __syncwarp();
        bulk_g2s_mc_e(sb + off, mi, 256, sb + boff, mcmask);
      }
    };
#define REL(b, g) mbar_arrive_remote_if(lane == 0, rb0 + ((nA - 4 + (g)) << 24) + OFF_BAR + 8 * (b))

  if (wg < 2) {
    asm volatile("setmaxnreg.inc.sync.aligned.u32 160;");
    LANE_INIT();
    uint32_t W[4 * (40 - SSQ)];
    mbar_waitw(bar + 8 * B_W0, 0);
    GTS(26);
    load_w<40 - SSQ>(W, sb + (wg ? STG_K : STG_Q), warp, lane);
    fence_async();
    bar_sync(1, 384);
    cluster_sync_all();
#define DESC(k) const Desc D = make_desc(M.d, min(wg, 2) * SSQ, fresh<k>(step))
    GTS(27);
#pragma unroll 1
    for (int step = -1; step < NSTEP; step++) {
      const uint32_t par = step & 1;
      asm volatile("" : "+r"(lane));
      const bool dual = is_dual(step), has_next = step + 1 < NSTEP;
#define QK_SA (sb + OFF_QK + wg * 15360 + (2 * warp + ((lane >> 3) & 1)) * 128 + (lane & 7) * 16)
#define QK_F (wg ? -5120 : 5120)
#define QK_S12 ((wg ? (lane >> 4) : 1 + 2 * (lane >> 4)) * 1024)
#define QK_S34 ((wg ? 2 + (lane >> 4) : 2 - 2 * (lane >> 4)) * 1024)
      if (step >= 0) {
        if (dual) {
          DESC(0);
          float acc[24];
          mbar_waitu(bar + 8 * (B_F1 + 0), par);
          if (wg + warp == 0) { TS(0); TSN(1); }
          CFENCE(); wg_fence(); proj<48, SSQ, 0, 0, 10>(acc, W, D); wg_commit();
          mbar_waitu(bar + 8 * (B_F1 + 1), par);
          CFENCE(); wg_fence(); proj<48, SSQ, 0, 10, 20>(acc, W, D); wg_commit();
          mbar_waitu(bar + 8 * (B_F1 + 2), par);
          CFENCE(); wg_fence(); proj<48, SSQ, 0, 20, 30>(acc, W, D); wg_commit();
          mbar_waitu(bar + 8 * (B_F1 + 3), par);
          if (wg + warp == 0) TS(2);
          CFENCE(); wg_fence(); proj<48, SSQ, 0, 30, 40>(acc, W, D); wg_commit();
          bar_arrive(N_VGO, 384);
          mbar_waitu(bar + 8 * B_PLFREE, par);
          const uint32_t sa = QK_SA, s0 = sa + 4096 + (lane >> 4) * QK_F, s1 = sa + QK_F + QK_S12, s2 = sa + QK_F + QK_S34;
          wg_wait<0>();
          if (wg + warp == 0) TS(3);
          stsm4t(s0, pack2(acc[0], acc[1]), pack2(acc[2], acc[3]), pack2(acc[20], acc[21]), pack2(acc[22], acc[23]));
          stsm4t(s1, pack2(acc[4], acc[5]), pack2(acc[6], acc[7]), pack2(acc[8], acc[9]), pack2(acc[10], acc[11]));
          stsm4t(s2, pack2(acc[12], acc[13]), pack2(acc[14], acc[15]), pack2(acc[16], acc[17]), pack2(acc[18], acc[19]));
        } else {
          DESC(1);
          float acc[4];
          mbar_waitu(bar + 8 * (B_F1 + 0), par);
          if (wg + warp == 0) { TS(0); TSN(1); }
          CFENCE(); wg_fence(); proj<8, SSQ, 0, 0, 10>(acc, W, D); wg_commit();
          mbar_waitu(bar + 8 * (B_F1 + 1), par);
          CFENCE(); wg_fence(); proj<8, SSQ, 0, 10, 20>(acc, W, D); wg_commit();
          mbar_waitu(bar + 8 * (B_F1 + 2), par);
          CFENCE(); wg_fence(); proj<8, SSQ, 0, 20, 30>(acc, W, D); wg_commit();
          mbar_waitu(bar + 8 * (B_F1 + 3), par);
          if (wg + warp == 0) TS(2);
          CFENCE(); wg_fence(); proj<8, SSQ, 0, 30, 40>(acc, W, D); wg_commit();
          bar_arrive(N_VGO, 384);
          mbar_waitu(bar + 8 * B_PLFREE, par);
          const uint32_t s0 = QK_SA + 4096;
          wg_wait<0>();
          if (wg + warp == 0) TS(3);
          stsm2t(s0, pack2(acc[0], acc[1]), pack2(acc[2], acc[3]));
        }
        fence_async();
        bar_sync(N_QK, 256);
        if (wg == 0 || dual) {
          float s[20];
          DESC(2);
          const Dsc ab = D.k1 + wg * 192, bb = D.k1 + (1 - wg) * 320;
          wg_fence();
          MM<40>::ss<dlo(OFF_QK, 128), dlo(OFF_QK + 10240, 128), 0, 0>(s, ab, bb);
          MM<40>::ss<dlo(OFF_QK + 256, 128), dlo(OFF_QK + 10240 + 256, 128), 1, 0>(s, ab, bb);
          MM<40>::ss<dlo(OFF_QK + 512, 128), dlo(OFF_QK + 10240 + 512, 128), 1, 0>(s, ab, bb);
          MM<40>::ss<dlo(OFF_QK + 768, 128), dlo(OFF_QK + 10240 + 768, 128), 1, 0>(s, ab, bb);
          wg_commit();
          bar_arrive(N_SISS, 384);
          const int rw = (warp - wg) & 3;
          const uint32_t bo = OFF_BAR + 8 * (B_SB + 3 * wg + rw), lo = OFF_PL + wg * PL_SZ + rw * 1792;
          const uint32_t km = wg ? 640 : 512;
          uint32_t l16 = lo + lane * 16, l4 = lo + lane * 4;
          mbar_expect_if(lane == 0 && rw < 3, sb + bo, rw < 2 ? 1792 : 1280);
          asm volatile("" : "+r"(l16), "+r"(l4));
          if (rw == 2) {
            wg_wait<0>();
            if (wg == 0) TSD(4, __float_as_uint(s[0]));
            const uint32_t w0 = pack2(s[0], s[1]), w1 = pack2(s[4], s[5]), w2 = pack2(s[8], s[9]), w3 = pack2(s[12], s[13]), w4 = pack2(s[16], s[17]);
            {
              st_async_v4(nxt + 896 + l16, w0, w1, w2, w3, nxt + bo);
              st_async_v4(prv + l16, w0, w1, w2, w3, prv + bo);
              st_async_b32(nxt + 896 + 768 + l4, w4, nxt + bo);
              st_async_b32(prv + 768 + l4, w4, prv + bo);
            }
            bar_arrive(N_SDONE, 256);
            mbar_waitu(sb + bo, (step - wg * LAG) & 1);
            if (wg == 0) TS(5);
            float x[10], m0;
            {
              const uint4 a = lds128(sb + l16), b = lds128(sb + 896 + l16);
              const uint32_t c = lds32(sb + 768 + l4), d = lds32(sb + 896 + 768 + l4);
              const uint32_t e0 = hadd2bf(hadd2bf(a.x, b.x), w0), e1 = hadd2bf(hadd2bf(a.y, b.y), w1), e2 = hadd2bf(hadd2bf(a.z, b.z), w2),
                             e3 = hadd2bf(hadd2bf(a.w, b.w), w3), e4 = hadd2bf(hadd2bf(c, d), w4);
              const uint32_t em = hmax2bf(hmax2bf(hmax2bf(e0, e1), hmax2bf(e2, e3)), e4);
              m0 = fmaxf(bf_lo(em), bf_hi(em));
              x[0] = bf_lo(e0); x[1] = bf_hi(e0); x[2] = bf_lo(e1); x[3] = bf_hi(e1); x[4] = bf_lo(e2);
              x[5] = bf_hi(e2); x[6] = bf_lo(e3); x[7] = bf_hi(e3); x[8] = bf_lo(e4); x[9] = bf_hi(e4);
            }
            m0 = fmaxf(m0, __shfl_xor_sync(~0u, m0, 1));
            sts32(sb + l4 + 1152 - km, 0u);
            m0 = fmaxf(m0, __shfl_xor_sync(~0u, m0, 2));
            m0 *= -SL2;
#pragma unroll
            for (int j = 0; j < 5; j++) {
              x[2 * j] = ex2(fmaf(x[2 * j], SL2, m0)); x[2 * j + 1] = ex2(fmaf(x[2 * j + 1], SL2, m0));
              sts32(sb + l4 + (j < 4 ? j * 128 : km), pack2(x[2 * j], x[2 * j + 1]));
            }
            float l = ((x[0] + x[1]) + (x[2] + x[3])) + ((x[4] + x[5]) + ((x[6] + x[7]) + (x[8] + x[9])));
            l += __shfl_xor_sync(~0u, l, 1);
            fence_async();
            sts32(sb + OFF_INV + wg * 64 + (lane >> 1) * 4, __float_as_uint(l));
            bar_arrive(N_PM, dual ? 224 : 192);
            if (wg == 0) TS(6);
          } else if (rw < 2) {
            const bool w1 = rw == 1;
            const uint32_t l8 = lo + 512 + lane * 8;
            uint32_t tw[7];
            wg_wait<0>();
            bar_arrive(N_SDONE, 256);
            tw[0] = pack2(s[0], s[1]); tw[1] = pack2(s[4], s[5]); tw[2] = pack2(s[8], s[9]); tw[3] = pack2(s[16], s[17]);
            tw[4] = w1 ? pack2(s[6], s[7]) : pack2(s[12], s[13]); tw[5] = pack2(s[2], s[3]); tw[6] = pack2(s[18], s[19]);
            { const uint32_t t0 = clock32(); while (clock32() - t0 < TOK_DELAY) {} }
            st_async_v4(nxt + 896 + l16, tw[0], tw[1], tw[2], tw[3], nxt + bo);
            st_async_v4(prv + l16, tw[0], tw[1], tw[2], tw[3], prv + bo);
            st_async_v2(nxt + 896 + l8, tw[5], tw[6], nxt + bo);
            st_async_v2(prv + l8, tw[5], tw[6], prv + bo);
            st_async_b32(nxt + 896 + 768 + l4, tw[4], nxt + bo);
            st_async_b32(prv + 768 + l4, tw[4], prv + bo);
            mbar_waitu(sb + bo, (step - wg * LAG) & 1);
            const uint4 a = lds128(sb + l16), b = lds128(sb + 896 + l16);
            const uint2 e = lds64(sb + l8), f = lds64(sb + 896 + l8);
            const uint32_t c = lds32(sb + 768 + l4), d = lds32(sb + 896 + 768 + l4);
            sts128(sb + l16, hadd2bf(hadd2bf(a.x, b.x), tw[0]), hadd2bf(hadd2bf(a.y, b.y), tw[1]), hadd2bf(hadd2bf(a.z, b.z), tw[2]), hadd2bf(hadd2bf(a.w, b.w), tw[3]));
            sts64(sb + l8, hadd2bf(hadd2bf(e.x, f.x), tw[5]), hadd2bf(hadd2bf(e.y, f.y), tw[6]));
            sts32(sb + 768 + l4, hadd2bf(hadd2bf(c, d), tw[4]));
            bar_arrive(N_PX, dual ? 256 : 192);
            if (wg + warp == 0) TS(9);
          } else {
            wg_wait<0>();
            if (wg == 0) {
              mbar_expect_if(lane < 3 && has_next, bar + 8 * (lane == 2 ? B_OPEER : B_WOF + lane), lane == 2 ? (dual ? 4096 : 2048) : lane ? 8192 : 20480);
              auto fetch = [&](int i, int n, uint32_t dst, int mb) {
                int c0, c1; wo_coord(i, t3, head, c0, c1);
                tma2d_e(dst, &M.wo32, c0, c1, bar + 8 * mb); if (n == 2) tma2d_e(dst + 4096, &M.wo32, c0, c1 + 32, bar + 8 * mb);
              };
              bar_sync(N_G3, 160);
              if (has_next) {
                fetch(0, 2, sb + OFF_WT, B_WTF);
                mbar_arrive_remote_if(lane < 2, (lane ? nxt : prv) + OFF_BAR + 8 * B_XFREE);
              }
              bar_sync(N_SDONE, 256);
              if (has_next) {
                fetch(15, 1, sb + OFF_QK, B_WOF); fetch(16, 2, sb + OFF_QK + 4096, B_WOF); fetch(18, 2, sb + OFF_QK + 12288, B_WOF);
                mbar_waitu(bar + 8 * B_XFREE, par);
              }
              bar_arrive(N_PM, dual ? 224 : 192);
              bar_sync(N_VDONE, 160);
              mbar_arrive_remote_if(lane < nA && has_next, rb0 + (lane << 24) + OFF_BAR + 8 * B_MEMFREE);
              if (has_next) mbar_waitu(bar + 8 * B_WTF, par);
            } else {
              bar_arrive(N_SDONE, 256);
              if ((unsigned)ig < IG_V) issue_tok(sched_l(step + 1), B_F2, B_R1, (step - LAG) & 1);
            }
          }
        } else {
          bar_arrive(N_SISS, 384);
          bar_arrive(N_SDONE, 256);
        }
        if (has_next) {
          if (step == 0) mbar_waitw(bar + 8 * B_W1, 0);
          const uint32_t r1 = rb0 + ((nA - 1) << 24) + OFF_BAR + 8 * B_R1;
          if (dual) { DESC(3); wo_phase<16>(sb, wg, warp, lane, par, r1, D); } else { DESC(4); wo_phase<8>(sb, wg, warp, lane, par, r1, D); }
          bar_arrive(N_C, 288);
          if (warp == 0) TS(7 + wg);
        }
      }
      if (has_next) {
        DESC(5);
        float acc[16];
        mbar_waitu(bar + 8 * B_F2, par ^ 1);
        wg_fence(); proj<32, SSQ, 1, 0, 10>(acc, W, D); wg_commit();
        mbar_waitu(bar + 8 * (B_F2 + 1), par ^ 1);
        wg_fence(); proj<32, SSQ, 1, 10, 14>(acc, W, D); wg_commit();
        wg_wait<1>(); REL(B_R2, 0);
        wg_fence(); proj<32, SSQ, 1, 14, 20>(acc, W, D); wg_commit();
        mbar_waitu(bar + 8 * (B_F2 + 2), par ^ 1);
        wg_fence(); proj<32, SSQ, 1, 20, 24>(acc, W, D); wg_commit();
        wg_wait<1>(); REL(B_R2, 1);
        wg_fence(); proj<32, SSQ, 1, 24, 30>(acc, W, D); wg_commit();
        mbar_waitu(bar + 8 * (B_F2 + 3), par ^ 1);
        wg_fence(); proj<32, SSQ, 1, 30, 34>(acc, W, D); wg_commit();
        wg_wait<1>(); REL(B_R2, 2);
        wg_fence(); proj<32, SSQ, 1, 34, 40>(acc, W, D); wg_commit();
        const uint32_t sa = QK_SA, s1 = sa + QK_S12, s2 = sa + QK_S34;
        wg_wait<0>(); REL(B_R2, 3);
        if (warp == 0) TS(11 + wg);
        stsm4t(s1, pack2(acc[0], acc[1]), pack2(acc[2], acc[3]), pack2(acc[4], acc[5]), pack2(acc[6], acc[7]));
        stsm4t(s2, pack2(acc[8], acc[9]), pack2(acc[10], acc[11]), pack2(acc[12], acc[13]), pack2(acc[14], acc[15]));
      }
    }
    GTS(28);
    cluster_sync_all();
  } else if (wg == 2) {
    asm volatile("setmaxnreg.inc.sync.aligned.u32 160;");
    LANE_INIT();
    uint32_t W[4 * (40 - SSV)];
    ld_rest<0>(W, reinterpret_cast<const uint32_t*>(M.wv + (lane >> 2) * HD + col0 + warp * 16) + (lane & 3));
    uint4 m0[5];
#pragma unroll
    for (int i = 0; i < 5; i++) {
      const int t = i * 128 + warp * 32 + lane;
      m0[i] = __ldg(reinterpret_cast<const uint4*>(mem0 + ((t >> 1) & 7) * DM + (t >> 4) * 16 + ((t ^ (t >> 3)) & 1) * 8));
    }
    mbar_waitw(bar + 8 * B_W0, 0);
    load_w<VA>(W, sb + STG_K + 27 * 2048, warp, lane);
    load_w<VST - VA>(W + 4 * VA, sb + STG_V2, warp, lane);
    fence_async();
    mbar_expect_if(warp + lane == 0, bar + 8 * B_W1, 26 * 2048);
    bar_sync(1, 384);
#pragma unroll
    for (int i = 0; i < 5; i++) {
      const int t = i * 128 + warp * 32 + lane;
      sts128(sb + OFF_TILE + (t / 160) * (TILE_GRP - TILE_SBO) + t * 16, m0[i].x, m0[i].y, m0[i].z, m0[i].w);
    }
#pragma unroll
    for (int i = 4 * VST; i < 4 * (40 - SSV); i++) W[i] = movm(W[i]);
    fence_async();
    mbar_arrive_if(lane == 0, bar + 8 * (B_F1 + warp));
    mbar_expect_if(lane == 0, bar + 8 * (B_F2 + warp), 10240);
    mbar_arrive_if(warp == 3 && lane < 2, bar + 8 * B_PLFREE);
    cluster_sync_all();
    uint32_t vl[8];
    {
      const int step = warp;
      DESC(0);
      float v[16];
      mbar_waitw4(bar + 8 * B_F2, 0);
      wg_fence(); proj<32, SSV, 1, 0, 40>(v, W, D); wg_commit();
      wg_wait<0>();
      mbar_arrive_remote_if(lane < 4, rb0 + ((nA - 4 + lane) << 24) + OFF_BAR + 8 * B_R2);
#pragma unroll
      for (int j = 0; j < 8; j++) vl[j] = pack2v(v[2 * j], v[2 * j + 1]);
      if (warp == 0 && (unsigned)ig < 3) issue_tok(1, B_F2, B_R2, 0);
    }
#pragma unroll 1
    for (int step = 0; step < NSTEP; step++) {
      const uint32_t par = step & 1;
      asm volatile("" : "+r"(lane));
      const bool dual = is_dual(step), has_next = step + 1 < NSTEP;
      mbar_expect_if(lane == 0 && has_next, bar + 8 * (B_F2 + warp), 10240);
      if (warp == 0 && ig >= IG_V && dual && sync_b) wait_cnt(&g_xready[sched_l(step + 1)][0], 32);
      bar_sync(N_VGO, 384);
      CFENCE();
#define F1_BYTES (is_dual(step + 1) ? 15360 : 2560)
#define ARM() do { \
        mbar_expect_if(lane == 0 && has_next, bar + 8 * (B_F1 + warp), F1_BYTES); \
        mbar_expect_if(lane == 0 && has_next && warp * nA + (int)rank < 40, bar + 8 * (B_RS + warp), (warp * nA + (int)rank >= 36 ? nA : nh) * (dual ? 512 : 256)); } while (0)
#define O_ADDR() uint32_t oa = sb + OFF_O + (lane >> 4) * PL_SZ + warp * 256 + (lane & 15) * 16, xo = (lane >> 4) * 1024 + warp * 256 + (lane & 15) * 16; \
        asm volatile("" : "+r"(oa), "+r"(xo))
#define O_READY(act) do { if (has_next) { const uint4 ov = lds128(oa); \
        if (act) { st_async_v4(nxt + OFF_XL + xo, ov.x, ov.y, ov.z, ov.w, nxt + OFF_BAR + 8 * B_OPEER); \
                   st_async_v4(prv + OFF_XF + xo, ov.x, ov.y, ov.z, ov.w, prv + OFF_BAR + 8 * B_OPEER); } \
        fence_async(); bar_arrive(N_O, 384); } \
        if (warp == 0) TS(15); } while (0)
#define TOK_L3(g0) if (warp == 0 && ig >= (g0) && has_next) { mbar_waitu(bar + 8 * B_R1, ig == 3 ? par : (step - LAG) & 1); asm volatile("fence.proxy.async.global;" ::: "memory"); \
        bulk_g2s_mc_e(sb + OFF_TILE + ig * TILE_GRP + TILE_SBO, &g_xn[0][0] + uni(sched_l(step + 1) * (32 * DM)) + ig * 5120, 10240, bar + 8 * (B_F2 + ig), mcmask); }
#define OX_SA (sb + OFF_PL + (lane & 7) * 128 + (((warp * 2 + ((lane >> 3) & 1)) ^ (lane & 7)) << 4))
      if (dual) {
        uint32_t vf[8], vm[4], vn[8];
        {
          DESC(0);
          float v[24];
          ARM();
          wg_fence(); proj<48, SSV, 0, 30, 40, 30>(v, W, D); wg_commit();
          proj<48, SSV, 0, 0, VD1 - 10, 30>(v, W, D);
          bar_sync(N_SISS, 384);
          proj<48, SSV, 0, VD1 - 10, VD1 - 7, 30>(v, W, D); wg_commit();
          wg_wait<1>(); bar_arrive(N_G3, 160);
          wg_fence(); proj<48, SSV, 0, VD1 - 7, 10, 30>(v, W, D); wg_commit();
          proj<48, SSV, 0, 10, 13, 30>(v, W, D); wg_commit();
          wg_wait<1>(); REL(B_R1, 0);
          wg_fence(); proj<48, SSV, 0, 13, 20, 30>(v, W, D); wg_commit();
          proj<48, SSV, 0, 20, 23, 30>(v, W, D); wg_commit();
          wg_wait<1>(); REL(B_R1, 1);
          wg_fence(); proj<48, SSV, 0, 23, 30, 30>(v, W, D); wg_commit();
          wg_wait<0>(); REL(B_R1, 2);
          bar_arrive(N_VDONE, 160);
          if (warp == 0) TS(14);
#pragma unroll
          for (int j = 4; j < 8; j++) vf[j] = pack2v(v[4 + 2 * j], v[5 + 2 * j]);
          keep4(vf + 4, lane);
          vm[0] = pack2v(v[0], v[1]); vm[1] = pack2v(v[2], v[3]); vm[2] = pack2v(v[20], v[21]); vm[3] = pack2v(v[22], v[23]);
          keep4(vm, lane);
#pragma unroll
          for (int j = 0; j < 4; j++) vf[j] = pack2v(v[4 + 2 * j], v[5 + 2 * j]);
          keep4(vf, lane);
        }
        {
          DESC(1);
          float o[8];
          O_ADDR();
          bar_sync(N_PM, 224);
          wg_fence();
          MM<8>::rs<dlo(OFF_PL + 3584, 128), 0>(o, vl, D.p);
          MM<8>::rs<dlo(OFF_PL + PL_SZ + 3584, 128), 0>(o + 4, vf, D.p);
          MM<8>::rs<dlo(OFF_PL + 3584 + 256, 128), 1>(o, vl + 4, D.p);
          MM<8>::rs<dlo(OFF_PL + PL_SZ + 3584 + 256, 128), 1>(o + 4, vf + 4, D.p);
          MM<8>::rs<dlo(OFF_PL + 3584 + 512, 128), 1>(o, vm, D.p);
          MM<8>::rs<dlo(OFF_PL + PL_SZ + 3584 + 512, 128), 1>(o + 4, vm, D.p);
          wg_commit();
          fence_sched(step);
          const uint4 il = lds128(sb + OFF_INV + (lane & 3) * 16), jf = lds128(sb + OFF_INV + 64 + (lane & 3) * 16);
          const float i0 = rcpf(__uint_as_float(il.x) + __uint_as_float(il.y)), i1 = rcpf(__uint_as_float(il.z) + __uint_as_float(il.w));
          const float j0 = rcpf(__uint_as_float(jf.x) + __uint_as_float(jf.y)), j1 = rcpf(__uint_as_float(jf.z) + __uint_as_float(jf.w));
          { const uint32_t k4[4] = {__float_as_uint(i0), __float_as_uint(i1), __float_as_uint(j0), __float_as_uint(j1)}; keep4(k4, lane | (oa ^ xo)); }
          wg_wait<0>();
          stsm4t(oa, pack2(o[0] * i0, o[1] * i1), pack2(o[2] * i0, o[3] * i1), pack2(o[4] * j0, o[5] * j1), pack2(o[6] * j0, o[7] * j1));
          O_READY(true);
          TOK_L3(IG_V);
        }
        {
          DESC(2);
          float v[16];
          bar_sync(N_TURN, 256);
          mbar_waitu(bar + 8 * B_F2, par ^ 1);
          wg_fence(); proj<32, SSV, 1, 0, 10>(v, W, D); wg_commit();
          mbar_waitu(bar + 8 * (B_F2 + 1), par ^ 1);
          wg_fence(); proj<32, SSV, 1, 10, 14>(v, W, D); wg_commit();
          wg_wait<1>(); REL(B_R2, 0);
          wg_fence(); proj<32, SSV, 1, 14, 20>(v, W, D); wg_commit();
          mbar_waitu(bar + 8 * (B_F2 + 2), par ^ 1);
          wg_fence(); proj<32, SSV, 1, 20, 24>(v, W, D); wg_commit();
          wg_wait<1>(); REL(B_R2, 1);
          wg_fence(); proj<32, SSV, 1, 24, 30>(v, W, D); wg_commit();
          mbar_waitu(bar + 8 * (B_F2 + 3), par ^ 1);
          wg_fence(); proj<32, SSV, 1, 30, 34>(v, W, D); wg_commit();
          wg_wait<1>(); REL(B_R2, 2);
          wg_fence(); proj<32, SSV, 1, 34, 40>(v, W, D); wg_commit();
          wg_wait<0>(); REL(B_R2, 3);
#pragma unroll
          for (int j = 0; j < 8; j++) vn[j] = pack2v(v[2 * j], v[2 * j + 1]);
          keep4(vn, lane); keep4(vn + 4, lane);
          if (warp == 0) TS(18);
        }
        DESC(3);
        uint32_t ow[16];
        bar_sync(N_P, 256);
        fence_async();
#define PV16(i, off, va) { float o[8]; wg_fence(); \
          MM<16>::rs<dlo(OFF_PL + (off), 128), 0>(o, va, D.p); \
          MM<16>::rs<dlo(OFF_PL + (off) + 256, 128), 1>(o, va + 4, D.p); \
          MM<16>::rs<dlo(OFF_PL + (off) + 512, 128), 1>(o, vm, D.p); \
          wg_commit(); wg_wait<0>(); \
          _Pragma("unroll") for (int j = 0; j < 4; j++) ow[4 * (i) + j] = pack2v(o[2 * j], o[2 * j + 1]); \
          keep4(ow + 4 * (i), lane); }
        PV16(0, 0, vl) PV16(1, 1792, vl) PV16(2, PL_SZ, vf) PV16(3, PL_SZ + 1792, vf)
        const uint32_t s1 = OX_SA + (lane < 16 ? 3072 : 0), s2 = OX_SA + (lane < 16 ? 2048 : 1024);
        bar_sync(N_V, 128);
        stsm4t(s1, ow[0], ow[1], ow[2], ow[3]);
        stsm4t(s2, ow[4], ow[5], ow[6], ow[7]);
        stsm4t(s1 + PL_SZ, ow[8], ow[9], ow[10], ow[11]);
        stsm4t(s2 + PL_SZ, ow[12], ow[13], ow[14], ow[15]);
#pragma unroll
        for (int j = 0; j < 8; j++) vl[j] = vn[j];
      } else {
        uint32_t vm[4], vn[8];
        {
          DESC(4);
          float v[4];
          wg_fence(); proj<8, SSV, 0, 30, 40, 30>(v, W, D); wg_commit();
          proj<8, SSV, 0, 0, VS1, 30>(v, W, D); wg_commit();
          ARM();
          bar_sync(N_SISS, 384);
          wg_wait<1>(); bar_arrive(N_G3, 160);
          wg_fence(); proj<8, SSV, 0, VS1, 30, 30>(v, W, D); wg_commit();
          if (has_next) { mbar_waitu2(bar + 8 * B_F2, bar + 8 * (B_F2 + 1), par ^ 1); mbar_waitu(bar + 8 * (B_F2 + 2), par ^ 1); }
          wg_wait<0>();
          bar_arrive(N_VDONE, 160);
          vm[0] = pack2v(v[0], v[1]); vm[1] = pack2v(v[2], v[3]); vm[2] = pack2v(v[1], v[0]); vm[3] = pack2v(v[3], v[2]);
        }
        DESC(5);
        float v[16];
        {
          wg_fence(); proj<32, SSV, 1, 0, VS2>(v, W, D); wg_commit();
          {
            float o[4];
            O_ADDR();
            bar_sync(N_PM, 192);
            if (warp == 0) TS(14);
            wg_fence();
            MM<8>::rs<dlo(OFF_PL + 3584, 128), 0>(o, vl, D.p);
            MM<8>::rs<dlo(OFF_PL + 3584 + 256, 128), 1>(o, vl + 4, D.p);
            MM<8>::rs<dlo(OFF_PL + 3584 + 512, 128), 1>(o, vm, D.p);
            wg_commit();
            fence_sched(step);
            const uint4 il = lds128(sb + OFF_INV + (lane & 3) * 16);
            const float i0 = rcpf(__uint_as_float(il.x) + __uint_as_float(il.y)), i1 = rcpf(__uint_as_float(il.z) + __uint_as_float(il.w));
            { const uint32_t k4[4] = {__float_as_uint(i0), __float_as_uint(i1), oa, xo}; keep4(k4, lane); }
            wg_wait<0>();
            stsm2t(oa, pack2(o[0] * i0, o[1] * i1), pack2(o[2] * i0, o[3] * i1));
            O_READY(lane < 16);
            TOK_L3(3);
          }
          if (has_next) {
            mbar_arrive_remote_if(lane < VS2 / 10, rb0 + ((nA - 4 + lane) << 24) + OFF_BAR + 8 * B_R2);
            bar_sync(N_TURN, 256);
          }
          if (VS2 < 30) { wg_fence(); proj<32, SSV, 1, VS2, 30>(v, W, D); wg_commit(); }
          if (has_next) mbar_waitu(bar + 8 * (B_F2 + 3), par ^ 1);
          if (VS2 < 30) { wg_wait<0>(); if (has_next) REL(B_R2, 2); }
          wg_fence(); proj<32, SSV, 1, 30, 40>(v, W, D); wg_commit();
          wg_wait<0>();
          if (has_next) REL(B_R2, 3);
#pragma unroll
          for (int j = 0; j < 8; j++) vn[j] = pack2v(v[2 * j], v[2 * j + 1]);
          keep4(vn, lane); keep4(vn + 4, lane);
          if (warp == 0) TS(18);
        }
        float o[16];
        bar_sync(N_P, 256);
        fence_async();
        wg_fence();
        MM<32>::rs<dlo(OFF_PL, 128), 0>(o, vl, D.p);
        MM<32>::rs<dlo(OFF_PL + 256, 128), 1>(o, vl + 4, D.p);
        MM<32>::rs<dlo(OFF_PL + 512, 128), 1>(o, vm, D.p);
        wg_commit();
        const uint32_t s1 = OX_SA + (lane < 16 ? 3072 : 0), s2 = OX_SA + (lane < 16 ? 2048 : 1024);
        wg_wait<0>();
        bar_sync(N_V, 128);
        stsm4t(s1, pack2(o[0], o[1]), pack2(o[2], o[3]), pack2(o[4], o[5]), pack2(o[6], o[7]));
        stsm4t(s2, pack2(o[8], o[9]), pack2(o[10], o[11]), pack2(o[12], o[13]), pack2(o[14], o[15]));
#pragma unroll
        for (int j = 0; j < 8; j++) vl[j] = vn[j];
      }
      bar_arrive(N_OX, 160);
      if (warp == 0) TS(16);
    }
    cluster_sync_all();
  } else {
    asm volatile("setmaxnreg.dec.sync.aligned.u32 32;");
    if (wg > 3) return;
    LANE_INIT();
    struct RsJob { uint32_t* gp; uint32_t la, mb; int n; };
    auto rs_prep = [&](int step, int s, int c) {
      RsJob j;
      const int u = s * nA + rank;
      j.gp = &g_part[0][0][0][0] + (uint32_t)((((step & 1) * 2 + c) * NCL + cl) * 2560 + u * 64 + (lane >> 2) * 8 + (lane & 3));
      j.la = sb + OFF_TILE + c * LAND_F + LAND(s) + lane * 8;
      j.mb = bar + 8 * (B_RS + s);
      j.n = u >= 40 ? 0 : u >= 36 ? 3 : 1;
      asm volatile("" : "+l"(j.gp), "+r"(j.la));
      return j;
    };
    auto rs_sum = [&](RsJob j, int step) {
      if (j.n) {
        auto five = [&](uint32_t la) {
          uint2 p[5];
#pragma unroll
          for (int i = 0; i < 4; i++) p[i] = lds64(la + i * 256);
          asm volatile("{\n.reg .pred q;\nsetp.eq.s32 q, %3, 5;\nmov.u32 %0, 0;\nmov.u32 %1, 0;\n@q ld.shared.v2.b32 {%0,%1}, [%2];\n}"
                       : "=r"(p[4].x), "=r"(p[4].y) : "r"(la + 1024), "r"(nh) : "memory");
          return make_uint2(hadd2bf(hadd2bf(p[0].x, p[1].x), hadd2bf(hadd2bf(p[2].x, p[3].x), p[4].x)),
                            hadd2bf(hadd2bf(p[0].y, p[1].y), hadd2bf(hadd2bf(p[2].y, p[3].y), p[4].y)));
        };
        const uint32_t tag = ((step >> 1) & 1) ^ 1;
        mbar_waitw(j.mb, step & 1);
        uint2 t = five(j.la);
        if (j.n > 1) {
          const uint2 a = five(j.la + (nh == 5 ? 1280 : TILE_GRP - 1280)), b = five(j.la + TILE_GRP);
          t.x = hadd2bf(t.x, hadd2bf(a.x, b.x)); t.y = hadd2bf(t.y, hadd2bf(a.y, b.y));
        }
        const uint32_t t0 = (movm(t.x) & ~1u) | tag, t1 = (movm(t.y) & ~1u) | tag;
        asm volatile("st.relaxed.gpu.global.b32 [%0], %1;" :: "l"(j.gp), "r"(lane & 16 ? t1 : t0) : "memory");
        asm volatile("st.relaxed.gpu.global.b32 [%0], %1;" :: "l"(j.gp + 4), "r"(lane & 16 ? t0 : t1) : "memory");
      }
    };
    if (warp * nA + (int)rank < 40) {
#pragma unroll
      for (int e = LAG; e < LAG + 2; e++)
        if ((e >> 1) & 1) *reinterpret_cast<uint2*>(&g_part[(e & 1) * 2 + 1][cl][warp * nA + rank][lane * 2]) = make_uint2(1u, 1u);
      __threadfence();
    }
    if (warp == 2 && ig >= 0 && sync_b) wait_cnt(&g_xready[0][0], 32);
    cluster_sync_all();
    if (warp == 2 && ig >= 0) bulk_g2s_mc_e(sb + OFF_TILE + ig * TILE_GRP + TILE_SBO, &g_xn[0][0] + ig * 5120, 10240, bar + 8 * (B_F2 + ig), mcmask);
    bar_sync(N_PI, 128);
#pragma unroll 1
    for (int i = warp; i < 20; i += 4) {
      int c0, c1; wo_coord(i, t3, head, c0, c1);
      if (i >= 2 && i < 15) tma2d_e(sb + OFF_WO + (i - 2) * 4096, &M.wo32, c0, c1, bar + 8 * B_W1);
      else if (lane == 0) tma2d_prefetch(&M.wo32, c0, c1);
      __syncwarp();
    }
#pragma unroll 1
    for (int step = 0; step < NSTEP; step++) {
      const uint32_t par = step & 1;
      asm volatile("" : "+r"(lane));
      const bool dual = is_dual(step), has_next = step + 1 < NSTEP;
      {
        bar_sync(N_PX, dual ? 256 : 192);
        if (dual || warp >= 2) tok_softmax(sb, dual ? warp : warp - 2, lane);
        bar_arrive(N_P, 256);
        asm volatile("" : "+r"(lane));
        if (has_next) {
          if (step + 2 == LAG && lane < 20) asm volatile("prefetch.global.L2 [%0];" :: "l"(mem0 + (warp * 20 + lane) * 64));
          const int nw = ig >= 0 ? 3 : 4, j0 = warp < nw ? warp : 8;
          const int sh = dual ? 1 : 0;
          rs_sum(rs_prep(step, j0 >> sh, j0 & sh), step);
          if (warp == 0) TS(17);
          if (dual) rs_sum(rs_prep(step, (j0 + nw) >> 1, (j0 + nw) & 1), step);
          if (warp == 0) { bar_sync(N_C, 288); }
          mbar_arrive_remote_if(lane < nA, rb0 + (lane << 24) + OFF_BAR + 8 * B_LANDFREE);
          const uint32_t gap = dual ? POLL_GAPD : POLL_GAP;
          if (gap) { const uint32_t t0 = clock32(); while (clock32() - t0 < gap) {} }
#pragma unroll 1
          for (int j = j0; j < (dual ? 8 : 4); j += nw) {
            const int u = (j >> sh) * nA + rank, c = j & sh;
            if (u < UMAX && (c || step + 1 != NSEG)) {
              const uint32_t* gq = &g_part[0][0][0][0] + (uint32_t)((par * 2 + c) * NCL * 2560 + u * 64 + lane * 2);
              uint2 pa[NCL];
              POLL(pa, gq);
              deliver(pa, gq, u, c, step + 1 < NSEG ? c : 0, dual ? DS_DUAL : DS_SINGLE, step, j == 0, lane);
            }
            if (warp == 0 && j == 0) TS(13);
          }
          if (warp >= nw && (is_dual(step + 1) || (ig < 3 && step + 2 < NSTEP))) {
            issue_tok(is_dual(step + 1) ? sched_f(step + 1) : sched_l(step + 2), is_dual(step + 1) ? B_F1 : B_F2, B_R2, par ^ 1);
          }
          if (step + 1 == LAG && UMAX) {
            uint4 v[5];
#pragma unroll
            for (int i = 0; i < 5; i++) { const int t = warp * 160 + i * 32 + lane; v[i] = *reinterpret_cast<const uint4*>(mem0 + ((t >> 1) & 7) * DM + (t >> 4) * 16 + ((t ^ (t >> 3)) & 1) * 8); }
            mbar_waitu(bar + 8 * B_LANDFREE, par);
#pragma unroll
            for (int i = 0; i < 5; i++)
              st_async_v4(sb + OFF_TILE + LAND_F + warp * TILE_GRP + (i * 32 + lane) * 16, v[i].x, v[i].y, v[i].z, v[i].w, bar + 8 * (B_F1 + warp));
          }
        }
      }
      if (warp == (ig >= 0 && !is_dual(step + 1) ? 2 : 3)) {
        unsigned char* o0 = g_o + uni(step % RO * (96 * 8192) + (head * 3 + t3) * (dual ? 8192 : 4096));
        bar_sync(N_OX, 160);
        fence_async();
        bulk_s2g_es(o0, sb + OFF_PL, 4096);
        if (dual) bulk_s2g_es(o0 + 4096, sb + OFF_PL + PL_SZ, 4096);
        asm volatile("cp.async.bulk.commit_group;" ::: "memory");
        asm volatile("cp.async.bulk.wait_group.read 0;" ::: "memory");
        __syncwarp();
        mbar_arrive_remote_if(lane < 2, (lane ? nxt : prv) + OFF_BAR + 8 * B_PLFREE);
        asm volatile("cp.async.bulk.wait_group 0;" ::: "memory");
        asm volatile("fence.proxy.async.global;" ::: "memory");
        __syncwarp();
        if (lane == 0) red_release(&g_f[F_O + (head * 3 + t3) / 5][step], 1u);
        __syncwarp();
      }
    }
    cluster_sync_all();
  }
}

__device__ __forceinline__ float gelu2(float x) {
  const float u = x * fmaf(x * x, 0.7978845608028654f * 0.044715f, 0.7978845608028654f);
  float t; asm("tanh.approx.f32 %0, %1;" : "=f"(t) : "f"(u));
  return fmaf(x, t, x); }

struct BParams {
  CUtensorMap wmap[5];
  CUtensorMap wo16;
  const __nv_bfloat16* x;
  __nv_bfloat16* out;
  uint64_t desc;
};
#define BO_O 0
#define BO_RES (6 * 8192)
#define OP_RES 63488
#define BO_STG (BO_RES + 2 * OP_RES)
#define BO_RING_OP (BO_STG + 16384)
#define OP_SLOT 12288
#define NS_OP 3
#define BO_H 81920
#define BO_W1 (BO_H + 16384)
#define BO_RING_MLP (BO_W1 + 81920)
#define BO_BAR 229376
#define BO_BOX (BO_BAR + 248)
#define BO_CARRY (BO_BAR + 512)
#define BO_STAT (BO_CARRY + 2048)
#define B_SMEM (BO_STAT + 256)
static_assert(B_SMEM <= 232448 && BO_RING_OP + NS_OP * OP_SLOT == BO_BAR && BO_RING_MLP + 3 * 16384 == BO_BAR && 2 * 83968 <= BO_RING_MLP, "smem");
enum { BB_W = 0, BB_FULL = 2, BB_TMP = BB_FULL + 3, BB_OFULL = BB_FULL + 5, BB_SFREE = BB_OFULL,
       BB_STAT = BB_SFREE + 6, BB_ZFREE, BB_DONE = BB_ZFREE + 3,
       BB_EMPTY, BB_START = BB_EMPTY, BB_USED = BB_EMPTY + 2, BB_NUM = BB_USED + 3 };
enum { NB_PP = 1, NB_H = 3, NB_END = 4, NB_END2 = 5, NB_STAGED = 6, NB_FREE = 8, NB_EARLY = 10, NB_LAST = 11 };

#define DESC_LO(off) (((SMEM0 + (off)) >> 4) | (1u << 16))

__device__ __forceinline__ uint32_t ld_relaxed(const uint32_t* p) { uint32_t v; asm volatile("ld.relaxed.gpu.global.b32 %0, [%1];" : "=r"(v) : "l"(p) : "memory"); return v; }
__device__ __forceinline__ int fmask(int r) { return (r < NSEG) | ((r >= LAG && r < NSTEP) << 1); }
__device__ __forceinline__ int bmask(int r) { return (r <= NSEG) | ((r >= LAG) << 1); }
__device__ __forceinline__ uint32_t rtarget(int mask) { return mask == 3 ? 64 : 32; }
__device__ __forceinline__ void warp_signal(uint32_t* p, int lane) {
  __syncwarp();
  asm volatile("{\n.reg .pred q;\nsetp.eq.u32 q, %1, 0;\n@q red.release.gpu.global.add.u32 [%0], 1;\n}" :: "l"(p), "r"(lane) : "memory");
}
__device__ __forceinline__ uint32_t pack2h(float lo, float hi) { uint32_t r; asm("cvt.rn.f16x2.f32 %0, %1, %2;" : "=r"(r) : "f"(hi), "f"(lo)); return r; }
template <bool H> __device__ __forceinline__ uint32_t pk(float lo, float hi) { return H ? pack2h(lo, hi) : pack2(lo, hi); }
template <int N, bool H> __device__ __forceinline__ void stage_out(const float* d, uint32_t dst, int warp, int lane) {
  const uint32_t sa = dst + ((lane >> 4) * 8 + (lane & 7)) * 128 + (((2 * warp + ((lane >> 3) & 1)) ^ (lane & 7)) << 4);
#pragma unroll
  for (int m = 0; m < N / 16; m++)
    stsm4t(sa + m * 2048, pk<H>(d[8 * m], d[8 * m + 1]), pk<H>(d[8 * m + 2], d[8 * m + 3]), pk<H>(d[8 * m + 4], d[8 * m + 5]), pk<H>(d[8 * m + 6], d[8 * m + 7]));
}
template <int N> __device__ __forceinline__ void acc_live(float* d) {
#pragma unroll
  for (int i = 0; i < N / 2; i++) asm volatile("" : "+f"(d[i]) :: "memory");
}
struct Ring {
  uint32_t sl, ph;
  template <int NS> __device__ __forceinline__ void step() { if (++sl == NS) { sl = 0; ph ^= 1; } }
};

#define LOCKSTEP 0
#define KOFF(x) (DESC_LO(BO_O) + ((x) >> 2) * (N * 8) + ((x) & 3) * 2)
template <int N, int P>
__device__ __forceinline__ void op_pass(const uint32_t* W, uint32_t bar, Dsc alo, Dsc blo, Dsc xlo, bool x2, Ring& rg, int wg, int warp, int lane, int r) {
  float acc[N / 2];
  blo.e = xlo.e = fresh<P + N / 64 * 5>(r);
  const Dsc tlo = blo + uni(rg.sl) * (OP_SLOT / 16);
  if (P == 0) mbar_waitu(bar + 8 * BB_OFULL, r & 1);
  CTS(5 * P);
  if (!LOCKSTEP || P > 1 || P == wg) bar_sync(NB_PP + wg, 256);
  wg_fence();
#define OP_R(x) MM<N>::template rs<KOFF(4 * (x >> 1) + (x & 1)), (x != 0)>(acc, W + 32 * P + 4 * x, blo);
#define OP_S(x) MM<N>::template ss<DESC_LO(BO_RES) + (6 * P + x) * 128, KOFF(4 * (x >> 1) + 2 + (x & 1)), 1>(acc, alo, blo);
#define OP_T(x) MM<N>::template ss<DESC_LO(BO_RING_OP) + x * 128, KOFF(14 + x), 1>(acc, tlo, blo);
  OP_R(0) OP_S(0) OP_R(1) OP_S(1) OP_R(2) OP_S(2) OP_R(3) OP_S(3)
  if (P == 0) mbar_waitu(bar + 8 * (BB_OFULL + 1), r & 1);
  if (P == 4) wg_commit();
  OP_R(4) OP_S(4) OP_R(5) OP_S(5)
  if (P == 1 && x2) MM<N>::template ss<DESC_LO(BO_RES) + 30 * 128, KOFF(20), 1>(acc, alo, xlo);
  if (P == 4) { wg_commit(); wg_wait<1>(); bar_arrive(NB_EARLY, 288); CTS(21); wg_fence(); }
  mbar_waitu(bar + 8 * (BB_FULL + rg.sl), rg.ph);
  OP_R(6) OP_T(0) OP_R(7) OP_T(1)
  if (P == 0) mbar_waitu(bar + 8 * (BB_OFULL + 2), r & 1);
  OP_T(2) OP_T(3)
  if (P == 0) MM<N>::template rs<KOFF(20), 1>(acc, W + 160, xlo);
  OP_T(4) OP_T(5)
  wg_commit();
  if (!LOCKSTEP || P) bar_arrive(NB_PP + 1 - wg, 256);
  CTS(5 * P + 2);
  bar_sync(NB_FREE + wg, 160);
  wg_wait<0>();
  acc_live<N>(acc);
  if (P == 4) bar_arrive(NB_LAST, 288);
  mbar_arrive_if(lane == 0, bar + 8 * (BB_USED + rg.sl));
  CTS(5 * P + 3);
  stage_out<N, false>(acc, SMEM0 + BO_STG + wg * 8192, warp, lane);
  bar_arrive(NB_STAGED + wg, 160);
  CTS(5 * P + 4);
  rg.step<NS_OP>(); rg.step<NS_OP>();
}
template <int N>
__device__ __forceinline__ void op_round(const uint32_t* W, uint32_t bar, Dsc alo, Dsc blo, Dsc xlo, bool x2, Ring& rg, int wg, int warp, int lane, int r) {
  op_pass<N, 0>(W, bar, alo, blo, xlo, x2, rg, wg, warp, lane, r);
  op_pass<N, 1>(W, bar, alo, blo, xlo, x2, rg, wg, warp, lane, r);
  op_pass<N, 2>(W, bar, alo, blo, xlo, x2, rg, wg, warp, lane, r);
  op_pass<N, 3>(W, bar, alo, blo, xlo, x2, rg, wg, warp, lane, r);
  op_pass<N, 4>(W, bar, alo, blo, xlo, x2, rg, wg, warp, lane, r);
}
__device__ __forceinline__ void carry_in(uint32_t sb, int wg, int warp, int lane) {
  const int row = (lane >> 1) & 3;
  if (lane < 16) {
    const uint4 v = lds128(sb + BO_CARRY + (wg * 4 + warp) * 256 + lane * 16);
    sts128(sb + BO_H + wg * 8192 + (lane >> 3) * 4096 + row * 128 + (((2 * warp + (lane & 1)) ^ row) << 4), v.x, v.y, v.z, v.w);
  }
  __syncwarp();
}
#define STAGGER 0
template <int N, int Z>
__device__ __forceinline__ void p1_pair(float* acc, const uint32_t* W, uint32_t bar, Dsc alo, Dsc blo, int lane, int r) {
  blo.e = fresh<10 + Z / 3 + N / 64 * 2>(r);
  mbar_waitu(bar + 8 * (BB_FULL + Z), r & 1);
  CTS(40 + Z);
  wg_fence();
#define P1_B(k) \
  MM<N, true>::template rs<DESC_LO(BO_RING_MLP) + (2 * Z % 3) * 1024 + k * 512, (2 * Z + k != 0)>(acc, W + 16 * Z + 8 * k, blo); \
  MM<N, true>::template ss<DESC_LO(BO_W1) + (2 * Z + k) * 512, DESC_LO(BO_RING_MLP) + (2 * Z % 3) * 1024 + k * 512 + 4, 1>(acc, alo, blo); \
  MM<N, true>::template rs<DESC_LO(BO_RING_MLP) + (2 * Z % 3) * 1024 + k * 512 + 2, 1>(acc, W + 16 * Z + 8 * k + 4, blo); \
  MM<N, true>::template ss<DESC_LO(BO_W1) + (2 * Z + k) * 512 + 128, DESC_LO(BO_RING_MLP) + (2 * Z % 3) * 1024 + k * 512 + 6, 1>(acc, alo, blo);
  P1_B(0)
  if (Z == 1 || Z == 2) { wg_commit(); wg_wait<1>(); mbar_arrive_if(lane == 0, bar + 8 * (BB_EMPTY + Z - 1)); wg_fence(); }
  P1_B(1)
  wg_commit();
}
template <int N>
__device__ __forceinline__ void phase1(const uint32_t* W, uint32_t sb, Dsc alo, Dsc blo, int half, int wg, int warp, int lane, int off, int r) {
  float acc[N / 2];
  const uint32_t bar = sb + BO_BAR;
  CTS(30);
  p1_pair<N, 0>(acc, W, bar, alo, blo, lane, r);
  p1_pair<N, 1>(acc, W, bar, alo, blo, lane, r);
  p1_pair<N, 2>(acc, W, bar, alo, blo, lane, r);
  mbar_waitu(bar + 8 * (BB_SFREE + 4 + wg), (r + 1) & 1);
  carry_in(sb, wg, warp, lane);
  if (STAGGER && wg) bar_sync(NB_PP + 1, 256);
  p1_pair<N, 3>(acc, W, bar, alo, blo, lane, r);
  p1_pair<N, 4>(acc, W, bar, alo, blo, lane, r);
  if (STAGGER && !wg) bar_arrive(NB_PP + 1, 256);
  const int c = (lane >> 3) & 1, i0 = (lane >> 4) * 8 + (lane & 7) + off;
  uint32_t a0 = sb + BO_H + wg * 8192 + half * 4096 + i0 * 128 + (((2 * warp + c) ^ (i0 & 7)) << 4);
  uint32_t a1 = i0 >= 16 ? sb + BO_CARRY + (wg * 4 + warp) * 256 + half * 128 + (i0 - 16) * 32 + c * 16 : a0 + 2048, a3 = a1 + (i0 >= 16 ? 128 : 4096);
  asm volatile("" : "+r"(a0), "+r"(a1), "+r"(a3));
  mbar_waitu(bar + 8 * BB_STAT, r & 1);
  const uint32_t sa = sb + BO_STAT + half * 128 + (lane & 3) * 32;
  uint4 t[2] = {lds128(sa), lds128(sa + 16)};
  wg_wait<0>();
  acc_live<N>(acc);
  CTS(32);
#pragma unroll
  for (int m = 0; m < N / 16; m++) {
    const float s0 = __uint_as_float(t[m & 1].x), s1 = __uint_as_float(t[m & 1].y), s2 = __uint_as_float(t[m & 1].z), s3 = __uint_as_float(t[m & 1].w);
    float* d = acc + 8 * m;
    d[0] *= s0; d[1] *= s1; d[2] *= s0; d[3] *= s1; d[4] *= s2; d[5] *= s3; d[6] *= s2; d[7] *= s3;
    if (m + 2 < N / 16) t[m & 1] = lds128(sa + 128 + m * 16);
#pragma unroll
    for (int j = 0; j < 8; j++) d[j] = gelu2(d[j]);
  }
#pragma unroll
  for (int m = 0; m < N / 16; m++)
    stsm4t(m == 1 ? a1 : m == 3 ? a3 : a0 + m * 2048, pack2(acc[8 * m], acc[8 * m + 1]), pack2(acc[8 * m + 2], acc[8 * m + 3]), pack2(acc[8 * m + 4], acc[8 * m + 5]), pack2(acc[8 * m + 6], acc[8 * m + 7]));
}
template <int N, int P>
__device__ __forceinline__ void p2_mma(float* acc, const uint32_t* W, Dsc alo, Dsc blo, int r) {
  blo.e = fresh<P + N / 64 * 5>(r);
  MM<N>::template rs<DESC_LO(BO_H), 0>(acc, W + 80 + 16 * P, blo);     MM<N>::template ss<DESC_LO(0) + P * 1024, DESC_LO(BO_H) + 512, 1>(acc, alo, blo);
  MM<N>::template rs<DESC_LO(BO_H) + 2, 1>(acc, W + 84 + 16 * P, blo); MM<N>::template ss<DESC_LO(0) + P * 1024 + 128, DESC_LO(BO_H) + 514, 1>(acc, alo, blo);
  MM<N>::template rs<DESC_LO(BO_H) + 4, 1>(acc, W + 88 + 16 * P, blo); MM<N>::template ss<DESC_LO(0) + P * 1024 + 512, DESC_LO(BO_H) + 516, 1>(acc, alo, blo);
  MM<N>::template rs<DESC_LO(BO_H) + 6, 1>(acc, W + 92 + 16 * P, blo); MM<N>::template ss<DESC_LO(0) + P * 1024 + 640, DESC_LO(BO_H) + 518, 1>(acc, alo, blo);
}
template <int N, int P, int T>
__device__ __forceinline__ void p2_pass(const uint32_t* W, uint32_t bar, Dsc alo, Dsc blo, int wg, int warp, int lane, int r) {
  float acc[N / 2], ac2[N / 2];
  CTS(5 * P);
  if (P || wg) bar_sync(NB_PP + wg, 256);
  wg_fence();
  p2_mma<N, P>(acc, W, alo, blo, r);
  wg_commit();
  if constexpr (T == 2) { p2_mma<N, P + 1>(ac2, W, alo, blo, r); wg_commit(); }
  if (P < 4 || !wg) bar_arrive(NB_PP + 1 - wg, 256);
  CTS(5 * P + 2);
  if (T == 1 && (P == 2 || P == 3)) mbar_waitu(bar + 8 * (BB_SFREE + 2 * (P - 2) + wg), r & 1);
  wg_wait<T - 1>();
  acc_live<N>(acc);
  if (P == 4) bar_sync(NB_H, 256);
  CTS(5 * P + 3);
  constexpr int K = P / T & 1;
  stage_out<N, true>(acc, SMEM0 + (P == 4 ? BO_H : BO_RING_MLP + (2 - K) * 16384) + wg * 8192, warp, lane);
  if constexpr (T == 2) {
    wg_wait<0>();
    acc_live<N>(ac2);
    stage_out<N, true>(ac2, SMEM0 + BO_RING_MLP + (2 - K) * 16384 + wg * 8192 + 4096, warp, lane);
  }
  bar_arrive(NB_STAGED + (P == 4 ? 4 : 2 * K) + wg, 160);
  CTS(5 * P + 4);
}
template <int N>
__device__ __forceinline__ void phase2(const uint32_t* W, uint32_t bar, Dsc alo, Dsc blo, int wg, int warp, int lane, int r) {
  if constexpr (N == 64) {
    p2_pass<N, 0, 1>(W, bar, alo, blo, wg, warp, lane, r);
    p2_pass<N, 1, 1>(W, bar, alo, blo, wg, warp, lane, r);
    p2_pass<N, 2, 1>(W, bar, alo, blo, wg, warp, lane, r);
    p2_pass<N, 3, 1>(W, bar, alo, blo, wg, warp, lane, r);
  } else {
    p2_pass<N, 0, 2>(W, bar, alo, blo, wg, warp, lane, r);
    p2_pass<N, 2, 2>(W, bar, alo, blo, wg, warp, lane, r);
  }
  p2_pass<N, 4, 1>(W, bar, alo, blo, wg, warp, lane, r);
}

__device__ __forceinline__ void ldg4(uint32_t* v, const void* p) {
  asm volatile("ld.relaxed.gpu.global.v4.u32 {%0,%1,%2,%3}, [%4];" : "=r"(v[0]), "=r"(v[1]), "=r"(v[2]), "=r"(v[3]) : "l"(p) : "memory"); }
__device__ __forceinline__ void stg4(void* p, const uint32_t* v) {
  asm volatile("st.global.v4.u32 [%0], {%1,%2,%3,%4};" :: "l"(p), "r"(v[0]), "r"(v[1]), "r"(v[2]), "r"(v[3]) : "memory"); }
struct RowPtr {
  unsigned char *p, *q, *t;
  __device__ __forceinline__ void ld(uint32_t* v, int o) const {
    ldg4(v, p + o); ldg4(v + 4, q + o);
    asm volatile("ld.relaxed.gpu.global.v2.u32 {%0,%1}, [%2];" : "=r"(v[8]), "=r"(v[9]) : "l"(t + o) : "memory");
  }
  __device__ __forceinline__ void st(const uint32_t* w, int o) const {
    stg4(p + o, w); stg4(q + o, w + 4);
    asm volatile("st.global.v2.u32 [%0], {%1,%2};" :: "l"(t + o), "r"(w[8]), "r"(w[9]) : "memory");
  }
};
__device__ __forceinline__ RowPtr row_img(int r, int n, int lane) {
  unsigned char* b = &g_acc[0][r % RD][n * 128];
  unsigned char* p = b + (uint32_t)((lane >> 3) * 8192 + (((lane ^ n) & 7) << 4));
  return {p, p + 32768, b + (uint32_t)(65536 + (lane >> 4) * 8192 + ((((lane >> 1) ^ n) & 7) << 4) + (lane & 1) * 8)};
}
__device__ __forceinline__ RowPtr row_ext(const void* lin, bool xn, int layer, int tok, int lane) {
  unsigned char* b = xn ? reinterpret_cast<unsigned char*>(&g_xn[layer][0]) + (uint32_t)((tok >> 5) * 40960 + ((tok >> 3) & 3) * 2560 + (tok & 7) * 32)
                        : (unsigned char*)lin + (uint32_t)(tok * 1280);
  const uint32_t o = (lane >> 1) * 256 + ((lane ^ (tok >> 2)) & 1) * 16;
  return {b + (uint32_t)(xn ? o + (lane >= 20 ? 7680 : 0) : lane * 16),
          b + (uint32_t)(xn ? o + 4096 + 7680 + (lane >= 8 ? 7680 : 0) + (lane >= 28 ? 7680 : 0) : lane * 16 + 512),
          b + (uint32_t)(xn ? (lane >> 2) * 256 + ((lane & 3) ^ ((tok >> 1) & 2)) * 8 + 8192 + 3 * 7680 : lane * 8 + 1024)};
}
__device__ __forceinline__ float2 h2f(uint32_t w) {
  float2 f; asm("{\n.reg .f16 l, h;\nmov.b32 {l, h}, %2;\ncvt.f32.f16 %0, l;\ncvt.f32.f16 %1, h;\n}" : "=f"(f.x), "=f"(f.y) : "r"(w)); return f; }
__device__ __forceinline__ float rsq(float x) { float y; asm("rsqrt.approx.ftz.f32 %0, %1;" : "=f"(y) : "f"(x)); return y; }
__device__ __forceinline__ void red_if(uint32_t v, const void* a) {
  asm volatile("{\n.reg .pred q;\nsetp.ne.u32 q, %1, 0;\n@q red.relaxed.gpu.global.add.u32 [%0], %1;\n}" :: "l"(a), "r"(v) : "memory"); }
__device__ __forceinline__ uint32_t dep0(uint32_t w, int lane) { uint32_t z; asm volatile("shr.b32 %0, %1, %2;" : "=r"(z) : "r"(w), "r"(lane + 32)); return z; }
__device__ __forceinline__ int lane_of(uint32_t w) {
  int lane; asm volatile("{\n.reg .u32 t;\nmov.u32 t, %%laneid;\nshr.u32 %0, %1, 20;\nadd.u32 %0, %0, t;\n}" : "=r"(lane) : "r"(w)); return lane; }
#define BUF (RD * TILE_B)
__device__ __forceinline__ int await(uint32_t v, const uint32_t* p, uint32_t target, bool lazy) {
  int n = 0;
  while (!__all_sync(~0u, v >= target)) {
    if (lazy) __nanosleep(200);
    if (++n > SPIN_LIMIT) FAIL();
    v = ld_relaxed(p);
  }
  asm volatile("fence.acquire.gpu;" ::: "memory");
  return lane_of(v);
}
template <int W> __device__ __forceinline__ void sum2(float& s, float& q, int lane) {
  const bool up = lane & (W / 2);
  float e = (up ? q : s) + __shfl_xor_sync(~0u, up ? s : q, W / 2);
#pragma unroll
  for (int o = W / 4; o; o >>= 1) e += __shfl_xor_sync(~0u, e, o);
  const float f = __shfl_xor_sync(~0u, e, W / 2);
  s = up ? f : e; q = up ? e : f;
}
template <int TYPE>
__device__ __forceinline__ void rrow(int r, int row, int tok, int lane, const uint32_t* go, int role, const __nv_bfloat16* x) {
  const int half = TYPE ? 0 : row >> 5;
  float v[20];
  float2 st = make_float2(1.f, 0.f);
  {
    uint32_t a[10], c[10], u[10], sh = 16;
    if (TYPE == 2) row_img(r + RD - ((row & 31) < 2), (row & 32) + ((row - 2) & 31), lane).ld(u, 4 * BUF);
    else row_ext(x, half, 1, tok, lane).ld(u, 0);
    if (TYPE == 2 || (TYPE == 0 && half))
      asm volatile("ld.relaxed.gpu.global.v2.f32 {%0,%1}, [%2];" : "=f"(st.x), "=f"(st.y) : "l"(g_stat + tok) : "memory");
    RowPtr ap = row_img(r, row, lane);
    const uint32_t g0 = TYPE != 3 ? ld_relaxed(go) : 0;
    if (TYPE == 2) {
      ap.ld(c, 2 * BUF);
      uint32_t z = dep0(c[9], lane);
#pragma unroll
      for (int i = 0; i < 10; i++) {
        const float2 g = h2f(u[i] | z), h = h2f(c[i] | z);
        v[2 * i] = fmaf(h.x, 0.5f, g.x * st.x); v[2 * i + 1] = fmaf(h.y, 0.5f, g.y * st.x);
        if (i & 1) z = dep0(__float_as_uint(v[2 * i]) | __float_as_uint(v[2 * i + 1]), lane);
      }
    }
    if (TYPE != 3) {
      asm volatile("" : "+l"(ap.p), "+l"(ap.t));
      ap.q = ap.p + 32768;
      lane = await(g0, go, NOP * NW12 * NW34, false); BTS2(r, 8 + 2 * TYPE); RTS(0);
      ap.ld(a, TYPE ? 3 * BUF : 0);
    }
    if (TYPE == 0) {
      ap.ld(c, BUF);
      const uint32_t one = 0x3f803f80u | dep0(c[9], lane);
#pragma unroll
      for (int i = 0; i < 10; i++) asm volatile("fma.rn.bf16x2 %0, %0, %1, %2;" : "+r"(a[i]) : "r"(one), "r"(c[i]));
      sh |= dep0(a[9], lane);
    }
    const float k = TYPE == 2 ? __uint_as_float(0x3f000000u | dep0(a[9], lane)) : 0.f;
#pragma unroll
    for (int i = 0; i < 10; i++) {
      if (TYPE == 2) { const float2 h = h2f(a[i]); v[2 * i] = fmaf(h.x, k, v[2 * i]); v[2 * i + 1] = fmaf(h.y, k, v[2 * i + 1]); continue; }
      float p = __uint_as_float(u[i] << sh), q = __uint_as_float(u[i] & (0xffffu << sh));
      if (TYPE == 0) { p = fmaf(p, st.x, bf_lo(a[i])); q = fmaf(q, st.x, bf_hi(a[i])); }
      v[2 * i] = p; v[2 * i + 1] = q;
    }
  }
  RTSD(1, v[19]);
  float s = 0.f, q = 0.f;
#pragma unroll
  for (int i = 0; i < 5; i++) {
    s += (v[4 * i] + v[4 * i + 1]) + (v[4 * i + 2] + v[4 * i + 3]);
    q += fmaf(v[4 * i], v[4 * i], v[4 * i + 1] * v[4 * i + 1]) + fmaf(v[4 * i + 2], v[4 * i + 2], v[4 * i + 3] * v[4 * i + 3]);
  }
  sum2<32>(s, q, lane);
  const float mean = s * (1.f / DM), var = fmaxf(q * (1.f / DM) - mean * mean, 0.f), rs = rsq(var + 1e-5f), k = TYPE ? rs : 2.f * rs, mr = -mean * k;
  RTSD(2, rs);
  uint32_t w[10];
#pragma unroll
  for (int i = 0; i < 10; i++) w[i] = pk<TYPE == 0>(fmaf(v[2 * i], k, mr), fmaf(v[2 * i + 1], k, mr));
  if (TYPE) row_ext(nullptr, true, TYPE == 2, tok, lane).st(w, 0);
  else {
    row_img(r, row, lane).st(w, 4 * BUF);
    row_img(r + ((row & 31) >= 30), (row & 32) + ((row + 2) & 31), lane).st(w, 2 * BUF);
    if (lane == 1) g_st2[0][r % RD][row] = (__float_as_uint(0.5f * rsq(fmaf(var * rs, rs, 1e-5f))) & ~127u) | (r + 1);
  }
  if (TYPE != 3 && lane == 0) g_stat[tok] = make_float2((var + 1e-5f) * rs * (TYPE ? 1.f : 0.5f), mean + st.y);
}
__device__ __forceinline__ void r2rows(int r, int row, int lane) {
  const int n = row + (lane >> 4);
  const unsigned char* ap = &g_acc[2][r % RD][0] + (uint32_t)(n * 128 + ((lane >> 3) & 1) * 8192 + (((lane ^ n) & 7) << 4));
  uint32_t a[20];
#pragma unroll
  for (int i = 0; i < 5; i++) ldg4(a + 4 * i, ap + i * 16384);
  const uint32_t z = dep0(a[19], lane);
  float s = 0.f, q = 0.f, q2 = 0.f;
#pragma unroll
  for (int i = 0; i < 20; i++) { const float2 h = h2f(a[i] | z); s += h.x + h.y; q = fmaf(h.x, h.x, q); q2 = fmaf(h.y, h.y, q2); }
  q += q2;
  sum2<16>(s, q, lane);
  const float mean = s * (0.5f / DM), rs = rsq(fmaxf(q * (0.25f / DM) - mean * mean, 0.f) + 1e-5f);
  if ((lane & 15) == 0) asm volatile("st.relaxed.gpu.global.u32 [%0], %1;" :: "l"(&g_st2[1][r % RD][n]), "r"((__float_as_uint(0.5f * rs) & ~127u) | (r + 1)) : "memory");
}
__device__ __forceinline__ void r3rows(int r, int row, int tok, int lane, __nv_bfloat16* out) {
  const int n = row + (lane >> 4), m = 32 + ((n - 2) & 31);
  const unsigned char* ap = &g_acc[0][r % RD][0] + (uint32_t)(n * 128 + ((lane >> 3) & 1) * 8192 + (((lane ^ n) & 7) << 4));
  const unsigned char* zp = &g_acc[4][(r + RD - (row == 32)) % RD][0] + (uint32_t)(m * 128 + ((lane >> 3) & 1) * 8192 + (((lane ^ m) & 7) << 4));
  unsigned char* op = reinterpret_cast<unsigned char*>(out) + (uint32_t)((tok + (lane >> 4)) * 1280 + (lane & 15) * 16);
  float2 st;
  asm volatile("ld.relaxed.gpu.global.v2.f32 {%0,%1}, [%2];" : "=f"(st.x), "=f"(st.y) : "l"(g_stat + tok + (lane >> 4)) : "memory");
#pragma unroll 1
  for (int i0 = 0; i0 < 3; i0++) {
    uint32_t a[8], c[8], u[8];
#pragma unroll
    for (int i = 0; i < 2; i++) { ldg4(a + 4 * i, ap + 3 * BUF + i * 16384); ldg4(c + 4 * i, ap + 2 * BUF + i * 16384); ldg4(u + 4 * i, zp + i * 16384); }
    uint32_t z = dep0(u[7], lane);
#pragma unroll
    for (int i = 0; i < 8; i++) {
      const float2 h = h2f(a[i] | z), e = h2f(c[i] | z), g = h2f(u[i] | z);
      a[i] = pack2(fmaf(h.x + e.x, 0.5f, fmaf(g.x, st.x, st.y)), fmaf(h.y + e.y, 0.5f, fmaf(g.y, st.x, st.y)));
      if (i & 1) z = dep0(a[i], lane);
    }
    if (i0 < 2) stg4(op, a);
    stg4(op + 256, a + 4);
    ap += 32768 >> i0; zp += 32768 >> i0; op += 512 >> i0;
  }
}
template <int TYPE>
__device__ __forceinline__ void rloop(int row, int cp, int role, const __nv_bfloat16* x, __nv_bfloat16* out) {
  constexpr int ST = TYPE == 4 ? 2 : TYPE;
  const int r0 = row & 32 ? LAG : 0;
  uint32_t v = 0;
#pragma unroll 1
  for (int r = r0; r < r0 + NSEG + (TYPE > 0); r++) {
    const int tok = (r - r0) * 32 + (row & 31) - (TYPE ? 2 : 0);
    const bool valid = TYPE == 0 || (unsigned)tok < S_LEN;
    const uint32_t* go = &g_f[F_R1 + 4 * ST + cp][r];
    const uint32_t* first = TYPE == 2 ? &g_f[F_R2 + cp][r] : TYPE ? go : (const uint32_t*)&g_xready[NSEG + r - r0][0];
    if constexpr (TYPE == 1 || TYPE == 4) {
      const int lane = await(v, go, NOP * NW12 * NW34, false);
      BTS2(r, 8 + 2 * ST); RTS(0);
      if (TYPE == 1) { r2rows(r, row, lane); BTS2(r, 11); continue; }
      if (valid) r3rows(r, row, tok, lane, out);
    } else {
      if (TYPE || row >= 32) await(v, first, TYPE ? NOP * NW12 * NW34 : 32, true);
      if (valid) rrow<TYPE>(r, row, tok, lane_of(r), go, role, x);
    }
    if (TYPE == 4 && r + RD - 2 >= NSTEP) { v = 0; BTS2(r, 13); continue; }
    const int lane = lane_of(r);
    const void* f = lane ? (const void*)&g_xready[NSEG + (tok >> 5)][0] : (const void*)&g_f[TYPE ? F_DONE : F_Z][r];
    asm volatile("" : "+l"(f));
    __syncwarp();
    RTS(3);
    v = ld_relaxed(first + (TYPE ? 1 : 8));
    asm volatile("fence.release.gpu;" ::: "memory");
    RTS(4);
    red_if(lane == 0 || (TYPE == 2 && lane == 1 && valid) ? (TYPE & 5 ? 2 : 1) : 0, f);
    RTS(5);
    RTS_OUT();
    BTS2(r, 9 + 2 * ST);
  }
}

#define RCV 1
#define SINGLE_OP 3
#define SINGLE_W 0
#define W_DELAY 0
#define BULK_ADD(T, dst, src, len) asm volatile("{\n.reg .pred e;\nelect.sync _|e, 0xffffffff;\n@e cp.reduce.async.bulk.global.shared::cta.bulk_group.add.noftz." T " [%0], [%1], %2;\n}" \
                                               :: "l"(dst), "r"(src), "r"(len) : "memory")
#define COMMIT() asm volatile("cp.async.bulk.commit_group;" ::: "memory")
#define DRAINED(n) do { asm volatile("cp.async.bulk.wait_group.read " #n ";" ::: "memory"); __syncwarp(); } while (0)
#define WRITTEN() do { asm volatile("cp.async.bulk.wait_group 0;\nfence.proxy.async.global;" ::: "memory"); __syncwarp(); } while (0)
__device__ __forceinline__ void wait_flags(const uint32_t* p, uint32_t target) {
  int n = 0;
  while (!__all_sync(~0u, ld_relaxed(p) >= target)) { if (++n > SPIN_LIMIT) FAIL(); }
  asm volatile("fence.acquire.gpu;" ::: "memory");
  asm volatile("fence.proxy.async.global;" ::: "memory");
}
__global__ void __launch_bounds__(512, 1) bworker_kernel(const __grid_constant__ BParams P) {
  extern __shared__ __align__(1024) unsigned char smem_raw[];
  const uint32_t sb = SMEM0, bar = sb + BO_BAR;
  const int wg = __shfl_sync(~0u, threadIdx.x >> 7, 0), warp = __shfl_sync(~0u, (threadIdx.x >> 5) & 3, 0);
  if (threadIdx.x == 0) {
    if (smem_u32(smem_raw) != SMEM0) FAIL();
    uint32_t smid; asm volatile("mov.u32 %0, %%smid;" : "=r"(smid));
    const uint32_t nb = ld_relaxed(&g_tpc[(smid >> 1) & 127]);
    const bool single = nb > 1, far = nb == 0 && (smid < 64 || smid >= 124);
    int kind = far || (single && atomicAdd(&g_f[F_MISC][35], 1u) < SINGLE_OP) ? 0 : single ? 1 + SINGLE_W : 1;
    int rc = (RCV ? smid >= 128 : single) || (smid >> 1) == 16 || (smid >> 1) == 63 ? 1 : far || single ? 2 : 0;
    uint32_t i = atomicAdd(&g_f[F_MISC][32 + kind], 1u), o = atomicAdd(&g_f[F_MISC][36 + rc], 1u);
    while (i >= (kind == 0 ? NOP : kind == 1 ? NW12 : NW34)) { kind = (kind + 1) % 3; i = atomicAdd(&g_f[F_MISC][32 + kind], 1u); }
    while (o >= (rc == 0 ? 16 : rc == 1 ? 8 : 12)) { rc = (rc + 1) % 3; o = atomicAdd(&g_f[F_MISC][36 + rc], 1u); }
    if (RCV && rc == 2) o = single ? 11 - atomicAdd(&g_f[F_MISC][40], 1u) : atomicAdd(&g_f[F_MISC][41], 1u);
    sts64(sb + BO_BOX, i + (kind == 0 ? 0 : kind == 1 ? NOP : NOP + NW12), o + (rc ? 8 + 8 * rc : 0));
    for (int k = 0; k < BB_NUM; k++) mbar_init(bar + 8 * k, k >= BB_USED ? 4 : k >= BB_EMPTY ? 8 : k >= BB_ZFREE && kind ? 2 : 1);
    asm volatile("fence.mbarrier_init.release.cluster;" ::: "memory");
  }
  if (threadIdx.x < 128) sts128(sb + BO_CARRY + threadIdx.x * 16, 0u, 0u, 0u, 0u);
  auto ln0 = [&](int t) {
    const int lane = lane_of(t);
    if (lane < 20 && t + 128 < S_LEN) asm volatile("prefetch.global.L2 [%0];" :: "l"(P.x + (t + (t < 4 * NBC ? 4 * NBC : 128)) * DM + (lane >> 1) * 64));
    rrow<3>(0, 0, t, lane, nullptr, 0, P.x);
    __syncwarp();
    asm volatile("fence.release.gpu;" ::: "memory");
    red_if(lane == 0, &g_xready[t >> 5][0]);
  };
  if (wg == 2) ln0(blockIdx.x * 4 + warp);
  fence_async();
  __syncthreads();
  const int role = uni(lds32(sb + BO_BOX));
  if (threadIdx.x < 32) BTS(94, 1);
  const bool op = role < NOP, w12 = role < NOP + NW12;
  const int j = op ? role : w12 ? role - NOP : role - NOP - NW12;
  const int rot = op ? (j ? 2 * ((j + 1) % 5) : 0) : 2 * (j % 5);
  if (wg == 3) {
    asm volatile("setmaxnreg.dec.sync.aligned.u32 24;");
    LANE_INIT();
    if (warp < 2) {
      auto announce = [&](int r) {
        const uint32_t* f = &g_f[(op ? F_R1 : w12 ? F_R2 : F_R3) + (lane & 3)][r];
        asm volatile("" : "+l"(f));
        if (warp == 0) { mbar_arrive_if(lane == 0, bar + 8 * BB_DONE); return; }
        mbar_waitw(bar + 8 * BB_DONE, r & 1);
        PTS(60);
        asm volatile("fence.release.gpu;" ::: "memory");
        red_if(lane >= 4 ? 0 : op ? NW12 * NW34 : w12 ? NOP * NW34 : NOP * NW12, f);
        PTS(61);
        BTS(r, 4);
      };
      if (op) {
        int mt = rot + warp;
        bar_arrive(NB_FREE + warp, 160);
#pragma unroll 1
        for (int r = 0; r < NSTEP; r++) {
          const uint32_t len = fmask(r) == 3 ? 8192 : 4096;
          unsigned char* acc = &g_acc[j & 1][r % RD][fmask(r) == 2 ? 4096 : 0];
#pragma unroll 1
          for (int p = 0; p < 5; p++) {
            bar_sync(NB_STAGED + warp, 160);
            PTS(50 + 2 * p + warp);
            fence_async();
            BULK_ADD("bf16", acc + mt * 8192, sb + BO_STG + warp * 8192, len);
            COMMIT();
            PTS(64 + 50 + 2 * p + warp);
            mt = mt >= 8 ? mt - 8 : mt + 2;
            DRAINED(0);
            bar_arrive(NB_FREE + warp, 160);
          }
          WRITTEN();
          announce(r);
        }
      } else {
#pragma unroll 1
        for (int r = 0; r < NR; r++) {
          const uint32_t len = bmask(r) == 3 ? 8192 : 4096;
          unsigned char* acc = &g_acc[w12 ? 2 : 3][r % RD][bmask(r) == 2 ? 4096 : 0];
          int mt = rot + warp;
          const bool pairs = len != 8192;
#pragma unroll 1
          for (int p = pairs ? 2 : 0; p < 5; p++) {
            const uint32_t src = sb + (p == 4 ? BO_H : BO_RING_MLP + (2 - (p & 1)) * 16384) + warp * 8192;
            bar_sync(NB_STAGED + (p == 4 ? 4 : 2 * (p & 1)) + warp, 160);
            PTS(50 + 2 * p + warp);
            fence_async();
            BULK_ADD("f16", acc + mt * 8192, src, len);
            mt = mt >= 8 ? mt - 8 : mt + 2;
            if (pairs && p < 4) { BULK_ADD("f16", acc + mt * 8192, src + 4096, len); mt = mt >= 8 ? mt - 8 : mt + 2; }
            COMMIT();
            PTS(64 + 50 + 2 * p + warp);
            if (p == 4 && !pairs) break;
            DRAINED(1);
            mbar_arrive_if(lane == 0, bar + 8 * (p == 1 || p == 2 ? BB_SFREE + 2 * (p - 1) + warp : BB_ZFREE + (p >> 1)));
            mbar_arrive_if(lane < 2 && pairs && p == 2, bar + 8 * (lane ? BB_SFREE + warp : BB_ZFREE));
            if (p == 3 && !pairs) { DRAINED(0); mbar_arrive_if(lane == 0, bar + 8 * (BB_ZFREE + 2)); }
          }
          WRITTEN();
          mbar_arrive_if(lane == 0, bar + 8 * (BB_SFREE + 4 + warp));
          announce(r);
        }
      }
    } else {
      if (op && warp == 2) {
        unsigned char* wt = g_wt + j * (10 * OP_SLOT);
#pragma unroll 1
        for (int m0 = 0; m0 < 10; m0 += 3) {
          const int nu = m0 < 9 ? 9 : 3;
          mbar_expect_if(lane == 0, bar + 8 * BB_TMP, nu * 4096);
#pragma unroll 1
          for (int k = 0; k < nu; k++) tma2d_e(sb + BO_RING_OP + k * 4096, &P.wmap[0], (m0 + k / 3) * 64, 320 * j + 224 + 32 * (k % 3), bar + 8 * BB_TMP);
          mbar_waitw(bar + 8 * BB_TMP, m0 & 1);
          bulk_s2g_e(wt + m0 * OP_SLOT, sb + BO_RING_OP, nu * 4096);
          COMMIT();
          WRITTEN();
        }
        asm volatile("fence.acq_rel.gpu;" ::: "memory");
        int sl = 0, ph = 1, mt = rot;
#pragma unroll 1
        for (int r = -1; r < NSTEP; r++) {
#pragma unroll 1
          for (int n = r < 0 ? 7 : 0; n < (r + 1 < NSTEP ? 10 : 7); n++) {
            mbar_waitw(bar + 8 * (BB_USED + sl), ph);
            mbar_expect_if(lane == 0, bar + 8 * (BB_FULL + sl), OP_SLOT);
            bulk_g2s_e(sb + BO_RING_OP + sl * OP_SLOT, wt + mt * OP_SLOT, OP_SLOT, bar + 8 * (BB_FULL + sl));
            if (++sl == 3) { sl = 0; ph ^= 1; }
            mt = mt == 9 ? 0 : mt + 1;
          }
        }
      } else if (op) {
        mbar_waitw(bar + 8 * BB_START, 0);
#pragma unroll 1
        for (int r = 0; r < NSTEP; r++) {
          const int rb = r - RD + 2;
          const uint32_t len = fmask(r) == 3 ? 8192 : 4096;
          const unsigned char* src = g_o + (uint32_t)(r % RO * (96 * 8192) + 5 * j * len);
          wait_flags(lane < 2 ? &g_f[F_O + (lane ? NOP : j)][r] : rb >= 0 ? &g_f[F_DONE][rb] : &g_f[F_MISC][0],
                     lane < 2 ? (lane ? 1 : 5) : rb >= 0 ? rtarget(bmask(rb)) : NBC * 8);
          PTS1(35);
          if (r) bar_sync(NB_EARLY, 288);
          if (r == LAG) bar_sync(NB_LAST, 288);
          mbar_expect_if(lane < 3, bar + 8 * (BB_OFULL + lane), 2 * len);
          bulk_g2s_e(sb + BO_O, src, 2 * len, bar + 8 * BB_OFULL);
          PTS(62); PTS1(38);
          if (r && r != LAG) bar_sync(NB_LAST, 288);
          bulk_g2s_e(sb + BO_O + 2 * len, src + 2 * len, 2 * len, bar + 8 * (BB_OFULL + 1));
          bulk_g2s_e(sb + BO_O + 4 * len, src + 4 * len, len, bar + 8 * (BB_OFULL + 2));
          bulk_g2s_e(sb + BO_O + 5 * len, src + (95 - 5 * j) * len, len, bar + 8 * (BB_OFULL + 2));
          PTS1(64 + 35);
          BTS(r, 0);
        }
      } else if (warp == 2) {
#pragma unroll 1
        for (int r = 0; r < NR; r++) {
          const int mk = w12 ? fmask(r) : bmask(r);
          if (mk) {
            const unsigned char* src = &g_acc[w12 ? 4 : 2][r % RD][mk == 2 ? 4096 : 0];
            wait_flags(w12 ? &g_f[F_Z][r] : lane && r >= 2 ? &g_f[F_R3 + (j & 3)][r - 2] : &g_f[F_R2 + (j & 3)][r], w12 ? rtarget(mk) : NOP * NW12 * NW34);
#pragma unroll 1
            for (int z = 0; z < 5; z++) {
              const uint32_t fb = bar + 8 * (BB_FULL + z), dst = sb + BO_RING_MLP + 2 * z % 3 * 16384 + (mk == 2 ? 4096 : 0);
              mbar_waitw(bar + 8 * (z < 3 ? BB_ZFREE + z : BB_EMPTY + z - 3), (r + (z < 3)) & 1);
              if (z == 0) PTS(62);
              mbar_expect_if(lane == 0, fb, mk == 3 ? 16384 : 8192);
              bulk_g2s_e(dst, src + z * 16384, mk == 3 ? 16384 : 4096, fb);
              if (mk != 3) bulk_g2s_e(dst + 8192, src + z * 16384 + 8192, 4096, fb);
              if (z == 0) BTS(r, 0);
            }
          }
          if (!w12) {
#pragma unroll 1
            for (int c = j; c < 120; c += NW34) bulk_s2g_e(&g_acc[c < 80 ? c / 40 : 3][(r + (c < 80 ? 0 : 2)) % RD][c % 40 * 2048], sb + BO_CARRY, 2048);
            COMMIT();
            WRITTEN();
          }
          mbar_waitw(bar + 8 * BB_DONE, (r + 1) & 1);
          mbar_arrive_if(lane == 0, bar + 8 * BB_DONE);
        }
      } else {
#pragma unroll 1
        for (int r = 0; r < (w12 ? NSTEP : NR); r++) {
          const bool idle = !((w12 ? fmask(r) : bmask(r)) >> (lane >> 4) & 1);
          uint32_t t0, t1;
          int n = 0;
          mbar_waitw(bar + 8 * BB_FULL, r & 1);
          do {
            asm volatile("ld.relaxed.gpu.global.v2.u32 {%0,%1}, [%2];" : "=r"(t0), "=r"(t1) : "l"(&g_st2[!w12][r % RD][2 * lane]) : "memory");
            if (++n > SPIN_LIMIT) FAIL();
          } while (!__all_sync(~0u, idle || (((t0 ^ (r + 1)) | (t1 ^ (r + 1))) & 127) == 0));
          sts64(sb + BO_STAT + (lane >> 4) * 128 + (lane & 3) * 32 + ((lane >> 2) & 3) * 8, t0, t1);
          __syncwarp();
          mbar_arrive_if(lane == 0, bar + 8 * BB_STAT);
          PTS(63);
        }
      }
    }
    bar_arrive(NB_END, 512);
  } else if (wg == 2) {
    asm volatile("setmaxnreg.dec.sync.aligned.u32 40;");
    const int ord = uni(lds32(sb + BO_BOX + 4));
    const int gw = ord < 16 ? warp * 16 + ord : ord < 24 ? 48 + warp * 8 + ord : !RCV ? 72 + warp * 12 + ord : ord >= 32 ? 97 + 2 * (warp * 4 + ord - 32) : warp < 2 ? 48 + 2 * (warp * 8 + ord) : 88 + warp * 8 + ord, row = gw < 64 ? gw : gw < 96 ? gw - 64 : gw < 128 ? 2 * gw - 192 : 2 * gw - 224;
    if (row >= 32) {
#pragma unroll 1
      for (int t = 4 * NBC + (gw < 64 ? gw - 32 : gw - 80); t < S_LEN; t += 64) ln0(t);
    }
    if (gw < 64) rloop<0>(row, gw & 3, role, P.x, P.out);
    else if (gw < 96) rloop<2>(row, gw & 3, role, P.x, P.out);
    else if (gw < 128) rloop<1>(row, gw & 3, role, P.x, P.out);
    else rloop<4>(row, gw & 3, role, P.x, P.out);
    asm volatile("griddepcontrol.wait;" ::: "memory");
    const int t = threadIdx.x & 127;
    for (int i = (blockIdx.x * 128 + t) * 4; i < 4 * NCL * 2560; i += NBC * 512)
      *reinterpret_cast<uint4*>(&g_part[0][0][0][0] + i) = make_uint4(0u, 0u, 0u, 0u);
    bar_sync(NB_END, 512);
    if (t == 0) {
      uint32_t n;
      asm volatile("atom.acq_rel.gpu.global.add.u32 %0, [%1], 1;" : "=r"(n) : "l"(&g_f[F_MISC][64]) : "memory");
      sts32(sb + BO_BOX, n);
    }
    bar_sync(NB_END2, 128);
    if (lds32(sb + BO_BOX) == NBC - 1) {
      for (int i = t; i < F_NUM * 24; i += 128) reinterpret_cast<uint4*>(&g_f[0][0])[i] = make_uint4(0u, 0u, 0u, 0u);
      g_xready[t][0] = 0; g_tpc[t] = 0;
    }
  } else {
    asm volatile("setmaxnreg.inc.sync.aligned.u32 224;");
    LANE_INIT();
    for (int i = blockIdx.x * 256 + threadIdx.x; i < 2 * (RD + 1) * TILE_B / 16; i += NBC * 256)
      reinterpret_cast<uint4*>(&g_acc[i < 2 * RD * TILE_B / 16 ? 0 : 1][0][0])[i] = make_uint4(0u, 0u, 0u, 0u);
    warp_signal(&g_f[F_MISC][0], lane);
    const int mt0 = (rot + wg) % 10;
    auto boxes = [&](int ss) {
      const int nb = op && ss ? 3 : 4;
      const uint32_t base = sb + (ss ? BO_RES + wg * OP_RES : wg * 83968);
      mbar_expect_if(warp == 0 && lane == 0, bar + 8 * (BB_W + wg), nb * 20480 + (op ? 2048 : 0));
      bar_sync(NB_H, 256);
      if (warp < nb) {
#pragma unroll 1
        for (int i = warp; i < 5 * nb; i += nb) {
          const int p = op ? i / nb : (i - 10) >> 1, mt = (mt0 + 2 * p) % 10;
          const bool first = !op && i < 10;
          tma2d_e(op || !ss ? base + i * 4096 : sb + (first ? BO_W1 : -81920) + (2 * i + wg) * 4096, &P.wmap[op ? 0 : (w12 ? 1 : 3) + !first], first ? 128 * j + 64 * wg : mt * 64,
                  op ? 320 * j + 64 * warp + 32 * ss : first ? 64 * i + 32 * ss : 128 * j + 32 * (i & 1) + 64 * ss, bar + 8 * (BB_W + wg));
        }
      }
      if (op && warp == 3) tma2d_e(base + nb * 20480, &P.wo16, (mt0 + 2 * ss) % 10 * 64, 95 * 64 + (j + 1) / 5 * 16, bar + 8 * (BB_W + wg));
      mbar_waitw(bar + 8 * (BB_W + wg), ss);
    };
    if (W_DELAY && !op) __nanosleep(W_DELAY);
    uint32_t W[164];
    boxes(0);
    load_w<41>(W, sb + wg * 83968, warp, lane);
    fence_async();
    boxes(1);
    if (!op) {
      float cs[2] = {0.f, 0.f};
      const uint32_t a0 = sb + BO_W1 + wg * 4096 + ((lane >> 4) * 8 + (lane & 7)) * 128 + (((warp * 2 + ((lane >> 3) & 1)) ^ (lane & 7)) << 4);
#pragma unroll
      for (int i = 0; i < 80; i++) cs[i & 1] += bf_lo(W[i]) + bf_hi(W[i]);
#pragma unroll 1
      for (int i = 0; i < 40; i++) {
        uint32_t t[4];
        const uint32_t ad = a0 + (i % 20 >> 1) * 8192 + (i & 1) * 2048;
        ldsm4t(t[0], t[1], t[2], t[3], ad);
#pragma unroll
        for (int k = 0; k < 4; k++) {
          if (i < 20) cs[k & 1] += bf_lo(t[k]) + bf_hi(t[k]);
          t[k] = pack2h(bf_lo(t[k]) - cs[k & 1], bf_hi(t[k]) - cs[k & 1]);
        }
        if (i >= 20) stsm4t(ad, t[0], t[1], t[2], t[3]);
        if (i == 19) {
#pragma unroll
          for (int k = 0; k < 2; k++) { cs[k] += __shfl_xor_sync(~0u, cs[k], 1); cs[k] += __shfl_xor_sync(~0u, cs[k], 2); cs[k] *= 1.f / DM; }
        }
      }
      const uint32_t z = dep0(__float_as_uint(cs[0]), lane);
#pragma unroll
      for (int i = 0; i < 80; i++) W[i] = pack2h(bf_lo(W[i] | z) - cs[i & 1], bf_hi(W[i] | z) - cs[i & 1]);
      fence_async();
      bar_sync(NB_H, 256);
    }
    if (warp == 0) BTS(94, 6 + wg);
    const Dsc blo = {P.desc, 1}, alo = blo + wg * (op ? OP_RES / 16 : 256);
    if (op) {
      Ring rg = {(uint32_t)wg, 0};
      mbar_arrive_if(lane == 0, bar + 8 * BB_START);
      if (wg) bar_arrive(NB_PP, 256);
      const Dsc xlo = blo + (j + 1) / 5 * 2;
#pragma unroll 1
      for (int r = 0; r < NSTEP; r++) {
        asm volatile("" : "+r"(lane));
        if (fmask(r) == 3) op_round<64>(W, bar, alo, blo, xlo, j == 0, rg, wg, warp, lane, r);
        else op_round<32>(W, bar, alo, blo, xlo, j == 0, rg, wg, warp, lane, r);
        if (warp == 0) BTS(r, 2 + wg);
      }
    } else {
      const int q4 = (128 * j + 64 * wg + 16 * warp) / 160, off = w12 ? (0x0413 >> (4 * q4)) & 7 : 0;
#pragma unroll 1
      for (int r = 0; r < NR; r++) {
        asm volatile("" : "+r"(lane));
        const int bm = bmask(r), fm = w12 ? fmask(r) : bm;
        if (fm == 3) phase1<64>(W, sb, alo, blo, 0, wg, warp, lane, off, r);
        else if (fm) phase1<32>(W, sb, alo, blo + (fm >> 1) * 256, fm >> 1, wg, warp, lane, off, r);
        else { mbar_waitu(bar + 8 * (BB_SFREE + 4 + wg), (r + 1) & 1); carry_in(sb, wg, warp, lane); }
        CTS(33);
        fence_async();
        bar_sync(NB_H, 256);
        if (wg + warp == 0) BTS(r, 1);
        if (bm == 3) phase2<64>(W, bar, alo, blo, wg, warp, lane, r);
        else phase2<32>(W, bar, alo, blo + (bm >> 1) * 256, wg, warp, lane, r);
        if (warp == 0) BTS(r, 2 + wg);
      }
    }
    CTS_OUT();
    bar_arrive(NB_END, 512);
  }
}

typedef CUresult (*EncodeFn)(CUtensorMap*, CUtensorMapDataType, cuuint32_t, void*, const cuuint64_t*, const cuuint64_t*, const cuuint32_t*,
                             const cuuint32_t*, CUtensorMapInterleave, CUtensorMapSwizzle, CUtensorMapL2promotion, CUtensorMapFloatOOBfill);
static void make_map(EncodeFn fn, CUtensorMap* tm, const void* ptr, uint64_t cols, uint64_t rows, uint32_t bc, uint32_t br) {
  cuuint64_t dims[2] = {cols, rows}; cuuint64_t strides[1] = {cols * 2}; cuuint32_t box[2] = {bc, br}; cuuint32_t es[2] = {1, 1};
  fn(tm, CU_TENSOR_MAP_DATA_TYPE_BFLOAT16, 2, const_cast<void*>(ptr), dims, strides, box, es, CU_TENSOR_MAP_INTERLEAVE_NONE,
     CU_TENSOR_MAP_SWIZZLE_128B, CU_TENSOR_MAP_L2_PROMOTION_L2_256B, CU_TENSOR_MAP_FLOAT_OOB_FILL_NONE);
}
#define dbg_a_only 0
extern "C" void kernel_launch(void* const* d_in, const int* in_sizes, int n_in, void* d_out, int out_size) {
  void* fnp = nullptr; cudaDriverEntryPointQueryResult qr;
  cudaGetDriverEntryPoint("cuTensorMapEncodeTiled", &fnp, cudaEnableDefault, &qr);
  EncodeFn fn = (EncodeFn)fnp;
  cudaStream_t st = cudaStreamPerThread;
  cudaFuncSetAttribute(bworker_kernel, cudaFuncAttributeMaxDynamicSharedMemorySize, B_SMEM);
  {
    AMaps M;
    for (int i = 0; i < 3; i++) make_map(fn, &M.w16[i], d_in[2 + i], HD, DM, 64, 16);
    M.wv = (const __nv_bfloat16*)d_in[4];
    make_map(fn, &M.wo32, d_in[5], DM, HD, 64, 32);
    const uint32_t hi[5] = {dhi(TILE_SBO, 3), dhi(1024, 1), dhi(1024, 0), dhi(PL_SZ, 0), dhi(896, 0)};
    for (int i = 0; i < 5; i++) M.d[i] = (uint64_t)hi[i] << 32;
    cudaFuncSetAttribute(acore_kernel, cudaFuncAttributeMaxDynamicSharedMemorySize, A_SMEM);
    cudaFuncSetAttribute(acore_kernel, cudaFuncAttributeNonPortableClusterSizeAllowed, 1);
    cudaLaunchConfig_t cfg = {};
    cfg.gridDim = dim3(CL_SIZE * NCL); cfg.blockDim = dim3(512); cfg.dynamicSmemBytes = A_SMEM; cfg.stream = st;
    cudaLaunchAttribute at[1]; at[0].id = cudaLaunchAttributeClusterDimension;
    at[0].val.clusterDim.x = CL_SIZE; at[0].val.clusterDim.y = 1; at[0].val.clusterDim.z = 1;
    cfg.attrs = at; cfg.numAttrs = 1;
    cudaLaunchKernelEx(&cfg, acore_kernel, M, (const __nv_bfloat16*)d_in[1], dbg_a_only ? 0 : 1);
  }
  if (!dbg_a_only) {
    BParams P;
    make_map(fn, &P.wmap[0], d_in[5], DM, HD, 64, 32);
    make_map(fn, &P.wo16, d_in[5], DM, HD, 64, 16);
    make_map(fn, &P.wmap[1], d_in[8], DM, DM, 64, 32);
    make_map(fn, &P.wmap[2], d_in[9], DM, DM, 64, 32);
    make_map(fn, &P.wmap[3], d_in[10], FF, DM, 64, 32);
    make_map(fn, &P.wmap[4], d_in[11], DM, FF, 64, 32);
    P.x = (const __nv_bfloat16*)d_in[0];
    P.out = (__nv_bfloat16*)d_out;
    P.desc = (uint64_t)dhi(1024, 1) << 32;
    cudaLaunchConfig_t cfg = {};
    cfg.gridDim = dim3(NBC); cfg.blockDim = dim3(512); cfg.dynamicSmemBytes = B_SMEM; cfg.stream = st;
    cudaLaunchAttribute at[1]; at[0].id = cudaLaunchAttributeProgrammaticStreamSerialization; at[0].val.programmaticStreamSerializationAllowed = 1;
    cfg.attrs = at; cfg.numAttrs = 1;
    cudaLaunchKernelEx(&cfg, bworker_kernel, P);
  }
}
```

```cpp
#include <cuda_runtime.h>
#include <cuda_bf16.h>
#include <cuda.h>
#include <stdint.h>

#define S_LEN 2048
#define DM 640
#define NH 32
#define DH 192
#define HD 6144
#define NSEG 64
#define FF 1536

__device__ __forceinline__ uint32_t smem_u32(const void* p) { return (uint32_t)__cvta_generic_to_shared(p); }
__device__ __forceinline__ uint32_t mapa(uint32_t a, uint32_t r) {
  uint32_t o; asm volatile("mapa.shared::cluster.u32 %0, %1, %2;" : "=r"(o) : "r"(a), "r"(r)); return o; }
__device__ __forceinline__ void mbar_init(uint32_t b, uint32_t c) {
  asm volatile("mbarrier.init.shared::cta.b64 [%0], %1;" :: "r"(b), "r"(c) : "memory"); }
__device__ __forceinline__ void mbar_expect(uint32_t b, uint32_t tx) {
  asm volatile("mbarrier.arrive.expect_tx.shared::cta.b64 _, [%0], %1;" :: "r"(b), "r"(tx) : "memory"); }
__device__ __forceinline__ void mbar_arrive(uint32_t b) {
  asm volatile("mbarrier.arrive.shared::cta.b64 _, [%0];" :: "r"(b) : "memory"); }
__device__ __forceinline__ void mbar_arrive_remote(uint32_t rb) {
  asm volatile("mbarrier.arrive.relaxed.cluster.shared::cluster.b64 _, [%0];" :: "r"(rb) : "memory"); }
__device__ __forceinline__ void mbar_expect_if(bool p, uint32_t b, uint32_t tx) {
  asm volatile("{\n.reg .pred q;\nsetp.ne.u32 q, %2, 0;\n@q mbarrier.arrive.expect_tx.shared::cta.b64 _, [%0], %1;\n}" :: "r"(b), "r"(tx), "r"((uint32_t)p) : "memory"); }
__device__ __forceinline__ void mbar_arrive_if(bool p, uint32_t b) {
  asm volatile("{\n.reg .pred q;\nsetp.ne.u32 q, %1, 0;\n@q mbarrier.arrive.shared::cta.b64 _, [%0];\n}" :: "r"(b), "r"((uint32_t)p) : "memory"); }
__device__ __forceinline__ void mbar_arrive_remote_if(bool p, uint32_t rb) {
  asm volatile("{\n.reg .pred q;\nsetp.ne.u32 q, %1, 0;\n@q mbarrier.arrive.relaxed.cluster.shared::cluster.b64 _, [%0];\n}" :: "r"(rb), "r"((uint32_t)p) : "memory"); }
__device__ __forceinline__ void sts32_if(bool p, uint32_t a, uint32_t v) {
  asm volatile("{\n.reg .pred q;\nsetp.ne.u32 q, %2, 0;\n@q st.shared.b32 [%0], %1;\n}" :: "r"(a), "r"(v), "r"((uint32_t)p) : "memory"); }
__device__ __forceinline__ void sts128z_if(bool p, uint32_t a) {
  asm volatile("{\n.reg .pred q;\nsetp.ne.u32 q, %1, 0;\n@q st.shared.v4.b32 [%0], {0,0,0,0};\n}" :: "r"(a), "r"((uint32_t)p) : "memory"); }
__device__ __forceinline__ bool mbar_try(uint32_t b, uint32_t ph) {
  uint32_t ok;
  asm volatile("{\n.reg .pred p;\nmbarrier.try_wait.parity.shared::cta.b64 p, [%1], %2;\nselp.u32 %0, 1, 0, p;\n}"
               : "=r"(ok) : "r"(b), "r"(ph) : "memory");
  return ok; }
__device__ __forceinline__ bool mbar_test(uint32_t b, uint32_t ph) {
  uint32_t ok;
  asm volatile("{\n.reg .pred p;\nmbarrier.test_wait.parity.shared::cta.b64 p, [%1], %2;\nselp.u32 %0, 1, 0, p;\n}"
               : "=r"(ok) : "r"(b), "r"(ph) : "memory");
  return ok; }
#define SPIN_LIMIT 4000000
#define FAIL() asm volatile("st.global.u32 [%0], 0;" :: "l"(8ull) : "memory")
#define CFENCE() asm volatile("fence.proxy.async::generic.acquire.sync_restrict::shared::cluster.cluster;" ::: "memory")
__device__ __forceinline__ void mbar_wait(uint32_t b, uint32_t ph) {
  int n = 0;
  while (!mbar_try(b, ph)) { if (++n > SPIN_LIMIT) FAIL(); } }
#define TIMEOUT_ACT "@!p st.shared.u32 [%0+1], 0;"
#define WAIT_HINT ", 20000"
#define WAIT_LIM "200000"
__device__ __forceinline__ void mbar_slow(uint32_t b, uint32_t ph) {
  asm volatile("{\n.reg .pred p, q;\n.reg .u32 n;\nmov.u32 n, 0;\n"
               "WL:\nmbarrier.try_wait.parity.shared::cta.b64 p, [%0], %1" WAIT_HINT ";\nadd.u32 n, n, 1;\nsetp.lt.and.u32 q, n, " WAIT_LIM ", !p;\n@q bra.uni WL;\n"
               TIMEOUT_ACT "\n}" :: "r"(b), "r"(ph) : "memory"); }
__device__ __forceinline__ void mbar_waitw(uint32_t b, uint32_t ph) {
  asm volatile("{\n.reg .pred p, q;\n.reg .u32 n;\nmbarrier.try_wait.parity.shared::cta.b64 p, [%0], %1;\n@p bra.uni WD;\nmov.u32 n, 0;\n"
               "WL:\nmbarrier.try_wait.parity.shared::cta.b64 p, [%0], %1" WAIT_HINT ";\nadd.u32 n, n, 1;\nsetp.lt.and.u32 q, n, " WAIT_LIM ", !p;\n@q bra.uni WL;\n"
               TIMEOUT_ACT "\nWD:\n}" :: "r"(b), "r"(ph) : "memory"); }
__device__ __forceinline__ void mbar_waitw2(uint32_t b0, uint32_t b1, uint32_t ph) {
  uint32_t ok;
  asm volatile("{\n.reg .pred p, r;\nmbarrier.try_wait.parity.shared::cta.b64 p, [%1], %3;\nmbarrier.try_wait.parity.shared::cta.b64 r, [%2], %3;\n"
               "and.pred p, p, r;\nselp.u32 %0, 1, 0, p;\n}" : "=r"(ok) : "r"(b0), "r"(b1), "r"(ph) : "memory");
  if (__builtin_expect(!__all_sync(~0u, ok), 0)) { mbar_slow(b0, ph); mbar_slow(b1, ph); }
}
__device__ __forceinline__ void mbar_waitu(uint32_t b, uint32_t ph) {
  asm volatile("{\n.reg .pred p;\nmbarrier.try_wait.parity.shared::cta.b64 p, [%0], %1;\n@p bra.uni WD;\n"
               "WL:\nmbarrier.try_wait.parity.shared::cta.b64 p, [%0], %1" WAIT_HINT ";\n@!p bra.uni WL;\nWD:\n}" :: "r"(b), "r"(ph) : "memory"); }
__device__ __forceinline__ void mbar_waitu2(uint32_t b0, uint32_t b1, uint32_t ph) {
  asm volatile("{\n.reg .pred p, r;\nWL:\nmbarrier.try_wait.parity.shared::cta.b64 p, [%0], %2;\nmbarrier.try_wait.parity.shared::cta.b64 r, [%1], %2;\n"
               "and.pred p, p, r;\n@!p bra.uni WL;\n}" :: "r"(b0), "r"(b1), "r"(ph) : "memory"); }
__device__ __forceinline__ void mbar_waitw4(uint32_t b, uint32_t ph) { mbar_waitw2(b, b + 8, ph); mbar_waitw2(b + 16, b + 24, ph); }
__device__ __forceinline__ uint32_t clock32() { uint32_t t; asm volatile("mov.u32 %0, %%clock;" : "=r"(t) :: "memory"); return t; }
template <int L> __device__ __forceinline__ uint32_t lop3(uint32_t a, uint32_t b, uint32_t c) {
  uint32_t r; asm("lop3.b32 %0, %1, %2, %3, %4;" : "=r"(r) : "r"(a), "r"(b), "r"(c), "n"(L)); return r; }
__device__ __forceinline__ void st_async_v2_if(bool p, uint32_t a, uint32_t v0, uint32_t v1, uint32_t mb) {
  asm volatile("{\n.reg .pred q;\nsetp.ne.u32 q, %4, 0;\n@q st.async.weak.shared::cluster.mbarrier::complete_tx::bytes.v2.b32 [%0], {%1,%2}, [%3];\n}"
               :: "r"(a), "r"(v0), "r"(v1), "r"(mb), "r"((uint32_t)p) : "memory"); }
__device__ __forceinline__ void keep4(const uint32_t* r, int lane) {
  asm volatile("{\n.reg .pred q;\nsetp.lt.s32 q, %4, 0;\n@q st.shared.v4.b32 [%4], {%0,%1,%2,%3};\n}" :: "r"(r[0]), "r"(r[1]), "r"(r[2]), "r"(r[3]), "r"(lane) : "memory"); }
__device__ __forceinline__ void fence_sched(int i) {
  asm volatile("{\n.reg .pred q;\nsetp.gt.s32 q, %0, 4096;\n@q st.shared.u32 [%0], 0;\n}" :: "r"(i) : "memory"); }
__device__ __forceinline__ uint32_t hmax2bf(uint32_t a, uint32_t b) { uint32_t r; asm("max.bf16x2 %0, %1, %2;" : "=r"(r) : "r"(a), "r"(b)); return r; }
__device__ __forceinline__ uint32_t uni(uint32_t x) { return __shfl_sync(~0u, x, 0); }
__device__ __forceinline__ void bulk_g2s_mc_e(uint32_t dst, const void* src, uint32_t bytes, uint32_t mb, uint16_t mask) {
  asm volatile("{\n.reg .pred e;\nelect.sync _|e, 0xffffffff;\n"
               "@e cp.async.bulk.shared::cluster.global.mbarrier::complete_tx::bytes.multicast::cluster [%0], [%1], %2, [%3], %4;\n}"
               :: "r"(dst), "l"(src), "r"(bytes), "r"(mb), "h"(mask) : "memory"); }
__device__ __forceinline__ void bulk_s2g_e(void* dst, uint32_t src, uint32_t bytes) {
  asm volatile("{\n.reg .pred e;\nelect.sync _|e, 0xffffffff;\n@e cp.async.bulk.global.shared::cta.bulk_group [%0], [%1], %2;\n}"
               :: "l"(dst), "r"(src), "r"(bytes) : "memory"); }
__device__ __forceinline__ void bulk_g2s_e(uint32_t dst, const void* src, uint32_t bytes, uint32_t mb) {
  asm volatile("{\n.reg .pred e;\nelect.sync _|e, 0xffffffff;\n@e cp.async.bulk.shared::cluster.global.mbarrier::complete_tx::bytes [%0], [%1], %2, [%3];\n}"
               :: "r"(dst), "l"(src), "r"(bytes), "r"(mb) : "memory"); }
#define STREAM_HINT 1
__device__ __forceinline__ void bulk_s2g_es(void* dst, uint32_t src, uint32_t bytes) {
  asm volatile("{\n.reg .pred e;\n.reg .b64 pol;\ncreatepolicy.fractional.L2::evict_first.b64 pol;\nelect.sync _|e, 0xffffffff;\n"
               "@e cp.async.bulk.global.shared::cta.bulk_group.L2::cache_hint [%0], [%1], %2, pol;\n}" :: "l"(dst), "r"(src), "r"(bytes) : "memory");
}
__device__ __forceinline__ void bulk_g2s_es(uint32_t dst, const void* src, uint32_t bytes, uint32_t mb) {
  asm volatile("{\n.reg .pred e;\n.reg .b64 pol;\ncreatepolicy.fractional.L2::evict_first.b64 pol;\nelect.sync _|e, 0xffffffff;\n"
               "@e cp.async.bulk.shared::cluster.global.mbarrier::complete_tx::bytes.L2::cache_hint [%0], [%1], %2, [%3], pol;\n}"
               :: "r"(dst), "l"(src), "r"(bytes), "r"(mb) : "memory"); }
__device__ __forceinline__ void tma2d_e(uint32_t dst, const CUtensorMap* tm, int c0, int c1, uint32_t mb) {
  asm volatile("{\n.reg .pred e;\nelect.sync _|e, 0xffffffff;\n"
               "@e cp.async.bulk.tensor.2d.shared::cluster.global.mbarrier::complete_tx::bytes [%0], [%1, {%3, %4}], [%2];\n}"
               :: "r"(dst), "l"((uint64_t)tm), "r"(mb), "r"(c0), "r"(c1) : "memory"); }
__device__ __forceinline__ uint32_t hadd2bf(uint32_t a, uint32_t b) {
  uint32_t r; asm("add.rn.bf16x2 %0, %1, %2;" : "=r"(r) : "r"(a), "r"(b)); return r; }
__device__ __forceinline__ void cluster_sync_all() {
  asm volatile("barrier.cluster.arrive.release.aligned;\nbarrier.cluster.wait.acquire.aligned;" ::: "memory"); }
__device__ __forceinline__ void bar_arrive(int id, int n) { asm volatile("bar.arrive %0, %1;" :: "r"(id), "r"(n) : "memory"); }
__device__ __forceinline__ void bar_arrive_dep(int id, int n, uint32_t dep) {
  asm volatile("{\n.reg .u32 t;\nand.b32 t, %2, 0;\nadd.u32 t, t, %0;\nbar.sync t, %1;\n}" :: "r"(id), "r"(n), "r"(dep) : "memory"); }
__device__ __forceinline__ void bar_sync(int id, int n) { asm volatile("bar.sync %0, %1;" :: "r"(id), "r"(n) : "memory"); }
__device__ __forceinline__ void fence_async() { asm volatile("fence.proxy.async.shared::cta;" ::: "memory"); }
__device__ __forceinline__ void st_async_b32(uint32_t a, uint32_t v, uint32_t mb) {
  asm volatile("st.async.weak.shared::cluster.mbarrier::complete_tx::bytes.b32 [%0], %1, [%2];" :: "r"(a), "r"(v), "r"(mb) : "memory"); }
__device__ __forceinline__ void st_async_v2(uint32_t a, uint32_t v0, uint32_t v1, uint32_t mb) {
  asm volatile("st.async.weak.shared::cluster.mbarrier::complete_tx::bytes.v2.b32 [%0], {%1,%2}, [%3];" :: "r"(a), "r"(v0), "r"(v1), "r"(mb) : "memory"); }
__device__ __forceinline__ void st_async_v4(uint32_t a, uint32_t v0, uint32_t v1, uint32_t v2, uint32_t v3, uint32_t mb) {
  asm volatile("st.async.weak.shared::cluster.mbarrier::complete_tx::bytes.v4.b32 [%0], {%1,%2,%3,%4}, [%5];" :: "r"(a), "r"(v0), "r"(v1), "r"(v2), "r"(v3), "r"(mb) : "memory"); }
__device__ __forceinline__ void ldsm4(uint32_t& r0, uint32_t& r1, uint32_t& r2, uint32_t& r3, uint32_t a) {
  asm volatile("ldmatrix.sync.aligned.m8n8.x4.shared.b16 {%0,%1,%2,%3}, [%4];" : "=r"(r0), "=r"(r1), "=r"(r2), "=r"(r3) : "r"(a) : "memory"); }
__device__ __forceinline__ void ldsm4t(uint32_t& r0, uint32_t& r1, uint32_t& r2, uint32_t& r3, uint32_t a) {
  asm volatile("ldmatrix.sync.aligned.m8n8.x4.trans.shared.b16 {%0,%1,%2,%3}, [%4];" : "=r"(r0), "=r"(r1), "=r"(r2), "=r"(r3) : "r"(a) : "memory"); }
__device__ __forceinline__ void stsm2t(uint32_t a, uint32_t r0, uint32_t r1) {
  asm volatile("stmatrix.sync.aligned.m8n8.x2.trans.shared.b16 [%0], {%1,%2};" :: "r"(a), "r"(r0), "r"(r1) : "memory"); }
__device__ __forceinline__ void stsm4t(uint32_t a, uint32_t r0, uint32_t r1, uint32_t r2, uint32_t r3) {
  asm volatile("stmatrix.sync.aligned.m8n8.x4.trans.shared.b16 [%0], {%1,%2,%3,%4};" :: "r"(a), "r"(r0), "r"(r1), "r"(r2), "r"(r3) : "memory"); }
__device__ __forceinline__ uint32_t movm(uint32_t a) {
  uint32_t d; asm volatile("movmatrix.sync.aligned.m8n8.trans.b16 %0, %1;" : "=r"(d) : "r"(a)); return d; }
__device__ __forceinline__ void mma16816(float* d, uint32_t a0, uint32_t a1, uint32_t a2, uint32_t a3, uint32_t b0, uint32_t b1) {
  asm("mma.sync.aligned.m16n8k16.row.col.f32.bf16.bf16.f32 {%0,%1,%2,%3}, {%4,%5,%6,%7}, {%8,%9}, {%0,%1,%2,%3};"
               : "+f"(d[0]), "+f"(d[1]), "+f"(d[2]), "+f"(d[3]) : "r"(a0), "r"(a1), "r"(a2), "r"(a3), "r"(b0), "r"(b1)); }
__device__ __forceinline__ void mma16816v(float* d, uint32_t a0, uint32_t a1, uint32_t a2, uint32_t a3, uint32_t b0, uint32_t b1) {
  asm volatile("mma.sync.aligned.m16n8k16.row.col.f32.bf16.bf16.f32 {%0,%1,%2,%3}, {%4,%5,%6,%7}, {%8,%9}, {%0,%1,%2,%3};"
               : "+f"(d[0]), "+f"(d[1]), "+f"(d[2]), "+f"(d[3]) : "r"(a0), "r"(a1), "r"(a2), "r"(a3), "r"(b0), "r"(b1)); }
__device__ __forceinline__ uint32_t pack2(float lo, float hi) {
  uint32_t r; asm("cvt.rn.bf16x2.f32 %0, %1, %2;" : "=r"(r) : "f"(hi), "f"(lo)); return r; }
__device__ __forceinline__ uint32_t pack2v(float lo, float hi) {
  uint32_t r; asm volatile("cvt.rn.bf16x2.f32 %0, %1, %2;" : "=r"(r) : "f"(hi), "f"(lo)); return r; }
__device__ __forceinline__ float bf_lo(uint32_t w) { return __uint_as_float(w << 16); }
__device__ __forceinline__ float bf_hi(uint32_t w) { return __uint_as_float(w & 0xffff0000u); }
__device__ __forceinline__ uint4 lds128(uint32_t a) {
  uint4 v; asm volatile("ld.shared.v4.b32 {%0,%1,%2,%3}, [%4];" : "=r"(v.x), "=r"(v.y), "=r"(v.z), "=r"(v.w) : "r"(a) : "memory"); return v; }
__device__ __forceinline__ uint4 lds128_nv(uint32_t a) {
  uint4 v; asm volatile("ld.shared.v4.b32 {%0,%1,%2,%3}, [%4];" : "=r"(v.x), "=r"(v.y), "=r"(v.z), "=r"(v.w) : "r"(a)); return v; }
__device__ __forceinline__ void st_async_v2_nm(uint32_t a, uint32_t v0, uint32_t v1, uint32_t mb) {
  asm volatile("st.async.weak.shared::cluster.mbarrier::complete_tx::bytes.v2.b32 [%0], {%1,%2}, [%3];" :: "r"(a), "r"(v0), "r"(v1), "r"(mb)); }
__device__ __forceinline__ float rcpf(float x) { float y; asm("rcp.approx.ftz.f32 %0, %1;" : "=f"(y) : "f"(x)); return y; }
__device__ __forceinline__ void sts64(uint32_t a, uint32_t x, uint32_t y) { asm volatile("st.shared.v2.b32 [%0], {%1,%2};" :: "r"(a), "r"(x), "r"(y) : "memory"); }
__device__ __forceinline__ float ex2(float x) { float y; asm("ex2.approx.ftz.f32 %0, %1;" : "=f"(y) : "f"(x)); return y; }
__device__ __forceinline__ uint32_t lds32(uint32_t a) {
  uint32_t v; asm volatile("ld.shared.b32 %0, [%1];" : "=r"(v) : "r"(a) : "memory"); return v; }
__device__ __forceinline__ uint2 lds64(uint32_t a) {
  uint2 v; asm volatile("ld.shared.v2.b32 {%0,%1}, [%2];" : "=r"(v.x), "=r"(v.y) : "r"(a) : "memory"); return v; }
__device__ __forceinline__ void sts128(uint32_t a, uint32_t x, uint32_t y, uint32_t z, uint32_t w) {
  asm volatile("st.shared.v4.b32 [%0], {%1,%2,%3,%4};" :: "r"(a), "r"(x), "r"(y), "r"(z), "r"(w) : "memory"); }
__device__ __forceinline__ void sts32(uint32_t a, uint32_t x) { asm volatile("st.shared.b32 [%0], %1;" :: "r"(a), "r"(x) : "memory"); }
__device__ __forceinline__ void tma2d(uint32_t dst, const CUtensorMap* tm, int c0, int c1, uint32_t mb) {
  asm volatile("cp.async.bulk.tensor.2d.shared::cluster.global.mbarrier::complete_tx::bytes [%0], [%1, {%3, %4}], [%2];"
               :: "r"(dst), "l"((uint64_t)tm), "r"(mb), "r"(c0), "r"(c1) : "memory"); }
__device__ __forceinline__ void tma2d_prefetch(const CUtensorMap* tm, int c0, int c1) {
  asm volatile("cp.async.bulk.prefetch.tensor.2d.L2.global.tile [%0, {%1, %2}];" :: "l"((uint64_t)tm), "r"(c0), "r"(c1) : "memory"); }
__device__ __forceinline__ void bulk_g2s_mc(uint32_t dst, const void* src, uint32_t bytes, uint32_t mb, uint16_t mask) {
  asm volatile("cp.async.bulk.shared::cluster.global.mbarrier::complete_tx::bytes.multicast::cluster [%0], [%1], %2, [%3], %4;"
               :: "r"(dst), "l"(src), "r"(bytes), "r"(mb), "h"(mask) : "memory"); }
__device__ __forceinline__ void bulk_s2g(void* dst, uint32_t src, uint32_t bytes) {
  asm volatile("cp.async.bulk.global.shared::cta.bulk_group [%0], [%1], %2;" :: "l"(dst), "r"(src), "r"(bytes) : "memory"); }
__device__ __forceinline__ void wg_fence() { asm volatile("wgmma.fence.sync.aligned;" ::: "memory"); }
__device__ __forceinline__ void wg_commit() { asm volatile("wgmma.commit_group.sync.aligned;" ::: "memory"); }
template <int N> __device__ __forceinline__ void wg_wait() { asm volatile("wgmma.wait_group.sync.aligned %0;" :: "n"(N) : "memory"); }
__device__ __forceinline__ uint64_t mkdesc(uint32_t addr, uint32_t lbo, uint32_t sbo, uint32_t swz) {
  return (uint64_t)((addr & 0x3FFFF) >> 4) | ((uint64_t)(lbo >> 4) << 16) | ((uint64_t)(sbo >> 4) << 32) | ((uint64_t)swz << 62); }

#define ACC4(d) "+f"(d[0]),"+f"(d[1]),"+f"(d[2]),"+f"(d[3])
#define ACC8(d) ACC4(d), ACC4((d + 4))
#define ACC16(d) ACC8(d), ACC8((d + 8))
#define ACC20(d) ACC16(d), ACC4((d + 16))
#define ACC24(d) ACC16(d), ACC8((d + 16))
#define SMEM0 0x400
__host__ __device__ constexpr uint32_t dlo(uint32_t off, uint32_t lbo) { return ((SMEM0 + off) >> 4) | ((lbo >> 4) << 16); }
__host__ __device__ constexpr uint32_t dhi(uint32_t sbo, uint32_t swz) { return (sbo >> 4) | (swz << 30); }
#define R4S "{%0,%1,%2,%3}"
#define R8S "{%0,%1,%2,%3,%4,%5,%6,%7}"
#define R16S "{%0,%1,%2,%3,%4,%5,%6,%7,%8,%9,%10,%11,%12,%13,%14,%15}"
#define R20S "{%0,%1,%2,%3,%4,%5,%6,%7,%8,%9,%10,%11,%12,%13,%14,%15,%16,%17,%18,%19}"
#define R24S "{%0,%1,%2,%3,%4,%5,%6,%7,%8,%9,%10,%11,%12,%13,%14,%15,%16,%17,%18,%19,%20,%21,%22,%23}"
#define ACC32(d) ACC16(d), ACC16((d + 16))
#define R32S "{%0,%1,%2,%3,%4,%5,%6,%7,%8,%9,%10,%11,%12,%13,%14,%15,%16,%17,%18,%19,%20,%21,%22,%23,%24,%25,%26,%27,%28,%29,%30,%31}"
struct Dsc {
  uint64_t b; uint32_t e;
  __device__ __forceinline__ Dsc operator+(uint32_t o) const { return {b + o, e}; }
};
template <int K> __device__ __forceinline__ uint32_t fresh(int i) {
  uint32_t e; asm volatile("{\n.reg .u32 t;\nadd.u32 t, %1, %2;\nshr.u32 %0, t, %3;\n}" : "=r"(e) : "r"(i), "n"((256 << K) + 1), "n"(8 + K)); return e; }
template <int N, bool H = false> struct MM;
#define DEF_MM(N, H, T, ACCM, RS_, I0, I1, I2, I3, I4, I5, I6, I7)                                                                \
  template <> struct MM<N, H> {                                                                                                   \
    template <uint32_t BLO, int ACC>                                                                                              \
    static __device__ __forceinline__ void rs(float* d, const uint32_t* a, Dsc b0) {                                              \
      asm volatile("{\n.reg .b64 b;\nmad.wide.u32 b, %" #I7 ", %" #I5 ", %" #I4 ";\n"                                             \
                   "wgmma.mma_async.sync.aligned.m64n" #N "k16.f32." T "." T " " RS_ ", {%" #I0 ",%" #I1 ",%" #I2 ",%" #I3 "}, b, %" #I6 ", 1, 1, 0;\n}" \
                   : ACCM(d) : "r"(a[0]), "r"(a[1]), "r"(a[2]), "r"(a[3]), "l"(b0.b), "n"(BLO), "n"(ACC), "r"(b0.e)); }           \
    template <uint32_t ALO, uint32_t BLO, int ACC, int TA = 1>                                                                    \
    static __device__ __forceinline__ void ss(float* d, Dsc a0, Dsc b0) {                                                         \
      asm volatile("{\n.reg .b64 a, b;\nmad.wide.u32 a, %" #I6 ", %" #I1 ", %" #I0 ";\nmad.wide.u32 b, %" #I6 ", %" #I3 ", %" #I2 ";\n" \
                   "wgmma.mma_async.sync.aligned.m64n" #N "k16.f32." T "." T " " RS_ ", a, b, %" #I4 ", 1, 1, %" #I5 ", 0;\n}"    \
                   : ACCM(d) : "l"(a0.b), "n"(ALO), "l"(b0.b), "n"(BLO), "n"(ACC), "n"(TA), "r"(b0.e)); }                         \
  };
DEF_MM(8, false, "bf16", ACC4, R4S, 4, 5, 6, 7, 8, 9, 10, 11)
DEF_MM(16, false, "bf16", ACC8, R8S, 8, 9, 10, 11, 12, 13, 14, 15)
DEF_MM(32, false, "bf16", ACC16, R16S, 16, 17, 18, 19, 20, 21, 22, 23)
DEF_MM(40, false, "bf16", ACC20, R20S, 20, 21, 22, 23, 24, 25, 26, 27)
DEF_MM(48, false, "bf16", ACC24, R24S, 24, 25, 26, 27, 28, 29, 30, 31)
DEF_MM(64, false, "bf16", ACC32, R32S, 32, 33, 34, 35, 36, 37, 38, 39)
DEF_MM(32, true, "f16", ACC16, R16S, 16, 17, 18, 19, 20, 21, 22, 23)
DEF_MM(64, true, "f16", ACC32, R32S, 32, 33, 34, 35, 36, 37, 38, 39)

#define LAG 11
#define NSTEP (NSEG + LAG)
#define NR (NSTEP + 1)
__device__ __align__(1024) __nv_bfloat16 g_xn[2][S_LEN * DM];
#define RO 16
static_assert(RO > LAG + 1, "ring");
__device__ __align__(1024) unsigned char g_o[RO * 96 * 8192];
__device__ __align__(1024) uint32_t g_part[6][7][40][64];
#define RD 16
#define TILE_B 81920
__device__ __align__(1024) float2 g_stat[S_LEN];
__device__ __align__(1024) uint32_t g_st2[2][RD][64];
__device__ __align__(1024) unsigned char g_acc[5][RD][TILE_B];
#define NOP 19
#define NW12 5
#define NW34 12
#define NBC (NOP + NW12 + NW34)
__device__ __align__(1024) unsigned char g_wt[NOP * 10 * 12288];
enum { F_O = 0, F_R1 = NOP + 1, F_R2 = F_R1 + 4, F_R3 = F_R2 + 4, F_Z = F_R3 + 4, F_DONE, F_MISC, F_NUM };
__device__ __align__(128) uint32_t g_f[F_NUM][96];
__device__ __align__(128) int g_xready[129][8];
__device__ uint32_t g_tpc[128];
#define TS(i)
#define TSV(i, v)
#define TSN(i)
#define TSD(i, dep)
#define BTS(k, i)
#define BTS2(k, i)
#define RTS(i)
#define RTSD(i, dep)
#define RTS_OUT()
#define CTS(i)
#define PTS(i)
#define PTS1(i)
#define CTS_OUT()
#define GTS(i)

#define CL_SIZE 15
#define NCL 7
#define SSQ 13
#define SSV 16
#define PL_SZ 5376
#define TILE_SBO 2560
#define TILE_GRP 15360
#define WS_SZ ((2 * SSQ + SSV) * 2048)
#define OFF_QK (OFF_WO + 26 * 2048)
#define LAYOUT 2
#define OFF_TILE 0
#define OFF_WS (4 * TILE_GRP)
#define OFF_WO (OFF_WS + WS_SZ)
#define OFF_PL (OFF_QK + 20480)
#define OFF_BAR (OFF_PL + 2 * PL_SZ)
#define STG_Q OFF_TILE
#define STG_K OFF_WO
#define VA 14
#define STG_V2 (OFF_TILE + 27 * 2048)
#define OFF_O (OFF_PL + 4352)
#define LAND(k) (((k) >> 1) * TILE_GRP + ((k) & 1) * 1280)
#define LAND_F (5 * TILE_SBO)
#define OFF_XL (OFF_TILE + 3 * TILE_GRP)
#define OFF_XF (OFF_XL + LAND_F)
#define OFF_WT ((OFF_XL + TILE_SBO + 1023) & ~1023)
#define OFF_TAB (OFF_BAR + 240)
#define OFF_INV (OFF_TAB + 64)
#define OFF_TS (OFF_INV + 128)
#define A_SMEM 232448
static_assert(WS_SZ + 72 * 1024 + 2 * PL_SZ + 4 * TILE_GRP + 512 == A_SMEM && OFF_WS % 1024 == 0 && OFF_WO % 1024 == 0 && SSQ == 13, "smem map");
enum { B_W0 = 0, B_W1, B_F1, B_F2 = B_F1 + 4, B_R1 = B_F2 + 4, B_R2, B_MEMFREE, B_LANDFREE, B_OPEER, B_PLFREE, B_XFREE, B_SB, B_WOF = B_SB + 6, B_WTF, B_RS, B_NUM = B_RS + 4 };
static_assert(B_NUM <= 30, "barriers");
enum { N_C = 0, N_SISS, N_QK, N_V, N_PM, N_TURN, N_PI, N_VGO, N_O, N_PX, N_AB, N_SDONE, N_VDONE, N_G3, N_P, N_OX };

__device__ __forceinline__ bool is_dual(int j) { return j >= LAG && j < NSEG; }
__device__ __forceinline__ int sched_l(int j) { return j < NSEG ? j : NSEG + j - LAG; }
__device__ __forceinline__ int sched_f(int j) { return NSEG + j - LAG; }
__device__ __forceinline__ void wait_cnt(const int* p, int target) {
  int v, n = 0;
  do {
    asm volatile("ld.relaxed.gpu.global.b32 %0, [%1];" : "=r"(v) : "l"(p) : "memory");
    if (v >= target) break;
    if (++n > SPIN_LIMIT) FAIL();
  } while (true);
  asm volatile("fence.acquire.gpu;" ::: "memory");
  asm volatile("fence.proxy.async.global;" ::: "memory");
}
__device__ __forceinline__ void red_release(void* p, uint32_t v) { asm volatile("red.release.gpu.global.add.u32 [%0], %1;" :: "l"(p), "r"(v) : "memory"); }
__device__ __forceinline__ void red_relaxed(void* p, uint32_t v) { asm volatile("red.relaxed.gpu.global.add.u32 [%0], %1;" :: "l"(p), "r"(v) : "memory"); }
#define VMASK 0xa5294a5294ull
__host__ __device__ constexpr int popc40(unsigned long long m) { int c = 0; for (; m; m &= m - 1) c++; return c; }
static_assert(popc40(VMASK) == SSV, "mask");
__host__ __device__ constexpr int ss_idx(int ks, int n) { return n == SSV ? popc40(VMASK & ((1ull << ks) - 1)) : ks * n / 40; }
__host__ __device__ constexpr bool is_ss(int ks, int n) { return ss_idx(ks + 1, n) != ss_idx(ks, n); }
__host__ __device__ constexpr int rs_idx(int ks, int n) { return ks - ss_idx(ks, n); }

#define SL2 (0.07216878364870322f * 1.4426950408889634f)

#define SUM_LOOP 0
struct Desc { Dsc tile, unit, k1, pl, p; };
__device__ __forceinline__ Desc make_desc(const uint64_t* h, uint32_t u, uint32_t e) {
  return {{h[0], e}, {h[1] + u * 128, e}, {h[2], e}, {h[3], e}, {h[4], e}};
}
template <int N, int NSS, int RG, int KS, int K1, int K0 = 0>
__device__ __forceinline__ void proj(float* acc, const uint32_t* W, const Desc& D) {
  if constexpr (KS < K1) {
    constexpr uint32_t BLO = dlo(OFF_TILE + (KS / 10) * TILE_GRP + RG * TILE_SBO + (KS % 10) * 256, 128);
    if constexpr (is_ss(KS, NSS)) MM<N>::template ss<dlo(OFF_WS + ss_idx(KS, NSS) * 2048, 0), BLO, (KS != K0)>(acc, D.unit, D.tile);
    else MM<N>::template rs<BLO, (KS != K0)>(acc, W + rs_idx(KS, NSS) * 4, D.tile);
    proj<N, NSS, RG, KS + 1, K1, K0>(acc, W, D);
  }
}
#define VST 17
template <int KS>
__device__ __forceinline__ void ld_rest(uint32_t* W, const uint32_t* p) {
  if constexpr (KS < 40) {
    if constexpr (!is_ss(KS, SSV) && rs_idx(KS, SSV) >= VST) {
#pragma unroll
      for (int i = 0; i < 4; i++) W[4 * rs_idx(KS, SSV) + i] = __ldg(p + (KS * 16 + (i >> 1) * 8) * (HD / 2) + (i & 1) * 4);
    }
    ld_rest<KS + 1>(W, p);
  }
}
template <int N>
__device__ __forceinline__ void load_w(uint32_t* W, uint32_t stage, int warp, int lane) {
  const int kr = (lane >> 4) * 8 + (lane & 7);
  const int cb = warp * 2 + ((lane >> 3) & 1);
  const uint32_t a0 = stage + kr * 128 + ((cb ^ (lane & 7)) << 4);
#pragma unroll
  for (int i = 0; i < N; i++) ldsm4t(W[4 * i], W[4 * i + 1], W[4 * i + 2], W[4 * i + 3], a0 + i * 2048);
}
template <int N, int G, int U, int OS, int ACC>
__device__ __forceinline__ void wo4(float* d, const Desc& D) {
  constexpr uint32_t WA = (U >= 4 ? OFF_WO + (U - 4) * 2048 : OFF_WT) - G * SSQ * 2048, OB = OS == 0 ? OFF_O : OS == 1 ? OFF_XL : OFF_XF;
  Dsc b = OS ? D.k1 : D.pl;
  b.e = fresh<(U < 16 ? U / 4 : U / 8 - 2) + (N == 8 ? 4 : 0)>(D.unit.e);
  MM<N>::template ss<dlo(WA, 0), dlo(OB, 128), ACC>(d, D.unit, b);
  MM<N>::template ss<dlo(WA + 2048, 0), dlo(OB + 256, 128), 1>(d, D.unit, b);
  MM<N>::template ss<dlo(WA + 4096, 0), dlo(OB + 512, 128), 1>(d, D.unit, b);
  MM<N>::template ss<dlo(WA + 6144, 0), dlo(OB + 768, 128), 1>(d, D.unit, b);
}
__device__ __forceinline__ void wo_coord(int i, int t3, int head, int& c0, int& c1) {
  const int g = i >> 1;
  const int blk = g == 0 ? 9 : (g < 4 ? g - 1 : (g - 4) >> 1) * 3 + t3;
  int sl = g < 4 ? t3 : (g & 1) ? t3 + 1 : t3 + 2;
  if (sl >= 3) sl -= 3;
  c0 = blk * 64; c1 = head * DH + sl * 64 + (i & 1) * 32;
}
__device__ __forceinline__ void tok_softmax(uint32_t sb, int job, int lane) {
  const bool w1 = job & 1;
  const int dg = (lane >> 2) - (lane & 3) * 2;
  const uint32_t lo = sb + OFF_PL + (job >> 1) * PL_SZ + (job & 1) * 1792, l8 = lo + 512 + lane * 8, pa = lo + lane * 4;
  const uint32_t km = job & 2 ? 640 : 512;
  float x[14];
  {
    const uint4 a = lds128(lo + lane * 16);
    const uint2 e = lds64(l8);
    const uint32_t c = lds32(768 + pa);
    x[0] = bf_lo(a.x); x[1] = bf_hi(a.x); x[2] = bf_lo(a.y); x[3] = bf_hi(a.y); x[4] = bf_lo(a.z); x[5] = bf_hi(a.z); x[6] = bf_lo(a.w); x[7] = bf_hi(a.w);
    x[8] = bf_lo(c); x[9] = bf_hi(c); x[10] = bf_lo(e.x); x[11] = bf_hi(e.x); x[12] = bf_lo(e.y); x[13] = bf_hi(e.y);
  }
  if (dg < 0) { x[8] = -INFINITY; if (w1) x[4] = -INFINITY; else x[10] = -INFINITY; }
  if (dg < 1) { x[9] = -INFINITY; if (w1) x[5] = -INFINITY; else x[11] = -INFINITY; }
  const float m4 = fmaxf(x[8], x[9]);
  float m0 = fmaxf(fmaxf(fmaxf(x[0], x[1]), fmaxf(x[2], x[3])), fmaxf(fmaxf(x[4], x[5]), fmaxf(x[6], x[7])));
  float m1 = fmaxf(fmaxf(x[10], x[11]), fmaxf(x[12], x[13]));
  if (w1) m1 = fmaxf(m1, m4); else m0 = fmaxf(m0, m4);
  m0 = fmaxf(m0, __shfl_xor_sync(~0u, m0, 1)); m1 = fmaxf(m1, __shfl_xor_sync(~0u, m1, 1));
  sts32(pa + (w1 ? 384 : 896 + 128), 0u); sts32(pa + 1152 - km, 0u); sts32(pa + 896 + 1152 - km, 0u); sts64(l8 + 896 - 256, 0u, 0u);
  m0 = fmaxf(m0, __shfl_xor_sync(~0u, m0, 2)); m1 = fmaxf(m1, __shfl_xor_sync(~0u, m1, 2));
  m0 *= -SL2; m1 *= -SL2;
#pragma unroll
  for (int j = 0; j < 14; j++) x[j] = ex2(fmaf(x[j], SL2, j < 8 ? m0 : j >= 10 ? m1 : w1 ? m1 : m0));
  const float l4s = x[8] + x[9];
  float l0 = ((x[0] + x[1]) + (x[2] + x[3])) + ((x[4] + x[5]) + (x[6] + x[7])), l1 = (x[10] + x[11]) + (x[12] + x[13]);
  if (w1) l1 += l4s; else l0 += l4s;
  l0 += __shfl_xor_sync(~0u, l0, 1); l1 += __shfl_xor_sync(~0u, l1, 1);
  l0 += __shfl_xor_sync(~0u, l0, 2); l1 += __shfl_xor_sync(~0u, l1, 2);
  l0 = rcpf(l0); l1 = rcpf(l1);
#pragma unroll
  for (int j = 0; j < 7; j++) {
    const float iv = j < 4 ? l0 : j > 4 ? l1 : w1 ? l1 : l0;
    sts32(pa + (j < 3 ? j * 128 : j == 3 ? km : j == 4 ? (w1 ? 896 + 128 : 384) : j == 5 ? 896 : 896 + km), pack2(x[2 * j] * iv, x[2 * j + 1] * iv));
  }
}
template <int N>
__device__ __forceinline__ void wo_phase(uint32_t sb, int wg, int warp, int lane, uint32_t par, uint32_t r1, const Desc& D) {
  const uint32_t bar = sb + OFF_BAR;
  float x[N / 2], y[N / 2];
  const uint2 ta = lds64(sb + OFF_TAB + (wg * 4 + warp) * 8);
  uint32_t xa = (ta.x & ~255u) + lane * 8, xb = (ta.x & 0xFF0000FFu) + SMEM0 + OFF_BAR, ya = (ta.y & ~255u) + lane * 8, yb = (ta.y & 0xFF0000FFu) + SMEM0 + OFF_BAR;
  asm volatile("" : "+r"(xa), "+r"(xb), "+r"(ya), "+r"(yb));
  auto scat = [&](uint32_t ad, uint32_t mb, const float* d) {
    st_async_v2(ad, pack2(d[0], d[1]), pack2(d[2], d[3]), mb);
    if (N == 16) st_async_v2(ad + LAND_F, pack2(d[4], d[5]), pack2(d[6], d[7]), mb);
  };
  if (wg == 0) {
    bar_sync(N_O, 384);
    wg_fence(); wo4<N, 0, 4, 0, 0>(x, D); wo4<N, 0, 8, 0, 0>(y, D); wg_commit();
    mbar_waitu(bar + 8 * B_OPEER, par);
    CFENCE(); wg_fence(); wo4<N, 0, 16, 1, 1>(x, D); wo4<N, 0, 20, 2, 1>(x, D); wg_commit();
    wo4<N, 0, 24, 1, 1>(y, D); wg_commit();
    mbar_waitu2(bar + 8 * B_WOF, bar + 8 * B_MEMFREE, par);
    wg_fence(); wo4<N, 0, 28, 2, 1>(y, D); wg_commit();
    bar_arrive(N_AB, 256);
    wg_wait<2>(); scat(xa, xb, x);
    wg_wait<0>(); scat(ya, yb, y);
  } else {
    bar_sync(N_O, 384);
    wg_fence(); wo4<N, 1, 0, 0, 0>(x, D); wg_commit(); wo4<N, 1, 12, 0, 0>(y, D); wg_commit();
    wg_wait<1>(); mbar_arrive_remote_if(lane == 0, r1);
    mbar_waitu(bar + 8 * B_MEMFREE, par);
    scat(xa, xb, x);
    bar_sync(N_AB, 256);
    CFENCE(); wg_fence(); wo4<N, 1, 32, 1, 1>(y, D); wo4<N, 1, 36, 2, 1>(y, D); wg_commit();
    bar_arrive(N_TURN, 256);
    wg_wait<0>(); scat(ya, yb, y);
  }
}
#define DS_DUAL 10
#define DS_SINGLE 20
#define POLL_GAP 100
#define POLL_GAPD 0
#define TOK_DELAY 250
#define LATE_SM 1
#define UMAX 40
#define VD1 10
#define VS2 20
#define IG_V 3
#define VS1 4
struct AMaps { CUtensorMap w16[3], wo32; uint64_t d[5]; const __nv_bfloat16* wv; };
__global__ void __launch_bounds__(512, 1)
acore_kernel(const __grid_constant__ AMaps M, const __nv_bfloat16* __restrict__ mem0, int sync_b) {
  extern __shared__ __align__(1024) unsigned char smem_raw[];
  const uint32_t sb = smem_u32(smem_raw);
  GTS(24);
  if (threadIdx.x == 480) {
    uint32_t smid; asm volatile("mov.u32 %0, %%smid;" : "=r"(smid));
    g_tpc[(smid >> 1) & 127] = blockIdx.x - CL_SIZE < 3 * CL_SIZE && blockIdx.x % CL_SIZE >= 12 ? 1 : 2;
    asm volatile("griddepcontrol.launch_dependents;");
  }
  const int lane0 = threadIdx.x & 31;
#define LANE_INIT() int lane; asm volatile("mov.u32 %0, %%laneid;" : "=r"(lane))
  const int warp = __shfl_sync(~0u, (threadIdx.x >> 5) & 3, 0);
  const int cl = blockIdx.x / CL_SIZE;
  const uint32_t rank = blockIdx.x - cl * CL_SIZE;
  const int nh = cl >= 1 && cl <= 3 ? 4 : 5;
  const int nA = 3 * nh;
  const int wg = __shfl_sync(~0u, (int)rank < nA ? threadIdx.x >> 7 : 4, 0);
  const int head = (cl < 4 ? (cl ? 1 + 4 * cl : 0) : 5 * cl - 3) + rank / 3;
  const int t3 = rank % 3;
  const int col0 = head * DH + t3 * 64;
  const uint32_t bar = sb + OFF_BAR;
  const uint32_t rb0 = SMEM0;
  const uint16_t mcmask = (uint16_t)((1u << nA) - 1);
  const uint32_t nxt = sb + ((t3 == 2 ? -2 : 1) << 24), prv = sb + ((t3 == 0 ? 2 : -1) << 24);
  const int ig = (int)rank - (nA - 4);

  if (threadIdx.x == 0) {
    if (mapa(sb, nA - 1) != rb0 + ((nA - 1) << 24) || mapa(sb, 0) != rb0 || mapa(sb, 1) != rb0 + (1u << 24) || sb != SMEM0 + (rank << 24)) FAIL();
    for (int i = 0; i < B_NUM; i++)
      mbar_init(bar + 8 * i, i == B_R1 ? 4 * nA : i == B_R2 ? 12 * nA : i == B_MEMFREE ? nA : i == B_LANDFREE ? 4 * nA : i == B_PLFREE || i == B_XFREE ? 2 : 1);
    asm volatile("fence.mbarrier_init.release.cluster;" ::: "memory");
    mbar_expect(bar + 8 * B_W0, (80 + SSV + VST) * 2048);
  }
  __syncthreads();
  if (lane0 == 0) {
    const int w12 = wg * 4 + warp;
    if (w12 < 10) {
#pragma unroll 1
      for (int ks = 4 * w12; ks < 4 * w12 + 4; ks++) {
        const bool ss = is_ss(ks, SSQ);
        tma2d(ss ? sb + OFF_WS + ss_idx(ks, SSQ) * 2048 : sb + STG_Q + rs_idx(ks, SSQ) * 2048, &M.w16[0], col0, ks * 16, bar + 8 * B_W0);
        tma2d(ss ? sb + OFF_WS + (SSQ + ss_idx(ks, SSQ)) * 2048 : sb + STG_K + rs_idx(ks, SSQ) * 2048, &M.w16[1], col0, ks * 16, bar + 8 * B_W0);
        if (is_ss(ks, SSV)) tma2d(sb + OFF_WS + (2 * SSQ + ss_idx(ks, SSV)) * 2048, &M.w16[2], col0, ks * 16, bar + 8 * B_W0);
        else if (rs_idx(ks, SSV) < VST) tma2d(sb + (rs_idx(ks, SSV) < VA ? STG_K + 27 * 2048 : STG_V2 - VA * 2048) + rs_idx(ks, SSV) * 2048, &M.w16[2], col0, ks * 16, bar + 8 * B_W0);
      }
    }
  }
  if (lane0 < 2 && wg < 2) {
    const int u = 4 * (wg ? (lane0 ? 6 + t3 : 9) : (lane0 ? 3 + t3 : t3)) + warp;
    const int li = (u >= nA) + (u >= 2 * nA) + (u >= 3 * nA);
    sts32(sb + OFF_TAB + (wg * 4 + warp) * 8 + lane0 * 4,
          rb0 + ((u - li * nA) << 24) + OFF_TILE + LAND(li + (u >= 36 ? t3 : 0)) + (rank / 3) * 256 + 8 * (B_RS + li));
  }
  __syncthreads();
  GTS(25);

  auto issue_tok = [&](int sc, int fb, int rel = -1, uint32_t ph = 0) {
    if (sync_b) wait_cnt(&g_xready[sc][0], 32);
    if (rel >= 0) mbar_waitu(bar + 8 * rel, ph);
    bulk_g2s_mc_e(sb + OFF_TILE + ig * TILE_GRP + TILE_SBO, &g_xn[0][0] + uni(sc * (32 * DM)) + ig * 5120, 10240, bar + 8 * (fb + ig), mcmask);
  };
#define POLL(d, q) _Pragma("unroll") for (int k = 0; k < NCL; k++) \
      asm volatile("ld.relaxed.gpu.global.v2.b32 {%0,%1}, [%2];" : "=r"(d[k].x), "=r"(d[k].y) : "l"(q + k * 2560) : "memory")
#define L3(L, a, b, c) lop3<L>(a, b, c)
#define TAGS(L, d) L3(L, L3(L, L3(L, d[0].x, d[0].y, d[1].x), L3(L, d[1].y, d[2].x, d[2].y), L3(L, d[3].x, d[3].y, d[4].x)), L3(L, d[4].y, d[5].x, d[5].y), L3(L, d[6].x, d[6].y, d[6].y))
    auto deliver = [&](uint2* pa, const uint32_t* gq, int u, int c, int dc, int ds, int step, bool first, int lane) {
      const uint32_t off = uni(OFF_TILE + ((u * 205) >> 11) * (TILE_GRP - TILE_SBO) + u * 256 + dc * LAND_F), boff = uni(OFF_BAR + 8 * (B_F1 + ((u * 205) >> 11)));
      const uint32_t* mi = &g_part[4][0][0][0] + uni((c * NCL + cl) * 2560 + u * 64);
      mbar_waitu(bar + 8 * B_LANDFREE, step & 1);
      int n = 0;
      while (true) {
        const bool ok = __all_sync(~0u, ((step & 2 ? ~TAGS(0xFE, pa) : TAGS(0x80, pa)) & 1) != 0);
        if (ok) break;
        if (++n > SPIN_LIMIT) FAIL();
        POLL(pa, gq);
      }
      if (warp == 0 && first) { TS(19); TSV(10, n); }
      const uint32_t w0 = hadd2bf(hadd2bf(hadd2bf(pa[0].x, pa[1].x), hadd2bf(pa[2].x, pa[3].x)), hadd2bf(hadd2bf(pa[4].x, pa[5].x), pa[6].x));
      const uint32_t w1 = hadd2bf(hadd2bf(hadd2bf(pa[0].y, pa[1].y), hadd2bf(pa[2].y, pa[3].y)), hadd2bf(hadd2bf(pa[4].y, pa[5].y), pa[6].y));
      if (u < ds) {
        const uint32_t da = SMEM0 + off + lane * 8, db = SMEM0 + boff;
#pragma unroll
        for (int d = 0; d < 12; d++) st_async_v2((d << 24) + da, w0, w1, (d << 24) + db);
#pragma unroll
        for (int d = 12; d < 15; d++) st_async_v2_if(nA == 15, (d << 24) + da, w0, w1, (d << 24) + db);
      } else {
        *reinterpret_cast<uint2*>(const_cast<uint32_t*>(gq) + ((4 - 2 * (step & 1)) * NCL + cl) * 2560) = make_uint2(w0, w1);
        asm volatile("fence.proxy.async.global;" ::: "memory");
        __syncwarp();
        bulk_g2s_mc_e(sb + off, mi, 256, sb + boff, mcmask);
      }
    };
#define REL(b, g) mbar_arrive_remote_if(lane == 0, rb0 + ((nA - 4 + (g)) << 24) + OFF_BAR + 8 * (b))

  if (wg < 2) {
    asm volatile("setmaxnreg.inc.sync.aligned.u32 160;");
    LANE_INIT();
    uint32_t W[4 * (40 - SSQ)];
    mbar_waitw(bar + 8 * B_W0, 0);
    GTS(26);
    load_w<40 - SSQ>(W, sb + (wg ? STG_K : STG_Q), warp, lane);
    fence_async();
    bar_sync(1, 384);
    cluster_sync_all();
#define DESC(k) const Desc D = make_desc(M.d, min(wg, 2) * SSQ, fresh<k>(step))
    GTS(27);
#pragma unroll 1
    for (int step = -1; step < NSTEP; step++) {
      const uint32_t par = step & 1;
      asm volatile("" : "+r"(lane));
      const bool dual = is_dual(step), has_next = step + 1 < NSTEP;
#define QK_SA (sb + OFF_QK + wg * 15360 + (2 * warp + ((lane >> 3) & 1)) * 128 + (lane & 7) * 16)
#define QK_F (wg ? -5120 : 5120)
#define QK_S12 ((wg ? (lane >> 4) : 1 + 2 * (lane >> 4)) * 1024)
#define QK_S34 ((wg ? 2 + (lane >> 4) : 2 - 2 * (lane >> 4)) * 1024)
      if (step >= 0) {
        if (dual) {
          DESC(0);
          float acc[24];
          mbar_waitu(bar + 8 * (B_F1 + 0), par);
          if (wg + warp == 0) { TS(0); TSN(1); }
          CFENCE(); wg_fence(); proj<48, SSQ, 0, 0, 10>(acc, W, D); wg_commit();
          mbar_waitu(bar + 8 * (B_F1 + 1), par);
          CFENCE(); wg_fence(); proj<48, SSQ, 0, 10, 20>(acc, W, D); wg_commit();
          mbar_waitu(bar + 8 * (B_F1 + 2), par);
          CFENCE(); wg_fence(); proj<48, SSQ, 0, 20, 30>(acc, W, D); wg_commit();
          mbar_waitu(bar + 8 * (B_F1 + 3), par);
          if (wg + warp == 0) TS(2);
          CFENCE(); wg_fence(); proj<48, SSQ, 0, 30, 40>(acc, W, D); wg_commit();
          bar_arrive(N_VGO, 384);
          mbar_waitu(bar + 8 * B_PLFREE, par);
          const uint32_t sa = QK_SA, s0 = sa + 4096 + (lane >> 4) * QK_F, s1 = sa + QK_F + QK_S12, s2 = sa + QK_F + QK_S34;
          wg_wait<0>();
          if (wg + warp == 0) TS(3);
          stsm4t(s0, pack2(acc[0], acc[1]), pack2(acc[2], acc[3]), pack2(acc[20], acc[21]), pack2(acc[22], acc[23]));
          stsm4t(s1, pack2(acc[4], acc[5]), pack2(acc[6], acc[7]), pack2(acc[8], acc[9]), pack2(acc[10], acc[11]));
          stsm4t(s2, pack2(acc[12], acc[13]), pack2(acc[14], acc[15]), pack2(acc[16], acc[17]), pack2(acc[18], acc[19]));
        } else {
          DESC(1);
          float acc[4];
          mbar_waitu(bar + 8 * (B_F1 + 0), par);
          if (wg + warp == 0) { TS(0); TSN(1); }
          CFENCE(); wg_fence(); proj<8, SSQ, 0, 0, 10>(acc, W, D); wg_commit();
          mbar_waitu(bar + 8 * (B_F1 + 1), par);
          CFENCE(); wg_fence(); proj<8, SSQ, 0, 10, 20>(acc, W, D); wg_commit();
          mbar_waitu(bar + 8 * (B_F1 + 2), par);
          CFENCE(); wg_fence(); proj<8, SSQ, 0, 20, 30>(acc, W, D); wg_commit();
          mbar_waitu(bar + 8 * (B_F1 + 3), par);
          if (wg + warp == 0) TS(2);
          CFENCE(); wg_fence(); proj<8, SSQ, 0, 30, 40>(acc, W, D); wg_commit();
          bar_arrive(N_VGO, 384);
          mbar_waitu(bar + 8 * B_PLFREE, par);
          const uint32_t s0 = QK_SA + 4096;
          wg_wait<0>();
          if (wg + warp == 0) TS(3);
          stsm2t(s0, pack2(acc[0], acc[1]), pack2(acc[2], acc[3]));
        }
        fence_async();
        bar_sync(N_QK, 256);
        if (wg == 0 || dual) {
          float s[20];
          DESC(2);
          const Dsc ab = D.k1 + wg * 192, bb = D.k1 + (1 - wg) * 320;
          wg_fence();
          MM<40>::ss<dlo(OFF_QK, 128), dlo(OFF_QK + 10240, 128), 0, 0>(s, ab, bb);
          MM<40>::ss<dlo(OFF_QK + 256, 128), dlo(OFF_QK + 10240 + 256, 128), 1, 0>(s, ab, bb);
          MM<40>::ss<dlo(OFF_QK + 512, 128), dlo(OFF_QK + 10240 + 512, 128), 1, 0>(s, ab, bb);
          MM<40>::ss<dlo(OFF_QK + 768, 128), dlo(OFF_QK + 10240 + 768, 128), 1, 0>(s, ab, bb);
          wg_commit();
          bar_arrive(N_SISS, 384);
          const int rw = (warp - wg) & 3;
          const uint32_t bo = OFF_BAR + 8 * (B_SB + 3 * wg + rw), lo = OFF_PL + wg * PL_SZ + rw * 1792;
          const uint32_t km = wg ? 640 : 512;
          uint32_t l16 = lo + lane * 16, l4 = lo + lane * 4;
          mbar_expect_if(lane == 0 && rw < 3, sb + bo, rw < 2 ? 1792 : 1280);
          asm volatile("" : "+r"(l16), "+r"(l4));
          if (rw == 2) {
            wg_wait<0>();
            if (wg == 0) TSD(4, __float_as_uint(s[0]));
            const uint32_t w0 = pack2(s[0], s[1]), w1 = pack2(s[4], s[5]), w2 = pack2(s[8], s[9]), w3 = pack2(s[12], s[13]), w4 = pack2(s[16], s[17]);
            {
              st_async_v4(nxt + 896 + l16, w0, w1, w2, w3, nxt + bo);
              st_async_v4(prv + l16, w0, w1, w2, w3, prv + bo);
              st_async_b32(nxt + 896 + 768 + l4, w4, nxt + bo);
              st_async_b32(prv + 768 + l4, w4, prv + bo);
            }
            bar_arrive(N_SDONE, 256);
            mbar_waitu(sb + bo, (step - wg * LAG) & 1);
            if (wg == 0) TS(5);
            float x[10], m0;
            {
              const uint4 a = lds128(sb + l16), b = lds128(sb + 896 + l16);
              const uint32_t c = lds32(sb + 768 + l4), d = lds32(sb + 896 + 768 + l4);
              const uint32_t e0 = hadd2bf(hadd2bf(a.x, b.x), w0), e1 = hadd2bf(hadd2bf(a.y, b.y), w1), e2 = hadd2bf(hadd2bf(a.z, b.z), w2),
                             e3 = hadd2bf(hadd2bf(a.w, b.w), w3), e4 = hadd2bf(hadd2bf(c, d), w4);
              const uint32_t em = hmax2bf(hmax2bf(hmax2bf(e0, e1), hmax2bf(e2, e3)), e4);
              m0 = fmaxf(bf_lo(em), bf_hi(em));
              x[0] = bf_lo(e0); x[1] = bf_hi(e0); x[2] = bf_lo(e1); x[3] = bf_hi(e1); x[4] = bf_lo(e2);
              x[5] = bf_hi(e2); x[6] = bf_lo(e3); x[7] = bf_hi(e3); x[8] = bf_lo(e4); x[9] = bf_hi(e4);
            }
            m0 = fmaxf(m0, __shfl_xor_sync(~0u, m0, 1));
            sts32(sb + l4 + 1152 - km, 0u);
            m0 = fmaxf(m0, __shfl_xor_sync(~0u, m0, 2));
            m0 *= -SL2;
#pragma unroll
            for (int j = 0; j < 5; j++) {
              x[2 * j] = ex2(fmaf(x[2 * j], SL2, m0)); x[2 * j + 1] = ex2(fmaf(x[2 * j + 1], SL2, m0));
              sts32(sb + l4 + (j < 4 ? j * 128 : km), pack2(x[2 * j], x[2 * j + 1]));
            }
            float l = ((x[0] + x[1]) + (x[2] + x[3])) + ((x[4] + x[5]) + ((x[6] + x[7]) + (x[8] + x[9])));
            l += __shfl_xor_sync(~0u, l, 1);
            fence_async();
            sts32(sb + OFF_INV + wg * 64 + (lane >> 1) * 4, __float_as_uint(l));
            bar_arrive(N_PM, dual ? 224 : 192);
            if (wg == 0) TS(6);
          } else if (rw < 2) {
            const bool w1 = rw == 1;
            const uint32_t l8 = lo + 512 + lane * 8;
            uint32_t tw[7];
            wg_wait<0>();
            bar_arrive(N_SDONE, 256);
            tw[0] = pack2(s[0], s[1]); tw[1] = pack2(s[4], s[5]); tw[2] = pack2(s[8], s[9]); tw[3] = pack2(s[16], s[17]);
            tw[4] = w1 ? pack2(s[6], s[7]) : pack2(s[12], s[13]); tw[5] = pack2(s[2], s[3]); tw[6] = pack2(s[18], s[19]);
            { const uint32_t t0 = clock32(); while (clock32() - t0 < TOK_DELAY) {} }
            st_async_v4(nxt + 896 + l16, tw[0], tw[1], tw[2], tw[3], nxt + bo);
            st_async_v4(prv + l16, tw[0], tw[1], tw[2], tw[3], prv + bo);
            st_async_v2(nxt + 896 + l8, tw[5], tw[6], nxt + bo);
            st_async_v2(prv + l8, tw[5], tw[6], prv + bo);
            st_async_b32(nxt + 896 + 768 + l4, tw[4], nxt + bo);
            st_async_b32(prv + 768 + l4, tw[4], prv + bo);
            mbar_waitu(sb + bo, (step - wg * LAG) & 1);
            const uint4 a = lds128(sb + l16), b = lds128(sb + 896 + l16);
            const uint2 e = lds64(sb + l8), f = lds64(sb + 896 + l8);
            const uint32_t c = lds32(sb + 768 + l4), d = lds32(sb + 896 + 768 + l4);
            sts128(sb + l16, hadd2bf(hadd2bf(a.x, b.x), tw[0]), hadd2bf(hadd2bf(a.y, b.y), tw[1]), hadd2bf(hadd2bf(a.z, b.z), tw[2]), hadd2bf(hadd2bf(a.w, b.w), tw[3]));
            sts64(sb + l8, hadd2bf(hadd2bf(e.x, f.x), tw[5]), hadd2bf(hadd2bf(e.y, f.y), tw[6]));
            sts32(sb + 768 + l4, hadd2bf(hadd2bf(c, d), tw[4]));
            bar_arrive(N_PX, dual ? 256 : 192);
            if (wg + warp == 0) TS(9);
          } else {
            wg_wait<0>();
            if (wg == 0) {
              mbar_expect_if(lane < 3 && has_next, bar + 8 * (lane == 2 ? B_OPEER : B_WOF + lane), lane == 2 ? (dual ? 4096 : 2048) : lane ? 8192 : 20480);
              auto fetch = [&](int i, int n, uint32_t dst, int mb) {
                int c0, c1; wo_coord(i, t3, head, c0, c1);
                tma2d_e(dst, &M.wo32, c0, c1, bar + 8 * mb); if (n == 2) tma2d_e(dst + 4096, &M.wo32, c0, c1 + 32, bar + 8 * mb);
              };
              bar_sync(N_G3, 160);
              if (has_next) {
                fetch(0, 2, sb + OFF_WT, B_WTF);
                mbar_arrive_remote_if(lane < 2, (lane ? nxt : prv) + OFF_BAR + 8 * B_XFREE);
              }
              bar_sync(N_SDONE, 256);
              if (has_next) {
                fetch(15, 1, sb + OFF_QK, B_WOF); fetch(16, 2, sb + OFF_QK + 4096, B_WOF); fetch(18, 2, sb + OFF_QK + 12288, B_WOF);
                mbar_waitu(bar + 8 * B_XFREE, par);
              }
              bar_arrive(N_PM, dual ? 224 : 192);
              bar_sync(N_VDONE, 160);
              mbar_arrive_remote_if(lane < nA && has_next, rb0 + (lane << 24) + OFF_BAR + 8 * B_MEMFREE);
              if (has_next) mbar_waitu(bar + 8 * B_WTF, par);
            } else {
              bar_arrive(N_SDONE, 256);
              if ((unsigned)ig < IG_V) issue_tok(sched_l(step + 1), B_F2, B_R1, (step - LAG) & 1);
            }
          }
        } else {
          bar_arrive(N_SISS, 384);
          bar_arrive(N_SDONE, 256);
        }
        if (has_next) {
          if (step == 0) mbar_waitw(bar + 8 * B_W1, 0);
          const uint32_t r1 = rb0 + ((nA - 1) << 24) + OFF_BAR + 8 * B_R1;
          if (dual) { DESC(3); wo_phase<16>(sb, wg, warp, lane, par, r1, D); } else { DESC(4); wo_phase<8>(sb, wg, warp, lane, par, r1, D); }
          bar_arrive(N_C, 288);
          if (warp == 0) TS(7 + wg);
        }
      }
      if (has_next) {
        DESC(5);
        float acc[16];
        mbar_waitu(bar + 8 * B_F2, par ^ 1);
        wg_fence(); proj<32, SSQ, 1, 0, 10>(acc, W, D); wg_commit();
        mbar_waitu(bar + 8 * (B_F2 + 1), par ^ 1);
        wg_fence(); proj<32, SSQ, 1, 10, 14>(acc, W, D); wg_commit();
        wg_wait<1>(); REL(B_R2, 0);
        wg_fence(); proj<32, SSQ, 1, 14, 20>(acc, W, D); wg_commit();
        mbar_waitu(bar + 8 * (B_F2 + 2), par ^ 1);
        wg_fence(); proj<32, SSQ, 1, 20, 24>(acc, W, D); wg_commit();
        wg_wait<1>(); REL(B_R2, 1);
        wg_fence(); proj<32, SSQ, 1, 24, 30>(acc, W, D); wg_commit();
        mbar_waitu(bar + 8 * (B_F2 + 3), par ^ 1);
        wg_fence(); proj<32, SSQ, 1, 30, 34>(acc, W, D); wg_commit();
        wg_wait<1>(); REL(B_R2, 2);
        wg_fence(); proj<32, SSQ, 1, 34, 40>(acc, W, D); wg_commit();
        const uint32_t sa = QK_SA, s1 = sa + QK_S12, s2 = sa + QK_S34;
        wg_wait<0>(); REL(B_R2, 3);
        if (warp == 0) TS(11 + wg);
        stsm4t(s1, pack2(acc[0], acc[1]), pack2(acc[2], acc[3]), pack2(acc[4], acc[5]), pack2(acc[6], acc[7]));
        stsm4t(s2, pack2(acc[8], acc[9]), pack2(acc[10], acc[11]), pack2(acc[12], acc[13]), pack2(acc[14], acc[15]));
      }
    }
    GTS(28);
    cluster_sync_all();
  } else if (wg == 2) {
    asm volatile("setmaxnreg.inc.sync.aligned.u32 160;");
    LANE_INIT();
    uint32_t W[4 * (40 - SSV)];
    ld_rest<0>(W, reinterpret_cast<const uint32_t*>(M.wv + (lane >> 2) * HD + col0 + warp * 16) + (lane & 3));
    uint4 m0[5];
#pragma unroll
    for (int i = 0; i < 5; i++) {
      const int t = i * 128 + warp * 32 + lane;
      m0[i] = __ldg(reinterpret_cast<const uint4*>(mem0 + ((t >> 1) & 7) * DM + (t >> 4) * 16 + ((t ^ (t >> 3)) & 1) * 8));
    }
    mbar_waitw(bar + 8 * B_W0, 0);
    load_w<VA>(W, sb + STG_K + 27 * 2048, warp, lane);
    load_w<VST - VA>(W + 4 * VA, sb + STG_V2, warp, lane);
    fence_async();
    mbar_expect_if(warp + lane == 0, bar + 8 * B_W1, 26 * 2048);
    bar_sync(1, 384);
#pragma unroll
    for (int i = 0; i < 5; i++) {
      const int t = i * 128 + warp * 32 + lane;
      sts128(sb + OFF_TILE + (t / 160) * (TILE_GRP - TILE_SBO) + t * 16, m0[i].x, m0[i].y, m0[i].z, m0[i].w);
    }
#pragma unroll
    for (int i = 4 * VST; i < 4 * (40 - SSV); i++) W[i] = movm(W[i]);
    fence_async();
    mbar_arrive_if(lane == 0, bar + 8 * (B_F1 + warp));
    mbar_expect_if(lane == 0, bar + 8 * (B_F2 + warp), 10240);
    mbar_arrive_if(warp == 3 && lane < 2, bar + 8 * B_PLFREE);
    cluster_sync_all();
    uint32_t vl[8];
    {
      const int step = warp;
      DESC(0);
      float v[16];
      mbar_waitw4(bar + 8 * B_F2, 0);
      wg_fence(); proj<32, SSV, 1, 0, 40>(v, W, D); wg_commit();
      wg_wait<0>();
      mbar_arrive_remote_if(lane < 4, rb0 + ((nA - 4 + lane) << 24) + OFF_BAR + 8 * B_R2);
#pragma unroll
      for (int j = 0; j < 8; j++) vl[j] = pack2v(v[2 * j], v[2 * j + 1]);
      if (warp == 0 && (unsigned)ig < 3) issue_tok(1, B_F2, B_R2, 0);
    }
#pragma unroll 1
    for (int step = 0; step < NSTEP; step++) {
      const uint32_t par = step & 1;
      asm volatile("" : "+r"(lane));
      const bool dual = is_dual(step), has_next = step + 1 < NSTEP;
      mbar_expect_if(lane == 0 && has_next, bar + 8 * (B_F2 + warp), 10240);
      if (warp == 0 && ig >= IG_V && dual && sync_b) wait_cnt(&g_xready[sched_l(step + 1)][0], 32);
      bar_sync(N_VGO, 384);
      CFENCE();
#define F1_BYTES (is_dual(step + 1) ? 15360 : 2560)
#define ARM() do { \
        mbar_expect_if(lane == 0 && has_next, bar + 8 * (B_F1 + warp), F1_BYTES); \
        mbar_expect_if(lane == 0 && has_next && warp * nA + (int)rank < 40, bar + 8 * (B_RS + warp), (warp * nA + (int)rank >= 36 ? nA : nh) * (dual ? 512 : 256)); } while (0)
#define O_ADDR() uint32_t oa = sb + OFF_O + (lane >> 4) * PL_SZ + warp * 256 + (lane & 15) * 16, xo = (lane >> 4) * 1024 + warp * 256 + (lane & 15) * 16; \
        asm volatile("" : "+r"(oa), "+r"(xo))
#define O_READY(act) do { if (has_next) { const uint4 ov = lds128(oa); \
        if (act) { st_async_v4(nxt + OFF_XL + xo, ov.x, ov.y, ov.z, ov.w, nxt + OFF_BAR + 8 * B_OPEER); \
                   st_async_v4(prv + OFF_XF + xo, ov.x, ov.y, ov.z, ov.w, prv + OFF_BAR + 8 * B_OPEER); } \
        fence_async(); bar_arrive(N_O, 384); } \
        if (warp == 0) TS(15); } while (0)
#define TOK_L3(g0) if (warp == 0 && ig >= (g0) && has_next) { mbar_waitu(bar + 8 * B_R1, ig == 3 ? par : (step - LAG) & 1); asm volatile("fence.proxy.async.global;" ::: "memory"); \
        bulk_g2s_mc_e(sb + OFF_TILE + ig * TILE_GRP + TILE_SBO, &g_xn[0][0] + uni(sched_l(step + 1) * (32 * DM)) + ig * 5120, 10240, bar + 8 * (B_F2 + ig), mcmask); }
#define OX_SA (sb + OFF_PL + (lane & 7) * 128 + (((warp * 2 + ((lane >> 3) & 1)) ^ (lane & 7)) << 4))
      if (dual) {
        uint32_t vf[8], vm[4], vn[8];
        {
          DESC(0);
          float v[24];
          ARM();
          wg_fence(); proj<48, SSV, 0, 30, 40, 30>(v, W, D); wg_commit();
          proj<48, SSV, 0, 0, VD1 - 10, 30>(v, W, D);
          bar_sync(N_SISS, 384);
          proj<48, SSV, 0, VD1 - 10, VD1 - 7, 30>(v, W, D); wg_commit();
          wg_wait<1>(); bar_arrive(N_G3, 160);
          wg_fence(); proj<48, SSV, 0, VD1 - 7, 10, 30>(v, W, D); wg_commit();
          proj<48, SSV, 0, 10, 13, 30>(v, W, D); wg_commit();
          wg_wait<1>(); REL(B_R1, 0);
          wg_fence(); proj<48, SSV, 0, 13, 20, 30>(v, W, D); wg_commit();
          proj<48, SSV, 0, 20, 23, 30>(v, W, D); wg_commit();
          wg_wait<1>(); REL(B_R1, 1);
          wg_fence(); proj<48, SSV, 0, 23, 30, 30>(v, W, D); wg_commit();
          wg_wait<0>(); REL(B_R1, 2);
          bar_arrive(N_VDONE, 160);
          if (warp == 0) TS(14);
#pragma unroll
          for (int j = 4; j < 8; j++) vf[j] = pack2v(v[4 + 2 * j], v[5 + 2 * j]);
          keep4(vf + 4, lane);
          vm[0] = pack2v(v[0], v[1]); vm[1] = pack2v(v[2], v[3]); vm[2] = pack2v(v[20], v[21]); vm[3] = pack2v(v[22], v[23]);
          keep4(vm, lane);
#pragma unroll
          for (int j = 0; j < 4; j++) vf[j] = pack2v(v[4 + 2 * j], v[5 + 2 * j]);
          keep4(vf, lane);
        }
        {
          DESC(1);
          float o[8];
          O_ADDR();
          bar_sync(N_PM, 224);
          wg_fence();
          MM<8>::rs<dlo(OFF_PL + 3584, 128), 0>(o, vl, D.p);
          MM<8>::rs<dlo(OFF_PL + PL_SZ + 3584, 128), 0>(o + 4, vf, D.p);
          MM<8>::rs<dlo(OFF_PL + 3584 + 256, 128), 1>(o, vl + 4, D.p);
          MM<8>::rs<dlo(OFF_PL + PL_SZ + 3584 + 256, 128), 1>(o + 4, vf + 4, D.p);
          MM<8>::rs<dlo(OFF_PL + 3584 + 512, 128), 1>(o, vm, D.p);
          MM<8>::rs<dlo(OFF_PL + PL_SZ + 3584 + 512, 128), 1>(o + 4, vm, D.p);
          wg_commit();
          fence_sched(step);
          const uint4 il = lds128(sb + OFF_INV + (lane & 3) * 16), jf = lds128(sb + OFF_INV + 64 + (lane & 3) * 16);
          const float i0 = rcpf(__uint_as_float(il.x) + __uint_as_float(il.y)), i1 = rcpf(__uint_as_float(il.z) + __uint_as_float(il.w));
          const float j0 = rcpf(__uint_as_float(jf.x) + __uint_as_float(jf.y)), j1 = rcpf(__uint_as_float(jf.z) + __uint_as_float(jf.w));
          { const uint32_t k4[4] = {__float_as_uint(i0), __float_as_uint(i1), __float_as_uint(j0), __float_as_uint(j1)}; keep4(k4, lane | (oa ^ xo)); }
          wg_wait<0>();
          stsm4t(oa, pack2(o[0] * i0, o[1] * i1), pack2(o[2] * i0, o[3] * i1), pack2(o[4] * j0, o[5] * j1), pack2(o[6] * j0, o[7] * j1));
          O_READY(true);
          TOK_L3(IG_V);
        }
        {
          DESC(2);
          float v[16];
          bar_sync(N_TURN, 256);
          mbar_waitu(bar + 8 * B_F2, par ^ 1);
          wg_fence(); proj<32, SSV, 1, 0, 10>(v, W, D); wg_commit();
          mbar_waitu(bar + 8 * (B_F2 + 1), par ^ 1);
          wg_fence(); proj<32, SSV, 1, 10, 14>(v, W, D); wg_commit();
          wg_wait<1>(); REL(B_R2, 0);
          wg_fence(); proj<32, SSV, 1, 14, 20>(v, W, D); wg_commit();
          mbar_waitu(bar + 8 * (B_F2 + 2), par ^ 1);
          wg_fence(); proj<32, SSV, 1, 20, 24>(v, W, D); wg_commit();
          wg_wait<1>(); REL(B_R2, 1);
          wg_fence(); proj<32, SSV, 1, 24, 30>(v, W, D); wg_commit();
          mbar_waitu(bar + 8 * (B_F2 + 3), par ^ 1);
          wg_fence(); proj<32, SSV, 1, 30, 34>(v, W, D); wg_commit();
          wg_wait<1>(); REL(B_R2, 2);
          wg_fence(); proj<32, SSV, 1, 34, 40>(v, W, D); wg_commit();
          wg_wait<0>(); REL(B_R2, 3);
#pragma unroll
          for (int j = 0; j < 8; j++) vn[j] = pack2v(v[2 * j], v[2 * j + 1]);
          keep4(vn, lane); keep4(vn + 4, lane);
          if (warp == 0) TS(18);
        }
        DESC(3);
        uint32_t ow[16];
        bar_sync(N_P, 256);
        fence_async();
#define PV16(i, off, va) { float o[8]; wg_fence(); \
          MM<16>::rs<dlo(OFF_PL + (off), 128), 0>(o, va, D.p); \
          MM<16>::rs<dlo(OFF_PL + (off) + 256, 128), 1>(o, va + 4, D.p); \
          MM<16>::rs<dlo(OFF_PL + (off) + 512, 128), 1>(o, vm, D.p); \
          wg_commit(); wg_wait<0>(); \
          _Pragma("unroll") for (int j = 0; j < 4; j++) ow[4 * (i) + j] = pack2v(o[2 * j], o[2 * j + 1]); \
          keep4(ow + 4 * (i), lane); }
        PV16(0, 0, vl) PV16(1, 1792, vl) PV16(2, PL_SZ, vf) PV16(3, PL_SZ + 1792, vf)
        const uint32_t s1 = OX_SA + (lane < 16 ? 3072 : 0), s2 = OX_SA + (lane < 16 ? 2048 : 1024);
        bar_sync(N_V, 128);
        stsm4t(s1, ow[0], ow[1], ow[2], ow[3]);
        stsm4t(s2, ow[4], ow[5], ow[6], ow[7]);
        stsm4t(s1 + PL_SZ, ow[8], ow[9], ow[10], ow[11]);
        stsm4t(s2 + PL_SZ, ow[12], ow[13], ow[14], ow[15]);
#pragma unroll
        for (int j = 0; j < 8; j++) vl[j] = vn[j];
      } else {
        uint32_t vm[4], vn[8];
        {
          DESC(4);
          float v[4];
          wg_fence(); proj<8, SSV, 0, 30, 40, 30>(v, W, D); wg_commit();
          proj<8, SSV, 0, 0, VS1, 30>(v, W, D); wg_commit();
          ARM();
          bar_sync(N_SISS, 384);
          wg_wait<1>(); bar_arrive(N_G3, 160);
          wg_fence(); proj<8, SSV, 0, VS1, 30, 30>(v, W, D); wg_commit();
          if (has_next) { mbar_waitu2(bar + 8 * B_F2, bar + 8 * (B_F2 + 1), par ^ 1); mbar_waitu(bar + 8 * (B_F2 + 2), par ^ 1); }
          wg_wait<0>();
          bar_arrive(N_VDONE, 160);
          vm[0] = pack2v(v[0], v[1]); vm[1] = pack2v(v[2], v[3]); vm[2] = pack2v(v[1], v[0]); vm[3] = pack2v(v[3], v[2]);
        }
        DESC(5);
        float v[16];
        {
          wg_fence(); proj<32, SSV, 1, 0, VS2>(v, W, D); wg_commit();
          {
            float o[4];
            O_ADDR();
            bar_sync(N_PM, 192);
            if (warp == 0) TS(14);
            wg_fence();
            MM<8>::rs<dlo(OFF_PL + 3584, 128), 0>(o, vl, D.p);
            MM<8>::rs<dlo(OFF_PL + 3584 + 256, 128), 1>(o, vl + 4, D.p);
            MM<8>::rs<dlo(OFF_PL + 3584 + 512, 128), 1>(o, vm, D.p);
            wg_commit();
            fence_sched(step);
            const uint4 il = lds128(sb + OFF_INV + (lane & 3) * 16);
            const float i0 = rcpf(__uint_as_float(il.x) + __uint_as_float(il.y)), i1 = rcpf(__uint_as_float(il.z) + __uint_as_float(il.w));
            { const uint32_t k4[4] = {__float_as_uint(i0), __float_as_uint(i1), oa, xo}; keep4(k4, lane); }
            wg_wait<0>();
            stsm2t(oa, pack2(o[0] * i0, o[1] * i1), pack2(o[2] * i0, o[3] * i1));
            O_READY(lane < 16);
            TOK_L3(3);
          }
          if (has_next) {
            mbar_arrive_remote_if(lane < VS2 / 10, rb0 + ((nA - 4 + lane) << 24) + OFF_BAR + 8 * B_R2);
            bar_sync(N_TURN, 256);
          }
          if (VS2 < 30) { wg_fence(); proj<32, SSV, 1, VS2, 30>(v, W, D); wg_commit(); }
          if (has_next) mbar_waitu(bar + 8 * (B_F2 + 3), par ^ 1);
          if (VS2 < 30) { wg_wait<0>(); if (has_next) REL(B_R2, 2); }
          wg_fence(); proj<32, SSV, 1, 30, 40>(v, W, D); wg_commit();
          wg_wait<0>();
          if (has_next) REL(B_R2, 3);
#pragma unroll
          for (int j = 0; j < 8; j++) vn[j] = pack2v(v[2 * j], v[2 * j + 1]);
          keep4(vn, lane); keep4(vn + 4, lane);
          if (warp == 0) TS(18);
        }
        float o[16];
        bar_sync(N_P, 256);
        fence_async();
        wg_fence();
        MM<32>::rs<dlo(OFF_PL, 128), 0>(o, vl, D.p);
        MM<32>::rs<dlo(OFF_PL + 256, 128), 1>(o, vl + 4, D.p);
        MM<32>::rs<dlo(OFF_PL + 512, 128), 1>(o, vm, D.p);
        wg_commit();
        const uint32_t s1 = OX_SA + (lane < 16 ? 3072 : 0), s2 = OX_SA + (lane < 16 ? 2048 : 1024);
        wg_wait<0>();
        bar_sync(N_V, 128);
        stsm4t(s1, pack2(o[0], o[1]), pack2(o[2], o[3]), pack2(o[4], o[5]), pack2(o[6], o[7]));
        stsm4t(s2, pack2(o[8], o[9]), pack2(o[10], o[11]), pack2(o[12], o[13]), pack2(o[14], o[15]));
#pragma unroll
        for (int j = 0; j < 8; j++) vl[j] = vn[j];
      }
      bar_arrive(N_OX, 160);
      if (warp == 0) TS(16);
    }
    cluster_sync_all();
  } else {
    asm volatile("setmaxnreg.dec.sync.aligned.u32 32;");
    if (wg > 3) return;
    LANE_INIT();
    struct RsJob { uint32_t* gp; uint32_t la, mb; int n; };
    auto rs_prep = [&](int step, int s, int c) {
      RsJob j;
      const int u = s * nA + rank;
      j.gp = &g_part[0][0][0][0] + (uint32_t)((((step & 1) * 2 + c) * NCL + cl) * 2560 + u * 64 + (lane >> 2) * 8 + (lane & 3));
      j.la = sb + OFF_TILE + c * LAND_F + LAND(s) + lane * 8;
      j.mb = bar + 8 * (B_RS + s);
      j.n = u >= 40 ? 0 : u >= 36 ? 3 : 1;
      asm volatile("" : "+l"(j.gp), "+r"(j.la));
      return j;
    };
    auto rs_sum = [&](RsJob j, int step) {
      if (j.n) {
        auto five = [&](uint32_t la) {
          uint2 p[5];
#pragma unroll
          for (int i = 0; i < 4; i++) p[i] = lds64(la + i * 256);
          asm volatile("{\n.reg .pred q;\nsetp.eq.s32 q, %3, 5;\nmov.u32 %0, 0;\nmov.u32 %1, 0;\n@q ld.shared.v2.b32 {%0,%1}, [%2];\n}"
                       : "=r"(p[4].x), "=r"(p[4].y) : "r"(la + 1024), "r"(nh) : "memory");
          return make_uint2(hadd2bf(hadd2bf(p[0].x, p[1].x), hadd2bf(hadd2bf(p[2].x, p[3].x), p[4].x)),
                            hadd2bf(hadd2bf(p[0].y, p[1].y), hadd2bf(hadd2bf(p[2].y, p[3].y), p[4].y)));
        };
        const uint32_t tag = ((step >> 1) & 1) ^ 1;
        mbar_waitw(j.mb, step & 1);
        uint2 t = five(j.la);
        if (j.n > 1) {
          const uint2 a = five(j.la + (nh == 5 ? 1280 : TILE_GRP - 1280)), b = five(j.la + TILE_GRP);
          t.x = hadd2bf(t.x, hadd2bf(a.x, b.x)); t.y = hadd2bf(t.y, hadd2bf(a.y, b.y));
        }
        const uint32_t t0 = (movm(t.x) & ~1u) | tag, t1 = (movm(t.y) & ~1u) | tag;
        asm volatile("st.relaxed.gpu.global.b32 [%0], %1;" :: "l"(j.gp), "r"(lane & 16 ? t1 : t0) : "memory");
        asm volatile("st.relaxed.gpu.global.b32 [%0], %1;" :: "l"(j.gp + 4), "r"(lane & 16 ? t0 : t1) : "memory");
      }
    };
    if (warp * nA + (int)rank < 40) {
#pragma unroll
      for (int e = LAG; e < LAG + 2; e++)
        if ((e >> 1) & 1) *reinterpret_cast<uint2*>(&g_part[(e & 1) * 2 + 1][cl][warp * nA + rank][lane * 2]) = make_uint2(1u, 1u);
      __threadfence();
    }
    if (warp == 2 && ig >= 0 && sync_b) wait_cnt(&g_xready[0][0], 32);
    cluster_sync_all();
    if (warp == 2 && ig >= 0) bulk_g2s_mc_e(sb + OFF_TILE + ig * TILE_GRP + TILE_SBO, &g_xn[0][0] + ig * 5120, 10240, bar + 8 * (B_F2 + ig), mcmask);
    bar_sync(N_PI, 128);
#pragma unroll 1
    for (int i = warp; i < 20; i += 4) {
      int c0, c1; wo_coord(i, t3, head, c0, c1);
      if (i >= 2 && i < 15) tma2d_e(sb + OFF_WO + (i - 2) * 4096, &M.wo32, c0, c1, bar + 8 * B_W1);
      else if (lane == 0) tma2d_prefetch(&M.wo32, c0, c1);
      __syncwarp();
    }
#pragma unroll 1
    for (int step = 0; step < NSTEP; step++) {
      const uint32_t par = step & 1;
      asm volatile("" : "+r"(lane));
      const bool dual = is_dual(step), has_next = step + 1 < NSTEP;
      {
        bar_sync(N_PX, dual ? 256 : 192);
        if (dual || warp >= 2) tok_softmax(sb, dual ? warp : warp - 2, lane);
        bar_arrive(N_P, 256);
        asm volatile("" : "+r"(lane));
        if (has_next) {
          if (step + 2 == LAG && lane < 20) asm volatile("prefetch.global.L2 [%0];" :: "l"(mem0 + (warp * 20 + lane) * 64));
          const int nw = ig >= 0 ? 3 : 4, j0 = warp < nw ? warp : 8;
          const int sh = dual ? 1 : 0;
          rs_sum(rs_prep(step, j0 >> sh, j0 & sh), step);
          if (warp == 0) TS(17);
          if (dual) rs_sum(rs_prep(step, (j0 + nw) >> 1, (j0 + nw) & 1), step);
          if (warp == 0) { bar_sync(N_C, 288); }
          mbar_arrive_remote_if(lane < nA, rb0 + (lane << 24) + OFF_BAR + 8 * B_LANDFREE);
          const uint32_t gap = dual ? POLL_GAPD : POLL_GAP;
          if (gap) { const uint32_t t0 = clock32(); while (clock32() - t0 < gap) {} }
#pragma unroll 1
          for (int j = j0; j < (dual ? 8 : 4); j += nw) {
            const int u = (j >> sh) * nA + rank, c = j & sh;
            if (u < UMAX && (c || step + 1 != NSEG)) {
              const uint32_t* gq = &g_part[0][0][0][0] + (uint32_t)((par * 2 + c) * NCL * 2560 + u * 64 + lane * 2);
              uint2 pa[NCL];
              POLL(pa, gq);
              deliver(pa, gq, u, c, step + 1 < NSEG ? c : 0, dual ? DS_DUAL : DS_SINGLE, step, j == 0, lane);
            }
            if (warp == 0 && j == 0) TS(13);
          }
          if (warp >= nw && (is_dual(step + 1) || (ig < 3 && step + 2 < NSTEP))) {
            issue_tok(is_dual(step + 1) ? sched_f(step + 1) : sched_l(step + 2), is_dual(step + 1) ? B_F1 : B_F2, B_R2, par ^ 1);
          }
          if (step + 1 == LAG && UMAX) {
            uint4 v[5];
#pragma unroll
            for (int i = 0; i < 5; i++) { const int t = warp * 160 + i * 32 + lane; v[i] = *reinterpret_cast<const uint4*>(mem0 + ((t >> 1) & 7) * DM + (t >> 4) * 16 + ((t ^ (t >> 3)) & 1) * 8); }
            mbar_waitu(bar + 8 * B_LANDFREE, par);
#pragma unroll
            for (int i = 0; i < 5; i++)
              st_async_v4(sb + OFF_TILE + LAND_F + warp * TILE_GRP + (i * 32 + lane) * 16, v[i].x, v[i].y, v[i].z, v[i].w, bar + 8 * (B_F1 + warp));
          }
        }
      }
      if (warp == (ig >= 0 && !is_dual(step + 1) ? 2 : 3)) {
        unsigned char* o0 = g_o + uni(step % RO * (96 * 8192) + (head * 3 + t3) * (dual ? 8192 : 4096));
        bar_sync(N_OX, 160);
        fence_async();
        bulk_s2g_es(o0, sb + OFF_PL, 4096);
        if (dual) bulk_s2g_es(o0 + 4096, sb + OFF_PL + PL_SZ, 4096);
        asm volatile("cp.async.bulk.commit_group;" ::: "memory");
        asm volatile("cp.async.bulk.wait_group.read 0;" ::: "memory");
        __syncwarp();
        mbar_arrive_remote_if(lane < 2, (lane ? nxt : prv) + OFF_BAR + 8 * B_PLFREE);
        asm volatile("cp.async.bulk.wait_group 0;" ::: "memory");
        asm volatile("fence.proxy.async.global;" ::: "memory");
        __syncwarp();
        if (lane == 0) red_release(&g_f[F_O + (head * 3 + t3) / 5][step], 1u);
        __syncwarp();
      }
    }
    cluster_sync_all();
  }
}

__device__ __forceinline__ float gelu2(float x) {
  const float u = x * fmaf(x * x, 0.7978845608028654f * 0.044715f, 0.7978845608028654f);
  float t; asm("tanh.approx.f32 %0, %1;" : "=f"(t) : "f"(u));
  return fmaf(x, t, x); }

struct BParams {
  CUtensorMap wmap[5];
  CUtensorMap wo16;
  const __nv_bfloat16* x;
  __nv_bfloat16* out;
  uint64_t desc;
};
#define BO_O 0
#define BO_RES (6 * 8192)
#define OP_RES 63488
#define BO_STG (BO_RES + 2 * OP_RES)
#define BO_RING_OP (BO_STG + 16384)
#define OP_SLOT 12288
#define NS_OP 3
#define BO_H 81920
#define BO_W1 (BO_H + 16384)
#define BO_RING_MLP (BO_W1 + 81920)
#define BO_BAR 229376
#define BO_BOX (BO_BAR + 248)
#define BO_CARRY (BO_BAR + 512)
#define BO_STAT (BO_CARRY + 2048)
#define B_SMEM (BO_STAT + 256)
static_assert(B_SMEM <= 232448 && BO_RING_OP + NS_OP * OP_SLOT == BO_BAR && BO_RING_MLP + 3 * 16384 == BO_BAR && 2 * 83968 <= BO_RING_MLP, "smem");
enum { BB_W = 0, BB_FULL = 2, BB_TMP = BB_FULL + 3, BB_OFULL = BB_FULL + 5, BB_SFREE = BB_OFULL,
       BB_STAT = BB_SFREE + 6, BB_ZFREE, BB_DONE = BB_ZFREE + 3,
       BB_EMPTY, BB_START = BB_EMPTY, BB_USED = BB_EMPTY + 2, BB_NUM = BB_USED + 3 };
enum { NB_PP = 1, NB_H = 3, NB_END = 4, NB_END2 = 5, NB_STAGED = 6, NB_FREE = 8, NB_EARLY = 10, NB_LAST = 11 };

#define DESC_LO(off) (((SMEM0 + (off)) >> 4) | (1u << 16))

__device__ __forceinline__ uint32_t ld_relaxed(const uint32_t* p) { uint32_t v; asm volatile("ld.relaxed.gpu.global.b32 %0, [%1];" : "=r"(v) : "l"(p) : "memory"); return v; }
__device__ __forceinline__ int fmask(int r) { return (r < NSEG) | ((r >= LAG && r < NSTEP) << 1); }
__device__ __forceinline__ int bmask(int r) { return (r <= NSEG) | ((r >= LAG) << 1); }
__device__ __forceinline__ uint32_t rtarget(int mask) { return mask == 3 ? 64 : 32; }
__device__ __forceinline__ void warp_signal(uint32_t* p, int lane) {
  __syncwarp();
  asm volatile("{\n.reg .pred q;\nsetp.eq.u32 q, %1, 0;\n@q red.release.gpu.global.add.u32 [%0], 1;\n}" :: "l"(p), "r"(lane) : "memory");
}
__device__ __forceinline__ uint32_t pack2h(float lo, float hi) { uint32_t r; asm("cvt.rn.f16x2.f32 %0, %1, %2;" : "=r"(r) : "f"(hi), "f"(lo)); return r; }
template <bool H> __device__ __forceinline__ uint32_t pk(float lo, float hi) { return H ? pack2h(lo, hi) : pack2(lo, hi); }
template <int N, bool H> __device__ __forceinline__ void stage_out(const float* d, uint32_t dst, int warp, int lane) {
  const uint32_t sa = dst + ((lane >> 4) * 8 + (lane & 7)) * 128 + (((2 * warp + ((lane >> 3) & 1)) ^ (lane & 7)) << 4);
#pragma unroll
  for (int m = 0; m < N / 16; m++)
    stsm4t(sa + m * 2048, pk<H>(d[8 * m], d[8 * m + 1]), pk<H>(d[8 * m + 2], d[8 * m + 3]), pk<H>(d[8 * m + 4], d[8 * m + 5]), pk<H>(d[8 * m + 6], d[8 * m + 7]));
}
template <int N> __device__ __forceinline__ void acc_live(float* d) {
#pragma unroll
  for (int i = 0; i < N / 2; i++) asm volatile("" : "+f"(d[i]) :: "memory");
}
struct Ring {
  uint32_t sl, ph;
  template <int NS> __device__ __forceinline__ void step() { if (++sl == NS) { sl = 0; ph ^= 1; } }
};

#define LOCKSTEP 0
#define KOFF(x) (DESC_LO(BO_O) + ((x) >> 2) * (N * 8) + ((x) & 3) * 2)
template <int N, int P>
__device__ __forceinline__ void op_pass(const uint32_t* W, uint32_t bar, Dsc alo, Dsc blo, Dsc xlo, bool x2, Ring& rg, int wg, int warp, int lane, int r) {
  float acc[N / 2];
  blo.e = xlo.e = fresh<P + N / 64 * 5>(r);
  const Dsc tlo = blo + uni(rg.sl) * (OP_SLOT / 16);
  if (P == 0) mbar_waitu(bar + 8 * BB_OFULL, r & 1);
  CTS(5 * P);
  if (!LOCKSTEP || P > 1 || P == wg) bar_sync(NB_PP + wg, 256);
  wg_fence();
#define OP_R(x) MM<N>::template rs<KOFF(4 * (x >> 1) + (x & 1)), (x != 0)>(acc, W + 32 * P + 4 * x, blo);
#define OP_S(x) MM<N>::template ss<DESC_LO(BO_RES) + (6 * P + x) * 128, KOFF(4 * (x >> 1) + 2 + (x & 1)), 1>(acc, alo, blo);
#define OP_T(x) MM<N>::template ss<DESC_LO(BO_RING_OP) + x * 128, KOFF(14 + x), 1>(acc, tlo, blo);
  OP_R(0) OP_S(0) OP_R(1) OP_S(1) OP_R(2) OP_S(2) OP_R(3) OP_S(3)
  if (P == 0) mbar_waitu(bar + 8 * (BB_OFULL + 1), r & 1);
  if (P == 4) wg_commit();
  OP_R(4) OP_S(4) OP_R(5) OP_S(5)
  if (P == 1 && x2) MM<N>::template ss<DESC_LO(BO_RES) + 30 * 128, KOFF(20), 1>(acc, alo, xlo);
  if (P == 4) { wg_commit(); wg_wait<1>(); bar_arrive(NB_EARLY, 288); CTS(21); wg_fence(); }
  mbar_waitu(bar + 8 * (BB_FULL + rg.sl), rg.ph);
  OP_R(6) OP_T(0) OP_R(7) OP_T(1)
  if (P == 0) mbar_waitu(bar + 8 * (BB_OFULL + 2), r & 1);
  OP_T(2) OP_T(3)
  if (P == 0) MM<N>::template rs<KOFF(20), 1>(acc, W + 160, xlo);
  OP_T(4) OP_T(5)
  wg_commit();
  if (!LOCKSTEP || P) bar_arrive(NB_PP + 1 - wg, 256);
  CTS(5 * P + 2);
  bar_sync(NB_FREE + wg, 160);
  wg_wait<0>();
  acc_live<N>(acc);
  if (P == 4) bar_arrive(NB_LAST, 288);
  mbar_arrive_if(lane == 0, bar + 8 * (BB_USED + rg.sl));
  CTS(5 * P + 3);
  stage_out<N, false>(acc, SMEM0 + BO_STG + wg * 8192, warp, lane);
  bar_arrive(NB_STAGED + wg, 160);
  CTS(5 * P + 4);
  rg.step<NS_OP>(); rg.step<NS_OP>();
}
template <int N>
__device__ __forceinline__ void op_round(const uint32_t* W, uint32_t bar, Dsc alo, Dsc blo, Dsc xlo, bool x2, Ring& rg, int wg, int warp, int lane, int r) {
  op_pass<N, 0>(W, bar, alo, blo, xlo, x2, rg, wg, warp, lane, r);
  op_pass<N, 1>(W, bar, alo, blo, xlo, x2, rg, wg, warp, lane, r);
  op_pass<N, 2>(W, bar, alo, blo, xlo, x2, rg, wg, warp, lane, r);
  op_pass<N, 3>(W, bar, alo, blo, xlo, x2, rg, wg, warp, lane, r);
  op_pass<N, 4>(W, bar, alo, blo, xlo, x2, rg, wg, warp, lane, r);
}
__device__ __forceinline__ void carry_in(uint32_t sb, int wg, int warp, int lane) {
  const int row = (lane >> 1) & 3;
  if (lane < 16) {
    const uint4 v = lds128(sb + BO_CARRY + (wg * 4 + warp) * 256 + lane * 16);
    sts128(sb + BO_H + wg * 8192 + (lane >> 3) * 4096 + row * 128 + (((2 * warp + (lane & 1)) ^ row) << 4), v.x, v.y, v.z, v.w);
  }
  __syncwarp();
}
template <int N, int Z>
__device__ __forceinline__ void p1_pair(float* acc, const uint32_t* W, uint32_t bar, Dsc alo, Dsc blo, int lane, int r) {
  constexpr int ZOFF = N == 64 ? (2 * Z % 3) * 1024 : (Z / 2 * 2 % 3) * 1024 + (Z & 1) * 256;
  blo.e = fresh<10 + Z / 3 + N / 64 * 2>(r);
  mbar_waitu(bar + 8 * (BB_FULL + Z), r & 1);
  CTS(40 + Z);
  wg_fence();
#define P1_B(k) \
  MM<N, true>::template rs<DESC_LO(BO_RING_MLP) + ZOFF + k * 512, (2 * Z + k != 0)>(acc, W + 16 * Z + 8 * k, blo); \
  MM<N, true>::template ss<DESC_LO(BO_W1) + (2 * Z + k) * 512, DESC_LO(BO_RING_MLP) + ZOFF + k * 512 + 4, 1>(acc, alo, blo); \
  MM<N, true>::template rs<DESC_LO(BO_RING_MLP) + ZOFF + k * 512 + 2, 1>(acc, W + 16 * Z + 8 * k + 4, blo); \
  MM<N, true>::template ss<DESC_LO(BO_W1) + (2 * Z + k) * 512 + 128, DESC_LO(BO_RING_MLP) + ZOFF + k * 512 + 6, 1>(acc, alo, blo);
  P1_B(0)
  if (N == 64 && (Z == 1 || Z == 2)) { wg_commit(); wg_wait<1>(); mbar_arrive_if(lane == 0, bar + 8 * (BB_EMPTY + Z - 1)); wg_fence(); }
  P1_B(1)
  wg_commit();
}
template <int N>
__device__ __forceinline__ void phase1(const uint32_t* W, uint32_t sb, Dsc alo, Dsc blo, int half, int wg, int warp, int lane, int off, int r) {
  float acc[N / 2];
  const uint32_t bar = sb + BO_BAR;
  CTS(30);
  p1_pair<N, 0>(acc, W, bar, alo, blo, lane, r);
  p1_pair<N, 1>(acc, W, bar, alo, blo, lane, r);
  p1_pair<N, 2>(acc, W, bar, alo, blo, lane, r);
  if (N == 32) p1_pair<N, 3>(acc, W, bar, alo, blo, lane, r);
  mbar_waitu(bar + 8 * (BB_SFREE + 4 + wg), (r + 1) & 1);
  carry_in(sb, wg, warp, lane);
  if (N == 32) mbar_arrive_if(lane < 2, bar + 8 * (BB_EMPTY + lane));
  else p1_pair<N, 3>(acc, W, bar, alo, blo, lane, r);
  p1_pair<N, 4>(acc, W, bar, alo, blo, lane, r);
  const int c = (lane >> 3) & 1, i0 = (lane >> 4) * 8 + (lane & 7) + off;
  uint32_t a0 = sb + BO_H + wg * 8192 + half * 4096 + i0 * 128 + (((2 * warp + c) ^ (i0 & 7)) << 4);
  uint32_t a1 = i0 >= 16 ? sb + BO_CARRY + (wg * 4 + warp) * 256 + half * 128 + (i0 - 16) * 32 + c * 16 : a0 + 2048, a3 = a1 + (i0 >= 16 ? 128 : 4096);
  asm volatile("" : "+r"(a0), "+r"(a1), "+r"(a3));
  mbar_waitu(bar + 8 * BB_STAT, r & 1);
  const uint32_t sa = sb + BO_STAT + half * 128 + (lane & 3) * 32;
  uint4 t[2] = {lds128(sa), lds128(sa + 16)};
  wg_wait<0>();
  acc_live<N>(acc);
  CTS(32);
#pragma unroll
  for (int m = 0; m < N / 16; m++) {
    const float s0 = __uint_as_float(t[m & 1].x), s1 = __uint_as_float(t[m & 1].y), s2 = __uint_as_float(t[m & 1].z), s3 = __uint_as_float(t[m & 1].w);
    float* d = acc + 8 * m;
    d[0] *= s0; d[1] *= s1; d[2] *= s0; d[3] *= s1; d[4] *= s2; d[5] *= s3; d[6] *= s2; d[7] *= s3;
    if (m + 2 < N / 16) t[m & 1] = lds128(sa + 128 + m * 16);
#pragma unroll
    for (int j = 0; j < 8; j++) d[j] = gelu2(d[j]);
  }
#pragma unroll
  for (int m = 0; m < N / 16; m++)
    stsm4t(m == 1 ? a1 : m == 3 ? a3 : a0 + m * 2048, pack2(acc[8 * m], acc[8 * m + 1]), pack2(acc[8 * m + 2], acc[8 * m + 3]), pack2(acc[8 * m + 4], acc[8 * m + 5]), pack2(acc[8 * m + 6], acc[8 * m + 7]));
}
template <int N, int P>
__device__ __forceinline__ void p2_mma(float* acc, const uint32_t* W, Dsc alo, Dsc blo, int r) {
  blo.e = fresh<P + N / 64 * 5>(r);
  MM<N>::template rs<DESC_LO(BO_H), 0>(acc, W + 80 + 16 * P, blo);     MM<N>::template ss<DESC_LO(0) + P * 1024, DESC_LO(BO_H) + 512, 1>(acc, alo, blo);
  MM<N>::template rs<DESC_LO(BO_H) + 2, 1>(acc, W + 84 + 16 * P, blo); MM<N>::template ss<DESC_LO(0) + P * 1024 + 128, DESC_LO(BO_H) + 514, 1>(acc, alo, blo);
  MM<N>::template rs<DESC_LO(BO_H) + 4, 1>(acc, W + 88 + 16 * P, blo); MM<N>::template ss<DESC_LO(0) + P * 1024 + 512, DESC_LO(BO_H) + 516, 1>(acc, alo, blo);
  MM<N>::template rs<DESC_LO(BO_H) + 6, 1>(acc, W + 92 + 16 * P, blo); MM<N>::template ss<DESC_LO(0) + P * 1024 + 640, DESC_LO(BO_H) + 518, 1>(acc, alo, blo);
}
template <int N, int P, int T>
__device__ __forceinline__ void p2_pass(const uint32_t* W, uint32_t bar, Dsc alo, Dsc blo, int wg, int warp, int lane, int r) {
  float acc[N / 2], ac2[N / 2];
  CTS(5 * P);
  if (P || wg) bar_sync(NB_PP + wg, 256);
  wg_fence();
  p2_mma<N, P>(acc, W, alo, blo, r);
  wg_commit();
  if constexpr (T == 2) { p2_mma<N, P + 1>(ac2, W, alo, blo, r); wg_commit(); }
  if (P < 4 || !wg) bar_arrive(NB_PP + 1 - wg, 256);
  CTS(5 * P + 2);
  if (T == 1 && (P == 2 || P == 3)) mbar_waitu(bar + 8 * (BB_SFREE + 2 * (P - 2) + wg), r & 1);
  wg_wait<T - 1>();
  acc_live<N>(acc);
  if (P == 4) bar_sync(NB_H, 256);
  CTS(5 * P + 3);
  constexpr int K = P / T & 1;
  stage_out<N, true>(acc, SMEM0 + (P == 4 ? BO_H : BO_RING_MLP + (2 - K) * 16384) + wg * 8192, warp, lane);
  if constexpr (T == 2) {
    wg_wait<0>();
    acc_live<N>(ac2);
    stage_out<N, true>(ac2, SMEM0 + BO_RING_MLP + (2 - K) * 16384 + wg * 8192 + 4096, warp, lane);
  }
  bar_arrive(NB_STAGED + (P == 4 ? 4 : 2 * K) + wg, 160);
  CTS(5 * P + 4);
}
template <int N>
__device__ __forceinline__ void phase2(const uint32_t* W, uint32_t bar, Dsc alo, Dsc blo, int wg, int warp, int lane, int r) {
  if constexpr (N == 64) {
    p2_pass<N, 0, 1>(W, bar, alo, blo, wg, warp, lane, r);
    p2_pass<N, 1, 1>(W, bar, alo, blo, wg, warp, lane, r);
    p2_pass<N, 2, 1>(W, bar, alo, blo, wg, warp, lane, r);
    p2_pass<N, 3, 1>(W, bar, alo, blo, wg, warp, lane, r);
  } else {
    p2_pass<N, 0, 2>(W, bar, alo, blo, wg, warp, lane, r);
    p2_pass<N, 2, 2>(W, bar, alo, blo, wg, warp, lane, r);
  }
  p2_pass<N, 4, 1>(W, bar, alo, blo, wg, warp, lane, r);
}

__device__ __forceinline__ void ldg4(uint32_t* v, const void* p) {
  asm volatile("ld.relaxed.gpu.global.v4.u32 {%0,%1,%2,%3}, [%4];" : "=r"(v[0]), "=r"(v[1]), "=r"(v[2]), "=r"(v[3]) : "l"(p) : "memory"); }
__device__ __forceinline__ void stg4(void* p, const uint32_t* v) {
  asm volatile("st.global.v4.u32 [%0], {%1,%2,%3,%4};" :: "l"(p), "r"(v[0]), "r"(v[1]), "r"(v[2]), "r"(v[3]) : "memory"); }
struct RowPtr {
  unsigned char *p, *q, *t;
  __device__ __forceinline__ void ld(uint32_t* v, int o) const {
    ldg4(v, p + o); ldg4(v + 4, q + o);
    asm volatile("ld.relaxed.gpu.global.v2.u32 {%0,%1}, [%2];" : "=r"(v[8]), "=r"(v[9]) : "l"(t + o) : "memory");
  }
  __device__ __forceinline__ void st(const uint32_t* w, int o) const {
    stg4(p + o, w); stg4(q + o, w + 4);
    asm volatile("st.global.v2.u32 [%0], {%1,%2};" :: "l"(t + o), "r"(w[8]), "r"(w[9]) : "memory");
  }
};
__device__ __forceinline__ RowPtr row_img(int r, int n, int lane) {
  unsigned char* b = &g_acc[0][r % RD][n * 128];
  unsigned char* p = b + (uint32_t)((lane >> 3) * 8192 + (((lane ^ n) & 7) << 4));
  return {p, p + 32768, b + (uint32_t)(65536 + (lane >> 4) * 8192 + ((((lane >> 1) ^ n) & 7) << 4) + (lane & 1) * 8)};
}
__device__ __forceinline__ RowPtr row_ext(const void* lin, bool xn, int layer, int tok, int lane) {
  unsigned char* b = xn ? reinterpret_cast<unsigned char*>(&g_xn[layer][0]) + (uint32_t)((tok >> 5) * 40960 + ((tok >> 3) & 3) * 2560 + (tok & 7) * 32)
                        : (unsigned char*)lin + (uint32_t)(tok * 1280);
  const uint32_t o = (lane >> 1) * 256 + ((lane ^ (tok >> 2)) & 1) * 16;
  return {b + (uint32_t)(xn ? o + (lane >= 20 ? 7680 : 0) : lane * 16),
          b + (uint32_t)(xn ? o + 4096 + 7680 + (lane >= 8 ? 7680 : 0) + (lane >= 28 ? 7680 : 0) : lane * 16 + 512),
          b + (uint32_t)(xn ? (lane >> 2) * 256 + ((lane & 3) ^ ((tok >> 1) & 2)) * 8 + 8192 + 3 * 7680 : lane * 8 + 1024)};
}
__device__ __forceinline__ float2 h2f(uint32_t w) {
  float2 f; asm("{\n.reg .f16 l, h;\nmov.b32 {l, h}, %2;\ncvt.f32.f16 %0, l;\ncvt.f32.f16 %1, h;\n}" : "=f"(f.x), "=f"(f.y) : "r"(w)); return f; }
__device__ __forceinline__ float rsq(float x) { float y; asm("rsqrt.approx.ftz.f32 %0, %1;" : "=f"(y) : "f"(x)); return y; }
__device__ __forceinline__ void red_if(uint32_t v, const void* a) {
  asm volatile("{\n.reg .pred q;\nsetp.ne.u32 q, %1, 0;\n@q red.relaxed.gpu.global.add.u32 [%0], %1;\n}" :: "l"(a), "r"(v) : "memory"); }
__device__ __forceinline__ uint32_t dep0(uint32_t w, int lane) { uint32_t z; asm volatile("shr.b32 %0, %1, %2;" : "=r"(z) : "r"(w), "r"(lane + 32)); return z; }
__device__ __forceinline__ int lane_of(uint32_t w) {
  int lane; asm volatile("{\n.reg .u32 t;\nmov.u32 t, %%laneid;\nshr.u32 %0, %1, 20;\nadd.u32 %0, %0, t;\n}" : "=r"(lane) : "r"(w)); return lane; }
#define BUF (RD * TILE_B)
__device__ __forceinline__ int await(uint32_t v, const uint32_t* p, uint32_t target, bool lazy) {
  int n = 0;
  while (!__all_sync(~0u, v >= target)) {
    if (lazy) __nanosleep(200);
    if (++n > SPIN_LIMIT) FAIL();
    v = ld_relaxed(p);
  }
  asm volatile("fence.acquire.gpu;" ::: "memory");
  return lane_of(v);
}
template <int W> __device__ __forceinline__ void sum2(float& s, float& q, int lane) {
  const bool up = lane & (W / 2);
  float e = (up ? q : s) + __shfl_xor_sync(~0u, up ? s : q, W / 2);
#pragma unroll
  for (int o = W / 4; o; o >>= 1) e += __shfl_xor_sync(~0u, e, o);
  const float f = __shfl_xor_sync(~0u, e, W / 2);
  s = up ? f : e; q = up ? e : f;
}
template <int TYPE>
__device__ __forceinline__ void rrow(int r, int row, int tok, int lane, const uint32_t* go, int role, const __nv_bfloat16* x, __nv_bfloat16* out) {
  const int half = TYPE == 3 ? 0 : row >> 5;
  float v[20];
  float2 st = make_float2(1.f, 0.f);
  {
    uint32_t a[10], c[10], u[10], sh = 16;
    if (TYPE == 2) row_img(r + RD - ((row & 31) < 2), (row & 32) + ((row - 2) & 31), lane).ld(u, 4 * BUF);
    else row_ext(x, half, 1, tok, lane).ld(u, 0);
    if (TYPE == 2 || (TYPE == 0 && half))
      asm volatile("ld.relaxed.gpu.global.v2.f32 {%0,%1}, [%2];" : "=f"(st.x), "=f"(st.y) : "l"(g_stat + tok) : "memory");
    RowPtr ap = row_img(r, row, lane);
    const uint32_t g0 = TYPE != 3 ? ld_relaxed(go) : 0;
    if (TYPE == 2) {
      ap.ld(c, 2 * BUF);
      uint32_t z = dep0(c[9], lane);
#pragma unroll
      for (int i = 0; i < 10; i++) {
        const float2 g = h2f(u[i] | z), h = h2f(c[i] | z);
        v[2 * i] = fmaf(h.x, 0.5f, g.x * st.x); v[2 * i + 1] = fmaf(h.y, 0.5f, g.y * st.x);
        if (i & 1) z = dep0(__float_as_uint(v[2 * i]) | __float_as_uint(v[2 * i + 1]), lane);
      }
    }
    if (TYPE != 3) {
      asm volatile("" : "+l"(ap.p), "+l"(ap.t));
      ap.q = ap.p + 32768;
      lane = await(g0, go, NOP * NW12 * NW34, false); BTS2(r, 8 + 2 * TYPE); RTS(0);
      ap.ld(a, TYPE ? 3 * BUF : 0);
    }
    if (TYPE == 0) {
      ap.ld(c, BUF);
      const uint32_t one = 0x3f803f80u | dep0(c[9], lane);
#pragma unroll
      for (int i = 0; i < 10; i++) asm volatile("fma.rn.bf16x2 %0, %0, %1, %2;" : "+r"(a[i]) : "r"(one), "r"(c[i]));
      sh |= dep0(a[9], lane);
    }
    const float k = TYPE == 2 ? __uint_as_float(0x3f000000u | dep0(a[9], lane)) : 0.f;
#pragma unroll
    for (int i = 0; i < 10; i++) {
      if (TYPE == 2) { const float2 h = h2f(a[i]); v[2 * i] = fmaf(h.x, k, v[2 * i]); v[2 * i + 1] = fmaf(h.y, k, v[2 * i + 1]); continue; }
      float p = __uint_as_float(u[i] << sh), q = __uint_as_float(u[i] & (0xffffu << sh));
      if (TYPE == 0) { p = fmaf(p, st.x, bf_lo(a[i])); q = fmaf(q, st.x, bf_hi(a[i])); }
      v[2 * i] = p; v[2 * i + 1] = q;
    }
  }
  RTSD(1, v[19]);
  float s = 0.f, q = 0.f;
#pragma unroll
  for (int i = 0; i < 5; i++) {
    s += (v[4 * i] + v[4 * i + 1]) + (v[4 * i + 2] + v[4 * i + 3]);
    q += fmaf(v[4 * i], v[4 * i], v[4 * i + 1] * v[4 * i + 1]) + fmaf(v[4 * i + 2], v[4 * i + 2], v[4 * i + 3] * v[4 * i + 3]);
  }
  if (!(TYPE == 2 && half)) sum2<32>(s, q, lane);
  const float mean = s * (1.f / DM), var = fmaxf(q * (1.f / DM) - mean * mean, 0.f), rs = rsq(var + 1e-5f);
  const float k = TYPE == 0 ? 2.f * rs : half ? 1.f : rs, mr = TYPE && half ? st.y : -mean * k;
  RTSD(2, rs);
  uint32_t w[10];
#pragma unroll
  for (int i = 0; i < 10; i++) w[i] = pk<TYPE == 0>(fmaf(v[2 * i], k, mr), fmaf(v[2 * i + 1], k, mr));
  if (TYPE) row_ext(out, !half, TYPE == 2, tok, lane).st(w, 0);
  else {
    row_img(r, row, lane).st(w, 4 * BUF);
    row_img(r + ((row & 31) >= 30), (row & 32) + ((row + 2) & 31), lane).st(w, 2 * BUF);
    if (lane == 1) g_st2[0][r % RD][row] = (__float_as_uint(0.5f * rsq(fmaf(var * rs, rs, 1e-5f))) & ~127u) | (r + 1);
  }
  if (TYPE != 3 && lane == 0) g_stat[tok] = make_float2((var + 1e-5f) * rs * (TYPE ? 1.f : 0.5f), mean + st.y);
}
__device__ __forceinline__ void r2rows(int r, int row, int lane) {
  const int n = row + (lane >> 4);
  const unsigned char* ap = &g_acc[2][r % RD][0] + (uint32_t)(n * 128 + ((lane >> 3) & 1) * 8192 + (((lane ^ n) & 7) << 4));
  uint32_t a[20];
#pragma unroll
  for (int i = 0; i < 5; i++) ldg4(a + 4 * i, ap + i * 16384);
  const uint32_t z = dep0(a[19], lane);
  float s = 0.f, q = 0.f, q2 = 0.f;
#pragma unroll
  for (int i = 0; i < 20; i++) { const float2 h = h2f(a[i] | z); s += h.x + h.y; q = fmaf(h.x, h.x, q); q2 = fmaf(h.y, h.y, q2); }
  q += q2;
  sum2<16>(s, q, lane);
  const float mean = s * (0.5f / DM), rs = rsq(fmaxf(q * (0.25f / DM) - mean * mean, 0.f) + 1e-5f);
  if ((lane & 15) == 0) asm volatile("st.relaxed.gpu.global.u32 [%0], %1;" :: "l"(&g_st2[1][r % RD][n]), "r"((__float_as_uint(0.5f * rs) & ~127u) | (r + 1)) : "memory");
}
__device__ __forceinline__ void r3rows(int r, int row, int tok, int lane, __nv_bfloat16* out) {
  const int n = row + (lane >> 4), m = 32 + ((n - 2) & 31);
  const unsigned char* ap = &g_acc[0][r % RD][0] + (uint32_t)(n * 128 + ((lane >> 3) & 1) * 8192 + (((lane ^ n) & 7) << 4));
  const unsigned char* zp = &g_acc[4][(r + RD - (row == 32)) % RD][0] + (uint32_t)(m * 128 + ((lane >> 3) & 1) * 8192 + (((lane ^ m) & 7) << 4));
  unsigned char* op = reinterpret_cast<unsigned char*>(out) + (uint32_t)((tok + (lane >> 4)) * 1280 + (lane & 15) * 16);
  float2 st;
  asm volatile("ld.relaxed.gpu.global.v2.f32 {%0,%1}, [%2];" : "=f"(st.x), "=f"(st.y) : "l"(g_stat + tok + (lane >> 4)) : "memory");
#pragma unroll 1
  for (int i0 = 0; i0 < 3; i0++) {
    uint32_t a[8], c[8], u[8];
#pragma unroll
    for (int i = 0; i < 2; i++) { ldg4(a + 4 * i, ap + 3 * BUF + i * 16384); ldg4(c + 4 * i, ap + 2 * BUF + i * 16384); ldg4(u + 4 * i, zp + i * 16384); }
    uint32_t z = dep0(u[7], lane);
#pragma unroll
    for (int i = 0; i < 8; i++) {
      const float2 h = h2f(a[i] | z), e = h2f(c[i] | z), g = h2f(u[i] | z);
      a[i] = pack2(fmaf(h.x + e.x, 0.5f, fmaf(g.x, st.x, st.y)), fmaf(h.y + e.y, 0.5f, fmaf(g.y, st.x, st.y)));
      if (i & 1) z = dep0(a[i], lane);
    }
    if (i0 < 2) stg4(op, a);
    stg4(op + 256, a + 4);
    ap += 32768 >> i0; zp += 32768 >> i0; op += 512 >> i0;
  }
}
template <int TYPE>
__device__ __forceinline__ void rloop(int row, int cp, int role, const __nv_bfloat16* x, __nv_bfloat16* out) {
  constexpr int ST = TYPE == 4 ? 2 : TYPE;
  const int r0 = row & 32 ? LAG : 0;
  uint32_t v = 0;
  static_assert(NSEG + RD - 1 >= NSTEP, "no signals");
#pragma unroll 1
  for (int r = r0; r < (TYPE == 2 ? NR : TYPE == 4 ? NSEG + 1 : r0 + NSEG + (TYPE > 0)); r++) {
    if (TYPE == 2 && r == NSEG + 1) row += 32;
    const int tok = (r - (row & 32 ? LAG : 0)) * 32 + (row & 31) - (TYPE ? 2 : 0);
    const bool valid = TYPE == 0 || (unsigned)tok < S_LEN;
    const uint32_t* go = &g_f[F_R1 + 4 * ST + cp][r];
    const uint32_t* first = TYPE == 2 ? &g_f[F_R2 + cp][r] : TYPE ? go : (const uint32_t*)&g_xready[NSEG + r - r0][0];
    if constexpr (TYPE == 1 || TYPE == 4) {
      const int lane = await(v, go, NOP * NW12 * NW34, false);
      BTS2(r, 8 + 2 * ST); RTS(0);
      if (TYPE == 1) { r2rows(r, row, lane); BTS2(r, 11); continue; }
      if (valid) r3rows(r, row, tok, lane, out);
    } else {
      if (TYPE || row >= 32) await(v, first, TYPE ? NOP * NW12 * NW34 : 32, true);
      if (valid) rrow<TYPE>(r, row, tok, lane_of(r), go, role, x, out);
    }
    if (TYPE > 1 && row >= 32 && r + RD - 2 >= NSTEP) { v = 0; BTS2(r, 13); continue; }
    const int lane = lane_of(r);
    const void* f = lane ? (const void*)&g_xready[NSEG + (tok >> 5)][0] : (const void*)&g_f[TYPE ? F_DONE : F_Z][r];
    asm volatile("" : "+l"(f));
    __syncwarp();
    RTS(3);
    v = ld_relaxed(first + (TYPE ? 1 : 8));
    asm volatile("fence.release.gpu;" ::: "memory");
    RTS(4);
    red_if(lane == 0 || (TYPE == 2 && lane == 1 && valid) ? (TYPE & 5 ? 2 : 1) : 0, f);
    RTS(5);
    RTS_OUT();
    BTS2(r, 9 + 2 * ST);
  }
}

#define RCV 1
#define SINGLE_OP 3
#define SINGLE_W 0
#define W_DELAY 0
#define BULK_ADD(T, dst, src, len) asm volatile("{\n.reg .pred e;\nelect.sync _|e, 0xffffffff;\n@e cp.reduce.async.bulk.global.shared::cta.bulk_group.add.noftz." T " [%0], [%1], %2;\n}" \
                                               :: "l"(dst), "r"(src), "r"(len) : "memory")
#define COMMIT() asm volatile("cp.async.bulk.commit_group;" ::: "memory")
#define DRAINED(n) do { asm volatile("cp.async.bulk.wait_group.read " #n ";" ::: "memory"); __syncwarp(); } while (0)
#define WRITTEN() do { asm volatile("cp.async.bulk.wait_group 0;\nfence.proxy.async.global;" ::: "memory"); __syncwarp(); } while (0)
__device__ __forceinline__ void wait_flags(const uint32_t* p, uint32_t target) {
  int n = 0;
  while (!__all_sync(~0u, ld_relaxed(p) >= target)) { if (++n > SPIN_LIMIT) FAIL(); }
  asm volatile("fence.acquire.gpu;" ::: "memory");
  asm volatile("fence.proxy.async.global;" ::: "memory");
}
__global__ void __launch_bounds__(512, 1) bworker_kernel(const __grid_constant__ BParams P) {
  extern __shared__ __align__(1024) unsigned char smem_raw[];
  const uint32_t sb = SMEM0, bar = sb + BO_BAR;
  const int wg = __shfl_sync(~0u, threadIdx.x >> 7, 0), warp = __shfl_sync(~0u, (threadIdx.x >> 5) & 3, 0);
  if (threadIdx.x == 0) {
    if (smem_u32(smem_raw) != SMEM0) FAIL();
    uint32_t smid; asm volatile("mov.u32 %0, %%smid;" : "=r"(smid));
    const uint32_t nb = ld_relaxed(&g_tpc[(smid >> 1) & 127]);
    const bool single = nb > 1, far = nb == 0 && (smid < 64 || smid >= 124);
    int kind = far || (single && atomicAdd(&g_f[F_MISC][35], 1u) < SINGLE_OP) ? 0 : single ? 1 + SINGLE_W : 1;
    int rc = (RCV ? smid >= 128 : single) || (smid >> 1) == 16 || (smid >> 1) == 63 ? 1 : far || single ? 2 : 0;
    uint32_t i = atomicAdd(&g_f[F_MISC][32 + kind], 1u), o = atomicAdd(&g_f[F_MISC][36 + rc], 1u);
    while (i >= (kind == 0 ? NOP : kind == 1 ? NW12 : NW34)) { kind = (kind + 1) % 3; i = atomicAdd(&g_f[F_MISC][32 + kind], 1u); }
    while (o >= (rc == 0 ? 16 : rc == 1 ? 8 : 12)) { rc = (rc + 1) % 3; o = atomicAdd(&g_f[F_MISC][36 + rc], 1u); }
    if (RCV && rc == 2) o = single ? 11 - atomicAdd(&g_f[F_MISC][40], 1u) : atomicAdd(&g_f[F_MISC][41], 1u);
    sts64(sb + BO_BOX, i + (kind == 0 ? 0 : kind == 1 ? NOP : NOP + NW12), o + (rc ? 8 + 8 * rc : 0));
    for (int k = 0; k < BB_NUM; k++) mbar_init(bar + 8 * k, k >= BB_USED ? 4 : k >= BB_EMPTY ? 8 : k >= BB_ZFREE && kind ? 2 : 1);
    asm volatile("fence.mbarrier_init.release.cluster;" ::: "memory");
  }
  if (threadIdx.x < 128) sts128(sb + BO_CARRY + threadIdx.x * 16, 0u, 0u, 0u, 0u);
  auto ln0 = [&](int t) {
    const int lane = lane_of(t);
    if (lane < 20 && t + 128 < S_LEN) asm volatile("prefetch.global.L2 [%0];" :: "l"(P.x + (t + (t < 4 * NBC ? 4 * NBC : 128)) * DM + (lane >> 1) * 64));
    rrow<3>(0, 0, t, lane, nullptr, 0, P.x, nullptr);
    __syncwarp();
    asm volatile("fence.release.gpu;" ::: "memory");
    red_if(lane == 0, &g_xready[t >> 5][0]);
  };
  if (wg == 2) ln0(blockIdx.x * 4 + warp);
  fence_async();
  __syncthreads();
  const int role = uni(lds32(sb + BO_BOX));
  if (threadIdx.x < 32) BTS(94, 1);
  const bool op = role < NOP, w12 = role < NOP + NW12;
  const int j = op ? role : w12 ? role - NOP : role - NOP - NW12;
  const int rot = op ? (j ? 2 * ((j + 1) % 5) : 0) : 2 * (j % 5);
  if (wg == 3) {
    asm volatile("setmaxnreg.dec.sync.aligned.u32 24;");
    LANE_INIT();
    if (warp < 2) {
      auto announce = [&](int r) {
        const uint32_t* f = &g_f[(op ? F_R1 : w12 ? F_R2 : F_R3) + (lane & 3)][r];
        asm volatile("" : "+l"(f));
        if (warp == 0) { mbar_arrive_if(lane == 0, bar + 8 * BB_DONE); return; }
        mbar_waitw(bar + 8 * BB_DONE, r & 1);
        PTS(60);
        asm volatile("fence.release.gpu;" ::: "memory");
        red_if(lane >= 4 ? 0 : op ? NW12 * NW34 : w12 ? NOP * NW34 : NOP * NW12, f);
        PTS(61);
        BTS(r, 4);
      };
      if (op) {
        int mt = rot + warp;
        bar_arrive(NB_FREE + warp, 160);
#pragma unroll 1
        for (int r = 0; r < NSTEP; r++) {
          const uint32_t len = fmask(r) == 3 ? 8192 : 4096;
          unsigned char* acc = &g_acc[j & 1][r % RD][fmask(r) == 2 ? 4096 : 0];
#pragma unroll 1
          for (int p = 0; p < 5; p++) {
            bar_sync(NB_STAGED + warp, 160);
            PTS(50 + 2 * p + warp);
            fence_async();
            BULK_ADD("bf16", acc + mt * 8192, sb + BO_STG + warp * 8192, len);
            COMMIT();
            PTS(64 + 50 + 2 * p + warp);
            mt = mt >= 8 ? mt - 8 : mt + 2;
            DRAINED(0);
            bar_arrive(NB_FREE + warp, 160);
          }
          WRITTEN();
          announce(r);
        }
      } else {
#pragma unroll 1
        for (int r = 0; r < NR; r++) {
          const uint32_t len = bmask(r) == 3 ? 8192 : 4096;
          unsigned char* acc = &g_acc[w12 ? 2 : 3][r % RD][bmask(r) == 2 ? 4096 : 0];
          int mt = rot + warp;
          const bool pairs = len != 8192;
#pragma unroll 1
          for (int p = pairs ? 2 : 0; p < 5; p++) {
            const uint32_t src = sb + (p == 4 ? BO_H : BO_RING_MLP + (2 - (p & 1)) * 16384) + warp * 8192;
            bar_sync(NB_STAGED + (p == 4 ? 4 : 2 * (p & 1)) + warp, 160);
            PTS(50 + 2 * p + warp);
            fence_async();
            BULK_ADD("f16", acc + mt * 8192, src, len);
            mt = mt >= 8 ? mt - 8 : mt + 2;
            if (pairs && p < 4) { BULK_ADD("f16", acc + mt * 8192, src + 4096, len); mt = mt >= 8 ? mt - 8 : mt + 2; }
            COMMIT();
            PTS(64 + 50 + 2 * p + warp);
            if (p == 4 && !pairs) break;
            DRAINED(1);
            mbar_arrive_if(lane == 0 && p, bar + 8 * (p < 3 ? BB_SFREE + 2 * (p - 1) + warp : BB_ZFREE + (p >> 1)));
            mbar_arrive_if(lane == 0 && pairs && p == 2, bar + 8 * (BB_SFREE + warp));
            if (p == 3 && !pairs) { DRAINED(0); mbar_arrive_if(lane == 0, bar + 8 * (BB_ZFREE + 2)); }
          }
          WRITTEN();
          mbar_arrive_if(lane == 0, bar + 8 * (BB_SFREE + 4 + warp));
          announce(r);
        }
      }
    } else {
      if (op && warp == 2) {
        unsigned char* wt = g_wt + j * (10 * OP_SLOT);
#pragma unroll 1
        for (int m0 = 0; m0 < 10; m0 += 3) {
          const int nu = m0 < 9 ? 9 : 3;
          mbar_expect_if(lane == 0, bar + 8 * BB_TMP, nu * 4096);
#pragma unroll 1
          for (int k = 0; k < nu; k++) tma2d_e(sb + BO_RING_OP + k * 4096, &P.wmap[0], (m0 + k / 3) * 64, 320 * j + 224 + 32 * (k % 3), bar + 8 * BB_TMP);
          mbar_waitw(bar + 8 * BB_TMP, m0 & 1);
          bulk_s2g_e(wt + m0 * OP_SLOT, sb + BO_RING_OP, nu * 4096);
          COMMIT();
          WRITTEN();
        }
        asm volatile("fence.acq_rel.gpu;" ::: "memory");
        int sl = 0, ph = 1, mt = rot;
#pragma unroll 1
        for (int r = -1; r < NSTEP; r++) {
#pragma unroll 1
          for (int n = r < 0 ? 7 : 0; n < (r + 1 < NSTEP ? 10 : 7); n++) {
            mbar_waitw(bar + 8 * (BB_USED + sl), ph);
            mbar_expect_if(lane == 0, bar + 8 * (BB_FULL + sl), OP_SLOT);
            bulk_g2s_e(sb + BO_RING_OP + sl * OP_SLOT, wt + mt * OP_SLOT, OP_SLOT, bar + 8 * (BB_FULL + sl));
            if (++sl == 3) { sl = 0; ph ^= 1; }
            mt = mt == 9 ? 0 : mt + 1;
          }
        }
      } else if (op) {
        mbar_waitw(bar + 8 * BB_START, 0);
#pragma unroll 1
        for (int r = 0; r < NSTEP; r++) {
          const int rb = r - RD + 2;
          const uint32_t len = fmask(r) == 3 ? 8192 : 4096;
          const unsigned char* src = g_o + (uint32_t)(r % RO * (96 * 8192) + 5 * j * len);
          wait_flags(lane < 2 ? &g_f[F_O + (lane ? NOP : j)][r] : rb >= 0 ? &g_f[F_DONE][rb] : &g_f[F_MISC][0],
                     lane < 2 ? (lane ? 1 : 5) : rb >= 0 ? rtarget(bmask(rb)) : NBC * 8);
          PTS1(35);
          if (r) bar_sync(NB_EARLY, 288);
          if (r == LAG) bar_sync(NB_LAST, 288);
          mbar_expect_if(lane < 3, bar + 8 * (BB_OFULL + lane), 2 * len);
          bulk_g2s_e(sb + BO_O, src, 2 * len, bar + 8 * BB_OFULL);
          PTS(62); PTS1(38);
          if (r && r != LAG) bar_sync(NB_LAST, 288);
          bulk_g2s_e(sb + BO_O + 2 * len, src + 2 * len, 2 * len, bar + 8 * (BB_OFULL + 1));
          bulk_g2s_e(sb + BO_O + 4 * len, src + 4 * len, len, bar + 8 * (BB_OFULL + 2));
          bulk_g2s_e(sb + BO_O + 5 * len, src + (95 - 5 * j) * len, len, bar + 8 * (BB_OFULL + 2));
          PTS1(64 + 35);
          BTS(r, 0);
        }
      } else if (warp == 2) {
#pragma unroll 1
        for (int r = 0; r < NR; r++) {
          const int mk = w12 ? fmask(r) : bmask(r);
          if (mk) {
            const unsigned char* src = &g_acc[w12 ? 4 : 2][r % RD][mk == 2 ? 4096 : 0];
            wait_flags(w12 ? &g_f[F_Z][r] : lane && r >= 2 ? &g_f[F_R3 + (j & 3)][r - 2] : &g_f[F_R2 + (j & 3)][r], w12 ? rtarget(mk) : NOP * NW12 * NW34);
#pragma unroll 1
            for (int z = 0; z < 5; z++) {
              const int k = mk == 3 ? z : z >> 1;
              const uint32_t fb = bar + 8 * (BB_FULL + z), dst = sb + BO_RING_MLP + 2 * k % 3 * 16384 + (mk == 3 ? 0 : (z & 1) * 4096);
              if (mk == 3 || !(z & 1)) mbar_waitw(bar + 8 * (k < 3 ? BB_ZFREE + k : BB_EMPTY + k - 3), (r + (k < 3)) & 1);
              if (z == 0) PTS(62);
              mbar_expect_if(lane == 0, fb, mk == 3 ? 16384 : 8192);
              bulk_g2s_e(dst, src + z * 16384, mk == 3 ? 16384 : 4096, fb);
              if (mk != 3) bulk_g2s_e(dst + 8192, src + z * 16384 + 8192, 4096, fb);
              if (z == 0) BTS(r, 0);
            }
          }
          if (!w12) {
#pragma unroll 1
            for (int c = j; c < 120; c += NW34) bulk_s2g_e(&g_acc[c < 80 ? c / 40 : 3][(r + (c < 80 ? 0 : 2)) % RD][c % 40 * 2048], sb + BO_CARRY, 2048);
            COMMIT();
            WRITTEN();
          }
          mbar_waitw(bar + 8 * BB_DONE, (r + 1) & 1);
          mbar_arrive_if(lane == 0, bar + 8 * BB_DONE);
        }
      } else {
#pragma unroll 1
        for (int r = 0; r < (w12 ? NSTEP : NR); r++) {
          const bool idle = !((w12 ? fmask(r) : bmask(r)) >> (lane >> 4) & 1);
          uint32_t t0, t1;
          int n = 0;
          mbar_waitw(bar + 8 * BB_FULL, r & 1);
          do {
            asm volatile("ld.relaxed.gpu.global.v2.u32 {%0,%1}, [%2];" : "=r"(t0), "=r"(t1) : "l"(&g_st2[!w12][r % RD][2 * lane]) : "memory");
            if (++n > SPIN_LIMIT) FAIL();
          } while (!__all_sync(~0u, idle || (((t0 ^ (r + 1)) | (t1 ^ (r + 1))) & 127) == 0));
          sts64(sb + BO_STAT + (lane >> 4) * 128 + (lane & 3) * 32 + ((lane >> 2) & 3) * 8, t0, t1);
          __syncwarp();
          mbar_arrive_if(lane == 0, bar + 8 * BB_STAT);
          PTS(63);
        }
      }
    }
    bar_arrive(NB_END, 512);
  } else if (wg == 2) {
    asm volatile("setmaxnreg.dec.sync.aligned.u32 40;");
    const int ord = uni(lds32(sb + BO_BOX + 4));
    const int gw = ord < 16 ? warp * 16 + ord : ord < 24 ? 48 + warp * 8 + ord : !RCV ? 72 + warp * 12 + ord : ord >= 32 ? 97 + 2 * (warp * 4 + ord - 32) : warp < 2 ? 48 + 2 * (warp * 8 + ord) : 88 + warp * 8 + ord, row = gw < 64 ? gw : gw < 96 ? gw - 64 : gw < 128 ? 2 * gw - 192 : 2 * gw - 224;
    if (row >= 32) {
#pragma unroll 1
      for (int t = 4 * NBC + (gw < 64 ? gw - 32 : gw - 80); t < S_LEN; t += 64) ln0(t);
    }
    if (gw < 64) rloop<0>(row, gw & 3, role, P.x, P.out);
    else if (gw < 96) rloop<2>(row, gw & 3, role, P.x, P.out);
    else if (gw < 128) rloop<1>(row, gw & 3, role, P.x, P.out);
    else rloop<4>(row, gw & 3, role, P.x, P.out);
    asm volatile("griddepcontrol.wait;" ::: "memory");
    const int t = threadIdx.x & 127;
    for (int i = (blockIdx.x * 128 + t) * 4; i < 4 * NCL * 2560; i += NBC * 512)
      *reinterpret_cast<uint4*>(&g_part[0][0][0][0] + i) = make_uint4(0u, 0u, 0u, 0u);
    bar_sync(NB_END, 512);
    if (t == 0) {
      uint32_t n;
      asm volatile("atom.acq_rel.gpu.global.add.u32 %0, [%1], 1;" : "=r"(n) : "l"(&g_f[F_MISC][64]) : "memory");
      sts32(sb + BO_BOX, n);
    }
    bar_sync(NB_END2, 128);
    if (lds32(sb + BO_BOX) == NBC - 1) {
      for (int i = t; i < F_NUM * 24; i += 128) reinterpret_cast<uint4*>(&g_f[0][0])[i] = make_uint4(0u, 0u, 0u, 0u);
      g_xready[t][0] = 0; g_tpc[t] = 0;
    }
  } else {
    asm volatile("setmaxnreg.inc.sync.aligned.u32 224;");
    LANE_INIT();
    for (int i = blockIdx.x * 256 + threadIdx.x; i < 2 * (RD + 1) * TILE_B / 16; i += NBC * 256)
      reinterpret_cast<uint4*>(&g_acc[i < 2 * RD * TILE_B / 16 ? 0 : 1][0][0])[i] = make_uint4(0u, 0u, 0u, 0u);
    warp_signal(&g_f[F_MISC][0], lane);
    const int mt0 = (rot + wg) % 10;
    auto boxes = [&](int ss) {
      const int nb = op && ss ? 3 : 4;
      const uint32_t base = sb + (ss ? BO_RES + wg * OP_RES : wg * 83968);
      mbar_expect_if(warp == 0 && lane == 0, bar + 8 * (BB_W + wg), nb * 20480 + (op ? 2048 : 0));
      bar_sync(NB_H, 256);
      if (warp < nb) {
#pragma unroll 1
        for (int i = warp; i < 5 * nb; i += nb) {
          const int p = op ? i / nb : (i - 10) >> 1, mt = (mt0 + 2 * p) % 10;
          const bool first = !op && i < 10;
          tma2d_e(op || !ss ? base + i * 4096 : sb + (first ? BO_W1 : -81920) + (2 * i + wg) * 4096, &P.wmap[op ? 0 : (w12 ? 1 : 3) + !first], first ? 128 * j + 64 * wg : mt * 64,
                  op ? 320 * j + 64 * warp + 32 * ss : first ? 64 * i + 32 * ss : 128 * j + 32 * (i & 1) + 64 * ss, bar + 8 * (BB_W + wg));
        }
      }
      if (op && warp == 3) tma2d_e(base + nb * 20480, &P.wo16, (mt0 + 2 * ss) % 10 * 64, 95 * 64 + (j + 1) / 5 * 16, bar + 8 * (BB_W + wg));
      mbar_waitw(bar + 8 * (BB_W + wg), ss);
    };
    if (W_DELAY && !op) __nanosleep(W_DELAY);
    uint32_t W[164];
    boxes(0);
    load_w<41>(W, sb + wg * 83968, warp, lane);
    fence_async();
    boxes(1);
    if (!op) {
      float cs[2] = {0.f, 0.f};
      const uint32_t a0 = sb + BO_W1 + wg * 4096 + ((lane >> 4) * 8 + (lane & 7)) * 128 + (((warp * 2 + ((lane >> 3) & 1)) ^ (lane & 7)) << 4);
#pragma unroll
      for (int i = 0; i < 80; i++) cs[i & 1] += bf_lo(W[i]) + bf_hi(W[i]);
#pragma unroll 1
      for (int i = 0; i < 40; i++) {
        uint32_t t[4];
        const uint32_t ad = a0 + (i % 20 >> 1) * 8192 + (i & 1) * 2048;
        ldsm4t(t[0], t[1], t[2], t[3], ad);
#pragma unroll
        for (int k = 0; k < 4; k++) {
          if (i < 20) cs[k & 1] += bf_lo(t[k]) + bf_hi(t[k]);
          t[k] = pack2h(bf_lo(t[k]) - cs[k & 1], bf_hi(t[k]) - cs[k & 1]);
        }
        if (i >= 20) stsm4t(ad, t[0], t[1], t[2], t[3]);
        if (i == 19) {
#pragma unroll
          for (int k = 0; k < 2; k++) { cs[k] += __shfl_xor_sync(~0u, cs[k], 1); cs[k] += __shfl_xor_sync(~0u, cs[k], 2); cs[k] *= 1.f / DM; }
        }
      }
      const uint32_t z = dep0(__float_as_uint(cs[0]), lane);
#pragma unroll
      for (int i = 0; i < 80; i++) W[i] = pack2h(bf_lo(W[i] | z) - cs[i & 1], bf_hi(W[i] | z) - cs[i & 1]);
      fence_async();
      bar_sync(NB_H, 256);
    }
    if (warp == 0) BTS(94, 6 + wg);
    const Dsc blo = {P.desc, 1}, alo = blo + wg * (op ? OP_RES / 16 : 256);
    if (op) {
      Ring rg = {(uint32_t)wg, 0};
      mbar_arrive_if(lane == 0, bar + 8 * BB_START);
      if (wg) bar_arrive(NB_PP, 256);
      const Dsc xlo = blo + (j + 1) / 5 * 2;
#pragma unroll 1
      for (int r = 0; r < NSTEP; r++) {
        asm volatile("" : "+r"(lane));
        if (fmask(r) == 3) op_round<64>(W, bar, alo, blo, xlo, j == 0, rg, wg, warp, lane, r);
        else op_round<32>(W, bar, alo, blo, xlo, j == 0, rg, wg, warp, lane, r);
        if (warp == 0) BTS(r, 2 + wg);
      }
    } else {
      const int q4 = (128 * j + 64 * wg + 16 * warp) / 160, off = w12 ? (0x0413 >> (4 * q4)) & 7 : 0;
#pragma unroll 1
      for (int r = 0; r < NR; r++) {
        asm volatile("" : "+r"(lane));
        const int bm = bmask(r), fm = w12 ? fmask(r) : bm;
        if (fm == 3) phase1<64>(W, sb, alo, blo, 0, wg, warp, lane, off, r);
        else if (fm) phase1<32>(W, sb, alo, blo, fm >> 1, wg, warp, lane, off, r);
        else { mbar_waitu(bar + 8 * (BB_SFREE + 4 + wg), (r + 1) & 1); carry_in(sb, wg, warp, lane); }
        CTS(33);
        fence_async();
        bar_sync(NB_H, 256);
        mbar_arrive_if(wg == 1 && warp == 0 && lane < 2, bar + 8 * BB_ZFREE);
        if (wg + warp == 0) BTS(r, 1);
        if (bm == 3) phase2<64>(W, bar, alo, blo, wg, warp, lane, r);
        else phase2<32>(W, bar, alo, blo + (bm >> 1) * 256, wg, warp, lane, r);
        if (warp == 0) BTS(r, 2 + wg);
      }
    }
    CTS_OUT();
    bar_arrive(NB_END, 512);
  }
}

typedef CUresult (*EncodeFn)(CUtensorMap*, CUtensorMapDataType, cuuint32_t, void*, const cuuint64_t*, const cuuint64_t*, const cuuint32_t*,
                             const cuuint32_t*, CUtensorMapInterleave, CUtensorMapSwizzle, CUtensorMapL2promotion, CUtensorMapFloatOOBfill);
static void make_map(EncodeFn fn, CUtensorMap* tm, const void* ptr, uint64_t cols, uint64_t rows, uint32_t bc, uint32_t br) {
  cuuint64_t dims[2] = {cols, rows}; cuuint64_t strides[1] = {cols * 2}; cuuint32_t box[2] = {bc, br}; cuuint32_t es[2] = {1, 1};
  fn(tm, CU_TENSOR_MAP_DATA_TYPE_BFLOAT16, 2, const_cast<void*>(ptr), dims, strides, box, es, CU_TENSOR_MAP_INTERLEAVE_NONE,
     CU_TENSOR_MAP_SWIZZLE_128B, CU_TENSOR_MAP_L2_PROMOTION_L2_256B, CU_TENSOR_MAP_FLOAT_OOB_FILL_NONE);
}
#define dbg_a_only 0
extern "C" void kernel_launch(void* const* d_in, const int* in_sizes, int n_in, void* d_out, int out_size) {
  void* fnp = nullptr; cudaDriverEntryPointQueryResult qr;
  cudaGetDriverEntryPoint("cuTensorMapEncodeTiled", &fnp, cudaEnableDefault, &qr);
  EncodeFn fn = (EncodeFn)fnp;
  cudaStream_t st = cudaStreamPerThread;
  cudaFuncSetAttribute(bworker_kernel, cudaFuncAttributeMaxDynamicSharedMemorySize, B_SMEM);
  {
    AMaps M;
    for (int i = 0; i < 3; i++) make_map(fn, &M.w16[i], d_in[2 + i], HD, DM, 64, 16);
    M.wv = (const __nv_bfloat16*)d_in[4];
    make_map(fn, &M.wo32, d_in[5], DM, HD, 64, 32);
    const uint32_t hi[5] = {dhi(TILE_SBO, 3), dhi(1024, 1), dhi(1024, 0), dhi(PL_SZ, 0), dhi(896, 0)};
    for (int i = 0; i < 5; i++) M.d[i] = (uint64_t)hi[i] << 32;
    cudaFuncSetAttribute(acore_kernel, cudaFuncAttributeMaxDynamicSharedMemorySize, A_SMEM);
    cudaFuncSetAttribute(acore_kernel, cudaFuncAttributeNonPortableClusterSizeAllowed, 1);
    cudaLaunchConfig_t cfg = {};
    cfg.gridDim = dim3(CL_SIZE * NCL); cfg.blockDim = dim3(512); cfg.dynamicSmemBytes = A_SMEM; cfg.stream = st;
    cudaLaunchAttribute at[1]; at[0].id = cudaLaunchAttributeClusterDimension;
    at[0].val.clusterDim.x = CL_SIZE; at[0].val.clusterDim.y = 1; at[0].val.clusterDim.z = 1;
    cfg.attrs = at; cfg.numAttrs = 1;
    cudaLaunchKernelEx(&cfg, acore_kernel, M, (const __nv_bfloat16*)d_in[1], dbg_a_only ? 0 : 1);
  }
  if (!dbg_a_only) {
    BParams P;
    make_map(fn, &P.wmap[0], d_in[5], DM, HD, 64, 32);
    make_map(fn, &P.wo16, d_in[5], DM, HD, 64, 16);
    make_map(fn, &P.wmap[1], d_in[8], DM, DM, 64, 32);
    make_map(fn, &P.wmap[2], d_in[9], DM, DM, 64, 32);
    make_map(fn, &P.wmap[3], d_in[10], FF, DM, 64, 32);
    make_map(fn, &P.wmap[4], d_in[11], DM, FF, 64, 32);
    P.x = (const __nv_bfloat16*)d_in[0];
    P.out = (__nv_bfloat16*)d_out;
    P.desc = (uint64_t)dhi(1024, 1) << 32;
    cudaLaunchConfig_t cfg = {};
    cfg.gridDim = dim3(NBC); cfg.blockDim = dim3(512); cfg.dynamicSmemBytes = B_SMEM; cfg.stream = st;
    cudaLaunchAttribute at[1]; at[0].id = cudaLaunchAttributeProgrammaticStreamSerialization; at[0].val.programmaticStreamSerializationAllowed = 1;
    cfg.attrs = at; cfg.numAttrs = 1;
    cudaLaunchKernelEx(&cfg, bworker_kernel, P);
  }
}
```

```cpp
#include <cuda_runtime.h>
#include <cuda_bf16.h>
#include <cuda.h>
#include <stdint.h>

#define S_LEN 2048
#define DM 640
#define NH 32
#define DH 192
#define HD 6144
#define NSEG 64
#define FF 1536

__device__ __forceinline__ uint32_t smem_u32(const void* p) { return (uint32_t)__cvta_generic_to_shared(p); }
__device__ __forceinline__ uint32_t mapa(uint32_t a, uint32_t r) {
  uint32_t o; asm volatile("mapa.shared::cluster.u32 %0, %1, %2;" : "=r"(o) : "r"(a), "r"(r)); return o; }
__device__ __forceinline__ void mbar_init(uint32_t b, uint32_t c) {
  asm volatile("mbarrier.init.shared::cta.b64 [%0], %1;" :: "r"(b), "r"(c) : "memory"); }
__device__ __forceinline__ void mbar_expect(uint32_t b, uint32_t tx) {
  asm volatile("mbarrier.arrive.expect_tx.shared::cta.b64 _, [%0], %1;" :: "r"(b), "r"(tx) : "memory"); }
__device__ __forceinline__ void mbar_arrive(uint32_t b) {
  asm volatile("mbarrier.arrive.shared::cta.b64 _, [%0];" :: "r"(b) : "memory"); }
__device__ __forceinline__ void mbar_arrive_remote(uint32_t rb) {
  asm volatile("mbarrier.arrive.relaxed.cluster.shared::cluster.b64 _, [%0];" :: "r"(rb) : "memory"); }
__device__ __forceinline__ void mbar_expect_if(bool p, uint32_t b, uint32_t tx) {
  asm volatile("{\n.reg .pred q;\nsetp.ne.u32 q, %2, 0;\n@q mbarrier.arrive.expect_tx.shared::cta.b64 _, [%0], %1;\n}" :: "r"(b), "r"(tx), "r"((uint32_t)p) : "memory"); }
__device__ __forceinline__ void mbar_arrive_if(bool p, uint32_t b) {
  asm volatile("{\n.reg .pred q;\nsetp.ne.u32 q, %1, 0;\n@q mbarrier.arrive.shared::cta.b64 _, [%0];\n}" :: "r"(b), "r"((uint32_t)p) : "memory"); }
__device__ __forceinline__ void mbar_arrive_remote_if(bool p, uint32_t rb) {
  asm volatile("{\n.reg .pred q;\nsetp.ne.u32 q, %1, 0;\n@q mbarrier.arrive.relaxed.cluster.shared::cluster.b64 _, [%0];\n}" :: "r"(rb), "r"((uint32_t)p) : "memory"); }
__device__ __forceinline__ void sts32_if(bool p, uint32_t a, uint32_t v) {
  asm volatile("{\n.reg .pred q;\nsetp.ne.u32 q, %2, 0;\n@q st.shared.b32 [%0], %1;\n}" :: "r"(a), "r"(v), "r"((uint32_t)p) : "memory"); }
__device__ __forceinline__ void sts128z_if(bool p, uint32_t a) {
  asm volatile("{\n.reg .pred q;\nsetp.ne.u32 q, %1, 0;\n@q st.shared.v4.b32 [%0], {0,0,0,0};\n}" :: "r"(a), "r"((uint32_t)p) : "memory"); }
__device__ __forceinline__ bool mbar_try(uint32_t b, uint32_t ph) {
  uint32_t ok;
  asm volatile("{\n.reg .pred p;\nmbarrier.try_wait.parity.shared::cta.b64 p, [%1], %2;\nselp.u32 %0, 1, 0, p;\n}"
               : "=r"(ok) : "r"(b), "r"(ph) : "memory");
  return ok; }
__device__ __forceinline__ bool mbar_test(uint32_t b, uint32_t ph) {
  uint32_t ok;
  asm volatile("{\n.reg .pred p;\nmbarrier.test_wait.parity.shared::cta.b64 p, [%1], %2;\nselp.u32 %0, 1, 0, p;\n}"
               : "=r"(ok) : "r"(b), "r"(ph) : "memory");
  return ok; }
#define SPIN_LIMIT 4000000
#define FAIL() asm volatile("st.global.u32 [%0], 0;" :: "l"(8ull) : "memory")
#define CFENCE() asm volatile("fence.proxy.async::generic.acquire.sync_restrict::shared::cluster.cluster;" ::: "memory")
__device__ __forceinline__ void mbar_wait(uint32_t b, uint32_t ph) {
  int n = 0;
  while (!mbar_try(b, ph)) { if (++n > SPIN_LIMIT) FAIL(); } }
#define TIMEOUT_ACT "@!p st.shared.u32 [%0+1], 0;"
#define WAIT_HINT ", 20000"
#define WAIT_LIM "200000"
__device__ __forceinline__ void mbar_slow(uint32_t b, uint32_t ph) {
  asm volatile("{\n.reg .pred p, q;\n.reg .u32 n;\nmov.u32 n, 0;\n"
               "WL:\nmbarrier.try_wait.parity.shared::cta.b64 p, [%0], %1" WAIT_HINT ";\nadd.u32 n, n, 1;\nsetp.lt.and.u32 q, n, " WAIT_LIM ", !p;\n@q bra.uni WL;\n"
               TIMEOUT_ACT "\n}" :: "r"(b), "r"(ph) : "memory"); }
__device__ __forceinline__ void mbar_waitw(uint32_t b, uint32_t ph) {
  asm volatile("{\n.reg .pred p, q;\n.reg .u32 n;\nmbarrier.try_wait.parity.shared::cta.b64 p, [%0], %1;\n@p bra.uni WD;\nmov.u32 n, 0;\n"
               "WL:\nmbarrier.try_wait.parity.shared::cta.b64 p, [%0], %1" WAIT_HINT ";\nadd.u32 n, n, 1;\nsetp.lt.and.u32 q, n, " WAIT_LIM ", !p;\n@q bra.uni WL;\n"
               TIMEOUT_ACT "\nWD:\n}" :: "r"(b), "r"(ph) : "memory"); }
__device__ __forceinline__ void mbar_waitw2(uint32_t b0, uint32_t b1, uint32_t ph) {
  uint32_t ok;
  asm volatile("{\n.reg .pred p, r;\nmbarrier.try_wait.parity.shared::cta.b64 p, [%1], %3;\nmbarrier.try_wait.parity.shared::cta.b64 r, [%2], %3;\n"
               "and.pred p, p, r;\nselp.u32 %0, 1, 0, p;\n}" : "=r"(ok) : "r"(b0), "r"(b1), "r"(ph) : "memory");
  if (__builtin_expect(!__all_sync(~0u, ok), 0)) { mbar_slow(b0, ph); mbar_slow(b1, ph); }
}
__device__ __forceinline__ void mbar_waitu(uint32_t b, uint32_t ph) {
  asm volatile("{\n.reg .pred p;\nmbarrier.try_wait.parity.shared::cta.b64 p, [%0], %1;\n@p bra.uni WD;\n"
               "WL:\nmbarrier.try_wait.parity.shared::cta.b64 p, [%0], %1" WAIT_HINT ";\n@!p bra.uni WL;\nWD:\n}" :: "r"(b), "r"(ph) : "memory"); }
__device__ __forceinline__ void mbar_waitu2(uint32_t b0, uint32_t b1, uint32_t ph) {
  asm volatile("{\n.reg .pred p, r;\nWL:\nmbarrier.try_wait.parity.shared::cta.b64 p, [%0], %2;\nmbarrier.try_wait.parity.shared::cta.b64 r, [%1], %2;\n"
               "and.pred p, p, r;\n@!p bra.uni WL;\n}" :: "r"(b0), "r"(b1), "r"(ph) : "memory"); }
__device__ __forceinline__ void mbar_waitw4(uint32_t b, uint32_t ph) { mbar_waitw2(b, b + 8, ph); mbar_waitw2(b + 16, b + 24, ph); }
__device__ __forceinline__ uint32_t clock32() { uint32_t t; asm volatile("mov.u32 %0, %%clock;" : "=r"(t) :: "memory"); return t; }
template <int L> __device__ __forceinline__ uint32_t lop3(uint32_t a, uint32_t b, uint32_t c) {
  uint32_t r; asm("lop3.b32 %0, %1, %2, %3, %4;" : "=r"(r) : "r"(a), "r"(b), "r"(c), "n"(L)); return r; }
__device__ __forceinline__ void st_async_v2_if(bool p, uint32_t a, uint32_t v0, uint32_t v1, uint32_t mb) {
  asm volatile("{\n.reg .pred q;\nsetp.ne.u32 q, %4, 0;\n@q st.async.weak.shared::cluster.mbarrier::complete_tx::bytes.v2.b32 [%0], {%1,%2}, [%3];\n}"
               :: "r"(a), "r"(v0), "r"(v1), "r"(mb), "r"((uint32_t)p) : "memory"); }
__device__ __forceinline__ void keep4(const uint32_t* r, int lane) {
  asm volatile("{\n.reg .pred q;\nsetp.lt.s32 q, %4, 0;\n@q st.shared.v4.b32 [%4], {%0,%1,%2,%3};\n}" :: "r"(r[0]), "r"(r[1]), "r"(r[2]), "r"(r[3]), "r"(lane) : "memory"); }
__device__ __forceinline__ void fence_sched(int i) {
  asm volatile("{\n.reg .pred q;\nsetp.gt.s32 q, %0, 4096;\n@q st.shared.u32 [%0], 0;\n}" :: "r"(i) : "memory"); }
__device__ __forceinline__ uint32_t hmax2bf(uint32_t a, uint32_t b) { uint32_t r; asm("max.bf16x2 %0, %1, %2;" : "=r"(r) : "r"(a), "r"(b)); return r; }
__device__ __forceinline__ uint32_t uni(uint32_t x) { return __shfl_sync(~0u, x, 0); }
__device__ __forceinline__ void bulk_g2s_mc_e(uint32_t dst, const void* src, uint32_t bytes, uint32_t mb, uint16_t mask) {
  asm volatile("{\n.reg .pred e;\nelect.sync _|e, 0xffffffff;\n"
               "@e cp.async.bulk.shared::cluster.global.mbarrier::complete_tx::bytes.multicast::cluster [%0], [%1], %2, [%3], %4;\n}"
               :: "r"(dst), "l"(src), "r"(bytes), "r"(mb), "h"(mask) : "memory"); }
__device__ __forceinline__ void bulk_s2g_e(void* dst, uint32_t src, uint32_t bytes) {
  asm volatile("{\n.reg .pred e;\nelect.sync _|e, 0xffffffff;\n@e cp.async.bulk.global.shared::cta.bulk_group [%0], [%1], %2;\n}"
               :: "l"(dst), "r"(src), "r"(bytes) : "memory"); }
__device__ __forceinline__ void bulk_g2s_e(uint32_t dst, const void* src, uint32_t bytes, uint32_t mb) {
  asm volatile("{\n.reg .pred e;\nelect.sync _|e, 0xffffffff;\n@e cp.async.bulk.shared::cluster.global.mbarrier::complete_tx::bytes [%0], [%1], %2, [%3];\n}"
               :: "r"(dst), "l"(src), "r"(bytes), "r"(mb) : "memory"); }
#define STREAM_HINT 1
__device__ __forceinline__ void bulk_s2g_es(void* dst, uint32_t src, uint32_t bytes) {
  asm volatile("{\n.reg .pred e;\n.reg .b64 pol;\ncreatepolicy.fractional.L2::evict_first.b64 pol;\nelect.sync _|e, 0xffffffff;\n"
               "@e cp.async.bulk.global.shared::cta.bulk_group.L2::cache_hint [%0], [%1], %2, pol;\n}" :: "l"(dst), "r"(src), "r"(bytes) : "memory");
}
__device__ __forceinline__ void bulk_g2s_es(uint32_t dst, const void* src, uint32_t bytes, uint32_t mb) {
  asm volatile("{\n.reg .pred e;\n.reg .b64 pol;\ncreatepolicy.fractional.L2::evict_first.b64 pol;\nelect.sync _|e, 0xffffffff;\n"
               "@e cp.async.bulk.shared::cluster.global.mbarrier::complete_tx::bytes.L2::cache_hint [%0], [%1], %2, [%3], pol;\n}"
               :: "r"(dst), "l"(src), "r"(bytes), "r"(mb) : "memory"); }
__device__ __forceinline__ void tma2d_e(uint32_t dst, const CUtensorMap* tm, int c0, int c1, uint32_t mb) {
  asm volatile("{\n.reg .pred e;\nelect.sync _|e, 0xffffffff;\n"
               "@e cp.async.bulk.tensor.2d.shared::cluster.global.mbarrier::complete_tx::bytes [%0], [%1, {%3, %4}], [%2];\n}"
               :: "r"(dst), "l"((uint64_t)tm), "r"(mb), "r"(c0), "r"(c1) : "memory"); }
__device__ __forceinline__ uint32_t hadd2bf(uint32_t a, uint32_t b) {
  uint32_t r; asm("add.rn.bf16x2 %0, %1, %2;" : "=r"(r) : "r"(a), "r"(b)); return r; }
__device__ __forceinline__ void cluster_sync_all() {
  asm volatile("barrier.cluster.arrive.release.aligned;\nbarrier.cluster.wait.acquire.aligned;" ::: "memory"); }
__device__ __forceinline__ void bar_arrive(int id, int n) { asm volatile("bar.arrive %0, %1;" :: "r"(id), "r"(n) : "memory"); }
__device__ __forceinline__ void bar_arrive_dep(int id, int n, uint32_t dep) {
  asm volatile("{\n.reg .u32 t;\nand.b32 t, %2, 0;\nadd.u32 t, t, %0;\nbar.sync t, %1;\n}" :: "r"(id), "r"(n), "r"(dep) : "memory"); }
__device__ __forceinline__ void bar_sync(int id, int n) { asm volatile("bar.sync %0, %1;" :: "r"(id), "r"(n) : "memory"); }
__device__ __forceinline__ void fence_async() { asm volatile("fence.proxy.async.shared::cta;" ::: "memory"); }
__device__ __forceinline__ void st_async_b32(uint32_t a, uint32_t v, uint32_t mb) {
  asm volatile("st.async.weak.shared::cluster.mbarrier::complete_tx::bytes.b32 [%0], %1, [%2];" :: "r"(a), "r"(v), "r"(mb) : "memory"); }
__device__ __forceinline__ void st_async_v2(uint32_t a, uint32_t v0, uint32_t v1, uint32_t mb) {
  asm volatile("st.async.weak.shared::cluster.mbarrier::complete_tx::bytes.v2.b32 [%0], {%1,%2}, [%3];" :: "r"(a), "r"(v0), "r"(v1), "r"(mb) : "memory"); }
__device__ __forceinline__ void st_async_v4(uint32_t a, uint32_t v0, uint32_t v1, uint32_t v2, uint32_t v3, uint32_t mb) {
  asm volatile("st.async.weak.shared::cluster.mbarrier::complete_tx::bytes.v4.b32 [%0], {%1,%2,%3,%4}, [%5];" :: "r"(a), "r"(v0), "r"(v1), "r"(v2), "r"(v3), "r"(mb) : "memory"); }
__device__ __forceinline__ void ldsm4(uint32_t& r0, uint32_t& r1, uint32_t& r2, uint32_t& r3, uint32_t a) {
  asm volatile("ldmatrix.sync.aligned.m8n8.x4.shared.b16 {%0,%1,%2,%3}, [%4];" : "=r"(r0), "=r"(r1), "=r"(r2), "=r"(r3) : "r"(a) : "memory"); }
__device__ __forceinline__ void ldsm4t(uint32_t& r0, uint32_t& r1, uint32_t& r2, uint32_t& r3, uint32_t a) {
  asm volatile("ldmatrix.sync.aligned.m8n8.x4.trans.shared.b16 {%0,%1,%2,%3}, [%4];" : "=r"(r0), "=r"(r1), "=r"(r2), "=r"(r3) : "r"(a) : "memory"); }
__device__ __forceinline__ void stsm2t(uint32_t a, uint32_t r0, uint32_t r1) {
  asm volatile("stmatrix.sync.aligned.m8n8.x2.trans.shared.b16 [%0], {%1,%2};" :: "r"(a), "r"(r0), "r"(r1) : "memory"); }
__device__ __forceinline__ void stsm4t(uint32_t a, uint32_t r0, uint32_t r1, uint32_t r2, uint32_t r3) {
  asm volatile("stmatrix.sync.aligned.m8n8.x4.trans.shared.b16 [%0], {%1,%2,%3,%4};" :: "r"(a), "r"(r0), "r"(r1), "r"(r2), "r"(r3) : "memory"); }
__device__ __forceinline__ uint32_t movm(uint32_t a) {
  uint32_t d; asm volatile("movmatrix.sync.aligned.m8n8.trans.b16 %0, %1;" : "=r"(d) : "r"(a)); return d; }
__device__ __forceinline__ void mma16816(float* d, uint32_t a0, uint32_t a1, uint32_t a2, uint32_t a3, uint32_t b0, uint32_t b1) {
  asm("mma.sync.aligned.m16n8k16.row.col.f32.bf16.bf16.f32 {%0,%1,%2,%3}, {%4,%5,%6,%7}, {%8,%9}, {%0,%1,%2,%3};"
               : "+f"(d[0]), "+f"(d[1]), "+f"(d[2]), "+f"(d[3]) : "r"(a0), "r"(a1), "r"(a2), "r"(a3), "r"(b0), "r"(b1)); }
__device__ __forceinline__ void mma16816v(float* d, uint32_t a0, uint32_t a1, uint32_t a2, uint32_t a3, uint32_t b0, uint32_t b1) {
  asm volatile("mma.sync.aligned.m16n8k16.row.col.f32.bf16.bf16.f32 {%0,%1,%2,%3}, {%4,%5,%6,%7}, {%8,%9}, {%0,%1,%2,%3};"
               : "+f"(d[0]), "+f"(d[1]), "+f"(d[2]), "+f"(d[3]) : "r"(a0), "r"(a1), "r"(a2), "r"(a3), "r"(b0), "r"(b1)); }
__device__ __forceinline__ uint32_t pack2(float lo, float hi) {
  uint32_t r; asm("cvt.rn.bf16x2.f32 %0, %1, %2;" : "=r"(r) : "f"(hi), "f"(lo)); return r; }
__device__ __forceinline__ uint32_t pack2v(float lo, float hi) {
  uint32_t r; asm volatile("cvt.rn.bf16x2.f32 %0, %1, %2;" : "=r"(r) : "f"(hi), "f"(lo)); return r; }
__device__ __forceinline__ float bf_lo(uint32_t w) { return __uint_as_float(w << 16); }
__device__ __forceinline__ float bf_hi(uint32_t w) { return __uint_as_float(w & 0xffff0000u); }
__device__ __forceinline__ uint4 lds128(uint32_t a) {
  uint4 v; asm volatile("ld.shared.v4.b32 {%0,%1,%2,%3}, [%4];" : "=r"(v.x), "=r"(v.y), "=r"(v.z), "=r"(v.w) : "r"(a) : "memory"); return v; }
__device__ __forceinline__ uint4 lds128_nv(uint32_t a) {
  uint4 v; asm volatile("ld.shared.v4.b32 {%0,%1,%2,%3}, [%4];" : "=r"(v.x), "=r"(v.y), "=r"(v.z), "=r"(v.w) : "r"(a)); return v; }
__device__ __forceinline__ void st_async_v2_nm(uint32_t a, uint32_t v0, uint32_t v1, uint32_t mb) {
  asm volatile("st.async.weak.shared::cluster.mbarrier::complete_tx::bytes.v2.b32 [%0], {%1,%2}, [%3];" :: "r"(a), "r"(v0), "r"(v1), "r"(mb)); }
__device__ __forceinline__ float rcpf(float x) { float y; asm("rcp.approx.ftz.f32 %0, %1;" : "=f"(y) : "f"(x)); return y; }
__device__ __forceinline__ void sts64(uint32_t a, uint32_t x, uint32_t y) { asm volatile("st.shared.v2.b32 [%0], {%1,%2};" :: "r"(a), "r"(x), "r"(y) : "memory"); }
__device__ __forceinline__ float ex2(float x) { float y; asm("ex2.approx.ftz.f32 %0, %1;" : "=f"(y) : "f"(x)); return y; }
__device__ __forceinline__ uint32_t lds32(uint32_t a) {
  uint32_t v; asm volatile("ld.shared.b32 %0, [%1];" : "=r"(v) : "r"(a) : "memory"); return v; }
__device__ __forceinline__ uint2 lds64(uint32_t a) {
  uint2 v; asm volatile("ld.shared.v2.b32 {%0,%1}, [%2];" : "=r"(v.x), "=r"(v.y) : "r"(a) : "memory"); return v; }
__device__ __forceinline__ void sts128(uint32_t a, uint32_t x, uint32_t y, uint32_t z, uint32_t w) {
  asm volatile("st.shared.v4.b32 [%0], {%1,%2,%3,%4};" :: "r"(a), "r"(x), "r"(y), "r"(z), "r"(w) : "memory"); }
__device__ __forceinline__ void sts32(uint32_t a, uint32_t x) { asm volatile("st.shared.b32 [%0], %1;" :: "r"(a), "r"(x) : "memory"); }
__device__ __forceinline__ void tma2d(uint32_t dst, const CUtensorMap* tm, int c0, int c1, uint32_t mb) {
  asm volatile("cp.async.bulk.tensor.2d.shared::cluster.global.mbarrier::complete_tx::bytes [%0], [%1, {%3, %4}], [%2];"
               :: "r"(dst), "l"((uint64_t)tm), "r"(mb), "r"(c0), "r"(c1) : "memory"); }
__device__ __forceinline__ void tma2d_prefetch(const CUtensorMap* tm, int c0, int c1) {
  asm volatile("cp.async.bulk.prefetch.tensor.2d.L2.global.tile [%0, {%1, %2}];" :: "l"((uint64_t)tm), "r"(c0), "r"(c1) : "memory"); }
__device__ __forceinline__ void bulk_g2s_mc(uint32_t dst, const void* src, uint32_t bytes, uint32_t mb, uint16_t mask) {
  asm volatile("cp.async.bulk.shared::cluster.global.mbarrier::complete_tx::bytes.multicast::cluster [%0], [%1], %2, [%3], %4;"
               :: "r"(dst), "l"(src), "r"(bytes), "r"(mb), "h"(mask) : "memory"); }
__device__ __forceinline__ void bulk_s2g(void* dst, uint32_t src, uint32_t bytes) {
  asm volatile("cp.async.bulk.global.shared::cta.bulk_group [%0], [%1], %2;" :: "l"(dst), "r"(src), "r"(bytes) : "memory"); }
__device__ __forceinline__ void wg_fence() { asm volatile("wgmma.fence.sync.aligned;" ::: "memory"); }
__device__ __forceinline__ void wg_commit() { asm volatile("wgmma.commit_group.sync.aligned;" ::: "memory"); }
template <int N> __device__ __forceinline__ void wg_wait() { asm volatile("wgmma.wait_group.sync.aligned %0;" :: "n"(N) : "memory"); }
__device__ __forceinline__ uint64_t mkdesc(uint32_t addr, uint32_t lbo, uint32_t sbo, uint32_t swz) {
  return (uint64_t)((addr & 0x3FFFF) >> 4) | ((uint64_t)(lbo >> 4) << 16) | ((uint64_t)(sbo >> 4) << 32) | ((uint64_t)swz << 62); }

#define ACC4(d) "+f"(d[0]),"+f"(d[1]),"+f"(d[2]),"+f"(d[3])
#define ACC8(d) ACC4(d), ACC4((d + 4))
#define ACC16(d) ACC8(d), ACC8((d + 8))
#define ACC20(d) ACC16(d), ACC4((d + 16))
#define ACC24(d) ACC16(d), ACC8((d + 16))
#define SMEM0 0x400
__host__ __device__ constexpr uint32_t dlo(uint32_t off, uint32_t lbo) { return ((SMEM0 + off) >> 4) | ((lbo >> 4) << 16); }
__host__ __device__ constexpr uint32_t dhi(uint32_t sbo, uint32_t swz) { return (sbo >> 4) | (swz << 30); }
#define R4S "{%0,%1,%2,%3}"
#define R8S "{%0,%1,%2,%3,%4,%5,%6,%7}"
#define R16S "{%0,%1,%2,%3,%4,%5,%6,%7,%8,%9,%10,%11,%12,%13,%14,%15}"
#define R20S "{%0,%1,%2,%3,%4,%5,%6,%7,%8,%9,%10,%11,%12,%13,%14,%15,%16,%17,%18,%19}"
#define R24S "{%0,%1,%2,%3,%4,%5,%6,%7,%8,%9,%10,%11,%12,%13,%14,%15,%16,%17,%18,%19,%20,%21,%22,%23}"
#define ACC32(d) ACC16(d), ACC16((d + 16))
#define R32S "{%0,%1,%2,%3,%4,%5,%6,%7,%8,%9,%10,%11,%12,%13,%14,%15,%16,%17,%18,%19,%20,%21,%22,%23,%24,%25,%26,%27,%28,%29,%30,%31}"
struct Dsc {
  uint64_t b; uint32_t e;
  __device__ __forceinline__ Dsc operator+(uint32_t o) const { return {b + o, e}; }
};
template <int K> __device__ __forceinline__ uint32_t fresh(int i) {
  uint32_t e; asm volatile("{\n.reg .u32 t;\nadd.u32 t, %1, %2;\nshr.u32 %0, t, %3;\n}" : "=r"(e) : "r"(i), "n"((256 << K) + 1), "n"(8 + K)); return e; }
template <int N, bool H = false> struct MM;
#define DEF_MM(N, H, T, ACCM, RS_, I0, I1, I2, I3, I4, I5, I6, I7)                                                                \
  template <> struct MM<N, H> {                                                                                                   \
    template <uint32_t BLO, int ACC>                                                                                              \
    static __device__ __forceinline__ void rs(float* d, const uint32_t* a, Dsc b0) {                                              \
      asm volatile("{\n.reg .b64 b;\nmad.wide.u32 b, %" #I7 ", %" #I5 ", %" #I4 ";\n"                                             \
                   "wgmma.mma_async.sync.aligned.m64n" #N "k16.f32." T "." T " " RS_ ", {%" #I0 ",%" #I1 ",%" #I2 ",%" #I3 "}, b, %" #I6 ", 1, 1, 0;\n}" \
                   : ACCM(d) : "r"(a[0]), "r"(a[1]), "r"(a[2]), "r"(a[3]), "l"(b0.b), "n"(BLO), "n"(ACC), "r"(b0.e)); }           \
    template <uint32_t ALO, uint32_t BLO, int ACC, int TA = 1>                                                                    \
    static __device__ __forceinline__ void ss(float* d, Dsc a0, Dsc b0) {                                                         \
      asm volatile("{\n.reg .b64 a, b;\nmad.wide.u32 a, %" #I6 ", %" #I1 ", %" #I0 ";\nmad.wide.u32 b, %" #I6 ", %" #I3 ", %" #I2 ";\n" \
                   "wgmma.mma_async.sync.aligned.m64n" #N "k16.f32." T "." T " " RS_ ", a, b, %" #I4 ", 1, 1, %" #I5 ", 0;\n}"    \
                   : ACCM(d) : "l"(a0.b), "n"(ALO), "l"(b0.b), "n"(BLO), "n"(ACC), "n"(TA), "r"(b0.e)); }                         \
  };
DEF_MM(8, false, "bf16", ACC4, R4S, 4, 5, 6, 7, 8, 9, 10, 11)
DEF_MM(16, false, "bf16", ACC8, R8S, 8, 9, 10, 11, 12, 13, 14, 15)
DEF_MM(32, false, "bf16", ACC16, R16S, 16, 17, 18, 19, 20, 21, 22, 23)
DEF_MM(40, false, "bf16", ACC20, R20S, 20, 21, 22, 23, 24, 25, 26, 27)
DEF_MM(48, false, "bf16", ACC24, R24S, 24, 25, 26, 27, 28, 29, 30, 31)
DEF_MM(64, false, "bf16", ACC32, R32S, 32, 33, 34, 35, 36, 37, 38, 39)
DEF_MM(32, true, "f16", ACC16, R16S, 16, 17, 18, 19, 20, 21, 22, 23)
DEF_MM(64, true, "f16", ACC32, R32S, 32, 33, 34, 35, 36, 37, 38, 39)

#define LAG 10
#define NSTEP (NSEG + LAG)
#define NR (NSTEP + 1)
__device__ __align__(1024) __nv_bfloat16 g_xn[2][S_LEN * DM];
#define RO 16
static_assert(RO > LAG + 1, "ring");
__device__ __align__(1024) unsigned char g_o[RO * 96 * 8192];
__device__ __align__(1024) uint32_t g_part[6][7][40][64];
#define RD 16
#define TILE_B 81920
__device__ __align__(1024) float2 g_stat[S_LEN];
__device__ __align__(1024) uint32_t g_st2[2][RD][64];
__device__ __align__(1024) unsigned char g_acc[5][RD][TILE_B];
#define NOP 19
#define NW12 5
#define NW34 12
#define NBC (NOP + NW12 + NW34)
__device__ __align__(1024) unsigned char g_wt[NOP * 10 * 12288];
enum { F_O = 0, F_R1 = NOP + 1, F_R2 = F_R1 + 4, F_R3 = F_R2 + 4, F_Z = F_R3 + 4, F_DONE, F_MISC, F_NUM };
__device__ __align__(128) uint32_t g_f[F_NUM][96];
__device__ __align__(128) int g_xready[129][8];
__device__ uint32_t g_tpc[128];
#define TS(i)
#define TSV(i, v)
#define TSN(i)
#define TSD(i, dep)
#define BTS(k, i)
#define BTS2(k, i)
#define RTS(i)
#define RTSD(i, dep)
#define RTS_OUT()
#define CTS(i)
#define PTS(i)
#define PTS1(i)
#define CTS_OUT()
#define GTS(i)

#define CL_SIZE 15
#define NCL 7
#define SSQ 13
#define SSV 16
#define PL_SZ 5376
#define TILE_SBO 2560
#define TILE_GRP 15360
#define WS_SZ ((2 * SSQ + SSV) * 2048)
#define OFF_QK (OFF_WO + 26 * 2048)
#define LAYOUT 2
#define OFF_TILE 0
#define OFF_WS (4 * TILE_GRP)
#define OFF_WO (OFF_WS + WS_SZ)
#define OFF_PL (OFF_QK + 20480)
#define OFF_BAR (OFF_PL + 2 * PL_SZ)
#define STG_Q OFF_TILE
#define STG_K OFF_WO
#define VA 14
#define STG_V2 (OFF_TILE + 27 * 2048)
#define OFF_O (OFF_PL + 4352)
#define LAND(k) (((k) >> 1) * TILE_GRP + ((k) & 1) * 1280)
#define LAND_F (5 * TILE_SBO)
#define OFF_XL (OFF_TILE + 3 * TILE_GRP)
#define OFF_XF (OFF_XL + LAND_F)
#define OFF_WT ((OFF_XL + TILE_SBO + 1023) & ~1023)
#define OFF_TAB (OFF_BAR + 240)
#define OFF_INV (OFF_TAB + 64)
#define OFF_TS (OFF_INV + 128)
#define A_SMEM 232448
static_assert(WS_SZ + 72 * 1024 + 2 * PL_SZ + 4 * TILE_GRP + 512 == A_SMEM && OFF_WS % 1024 == 0 && OFF_WO % 1024 == 0 && SSQ == 13, "smem map");
enum { B_W0 = 0, B_W1, B_F1, B_F2 = B_F1 + 4, B_R1 = B_F2 + 4, B_R2, B_MEMFREE, B_LANDFREE, B_OPEER, B_PLFREE, B_XFREE, B_SB, B_WOF = B_SB + 6, B_WTF, B_RS, B_NUM = B_RS + 4 };
static_assert(B_NUM <= 30, "barriers");
enum { N_C = 0, N_SISS, N_QK, N_V, N_PM, N_TURN, N_PI, N_VGO, N_O, N_PX, N_AB, N_SDONE, N_VDONE, N_G3, N_P, N_OX };

__device__ __forceinline__ bool is_dual(int j) { return j >= LAG && j < NSEG; }
__device__ __forceinline__ int sched_l(int j) { return j < NSEG ? j : NSEG + j - LAG; }
__device__ __forceinline__ int sched_f(int j) { return NSEG + j - LAG; }
__device__ __forceinline__ void wait_cnt(const int* p, int target) {
  int v, n = 0;
  do {
    asm volatile("ld.relaxed.gpu.global.b32 %0, [%1];" : "=r"(v) : "l"(p) : "memory");
    if (v >= target) break;
    if (++n > SPIN_LIMIT) FAIL();
  } while (true);
  asm volatile("fence.acquire.gpu;" ::: "memory");
  asm volatile("fence.proxy.async.global;" ::: "memory");
}
__device__ __forceinline__ void red_release(void* p, uint32_t v) { asm volatile("red.release.gpu.global.add.u32 [%0], %1;" :: "l"(p), "r"(v) : "memory"); }
__device__ __forceinline__ void red_relaxed(void* p, uint32_t v) { asm volatile("red.relaxed.gpu.global.add.u32 [%0], %1;" :: "l"(p), "r"(v) : "memory"); }
#define VMASK 0xa5294a5294ull
__host__ __device__ constexpr int popc40(unsigned long long m) { int c = 0; for (; m; m &= m - 1) c++; return c; }
static_assert(popc40(VMASK) == SSV, "mask");
__host__ __device__ constexpr int ss_idx(int ks, int n) { return n == SSV ? popc40(VMASK & ((1ull << ks) - 1)) : ks * n / 40; }
__host__ __device__ constexpr bool is_ss(int ks, int n) { return ss_idx(ks + 1, n) != ss_idx(ks, n); }
__host__ __device__ constexpr int rs_idx(int ks, int n) { return ks - ss_idx(ks, n); }

#define SL2 (0.07216878364870322f * 1.4426950408889634f)

#define SUM_LOOP 0
struct Desc { Dsc tile, unit, k1, pl, p; };
__device__ __forceinline__ Desc make_desc(const uint64_t* h, uint32_t u, uint32_t e) {
  return {{h[0], e}, {h[1] + u * 128, e}, {h[2], e}, {h[3], e}, {h[4], e}};
}
template <int N, int NSS, int RG, int KS, int K1, int K0 = 0>
__device__ __forceinline__ void proj(float* acc, const uint32_t* W, const Desc& D) {
  if constexpr (KS < K1) {
    constexpr uint32_t BLO = dlo(OFF_TILE + (KS / 10) * TILE_GRP + RG * TILE_SBO + (KS % 10) * 256, 128);
    if constexpr (is_ss(KS, NSS)) MM<N>::template ss<dlo(OFF_WS + ss_idx(KS, NSS) * 2048, 0), BLO, (KS != K0)>(acc, D.unit, D.tile);
    else MM<N>::template rs<BLO, (KS != K0)>(acc, W + rs_idx(KS, NSS) * 4, D.tile);
    proj<N, NSS, RG, KS + 1, K1, K0>(acc, W, D);
  }
}
#define VST 17
template <int KS>
__device__ __forceinline__ void ld_rest(uint32_t* W, const uint32_t* p) {
  if constexpr (KS < 40) {
    if constexpr (!is_ss(KS, SSV) && rs_idx(KS, SSV) >= VST) {
#pragma unroll
      for (int i = 0; i < 4; i++) W[4 * rs_idx(KS, SSV) + i] = __ldg(p + (KS * 16 + (i >> 1) * 8) * (HD / 2) + (i & 1) * 4);
    }
    ld_rest<KS + 1>(W, p);
  }
}
template <int N>
__device__ __forceinline__ void load_w(uint32_t* W, uint32_t stage, int warp, int lane) {
  const int kr = (lane >> 4) * 8 + (lane & 7);
  const int cb = warp * 2 + ((lane >> 3) & 1);
  const uint32_t a0 = stage + kr * 128 + ((cb ^ (lane & 7)) << 4);
#pragma unroll
  for (int i = 0; i < N; i++) ldsm4t(W[4 * i], W[4 * i + 1], W[4 * i + 2], W[4 * i + 3], a0 + i * 2048);
}
template <int N, int G, int U, int OS, int ACC>
__device__ __forceinline__ void wo4(float* d, const Desc& D) {
  constexpr uint32_t WA = (U >= 4 ? OFF_WO + (U - 4) * 2048 : OFF_WT) - G * SSQ * 2048, OB = OS == 0 ? OFF_O : OS == 1 ? OFF_XL : OFF_XF;
  Dsc b = OS ? D.k1 : D.pl;
  b.e = fresh<(U < 16 ? U / 4 : U / 8 - 2) + (N == 8 ? 4 : 0)>(D.unit.e);
  MM<N>::template ss<dlo(WA, 0), dlo(OB, 128), ACC>(d, D.unit, b);
  MM<N>::template ss<dlo(WA + 2048, 0), dlo(OB + 256, 128), 1>(d, D.unit, b);
  MM<N>::template ss<dlo(WA + 4096, 0), dlo(OB + 512, 128), 1>(d, D.unit, b);
  MM<N>::template ss<dlo(WA + 6144, 0), dlo(OB + 768, 128), 1>(d, D.unit, b);
}
__device__ __forceinline__ void wo_coord(int i, int t3, int head, int& c0, int& c1) {
  const int g = i >> 1;
  const int blk = g == 0 ? 9 : (g < 4 ? g - 1 : (g - 4) >> 1) * 3 + t3;
  int sl = g < 4 ? t3 : (g & 1) ? t3 + 1 : t3 + 2;
  if (sl >= 3) sl -= 3;
  c0 = blk * 64; c1 = head * DH + sl * 64 + (i & 1) * 32;
}
__device__ __forceinline__ void tok_softmax(uint32_t sb, int job, int lane) {
  const bool w1 = job & 1;
  const int dg = (lane >> 2) - (lane & 3) * 2;
  const uint32_t lo = sb + OFF_PL + (job >> 1) * PL_SZ + (job & 1) * 1792, l8 = lo + 512 + lane * 8, pa = lo + lane * 4;
  const uint32_t km = job & 2 ? 640 : 512;
  float x[14];
  {
    const uint4 a = lds128(lo + lane * 16);
    const uint2 e = lds64(l8);
    const uint32_t c = lds32(768 + pa);
    x[0] = bf_lo(a.x); x[1] = bf_hi(a.x); x[2] = bf_lo(a.y); x[3] = bf_hi(a.y); x[4] = bf_lo(a.z); x[5] = bf_hi(a.z); x[6] = bf_lo(a.w); x[7] = bf_hi(a.w);
    x[8] = bf_lo(c); x[9] = bf_hi(c); x[10] = bf_lo(e.x); x[11] = bf_hi(e.x); x[12] = bf_lo(e.y); x[13] = bf_hi(e.y);
  }
  if (dg < 0) { x[8] = -INFINITY; if (w1) x[4] = -INFINITY; else x[10] = -INFINITY; }
  if (dg < 1) { x[9] = -INFINITY; if (w1) x[5] = -INFINITY; else x[11] = -INFINITY; }
  const float m4 = fmaxf(x[8], x[9]);
  float m0 = fmaxf(fmaxf(fmaxf(x[0], x[1]), fmaxf(x[2], x[3])), fmaxf(fmaxf(x[4], x[5]), fmaxf(x[6], x[7])));
  float m1 = fmaxf(fmaxf(x[10], x[11]), fmaxf(x[12], x[13]));
  if (w1) m1 = fmaxf(m1, m4); else m0 = fmaxf(m0, m4);
  m0 = fmaxf(m0, __shfl_xor_sync(~0u, m0, 1)); m1 = fmaxf(m1, __shfl_xor_sync(~0u, m1, 1));
  sts32(pa + (w1 ? 384 : 896 + 128), 0u); sts32(pa + 1152 - km, 0u); sts32(pa + 896 + 1152 - km, 0u); sts64(l8 + 896 - 256, 0u, 0u);
  m0 = fmaxf(m0, __shfl_xor_sync(~0u, m0, 2)); m1 = fmaxf(m1, __shfl_xor_sync(~0u, m1, 2));
  m0 *= -SL2; m1 *= -SL2;
#pragma unroll
  for (int j = 0; j < 14; j++) x[j] = ex2(fmaf(x[j], SL2, j < 8 ? m0 : j >= 10 ? m1 : w1 ? m1 : m0));
  const float l4s = x[8] + x[9];
  float l0 = ((x[0] + x[1]) + (x[2] + x[3])) + ((x[4] + x[5]) + (x[6] + x[7])), l1 = (x[10] + x[11]) + (x[12] + x[13]);
  if (w1) l1 += l4s; else l0 += l4s;
  l0 += __shfl_xor_sync(~0u, l0, 1); l1 += __shfl_xor_sync(~0u, l1, 1);
  l0 += __shfl_xor_sync(~0u, l0, 2); l1 += __shfl_xor_sync(~0u, l1, 2);
  l0 = rcpf(l0); l1 = rcpf(l1);
#pragma unroll
  for (int j = 0; j < 7; j++) {
    const float iv = j < 4 ? l0 : j > 4 ? l1 : w1 ? l1 : l0;
    sts32(pa + (j < 3 ? j * 128 : j == 3 ? km : j == 4 ? (w1 ? 896 + 128 : 384) : j == 5 ? 896 : 896 + km), pack2(x[2 * j] * iv, x[2 * j + 1] * iv));
  }
}
template <int N>
__device__ __forceinline__ void wo_phase(uint32_t sb, int wg, int warp, int lane, uint32_t par, uint32_t r1, const Desc& D) {
  const uint32_t bar = sb + OFF_BAR;
  float x[N / 2], y[N / 2];
  const uint2 ta = lds64(sb + OFF_TAB + (wg * 4 + warp) * 8);
  uint32_t xa = (ta.x & ~255u) + lane * 8, xb = (ta.x & 0xFF0000FFu) + SMEM0 + OFF_BAR, ya = (ta.y & ~255u) + lane * 8, yb = (ta.y & 0xFF0000FFu) + SMEM0 + OFF_BAR;
  asm volatile("" : "+r"(xa), "+r"(xb), "+r"(ya), "+r"(yb));
  auto scat = [&](uint32_t ad, uint32_t mb, const float* d) {
    st_async_v2(ad, pack2(d[0], d[1]), pack2(d[2], d[3]), mb);
    if (N == 16) st_async_v2(ad + LAND_F, pack2(d[4], d[5]), pack2(d[6], d[7]), mb);
  };
  if (wg == 0) {
    bar_sync(N_O, 384);
    wg_fence(); wo4<N, 0, 4, 0, 0>(x, D); wo4<N, 0, 8, 0, 0>(y, D); wg_commit();
    mbar_waitu(bar + 8 * B_OPEER, par);
    CFENCE(); wg_fence(); wo4<N, 0, 16, 1, 1>(x, D); wo4<N, 0, 20, 2, 1>(x, D); wg_commit();
    wo4<N, 0, 24, 1, 1>(y, D); wg_commit();
    mbar_waitu2(bar + 8 * B_WOF, bar + 8 * B_MEMFREE, par);
    wg_fence(); wo4<N, 0, 28, 2, 1>(y, D); wg_commit();
    bar_arrive(N_AB, 256);
    wg_wait<2>(); scat(xa, xb, x);
    wg_wait<0>(); scat(ya, yb, y);
  } else {
    bar_sync(N_O, 384);
    wg_fence(); wo4<N, 1, 0, 0, 0>(x, D); wg_commit(); wo4<N, 1, 12, 0, 0>(y, D); wg_commit();
    wg_wait<1>(); mbar_arrive_remote_if(lane == 0, r1);
    mbar_waitu(bar + 8 * B_MEMFREE, par);
    scat(xa, xb, x);
    bar_sync(N_AB, 256);
    CFENCE(); wg_fence(); wo4<N, 1, 32, 1, 1>(y, D); wo4<N, 1, 36, 2, 1>(y, D); wg_commit();
    bar_arrive(N_TURN, 256);
    wg_wait<0>(); scat(ya, yb, y);
  }
}
#define DS_DUAL 10
#define DS_SINGLE 20
#define POLL_GAP 100
#define POLL_GAPD 0
#define TOK_DELAY 250
#define LATE_SM 1
#define UMAX 40
#define VD1 10
#define VS2 20
#define IG_V 3
#define VS1 4
struct AMaps { CUtensorMap w16[3], wo32; uint64_t d[5]; const __nv_bfloat16* wv; };
__global__ void __launch_bounds__(512, 1)
acore_kernel(const __grid_constant__ AMaps M, const __nv_bfloat16* __restrict__ mem0, int sync_b) {
  extern __shared__ __align__(1024) unsigned char smem_raw[];
  const uint32_t sb = smem_u32(smem_raw);
  GTS(24);
  if (threadIdx.x == 480) {
    uint32_t smid; asm volatile("mov.u32 %0, %%smid;" : "=r"(smid));
    g_tpc[(smid >> 1) & 127] = blockIdx.x - CL_SIZE < 3 * CL_SIZE && blockIdx.x % CL_SIZE >= 12 ? 1 : 2;
    asm volatile("griddepcontrol.launch_dependents;");
  }
  const int lane0 = threadIdx.x & 31;
#define LANE_INIT() int lane; asm volatile("mov.u32 %0, %%laneid;" : "=r"(lane))
  const int warp = __shfl_sync(~0u, (threadIdx.x >> 5) & 3, 0);
  const int cl = blockIdx.x / CL_SIZE;
  const uint32_t rank = blockIdx.x - cl * CL_SIZE;
  const int nh = cl >= 1 && cl <= 3 ? 4 : 5;
  const int nA = 3 * nh;
  const int wg = __shfl_sync(~0u, (int)rank < nA ? threadIdx.x >> 7 : 4, 0);
  const int head = (cl < 4 ? (cl ? 1 + 4 * cl : 0) : 5 * cl - 3) + rank / 3;
  const int t3 = rank % 3;
  const int col0 = head * DH + t3 * 64;
  const uint32_t bar = sb + OFF_BAR;
  const uint32_t rb0 = SMEM0;
  const uint16_t mcmask = (uint16_t)((1u << nA) - 1);
  const uint32_t nxt = sb + ((t3 == 2 ? -2 : 1) << 24), prv = sb + ((t3 == 0 ? 2 : -1) << 24);
  const int ig = (int)rank - (nA - 4);

  if (threadIdx.x == 0) {
    if (mapa(sb, nA - 1) != rb0 + ((nA - 1) << 24) || mapa(sb, 0) != rb0 || mapa(sb, 1) != rb0 + (1u << 24) || sb != SMEM0 + (rank << 24)) FAIL();
    for (int i = 0; i < B_NUM; i++)
      mbar_init(bar + 8 * i, i == B_R1 ? 4 * nA : i == B_R2 ? 12 * nA : i == B_MEMFREE ? nA : i == B_LANDFREE ? 4 * nA : i == B_PLFREE || i == B_XFREE ? 2 : 1);
    asm volatile("fence.mbarrier_init.release.cluster;" ::: "memory");
    mbar_expect(bar + 8 * B_W0, (80 + SSV + VST) * 2048);
  }
  __syncthreads();
  if (lane0 == 0) {
    const int w12 = wg * 4 + warp;
    if (w12 < 10) {
#pragma unroll 1
      for (int ks = 4 * w12; ks < 4 * w12 + 4; ks++) {
        const bool ss = is_ss(ks, SSQ);
        tma2d(ss ? sb + OFF_WS + ss_idx(ks, SSQ) * 2048 : sb + STG_Q + rs_idx(ks, SSQ) * 2048, &M.w16[0], col0, ks * 16, bar + 8 * B_W0);
        tma2d(ss ? sb + OFF_WS + (SSQ + ss_idx(ks, SSQ)) * 2048 : sb + STG_K + rs_idx(ks, SSQ) * 2048, &M.w16[1], col0, ks * 16, bar + 8 * B_W0);
        if (is_ss(ks, SSV)) tma2d(sb + OFF_WS + (2 * SSQ + ss_idx(ks, SSV)) * 2048, &M.w16[2], col0, ks * 16, bar + 8 * B_W0);
        else if (rs_idx(ks, SSV) < VST) tma2d(sb + (rs_idx(ks, SSV) < VA ? STG_K + 27 * 2048 : STG_V2 - VA * 2048) + rs_idx(ks, SSV) * 2048, &M.w16[2], col0, ks * 16, bar + 8 * B_W0);
      }
    }
  }
  if (lane0 < 2 && wg < 2) {
    const int u = 4 * (wg ? (lane0 ? 6 + t3 : 9) : (lane0 ? 3 + t3 : t3)) + warp;
    const int li = (u >= nA) + (u >= 2 * nA) + (u >= 3 * nA);
    sts32(sb + OFF_TAB + (wg * 4 + warp) * 8 + lane0 * 4,
          rb0 + ((u - li * nA) << 24) + OFF_TILE + LAND(li + (u >= 36 ? t3 : 0)) + (rank / 3) * 256 + 8 * (B_RS + li));
  }
  __syncthreads();
  GTS(25);

  auto issue_tok = [&](int sc, int fb, int rel = -1, uint32_t ph = 0) {
    if (sync_b) wait_cnt(&g_xready[sc][0], 32);
    if (rel >= 0) mbar_waitu(bar + 8 * rel, ph);
    bulk_g2s_mc_e(sb + OFF_TILE + ig * TILE_GRP + TILE_SBO, &g_xn[0][0] + uni(sc * (32 * DM)) + ig * 5120, 10240, bar + 8 * (fb + ig), mcmask);
  };
#define POLL(d, q) _Pragma("unroll") for (int k = 0; k < NCL; k++) \
      asm volatile("ld.relaxed.gpu.global.v2.b32 {%0,%1}, [%2];" : "=r"(d[k].x), "=r"(d[k].y) : "l"(q + k * 2560) : "memory")
#define L3(L, a, b, c) lop3<L>(a, b, c)
#define TAGS(L, d) L3(L, L3(L, L3(L, d[0].x, d[0].y, d[1].x), L3(L, d[1].y, d[2].x, d[2].y), L3(L, d[3].x, d[3].y, d[4].x)), L3(L, d[4].y, d[5].x, d[5].y), L3(L, d[6].x, d[6].y, d[6].y))
    auto deliver = [&](uint2* pa, const uint32_t* gq, int u, int c, int dc, int ds, int step, bool first, int lane) {
      const uint32_t off = uni(OFF_TILE + ((u * 205) >> 11) * (TILE_GRP - TILE_SBO) + u * 256 + dc * LAND_F), boff = uni(OFF_BAR + 8 * (B_F1 + ((u * 205) >> 11)));
      const uint32_t* mi = &g_part[4][0][0][0] + uni((c * NCL + cl) * 2560 + u * 64);
      mbar_waitu(bar + 8 * B_LANDFREE, step & 1);
      int n = 0;
      while (true) {
        const bool ok = __all_sync(~0u, ((step & 2 ? ~TAGS(0xFE, pa) : TAGS(0x80, pa)) & 1) != 0);
        if (ok) break;
        if (++n > SPIN_LIMIT) FAIL();
        POLL(pa, gq);
      }
      if (warp == 0 && first) { TS(19); TSV(10, n); }
      const uint32_t w0 = hadd2bf(hadd2bf(hadd2bf(pa[0].x, pa[1].x), hadd2bf(pa[2].x, pa[3].x)), hadd2bf(hadd2bf(pa[4].x, pa[5].x), pa[6].x));
      const uint32_t w1 = hadd2bf(hadd2bf(hadd2bf(pa[0].y, pa[1].y), hadd2bf(pa[2].y, pa[3].y)), hadd2bf(hadd2bf(pa[4].y, pa[5].y), pa[6].y));
      if (u < ds) {
        const uint32_t da = SMEM0 + off + lane * 8, db = SMEM0 + boff;
#pragma unroll
        for (int d = 0; d < 12; d++) st_async_v2((d << 24) + da, w0, w1, (d << 24) + db);
#pragma unroll
        for (int d = 12; d < 15; d++) st_async_v2_if(nA == 15, (d << 24) + da, w0, w1, (d << 24) + db);
      } else {
        *reinterpret_cast<uint2*>(const_cast<uint32_t*>(gq) + ((4 - 2 * (step & 1)) * NCL + cl) * 2560) = make_uint2(w0, w1);
        asm volatile("fence.proxy.async.global;" ::: "memory");
        __syncwarp();
        bulk_g2s_mc_e(sb + off, mi, 256, sb + boff, mcmask);
      }
    };
#define REL(b, g) mbar_arrive_remote_if(lane == 0, rb0 + ((nA - 4 + (g)) << 24) + OFF_BAR + 8 * (b))

  if (wg < 2) {
    asm volatile("setmaxnreg.inc.sync.aligned.u32 160;");
    LANE_INIT();
    uint32_t W[4 * (40 - SSQ)];
    mbar_waitw(bar + 8 * B_W0, 0);
    GTS(26);
    load_w<40 - SSQ>(W, sb + (wg ? STG_K : STG_Q), warp, lane);
    fence_async();
    bar_sync(1, 384);
    cluster_sync_all();
#define DESC(k) const Desc D = make_desc(M.d, min(wg, 2) * SSQ, fresh<k>(step))
    GTS(27);
#pragma unroll 1
    for (int step = -1; step < NSTEP; step++) {
      const uint32_t par = step & 1;
      asm volatile("" : "+r"(lane));
      const bool dual = is_dual(step), has_next = step + 1 < NSTEP;
#define QK_SA (sb + OFF_QK + wg * 15360 + (2 * warp + ((lane >> 3) & 1)) * 128 + (lane & 7) * 16)
#define QK_F (wg ? -5120 : 5120)
#define QK_S12 ((wg ? (lane >> 4) : 1 + 2 * (lane >> 4)) * 1024)
#define QK_S34 ((wg ? 2 + (lane >> 4) : 2 - 2 * (lane >> 4)) * 1024)
      if (step >= 0) {
        if (dual) {
          DESC(0);
          float acc[24];
          mbar_waitu(bar + 8 * (B_F1 + 0), par);
          if (wg + warp == 0) { TS(0); TSN(1); }
          CFENCE(); wg_fence(); proj<48, SSQ, 0, 0, 10>(acc, W, D); wg_commit();
          mbar_waitu(bar + 8 * (B_F1 + 1), par);
          CFENCE(); wg_fence(); proj<48, SSQ, 0, 10, 20>(acc, W, D); wg_commit();
          mbar_waitu(bar + 8 * (B_F1 + 2), par);
          CFENCE(); wg_fence(); proj<48, SSQ, 0, 20, 30>(acc, W, D); wg_commit();
          mbar_waitu(bar + 8 * (B_F1 + 3), par);
          if (wg + warp == 0) TS(2);
          CFENCE(); wg_fence(); proj<48, SSQ, 0, 30, 40>(acc, W, D); wg_commit();
          bar_arrive(N_VGO, 384);
          mbar_waitu(bar + 8 * B_PLFREE, par);
          const uint32_t sa = QK_SA, s0 = sa + 4096 + (lane >> 4) * QK_F, s1 = sa + QK_F + QK_S12, s2 = sa + QK_F + QK_S34;
          wg_wait<0>();
          if (wg + warp == 0) TS(3);
          stsm4t(s0, pack2(acc[0], acc[1]), pack2(acc[2], acc[3]), pack2(acc[20], acc[21]), pack2(acc[22], acc[23]));
          stsm4t(s1, pack2(acc[4], acc[5]), pack2(acc[6], acc[7]), pack2(acc[8], acc[9]), pack2(acc[10], acc[11]));
          stsm4t(s2, pack2(acc[12], acc[13]), pack2(acc[14], acc[15]), pack2(acc[16], acc[17]), pack2(acc[18], acc[19]));
        } else {
          DESC(1);
          float acc[4];
          mbar_waitu(bar + 8 * (B_F1 + 0), par);
          if (wg + warp == 0) { TS(0); TSN(1); }
          CFENCE(); wg_fence(); proj<8, SSQ, 0, 0, 10>(acc, W, D); wg_commit();
          mbar_waitu(bar + 8 * (B_F1 + 1), par);
          CFENCE(); wg_fence(); proj<8, SSQ, 0, 10, 20>(acc, W, D); wg_commit();
          mbar_waitu(bar + 8 * (B_F1 + 2), par);
          CFENCE(); wg_fence(); proj<8, SSQ, 0, 20, 30>(acc, W, D); wg_commit();
          mbar_waitu(bar + 8 * (B_F1 + 3), par);
          if (wg + warp == 0) TS(2);
          CFENCE(); wg_fence(); proj<8, SSQ, 0, 30, 40>(acc, W, D); wg_commit();
          bar_arrive(N_VGO, 384);
          mbar_waitu(bar + 8 * B_PLFREE, par);
          const uint32_t s0 = QK_SA + 4096;
          wg_wait<0>();
          if (wg + warp == 0) TS(3);
          stsm2t(s0, pack2(acc[0], acc[1]), pack2(acc[2], acc[3]));
        }
        fence_async();
        bar_sync(N_QK, 256);
        if (wg == 0 || dual) {
          float s[20];
          DESC(2);
          const Dsc ab = D.k1 + wg * 192, bb = D.k1 + (1 - wg) * 320;
          wg_fence();
          MM<40>::ss<dlo(OFF_QK, 128), dlo(OFF_QK + 10240, 128), 0, 0>(s, ab, bb);
          MM<40>::ss<dlo(OFF_QK + 256, 128), dlo(OFF_QK + 10240 + 256, 128), 1, 0>(s, ab, bb);
          MM<40>::ss<dlo(OFF_QK + 512, 128), dlo(OFF_QK + 10240 + 512, 128), 1, 0>(s, ab, bb);
          MM<40>::ss<dlo(OFF_QK + 768, 128), dlo(OFF_QK + 10240 + 768, 128), 1, 0>(s, ab, bb);
          wg_commit();
          bar_arrive(N_SISS, 384);
          const int rw = (warp - wg) & 3;
          const uint32_t bo = OFF_BAR + 8 * (B_SB + 3 * wg + rw), lo = OFF_PL + wg * PL_SZ + rw * 1792;
          const uint32_t km = wg ? 640 : 512;
          uint32_t l16 = lo + lane * 16, l4 = lo + lane * 4;
          mbar_expect_if(lane == 0 && rw < 3, sb + bo, rw < 2 ? 1792 : 1280);
          asm volatile("" : "+r"(l16), "+r"(l4));
          if (rw == 2) {
            wg_wait<0>();
            if (wg == 0) TSD(4, __float_as_uint(s[0]));
            const uint32_t w0 = pack2(s[0], s[1]), w1 = pack2(s[4], s[5]), w2 = pack2(s[8], s[9]), w3 = pack2(s[12], s[13]), w4 = pack2(s[16], s[17]);
            {
              st_async_v4(nxt + 896 + l16, w0, w1, w2, w3, nxt + bo);
              st_async_v4(prv + l16, w0, w1, w2, w3, prv + bo);
              st_async_b32(nxt + 896 + 768 + l4, w4, nxt + bo);
              st_async_b32(prv + 768 + l4, w4, prv + bo);
            }
            bar_arrive(N_SDONE, 256);
            mbar_waitu(sb + bo, (step - wg * LAG) & 1);
            if (wg == 0) TS(5);
            float x[10], m0;
            {
              const uint4 a = lds128(sb + l16), b = lds128(sb + 896 + l16);
              const uint32_t c = lds32(sb + 768 + l4), d = lds32(sb + 896 + 768 + l4);
              const uint32_t e0 = hadd2bf(hadd2bf(a.x, b.x), w0), e1 = hadd2bf(hadd2bf(a.y, b.y), w1), e2 = hadd2bf(hadd2bf(a.z, b.z), w2),
                             e3 = hadd2bf(hadd2bf(a.w, b.w), w3), e4 = hadd2bf(hadd2bf(c, d), w4);
              const uint32_t em = hmax2bf(hmax2bf(hmax2bf(e0, e1), hmax2bf(e2, e3)), e4);
              m0 = fmaxf(bf_lo(em), bf_hi(em));
              x[0] = bf_lo(e0); x[1] = bf_hi(e0); x[2] = bf_lo(e1); x[3] = bf_hi(e1); x[4] = bf_lo(e2);
              x[5] = bf_hi(e2); x[6] = bf_lo(e3); x[7] = bf_hi(e3); x[8] = bf_lo(e4); x[9] = bf_hi(e4);
            }
            m0 = fmaxf(m0, __shfl_xor_sync(~0u, m0, 1));
            sts32(sb + l4 + 1152 - km, 0u);
            m0 = fmaxf(m0, __shfl_xor_sync(~0u, m0, 2));
            m0 *= -SL2;
#pragma unroll
            for (int j = 0; j < 5; j++) {
              x[2 * j] = ex2(fmaf(x[2 * j], SL2, m0)); x[2 * j + 1] = ex2(fmaf(x[2 * j + 1], SL2, m0));
              sts32(sb + l4 + (j < 4 ? j * 128 : km), pack2(x[2 * j], x[2 * j + 1]));
            }
            float l = ((x[0] + x[1]) + (x[2] + x[3])) + ((x[4] + x[5]) + ((x[6] + x[7]) + (x[8] + x[9])));
            l += __shfl_xor_sync(~0u, l, 1);
            fence_async();
            sts32(sb + OFF_INV + wg * 64 + (lane >> 1) * 4, __float_as_uint(l));
            bar_arrive(N_PM, dual ? 224 : 192);
            if (wg == 0) TS(6);
          } else if (rw < 2) {
            const bool w1 = rw == 1;
            const uint32_t l8 = lo + 512 + lane * 8;
            uint32_t tw[7];
            wg_wait<0>();
            bar_arrive(N_SDONE, 256);
            tw[0] = pack2(s[0], s[1]); tw[1] = pack2(s[4], s[5]); tw[2] = pack2(s[8], s[9]); tw[3] = pack2(s[16], s[17]);
            tw[4] = w1 ? pack2(s[6], s[7]) : pack2(s[12], s[13]); tw[5] = pack2(s[2], s[3]); tw[6] = pack2(s[18], s[19]);
            { const uint32_t t0 = clock32(); while (clock32() - t0 < TOK_DELAY) {} }
            st_async_v4(nxt + 896 + l16, tw[0], tw[1], tw[2], tw[3], nxt + bo);
            st_async_v4(prv + l16, tw[0], tw[1], tw[2], tw[3], prv + bo);
            st_async_v2(nxt + 896 + l8, tw[5], tw[6], nxt + bo);
            st_async_v2(prv + l8, tw[5], tw[6], prv + bo);
            st_async_b32(nxt + 896 + 768 + l4, tw[4], nxt + bo);
            st_async_b32(prv + 768 + l4, tw[4], prv + bo);
            mbar_waitu(sb + bo, (step - wg * LAG) & 1);
            const uint4 a = lds128(sb + l16), b = lds128(sb + 896 + l16);
            const uint2 e = lds64(sb + l8), f = lds64(sb + 896 + l8);
            const uint32_t c = lds32(sb + 768 + l4), d = lds32(sb + 896 + 768 + l4);
            sts128(sb + l16, hadd2bf(hadd2bf(a.x, b.x), tw[0]), hadd2bf(hadd2bf(a.y, b.y), tw[1]), hadd2bf(hadd2bf(a.z, b.z), tw[2]), hadd2bf(hadd2bf(a.w, b.w), tw[3]));
            sts64(sb + l8, hadd2bf(hadd2bf(e.x, f.x), tw[5]), hadd2bf(hadd2bf(e.y, f.y), tw[6]));
            sts32(sb + 768 + l4, hadd2bf(hadd2bf(c, d), tw[4]));
            bar_arrive(N_PX, dual ? 256 : 192);
            if (wg + warp == 0) TS(9);
          } else {
            wg_wait<0>();
            if (wg == 0) {
              mbar_expect_if(lane < 3 && has_next, bar + 8 * (lane == 2 ? B_OPEER : B_WOF + lane), lane == 2 ? (dual ? 4096 : 2048) : lane ? 8192 : 20480);
              auto fetch = [&](int i, int n, uint32_t dst, int mb) {
                int c0, c1; wo_coord(i, t3, head, c0, c1);
                tma2d_e(dst, &M.wo32, c0, c1, bar + 8 * mb); if (n == 2) tma2d_e(dst + 4096, &M.wo32, c0, c1 + 32, bar + 8 * mb);
              };
              bar_sync(N_G3, 160);
              if (has_next) {
                fetch(0, 2, sb + OFF_WT, B_WTF);
                mbar_arrive_remote_if(lane < 2, (lane ? nxt : prv) + OFF_BAR + 8 * B_XFREE);
              }
              bar_sync(N_SDONE, 256);
              if (has_next) {
                fetch(15, 1, sb + OFF_QK, B_WOF); fetch(16, 2, sb + OFF_QK + 4096, B_WOF); fetch(18, 2, sb + OFF_QK + 12288, B_WOF);
                mbar_waitu(bar + 8 * B_XFREE, par);
              }
              bar_arrive(N_PM, dual ? 224 : 192);
              bar_sync(N_VDONE, 160);
              mbar_arrive_remote_if(lane < nA && has_next, rb0 + (lane << 24) + OFF_BAR + 8 * B_MEMFREE);
              if (has_next) mbar_waitu(bar + 8 * B_WTF, par);
            } else {
              bar_arrive(N_SDONE, 256);
              if ((unsigned)ig < IG_V) issue_tok(sched_l(step + 1), B_F2, B_R1, (step - LAG) & 1);
            }
          }
        } else {
          bar_arrive(N_SISS, 384);
          bar_arrive(N_SDONE, 256);
        }
        if (has_next) {
          if (step == 0) mbar_waitw(bar + 8 * B_W1, 0);
          const uint32_t r1 = rb0 + ((nA - 1) << 24) + OFF_BAR + 8 * B_R1;
          if (dual) { DESC(3); wo_phase<16>(sb, wg, warp, lane, par, r1, D); } else { DESC(4); wo_phase<8>(sb, wg, warp, lane, par, r1, D); }
          bar_arrive(N_C, 288);
          if (warp == 0) TS(7 + wg);
        }
      }
      if (has_next) {
        DESC(5);
        float acc[16];
        mbar_waitu(bar + 8 * B_F2, par ^ 1);
        wg_fence(); proj<32, SSQ, 1, 0, 10>(acc, W, D); wg_commit();
        mbar_waitu(bar + 8 * (B_F2 + 1), par ^ 1);
        wg_fence(); proj<32, SSQ, 1, 10, 14>(acc, W, D); wg_commit();
        wg_wait<1>(); REL(B_R2, 0);
        wg_fence(); proj<32, SSQ, 1, 14, 20>(acc, W, D); wg_commit();
        mbar_waitu(bar + 8 * (B_F2 + 2), par ^ 1);
        wg_fence(); proj<32, SSQ, 1, 20, 24>(acc, W, D); wg_commit();
        wg_wait<1>(); REL(B_R2, 1);
        wg_fence(); proj<32, SSQ, 1, 24, 30>(acc, W, D); wg_commit();
        mbar_waitu(bar + 8 * (B_F2 + 3), par ^ 1);
        wg_fence(); proj<32, SSQ, 1, 30, 34>(acc, W, D); wg_commit();
        wg_wait<1>(); REL(B_R2, 2);
        wg_fence(); proj<32, SSQ, 1, 34, 40>(acc, W, D); wg_commit();
        const uint32_t sa = QK_SA, s1 = sa + QK_S12, s2 = sa + QK_S34;
        wg_wait<0>(); REL(B_R2, 3);
        if (warp == 0) TS(11 + wg);
        stsm4t(s1, pack2(acc[0], acc[1]), pack2(acc[2], acc[3]), pack2(acc[4], acc[5]), pack2(acc[6], acc[7]));
        stsm4t(s2, pack2(acc[8], acc[9]), pack2(acc[10], acc[11]), pack2(acc[12], acc[13]), pack2(acc[14], acc[15]));
      }
    }
    GTS(28);
    cluster_sync_all();
  } else if (wg == 2) {
    asm volatile("setmaxnreg.inc.sync.aligned.u32 160;");
    LANE_INIT();
    uint32_t W[4 * (40 - SSV)];
    ld_rest<0>(W, reinterpret_cast<const uint32_t*>(M.wv + (lane >> 2) * HD + col0 + warp * 16) + (lane & 3));
    uint4 m0[5];
#pragma unroll
    for (int i = 0; i < 5; i++) {
      const int t = i * 128 + warp * 32 + lane;
      m0[i] = __ldg(reinterpret_cast<const uint4*>(mem0 + ((t >> 1) & 7) * DM + (t >> 4) * 16 + ((t ^ (t >> 3)) & 1) * 8));
    }
    mbar_waitw(bar + 8 * B_W0, 0);
    load_w<VA>(W, sb + STG_K + 27 * 2048, warp, lane);
    load_w<VST - VA>(W + 4 * VA, sb + STG_V2, warp, lane);
    fence_async();
    mbar_expect_if(warp + lane == 0, bar + 8 * B_W1, 26 * 2048);
    bar_sync(1, 384);
#pragma unroll
    for (int i = 0; i < 5; i++) {
      const int t = i * 128 + warp * 32 + lane;
      sts128(sb + OFF_TILE + (t / 160) * (TILE_GRP - TILE_SBO) + t * 16, m0[i].x, m0[i].y, m0[i].z, m0[i].w);
    }
#pragma unroll
    for (int i = 4 * VST; i < 4 * (40 - SSV); i++) W[i] = movm(W[i]);
    fence_async();
    mbar_arrive_if(lane == 0, bar + 8 * (B_F1 + warp));
    mbar_expect_if(lane == 0, bar + 8 * (B_F2 + warp), 10240);
    mbar_arrive_if(warp == 3 && lane < 2, bar + 8 * B_PLFREE);
    cluster_sync_all();
    uint32_t vl[8];
    {
      const int step = warp;
      DESC(0);
      float v[16];
      mbar_waitw4(bar + 8 * B_F2, 0);
      wg_fence(); proj<32, SSV, 1, 0, 40>(v, W, D); wg_commit();
      wg_wait<0>();
      mbar_arrive_remote_if(lane < 4, rb0 + ((nA - 4 + lane) << 24) + OFF_BAR + 8 * B_R2);
#pragma unroll
      for (int j = 0; j < 8; j++) vl[j] = pack2v(v[2 * j], v[2 * j + 1]);
      if (warp == 0 && (unsigned)ig < 3) issue_tok(1, B_F2, B_R2, 0);
    }
#pragma unroll 1
    for (int step = 0; step < NSTEP; step++) {
      const uint32_t par = step & 1;
      asm volatile("" : "+r"(lane));
      const bool dual = is_dual(step), has_next = step + 1 < NSTEP;
      mbar_expect_if(lane == 0 && has_next, bar + 8 * (B_F2 + warp), 10240);
      if (warp == 0 && ig >= IG_V && dual && sync_b) wait_cnt(&g_xready[sched_l(step + 1)][0], 32);
      bar_sync(N_VGO, 384);
      CFENCE();
#define F1_BYTES (is_dual(step + 1) ? 15360 : 2560)
#define ARM() do { \
        mbar_expect_if(lane == 0 && has_next, bar + 8 * (B_F1 + warp), F1_BYTES); \
        mbar_expect_if(lane == 0 && has_next && warp * nA + (int)rank < 40, bar + 8 * (B_RS + warp), (warp * nA + (int)rank >= 36 ? nA : nh) * (dual ? 512 : 256)); } while (0)
#define O_ADDR() uint32_t oa = sb + OFF_O + (lane >> 4) * PL_SZ + warp * 256 + (lane & 15) * 16, xo = (lane >> 4) * 1024 + warp * 256 + (lane & 15) * 16; \
        asm volatile("" : "+r"(oa), "+r"(xo))
#define O_READY(act) do { if (has_next) { const uint4 ov = lds128(oa); \
        if (act) { st_async_v4(nxt + OFF_XL + xo, ov.x, ov.y, ov.z, ov.w, nxt + OFF_BAR + 8 * B_OPEER); \
                   st_async_v4(prv + OFF_XF + xo, ov.x, ov.y, ov.z, ov.w, prv + OFF_BAR + 8 * B_OPEER); } \
        fence_async(); bar_arrive(N_O, 384); } \
        if (warp == 0) TS(15); } while (0)
#define TOK_L3(g0) if (warp == 0 && ig >= (g0) && has_next) { mbar_waitu(bar + 8 * B_R1, ig == 3 ? par : (step - LAG) & 1); asm volatile("fence.proxy.async.global;" ::: "memory"); \
        bulk_g2s_mc_e(sb + OFF_TILE + ig * TILE_GRP + TILE_SBO, &g_xn[0][0] + uni(sched_l(step + 1) * (32 * DM)) + ig * 5120, 10240, bar + 8 * (B_F2 + ig), mcmask); }
#define OX_ADDR() const bool ox = head * 3 + t3 == 95; \
        const uint32_t oxa = sb + OFF_PL + (ox ? warp * 1024 + (lane & 7) * 32 + ((((lane >> 3) ^ (lane >> 2)) & 1) << 4) : (lane & 7) * 128 + (((warp * 2 + ((lane >> 3) & 1)) ^ (lane & 7)) << 4)); \
        const uint32_t s1 = oxa + ((lane < 16 ? 3072 : 0) >> (ox ? 2 : 0)), s2 = oxa + ((lane < 16 ? 2048 : 1024) >> (ox ? 2 : 0))
      if (dual) {
        uint32_t vf[8], vm[4], vn[8];
        {
          DESC(0);
          float v[24];
          ARM();
          wg_fence(); proj<48, SSV, 0, 30, 40, 30>(v, W, D); wg_commit();
          proj<48, SSV, 0, 0, VD1 - 10, 30>(v, W, D);
          bar_sync(N_SISS, 384);
          proj<48, SSV, 0, VD1 - 10, VD1 - 7, 30>(v, W, D); wg_commit();
          wg_wait<1>(); bar_arrive(N_G3, 160);
          wg_fence(); proj<48, SSV, 0, VD1 - 7, 10, 30>(v, W, D); wg_commit();
          proj<48, SSV, 0, 10, 13, 30>(v, W, D); wg_commit();
          wg_wait<1>(); REL(B_R1, 0);
          wg_fence(); proj<48, SSV, 0, 13, 20, 30>(v, W, D); wg_commit();
          proj<48, SSV, 0, 20, 23, 30>(v, W, D); wg_commit();
          wg_wait<1>(); REL(B_R1, 1);
          wg_fence(); proj<48, SSV, 0, 23, 30, 30>(v, W, D); wg_commit();
          wg_wait<0>(); REL(B_R1, 2);
          bar_arrive(N_VDONE, 160);
          if (warp == 0) TS(14);
#pragma unroll
          for (int j = 4; j < 8; j++) vf[j] = pack2v(v[4 + 2 * j], v[5 + 2 * j]);
          keep4(vf + 4, lane);
          vm[0] = pack2v(v[0], v[1]); vm[1] = pack2v(v[2], v[3]); vm[2] = pack2v(v[20], v[21]); vm[3] = pack2v(v[22], v[23]);
          keep4(vm, lane);
#pragma unroll
          for (int j = 0; j < 4; j++) vf[j] = pack2v(v[4 + 2 * j], v[5 + 2 * j]);
          keep4(vf, lane);
        }
        {
          DESC(1);
          float o[8];
          O_ADDR();
          bar_sync(N_PM, 224);
          wg_fence();
          MM<8>::rs<dlo(OFF_PL + 3584, 128), 0>(o, vl, D.p);
          MM<8>::rs<dlo(OFF_PL + PL_SZ + 3584, 128), 0>(o + 4, vf, D.p);
          MM<8>::rs<dlo(OFF_PL + 3584 + 256, 128), 1>(o, vl + 4, D.p);
          MM<8>::rs<dlo(OFF_PL + PL_SZ + 3584 + 256, 128), 1>(o + 4, vf + 4, D.p);
          MM<8>::rs<dlo(OFF_PL + 3584 + 512, 128), 1>(o, vm, D.p);
          MM<8>::rs<dlo(OFF_PL + PL_SZ + 3584 + 512, 128), 1>(o + 4, vm, D.p);
          wg_commit();
          fence_sched(step);
          const uint4 il = lds128(sb + OFF_INV + (lane & 3) * 16), jf = lds128(sb + OFF_INV + 64 + (lane & 3) * 16);
          const float i0 = rcpf(__uint_as_float(il.x) + __uint_as_float(il.y)), i1 = rcpf(__uint_as_float(il.z) + __uint_as_float(il.w));
          const float j0 = rcpf(__uint_as_float(jf.x) + __uint_as_float(jf.y)), j1 = rcpf(__uint_as_float(jf.z) + __uint_as_float(jf.w));
          { const uint32_t k4[4] = {__float_as_uint(i0), __float_as_uint(i1), __float_as_uint(j0), __float_as_uint(j1)}; keep4(k4, lane | (oa ^ xo)); }
          wg_wait<0>();
          stsm4t(oa, pack2(o[0] * i0, o[1] * i1), pack2(o[2] * i0, o[3] * i1), pack2(o[4] * j0, o[5] * j1), pack2(o[6] * j0, o[7] * j1));
          O_READY(true);
          TOK_L3(IG_V);
        }
        {
          DESC(2);
          float v[16];
          bar_sync(N_TURN, 256);
          mbar_waitu(bar + 8 * B_F2, par ^ 1);
          wg_fence(); proj<32, SSV, 1, 0, 10>(v, W, D); wg_commit();
          mbar_waitu(bar + 8 * (B_F2 + 1), par ^ 1);
          wg_fence(); proj<32, SSV, 1, 10, 14>(v, W, D); wg_commit();
          wg_wait<1>(); REL(B_R2, 0);
          wg_fence(); proj<32, SSV, 1, 14, 20>(v, W, D); wg_commit();
          mbar_waitu(bar + 8 * (B_F2 + 2), par ^ 1);
          wg_fence(); proj<32, SSV, 1, 20, 24>(v, W, D); wg_commit();
          wg_wait<1>(); REL(B_R2, 1);
          wg_fence(); proj<32, SSV, 1, 24, 30>(v, W, D); wg_commit();
          mbar_waitu(bar + 8 * (B_F2 + 3), par ^ 1);
          wg_fence(); proj<32, SSV, 1, 30, 34>(v, W, D); wg_commit();
          wg_wait<1>(); REL(B_R2, 2);
          wg_fence(); proj<32, SSV, 1, 34, 40>(v, W, D); wg_commit();
          wg_wait<0>(); REL(B_R2, 3);
#pragma unroll
          for (int j = 0; j < 8; j++) vn[j] = pack2v(v[2 * j], v[2 * j + 1]);
          keep4(vn, lane); keep4(vn + 4, lane);
          if (warp == 0) TS(18);
        }
        DESC(3);
        uint32_t ow[16];
        bar_sync(N_P, 256);
        fence_async();
#define PV16(i, off, va) { float o[8]; wg_fence(); \
          MM<16>::rs<dlo(OFF_PL + (off), 128), 0>(o, va, D.p); \
          MM<16>::rs<dlo(OFF_PL + (off) + 256, 128), 1>(o, va + 4, D.p); \
          MM<16>::rs<dlo(OFF_PL + (off) + 512, 128), 1>(o, vm, D.p); \
          wg_commit(); wg_wait<0>(); \
          _Pragma("unroll") for (int j = 0; j < 4; j++) ow[4 * (i) + j] = pack2v(o[2 * j], o[2 * j + 1]); \
          keep4(ow + 4 * (i), lane); }
        PV16(0, 0, vl) PV16(1, 1792, vl) PV16(2, PL_SZ, vf) PV16(3, PL_SZ + 1792, vf)
        OX_ADDR();
        bar_sync(N_V, 128);
        stsm4t(s1, ow[0], ow[1], ow[2], ow[3]);
        stsm4t(s2, ow[4], ow[5], ow[6], ow[7]);
        stsm4t(s1 + PL_SZ, ow[8], ow[9], ow[10], ow[11]);
        stsm4t(s2 + PL_SZ, ow[12], ow[13], ow[14], ow[15]);
#pragma unroll
        for (int j = 0; j < 8; j++) vl[j] = vn[j];
      } else {
        uint32_t vm[4], vn[8];
        {
          DESC(4);
          float v[4];
          wg_fence(); proj<8, SSV, 0, 30, 40, 30>(v, W, D); wg_commit();
          proj<8, SSV, 0, 0, VS1, 30>(v, W, D); wg_commit();
          ARM();
          bar_sync(N_SISS, 384);
          wg_wait<1>(); bar_arrive(N_G3, 160);
          wg_fence(); proj<8, SSV, 0, VS1, 30, 30>(v, W, D); wg_commit();
          if (has_next) { mbar_waitu2(bar + 8 * B_F2, bar + 8 * (B_F2 + 1), par ^ 1); mbar_waitu(bar + 8 * (B_F2 + 2), par ^ 1); }
          wg_wait<0>();
          bar_arrive(N_VDONE, 160);
          vm[0] = pack2v(v[0], v[1]); vm[1] = pack2v(v[2], v[3]); vm[2] = pack2v(v[1], v[0]); vm[3] = pack2v(v[3], v[2]);
        }
        DESC(5);
        float v[16];
        {
          wg_fence(); proj<32, SSV, 1, 0, VS2>(v, W, D); wg_commit();
          {
            float o[4];
            O_ADDR();
            bar_sync(N_PM, 192);
            if (warp == 0) TS(14);
            wg_fence();
            MM<8>::rs<dlo(OFF_PL + 3584, 128), 0>(o, vl, D.p);
            MM<8>::rs<dlo(OFF_PL + 3584 + 256, 128), 1>(o, vl + 4, D.p);
            MM<8>::rs<dlo(OFF_PL + 3584 + 512, 128), 1>(o, vm, D.p);
            wg_commit();
            fence_sched(step);
            const uint4 il = lds128(sb + OFF_INV + (lane & 3) * 16);
            const float i0 = rcpf(__uint_as_float(il.x) + __uint_as_float(il.y)), i1 = rcpf(__uint_as_float(il.z) + __uint_as_float(il.w));
            { const uint32_t k4[4] = {__float_as_uint(i0), __float_as_uint(i1), oa, xo}; keep4(k4, lane); }
            wg_wait<0>();
            stsm2t(oa, pack2(o[0] * i0, o[1] * i1), pack2(o[2] * i0, o[3] * i1));
            O_READY(lane < 16);
            TOK_L3(3);
          }
          if (has_next) {
            mbar_arrive_remote_if(lane < VS2 / 10, rb0 + ((nA - 4 + lane) << 24) + OFF_BAR + 8 * B_R2);
            bar_sync(N_TURN, 256);
          }
          if (VS2 < 30) { wg_fence(); proj<32, SSV, 1, VS2, 30>(v, W, D); wg_commit(); }
          if (has_next) mbar_waitu(bar + 8 * (B_F2 + 3), par ^ 1);
          if (VS2 < 30) { wg_wait<0>(); if (has_next) REL(B_R2, 2); }
          wg_fence(); proj<32, SSV, 1, 30, 40>(v, W, D); wg_commit();
          wg_wait<0>();
          if (has_next) REL(B_R2, 3);
#pragma unroll
          for (int j = 0; j < 8; j++) vn[j] = pack2v(v[2 * j], v[2 * j + 1]);
          keep4(vn, lane); keep4(vn + 4, lane);
          if (warp == 0) TS(18);
        }
        float o[16];
        bar_sync(N_P, 256);
        fence_async();
        wg_fence();
        MM<32>::rs<dlo(OFF_PL, 128), 0>(o, vl, D.p);
        MM<32>::rs<dlo(OFF_PL + 256, 128), 1>(o, vl + 4, D.p);
        MM<32>::rs<dlo(OFF_PL + 512, 128), 1>(o, vm, D.p);
        wg_commit();
        OX_ADDR();
        wg_wait<0>();
        bar_sync(N_V, 128);
        stsm4t(s1, pack2(o[0], o[1]), pack2(o[2], o[3]), pack2(o[4], o[5]), pack2(o[6], o[7]));
        stsm4t(s2, pack2(o[8], o[9]), pack2(o[10], o[11]), pack2(o[12], o[13]), pack2(o[14], o[15]));
#pragma unroll
        for (int j = 0; j < 8; j++) vl[j] = vn[j];
      }
      bar_arrive(N_OX, 160);
      if (warp == 0) TS(16);
    }
    cluster_sync_all();
  } else {
    asm volatile("setmaxnreg.dec.sync.aligned.u32 32;");
    if (wg > 3) return;
    LANE_INIT();
    struct RsJob { uint32_t* gp; uint32_t la, mb; int n; };
    auto rs_prep = [&](int step, int s, int c) {
      RsJob j;
      const int u = s * nA + rank;
      j.gp = &g_part[0][0][0][0] + (uint32_t)((((step & 1) * 2 + c) * NCL + cl) * 2560 + u * 64 + (lane >> 2) * 8 + (lane & 3));
      j.la = sb + OFF_TILE + c * LAND_F + LAND(s) + lane * 8;
      j.mb = bar + 8 * (B_RS + s);
      j.n = u >= 40 ? 0 : u >= 36 ? 3 : 1;
      asm volatile("" : "+l"(j.gp), "+r"(j.la));
      return j;
    };
    auto rs_sum = [&](RsJob j, int step) {
      if (j.n) {
        auto five = [&](uint32_t la) {
          uint2 p[5];
#pragma unroll
          for (int i = 0; i < 4; i++) p[i] = lds64(la + i * 256);
          asm volatile("{\n.reg .pred q;\nsetp.eq.s32 q, %3, 5;\nmov.u32 %0, 0;\nmov.u32 %1, 0;\n@q ld.shared.v2.b32 {%0,%1}, [%2];\n}"
                       : "=r"(p[4].x), "=r"(p[4].y) : "r"(la + 1024), "r"(nh) : "memory");
          return make_uint2(hadd2bf(hadd2bf(p[0].x, p[1].x), hadd2bf(hadd2bf(p[2].x, p[3].x), p[4].x)),
                            hadd2bf(hadd2bf(p[0].y, p[1].y), hadd2bf(hadd2bf(p[2].y, p[3].y), p[4].y)));
        };
        const uint32_t tag = ((step >> 1) & 1) ^ 1;
        mbar_waitw(j.mb, step & 1);
        uint2 t = five(j.la);
        if (j.n > 1) {
          const uint2 a = five(j.la + (nh == 5 ? 1280 : TILE_GRP - 1280)), b = five(j.la + TILE_GRP);
          t.x = hadd2bf(t.x, hadd2bf(a.x, b.x)); t.y = hadd2bf(t.y, hadd2bf(a.y, b.y));
        }
        const uint32_t t0 = (movm(t.x) & ~1u) | tag, t1 = (movm(t.y) & ~1u) | tag;
        asm volatile("st.relaxed.gpu.global.b32 [%0], %1;" :: "l"(j.gp), "r"(lane & 16 ? t1 : t0) : "memory");
        asm volatile("st.relaxed.gpu.global.b32 [%0], %1;" :: "l"(j.gp + 4), "r"(lane & 16 ? t0 : t1) : "memory");
      }
    };
    if (warp * nA + (int)rank < 40) {
#pragma unroll
      for (int e = LAG; e < LAG + 2; e++)
        if ((e >> 1) & 1) *reinterpret_cast<uint2*>(&g_part[(e & 1) * 2 + 1][cl][warp * nA + rank][lane * 2]) = make_uint2(1u, 1u);
      __threadfence();
    }
    if (warp == 2 && ig >= 0 && sync_b) wait_cnt(&g_xready[0][0], 32);
    cluster_sync_all();
    if (warp == 2 && ig >= 0) bulk_g2s_mc_e(sb + OFF_TILE + ig * TILE_GRP + TILE_SBO, &g_xn[0][0] + ig * 5120, 10240, bar + 8 * (B_F2 + ig), mcmask);
    bar_sync(N_PI, 128);
#pragma unroll 1
    for (int i = warp; i < 20; i += 4) {
      int c0, c1; wo_coord(i, t3, head, c0, c1);
      if (i >= 2 && i < 15) tma2d_e(sb + OFF_WO + (i - 2) * 4096, &M.wo32, c0, c1, bar + 8 * B_W1);
      else if (lane == 0) tma2d_prefetch(&M.wo32, c0, c1);
      __syncwarp();
    }
#pragma unroll 1
    for (int step = 0; step < NSTEP; step++) {
      const uint32_t par = step & 1;
      asm volatile("" : "+r"(lane));
      const bool dual = is_dual(step), has_next = step + 1 < NSTEP;
      {
        bar_sync(N_PX, dual ? 256 : 192);
        if (dual || warp >= 2) tok_softmax(sb, dual ? warp : warp - 2, lane);
        bar_arrive(N_P, 256);
        asm volatile("" : "+r"(lane));
        if (has_next) {
          if (step + 2 == LAG && lane < 20) asm volatile("prefetch.global.L2 [%0];" :: "l"(mem0 + (warp * 20 + lane) * 64));
          const int nw = ig >= 0 ? 3 : 4, j0 = warp < nw ? warp : 8;
          const int sh = dual ? 1 : 0;
          rs_sum(rs_prep(step, j0 >> sh, j0 & sh), step);
          if (warp == 0) TS(17);
          if (dual) rs_sum(rs_prep(step, (j0 + nw) >> 1, (j0 + nw) & 1), step);
          if (warp == 0) { bar_sync(N_C, 288); }
          mbar_arrive_remote_if(lane < nA, rb0 + (lane << 24) + OFF_BAR + 8 * B_LANDFREE);
          const uint32_t gap = dual ? POLL_GAPD : POLL_GAP;
          if (gap) { const uint32_t t0 = clock32(); while (clock32() - t0 < gap) {} }
#pragma unroll 1
          for (int j = j0; j < (dual ? 8 : 4); j += nw) {
            const int u = (j >> sh) * nA + rank, c = j & sh;
            if (u < UMAX && (c || step + 1 != NSEG)) {
              const uint32_t* gq = &g_part[0][0][0][0] + (uint32_t)((par * 2 + c) * NCL * 2560 + u * 64 + lane * 2);
              uint2 pa[NCL];
              POLL(pa, gq);
              deliver(pa, gq, u, c, step + 1 < NSEG ? c : 0, dual ? DS_DUAL : DS_SINGLE, step, j == 0, lane);
            }
            if (warp == 0 && j == 0) TS(13);
          }
          if (warp >= nw && (is_dual(step + 1) || (ig < 3 && step + 2 < NSTEP))) {
            issue_tok(is_dual(step + 1) ? sched_f(step + 1) : sched_l(step + 2), is_dual(step + 1) ? B_F1 : B_F2, B_R2, par ^ 1);
          }
          if (step + 1 == LAG && UMAX) {
            uint4 v[5];
#pragma unroll
            for (int i = 0; i < 5; i++) { const int t = warp * 160 + i * 32 + lane; v[i] = *reinterpret_cast<const uint4*>(mem0 + ((t >> 1) & 7) * DM + (t >> 4) * 16 + ((t ^ (t >> 3)) & 1) * 8); }
            mbar_waitu(bar + 8 * B_LANDFREE, par);
#pragma unroll
            for (int i = 0; i < 5; i++)
              st_async_v4(sb + OFF_TILE + LAND_F + warp * TILE_GRP + (i * 32 + lane) * 16, v[i].x, v[i].y, v[i].z, v[i].w, bar + 8 * (B_F1 + warp));
          }
        }
      }
      if (warp == (ig >= 0 && !is_dual(step + 1) ? 2 : 3)) {
        unsigned char* o0 = g_o + uni(step % RO * (96 * 8192) + (head * 3 + t3) * (dual ? 8192 : 4096));
        bar_sync(N_OX, 160);
        fence_async();
        bulk_s2g_es(o0, sb + OFF_PL, 4096);
        if (dual) bulk_s2g_es(o0 + 4096, sb + OFF_PL + PL_SZ, 4096);
        asm volatile("cp.async.bulk.commit_group;" ::: "memory");
        asm volatile("cp.async.bulk.wait_group.read 0;" ::: "memory");
        __syncwarp();
        mbar_arrive_remote_if(lane < 2, (lane ? nxt : prv) + OFF_BAR + 8 * B_PLFREE);
        asm volatile("cp.async.bulk.wait_group 0;" ::: "memory");
        asm volatile("fence.proxy.async.global;" ::: "memory");
        __syncwarp();
        if (lane == 0) red_release(&g_f[F_O + (head * 3 + t3) / 5][step], 1u);
        __syncwarp();
      }
    }
    cluster_sync_all();
  }
}

__device__ __forceinline__ float gelu2(float x) {
  const float u = x * fmaf(x * x, 0.7978845608028654f * 0.044715f, 0.7978845608028654f);
  float t; asm("tanh.approx.f32 %0, %1;" : "=f"(t) : "f"(u));
  return fmaf(x, t, x); }

struct BParams {
  CUtensorMap wmap[5];
  CUtensorMap wo16;
  const __nv_bfloat16* x;
  __nv_bfloat16* out;
  uint64_t desc, desc32;
};
#define BO_O 0
#define BO_RES (6 * 8192)
#define OP_RES 63488
#define BO_STG (BO_RES + 2 * OP_RES)
#define BO_RING_OP (BO_STG + 16384)
#define OP_SLOT 12288
#define NS_OP 3
#define BO_H 81920
#define BO_W1 (BO_H + 16384)
#define BO_RING_MLP (BO_W1 + 81920)
#define BO_BAR 229376
#define BO_BOX (BO_BAR + 248)
#define BO_CARRY (BO_BAR + 512)
#define BO_STAT (BO_CARRY + 2048)
#define B_SMEM (BO_STAT + 256)
static_assert(B_SMEM <= 232448 && BO_RING_OP + NS_OP * OP_SLOT == BO_BAR && BO_RING_MLP + 3 * 16384 == BO_BAR && 2 * 83968 <= BO_RING_MLP, "smem");
enum { BB_W = 0, BB_FULL = 2, BB_TMP = BB_FULL + 3, BB_OFULL = BB_FULL + 5, BB_SFREE = BB_OFULL,
       BB_STAT = BB_SFREE + 6, BB_ZFREE, BB_DONE = BB_ZFREE + 3,
       BB_EMPTY, BB_START = BB_EMPTY, BB_USED = BB_EMPTY + 2, BB_NUM = BB_USED + 3 };
enum { NB_PP = 1, NB_H = 3, NB_END = 4, NB_END2 = 5, NB_STAGED = 6, NB_FREE = 8, NB_EARLY = 10, NB_LAST = 11 };

#define DESC_LO(off) (((SMEM0 + (off)) >> 4) | (1u << 16))

__device__ __forceinline__ uint32_t ld_relaxed(const uint32_t* p) { uint32_t v; asm volatile("ld.relaxed.gpu.global.b32 %0, [%1];" : "=r"(v) : "l"(p) : "memory"); return v; }
__device__ __forceinline__ int fmask(int r) { return (r < NSEG) | ((r >= LAG && r < NSTEP) << 1); }
__device__ __forceinline__ int bmask(int r) { return (r <= NSEG) | ((r >= LAG) << 1); }
__device__ __forceinline__ uint32_t rtarget(int mask) { return mask == 3 ? 64 : 32; }
__device__ __forceinline__ void warp_signal(uint32_t* p, int lane) {
  __syncwarp();
  asm volatile("{\n.reg .pred q;\nsetp.eq.u32 q, %1, 0;\n@q red.release.gpu.global.add.u32 [%0], 1;\n}" :: "l"(p), "r"(lane) : "memory");
}
__device__ __forceinline__ uint32_t pack2h(float lo, float hi) { uint32_t r; asm("cvt.rn.f16x2.f32 %0, %1, %2;" : "=r"(r) : "f"(hi), "f"(lo)); return r; }
template <bool H> __device__ __forceinline__ uint32_t pk(float lo, float hi) { return H ? pack2h(lo, hi) : pack2(lo, hi); }
template <int N, bool H> __device__ __forceinline__ void stage_out(const float* d, uint32_t dst, int warp, int lane) {
  const uint32_t sa = dst + ((lane >> 4) * 8 + (lane & 7)) * 128 + (((2 * warp + ((lane >> 3) & 1)) ^ (lane & 7)) << 4);
#pragma unroll
  for (int m = 0; m < N / 16; m++)
    stsm4t(sa + m * 2048, pk<H>(d[8 * m], d[8 * m + 1]), pk<H>(d[8 * m + 2], d[8 * m + 3]), pk<H>(d[8 * m + 4], d[8 * m + 5]), pk<H>(d[8 * m + 6], d[8 * m + 7]));
}
template <int N> __device__ __forceinline__ void acc_live(float* d) {
#pragma unroll
  for (int i = 0; i < N / 2; i++) asm volatile("" : "+f"(d[i]) :: "memory");
}
struct Ring {
  uint32_t sl, ph;
  template <int NS> __device__ __forceinline__ void step() { if (++sl == NS) { sl = 0; ph ^= 1; } }
};

#define KOFF(x) (DESC_LO(BO_O) + ((x) >> 2) * 512 + ((x) & 3) * 2)
template <int N, int P>
__device__ __forceinline__ void op_pass(const uint32_t* W, uint32_t bar, Dsc alo, Dsc blo, Dsc xlo, bool x2, Ring& rg, int wg, int warp, int lane, int r) {
  float acc[N / 2];
  blo.e = xlo.e = fresh<P + N / 64 * 5>(r);
  const Dsc tlo = blo + uni(rg.sl) * (OP_SLOT / 16), b2 = blo + (r & 1) * 1536;
  if (P == 0) mbar_waitu(bar + 8 * (BB_OFULL + 2 + (r & 1)), (r >> 1) & 1);
  CTS(5 * P);
  bar_sync(NB_PP + wg, 256);
  wg_fence();
#define OP_R(x, b) MM<N>::template rs<KOFF(4 * (x >> 1) + (x & 1)), (x != (P ? 0 : 4))>(acc, W + 32 * P + 4 * x, b);
#define OP_S(x, b) MM<N>::template ss<DESC_LO(BO_RES) + (6 * P + x) * 128, KOFF(4 * (x >> 1) + 2 + (x & 1)), 1>(acc, alo, b);
#define OP_T(x) MM<N>::template ss<DESC_LO(BO_RING_OP) + x * 128, KOFF(14 + x), 1>(acc, tlo, blo);
#define OP_B2() OP_R(4, b2) OP_S(4, b2) OP_R(5, b2) OP_S(5, b2)
  if (P == 0) { OP_B2() mbar_waitu(bar + 8 * BB_OFULL, r & 1); }
  OP_R(0, blo) OP_S(0, blo) OP_R(1, blo) OP_S(1, blo) OP_R(2, blo) OP_S(2, blo) OP_R(3, blo) OP_S(3, blo)
  if (P == 0) mbar_waitu(bar + 8 * (BB_OFULL + 1), r & 1);
  if (P == 4) wg_commit();
  if (P & 3) { OP_B2() }
  if (P == 1 && x2) MM<N>::template ss<DESC_LO(BO_RES) + 30 * 128, DESC_LO(BO_CARRY), 1>(acc, alo, xlo);
  mbar_waitu(bar + 8 * (BB_FULL + rg.sl), rg.ph);
  OP_R(6, blo) OP_T(0) OP_R(7, blo) OP_T(1)
  if (P == 4) { wg_commit(); wg_wait<1>(); bar_arrive(NB_EARLY, 288); CTS(21); wg_fence(); }
  OP_T(2) OP_T(3)
  if (P == 0) MM<N>::template rs<DESC_LO(BO_CARRY), 1>(acc, W + 160, xlo);
  OP_T(4) OP_T(5)
  if (P == 4) { wg_commit(); OP_B2() }
  wg_commit();
  bar_arrive(NB_PP + 1 - wg, 256);
  CTS(5 * P + 2);
  if (P == 4) { wg_wait<1>(); bar_arrive(NB_LAST, 288); }
  bar_sync(NB_FREE + wg, 160);
  wg_wait<0>();
  acc_live<N>(acc);
  mbar_arrive_if(lane == 0, bar + 8 * (BB_USED + rg.sl));
  CTS(5 * P + 3);
  stage_out<N, false>(acc, SMEM0 + BO_STG + wg * 8192, warp, lane);
  bar_arrive(NB_STAGED + wg, 160);
  CTS(5 * P + 4);
  rg.step<NS_OP>(); rg.step<NS_OP>();
}
template <int N>
__device__ __forceinline__ void op_round(const uint32_t* W, uint32_t bar, Dsc alo, Dsc blo, Dsc xlo, bool x2, Ring& rg, int wg, int warp, int lane, int r) {
  op_pass<N, 0>(W, bar, alo, blo, xlo, x2, rg, wg, warp, lane, r);
  op_pass<N, 1>(W, bar, alo, blo, xlo, x2, rg, wg, warp, lane, r);
  op_pass<N, 2>(W, bar, alo, blo, xlo, x2, rg, wg, warp, lane, r);
  op_pass<N, 3>(W, bar, alo, blo, xlo, x2, rg, wg, warp, lane, r);
  op_pass<N, 4>(W, bar, alo, blo, xlo, x2, rg, wg, warp, lane, r);
}
__device__ __forceinline__ void carry_in(uint32_t sb, int wg, int warp, int lane) {
  const int row = (lane >> 1) & 3;
  if (lane < 16) {
    const uint4 v = lds128(sb + BO_CARRY + (wg * 4 + warp) * 256 + lane * 16);
    sts128(sb + BO_H + wg * 8192 + (lane >> 3) * 4096 + row * 128 + (((2 * warp + (lane & 1)) ^ row) << 4), v.x, v.y, v.z, v.w);
  }
  __syncwarp();
}
template <int N, int Z>
__device__ __forceinline__ void p1_pair(float* acc, const uint32_t* W, uint32_t bar, Dsc alo, Dsc blo, int lane, int r) {
  constexpr int ZOFF = N == 64 ? (2 * Z % 3) * 1024 : (Z / 2 * 2 % 3) * 1024 + (Z & 1) * 256;
  blo.e = fresh<10 + Z / 3 + N / 64 * 2>(r);
  mbar_waitu(bar + 8 * (BB_FULL + Z), r & 1);
  CTS(40 + Z);
  wg_fence();
#define P1_B(k) \
  MM<N, true>::template rs<DESC_LO(BO_RING_MLP) + ZOFF + k * 512, (2 * Z + k != 0)>(acc, W + 16 * Z + 8 * k, blo); \
  MM<N, true>::template ss<DESC_LO(BO_W1) + (2 * Z + k) * 512, DESC_LO(BO_RING_MLP) + ZOFF + k * 512 + 4, 1>(acc, alo, blo); \
  MM<N, true>::template rs<DESC_LO(BO_RING_MLP) + ZOFF + k * 512 + 2, 1>(acc, W + 16 * Z + 8 * k + 4, blo); \
  MM<N, true>::template ss<DESC_LO(BO_W1) + (2 * Z + k) * 512 + 128, DESC_LO(BO_RING_MLP) + ZOFF + k * 512 + 6, 1>(acc, alo, blo);
  P1_B(0)
  if (N == 64 && (Z == 1 || Z == 2)) { wg_commit(); wg_wait<1>(); mbar_arrive_if(lane == 0, bar + 8 * (BB_EMPTY + Z - 1)); wg_fence(); }
  P1_B(1)
  wg_commit();
}
template <int N>
__device__ __forceinline__ void phase1(const uint32_t* W, uint32_t sb, Dsc alo, Dsc blo, int half, int wg, int warp, int lane, int off, int r) {
  float acc[N / 2];
  const uint32_t bar = sb + BO_BAR;
  CTS(30);
  p1_pair<N, 0>(acc, W, bar, alo, blo, lane, r);
  p1_pair<N, 1>(acc, W, bar, alo, blo, lane, r);
  p1_pair<N, 2>(acc, W, bar, alo, blo, lane, r);
  if (N == 32) p1_pair<N, 3>(acc, W, bar, alo, blo, lane, r);
  mbar_waitu(bar + 8 * (BB_SFREE + 4 + wg), (r + 1) & 1);
  carry_in(sb, wg, warp, lane);
  if (N == 32) mbar_arrive_if(lane < 2, bar + 8 * (BB_EMPTY + lane));
  else p1_pair<N, 3>(acc, W, bar, alo, blo, lane, r);
  p1_pair<N, 4>(acc, W, bar, alo, blo, lane, r);
  const int c = (lane >> 3) & 1, i0 = (lane >> 4) * 8 + (lane & 7) + off;
  uint32_t a0 = sb + BO_H + wg * 8192 + half * 4096 + i0 * 128 + (((2 * warp + c) ^ (i0 & 7)) << 4);
  uint32_t a1 = i0 >= 16 ? sb + BO_CARRY + (wg * 4 + warp) * 256 + half * 128 + (i0 - 16) * 32 + c * 16 : a0 + 2048, a3 = a1 + (i0 >= 16 ? 128 : 4096);
  asm volatile("" : "+r"(a0), "+r"(a1), "+r"(a3));
  mbar_waitu(bar + 8 * BB_STAT, r & 1);
  const uint32_t sa = sb + BO_STAT + half * 128 + (lane & 3) * 32;
  uint4 t[2] = {lds128(sa), lds128(sa + 16)};
  wg_wait<0>();
  acc_live<N>(acc);
  CTS(32);
#pragma unroll
  for (int m = 0; m < N / 16; m++) {
    const float s0 = __uint_as_float(t[m & 1].x), s1 = __uint_as_float(t[m & 1].y), s2 = __uint_as_float(t[m & 1].z), s3 = __uint_as_float(t[m & 1].w);
    float* d = acc + 8 * m;
    d[0] *= s0; d[1] *= s1; d[2] *= s0; d[3] *= s1; d[4] *= s2; d[5] *= s3; d[6] *= s2; d[7] *= s3;
    if (m + 2 < N / 16) t[m & 1] = lds128(sa + 128 + m * 16);
#pragma unroll
    for (int j = 0; j < 8; j++) d[j] = gelu2(d[j]);
  }
#pragma unroll
  for (int m = 0; m < N / 16; m++)
    stsm4t(m == 1 ? a1 : m == 3 ? a3 : a0 + m * 2048, pack2(acc[8 * m], acc[8 * m + 1]), pack2(acc[8 * m + 2], acc[8 * m + 3]), pack2(acc[8 * m + 4], acc[8 * m + 5]), pack2(acc[8 * m + 6], acc[8 * m + 7]));
}
template <int N, int P>
__device__ __forceinline__ void p2_mma(float* acc, const uint32_t* W, Dsc alo, Dsc blo, int r) {
  blo.e = fresh<P + N / 64 * 5>(r);
  MM<N>::template rs<DESC_LO(BO_H), 0>(acc, W + 80 + 16 * P, blo);     MM<N>::template ss<DESC_LO(0) + P * 1024, DESC_LO(BO_H) + 512, 1>(acc, alo, blo);
  MM<N>::template rs<DESC_LO(BO_H) + 2, 1>(acc, W + 84 + 16 * P, blo); MM<N>::template ss<DESC_LO(0) + P * 1024 + 128, DESC_LO(BO_H) + 514, 1>(acc, alo, blo);
  MM<N>::template rs<DESC_LO(BO_H) + 4, 1>(acc, W + 88 + 16 * P, blo); MM<N>::template ss<DESC_LO(0) + P * 1024 + 512, DESC_LO(BO_H) + 516, 1>(acc, alo, blo);
  MM<N>::template rs<DESC_LO(BO_H) + 6, 1>(acc, W + 92 + 16 * P, blo); MM<N>::template ss<DESC_LO(0) + P * 1024 + 640, DESC_LO(BO_H) + 518, 1>(acc, alo, blo);
}
template <int N, int P, int T>
__device__ __forceinline__ void p2_pass(const uint32_t* W, uint32_t bar, Dsc alo, Dsc blo, int wg, int warp, int lane, int r) {
  float acc[N / 2], ac2[N / 2];
  CTS(5 * P);
  if (P || wg) bar_sync(NB_PP + wg, 256);
  wg_fence();
  p2_mma<N, P>(acc, W, alo, blo, r);
  wg_commit();
  if constexpr (T == 2) { p2_mma<N, P + 1>(ac2, W, alo, blo, r); wg_commit(); }
  if (P < 4 || !wg) bar_arrive(NB_PP + 1 - wg, 256);
  CTS(5 * P + 2);
  if (T == 1 && (P == 2 || P == 3)) mbar_waitu(bar + 8 * (BB_SFREE + 2 * (P - 2) + wg), r & 1);
  wg_wait<T - 1>();
  acc_live<N>(acc);
  if (P == 4) bar_sync(NB_H, 256);
  CTS(5 * P + 3);
  constexpr int K = P / T & 1;
  stage_out<N, true>(acc, SMEM0 + (P == 4 ? BO_H : BO_RING_MLP + (2 - K) * 16384) + wg * 8192, warp, lane);
  if constexpr (T == 2) {
    wg_wait<0>();
    acc_live<N>(ac2);
    stage_out<N, true>(ac2, SMEM0 + BO_RING_MLP + (2 - K) * 16384 + wg * 8192 + 4096, warp, lane);
  }
  bar_arrive(NB_STAGED + (P == 4 ? 4 : 2 * K) + wg, 160);
  CTS(5 * P + 4);
}
template <int N>
__device__ __forceinline__ void phase2(const uint32_t* W, uint32_t bar, Dsc alo, Dsc blo, int wg, int warp, int lane, int r) {
  if constexpr (N == 64) {
    p2_pass<N, 0, 1>(W, bar, alo, blo, wg, warp, lane, r);
    p2_pass<N, 1, 1>(W, bar, alo, blo, wg, warp, lane, r);
    p2_pass<N, 2, 1>(W, bar, alo, blo, wg, warp, lane, r);
    p2_pass<N, 3, 1>(W, bar, alo, blo, wg, warp, lane, r);
  } else {
    p2_pass<N, 0, 2>(W, bar, alo, blo, wg, warp, lane, r);
    p2_pass<N, 2, 2>(W, bar, alo, blo, wg, warp, lane, r);
  }
  p2_pass<N, 4, 1>(W, bar, alo, blo, wg, warp, lane, r);
}

__device__ __forceinline__ void ldg4(uint32_t* v, const void* p) {
  asm volatile("ld.relaxed.gpu.global.v4.u32 {%0,%1,%2,%3}, [%4];" : "=r"(v[0]), "=r"(v[1]), "=r"(v[2]), "=r"(v[3]) : "l"(p) : "memory"); }
__device__ __forceinline__ void stg4(void* p, const uint32_t* v) {
  asm volatile("st.global.v4.u32 [%0], {%1,%2,%3,%4};" :: "l"(p), "r"(v[0]), "r"(v[1]), "r"(v[2]), "r"(v[3]) : "memory"); }
struct RowPtr {
  unsigned char *p, *q, *t;
  __device__ __forceinline__ void ld(uint32_t* v, int o) const {
    ldg4(v, p + o); ldg4(v + 4, q + o);
    asm volatile("ld.relaxed.gpu.global.v2.u32 {%0,%1}, [%2];" : "=r"(v[8]), "=r"(v[9]) : "l"(t + o) : "memory");
  }
  __device__ __forceinline__ void st(const uint32_t* w, int o) const {
    stg4(p + o, w); stg4(q + o, w + 4);
    asm volatile("st.global.v2.u32 [%0], {%1,%2};" :: "l"(t + o), "r"(w[8]), "r"(w[9]) : "memory");
  }
};
__device__ __forceinline__ RowPtr row_img(int r, int n, int lane) {
  unsigned char* b = &g_acc[0][r % RD][n * 128];
  unsigned char* p = b + (uint32_t)((lane >> 3) * 8192 + (((lane ^ n) & 7) << 4));
  return {p, p + 32768, b + (uint32_t)(65536 + (lane >> 4) * 8192 + ((((lane >> 1) ^ n) & 7) << 4) + (lane & 1) * 8)};
}
__device__ __forceinline__ RowPtr row_ext(const void* lin, bool xn, int layer, int tok, int lane) {
  unsigned char* b = xn ? reinterpret_cast<unsigned char*>(&g_xn[layer][0]) + (uint32_t)((tok >> 5) * 40960 + ((tok >> 3) & 3) * 2560 + (tok & 7) * 32)
                        : (unsigned char*)lin + (uint32_t)(tok * 1280);
  const uint32_t o = (lane >> 1) * 256 + ((lane ^ (tok >> 2)) & 1) * 16;
  return {b + (uint32_t)(xn ? o + (lane >= 20 ? 7680 : 0) : lane * 16),
          b + (uint32_t)(xn ? o + 4096 + 7680 + (lane >= 8 ? 7680 : 0) + (lane >= 28 ? 7680 : 0) : lane * 16 + 512),
          b + (uint32_t)(xn ? (lane >> 2) * 256 + ((lane & 3) ^ ((tok >> 1) & 2)) * 8 + 8192 + 3 * 7680 : lane * 8 + 1024)};
}
__device__ __forceinline__ float2 h2f(uint32_t w) {
  float2 f; asm("{\n.reg .f16 l, h;\nmov.b32 {l, h}, %2;\ncvt.f32.f16 %0, l;\ncvt.f32.f16 %1, h;\n}" : "=f"(f.x), "=f"(f.y) : "r"(w)); return f; }
__device__ __forceinline__ float rsq(float x) { float y; asm("rsqrt.approx.ftz.f32 %0, %1;" : "=f"(y) : "f"(x)); return y; }
__device__ __forceinline__ void red_if(uint32_t v, const void* a) {
  asm volatile("{\n.reg .pred q;\nsetp.ne.u32 q, %1, 0;\n@q red.relaxed.gpu.global.add.u32 [%0], %1;\n}" :: "l"(a), "r"(v) : "memory"); }
__device__ __forceinline__ uint32_t dep0(uint32_t w, int lane) { uint32_t z; asm volatile("shr.b32 %0, %1, %2;" : "=r"(z) : "r"(w), "r"(lane + 32)); return z; }
__device__ __forceinline__ int lane_of(uint32_t w) {
  int lane; asm volatile("{\n.reg .u32 t;\nmov.u32 t, %%laneid;\nshr.u32 %0, %1, 20;\nadd.u32 %0, %0, t;\n}" : "=r"(lane) : "r"(w)); return lane; }
#define BUF (RD * TILE_B)
__device__ __forceinline__ int await(uint32_t v, const uint32_t* p, uint32_t target, bool lazy) {
  int n = 0;
  while (!__all_sync(~0u, v >= target)) {
    if (lazy) __nanosleep(200);
    if (++n > SPIN_LIMIT) FAIL();
    v = ld_relaxed(p);
  }
  asm volatile("fence.acquire.gpu;" ::: "memory");
  return lane_of(v);
}
template <int W> __device__ __forceinline__ void sum2(float& s, float& q, int lane) {
  const bool up = lane & (W / 2);
  float e = (up ? q : s) + __shfl_xor_sync(~0u, up ? s : q, W / 2);
#pragma unroll
  for (int o = W / 4; o; o >>= 1) e += __shfl_xor_sync(~0u, e, o);
  const float f = __shfl_xor_sync(~0u, e, W / 2);
  s = up ? f : e; q = up ? e : f;
}
template <int TYPE>
__device__ __forceinline__ void rrow(int r, int row, int tok, int lane, const uint32_t* go, int role, const __nv_bfloat16* x, __nv_bfloat16* out) {
  const int half = TYPE == 3 ? 0 : row >> 5;
  float v[20];
  float2 st = make_float2(1.f, 0.f);
  {
    uint32_t a[10], c[10], u[10], sh = 16;
    if (TYPE == 2) row_img(r + RD - ((row & 31) < 2), (row & 32) + ((row - 2) & 31), lane).ld(u, 4 * BUF);
    else row_ext(x, half, 1, tok, lane).ld(u, 0);
    if (TYPE == 2 || (TYPE == 0 && half))
      asm volatile("ld.relaxed.gpu.global.v2.f32 {%0,%1}, [%2];" : "=f"(st.x), "=f"(st.y) : "l"(g_stat + tok) : "memory");
    RowPtr ap = row_img(r, row, lane);
    const uint32_t g0 = TYPE != 3 ? ld_relaxed(go) : 0;
    if (TYPE == 2) {
      ap.ld(c, 2 * BUF);
      uint32_t z = dep0(c[9], lane);
#pragma unroll
      for (int i = 0; i < 10; i++) {
        const float2 g = h2f(u[i] | z), h = h2f(c[i] | z);
        v[2 * i] = fmaf(h.x, 0.5f, g.x * st.x); v[2 * i + 1] = fmaf(h.y, 0.5f, g.y * st.x);
        if (i & 1) z = dep0(__float_as_uint(v[2 * i]) | __float_as_uint(v[2 * i + 1]), lane);
      }
    }
    if (TYPE != 3) {
      asm volatile("" : "+l"(ap.p), "+l"(ap.t));
      ap.q = ap.p + 32768;
      lane = await(g0, go, NOP * NW12 * NW34, false); BTS2(r, 8 + 2 * TYPE); RTS(0);
      ap.ld(a, TYPE ? 3 * BUF : 0);
    }
    if (TYPE == 0) {
      ap.ld(c, BUF);
      const uint32_t one = 0x3f803f80u | dep0(c[9], lane);
#pragma unroll
      for (int i = 0; i < 10; i++) asm volatile("fma.rn.bf16x2 %0, %0, %1, %2;" : "+r"(a[i]) : "r"(one), "r"(c[i]));
      sh |= dep0(a[9], lane);
    }
    const float k = TYPE == 2 ? __uint_as_float(0x3f000000u | dep0(a[9], lane)) : 0.f;
#pragma unroll
    for (int i = 0; i < 10; i++) {
      if (TYPE == 2) { const float2 h = h2f(a[i]); v[2 * i] = fmaf(h.x, k, v[2 * i]); v[2 * i + 1] = fmaf(h.y, k, v[2 * i + 1]); continue; }
      float p = __uint_as_float(u[i] << sh), q = __uint_as_float(u[i] & (0xffffu << sh));
      if (TYPE == 0) { p = fmaf(p, st.x, bf_lo(a[i])); q = fmaf(q, st.x, bf_hi(a[i])); }
      v[2 * i] = p; v[2 * i + 1] = q;
    }
  }
  RTSD(1, v[19]);
  float s = 0.f, q = 0.f;
#pragma unroll
  for (int i = 0; i < 5; i++) {
    s += (v[4 * i] + v[4 * i + 1]) + (v[4 * i + 2] + v[4 * i + 3]);
    q += fmaf(v[4 * i], v[4 * i], v[4 * i + 1] * v[4 * i + 1]) + fmaf(v[4 * i + 2], v[4 * i + 2], v[4 * i + 3] * v[4 * i + 3]);
  }
  if (!(TYPE == 2 && half)) sum2<32>(s, q, lane);
  const float mean = s * (1.f / DM), var = fmaxf(q * (1.f / DM) - mean * mean, 0.f), rs = rsq(var + 1e-5f);
  const float k = TYPE == 0 ? 2.f * rs : half ? 1.f : rs, mr = TYPE && half ? st.y : -mean * k;
  RTSD(2, rs);
  uint32_t w[10];
#pragma unroll
  for (int i = 0; i < 10; i++) w[i] = pk<TYPE == 0>(fmaf(v[2 * i], k, mr), fmaf(v[2 * i + 1], k, mr));
  if (TYPE) row_ext(out, !half, TYPE == 2, tok, lane).st(w, 0);
  else {
    row_img(r, row, lane).st(w, 4 * BUF);
    row_img(r + ((row & 31) >= 30), (row & 32) + ((row + 2) & 31), lane).st(w, 2 * BUF);
    if (lane == 1) g_st2[0][r % RD][row] = (__float_as_uint(0.5f * rsq(fmaf(var * rs, rs, 1e-5f))) & ~127u) | (r + 1);
  }
  if (TYPE != 3 && lane == 0) g_stat[tok] = make_float2((var + 1e-5f) * rs * (TYPE ? 1.f : 0.5f), mean + st.y);
}
__device__ __forceinline__ void r2rows(int r, int row, int lane) {
  const int n = row + (lane >> 4);
  const unsigned char* ap = &g_acc[2][r % RD][0] + (uint32_t)(n * 128 + ((lane >> 3) & 1) * 8192 + (((lane ^ n) & 7) << 4));
  uint32_t a[20];
#pragma unroll
  for (int i = 0; i < 5; i++) ldg4(a + 4 * i, ap + i * 16384);
  const uint32_t z = dep0(a[19], lane);
  float s = 0.f, q = 0.f, q2 = 0.f;
#pragma unroll
  for (int i = 0; i < 20; i++) { const float2 h = h2f(a[i] | z); s += h.x + h.y; q = fmaf(h.x, h.x, q); q2 = fmaf(h.y, h.y, q2); }
  q += q2;
  sum2<16>(s, q, lane);
  const float mean = s * (0.5f / DM), rs = rsq(fmaxf(q * (0.25f / DM) - mean * mean, 0.f) + 1e-5f);
  if ((lane & 15) == 0) asm volatile("st.relaxed.gpu.global.u32 [%0], %1;" :: "l"(&g_st2[1][r % RD][n]), "r"((__float_as_uint(0.5f * rs) & ~127u) | (r + 1)) : "memory");
}
__device__ __forceinline__ void r3rows(int r, int row, int tok, int lane, __nv_bfloat16* out) {
  const int n = row + (lane >> 4), m = 32 + ((n - 2) & 31);
  const unsigned char* ap = &g_acc[0][r % RD][0] + (uint32_t)(n * 128 + ((lane >> 3) & 1) * 8192 + (((lane ^ n) & 7) << 4));
  const unsigned char* zp = &g_acc[4][(r + RD - (row == 32)) % RD][0] + (uint32_t)(m * 128 + ((lane >> 3) & 1) * 8192 + (((lane ^ m) & 7) << 4));
  unsigned char* op = reinterpret_cast<unsigned char*>(out) + (uint32_t)((tok + (lane >> 4)) * 1280 + (lane & 15) * 16);
  float2 st;
  asm volatile("ld.relaxed.gpu.global.v2.f32 {%0,%1}, [%2];" : "=f"(st.x), "=f"(st.y) : "l"(g_stat + tok + (lane >> 4)) : "memory");
#pragma unroll 1
  for (int i0 = 0; i0 < 3; i0++) {
    uint32_t a[8], c[8], u[8];
#pragma unroll
    for (int i = 0; i < 2; i++) { ldg4(a + 4 * i, ap + 3 * BUF + i * 16384); ldg4(c + 4 * i, ap + 2 * BUF + i * 16384); ldg4(u + 4 * i, zp + i * 16384); }
    uint32_t z = dep0(u[7], lane);
#pragma unroll
    for (int i = 0; i < 8; i++) {
      const float2 h = h2f(a[i] | z), e = h2f(c[i] | z), g = h2f(u[i] | z);
      a[i] = pack2(fmaf(h.x + e.x, 0.5f, fmaf(g.x, st.x, st.y)), fmaf(h.y + e.y, 0.5f, fmaf(g.y, st.x, st.y)));
      if (i & 1) z = dep0(a[i], lane);
    }
    if (i0 < 2) stg4(op, a);
    stg4(op + 256, a + 4);
    ap += 32768 >> i0; zp += 32768 >> i0; op += 512 >> i0;
  }
}
template <int TYPE>
__device__ __forceinline__ void rloop(int row, int cp, int role, const __nv_bfloat16* x, __nv_bfloat16* out) {
  constexpr int ST = TYPE == 4 ? 2 : TYPE;
  const int r0 = row & 32 ? LAG : 0;
  uint32_t v = 0;
  static_assert(NSEG + RD - 1 >= NSTEP, "no signals");
#pragma unroll 1
  for (int r = r0; r < (TYPE == 2 ? NR : TYPE == 4 ? NSEG + 1 : r0 + NSEG + (TYPE > 0)); r++) {
    if (TYPE == 2 && r == NSEG + 1) row += 32;
    const int tok = (r - (row & 32 ? LAG : 0)) * 32 + (row & 31) - (TYPE ? 2 : 0);
    const bool valid = TYPE == 0 || (unsigned)tok < S_LEN;
    const uint32_t* go = &g_f[F_R1 + 4 * ST + cp][r];
    const uint32_t* first = TYPE == 2 ? &g_f[F_R2 + cp][r] : TYPE ? go : (const uint32_t*)&g_xready[NSEG + r - r0][0];
    if constexpr (TYPE == 1 || TYPE == 4) {
      const int lane = await(v, go, NOP * NW12 * NW34, false);
      BTS2(r, 8 + 2 * ST); RTS(0);
      if (TYPE == 1) { r2rows(r, row, lane); BTS2(r, 11); continue; }
      if (valid) r3rows(r, row, tok, lane, out);
    } else {
      if (TYPE || row >= 32) await(v, first, TYPE ? NOP * NW12 * NW34 : 32, true);
      if (valid) rrow<TYPE>(r, row, tok, lane_of(r), go, role, x, out);
    }
    if (TYPE > 1 && row >= 32 && r + RD - 2 >= NSTEP) { v = 0; BTS2(r, 13); continue; }
    const int lane = lane_of(r);
    const void* f = lane ? (const void*)&g_xready[NSEG + (tok >> 5)][0] : (const void*)&g_f[TYPE ? F_DONE : F_Z][r];
    asm volatile("" : "+l"(f));
    __syncwarp();
    RTS(3);
    v = ld_relaxed(first + (TYPE ? 1 : 8));
    asm volatile("fence.release.gpu;" ::: "memory");
    RTS(4);
    red_if(lane == 0 || (TYPE == 2 && lane == 1 && valid) ? (TYPE & 5 ? 2 : 1) : 0, f);
    RTS(5);
    RTS_OUT();
    BTS2(r, 9 + 2 * ST);
  }
}

#define RCV 1
#define SINGLE_OP 3
#define SINGLE_W 0
#define W_DELAY 0
#define BULK_ADD(T, dst, src, len) asm volatile("{\n.reg .pred e;\nelect.sync _|e, 0xffffffff;\n@e cp.reduce.async.bulk.global.shared::cta.bulk_group.add.noftz." T " [%0], [%1], %2;\n}" \
                                               :: "l"(dst), "r"(src), "r"(len) : "memory")
#define COMMIT() asm volatile("cp.async.bulk.commit_group;" ::: "memory")
#define DRAINED(n) do { asm volatile("cp.async.bulk.wait_group.read " #n ";" ::: "memory"); __syncwarp(); } while (0)
#define WRITTEN() do { asm volatile("cp.async.bulk.wait_group 0;\nfence.proxy.async.global;" ::: "memory"); __syncwarp(); } while (0)
__device__ __forceinline__ void wait_flags(const uint32_t* p, uint32_t target) {
  int n = 0;
  while (!__all_sync(~0u, ld_relaxed(p) >= target)) { if (++n > SPIN_LIMIT) FAIL(); }
  asm volatile("fence.acquire.gpu;" ::: "memory");
  asm volatile("fence.proxy.async.global;" ::: "memory");
}
__global__ void __launch_bounds__(512, 1) bworker_kernel(const __grid_constant__ BParams P) {
  extern __shared__ __align__(1024) unsigned char smem_raw[];
  const uint32_t sb = SMEM0, bar = sb + BO_BAR;
  const int wg = __shfl_sync(~0u, threadIdx.x >> 7, 0), warp = __shfl_sync(~0u, (threadIdx.x >> 5) & 3, 0);
  if (threadIdx.x == 0) {
    if (smem_u32(smem_raw) != SMEM0) FAIL();
    uint32_t smid; asm volatile("mov.u32 %0, %%smid;" : "=r"(smid));
    const uint32_t nb = ld_relaxed(&g_tpc[(smid >> 1) & 127]);
    const bool single = nb > 1, far = nb == 0 && (smid < 64 || smid >= 124);
    int kind = far || (single && atomicAdd(&g_f[F_MISC][35], 1u) < SINGLE_OP) ? 0 : single ? 1 + SINGLE_W : 1;
    int rc = (RCV ? smid >= 128 : single) || (smid >> 1) == 16 || (smid >> 1) == 63 ? 1 : far || single ? 2 : 0;
    uint32_t i = atomicAdd(&g_f[F_MISC][32 + kind], 1u), o = atomicAdd(&g_f[F_MISC][36 + rc], 1u);
    while (i >= (kind == 0 ? NOP : kind == 1 ? NW12 : NW34)) { kind = (kind + 1) % 3; i = atomicAdd(&g_f[F_MISC][32 + kind], 1u); }
    while (o >= (rc == 0 ? 16 : rc == 1 ? 8 : 12)) { rc = (rc + 1) % 3; o = atomicAdd(&g_f[F_MISC][36 + rc], 1u); }
    if (RCV && rc == 2) o = single ? 11 - atomicAdd(&g_f[F_MISC][40], 1u) : atomicAdd(&g_f[F_MISC][41], 1u);
    sts64(sb + BO_BOX, i + (kind == 0 ? 0 : kind == 1 ? NOP : NOP + NW12), o + (rc ? 8 + 8 * rc : 0));
    for (int k = 0; k < BB_NUM; k++) mbar_init(bar + 8 * k, k >= BB_USED ? 4 : k >= BB_EMPTY ? 8 : k >= BB_ZFREE && kind ? 2 : 1);
    asm volatile("fence.mbarrier_init.release.cluster;" ::: "memory");
  }
  if (threadIdx.x < 128) sts128(sb + BO_CARRY + threadIdx.x * 16, 0u, 0u, 0u, 0u);
  auto ln0 = [&](int t) {
    const int lane = lane_of(t);
    if (lane < 20 && t + 128 < S_LEN) asm volatile("prefetch.global.L2 [%0];" :: "l"(P.x + (t + (t < 4 * NBC ? 4 * NBC : 128)) * DM + (lane >> 1) * 64));
    rrow<3>(0, 0, t, lane, nullptr, 0, P.x, nullptr);
    __syncwarp();
    asm volatile("fence.release.gpu;" ::: "memory");
    red_if(lane == 0, &g_xready[t >> 5][0]);
  };
  if (wg == 2) ln0(blockIdx.x * 4 + warp);
  fence_async();
  __syncthreads();
  const int role = uni(lds32(sb + BO_BOX));
  if (threadIdx.x < 32) BTS(94, 1);
  const bool op = role < NOP, w12 = role < NOP + NW12;
  const int j = op ? role : w12 ? role - NOP : role - NOP - NW12;
  const int rot = op ? (j ? 2 * ((j + 1) % 5) : 0) : 2 * (j % 5);
  if (wg == 3) {
    asm volatile("setmaxnreg.dec.sync.aligned.u32 24;");
    LANE_INIT();
    if (warp < 2) {
      auto announce = [&](int r) {
        const uint32_t* f = &g_f[(op ? F_R1 : w12 ? F_R2 : F_R3) + (lane & 3)][r];
        asm volatile("" : "+l"(f));
        if (warp == 0) { mbar_arrive_if(lane == 0, bar + 8 * BB_DONE); return; }
        mbar_waitw(bar + 8 * BB_DONE, r & 1);
        PTS(60);
        asm volatile("fence.release.gpu;" ::: "memory");
        red_if(lane >= 4 ? 0 : op ? NW12 * NW34 : w12 ? NOP * NW34 : NOP * NW12, f);
        PTS(61);
        BTS(r, 4);
      };
      if (op) {
        int mt = rot + warp;
        bar_arrive(NB_FREE + warp, 160);
#pragma unroll 1
        for (int r = 0; r < NSTEP; r++) {
          const uint32_t len = fmask(r) == 3 ? 8192 : 4096;
          unsigned char* acc = &g_acc[j & 1][r % RD][fmask(r) == 2 ? 4096 : 0];
#pragma unroll 1
          for (int p = 0; p < 5; p++) {
            bar_sync(NB_STAGED + warp, 160);
            PTS(50 + 2 * p + warp);
            fence_async();
            BULK_ADD("bf16", acc + mt * 8192, sb + BO_STG + warp * 8192, len);
            COMMIT();
            PTS(64 + 50 + 2 * p + warp);
            mt = mt >= 8 ? mt - 8 : mt + 2;
            DRAINED(0);
            bar_arrive(NB_FREE + warp, 160);
          }
          WRITTEN();
          announce(r);
        }
      } else {
#pragma unroll 1
        for (int r = 0; r < NR; r++) {
          const uint32_t len = bmask(r) == 3 ? 8192 : 4096;
          unsigned char* acc = &g_acc[w12 ? 2 : 3][r % RD][bmask(r) == 2 ? 4096 : 0];
          int mt = rot + warp;
          const bool pairs = len != 8192;
#pragma unroll 1
          for (int p = pairs ? 2 : 0; p < 5; p++) {
            const uint32_t src = sb + (p == 4 ? BO_H : BO_RING_MLP + (2 - (p & 1)) * 16384) + warp * 8192;
            bar_sync(NB_STAGED + (p == 4 ? 4 : 2 * (p & 1)) + warp, 160);
            PTS(50 + 2 * p + warp);
            fence_async();
            BULK_ADD("f16", acc + mt * 8192, src, len);
            mt = mt >= 8 ? mt - 8 : mt + 2;
            if (pairs && p < 4) { BULK_ADD("f16", acc + mt * 8192, src + 4096, len); mt = mt >= 8 ? mt - 8 : mt + 2; }
            COMMIT();
            PTS(64 + 50 + 2 * p + warp);
            if (p == 4 && !pairs) break;
            DRAINED(1);
            mbar_arrive_if(lane == 0 && p, bar + 8 * (p < 3 ? BB_SFREE + 2 * (p - 1) + warp : BB_ZFREE + (p >> 1)));
            mbar_arrive_if(lane == 0 && pairs && p == 2, bar + 8 * (BB_SFREE + warp));
            if (p == 3 && !pairs) { DRAINED(0); mbar_arrive_if(lane == 0, bar + 8 * (BB_ZFREE + 2)); }
          }
          WRITTEN();
          mbar_arrive_if(lane == 0, bar + 8 * (BB_SFREE + 4 + warp));
          announce(r);
        }
      }
    } else {
      if (op && warp == 2) {
        unsigned char* wt = g_wt + j * (10 * OP_SLOT);
#pragma unroll 1
        for (int m0 = 0; m0 < 10; m0 += 3) {
          const int nu = m0 < 9 ? 9 : 3;
          mbar_expect_if(lane == 0, bar + 8 * BB_TMP, nu * 4096);
#pragma unroll 1
          for (int k = 0; k < nu; k++) tma2d_e(sb + BO_RING_OP + k * 4096, &P.wmap[0], (m0 + k / 3) * 64, 320 * j + 224 + 32 * (k % 3), bar + 8 * BB_TMP);
          mbar_waitw(bar + 8 * BB_TMP, m0 & 1);
          bulk_s2g_e(wt + m0 * OP_SLOT, sb + BO_RING_OP, nu * 4096);
          COMMIT();
          WRITTEN();
        }
        asm volatile("fence.acq_rel.gpu;" ::: "memory");
        int sl = 0, ph = 1, mt = rot;
#pragma unroll 1
        for (int r = -1; r < NSTEP; r++) {
#pragma unroll 1
          for (int n = r < 0 ? 7 : 0; n < (r + 1 < NSTEP ? 10 : 7); n++) {
            mbar_waitw(bar + 8 * (BB_USED + sl), ph);
            mbar_expect_if(lane == 0, bar + 8 * (BB_FULL + sl), OP_SLOT);
            bulk_g2s_e(sb + BO_RING_OP + sl * OP_SLOT, wt + mt * OP_SLOT, OP_SLOT, bar + 8 * (BB_FULL + sl));
            if (++sl == 3) { sl = 0; ph ^= 1; }
            mt = mt == 9 ? 0 : mt + 1;
          }
        }
      } else if (op) {
        mbar_waitw(bar + 8 * BB_START, 0);
#pragma unroll 1
        for (int r = 0; r < NSTEP; r++) {
          const int rb = r - RD + 2;
          const uint32_t len = fmask(r) == 3 ? 8192 : 4096;
          const unsigned char* src = g_o + (uint32_t)(r % RO * (96 * 8192) + 5 * j * len);
          wait_flags(lane < 2 ? &g_f[F_O + (lane ? NOP : j)][r] : rb >= 0 ? &g_f[F_DONE][rb] : &g_f[F_MISC][0],
                     lane < 2 ? (lane ? 1 : 5) : rb >= 0 ? rtarget(bmask(rb)) : NBC * 8);
          PTS1(35);
          auto two = [&](int k, uint32_t mb) {
            bulk_g2s_e(sb + BO_O + k * 8192, src + k * len, len == 8192 ? 16384 : 4096, mb);
            if (len != 8192) bulk_g2s_e(sb + BO_O + k * 8192 + 8192, src + k * len + 4096, 4096, mb);
          };
          mbar_expect_if(lane == 0, bar + 8 * (BB_OFULL + 2 + (r & 1)), len);
          bulk_g2s_e(sb + BO_O + (r & 1 ? 5 : 2) * 8192, src + 2 * len, len, bar + 8 * (BB_OFULL + 2 + (r & 1)));
          if (r) bar_sync(NB_EARLY, 288);
          mbar_expect_if(lane < 2, bar + 8 * (BB_OFULL + lane), 2 * len + (lane ? len / 4 : 0));
          two(0, bar + 8 * BB_OFULL);
          PTS(62); PTS1(38);
          const unsigned char* sx = src + (95 - 5 * j) * len + (j + 1) / 5 * 1024;
          if (r) bar_sync(NB_LAST, 288);
          two(3, bar + 8 * (BB_OFULL + 1));
          bulk_g2s_e(sb + BO_CARRY, sx, 1024, bar + 8 * (BB_OFULL + 1));
          if (len == 8192) bulk_g2s_e(sb + BO_CARRY + 1024, sx + 4096, 1024, bar + 8 * (BB_OFULL + 1));
          if (r) {
            mbar_waitw(bar + 8 * (BB_USED + (10 * r - 2) % 3), (10 * r - 2) / 3 & 1);
            mbar_waitw(bar + 8 * (BB_USED + (10 * r - 1) % 3), (10 * r - 1) / 3 & 1);
          }
          PTS1(64 + 35);
          BTS(r, 0);
        }
      } else if (warp == 2) {
#pragma unroll 1
        for (int r = 0; r < NR; r++) {
          const int mk = w12 ? fmask(r) : bmask(r);
          if (mk) {
            const unsigned char* src = &g_acc[w12 ? 4 : 2][r % RD][mk == 2 ? 4096 : 0];
            wait_flags(w12 ? &g_f[F_Z][r] : lane && r >= 2 ? &g_f[F_R3 + (j & 3)][r - 2] : &g_f[F_R2 + (j & 3)][r], w12 ? rtarget(mk) : NOP * NW12 * NW34);
#pragma unroll 1
            for (int z = 0; z < 5; z++) {
              const int k = mk == 3 ? z : z >> 1;
              const uint32_t fb = bar + 8 * (BB_FULL + z), dst = sb + BO_RING_MLP + 2 * k % 3 * 16384 + (mk == 3 ? 0 : (z & 1) * 4096);
              if (mk == 3 || !(z & 1)) mbar_waitw(bar + 8 * (k < 3 ? BB_ZFREE + k : BB_EMPTY + k - 3), (r + (k < 3)) & 1);
              if (z == 0) PTS(62);
              mbar_expect_if(lane == 0, fb, mk == 3 ? 16384 : 8192);
              bulk_g2s_e(dst, src + z * 16384, mk == 3 ? 16384 : 4096, fb);
              if (mk != 3) bulk_g2s_e(dst + 8192, src + z * 16384 + 8192, 4096, fb);
              if (z == 0) BTS(r, 0);
            }
          }
          if (!w12) {
#pragma unroll 1
            for (int c = j; c < 120; c += NW34) bulk_s2g_e(&g_acc[c < 80 ? c / 40 : 3][(r + (c < 80 ? 0 : 2)) % RD][c % 40 * 2048], sb + BO_CARRY, 2048);
            COMMIT();
            WRITTEN();
          }
          mbar_waitw(bar + 8 * BB_DONE, (r + 1) & 1);
          mbar_arrive_if(lane == 0, bar + 8 * BB_DONE);
        }
      } else {
#pragma unroll 1
        for (int r = 0; r < (w12 ? NSTEP : NR); r++) {
          const bool idle = !((w12 ? fmask(r) : bmask(r)) >> (lane >> 4) & 1);
          uint32_t t0, t1;
          int n = 0;
          mbar_waitw(bar + 8 * BB_FULL, r & 1);
          do {
            asm volatile("ld.relaxed.gpu.global.v2.u32 {%0,%1}, [%2];" : "=r"(t0), "=r"(t1) : "l"(&g_st2[!w12][r % RD][2 * lane]) : "memory");
            if (++n > SPIN_LIMIT) FAIL();
          } while (!__all_sync(~0u, idle || (((t0 ^ (r + 1)) | (t1 ^ (r + 1))) & 127) == 0));
          sts64(sb + BO_STAT + (lane >> 4) * 128 + (lane & 3) * 32 + ((lane >> 2) & 3) * 8, t0, t1);
          __syncwarp();
          mbar_arrive_if(lane == 0, bar + 8 * BB_STAT);
          PTS(63);
        }
      }
    }
    bar_arrive(NB_END, 512);
  } else if (wg == 2) {
    asm volatile("setmaxnreg.dec.sync.aligned.u32 40;");
    const int ord = uni(lds32(sb + BO_BOX + 4));
    const int gw = ord < 16 ? warp * 16 + ord : ord < 24 ? 48 + warp * 8 + ord : !RCV ? 72 + warp * 12 + ord : ord >= 32 ? 97 + 2 * (warp * 4 + ord - 32) : warp < 2 ? 48 + 2 * (warp * 8 + ord) : 88 + warp * 8 + ord, row = gw < 64 ? gw : gw < 96 ? gw - 64 : gw < 128 ? 2 * gw - 192 : 2 * gw - 224;
    if (row >= 32) {
#pragma unroll 1
      for (int t = 4 * NBC + (gw < 64 ? gw - 32 : gw - 80); t < S_LEN; t += 64) ln0(t);
    }
    if (gw < 64) rloop<0>(row, gw & 3, role, P.x, P.out);
    else if (gw < 96) rloop<2>(row, gw & 3, role, P.x, P.out);
    else if (gw < 128) rloop<1>(row, gw & 3, role, P.x, P.out);
    else rloop<4>(row, gw & 3, role, P.x, P.out);
    asm volatile("griddepcontrol.wait;" ::: "memory");
    const int t = threadIdx.x & 127;
    for (int i = (blockIdx.x * 128 + t) * 4; i < 4 * NCL * 2560; i += NBC * 512)
      *reinterpret_cast<uint4*>(&g_part[0][0][0][0] + i) = make_uint4(0u, 0u, 0u, 0u);
    bar_sync(NB_END, 512);
    if (t == 0) {
      uint32_t n;
      asm volatile("atom.acq_rel.gpu.global.add.u32 %0, [%1], 1;" : "=r"(n) : "l"(&g_f[F_MISC][64]) : "memory");
      sts32(sb + BO_BOX, n);
    }
    bar_sync(NB_END2, 128);
    if (lds32(sb + BO_BOX) == NBC - 1) {
      for (int i = t; i < F_NUM * 24; i += 128) reinterpret_cast<uint4*>(&g_f[0][0])[i] = make_uint4(0u, 0u, 0u, 0u);
      g_xready[t][0] = 0; g_tpc[t] = 0;
    }
  } else {
    asm volatile("setmaxnreg.inc.sync.aligned.u32 224;");
    LANE_INIT();
    for (int i = blockIdx.x * 256 + threadIdx.x; i < 2 * (RD + 1) * TILE_B / 16; i += NBC * 256)
      reinterpret_cast<uint4*>(&g_acc[i < 2 * RD * TILE_B / 16 ? 0 : 1][0][0])[i] = make_uint4(0u, 0u, 0u, 0u);
    warp_signal(&g_f[F_MISC][0], lane);
    const int mt0 = (rot + wg) % 10;
    auto boxes = [&](int ss) {
      const int nb = op && ss ? 3 : 4;
      const uint32_t base = sb + (ss ? BO_RES + wg * OP_RES : wg * 83968);
      mbar_expect_if(warp == 0 && lane == 0, bar + 8 * (BB_W + wg), nb * 20480 + (op ? 2048 : 0));
      bar_sync(NB_H, 256);
      if (warp < nb) {
#pragma unroll 1
        for (int i = warp; i < 5 * nb; i += nb) {
          const int p = op ? i / nb : (i - 10) >> 1, mt = (mt0 + 2 * p) % 10;
          const bool first = !op && i < 10;
          tma2d_e(op || !ss ? base + i * 4096 : sb + (first ? BO_W1 : -81920) + (2 * i + wg) * 4096, &P.wmap[op ? 0 : (w12 ? 1 : 3) + !first], first ? 128 * j + 64 * wg : mt * 64,
                  op ? 320 * j + 64 * warp + 32 * ss : first ? 64 * i + 32 * ss : 128 * j + 32 * (i & 1) + 64 * ss, bar + 8 * (BB_W + wg));
        }
      }
      if (op && warp == 3) tma2d_e(base + nb * 20480, &P.wo16, (mt0 + 2 * ss) % 10 * 64, 95 * 64 + (j + 1) / 5 * 16, bar + 8 * (BB_W + wg));
      mbar_waitw(bar + 8 * (BB_W + wg), ss);
    };
    if (W_DELAY && !op) __nanosleep(W_DELAY);
    uint32_t W[164];
    boxes(0);
    load_w<41>(W, sb + wg * 83968, warp, lane);
    fence_async();
    boxes(1);
    if (!op) {
      float cs[2] = {0.f, 0.f};
      const uint32_t a0 = sb + BO_W1 + wg * 4096 + ((lane >> 4) * 8 + (lane & 7)) * 128 + (((warp * 2 + ((lane >> 3) & 1)) ^ (lane & 7)) << 4);
#pragma unroll
      for (int i = 0; i < 80; i++) cs[i & 1] += bf_lo(W[i]) + bf_hi(W[i]);
#pragma unroll 1
      for (int i = 0; i < 40; i++) {
        uint32_t t[4];
        const uint32_t ad = a0 + (i % 20 >> 1) * 8192 + (i & 1) * 2048;
        ldsm4t(t[0], t[1], t[2], t[3], ad);
#pragma unroll
        for (int k = 0; k < 4; k++) {
          if (i < 20) cs[k & 1] += bf_lo(t[k]) + bf_hi(t[k]);
          t[k] = pack2h(bf_lo(t[k]) - cs[k & 1], bf_hi(t[k]) - cs[k & 1]);
        }
        if (i >= 20) stsm4t(ad, t[0], t[1], t[2], t[3]);
        if (i == 19) {
#pragma unroll
          for (int k = 0; k < 2; k++) { cs[k] += __shfl_xor_sync(~0u, cs[k], 1); cs[k] += __shfl_xor_sync(~0u, cs[k], 2); cs[k] *= 1.f / DM; }
        }
      }
      const uint32_t z = dep0(__float_as_uint(cs[0]), lane);
#pragma unroll
      for (int i = 0; i < 80; i++) W[i] = pack2h(bf_lo(W[i] | z) - cs[i & 1], bf_hi(W[i] | z) - cs[i & 1]);
      fence_async();
      bar_sync(NB_H, 256);
    }
    if (warp == 0) BTS(94, 6 + wg);
    const Dsc blo = {P.desc, 1}, alo = blo + wg * (op ? OP_RES / 16 : 256);
    if (op) {
      Ring rg = {(uint32_t)wg, 0};
      mbar_arrive_if(lane == 0, bar + 8 * BB_START);
      if (wg) bar_arrive(NB_PP, 256);
      const Dsc xlo = {P.desc32, 1};
#pragma unroll 1
      for (int r = 0; r < NSTEP; r++) {
        asm volatile("" : "+r"(lane));
        if (fmask(r) == 3) op_round<64>(W, bar, alo, blo, xlo, j == 0, rg, wg, warp, lane, r);
        else op_round<32>(W, bar, alo, blo, xlo, j == 0, rg, wg, warp, lane, r);
        if (warp == 0) BTS(r, 2 + wg);
      }
    } else {
      const int q4 = (128 * j + 64 * wg + 16 * warp) / 160, off = w12 ? (0x0413 >> (4 * q4)) & 7 : 0;
#pragma unroll 1
      for (int r = 0; r < NR; r++) {
        asm volatile("" : "+r"(lane));
        const int bm = bmask(r), fm = w12 ? fmask(r) : bm;
        if (fm == 3) phase1<64>(W, sb, alo, blo, 0, wg, warp, lane, off, r);
        else if (fm) phase1<32>(W, sb, alo, blo, fm >> 1, wg, warp, lane, off, r);
        else { mbar_waitu(bar + 8 * (BB_SFREE + 4 + wg), (r + 1) & 1); carry_in(sb, wg, warp, lane); }
        CTS(33);
        fence_async();
        bar_sync(NB_H, 256);
        mbar_arrive_if(wg == 1 && warp == 0 && lane < 2, bar + 8 * BB_ZFREE);
        if (wg + warp == 0) BTS(r, 1);
        if (bm == 3) phase2<64>(W, bar, alo, blo, wg, warp, lane, r);
        else phase2<32>(W, bar, alo, blo + (bm >> 1) * 256, wg, warp, lane, r);
        if (warp == 0) BTS(r, 2 + wg);
      }
    }
    CTS_OUT();
    bar_arrive(NB_END, 512);
  }
}

typedef CUresult (*EncodeFn)(CUtensorMap*, CUtensorMapDataType, cuuint32_t, void*, const cuuint64_t*, const cuuint64_t*, const cuuint32_t*,
                             const cuuint32_t*, CUtensorMapInterleave, CUtensorMapSwizzle, CUtensorMapL2promotion, CUtensorMapFloatOOBfill);
static void make_map(EncodeFn fn, CUtensorMap* tm, const void* ptr, uint64_t cols, uint64_t rows, uint32_t bc, uint32_t br) {
  cuuint64_t dims[2] = {cols, rows}; cuuint64_t strides[1] = {cols * 2}; cuuint32_t box[2] = {bc, br}; cuuint32_t es[2] = {1, 1};
  fn(tm, CU_TENSOR_MAP_DATA_TYPE_BFLOAT16, 2, const_cast<void*>(ptr), dims, strides, box, es, CU_TENSOR_MAP_INTERLEAVE_NONE,
     CU_TENSOR_MAP_SWIZZLE_128B, CU_TENSOR_MAP_L2_PROMOTION_L2_256B, CU_TENSOR_MAP_FLOAT_OOB_FILL_NONE);
}
#define dbg_a_only 0
extern "C" void kernel_launch(void* const* d_in, const int* in_sizes, int n_in, void* d_out, int out_size) {
  void* fnp = nullptr; cudaDriverEntryPointQueryResult qr;
  cudaGetDriverEntryPoint("cuTensorMapEncodeTiled", &fnp, cudaEnableDefault, &qr);
  EncodeFn fn = (EncodeFn)fnp;
  cudaStream_t st = cudaStreamPerThread;
  cudaFuncSetAttribute(bworker_kernel, cudaFuncAttributeMaxDynamicSharedMemorySize, B_SMEM);
  {
    AMaps M;
    for (int i = 0; i < 3; i++) make_map(fn, &M.w16[i], d_in[2 + i], HD, DM, 64, 16);
    M.wv = (const __nv_bfloat16*)d_in[4];
    make_map(fn, &M.wo32, d_in[5], DM, HD, 64, 32);
    const uint32_t hi[5] = {dhi(TILE_SBO, 3), dhi(1024, 1), dhi(1024, 0), dhi(PL_SZ, 0), dhi(896, 0)};
    for (int i = 0; i < 5; i++) M.d[i] = (uint64_t)hi[i] << 32;
    cudaFuncSetAttribute(acore_kernel, cudaFuncAttributeMaxDynamicSharedMemorySize, A_SMEM);
    cudaFuncSetAttribute(acore_kernel, cudaFuncAttributeNonPortableClusterSizeAllowed, 1);
    cudaLaunchConfig_t cfg = {};
    cfg.gridDim = dim3(CL_SIZE * NCL); cfg.blockDim = dim3(512); cfg.dynamicSmemBytes = A_SMEM; cfg.stream = st;
    cudaLaunchAttribute at[1]; at[0].id = cudaLaunchAttributeClusterDimension;
    at[0].val.clusterDim.x = CL_SIZE; at[0].val.clusterDim.y = 1; at[0].val.clusterDim.z = 1;
    cfg.attrs = at; cfg.numAttrs = 1;
    cudaLaunchKernelEx(&cfg, acore_kernel, M, (const __nv_bfloat16*)d_in[1], dbg_a_only ? 0 : 1);
  }
  if (!dbg_a_only) {
    BParams P;
    make_map(fn, &P.wmap[0], d_in[5], DM, HD, 64, 32);
    make_map(fn, &P.wo16, d_in[5], DM, HD, 64, 16);
    make_map(fn, &P.wmap[1], d_in[8], DM, DM, 64, 32);
    make_map(fn, &P.wmap[2], d_in[9], DM, DM, 64, 32);
    make_map(fn, &P.wmap[3], d_in[10], FF, DM, 64, 32);
    make_map(fn, &P.wmap[4], d_in[11], DM, FF, 64, 32);
    P.x = (const __nv_bfloat16*)d_in[0];
    P.out = (__nv_bfloat16*)d_out;
    P.desc = (uint64_t)dhi(1024, 1) << 32;
    P.desc32 = (uint64_t)dhi(256, 3) << 32;
    cudaLaunchConfig_t cfg = {};
    cfg.gridDim = dim3(NBC); cfg.blockDim = dim3(512); cfg.dynamicSmemBytes = B_SMEM; cfg.stream = st;
    cudaLaunchAttribute at[1]; at[0].id = cudaLaunchAttributeProgrammaticStreamSerialization; at[0].val.programmaticStreamSerializationAllowed = 1;
    cfg.attrs = at; cfg.numAttrs = 1;
    cudaLaunchKernelEx(&cfg, bworker_kernel, P);
  }
}
```

```cpp
#include <cuda_runtime.h>
#include <cuda_bf16.h>
#include <cuda.h>
#include <stdint.h>

#define S_LEN 2048
#define DM 640
#define NH 32
#define DH 192
#define HD 6144
#define NSEG 64
#define FF 1536

__device__ __forceinline__ uint32_t smem_u32(const void* p) { return (uint32_t)__cvta_generic_to_shared(p); }
__device__ __forceinline__ uint32_t mapa(uint32_t a, uint32_t r) {
  uint32_t o; asm volatile("mapa.shared::cluster.u32 %0, %1, %2;" : "=r"(o) : "r"(a), "r"(r)); return o; }
__device__ __forceinline__ void mbar_init(uint32_t b, uint32_t c) {
  asm volatile("mbarrier.init.shared::cta.b64 [%0], %1;" :: "r"(b), "r"(c) : "memory"); }
__device__ __forceinline__ void mbar_expect(uint32_t b, uint32_t tx) {
  asm volatile("mbarrier.arrive.expect_tx.shared::cta.b64 _, [%0], %1;" :: "r"(b), "r"(tx) : "memory"); }
__device__ __forceinline__ void mbar_arrive(uint32_t b) {
  asm volatile("mbarrier.arrive.shared::cta.b64 _, [%0];" :: "r"(b) : "memory"); }
__device__ __forceinline__ void mbar_arrive_remote(uint32_t rb) {
  asm volatile("mbarrier.arrive.relaxed.cluster.shared::cluster.b64 _, [%0];" :: "r"(rb) : "memory"); }
__device__ __forceinline__ void mbar_expect_if(bool p, uint32_t b, uint32_t tx) {
  asm volatile("{\n.reg .pred q;\nsetp.ne.u32 q, %2, 0;\n@q mbarrier.arrive.expect_tx.shared::cta.b64 _, [%0], %1;\n}" :: "r"(b), "r"(tx), "r"((uint32_t)p) : "memory"); }
__device__ __forceinline__ void mbar_arrive_if(bool p, uint32_t b) {
  asm volatile("{\n.reg .pred q;\nsetp.ne.u32 q, %1, 0;\n@q mbarrier.arrive.shared::cta.b64 _, [%0];\n}" :: "r"(b), "r"((uint32_t)p) : "memory"); }
__device__ __forceinline__ void mbar_arrive_remote_if(bool p, uint32_t rb) {
  asm volatile("{\n.reg .pred q;\nsetp.ne.u32 q, %1, 0;\n@q mbarrier.arrive.relaxed.cluster.shared::cluster.b64 _, [%0];\n}" :: "r"(rb), "r"((uint32_t)p) : "memory"); }
__device__ __forceinline__ void sts32_if(bool p, uint32_t a, uint32_t v) {
  asm volatile("{\n.reg .pred q;\nsetp.ne.u32 q, %2, 0;\n@q st.shared.b32 [%0], %1;\n}" :: "r"(a), "r"(v), "r"((uint32_t)p) : "memory"); }
__device__ __forceinline__ void sts128z_if(bool p, uint32_t a) {
  asm volatile("{\n.reg .pred q;\nsetp.ne.u32 q, %1, 0;\n@q st.shared.v4.b32 [%0], {0,0,0,0};\n}" :: "r"(a), "r"((uint32_t)p) : "memory"); }
__device__ __forceinline__ bool mbar_try(uint32_t b, uint32_t ph) {
  uint32_t ok;
  asm volatile("{\n.reg .pred p;\nmbarrier.try_wait.parity.shared::cta.b64 p, [%1], %2;\nselp.u32 %0, 1, 0, p;\n}"
               : "=r"(ok) : "r"(b), "r"(ph) : "memory");
  return ok; }
__device__ __forceinline__ bool mbar_test(uint32_t b, uint32_t ph) {
  uint32_t ok;
  asm volatile("{\n.reg .pred p;\nmbarrier.test_wait.parity.shared::cta.b64 p, [%1], %2;\nselp.u32 %0, 1, 0, p;\n}"
               : "=r"(ok) : "r"(b), "r"(ph) : "memory");
  return ok; }
#define SPIN_LIMIT 4000000
#define FAIL() asm volatile("st.global.u32 [%0], 0;" :: "l"(8ull) : "memory")
#define CFENCE() asm volatile("fence.proxy.async::generic.acquire.sync_restrict::shared::cluster.cluster;" ::: "memory")
__device__ __forceinline__ void mbar_wait(uint32_t b, uint32_t ph) {
  int n = 0;
  while (!mbar_try(b, ph)) { if (++n > SPIN_LIMIT) FAIL(); } }
#define TIMEOUT_ACT "@!p st.shared.u32 [%0+1], 0;"
#define WAIT_HINT ", 20000"
#define WAIT_LIM "200000"
__device__ __forceinline__ void mbar_slow(uint32_t b, uint32_t ph) {
  asm volatile("{\n.reg .pred p, q;\n.reg .u32 n;\nmov.u32 n, 0;\n"
               "WL:\nmbarrier.try_wait.parity.shared::cta.b64 p, [%0], %1" WAIT_HINT ";\nadd.u32 n, n, 1;\nsetp.lt.and.u32 q, n, " WAIT_LIM ", !p;\n@q bra.uni WL;\n"
               TIMEOUT_ACT "\n}" :: "r"(b), "r"(ph) : "memory"); }
__device__ __forceinline__ void mbar_waitw(uint32_t b, uint32_t ph) {
  asm volatile("{\n.reg .pred p, q;\n.reg .u32 n;\nmbarrier.try_wait.parity.shared::cta.b64 p, [%0], %1;\n@p bra.uni WD;\nmov.u32 n, 0;\n"
               "WL:\nmbarrier.try_wait.parity.shared::cta.b64 p, [%0], %1" WAIT_HINT ";\nadd.u32 n, n, 1;\nsetp.lt.and.u32 q, n, " WAIT_LIM ", !p;\n@q bra.uni WL;\n"
               TIMEOUT_ACT "\nWD:\n}" :: "r"(b), "r"(ph) : "memory"); }
__device__ __forceinline__ void mbar_waitw2(uint32_t b0, uint32_t b1, uint32_t ph) {
  uint32_t ok;
  asm volatile("{\n.reg .pred p, r;\nmbarrier.try_wait.parity.shared::cta.b64 p, [%1], %3;\nmbarrier.try_wait.parity.shared::cta.b64 r, [%2], %3;\n"
               "and.pred p, p, r;\nselp.u32 %0, 1, 0, p;\n}" : "=r"(ok) : "r"(b0), "r"(b1), "r"(ph) : "memory");
  if (__builtin_expect(!__all_sync(~0u, ok), 0)) { mbar_slow(b0, ph); mbar_slow(b1, ph); }
}
__device__ __forceinline__ void mbar_waitu(uint32_t b, uint32_t ph) {
  asm volatile("{\n.reg .pred p;\nmbarrier.try_wait.parity.shared::cta.b64 p, [%0], %1;\n@p bra.uni WD;\n"
               "WL:\nmbarrier.try_wait.parity.shared::cta.b64 p, [%0], %1" WAIT_HINT ";\n@!p bra.uni WL;\nWD:\n}" :: "r"(b), "r"(ph) : "memory"); }
__device__ __forceinline__ void mbar_waitu2(uint32_t b0, uint32_t b1, uint32_t ph) {
  asm volatile("{\n.reg .pred p, r;\nWL:\nmbarrier.try_wait.parity.shared::cta.b64 p, [%0], %2;\nmbarrier.try_wait.parity.shared::cta.b64 r, [%1], %2;\n"
               "and.pred p, p, r;\n@!p bra.uni WL;\n}" :: "r"(b0), "r"(b1), "r"(ph) : "memory"); }
__device__ __forceinline__ void mbar_waitw4(uint32_t b, uint32_t ph) { mbar_waitw2(b, b + 8, ph); mbar_waitw2(b + 16, b + 24, ph); }
__device__ __forceinline__ uint32_t clock32() { uint32_t t; asm volatile("mov.u32 %0, %%clock;" : "=r"(t) :: "memory"); return t; }
template <int L> __device__ __forceinline__ uint32_t lop3(uint32_t a, uint32_t b, uint32_t c) {
  uint32_t r; asm("lop3.b32 %0, %1, %2, %3, %4;" : "=r"(r) : "r"(a), "r"(b), "r"(c), "n"(L)); return r; }
__device__ __forceinline__ void st_async_v2_if(bool p, uint32_t a, uint32_t v0, uint32_t v1, uint32_t mb) {
  asm volatile("{\n.reg .pred q;\nsetp.ne.u32 q, %4, 0;\n@q st.async.weak.shared::cluster.mbarrier::complete_tx::bytes.v2.b32 [%0], {%1,%2}, [%3];\n}"
               :: "r"(a), "r"(v0), "r"(v1), "r"(mb), "r"((uint32_t)p) : "memory"); }
__device__ __forceinline__ void keep4(const uint32_t* r, int lane) {
  asm volatile("{\n.reg .pred q;\nsetp.lt.s32 q, %4, 0;\n@q st.shared.v4.b32 [%4], {%0,%1,%2,%3};\n}" :: "r"(r[0]), "r"(r[1]), "r"(r[2]), "r"(r[3]), "r"(lane) : "memory"); }
__device__ __forceinline__ void fence_sched(int i) {
  asm volatile("{\n.reg .pred q;\nsetp.gt.s32 q, %0, 4096;\n@q st.shared.u32 [%0], 0;\n}" :: "r"(i) : "memory"); }
__device__ __forceinline__ uint32_t hmax2bf(uint32_t a, uint32_t b) { uint32_t r; asm("max.bf16x2 %0, %1, %2;" : "=r"(r) : "r"(a), "r"(b)); return r; }
__device__ __forceinline__ uint32_t uni(uint32_t x) { return __shfl_sync(~0u, x, 0); }
__device__ __forceinline__ void bulk_g2s_mc_e(uint32_t dst, const void* src, uint32_t bytes, uint32_t mb, uint16_t mask) {
  asm volatile("{\n.reg .pred e;\nelect.sync _|e, 0xffffffff;\n"
               "@e cp.async.bulk.shared::cluster.global.mbarrier::complete_tx::bytes.multicast::cluster [%0], [%1], %2, [%3], %4;\n}"
               :: "r"(dst), "l"(src), "r"(bytes), "r"(mb), "h"(mask) : "memory"); }
__device__ __forceinline__ void bulk_s2g_e(void* dst, uint32_t src, uint32_t bytes) {
  asm volatile("{\n.reg .pred e;\nelect.sync _|e, 0xffffffff;\n@e cp.async.bulk.global.shared::cta.bulk_group [%0], [%1], %2;\n}"
               :: "l"(dst), "r"(src), "r"(bytes) : "memory"); }
__device__ __forceinline__ void bulk_g2s_e(uint32_t dst, const void* src, uint32_t bytes, uint32_t mb) {
  asm volatile("{\n.reg .pred e;\nelect.sync _|e, 0xffffffff;\n@e cp.async.bulk.shared::cluster.global.mbarrier::complete_tx::bytes [%0], [%1], %2, [%3];\n}"
               :: "r"(dst), "l"(src), "r"(bytes), "r"(mb) : "memory"); }
#define STREAM_HINT 1
__device__ __forceinline__ void bulk_s2g_es(void* dst, uint32_t src, uint32_t bytes) {
  asm volatile("{\n.reg .pred e;\n.reg .b64 pol;\ncreatepolicy.fractional.L2::evict_first.b64 pol;\nelect.sync _|e, 0xffffffff;\n"
               "@e cp.async.bulk.global.shared::cta.bulk_group.L2::cache_hint [%0], [%1], %2, pol;\n}" :: "l"(dst), "r"(src), "r"(bytes) : "memory");
}
__device__ __forceinline__ void bulk_g2s_es(uint32_t dst, const void* src, uint32_t bytes, uint32_t mb) {
  asm volatile("{\n.reg .pred e;\n.reg .b64 pol;\ncreatepolicy.fractional.L2::evict_first.b64 pol;\nelect.sync _|e, 0xffffffff;\n"
               "@e cp.async.bulk.shared::cluster.global.mbarrier::complete_tx::bytes.L2::cache_hint [%0], [%1], %2, [%3], pol;\n}"
               :: "r"(dst), "l"(src), "r"(bytes), "r"(mb) : "memory"); }
__device__ __forceinline__ void tma2d_e(uint32_t dst, const CUtensorMap* tm, int c0, int c1, uint32_t mb) {
  asm volatile("{\n.reg .pred e;\nelect.sync _|e, 0xffffffff;\n"
               "@e cp.async.bulk.tensor.2d.shared::cluster.global.mbarrier::complete_tx::bytes [%0], [%1, {%3, %4}], [%2];\n}"
               :: "r"(dst), "l"((uint64_t)tm), "r"(mb), "r"(c0), "r"(c1) : "memory"); }
__device__ __forceinline__ uint32_t hadd2bf(uint32_t a, uint32_t b) {
  uint32_t r; asm("add.rn.bf16x2 %0, %1, %2;" : "=r"(r) : "r"(a), "r"(b)); return r; }
__device__ __forceinline__ void cluster_sync_all() {
  asm volatile("barrier.cluster.arrive.release.aligned;\nbarrier.cluster.wait.acquire.aligned;" ::: "memory"); }
__device__ __forceinline__ void bar_arrive(int id, int n) { asm volatile("bar.arrive %0, %1;" :: "r"(id), "r"(n) : "memory"); }
__device__ __forceinline__ void bar_arrive_dep(int id, int n, uint32_t dep) {
  asm volatile("{\n.reg .u32 t;\nand.b32 t, %2, 0;\nadd.u32 t, t, %0;\nbar.sync t, %1;\n}" :: "r"(id), "r"(n), "r"(dep) : "memory"); }
__device__ __forceinline__ void bar_sync(int id, int n) { asm volatile("bar.sync %0, %1;" :: "r"(id), "r"(n) : "memory"); }
__device__ __forceinline__ void fence_async() { asm volatile("fence.proxy.async.shared::cta;" ::: "memory"); }
__device__ __forceinline__ void st_async_b32(uint32_t a, uint32_t v, uint32_t mb) {
  asm volatile("st.async.weak.shared::cluster.mbarrier::complete_tx::bytes.b32 [%0], %1, [%2];" :: "r"(a), "r"(v), "r"(mb) : "memory"); }
__device__ __forceinline__ void st_async_v2(uint32_t a, uint32_t v0, uint32_t v1, uint32_t mb) {
  asm volatile("st.async.weak.shared::cluster.mbarrier::complete_tx::bytes.v2.b32 [%0], {%1,%2}, [%3];" :: "r"(a), "r"(v0), "r"(v1), "r"(mb) : "memory"); }
__device__ __forceinline__ void st_async_v4(uint32_t a, uint32_t v0, uint32_t v1, uint32_t v2, uint32_t v3, uint32_t mb) {
  asm volatile("st.async.weak.shared::cluster.mbarrier::complete_tx::bytes.v4.b32 [%0], {%1,%2,%3,%4}, [%5];" :: "r"(a), "r"(v0), "r"(v1), "r"(v2), "r"(v3), "r"(mb) : "memory"); }
__device__ __forceinline__ void ldsm4(uint32_t& r0, uint32_t& r1, uint32_t& r2, uint32_t& r3, uint32_t a) {
  asm volatile("ldmatrix.sync.aligned.m8n8.x4.shared.b16 {%0,%1,%2,%3}, [%4];" : "=r"(r0), "=r"(r1), "=r"(r2), "=r"(r3) : "r"(a) : "memory"); }
__device__ __forceinline__ void ldsm4t(uint32_t& r0, uint32_t& r1, uint32_t& r2, uint32_t& r3, uint32_t a) {
  asm volatile("ldmatrix.sync.aligned.m8n8.x4.trans.shared.b16 {%0,%1,%2,%3}, [%4];" : "=r"(r0), "=r"(r1), "=r"(r2), "=r"(r3) : "r"(a) : "memory"); }
__device__ __forceinline__ void stsm2t(uint32_t a, uint32_t r0, uint32_t r1) {
  asm volatile("stmatrix.sync.aligned.m8n8.x2.trans.shared.b16 [%0], {%1,%2};" :: "r"(a), "r"(r0), "r"(r1) : "memory"); }
__device__ __forceinline__ void stsm4t(uint32_t a, uint32_t r0, uint32_t r1, uint32_t r2, uint32_t r3) {
  asm volatile("stmatrix.sync.aligned.m8n8.x4.trans.shared.b16 [%0], {%1,%2,%3,%4};" :: "r"(a), "r"(r0), "r"(r1), "r"(r2), "r"(r3) : "memory"); }
__device__ __forceinline__ uint32_t movm(uint32_t a) {
  uint32_t d; asm volatile("movmatrix.sync.aligned.m8n8.trans.b16 %0, %1;" : "=r"(d) : "r"(a)); return d; }
__device__ __forceinline__ void mma16816(float* d, uint32_t a0, uint32_t a1, uint32_t a2, uint32_t a3, uint32_t b0, uint32_t b1) {
  asm("mma.sync.aligned.m16n8k16.row.col.f32.bf16.bf16.f32 {%0,%1,%2,%3}, {%4,%5,%6,%7}, {%8,%9}, {%0,%1,%2,%3};"
               : "+f"(d[0]), "+f"(d[1]), "+f"(d[2]), "+f"(d[3]) : "r"(a0), "r"(a1), "r"(a2), "r"(a3), "r"(b0), "r"(b1)); }
__device__ __forceinline__ void mma16816v(float* d, uint32_t a0, uint32_t a1, uint32_t a2, uint32_t a3, uint32_t b0, uint32_t b1) {
  asm volatile("mma.sync.aligned.m16n8k16.row.col.f32.bf16.bf16.f32 {%0,%1,%2,%3}, {%4,%5,%6,%7}, {%8,%9}, {%0,%1,%2,%3};"
               : "+f"(d[0]), "+f"(d[1]), "+f"(d[2]), "+f"(d[3]) : "r"(a0), "r"(a1), "r"(a2), "r"(a3), "r"(b0), "r"(b1)); }
__device__ __forceinline__ uint32_t pack2(float lo, float hi) {
  uint32_t r; asm("cvt.rn.bf16x2.f32 %0, %1, %2;" : "=r"(r) : "f"(hi), "f"(lo)); return r; }
__device__ __forceinline__ uint32_t pack2v(float lo, float hi) {
  uint32_t r; asm volatile("cvt.rn.bf16x2.f32 %0, %1, %2;" : "=r"(r) : "f"(hi), "f"(lo)); return r; }
__device__ __forceinline__ float bf_lo(uint32_t w) { return __uint_as_float(w << 16); }
__device__ __forceinline__ float bf_hi(uint32_t w) { return __uint_as_float(w & 0xffff0000u); }
__device__ __forceinline__ uint4 lds128(uint32_t a) {
  uint4 v; asm volatile("ld.shared.v4.b32 {%0,%1,%2,%3}, [%4];" : "=r"(v.x), "=r"(v.y), "=r"(v.z), "=r"(v.w) : "r"(a) : "memory"); return v; }
__device__ __forceinline__ uint4 lds128_nv(uint32_t a) {
  uint4 v; asm volatile("ld.shared.v4.b32 {%0,%1,%2,%3}, [%4];" : "=r"(v.x), "=r"(v.y), "=r"(v.z), "=r"(v.w) : "r"(a)); return v; }
__device__ __forceinline__ void st_async_v2_nm(uint32_t a, uint32_t v0, uint32_t v1, uint32_t mb) {
  asm volatile("st.async.weak.shared::cluster.mbarrier::complete_tx::bytes.v2.b32 [%0], {%1,%2}, [%3];" :: "r"(a), "r"(v0), "r"(v1), "r"(mb)); }
__device__ __forceinline__ float rcpf(float x) { float y; asm("rcp.approx.ftz.f32 %0, %1;" : "=f"(y) : "f"(x)); return y; }
__device__ __forceinline__ void sts64(uint32_t a, uint32_t x, uint32_t y) { asm volatile("st.shared.v2.b32 [%0], {%1,%2};" :: "r"(a), "r"(x), "r"(y) : "memory"); }
__device__ __forceinline__ float ex2(float x) { float y; asm("ex2.approx.ftz.f32 %0, %1;" : "=f"(y) : "f"(x)); return y; }
__device__ __forceinline__ uint32_t lds32(uint32_t a) {
  uint32_t v; asm volatile("ld.shared.b32 %0, [%1];" : "=r"(v) : "r"(a) : "memory"); return v; }
__device__ __forceinline__ uint2 lds64(uint32_t a) {
  uint2 v; asm volatile("ld.shared.v2.b32 {%0,%1}, [%2];" : "=r"(v.x), "=r"(v.y) : "r"(a) : "memory"); return v; }
__device__ __forceinline__ void sts128(uint32_t a, uint32_t x, uint32_t y, uint32_t z, uint32_t w) {
  asm volatile("st.shared.v4.b32 [%0], {%1,%2,%3,%4};" :: "r"(a), "r"(x), "r"(y), "r"(z), "r"(w) : "memory"); }
__device__ __forceinline__ void sts32(uint32_t a, uint32_t x) { asm volatile("st.shared.b32 [%0], %1;" :: "r"(a), "r"(x) : "memory"); }
__device__ __forceinline__ void tma2d(uint32_t dst, const CUtensorMap* tm, int c0, int c1, uint32_t mb) {
  asm volatile("cp.async.bulk.tensor.2d.shared::cluster.global.mbarrier::complete_tx::bytes [%0], [%1, {%3, %4}], [%2];"
               :: "r"(dst), "l"((uint64_t)tm), "r"(mb), "r"(c0), "r"(c1) : "memory"); }
__device__ __forceinline__ void tma2d_prefetch(const CUtensorMap* tm, int c0, int c1) {
  asm volatile("cp.async.bulk.prefetch.tensor.2d.L2.global.tile [%0, {%1, %2}];" :: "l"((uint64_t)tm), "r"(c0), "r"(c1) : "memory"); }
__device__ __forceinline__ void bulk_g2s_mc(uint32_t dst, const void* src, uint32_t bytes, uint32_t mb, uint16_t mask) {
  asm volatile("cp.async.bulk.shared::cluster.global.mbarrier::complete_tx::bytes.multicast::cluster [%0], [%1], %2, [%3], %4;"
               :: "r"(dst), "l"(src), "r"(bytes), "r"(mb), "h"(mask) : "memory"); }
__device__ __forceinline__ void bulk_s2g(void* dst, uint32_t src, uint32_t bytes) {
  asm volatile("cp.async.bulk.global.shared::cta.bulk_group [%0], [%1], %2;" :: "l"(dst), "r"(src), "r"(bytes) : "memory"); }
__device__ __forceinline__ void wg_fence() { asm volatile("wgmma.fence.sync.aligned;" ::: "memory"); }
__device__ __forceinline__ void wg_commit() { asm volatile("wgmma.commit_group.sync.aligned;" ::: "memory"); }
template <int N> __device__ __forceinline__ void wg_wait() { asm volatile("wgmma.wait_group.sync.aligned %0;" :: "n"(N) : "memory"); }
__device__ __forceinline__ uint64_t mkdesc(uint32_t addr, uint32_t lbo, uint32_t sbo, uint32_t swz) {
  return (uint64_t)((addr & 0x3FFFF) >> 4) | ((uint64_t)(lbo >> 4) << 16) | ((uint64_t)(sbo >> 4) << 32) | ((uint64_t)swz << 62); }

#define ACC4(d) "+f"(d[0]),"+f"(d[1]),"+f"(d[2]),"+f"(d[3])
#define ACC8(d) ACC4(d), ACC4((d + 4))
#define ACC16(d) ACC8(d), ACC8((d + 8))
#define ACC20(d) ACC16(d), ACC4((d + 16))
#define ACC24(d) ACC16(d), ACC8((d + 16))
#define SMEM0 0x400
__host__ __device__ constexpr uint32_t dlo(uint32_t off, uint32_t lbo) { return ((SMEM0 + off) >> 4) | ((lbo >> 4) << 16); }
__host__ __device__ constexpr uint32_t dhi(uint32_t sbo, uint32_t swz) { return (sbo >> 4) | (swz << 30); }
#define R4S "{%0,%1,%2,%3}"
#define R8S "{%0,%1,%2,%3,%4,%5,%6,%7}"
#define R16S "{%0,%1,%2,%3,%4,%5,%6,%7,%8,%9,%10,%11,%12,%13,%14,%15}"
#define R20S "{%0,%1,%2,%3,%4,%5,%6,%7,%8,%9,%10,%11,%12,%13,%14,%15,%16,%17,%18,%19}"
#define R24S "{%0,%1,%2,%3,%4,%5,%6,%7,%8,%9,%10,%11,%12,%13,%14,%15,%16,%17,%18,%19,%20,%21,%22,%23}"
#define ACC32(d) ACC16(d), ACC16((d + 16))
#define R32S "{%0,%1,%2,%3,%4,%5,%6,%7,%8,%9,%10,%11,%12,%13,%14,%15,%16,%17,%18,%19,%20,%21,%22,%23,%24,%25,%26,%27,%28,%29,%30,%31}"
struct Dsc {
  uint64_t b; uint32_t e;
  __device__ __forceinline__ Dsc operator+(uint32_t o) const { return {b + o, e}; }
};
template <int K> __device__ __forceinline__ uint32_t fresh(int i) {
  uint32_t e; asm volatile("{\n.reg .u32 t;\nadd.u32 t, %1, %2;\nshr.u32 %0, t, %3;\n}" : "=r"(e) : "r"(i), "n"((256 << K) + 1), "n"(8 + K)); return e; }
template <int N, bool H = false> struct MM;
#define DEF_MM(N, H, T, ACCM, RS_, I0, I1, I2, I3, I4, I5, I6, I7)                                                                \
  template <> struct MM<N, H> {                                                                                                   \
    template <uint32_t BLO, int ACC>                                                                                              \
    static __device__ __forceinline__ void rs(float* d, const uint32_t* a, Dsc b0) {                                              \
      asm volatile("{\n.reg .b64 b;\nmad.wide.u32 b, %" #I7 ", %" #I5 ", %" #I4 ";\n"                                             \
                   "wgmma.mma_async.sync.aligned.m64n" #N "k16.f32." T "." T " " RS_ ", {%" #I0 ",%" #I1 ",%" #I2 ",%" #I3 "}, b, %" #I6 ", 1, 1, 0;\n}" \
                   : ACCM(d) : "r"(a[0]), "r"(a[1]), "r"(a[2]), "r"(a[3]), "l"(b0.b), "n"(BLO), "n"(ACC), "r"(b0.e)); }           \
    template <uint32_t ALO, uint32_t BLO, int ACC, int TA = 1>                                                                    \
    static __device__ __forceinline__ void ss(float* d, Dsc a0, Dsc b0) {                                                         \
      asm volatile("{\n.reg .b64 a, b;\nmad.wide.u32 a, %" #I6 ", %" #I1 ", %" #I0 ";\nmad.wide.u32 b, %" #I6 ", %" #I3 ", %" #I2 ";\n" \
                   "wgmma.mma_async.sync.aligned.m64n" #N "k16.f32." T "." T " " RS_ ", a, b, %" #I4 ", 1, 1, %" #I5 ", 0;\n}"    \
                   : ACCM(d) : "l"(a0.b), "n"(ALO), "l"(b0.b), "n"(BLO), "n"(ACC), "n"(TA), "r"(b0.e)); }                         \
  };
DEF_MM(8, false, "bf16", ACC4, R4S, 4, 5, 6, 7, 8, 9, 10, 11)
DEF_MM(16, false, "bf16", ACC8, R8S, 8, 9, 10, 11, 12, 13, 14, 15)
DEF_MM(32, false, "bf16", ACC16, R16S, 16, 17, 18, 19, 20, 21, 22, 23)
DEF_MM(40, false, "bf16", ACC20, R20S, 20, 21, 22, 23, 24, 25, 26, 27)
DEF_MM(48, false, "bf16", ACC24, R24S, 24, 25, 26, 27, 28, 29, 30, 31)
DEF_MM(64, false, "bf16", ACC32, R32S, 32, 33, 34, 35, 36, 37, 38, 39)
DEF_MM(32, true, "f16", ACC16, R16S, 16, 17, 18, 19, 20, 21, 22, 23)
DEF_MM(64, true, "f16", ACC32, R32S, 32, 33, 34, 35, 36, 37, 38, 39)

#define LAG 10
#define NSTEP (NSEG + LAG)
#define NR (NSTEP + 1)
__device__ __align__(1024) __nv_bfloat16 g_xn[2][S_LEN * DM];
#define RO 16
static_assert(RO > LAG + 1, "ring");
__device__ __align__(1024) unsigned char g_o[RO * 96 * 8192];
__device__ __align__(1024) uint32_t g_part[6][7][40][64];
#define RD 16
static_assert(2 * RD <= NSEG && NR < 96, "the tags of the last lap differ from those of the first");
#define TILE_B 81920
__device__ __align__(1024) float2 g_stat[S_LEN];
__device__ __align__(1024) uint32_t g_st2[2][RD][64];
__device__ __align__(1024) unsigned char g_acc[4][RD][TILE_B];
#define NOP 19
#define NW12 5
#define NW34 12
#define NBC (NOP + NW12 + NW34)
__device__ __align__(1024) unsigned char g_wt[NOP * 10 * 12288];
enum { F_O = 0, F_R1 = NOP + 1, F_R2 = F_R1 + 4, F_R3 = F_R2 + 4, F_Z = F_R3 + 4, F_DONE, F_GOT, F_MISC, F_NUM };
__device__ __align__(128) uint32_t g_f[F_NUM][96];
__device__ __align__(128) int g_xready[129][8];
__device__ uint32_t g_tpc[128];
#define TS(i)
#define TSV(i, v)
#define TSN(i)
#define TSD(i, dep)
#define BTS(k, i)
#define BTS2(k, i)
#define RTS(i)
#define RTSD(i, dep)
#define RTS_OUT()
#define CTS(i)
#define PTS(i)
#define PTS1(i)
#define CTS_OUT()
#define GTS(i)

#define CL_SIZE 15
#define NCL 7
#define SSQ 13
#define SSV 16
#define PL_SZ 5376
#define TILE_SBO 2560
#define TILE_GRP 15360
#define WS_SZ ((2 * SSQ + SSV) * 2048)
#define OFF_QK (OFF_WO + 26 * 2048)
#define LAYOUT 2
#define OFF_TILE 0
#define OFF_WS (4 * TILE_GRP)
#define OFF_WO (OFF_WS + WS_SZ)
#define OFF_PL (OFF_QK + 20480)
#define OFF_BAR (OFF_PL + 2 * PL_SZ)
#define STG_Q OFF_TILE
#define STG_K OFF_WO
#define VA 14
#define STG_V2 (OFF_TILE + 27 * 2048)
#define OFF_O (OFF_PL + 4352)
#define LAND(k) (((k) >> 1) * TILE_GRP + ((k) & 1) * 1280)
#define LAND_F (5 * TILE_SBO)
#define OFF_XL (OFF_TILE + 3 * TILE_GRP)
#define OFF_XF (OFF_XL + LAND_F)
#define OFF_WT ((OFF_XL + TILE_SBO + 1023) & ~1023)
#define OFF_TAB (OFF_BAR + 240)
#define OFF_INV (OFF_TAB + 64)
#define OFF_TS (OFF_INV + 128)
#define A_SMEM 232448
static_assert(WS_SZ + 72 * 1024 + 2 * PL_SZ + 4 * TILE_GRP + 512 == A_SMEM && OFF_WS % 1024 == 0 && OFF_WO % 1024 == 0 && SSQ == 13, "smem map");
enum { B_W0 = 0, B_W1, B_F1, B_F2 = B_F1 + 4, B_R1 = B_F2 + 4, B_R2, B_MEMFREE, B_LANDFREE, B_OPEER, B_PLFREE, B_XFREE, B_SB, B_WOF = B_SB + 6, B_WTF, B_RS, B_NUM = B_RS + 4 };
static_assert(B_NUM <= 30, "barriers");
enum { N_C = 0, N_SISS, N_QK, N_V, N_PM, N_TURN, N_PI, N_VGO, N_O, N_PX, N_AB, N_SDONE, N_VDONE, N_G3, N_P, N_OX };

__device__ __forceinline__ bool is_dual(int j) { return j >= LAG && j < NSEG; }
__device__ __forceinline__ int sched_l(int j) { return j < NSEG ? j : NSEG + j - LAG; }
__device__ __forceinline__ int sched_f(int j) { return NSEG + j - LAG; }
__device__ __forceinline__ void wait_cnt(const int* p, int target) {
  int v, n = 0;
  do {
    asm volatile("ld.relaxed.gpu.global.b32 %0, [%1];" : "=r"(v) : "l"(p) : "memory");
    if (v >= target) break;
    if (++n > SPIN_LIMIT) FAIL();
  } while (true);
  asm volatile("fence.acquire.gpu;" ::: "memory");
  asm volatile("fence.proxy.async.global;" ::: "memory");
}
__device__ __forceinline__ void red_release(void* p, uint32_t v) { asm volatile("red.release.gpu.global.add.u32 [%0], %1;" :: "l"(p), "r"(v) : "memory"); }
__device__ __forceinline__ void red_relaxed(void* p, uint32_t v) { asm volatile("red.relaxed.gpu.global.add.u32 [%0], %1;" :: "l"(p), "r"(v) : "memory"); }
#define VMASK 0xa5294a5294ull
__host__ __device__ constexpr int popc40(unsigned long long m) { int c = 0; for (; m; m &= m - 1) c++; return c; }
static_assert(popc40(VMASK) == SSV, "mask");
__host__ __device__ constexpr int ss_idx(int ks, int n) { return n == SSV ? popc40(VMASK & ((1ull << ks) - 1)) : ks * n / 40; }
__host__ __device__ constexpr bool is_ss(int ks, int n) { return ss_idx(ks + 1, n) != ss_idx(ks, n); }
__host__ __device__ constexpr int rs_idx(int ks, int n) { return ks - ss_idx(ks, n); }

#define SL2 (0.07216878364870322f * 1.4426950408889634f)

#define SUM_LOOP 0
struct Desc { Dsc tile, unit, k1, pl, p; };
__device__ __forceinline__ Desc make_desc(const uint64_t* h, uint32_t u, uint32_t e) {
  return {{h[0], e}, {h[1] + u * 128, e}, {h[2], e}, {h[3], e}, {h[4], e}};
}
template <int N, int NSS, int RG, int KS, int K1, int K0 = 0>
__device__ __forceinline__ void proj(float* acc, const uint32_t* W, const Desc& D) {
  if constexpr (KS < K1) {
    constexpr uint32_t BLO = dlo(OFF_TILE + (KS / 10) * TILE_GRP + RG * TILE_SBO + (KS % 10) * 256, 128);
    if constexpr (is_ss(KS, NSS)) MM<N>::template ss<dlo(OFF_WS + ss_idx(KS, NSS) * 2048, 0), BLO, (KS != K0)>(acc, D.unit, D.tile);
    else MM<N>::template rs<BLO, (KS != K0)>(acc, W + rs_idx(KS, NSS) * 4, D.tile);
    proj<N, NSS, RG, KS + 1, K1, K0>(acc, W, D);
  }
}
#define VST 17
template <int KS>
__device__ __forceinline__ void ld_rest(uint32_t* W, const uint32_t* p) {
  if constexpr (KS < 40) {
    if constexpr (!is_ss(KS, SSV) && rs_idx(KS, SSV) >= VST) {
#pragma unroll
      for (int i = 0; i < 4; i++) W[4 * rs_idx(KS, SSV) + i] = __ldg(p + (KS * 16 + (i >> 1) * 8) * (HD / 2) + (i & 1) * 4);
    }
    ld_rest<KS + 1>(W, p);
  }
}
template <int N>
__device__ __forceinline__ void load_w(uint32_t* W, uint32_t stage, int warp, int lane) {
  const int kr = (lane >> 4) * 8 + (lane & 7);
  const int cb = warp * 2 + ((lane >> 3) & 1);
  const uint32_t a0 = stage + kr * 128 + ((cb ^ (lane & 7)) << 4);
#pragma unroll
  for (int i = 0; i < N; i++) ldsm4t(W[4 * i], W[4 * i + 1], W[4 * i + 2], W[4 * i + 3], a0 + i * 2048);
}
template <int N, int G, int U, int OS, int ACC>
__device__ __forceinline__ void wo4(float* d, const Desc& D) {
  constexpr uint32_t WA = (U >= 4 ? OFF_WO + (U - 4) * 2048 : OFF_WT) - G * SSQ * 2048, OB = OS == 0 ? OFF_O : OS == 1 ? OFF_XL : OFF_XF;
  Dsc b = OS ? D.k1 : D.pl;
  b.e = fresh<(U < 16 ? U / 4 : U / 8 - 2) + (N == 8 ? 4 : 0)>(D.unit.e);
  MM<N>::template ss<dlo(WA, 0), dlo(OB, 128), ACC>(d, D.unit, b);
  MM<N>::template ss<dlo(WA + 2048, 0), dlo(OB + 256, 128), 1>(d, D.unit, b);
  MM<N>::template ss<dlo(WA + 4096, 0), dlo(OB + 512, 128), 1>(d, D.unit, b);
  MM<N>::template ss<dlo(WA + 6144, 0), dlo(OB + 768, 128), 1>(d, D.unit, b);
}
__device__ __forceinline__ void wo_coord(int i, int t3, int head, int& c0, int& c1) {
  const int g = i >> 1;
  const int blk = g == 0 ? 9 : (g < 4 ? g - 1 : (g - 4) >> 1) * 3 + t3;
  int sl = g < 4 ? t3 : (g & 1) ? t3 + 1 : t3 + 2;
  if (sl >= 3) sl -= 3;
  c0 = blk * 64; c1 = head * DH + sl * 64 + (i & 1) * 32;
}
__device__ __forceinline__ void tok_softmax(uint32_t sb, int job, int lane) {
  const bool w1 = job & 1;
  const int dg = (lane >> 2) - (lane & 3) * 2;
  const uint32_t lo = sb + OFF_PL + (job >> 1) * PL_SZ + (job & 1) * 1792, l8 = lo + 512 + lane * 8, pa = lo + lane * 4;
  const uint32_t km = job & 2 ? 640 : 512;
  float x[14];
  {
    const uint4 a = lds128(lo + lane * 16);
    const uint2 e = lds64(l8);
    const uint32_t c = lds32(768 + pa);
    x[0] = bf_lo(a.x); x[1] = bf_hi(a.x); x[2] = bf_lo(a.y); x[3] = bf_hi(a.y); x[4] = bf_lo(a.z); x[5] = bf_hi(a.z); x[6] = bf_lo(a.w); x[7] = bf_hi(a.w);
    x[8] = bf_lo(c); x[9] = bf_hi(c); x[10] = bf_lo(e.x); x[11] = bf_hi(e.x); x[12] = bf_lo(e.y); x[13] = bf_hi(e.y);
  }
  if (dg < 0) { x[8] = -INFINITY; if (w1) x[4] = -INFINITY; else x[10] = -INFINITY; }
  if (dg < 1) { x[9] = -INFINITY; if (w1) x[5] = -INFINITY; else x[11] = -INFINITY; }
  const float m4 = fmaxf(x[8], x[9]);
  float m0 = fmaxf(fmaxf(fmaxf(x[0], x[1]), fmaxf(x[2], x[3])), fmaxf(fmaxf(x[4], x[5]), fmaxf(x[6], x[7])));
  float m1 = fmaxf(fmaxf(x[10], x[11]), fmaxf(x[12], x[13]));
  if (w1) m1 = fmaxf(m1, m4); else m0 = fmaxf(m0, m4);
  m0 = fmaxf(m0, __shfl_xor_sync(~0u, m0, 1)); m1 = fmaxf(m1, __shfl_xor_sync(~0u, m1, 1));
  sts32(pa + (w1 ? 384 : 896 + 128), 0u); sts32(pa + 1152 - km, 0u); sts32(pa + 896 + 1152 - km, 0u); sts64(l8 + 896 - 256, 0u, 0u);
  m0 = fmaxf(m0, __shfl_xor_sync(~0u, m0, 2)); m1 = fmaxf(m1, __shfl_xor_sync(~0u, m1, 2));
  m0 *= -SL2; m1 *= -SL2;
#pragma unroll
  for (int j = 0; j < 14; j++) x[j] = ex2(fmaf(x[j], SL2, j < 8 ? m0 : j >= 10 ? m1 : w1 ? m1 : m0));
  const float l4s = x[8] + x[9];
  float l0 = ((x[0] + x[1]) + (x[2] + x[3])) + ((x[4] + x[5]) + (x[6] + x[7])), l1 = (x[10] + x[11]) + (x[12] + x[13]);
  if (w1) l1 += l4s; else l0 += l4s;
  l0 += __shfl_xor_sync(~0u, l0, 1); l1 += __shfl_xor_sync(~0u, l1, 1);
  l0 += __shfl_xor_sync(~0u, l0, 2); l1 += __shfl_xor_sync(~0u, l1, 2);
  l0 = rcpf(l0); l1 = rcpf(l1);
#pragma unroll
  for (int j = 0; j < 7; j++) {
    const float iv = j < 4 ? l0 : j > 4 ? l1 : w1 ? l1 : l0;
    sts32(pa + (j < 3 ? j * 128 : j == 3 ? km : j == 4 ? (w1 ? 896 + 128 : 384) : j == 5 ? 896 : 896 + km), pack2(x[2 * j] * iv, x[2 * j + 1] * iv));
  }
}
template <int N>
__device__ __forceinline__ void wo_phase(uint32_t sb, int wg, int warp, int lane, uint32_t par, uint32_t r1, const Desc& D) {
  const uint32_t bar = sb + OFF_BAR;
  float x[N / 2], y[N / 2];
  const uint2 ta = lds64(sb + OFF_TAB + (wg * 4 + warp) * 8);
  uint32_t xa = (ta.x & ~255u) + lane * 8, xb = (ta.x & 0xFF0000FFu) + SMEM0 + OFF_BAR, ya = (ta.y & ~255u) + lane * 8, yb = (ta.y & 0xFF0000FFu) + SMEM0 + OFF_BAR;
  asm volatile("" : "+r"(xa), "+r"(xb), "+r"(ya), "+r"(yb));
  auto scat = [&](uint32_t ad, uint32_t mb, const float* d) {
    st_async_v2(ad, pack2(d[0], d[1]), pack2(d[2], d[3]), mb);
    if (N == 16) st_async_v2(ad + LAND_F, pack2(d[4], d[5]), pack2(d[6], d[7]), mb);
  };
  if (wg == 0) {
    bar_sync(N_O, 384);
    wg_fence(); wo4<N, 0, 4, 0, 0>(x, D); wo4<N, 0, 8, 0, 0>(y, D); wg_commit();
    mbar_waitu(bar + 8 * B_OPEER, par);
    CFENCE(); wg_fence(); wo4<N, 0, 16, 1, 1>(x, D); wo4<N, 0, 20, 2, 1>(x, D); wg_commit();
    wo4<N, 0, 24, 1, 1>(y, D); wg_commit();
    mbar_waitu2(bar + 8 * B_WOF, bar + 8 * B_MEMFREE, par);
    wg_fence(); wo4<N, 0, 28, 2, 1>(y, D); wg_commit();
    bar_arrive(N_AB, 256);
    wg_wait<2>(); scat(xa, xb, x);
    wg_wait<0>(); scat(ya, yb, y);
  } else {
    bar_sync(N_O, 384);
    wg_fence(); wo4<N, 1, 0, 0, 0>(x, D); wg_commit(); wo4<N, 1, 12, 0, 0>(y, D); wg_commit();
    wg_wait<1>(); mbar_arrive_remote_if(lane == 0, r1);
    mbar_waitu(bar + 8 * B_MEMFREE, par);
    scat(xa, xb, x);
    bar_sync(N_AB, 256);
    CFENCE(); wg_fence(); wo4<N, 1, 32, 1, 1>(y, D); wo4<N, 1, 36, 2, 1>(y, D); wg_commit();
    bar_arrive(N_TURN, 256);
    wg_wait<0>(); scat(ya, yb, y);
  }
}
#define DS_DUAL 10
#define DS_SINGLE 20
#define POLL_GAP 100
#define POLL_GAPD 0
#define TOK_DELAY 250
#define LATE_SM 1
#define UMAX 40
#define VD1 10
#define VS2 20
#define IG_V 3
#define VS1 4
struct AMaps { CUtensorMap w16[3], wo32; uint64_t d[5]; const __nv_bfloat16* wv; };
__global__ void __launch_bounds__(512, 1)
acore_kernel(const __grid_constant__ AMaps M, const __nv_bfloat16* __restrict__ mem0, int sync_b) {
  extern __shared__ __align__(1024) unsigned char smem_raw[];
  const uint32_t sb = smem_u32(smem_raw);
  GTS(24);
  if (threadIdx.x == 480) {
    uint32_t smid; asm volatile("mov.u32 %0, %%smid;" : "=r"(smid));
    g_tpc[(smid >> 1) & 127] = blockIdx.x - CL_SIZE < 3 * CL_SIZE && blockIdx.x % CL_SIZE >= 12 ? 1 : 2;
    asm volatile("griddepcontrol.launch_dependents;");
  }
  const int lane0 = threadIdx.x & 31;
#define LANE_INIT() int lane; asm volatile("mov.u32 %0, %%laneid;" : "=r"(lane))
  const int warp = __shfl_sync(~0u, (threadIdx.x >> 5) & 3, 0);
  const int cl = blockIdx.x / CL_SIZE;
  const uint32_t rank = blockIdx.x - cl * CL_SIZE;
  const int nh = cl >= 1 && cl <= 3 ? 4 : 5;
  const int nA = 3 * nh;
  const int wg = __shfl_sync(~0u, (int)rank < nA ? threadIdx.x >> 7 : 4, 0);
  const int head = (cl < 4 ? (cl ? 1 + 4 * cl : 0) : 5 * cl - 3) + rank / 3;
  const int t3 = rank % 3;
  const int col0 = head * DH + t3 * 64;
  const uint32_t bar = sb + OFF_BAR;
  const uint32_t rb0 = SMEM0;
  const uint16_t mcmask = (uint16_t)((1u << nA) - 1);
  const uint32_t nxt = sb + ((t3 == 2 ? -2 : 1) << 24), prv = sb + ((t3 == 0 ? 2 : -1) << 24);
  const int ig = (int)rank - (nA - 4);

  if (threadIdx.x == 0) {
    if (mapa(sb, nA - 1) != rb0 + ((nA - 1) << 24) || mapa(sb, 0) != rb0 || mapa(sb, 1) != rb0 + (1u << 24) || sb != SMEM0 + (rank << 24)) FAIL();
    for (int i = 0; i < B_NUM; i++)
      mbar_init(bar + 8 * i, i == B_R1 ? 4 * nA : i == B_R2 ? 12 * nA : i == B_MEMFREE ? nA : i == B_LANDFREE ? 4 * nA : i == B_PLFREE || i == B_XFREE ? 2 : 1);
    asm volatile("fence.mbarrier_init.release.cluster;" ::: "memory");
    mbar_expect(bar + 8 * B_W0, (80 + SSV + VST) * 2048);
  }
  __syncthreads();
  if (lane0 == 0) {
    const int w12 = wg * 4 + warp;
    if (w12 < 10) {
#pragma unroll 1
      for (int ks = 4 * w12; ks < 4 * w12 + 4; ks++) {
        const bool ss = is_ss(ks, SSQ);
        tma2d(ss ? sb + OFF_WS + ss_idx(ks, SSQ) * 2048 : sb + STG_Q + rs_idx(ks, SSQ) * 2048, &M.w16[0], col0, ks * 16, bar + 8 * B_W0);
        tma2d(ss ? sb + OFF_WS + (SSQ + ss_idx(ks, SSQ)) * 2048 : sb + STG_K + rs_idx(ks, SSQ) * 2048, &M.w16[1], col0, ks * 16, bar + 8 * B_W0);
        if (is_ss(ks, SSV)) tma2d(sb + OFF_WS + (2 * SSQ + ss_idx(ks, SSV)) * 2048, &M.w16[2], col0, ks * 16, bar + 8 * B_W0);
        else if (rs_idx(ks, SSV) < VST) tma2d(sb + (rs_idx(ks, SSV) < VA ? STG_K + 27 * 2048 : STG_V2 - VA * 2048) + rs_idx(ks, SSV) * 2048, &M.w16[2], col0, ks * 16, bar + 8 * B_W0);
      }
    }
  }
  if (lane0 < 2 && wg < 2) {
    const int u = 4 * (wg ? (lane0 ? 6 + t3 : 9) : (lane0 ? 3 + t3 : t3)) + warp;
    const int li = (u >= nA) + (u >= 2 * nA) + (u >= 3 * nA);
    sts32(sb + OFF_TAB + (wg * 4 + warp) * 8 + lane0 * 4,
          rb0 + ((u - li * nA) << 24) + OFF_TILE + LAND(li + (u >= 36 ? t3 : 0)) + (rank / 3) * 256 + 8 * (B_RS + li));
  }
  __syncthreads();
  GTS(25);

  auto issue_tok = [&](int sc, int fb, int rel = -1, uint32_t ph = 0) {
    if (sync_b) wait_cnt(&g_xready[sc][0], 32);
    if (rel >= 0) mbar_waitu(bar + 8 * rel, ph);
    bulk_g2s_mc_e(sb + OFF_TILE + ig * TILE_GRP + TILE_SBO, &g_xn[0][0] + uni(sc * (32 * DM)) + ig * 5120, 10240, bar + 8 * (fb + ig), mcmask);
  };
#define POLL(d, q) _Pragma("unroll") for (int k = 0; k < NCL; k++) \
      asm volatile("ld.relaxed.gpu.global.v2.b32 {%0,%1}, [%2];" : "=r"(d[k].x), "=r"(d[k].y) : "l"(q + k * 2560) : "memory")
#define L3(L, a, b, c) lop3<L>(a, b, c)
#define TAGS(L, d) L3(L, L3(L, L3(L, d[0].x, d[0].y, d[1].x), L3(L, d[1].y, d[2].x, d[2].y), L3(L, d[3].x, d[3].y, d[4].x)), L3(L, d[4].y, d[5].x, d[5].y), L3(L, d[6].x, d[6].y, d[6].y))
    auto deliver = [&](uint2* pa, const uint32_t* gq, int u, int c, int dc, int ds, int step, bool first, int lane) {
      const uint32_t off = uni(OFF_TILE + ((u * 205) >> 11) * (TILE_GRP - TILE_SBO) + u * 256 + dc * LAND_F), boff = uni(OFF_BAR + 8 * (B_F1 + ((u * 205) >> 11)));
      const uint32_t* mi = &g_part[4][0][0][0] + uni((c * NCL + cl) * 2560 + u * 64);
      mbar_waitu(bar + 8 * B_LANDFREE, step & 1);
      int n = 0;
      while (true) {
        const bool ok = __all_sync(~0u, ((step & 2 ? ~TAGS(0xFE, pa) : TAGS(0x80, pa)) & 1) != 0);
        if (ok) break;
        if (++n > SPIN_LIMIT) FAIL();
        POLL(pa, gq);
      }
      if (warp == 0 && first) { TS(19); TSV(10, n); }
      const uint32_t w0 = hadd2bf(hadd2bf(hadd2bf(pa[0].x, pa[1].x), hadd2bf(pa[2].x, pa[3].x)), hadd2bf(hadd2bf(pa[4].x, pa[5].x), pa[6].x));
      const uint32_t w1 = hadd2bf(hadd2bf(hadd2bf(pa[0].y, pa[1].y), hadd2bf(pa[2].y, pa[3].y)), hadd2bf(hadd2bf(pa[4].y, pa[5].y), pa[6].y));
      if (u < ds) {
        const uint32_t da = SMEM0 + off + lane * 8, db = SMEM0 + boff;
#pragma unroll
        for (int d = 0; d < 12; d++) st_async_v2((d << 24) + da, w0, w1, (d << 24) + db);
#pragma unroll
        for (int d = 12; d < 15; d++) st_async_v2_if(nA == 15, (d << 24) + da, w0, w1, (d << 24) + db);
      } else {
        *reinterpret_cast<uint2*>(const_cast<uint32_t*>(gq) + ((4 - 2 * (step & 1)) * NCL + cl) * 2560) = make_uint2(w0, w1);
        asm volatile("fence.proxy.async.global;" ::: "memory");
        __syncwarp();
        bulk_g2s_mc_e(sb + off, mi, 256, sb + boff, mcmask);
      }
    };
#define REL(b, g) mbar_arrive_remote_if(lane == 0, rb0 + ((nA - 4 + (g)) << 24) + OFF_BAR + 8 * (b))

  if (wg < 2) {
    asm volatile("setmaxnreg.inc.sync.aligned.u32 160;");
    LANE_INIT();
    uint32_t W[4 * (40 - SSQ)];
    mbar_waitw(bar + 8 * B_W0, 0);
    GTS(26);
    load_w<40 - SSQ>(W, sb + (wg ? STG_K : STG_Q), warp, lane);
    fence_async();
    bar_sync(1, 384);
    cluster_sync_all();
#define DESC(k) const Desc D = make_desc(M.d, min(wg, 2) * SSQ, fresh<k>(step))
    GTS(27);
#pragma unroll 1
    for (int step = -1; step < NSTEP; step++) {
      const uint32_t par = step & 1;
      asm volatile("" : "+r"(lane));
      const bool dual = is_dual(step), has_next = step + 1 < NSTEP;
#define QK_SA (sb + OFF_QK + wg * 15360 + (2 * warp + ((lane >> 3) & 1)) * 128 + (lane & 7) * 16)
#define QK_F (wg ? -5120 : 5120)
#define QK_S12 ((wg ? (lane >> 4) : 1 + 2 * (lane >> 4)) * 1024)
#define QK_S34 ((wg ? 2 + (lane >> 4) : 2 - 2 * (lane >> 4)) * 1024)
      if (step >= 0) {
        if (dual) {
          DESC(0);
          float acc[24];
          mbar_waitu(bar + 8 * (B_F1 + 0), par);
          if (wg + warp == 0) { TS(0); TSN(1); }
          CFENCE(); wg_fence(); proj<48, SSQ, 0, 0, 10>(acc, W, D); wg_commit();
          mbar_waitu(bar + 8 * (B_F1 + 1), par);
          CFENCE(); wg_fence(); proj<48, SSQ, 0, 10, 20>(acc, W, D); wg_commit();
          mbar_waitu(bar + 8 * (B_F1 + 2), par);
          CFENCE(); wg_fence(); proj<48, SSQ, 0, 20, 30>(acc, W, D); wg_commit();
          mbar_waitu(bar + 8 * (B_F1 + 3), par);
          if (wg + warp == 0) TS(2);
          CFENCE(); wg_fence(); proj<48, SSQ, 0, 30, 40>(acc, W, D); wg_commit();
          bar_arrive(N_VGO, 384);
          mbar_waitu(bar + 8 * B_PLFREE, par);
          const uint32_t sa = QK_SA, s0 = sa + 4096 + (lane >> 4) * QK_F, s1 = sa + QK_F + QK_S12, s2 = sa + QK_F + QK_S34;
          wg_wait<0>();
          if (wg + warp == 0) TS(3);
          stsm4t(s0, pack2(acc[0], acc[1]), pack2(acc[2], acc[3]), pack2(acc[20], acc[21]), pack2(acc[22], acc[23]));
          stsm4t(s1, pack2(acc[4], acc[5]), pack2(acc[6], acc[7]), pack2(acc[8], acc[9]), pack2(acc[10], acc[11]));
          stsm4t(s2, pack2(acc[12], acc[13]), pack2(acc[14], acc[15]), pack2(acc[16], acc[17]), pack2(acc[18], acc[19]));
        } else {
          DESC(1);
          float acc[4];
          mbar_waitu(bar + 8 * (B_F1 + 0), par);
          if (wg + warp == 0) { TS(0); TSN(1); }
          CFENCE(); wg_fence(); proj<8, SSQ, 0, 0, 10>(acc, W, D); wg_commit();
          mbar_waitu(bar + 8 * (B_F1 + 1), par);
          CFENCE(); wg_fence(); proj<8, SSQ, 0, 10, 20>(acc, W, D); wg_commit();
          mbar_waitu(bar + 8 * (B_F1 + 2), par);
          CFENCE(); wg_fence(); proj<8, SSQ, 0, 20, 30>(acc, W, D); wg_commit();
          mbar_waitu(bar + 8 * (B_F1 + 3), par);
          if (wg + warp == 0) TS(2);
          CFENCE(); wg_fence(); proj<8, SSQ, 0, 30, 40>(acc, W, D); wg_commit();
          bar_arrive(N_VGO, 384);
          mbar_waitu(bar + 8 * B_PLFREE, par);
          const uint32_t s0 = QK_SA + 4096;
          wg_wait<0>();
          if (wg + warp == 0) TS(3);
          stsm2t(s0, pack2(acc[0], acc[1]), pack2(acc[2], acc[3]));
        }
        fence_async();
        bar_sync(N_QK, 256);
        if (wg == 0 || dual) {
          float s[20];
          DESC(2);
          const Dsc ab = D.k1 + wg * 192, bb = D.k1 + (1 - wg) * 320;
          wg_fence();
          MM<40>::ss<dlo(OFF_QK, 128), dlo(OFF_QK + 10240, 128), 0, 0>(s, ab, bb);
          MM<40>::ss<dlo(OFF_QK + 256, 128), dlo(OFF_QK + 10240 + 256, 128), 1, 0>(s, ab, bb);
          MM<40>::ss<dlo(OFF_QK + 512, 128), dlo(OFF_QK + 10240 + 512, 128), 1, 0>(s, ab, bb);
          MM<40>::ss<dlo(OFF_QK + 768, 128), dlo(OFF_QK + 10240 + 768, 128), 1, 0>(s, ab, bb);
          wg_commit();
          bar_arrive(N_SISS, 384);
          const int rw = (warp - wg) & 3;
          const uint32_t bo = OFF_BAR + 8 * (B_SB + 3 * wg + rw), lo = OFF_PL + wg * PL_SZ + rw * 1792;
          const uint32_t km = wg ? 640 : 512;
          uint32_t l16 = lo + lane * 16, l4 = lo + lane * 4;
          mbar_expect_if(lane == 0 && rw < 3, sb + bo, rw < 2 ? 1792 : 1280);
          asm volatile("" : "+r"(l16), "+r"(l4));
          if (rw == 2) {
            wg_wait<0>();
            if (wg == 0) TSD(4, __float_as_uint(s[0]));
            const uint32_t w0 = pack2(s[0], s[1]), w1 = pack2(s[4], s[5]), w2 = pack2(s[8], s[9]), w3 = pack2(s[12], s[13]), w4 = pack2(s[16], s[17]);
            {
              st_async_v4(nxt + 896 + l16, w0, w1, w2, w3, nxt + bo);
              st_async_v4(prv + l16, w0, w1, w2, w3, prv + bo);
              st_async_b32(nxt + 896 + 768 + l4, w4, nxt + bo);
              st_async_b32(prv + 768 + l4, w4, prv + bo);
            }
            bar_arrive(N_SDONE, 256);
            mbar_waitu(sb + bo, (step - wg * LAG) & 1);
            if (wg == 0) TS(5);
            float x[10], m0;
            {
              const uint4 a = lds128(sb + l16), b = lds128(sb + 896 + l16);
              const uint32_t c = lds32(sb + 768 + l4), d = lds32(sb + 896 + 768 + l4);
              const uint32_t e0 = hadd2bf(hadd2bf(a.x, b.x), w0), e1 = hadd2bf(hadd2bf(a.y, b.y), w1), e2 = hadd2bf(hadd2bf(a.z, b.z), w2),
                             e3 = hadd2bf(hadd2bf(a.w, b.w), w3), e4 = hadd2bf(hadd2bf(c, d), w4);
              const uint32_t em = hmax2bf(hmax2bf(hmax2bf(e0, e1), hmax2bf(e2, e3)), e4);
              m0 = fmaxf(bf_lo(em), bf_hi(em));
              x[0] = bf_lo(e0); x[1] = bf_hi(e0); x[2] = bf_lo(e1); x[3] = bf_hi(e1); x[4] = bf_lo(e2);
              x[5] = bf_hi(e2); x[6] = bf_lo(e3); x[7] = bf_hi(e3); x[8] = bf_lo(e4); x[9] = bf_hi(e4);
            }
            m0 = fmaxf(m0, __shfl_xor_sync(~0u, m0, 1));
            sts32(sb + l4 + 1152 - km, 0u);
            m0 = fmaxf(m0, __shfl_xor_sync(~0u, m0, 2));
            m0 *= -SL2;
#pragma unroll
            for (int j = 0; j < 5; j++) {
              x[2 * j] = ex2(fmaf(x[2 * j], SL2, m0)); x[2 * j + 1] = ex2(fmaf(x[2 * j + 1], SL2, m0));
              sts32(sb + l4 + (j < 4 ? j * 128 : km), pack2(x[2 * j], x[2 * j + 1]));
            }
            float l = ((x[0] + x[1]) + (x[2] + x[3])) + ((x[4] + x[5]) + ((x[6] + x[7]) + (x[8] + x[9])));
            l += __shfl_xor_sync(~0u, l, 1);
            fence_async();
            sts32(sb + OFF_INV + wg * 64 + (lane >> 1) * 4, __float_as_uint(l));
            bar_arrive(N_PM, dual ? 224 : 192);
            if (wg == 0) TS(6);
          } else if (rw < 2) {
            const bool w1 = rw == 1;
            const uint32_t l8 = lo + 512 + lane * 8;
            uint32_t tw[7];
            wg_wait<0>();
            bar_arrive(N_SDONE, 256);
            tw[0] = pack2(s[0], s[1]); tw[1] = pack2(s[4], s[5]); tw[2] = pack2(s[8], s[9]); tw[3] = pack2(s[16], s[17]);
            tw[4] = w1 ? pack2(s[6], s[7]) : pack2(s[12], s[13]); tw[5] = pack2(s[2], s[3]); tw[6] = pack2(s[18], s[19]);
            { const uint32_t t0 = clock32(); while (clock32() - t0 < TOK_DELAY) {} }
            st_async_v4(nxt + 896 + l16, tw[0], tw[1], tw[2], tw[3], nxt + bo);
            st_async_v4(prv + l16, tw[0], tw[1], tw[2], tw[3], prv + bo);
            st_async_v2(nxt + 896 + l8, tw[5], tw[6], nxt + bo);
            st_async_v2(prv + l8, tw[5], tw[6], prv + bo);
            st_async_b32(nxt + 896 + 768 + l4, tw[4], nxt + bo);
            st_async_b32(prv + 768 + l4, tw[4], prv + bo);
            mbar_waitu(sb + bo, (step - wg * LAG) & 1);
            const uint4 a = lds128(sb + l16), b = lds128(sb + 896 + l16);
            const uint2 e = lds64(sb + l8), f = lds64(sb + 896 + l8);
            const uint32_t c = lds32(sb + 768 + l4), d = lds32(sb + 896 + 768 + l4);
            sts128(sb + l16, hadd2bf(hadd2bf(a.x, b.x), tw[0]), hadd2bf(hadd2bf(a.y, b.y), tw[1]), hadd2bf(hadd2bf(a.z, b.z), tw[2]), hadd2bf(hadd2bf(a.w, b.w), tw[3]));
            sts64(sb + l8, hadd2bf(hadd2bf(e.x, f.x), tw[5]), hadd2bf(hadd2bf(e.y, f.y), tw[6]));
            sts32(sb + 768 + l4, hadd2bf(hadd2bf(c, d), tw[4]));
            bar_arrive(N_PX, dual ? 256 : 192);
            if (wg + warp == 0) TS(9);
          } else {
            wg_wait<0>();
            if (wg == 0) {
              mbar_expect_if(lane < 3 && has_next, bar + 8 * (lane == 2 ? B_OPEER : B_WOF + lane), lane == 2 ? (dual ? 4096 : 2048) : lane ? 8192 : 20480);
              auto fetch = [&](int i, int n, uint32_t dst, int mb) {
                int c0, c1; wo_coord(i, t3, head, c0, c1);
                tma2d_e(dst, &M.wo32, c0, c1, bar + 8 * mb); if (n == 2) tma2d_e(dst + 4096, &M.wo32, c0, c1 + 32, bar + 8 * mb);
              };
              bar_sync(N_G3, 160);
              if (has_next) {
                fetch(0, 2, sb + OFF_WT, B_WTF);
                mbar_arrive_remote_if(lane < 2, (lane ? nxt : prv) + OFF_BAR + 8 * B_XFREE);
              }
              bar_sync(N_SDONE, 256);
              if (has_next) {
                fetch(15, 1, sb + OFF_QK, B_WOF); fetch(16, 2, sb + OFF_QK + 4096, B_WOF); fetch(18, 2, sb + OFF_QK + 12288, B_WOF);
                mbar_waitu(bar + 8 * B_XFREE, par);
              }
              bar_arrive(N_PM, dual ? 224 : 192);
              bar_sync(N_VDONE, 160);
              mbar_arrive_remote_if(lane < nA && has_next, rb0 + (lane << 24) + OFF_BAR + 8 * B_MEMFREE);
              if (has_next) mbar_waitu(bar + 8 * B_WTF, par);
            } else {
              bar_arrive(N_SDONE, 256);
              if ((unsigned)ig < IG_V) issue_tok(sched_l(step + 1), B_F2, B_R1, (step - LAG) & 1);
            }
          }
        } else {
          bar_arrive(N_SISS, 384);
          bar_arrive(N_SDONE, 256);
        }
        if (has_next) {
          if (step == 0) mbar_waitw(bar + 8 * B_W1, 0);
          const uint32_t r1 = rb0 + ((nA - 1) << 24) + OFF_BAR + 8 * B_R1;
          if (dual) { DESC(3); wo_phase<16>(sb, wg, warp, lane, par, r1, D); } else { DESC(4); wo_phase<8>(sb, wg, warp, lane, par, r1, D); }
          bar_arrive(N_C, 288);
          if (warp == 0) TS(7 + wg);
        }
      }
      if (has_next) {
        DESC(5);
        float acc[16];
        mbar_waitu(bar + 8 * B_F2, par ^ 1);
        wg_fence(); proj<32, SSQ, 1, 0, 10>(acc, W, D); wg_commit();
        mbar_waitu(bar + 8 * (B_F2 + 1), par ^ 1);
        wg_fence(); proj<32, SSQ, 1, 10, 14>(acc, W, D); wg_commit();
        wg_wait<1>(); REL(B_R2, 0);
        wg_fence(); proj<32, SSQ, 1, 14, 20>(acc, W, D); wg_commit();
        mbar_waitu(bar + 8 * (B_F2 + 2), par ^ 1);
        wg_fence(); proj<32, SSQ, 1, 20, 24>(acc, W, D); wg_commit();
        wg_wait<1>(); REL(B_R2, 1);
        wg_fence(); proj<32, SSQ, 1, 24, 30>(acc, W, D); wg_commit();
        mbar_waitu(bar + 8 * (B_F2 + 3), par ^ 1);
        wg_fence(); proj<32, SSQ, 1, 30, 34>(acc, W, D); wg_commit();
        wg_wait<1>(); REL(B_R2, 2);
        wg_fence(); proj<32, SSQ, 1, 34, 40>(acc, W, D); wg_commit();
        const uint32_t sa = QK_SA, s1 = sa + QK_S12, s2 = sa + QK_S34;
        wg_wait<0>(); REL(B_R2, 3);
        if (warp == 0) TS(11 + wg);
        stsm4t(s1, pack2(acc[0], acc[1]), pack2(acc[2], acc[3]), pack2(acc[4], acc[5]), pack2(acc[6], acc[7]));
        stsm4t(s2, pack2(acc[8], acc[9]), pack2(acc[10], acc[11]), pack2(acc[12], acc[13]), pack2(acc[14], acc[15]));
      }
    }
    GTS(28);
    cluster_sync_all();
  } else if (wg == 2) {
    asm volatile("setmaxnreg.inc.sync.aligned.u32 160;");
    LANE_INIT();
    uint32_t W[4 * (40 - SSV)];
    ld_rest<0>(W, reinterpret_cast<const uint32_t*>(M.wv + (lane >> 2) * HD + col0 + warp * 16) + (lane & 3));
    uint4 m0[5];
#pragma unroll
    for (int i = 0; i < 5; i++) {
      const int t = i * 128 + warp * 32 + lane;
      m0[i] = __ldg(reinterpret_cast<const uint4*>(mem0 + ((t >> 1) & 7) * DM + (t >> 4) * 16 + ((t ^ (t >> 3)) & 1) * 8));
    }
    mbar_waitw(bar + 8 * B_W0, 0);
    load_w<VA>(W, sb + STG_K + 27 * 2048, warp, lane);
    load_w<VST - VA>(W + 4 * VA, sb + STG_V2, warp, lane);
    fence_async();
    mbar_expect_if(warp + lane == 0, bar + 8 * B_W1, 26 * 2048);
    bar_sync(1, 384);
#pragma unroll
    for (int i = 0; i < 5; i++) {
      const int t = i * 128 + warp * 32 + lane;
      sts128(sb + OFF_TILE + (t / 160) * (TILE_GRP - TILE_SBO) + t * 16, m0[i].x, m0[i].y, m0[i].z, m0[i].w);
    }
#pragma unroll
    for (int i = 4 * VST; i < 4 * (40 - SSV); i++) W[i] = movm(W[i]);
    fence_async();
    mbar_arrive_if(lane == 0, bar + 8 * (B_F1 + warp));
    mbar_expect_if(lane == 0, bar + 8 * (B_F2 + warp), 10240);
    mbar_arrive_if(warp == 3 && lane < 2, bar + 8 * B_PLFREE);
    cluster_sync_all();
    uint32_t vl[8];
    {
      const int step = warp;
      DESC(0);
      float v[16];
      mbar_waitw4(bar + 8 * B_F2, 0);
      wg_fence(); proj<32, SSV, 1, 0, 40>(v, W, D); wg_commit();
      wg_wait<0>();
      mbar_arrive_remote_if(lane < 4, rb0 + ((nA - 4 + lane) << 24) + OFF_BAR + 8 * B_R2);
#pragma unroll
      for (int j = 0; j < 8; j++) vl[j] = pack2v(v[2 * j], v[2 * j + 1]);
      if (warp == 0 && (unsigned)ig < 3) issue_tok(1, B_F2, B_R2, 0);
    }
#pragma unroll 1
    for (int step = 0; step < NSTEP; step++) {
      const uint32_t par = step & 1;
      asm volatile("" : "+r"(lane));
      const bool dual = is_dual(step), has_next = step + 1 < NSTEP;
      mbar_expect_if(lane == 0 && has_next, bar + 8 * (B_F2 + warp), 10240);
      if (warp == 0 && ig >= IG_V && dual && sync_b) wait_cnt(&g_xready[sched_l(step + 1)][0], 32);
      bar_sync(N_VGO, 384);
      CFENCE();
#define F1_BYTES (is_dual(step + 1) ? 15360 : 2560)
#define ARM() do { \
        mbar_expect_if(lane == 0 && has_next, bar + 8 * (B_F1 + warp), F1_BYTES); \
        mbar_expect_if(lane == 0 && has_next && warp * nA + (int)rank < 40, bar + 8 * (B_RS + warp), (warp * nA + (int)rank >= 36 ? nA : nh) * (dual ? 512 : 256)); } while (0)
#define O_ADDR() uint32_t oa = sb + OFF_O + (lane >> 4) * PL_SZ + warp * 256 + (lane & 15) * 16, xo = (lane >> 4) * 1024 + warp * 256 + (lane & 15) * 16; \
        asm volatile("" : "+r"(oa), "+r"(xo))
#define O_READY(act) do { if (has_next) { const uint4 ov = lds128(oa); \
        if (act) { st_async_v4(nxt + OFF_XL + xo, ov.x, ov.y, ov.z, ov.w, nxt + OFF_BAR + 8 * B_OPEER); \
                   st_async_v4(prv + OFF_XF + xo, ov.x, ov.y, ov.z, ov.w, prv + OFF_BAR + 8 * B_OPEER); } \
        fence_async(); bar_arrive(N_O, 384); } \
        if (warp == 0) TS(15); } while (0)
#define TOK_L3(g0) if (warp == 0 && ig >= (g0) && has_next) { mbar_waitu(bar + 8 * B_R1, ig == 3 ? par : (step - LAG) & 1); asm volatile("fence.proxy.async.global;" ::: "memory"); \
        bulk_g2s_mc_e(sb + OFF_TILE + ig * TILE_GRP + TILE_SBO, &g_xn[0][0] + uni(sched_l(step + 1) * (32 * DM)) + ig * 5120, 10240, bar + 8 * (B_F2 + ig), mcmask); }
#define OX_ADDR() const bool ox = head * 3 + t3 == 95; \
        const uint32_t oxa = sb + OFF_PL + (ox ? warp * 1024 + (lane & 7) * 32 + ((((lane >> 3) ^ (lane >> 2)) & 1) << 4) : (lane & 7) * 128 + (((warp * 2 + ((lane >> 3) & 1)) ^ (lane & 7)) << 4)); \
        const uint32_t s1 = oxa + ((lane < 16 ? 3072 : 0) >> (ox ? 2 : 0)), s2 = oxa + ((lane < 16 ? 2048 : 1024) >> (ox ? 2 : 0))
      if (dual) {
        uint32_t vf[8], vm[4], vn[8];
        {
          DESC(0);
          float v[24];
          ARM();
          wg_fence(); proj<48, SSV, 0, 30, 40, 30>(v, W, D); wg_commit();
          proj<48, SSV, 0, 0, VD1 - 10, 30>(v, W, D);
          bar_sync(N_SISS, 384);
          proj<48, SSV, 0, VD1 - 10, VD1 - 7, 30>(v, W, D); wg_commit();
          wg_wait<1>(); bar_arrive(N_G3, 160);
          wg_fence(); proj<48, SSV, 0, VD1 - 7, 10, 30>(v, W, D); wg_commit();
          proj<48, SSV, 0, 10, 13, 30>(v, W, D); wg_commit();
          wg_wait<1>(); REL(B_R1, 0);
          wg_fence(); proj<48, SSV, 0, 13, 20, 30>(v, W, D); wg_commit();
          proj<48, SSV, 0, 20, 23, 30>(v, W, D); wg_commit();
          wg_wait<1>(); REL(B_R1, 1);
          wg_fence(); proj<48, SSV, 0, 23, 30, 30>(v, W, D); wg_commit();
          wg_wait<0>(); REL(B_R1, 2);
          bar_arrive(N_VDONE, 160);
          if (warp == 0) TS(14);
#pragma unroll
          for (int j = 4; j < 8; j++) vf[j] = pack2v(v[4 + 2 * j], v[5 + 2 * j]);
          keep4(vf + 4, lane);
          vm[0] = pack2v(v[0], v[1]); vm[1] = pack2v(v[2], v[3]); vm[2] = pack2v(v[20], v[21]); vm[3] = pack2v(v[22], v[23]);
          keep4(vm, lane);
#pragma unroll
          for (int j = 0; j < 4; j++) vf[j] = pack2v(v[4 + 2 * j], v[5 + 2 * j]);
          keep4(vf, lane);
        }
        {
          DESC(1);
          float o[8];
          O_ADDR();
          bar_sync(N_PM, 224);
          wg_fence();
          MM<8>::rs<dlo(OFF_PL + 3584, 128), 0>(o, vl, D.p);
          MM<8>::rs<dlo(OFF_PL + PL_SZ + 3584, 128), 0>(o + 4, vf, D.p);
          MM<8>::rs<dlo(OFF_PL + 3584 + 256, 128), 1>(o, vl + 4, D.p);
          MM<8>::rs<dlo(OFF_PL + PL_SZ + 3584 + 256, 128), 1>(o + 4, vf + 4, D.p);
          MM<8>::rs<dlo(OFF_PL + 3584 + 512, 128), 1>(o, vm, D.p);
          MM<8>::rs<dlo(OFF_PL + PL_SZ + 3584 + 512, 128), 1>(o + 4, vm, D.p);
          wg_commit();
          fence_sched(step);
          const uint4 il = lds128(sb + OFF_INV + (lane & 3) * 16), jf = lds128(sb + OFF_INV + 64 + (lane & 3) * 16);
          const float i0 = rcpf(__uint_as_float(il.x) + __uint_as_float(il.y)), i1 = rcpf(__uint_as_float(il.z) + __uint_as_float(il.w));
          const float j0 = rcpf(__uint_as_float(jf.x) + __uint_as_float(jf.y)), j1 = rcpf(__uint_as_float(jf.z) + __uint_as_float(jf.w));
          { const uint32_t k4[4] = {__float_as_uint(i0), __float_as_uint(i1), __float_as_uint(j0), __float_as_uint(j1)}; keep4(k4, lane | (oa ^ xo)); }
          wg_wait<0>();
          stsm4t(oa, pack2(o[0] * i0, o[1] * i1), pack2(o[2] * i0, o[3] * i1), pack2(o[4] * j0, o[5] * j1), pack2(o[6] * j0, o[7] * j1));
          O_READY(true);
          TOK_L3(IG_V);
        }
        {
          DESC(2);
          float v[16];
          bar_sync(N_TURN, 256);
          mbar_waitu(bar + 8 * B_F2, par ^ 1);
          wg_fence(); proj<32, SSV, 1, 0, 10>(v, W, D); wg_commit();
          mbar_waitu(bar + 8 * (B_F2 + 1), par ^ 1);
          wg_fence(); proj<32, SSV, 1, 10, 14>(v, W, D); wg_commit();
          wg_wait<1>(); REL(B_R2, 0);
          wg_fence(); proj<32, SSV, 1, 14, 20>(v, W, D); wg_commit();
          mbar_waitu(bar + 8 * (B_F2 + 2), par ^ 1);
          wg_fence(); proj<32, SSV, 1, 20, 24>(v, W, D); wg_commit();
          wg_wait<1>(); REL(B_R2, 1);
          wg_fence(); proj<32, SSV, 1, 24, 30>(v, W, D); wg_commit();
          mbar_waitu(bar + 8 * (B_F2 + 3), par ^ 1);
          wg_fence(); proj<32, SSV, 1, 30, 34>(v, W, D); wg_commit();
          wg_wait<1>(); REL(B_R2, 2);
          wg_fence(); proj<32, SSV, 1, 34, 40>(v, W, D); wg_commit();
          wg_wait<0>(); REL(B_R2, 3);
#pragma unroll
          for (int j = 0; j < 8; j++) vn[j] = pack2v(v[2 * j], v[2 * j + 1]);
          keep4(vn, lane); keep4(vn + 4, lane);
          if (warp == 0) TS(18);
        }
        DESC(3);
        uint32_t ow[16];
        bar_sync(N_P, 256);
        fence_async();
#define PV16(i, off, va) { float o[8]; wg_fence(); \
          MM<16>::rs<dlo(OFF_PL + (off), 128), 0>(o, va, D.p); \
          MM<16>::rs<dlo(OFF_PL + (off) + 256, 128), 1>(o, va + 4, D.p); \
          MM<16>::rs<dlo(OFF_PL + (off) + 512, 128), 1>(o, vm, D.p); \
          wg_commit(); wg_wait<0>(); \
          _Pragma("unroll") for (int j = 0; j < 4; j++) ow[4 * (i) + j] = pack2v(o[2 * j], o[2 * j + 1]); \
          keep4(ow + 4 * (i), lane); }
        PV16(0, 0, vl) PV16(1, 1792, vl) PV16(2, PL_SZ, vf) PV16(3, PL_SZ + 1792, vf)
        OX_ADDR();
        bar_sync(N_V, 128);
        stsm4t(s1, ow[0], ow[1], ow[2], ow[3]);
        stsm4t(s2, ow[4], ow[5], ow[6], ow[7]);
        stsm4t(s1 + PL_SZ, ow[8], ow[9], ow[10], ow[11]);
        stsm4t(s2 + PL_SZ, ow[12], ow[13], ow[14], ow[15]);
#pragma unroll
        for (int j = 0; j < 8; j++) vl[j] = vn[j];
      } else {
        uint32_t vm[4], vn[8];
        {
          DESC(4);
          float v[4];
          wg_fence(); proj<8, SSV, 0, 30, 40, 30>(v, W, D); wg_commit();
          proj<8, SSV, 0, 0, VS1, 30>(v, W, D); wg_commit();
          ARM();
          bar_sync(N_SISS, 384);
          wg_wait<1>(); bar_arrive(N_G3, 160);
          wg_fence(); proj<8, SSV, 0, VS1, 30, 30>(v, W, D); wg_commit();
          if (has_next) { mbar_waitu2(bar + 8 * B_F2, bar + 8 * (B_F2 + 1), par ^ 1); mbar_waitu(bar + 8 * (B_F2 + 2), par ^ 1); }
          wg_wait<0>();
          bar_arrive(N_VDONE, 160);
          vm[0] = pack2v(v[0], v[1]); vm[1] = pack2v(v[2], v[3]); vm[2] = pack2v(v[1], v[0]); vm[3] = pack2v(v[3], v[2]);
        }
        DESC(5);
        float v[16];
        {
          wg_fence(); proj<32, SSV, 1, 0, VS2>(v, W, D); wg_commit();
          {
            float o[4];
            O_ADDR();
            bar_sync(N_PM, 192);
            if (warp == 0) TS(14);
            wg_fence();
            MM<8>::rs<dlo(OFF_PL + 3584, 128), 0>(o, vl, D.p);
            MM<8>::rs<dlo(OFF_PL + 3584 + 256, 128), 1>(o, vl + 4, D.p);
            MM<8>::rs<dlo(OFF_PL + 3584 + 512, 128), 1>(o, vm, D.p);
            wg_commit();
            fence_sched(step);
            const uint4 il = lds128(sb + OFF_INV + (lane & 3) * 16);
            const float i0 = rcpf(__uint_as_float(il.x) + __uint_as_float(il.y)), i1 = rcpf(__uint_as_float(il.z) + __uint_as_float(il.w));
            { const uint32_t k4[4] = {__float_as_uint(i0), __float_as_uint(i1), oa, xo}; keep4(k4, lane); }
            wg_wait<0>();
            stsm2t(oa, pack2(o[0] * i0, o[1] * i1), pack2(o[2] * i0, o[3] * i1));
            O_READY(lane < 16);
            TOK_L3(3);
          }
          if (has_next) {
            mbar_arrive_remote_if(lane < VS2 / 10, rb0 + ((nA - 4 + lane) << 24) + OFF_BAR + 8 * B_R2);
            bar_sync(N_TURN, 256);
          }
          if (VS2 < 30) { wg_fence(); proj<32, SSV, 1, VS2, 30>(v, W, D); wg_commit(); }
          if (has_next) mbar_waitu(bar + 8 * (B_F2 + 3), par ^ 1);
          if (VS2 < 30) { wg_wait<0>(); if (has_next) REL(B_R2, 2); }
          wg_fence(); proj<32, SSV, 1, 30, 40>(v, W, D); wg_commit();
          wg_wait<0>();
          if (has_next) REL(B_R2, 3);
#pragma unroll
          for (int j = 0; j < 8; j++) vn[j] = pack2v(v[2 * j], v[2 * j + 1]);
          keep4(vn, lane); keep4(vn + 4, lane);
          if (warp == 0) TS(18);
        }
        float o[16];
        bar_sync(N_P, 256);
        fence_async();
        wg_fence();
        MM<32>::rs<dlo(OFF_PL, 128), 0>(o, vl, D.p);
        MM<32>::rs<dlo(OFF_PL + 256, 128), 1>(o, vl + 4, D.p);
        MM<32>::rs<dlo(OFF_PL + 512, 128), 1>(o, vm, D.p);
        wg_commit();
        OX_ADDR();
        wg_wait<0>();
        bar_sync(N_V, 128);
        stsm4t(s1, pack2(o[0], o[1]), pack2(o[2], o[3]), pack2(o[4], o[5]), pack2(o[6], o[7]));
        stsm4t(s2, pack2(o[8], o[9]), pack2(o[10], o[11]), pack2(o[12], o[13]), pack2(o[14], o[15]));
#pragma unroll
        for (int j = 0; j < 8; j++) vl[j] = vn[j];
      }
      bar_arrive(N_OX, 160);
      if (warp == 0) TS(16);
    }
    cluster_sync_all();
  } else {
    asm volatile("setmaxnreg.dec.sync.aligned.u32 32;");
    if (wg > 3) return;
    LANE_INIT();
    struct RsJob { uint32_t* gp; uint32_t la, mb; int n; };
    auto rs_prep = [&](int step, int s, int c) {
      RsJob j;
      const int u = s * nA + rank;
      j.gp = &g_part[0][0][0][0] + (uint32_t)((((step & 1) * 2 + c) * NCL + cl) * 2560 + u * 64 + (lane >> 2) * 8 + (lane & 3));
      j.la = sb + OFF_TILE + c * LAND_F + LAND(s) + lane * 8;
      j.mb = bar + 8 * (B_RS + s);
      j.n = u >= 40 ? 0 : u >= 36 ? 3 : 1;
      asm volatile("" : "+l"(j.gp), "+r"(j.la));
      return j;
    };
    auto rs_sum = [&](RsJob j, int step) {
      if (j.n) {
        auto five = [&](uint32_t la) {
          uint2 p[5];
#pragma unroll
          for (int i = 0; i < 4; i++) p[i] = lds64(la + i * 256);
          asm volatile("{\n.reg .pred q;\nsetp.eq.s32 q, %3, 5;\nmov.u32 %0, 0;\nmov.u32 %1, 0;\n@q ld.shared.v2.b32 {%0,%1}, [%2];\n}"
                       : "=r"(p[4].x), "=r"(p[4].y) : "r"(la + 1024), "r"(nh) : "memory");
          return make_uint2(hadd2bf(hadd2bf(p[0].x, p[1].x), hadd2bf(hadd2bf(p[2].x, p[3].x), p[4].x)),
                            hadd2bf(hadd2bf(p[0].y, p[1].y), hadd2bf(hadd2bf(p[2].y, p[3].y), p[4].y)));
        };
        const uint32_t tag = ((step >> 1) & 1) ^ 1;
        mbar_waitw(j.mb, step & 1);
        uint2 t = five(j.la);
        if (j.n > 1) {
          const uint2 a = five(j.la + (nh == 5 ? 1280 : TILE_GRP - 1280)), b = five(j.la + TILE_GRP);
          t.x = hadd2bf(t.x, hadd2bf(a.x, b.x)); t.y = hadd2bf(t.y, hadd2bf(a.y, b.y));
        }
        const uint32_t t0 = (movm(t.x) & ~1u) | tag, t1 = (movm(t.y) & ~1u) | tag;
        asm volatile("st.relaxed.gpu.global.b32 [%0], %1;" :: "l"(j.gp), "r"(lane & 16 ? t1 : t0) : "memory");
        asm volatile("st.relaxed.gpu.global.b32 [%0], %1;" :: "l"(j.gp + 4), "r"(lane & 16 ? t0 : t1) : "memory");
      }
    };
    if (warp * nA + (int)rank < 40) {
#pragma unroll
      for (int e = LAG; e < LAG + 2; e++)
        if ((e >> 1) & 1) *reinterpret_cast<uint2*>(&g_part[(e & 1) * 2 + 1][cl][warp * nA + rank][lane * 2]) = make_uint2(1u, 1u);
      __threadfence();
    }
    if (warp == 2 && ig >= 0 && sync_b) wait_cnt(&g_xready[0][0], 32);
    cluster_sync_all();
    if (warp == 2 && ig >= 0) bulk_g2s_mc_e(sb + OFF_TILE + ig * TILE_GRP + TILE_SBO, &g_xn[0][0] + ig * 5120, 10240, bar + 8 * (B_F2 + ig), mcmask);
    bar_sync(N_PI, 128);
#pragma unroll 1
    for (int i = warp; i < 20; i += 4) {
      int c0, c1; wo_coord(i, t3, head, c0, c1);
      if (i >= 2 && i < 15) tma2d_e(sb + OFF_WO + (i - 2) * 4096, &M.wo32, c0, c1, bar + 8 * B_W1);
      else if (lane == 0) tma2d_prefetch(&M.wo32, c0, c1);
      __syncwarp();
    }
#pragma unroll 1
    for (int step = 0; step < NSTEP; step++) {
      const uint32_t par = step & 1;
      asm volatile("" : "+r"(lane));
      const bool dual = is_dual(step), has_next = step + 1 < NSTEP;
      {
        bar_sync(N_PX, dual ? 256 : 192);
        if (dual || warp >= 2) tok_softmax(sb, dual ? warp : warp - 2, lane);
        bar_arrive(N_P, 256);
        asm volatile("" : "+r"(lane));
        if (has_next) {
          if (step + 2 == LAG && lane < 20) asm volatile("prefetch.global.L2 [%0];" :: "l"(mem0 + (warp * 20 + lane) * 64));
          const int nw = ig >= 0 ? 3 : 4, j0 = warp < nw ? warp : 8;
          const int sh = dual ? 1 : 0;
          rs_sum(rs_prep(step, j0 >> sh, j0 & sh), step);
          if (warp == 0) TS(17);
          if (dual) rs_sum(rs_prep(step, (j0 + nw) >> 1, (j0 + nw) & 1), step);
          if (warp == 0) { bar_sync(N_C, 288); }
          mbar_arrive_remote_if(lane < nA, rb0 + (lane << 24) + OFF_BAR + 8 * B_LANDFREE);
          const uint32_t gap = dual ? POLL_GAPD : POLL_GAP;
          if (gap) { const uint32_t t0 = clock32(); while (clock32() - t0 < gap) {} }
#pragma unroll 1
          for (int j = j0; j < (dual ? 8 : 4); j += nw) {
            const int u = (j >> sh) * nA + rank, c = j & sh;
            if (u < UMAX && (c || step + 1 != NSEG)) {
              const uint32_t* gq = &g_part[0][0][0][0] + (uint32_t)((par * 2 + c) * NCL * 2560 + u * 64 + lane * 2);
              uint2 pa[NCL];
              POLL(pa, gq);
              deliver(pa, gq, u, c, step + 1 < NSEG ? c : 0, dual ? DS_DUAL : DS_SINGLE, step, j == 0, lane);
            }
            if (warp == 0 && j == 0) TS(13);
          }
          if (warp >= nw && (is_dual(step + 1) || (ig < 3 && step + 2 < NSTEP))) {
            issue_tok(is_dual(step + 1) ? sched_f(step + 1) : sched_l(step + 2), is_dual(step + 1) ? B_F1 : B_F2, B_R2, par ^ 1);
          }
          if (step + 1 == LAG && UMAX) {
            uint4 v[5];
#pragma unroll
            for (int i = 0; i < 5; i++) { const int t = warp * 160 + i * 32 + lane; v[i] = *reinterpret_cast<const uint4*>(mem0 + ((t >> 1) & 7) * DM + (t >> 4) * 16 + ((t ^ (t >> 3)) & 1) * 8); }
            mbar_waitu(bar + 8 * B_LANDFREE, par);
#pragma unroll
            for (int i = 0; i < 5; i++)
              st_async_v4(sb + OFF_TILE + LAND_F + warp * TILE_GRP + (i * 32 + lane) * 16, v[i].x, v[i].y, v[i].z, v[i].w, bar + 8 * (B_F1 + warp));
          }
        }
      }
      if (warp == (ig >= 0 && !is_dual(step + 1) ? 2 : 3)) {
        unsigned char* o0 = g_o + uni(step % RO * (96 * 8192) + (head * 3 + t3) * (dual ? 8192 : 4096));
        bar_sync(N_OX, 160);
        fence_async();
        bulk_s2g_es(o0, sb + OFF_PL, 4096);
        if (dual) bulk_s2g_es(o0 + 4096, sb + OFF_PL + PL_SZ, 4096);
        asm volatile("cp.async.bulk.commit_group;" ::: "memory");
        asm volatile("cp.async.bulk.wait_group.read 0;" ::: "memory");
        __syncwarp();
        mbar_arrive_remote_if(lane < 2, (lane ? nxt : prv) + OFF_BAR + 8 * B_PLFREE);
        asm volatile("cp.async.bulk.wait_group 0;" ::: "memory");
        asm volatile("fence.proxy.async.global;" ::: "memory");
        __syncwarp();
        if (lane == 0) red_release(&g_f[F_O + (head * 3 + t3) / 5][step], 1u);
        __syncwarp();
      }
    }
    cluster_sync_all();
  }
}

__device__ __forceinline__ float gelu2(float x) {
  const float u = x * fmaf(x * x, 0.7978845608028654f * 0.044715f, 0.7978845608028654f);
  float t; asm("tanh.approx.f32 %0, %1;" : "=f"(t) : "f"(u));
  return fmaf(x, t, x); }

struct BParams {
  CUtensorMap wmap[5];
  CUtensorMap wo16;
  const __nv_bfloat16* x;
  __nv_bfloat16* out;
  uint64_t desc, desc32;
};
#define BO_O 0
#define BO_RES (6 * 8192)
#define OP_RES 63488
#define BO_STG (BO_RES + 2 * OP_RES)
#define BO_RING_OP (BO_STG + 16384)
#define OP_SLOT 12288
#define NS_OP 3
#define BO_H 81920
#define BO_W1 (BO_H + 16384)
#define BO_RING_MLP (BO_W1 + 81920)
#define BO_BAR 229376
#define BO_BOX (BO_BAR + 248)
#define BO_CARRY (BO_BAR + 512)
#define BO_STAT (BO_CARRY + 2048)
#define B_SMEM (BO_STAT + 256)
static_assert(B_SMEM <= 232448 && BO_RING_OP + NS_OP * OP_SLOT == BO_BAR && BO_RING_MLP + 3 * 16384 == BO_BAR && 2 * 83968 <= BO_RING_MLP, "smem");
enum { BB_W = 0, BB_FULL = 2, BB_TMP = BB_FULL + 3, BB_OFULL = BB_FULL + 5, BB_SFREE = BB_OFULL,
       BB_STAT = BB_SFREE + 6, BB_GO, BB_ZFREE, BB_DONE = BB_ZFREE + 3,
       BB_EMPTY, BB_START = BB_EMPTY, BB_USED = BB_EMPTY + 2, BB_NUM = BB_USED + 3 };
enum { NB_PP = 1, NB_H = 3, NB_END = 4, NB_END2 = 5, NB_STAGED = 6, NB_FREE = 8, NB_EARLY = 10, NB_LAST = 11 };

#define DESC_LO(off) (((SMEM0 + (off)) >> 4) | (1u << 16))

__device__ __forceinline__ uint32_t ld_relaxed(const uint32_t* p) { uint32_t v; asm volatile("ld.relaxed.gpu.global.b32 %0, [%1];" : "=r"(v) : "l"(p) : "memory"); return v; }
__device__ __forceinline__ int fmask(int r) { return (r < NSEG) | ((r >= LAG && r < NSTEP) << 1); }
__device__ __forceinline__ int bmask(int r) { return (r <= NSEG) | ((r >= LAG) << 1); }
__device__ __forceinline__ uint32_t rtarget(int mask) { return mask == 3 ? 64 : 32; }
__device__ __forceinline__ void warp_signal(uint32_t* p, int lane) {
  __syncwarp();
  asm volatile("{\n.reg .pred q;\nsetp.eq.u32 q, %1, 0;\n@q red.release.gpu.global.add.u32 [%0], 1;\n}" :: "l"(p), "r"(lane) : "memory");
}
__device__ __forceinline__ uint32_t pack2h(float lo, float hi) { uint32_t r; asm("cvt.rn.f16x2.f32 %0, %1, %2;" : "=r"(r) : "f"(hi), "f"(lo)); return r; }
template <bool H> __device__ __forceinline__ uint32_t pk(float lo, float hi) { return H ? pack2h(lo, hi) : pack2(lo, hi); }
template <int N, bool H> __device__ __forceinline__ void stage_out(const float* d, uint32_t dst, int warp, int lane) {
  const uint32_t sa = dst + ((lane >> 4) * 8 + (lane & 7)) * 128 + (((2 * warp + ((lane >> 3) & 1)) ^ (lane & 7)) << 4);
#pragma unroll
  for (int m = 0; m < N / 16; m++)
    stsm4t(sa + m * 2048, pk<H>(d[8 * m], d[8 * m + 1]), pk<H>(d[8 * m + 2], d[8 * m + 3]), pk<H>(d[8 * m + 4], d[8 * m + 5]), pk<H>(d[8 * m + 6], d[8 * m + 7]));
}
template <int N> __device__ __forceinline__ void acc_live(float* d) {
#pragma unroll
  for (int i = 0; i < N / 2; i++) asm volatile("" : "+f"(d[i]) :: "memory");
}
struct Ring {
  uint32_t sl, ph;
  template <int NS> __device__ __forceinline__ void step() { if (++sl == NS) { sl = 0; ph ^= 1; } }
};

#define KOFF(x) (DESC_LO(BO_O) + ((x) >> 2) * 512 + ((x) & 3) * 2)
template <int N, int P>
__device__ __forceinline__ void op_pass(const uint32_t* W, uint32_t bar, Dsc alo, Dsc blo, Dsc xlo, bool x2, Ring& rg, int wg, int warp, int lane, int r) {
  float acc[N / 2];
  blo.e = xlo.e = fresh<P + N / 64 * 5>(r);
  const Dsc tlo = blo + uni(rg.sl) * (OP_SLOT / 16), b2 = blo + (r & 1) * 1536;
  if (P == 0) mbar_waitu(bar + 8 * (BB_OFULL + 2 + (r & 1)), (r >> 1) & 1);
  CTS(5 * P);
  bar_sync(NB_PP + wg, 256);
  wg_fence();
#define OP_R(x, b) MM<N>::template rs<KOFF(4 * (x >> 1) + (x & 1)), (x != (P ? 0 : 4))>(acc, W + 32 * P + 4 * x, b);
#define OP_S(x, b) MM<N>::template ss<DESC_LO(BO_RES) + (6 * P + x) * 128, KOFF(4 * (x >> 1) + 2 + (x & 1)), 1>(acc, alo, b);
#define OP_T(x) MM<N>::template ss<DESC_LO(BO_RING_OP) + x * 128, KOFF(14 + x), 1>(acc, tlo, blo);
#define OP_B2() OP_R(4, b2) OP_S(4, b2) OP_R(5, b2) OP_S(5, b2)
  if (P == 0) { OP_B2() mbar_waitu(bar + 8 * BB_OFULL, r & 1); }
  OP_R(0, blo) OP_S(0, blo) OP_R(1, blo) OP_S(1, blo) OP_R(2, blo) OP_S(2, blo) OP_R(3, blo) OP_S(3, blo)
  if (P == 0) mbar_waitu(bar + 8 * (BB_OFULL + 1), r & 1);
  if (P == 4) wg_commit();
  if (P & 3) { OP_B2() }
  if (P == 1 && x2) MM<N>::template ss<DESC_LO(BO_RES) + 30 * 128, DESC_LO(BO_CARRY), 1>(acc, alo, xlo);
  mbar_waitu(bar + 8 * (BB_FULL + rg.sl), rg.ph);
  OP_R(6, blo) OP_T(0) OP_R(7, blo) OP_T(1)
  if (P == 4) { wg_commit(); wg_wait<1>(); bar_arrive(NB_EARLY, 288); CTS(21); wg_fence(); }
  OP_T(2) OP_T(3)
  if (P == 0) MM<N>::template rs<DESC_LO(BO_CARRY), 1>(acc, W + 160, xlo);
  OP_T(4) OP_T(5)
  if (P == 4) { wg_commit(); OP_B2() }
  wg_commit();
  bar_arrive(NB_PP + 1 - wg, 256);
  CTS(5 * P + 2);
  if (P == 4) { wg_wait<1>(); bar_arrive(NB_LAST, 288); }
  bar_sync(NB_FREE + wg, 160);
  wg_wait<0>();
  acc_live<N>(acc);
  mbar_arrive_if(lane == 0, bar + 8 * (BB_USED + rg.sl));
  CTS(5 * P + 3);
  stage_out<N, false>(acc, SMEM0 + BO_STG + wg * 8192, warp, lane);
  bar_arrive(NB_STAGED + wg, 160);
  CTS(5 * P + 4);
  rg.step<NS_OP>(); rg.step<NS_OP>();
}
template <int N>
__device__ __forceinline__ void op_round(const uint32_t* W, uint32_t bar, Dsc alo, Dsc blo, Dsc xlo, bool x2, Ring& rg, int wg, int warp, int lane, int r) {
  op_pass<N, 0>(W, bar, alo, blo, xlo, x2, rg, wg, warp, lane, r);
  op_pass<N, 1>(W, bar, alo, blo, xlo, x2, rg, wg, warp, lane, r);
  op_pass<N, 2>(W, bar, alo, blo, xlo, x2, rg, wg, warp, lane, r);
  op_pass<N, 3>(W, bar, alo, blo, xlo, x2, rg, wg, warp, lane, r);
  op_pass<N, 4>(W, bar, alo, blo, xlo, x2, rg, wg, warp, lane, r);
}
__device__ __forceinline__ void carry_in(uint32_t sb, int wg, int warp, int lane) {
  const int row = (lane >> 1) & 3;
  if (lane < 16) {
    const uint4 v = lds128(sb + BO_CARRY + (wg * 4 + warp) * 256 + lane * 16);
    sts128(sb + BO_H + wg * 8192 + (lane >> 3) * 4096 + row * 128 + (((2 * warp + (lane & 1)) ^ row) << 4), v.x, v.y, v.z, v.w);
  }
  __syncwarp();
}
template <int N, int Z>
__device__ __forceinline__ void p1_pair(float* acc, const uint32_t* W, uint32_t bar, Dsc alo, Dsc blo, int lane, int r) {
  constexpr int ZOFF = N == 64 ? (2 * Z % 3) * 1024 : (Z / 2 * 2 % 3) * 1024 + (Z & 1) * 256;
  blo.e = fresh<10 + Z / 3 + N / 64 * 2>(r);
  mbar_waitu(bar + 8 * (BB_FULL + Z), r & 1);
  CTS(40 + Z);
  wg_fence();
#define P1_B(k) \
  MM<N, true>::template rs<DESC_LO(BO_RING_MLP) + ZOFF + k * 512, (2 * Z + k != 0)>(acc, W + 16 * Z + 8 * k, blo); \
  MM<N, true>::template ss<DESC_LO(BO_W1) + (2 * Z + k) * 512, DESC_LO(BO_RING_MLP) + ZOFF + k * 512 + 4, 1>(acc, alo, blo); \
  MM<N, true>::template rs<DESC_LO(BO_RING_MLP) + ZOFF + k * 512 + 2, 1>(acc, W + 16 * Z + 8 * k + 4, blo); \
  MM<N, true>::template ss<DESC_LO(BO_W1) + (2 * Z + k) * 512 + 128, DESC_LO(BO_RING_MLP) + ZOFF + k * 512 + 6, 1>(acc, alo, blo);
  P1_B(0)
  if (N == 64 && (Z == 1 || Z == 2)) { wg_commit(); wg_wait<1>(); mbar_arrive_if(lane == 0, bar + 8 * (BB_EMPTY + Z - 1)); wg_fence(); }
  P1_B(1)
  wg_commit();
}
template <int N>
__device__ __forceinline__ void phase1(const uint32_t* W, uint32_t sb, Dsc alo, Dsc blo, int half, int wg, int warp, int lane, int off, int r) {
  float acc[N / 2];
  const uint32_t bar = sb + BO_BAR;
  CTS(30);
  p1_pair<N, 0>(acc, W, bar, alo, blo, lane, r);
  p1_pair<N, 1>(acc, W, bar, alo, blo, lane, r);
  p1_pair<N, 2>(acc, W, bar, alo, blo, lane, r);
  if (N == 32) p1_pair<N, 3>(acc, W, bar, alo, blo, lane, r);
  mbar_waitu(bar + 8 * (BB_SFREE + 4 + wg), (r + 1) & 1);
  carry_in(sb, wg, warp, lane);
  if (N == 32) mbar_arrive_if(lane < 2, bar + 8 * (BB_EMPTY + lane));
  else p1_pair<N, 3>(acc, W, bar, alo, blo, lane, r);
  p1_pair<N, 4>(acc, W, bar, alo, blo, lane, r);
  const int c = (lane >> 3) & 1, i0 = (lane >> 4) * 8 + (lane & 7) + off;
  uint32_t a0 = sb + BO_H + wg * 8192 + half * 4096 + i0 * 128 + (((2 * warp + c) ^ (i0 & 7)) << 4);
  uint32_t a1 = i0 >= 16 ? sb + BO_CARRY + (wg * 4 + warp) * 256 + half * 128 + (i0 - 16) * 32 + c * 16 : a0 + 2048, a3 = a1 + (i0 >= 16 ? 128 : 4096);
  asm volatile("" : "+r"(a0), "+r"(a1), "+r"(a3));
  mbar_waitu(bar + 8 * BB_STAT, r & 1);
  const uint32_t sa = sb + BO_STAT + half * 128 + (lane & 3) * 32;
  uint4 t[2] = {lds128(sa), lds128(sa + 16)};
  wg_wait<0>();
  acc_live<N>(acc);
  CTS(32);
#pragma unroll
  for (int m = 0; m < N / 16; m++) {
    const float s0 = __uint_as_float(t[m & 1].x), s1 = __uint_as_float(t[m & 1].y), s2 = __uint_as_float(t[m & 1].z), s3 = __uint_as_float(t[m & 1].w);
    float* d = acc + 8 * m;
    d[0] *= s0; d[1] *= s1; d[2] *= s0; d[3] *= s1; d[4] *= s2; d[5] *= s3; d[6] *= s2; d[7] *= s3;
    if (m + 2 < N / 16) t[m & 1] = lds128(sa + 128 + m * 16);
#pragma unroll
    for (int j = 0; j < 8; j++) d[j] = gelu2(d[j]);
  }
#pragma unroll
  for (int m = 0; m < N / 16; m++)
    stsm4t(m == 1 ? a1 : m == 3 ? a3 : a0 + m * 2048, pack2(acc[8 * m], acc[8 * m + 1]), pack2(acc[8 * m + 2], acc[8 * m + 3]), pack2(acc[8 * m + 4], acc[8 * m + 5]), pack2(acc[8 * m + 6], acc[8 * m + 7]));
}
template <int N, int P>
__device__ __forceinline__ void p2_mma(float* acc, const uint32_t* W, Dsc alo, Dsc blo, int r) {
  blo.e = fresh<P + N / 64 * 5>(r);
  MM<N>::template rs<DESC_LO(BO_H), 0>(acc, W + 80 + 16 * P, blo);     MM<N>::template ss<DESC_LO(0) + P * 1024, DESC_LO(BO_H) + 512, 1>(acc, alo, blo);
  MM<N>::template rs<DESC_LO(BO_H) + 2, 1>(acc, W + 84 + 16 * P, blo); MM<N>::template ss<DESC_LO(0) + P * 1024 + 128, DESC_LO(BO_H) + 514, 1>(acc, alo, blo);
  MM<N>::template rs<DESC_LO(BO_H) + 4, 1>(acc, W + 88 + 16 * P, blo); MM<N>::template ss<DESC_LO(0) + P * 1024 + 512, DESC_LO(BO_H) + 516, 1>(acc, alo, blo);
  MM<N>::template rs<DESC_LO(BO_H) + 6, 1>(acc, W + 92 + 16 * P, blo); MM<N>::template ss<DESC_LO(0) + P * 1024 + 640, DESC_LO(BO_H) + 518, 1>(acc, alo, blo);
}
template <int N, int P, int T>
__device__ __forceinline__ void p2_pass(const uint32_t* W, uint32_t bar, Dsc alo, Dsc blo, int wg, int warp, int lane, int r) {
  float acc[N / 2], ac2[N / 2];
  CTS(5 * P);
  if (P || wg) bar_sync(NB_PP + wg, 256);
  wg_fence();
  p2_mma<N, P>(acc, W, alo, blo, r);
  wg_commit();
  if constexpr (T == 2) { p2_mma<N, P + 1>(ac2, W, alo, blo, r); wg_commit(); }
  if (P < 4 || !wg) bar_arrive(NB_PP + 1 - wg, 256);
  CTS(5 * P + 2);
  if (T == 1 && (P == 2 || P == 3)) mbar_waitu(bar + 8 * (BB_SFREE + 2 * (P - 2) + wg), r & 1);
  wg_wait<T - 1>();
  acc_live<N>(acc);
  if (P == 4) bar_sync(NB_H, 256);
  CTS(5 * P + 3);
  constexpr int K = P / T & 1;
  stage_out<N, true>(acc, SMEM0 + (P == 4 ? BO_H : BO_RING_MLP + (2 - K) * 16384) + wg * 8192, warp, lane);
  if constexpr (T == 2) {
    wg_wait<0>();
    acc_live<N>(ac2);
    stage_out<N, true>(ac2, SMEM0 + BO_RING_MLP + (2 - K) * 16384 + wg * 8192 + 4096, warp, lane);
  }
  bar_arrive(NB_STAGED + (P == 4 ? 4 : 2 * K) + wg, 160);
  CTS(5 * P + 4);
}
template <int N>
__device__ __forceinline__ void phase2(const uint32_t* W, uint32_t bar, Dsc alo, Dsc blo, int wg, int warp, int lane, int r) {
  if constexpr (N == 64) {
    p2_pass<N, 0, 1>(W, bar, alo, blo, wg, warp, lane, r);
    p2_pass<N, 1, 1>(W, bar, alo, blo, wg, warp, lane, r);
    p2_pass<N, 2, 1>(W, bar, alo, blo, wg, warp, lane, r);
    p2_pass<N, 3, 1>(W, bar, alo, blo, wg, warp, lane, r);
  } else {
    p2_pass<N, 0, 2>(W, bar, alo, blo, wg, warp, lane, r);
    p2_pass<N, 2, 2>(W, bar, alo, blo, wg, warp, lane, r);
  }
  p2_pass<N, 4, 1>(W, bar, alo, blo, wg, warp, lane, r);
}

__device__ __forceinline__ void ldg4(uint32_t* v, const void* p) {
  asm volatile("ld.relaxed.gpu.global.v4.u32 {%0,%1,%2,%3}, [%4];" : "=r"(v[0]), "=r"(v[1]), "=r"(v[2]), "=r"(v[3]) : "l"(p) : "memory"); }
__device__ __forceinline__ void stg4(void* p, const uint32_t* v) {
  asm volatile("st.global.v4.u32 [%0], {%1,%2,%3,%4};" :: "l"(p), "r"(v[0]), "r"(v[1]), "r"(v[2]), "r"(v[3]) : "memory"); }
struct RowPtr {
  unsigned char *p, *q, *t;
  __device__ __forceinline__ void ld(uint32_t* v, int o) const {
    ldg4(v, p + o); ldg4(v + 4, q + o);
    asm volatile("ld.relaxed.gpu.global.v2.u32 {%0,%1}, [%2];" : "=r"(v[8]), "=r"(v[9]) : "l"(t + o) : "memory");
  }
  __device__ __forceinline__ void st(const uint32_t* w, int o) const {
    stg4(p + o, w); stg4(q + o, w + 4);
    asm volatile("st.global.v2.u32 [%0], {%1,%2};" :: "l"(t + o), "r"(w[8]), "r"(w[9]) : "memory");
  }
};
__device__ __forceinline__ RowPtr row_img(int r, int n, int lane) {
  unsigned char* b = &g_acc[0][r % RD][n * 128];
  unsigned char* p = b + (uint32_t)((lane >> 3) * 8192 + (((lane ^ n) & 7) << 4));
  return {p, p + 32768, b + (uint32_t)(65536 + (lane >> 4) * 8192 + ((((lane >> 1) ^ n) & 7) << 4) + (lane & 1) * 8)};
}
__device__ __forceinline__ RowPtr row_ext(const void* lin, bool xn, int layer, int tok, int lane) {
  unsigned char* b = xn ? reinterpret_cast<unsigned char*>(&g_xn[layer][0]) + (uint32_t)((tok >> 5) * 40960 + ((tok >> 3) & 3) * 2560 + (tok & 7) * 32)
                        : (unsigned char*)lin + (uint32_t)(tok * 1280);
  const uint32_t o = (lane >> 1) * 256 + ((lane ^ (tok >> 2)) & 1) * 16;
  return {b + (uint32_t)(xn ? o + (lane >= 20 ? 7680 : 0) : lane * 16),
          b + (uint32_t)(xn ? o + 4096 + 7680 + (lane >= 8 ? 7680 : 0) + (lane >= 28 ? 7680 : 0) : lane * 16 + 512),
          b + (uint32_t)(xn ? (lane >> 2) * 256 + ((lane & 3) ^ ((tok >> 1) & 2)) * 8 + 8192 + 3 * 7680 : lane * 8 + 1024)};
}
__device__ __forceinline__ float2 h2f(uint32_t w) {
  float2 f; asm("{\n.reg .f16 l, h;\nmov.b32 {l, h}, %2;\ncvt.f32.f16 %0, l;\ncvt.f32.f16 %1, h;\n}" : "=f"(f.x), "=f"(f.y) : "r"(w)); return f; }
__device__ __forceinline__ float rsq(float x) { float y; asm("rsqrt.approx.ftz.f32 %0, %1;" : "=f"(y) : "f"(x)); return y; }
__device__ __forceinline__ void red_if(uint32_t v, const void* a) {
  asm volatile("{\n.reg .pred q;\nsetp.ne.u32 q, %1, 0;\n@q red.relaxed.gpu.global.add.u32 [%0], %1;\n}" :: "l"(a), "r"(v) : "memory"); }
__device__ __forceinline__ uint32_t dep0(uint32_t w, int lane) { uint32_t z; asm volatile("shr.b32 %0, %1, %2;" : "=r"(z) : "r"(w), "r"(lane + 32)); return z; }
__device__ __forceinline__ int lane_of(uint32_t w) {
  int lane; asm volatile("{\n.reg .u32 t;\nmov.u32 t, %%laneid;\nshr.u32 %0, %1, 20;\nadd.u32 %0, %0, t;\n}" : "=r"(lane) : "r"(w)); return lane; }
#define BUF (RD * TILE_B)
__device__ __forceinline__ int await(uint32_t v, const uint32_t* p, uint32_t target, bool lazy) {
  int n = 0;
  while (!__all_sync(~0u, v >= target)) {
    if (lazy) __nanosleep(200);
    if (++n > SPIN_LIMIT) FAIL();
    v = ld_relaxed(p);
  }
  asm volatile("fence.acquire.gpu;" ::: "memory");
  return lane_of(v);
}
template <int W> __device__ __forceinline__ void sum2(float& s, float& q, int lane) {
  const bool up = lane & (W / 2);
  float e = (up ? q : s) + __shfl_xor_sync(~0u, up ? s : q, W / 2);
#pragma unroll
  for (int o = W / 4; o; o >>= 1) e += __shfl_xor_sync(~0u, e, o);
  const float f = __shfl_xor_sync(~0u, e, W / 2);
  s = up ? f : e; q = up ? e : f;
}
template <int TYPE>
__device__ __forceinline__ void rrow(int r, int row, int tok, int lane, const uint32_t* go, int role, const __nv_bfloat16* x, __nv_bfloat16* out) {
  const int half = TYPE == 3 ? 0 : row >> 5;
  float v[20];
  float2 st = make_float2(1.f, 0.f);
  {
    uint32_t a[10], c[10], u[10], sh = 16;
    if (TYPE == 2) row_img(r + RD - ((row & 31) < 2), (row & 32) + ((row - 2) & 31), lane).ld(u, 3 * BUF);
    else row_ext(x, half, 1, tok, lane).ld(u, 0);
    if (TYPE == 2 || (TYPE == 0 && half))
      asm volatile("ld.relaxed.gpu.global.v2.f32 {%0,%1}, [%2];" : "=f"(st.x), "=f"(st.y) : "l"(g_stat + tok) : "memory");
    RowPtr ap = row_img(r, row, lane);
    const uint32_t g0 = TYPE != 3 ? ld_relaxed(go) : 0;
    if (TYPE != 3) {
      asm volatile("" : "+l"(ap.p), "+l"(ap.t));
      ap.q = ap.p + 32768;
      lane = await(g0, go, NOP * NW12 * NW34, false); BTS2(r, 8 + 2 * TYPE); RTS(0);
      ap.ld(a, TYPE ? 2 * BUF : 0);
    }
    if (TYPE == 0) {
      ap.ld(c, BUF);
      const uint32_t one = 0x3f803f80u | dep0(c[9], lane);
#pragma unroll
      for (int i = 0; i < 10; i++) asm volatile("fma.rn.bf16x2 %0, %0, %1, %2;" : "+r"(a[i]) : "r"(one), "r"(c[i]));
      sh |= dep0(a[9], lane);
    }
    const uint32_t z = TYPE == 2 ? dep0(a[9], lane) : 0;
#pragma unroll
    for (int i = 0; i < 10; i++) {
      if (TYPE == 2) { const float2 g = h2f(u[i] | z), h = h2f(a[i] | z); v[2 * i] = fmaf(h.x, 0.5f, g.x * st.x); v[2 * i + 1] = fmaf(h.y, 0.5f, g.y * st.x); continue; }
      float p = __uint_as_float(u[i] << sh), q = __uint_as_float(u[i] & (0xffffu << sh));
      if (TYPE == 0) { p = fmaf(p, st.x, bf_lo(a[i])); q = fmaf(q, st.x, bf_hi(a[i])); }
      v[2 * i] = p; v[2 * i + 1] = q;
    }
  }
  RTSD(1, v[19]);
  float s = 0.f, q = 0.f;
#pragma unroll
  for (int i = 0; i < 5; i++) {
    s += (v[4 * i] + v[4 * i + 1]) + (v[4 * i + 2] + v[4 * i + 3]);
    q += fmaf(v[4 * i], v[4 * i], v[4 * i + 1] * v[4 * i + 1]) + fmaf(v[4 * i + 2], v[4 * i + 2], v[4 * i + 3] * v[4 * i + 3]);
  }
  if (!(TYPE == 2 && half)) sum2<32>(s, q, lane);
  const float mean = s * (1.f / DM), var = fmaxf(q * (1.f / DM) - mean * mean, 0.f), rs = rsq(var + 1e-5f);
  const float k = TYPE == 0 ? 2.f * rs : half ? 1.f : rs, mr = TYPE && half ? st.y : -mean * k;
  RTSD(2, rs);
  uint32_t w[10];
#pragma unroll
  for (int i = 0; i < 10; i++) w[i] = pk<TYPE == 0>(fmaf(v[2 * i], k, mr), fmaf(v[2 * i + 1], k, mr));
  if (TYPE) row_ext(out, !half, TYPE == 2, tok, lane).st(w, 0);
  else {
    row_img(r, row, lane).st(w, 3 * BUF);
    row_img(r + ((row & 31) >= 30), (row & 32) + ((row + 2) & 31), lane).st(w, 2 * BUF);
    if (lane == 1) g_st2[0][r % RD][row] = (__float_as_uint(0.5f * rsq(fmaf(var * rs, rs, 1e-5f))) & ~127u) | (r + 1);
  }
  if (TYPE != 3 && lane == 0) g_stat[tok] = make_float2((var + 1e-5f) * rs * (TYPE ? 1.f : 0.5f), mean + st.y);
}
__device__ __forceinline__ void r2rows(int r, int row, int lane) {
  const int n = row + (lane >> 4);
  const unsigned char* ap = &g_acc[2][r % RD][0] + (uint32_t)(n * 128 + ((lane >> 3) & 1) * 8192 + (((lane ^ n) & 7) << 4));
  uint32_t a[20];
#pragma unroll
  for (int i = 0; i < 5; i++) ldg4(a + 4 * i, ap + i * 16384);
  const uint32_t z = dep0(a[19], lane);
  float s = 0.f, q = 0.f, q2 = 0.f;
#pragma unroll
  for (int i = 0; i < 20; i++) { const float2 h = h2f(a[i] | z); s += h.x + h.y; q = fmaf(h.x, h.x, q); q2 = fmaf(h.y, h.y, q2); }
  q += q2;
  sum2<16>(s, q, lane);
  const float mean = s * (0.5f / DM), rs = rsq(fmaxf(q * (0.25f / DM) - mean * mean, 0.f) + 1e-5f);
  if ((lane & 15) == 0) asm volatile("st.relaxed.gpu.global.u32 [%0], %1;" :: "l"(&g_st2[1][r % RD][n]), "r"((__float_as_uint(0.5f * rs) & ~127u) | (r + 1)) : "memory");
}
__device__ __forceinline__ void r3rows(int r, int row, int tok, int lane, __nv_bfloat16* out) {
  const int n = row + (lane >> 4), m = 32 + ((n - 2) & 31);
  const unsigned char* ap = &g_acc[0][r % RD][0] + (uint32_t)(n * 128 + ((lane >> 3) & 1) * 8192 + (((lane ^ n) & 7) << 4));
  const unsigned char* zp = &g_acc[3][(r + RD - (row == 32)) % RD][0] + (uint32_t)(m * 128 + ((lane >> 3) & 1) * 8192 + (((lane ^ m) & 7) << 4));
  unsigned char* op = reinterpret_cast<unsigned char*>(out) + (uint32_t)((tok + (lane >> 4)) * 1280 + (lane & 15) * 16);
  float2 st;
  asm volatile("ld.relaxed.gpu.global.v2.f32 {%0,%1}, [%2];" : "=f"(st.x), "=f"(st.y) : "l"(g_stat + tok + (lane >> 4)) : "memory");
#pragma unroll 1
  for (int i0 = 0; i0 < 2; i0++) {
    uint32_t a[12], u[12];
#pragma unroll
    for (int i = 0; i < 3; i++) { ldg4(a + 4 * i, ap + 2 * BUF + i * 16384); ldg4(u + 4 * i, zp + i * 16384); }
    uint32_t z = dep0(u[11], lane);
#pragma unroll
    for (int i = 0; i < 12; i++) {
      const float2 h = h2f(a[i] | z), g = h2f(u[i] | z);
      a[i] = pack2(fmaf(h.x, 0.5f, fmaf(g.x, st.x, st.y)), fmaf(h.y, 0.5f, fmaf(g.y, st.x, st.y)));
      if (i & 1) z = dep0(a[i], lane);
    }
    if (i0 == 0) stg4(op, a);
    stg4(op + 256, a + 4); stg4(op + 512, a + 8);
    ap += 32768; zp += 32768; op += 512;
  }
}
template <int TYPE>
__device__ __forceinline__ void rloop(int row, int cp, int role, const __nv_bfloat16* x, __nv_bfloat16* out) {
  constexpr int ST = TYPE == 4 ? 2 : TYPE;
  const int r0 = row & 32 ? LAG : 0;
  uint32_t v = 0;
  static_assert(NSEG + RD >= NSTEP, "no signals");
#pragma unroll 1
  for (int r = r0; r < (TYPE == 2 ? NR : TYPE == 4 ? NSEG + 1 : r0 + NSEG + (TYPE > 0)); r++) {
    if (TYPE == 2 && r == NSEG + 1) row += 32;
    const int tok = (r - (row & 32 ? LAG : 0)) * 32 + (row & 31) - (TYPE ? 2 : 0);
    const bool valid = TYPE == 0 || (unsigned)tok < S_LEN;
    const uint32_t* go = &g_f[F_R1 + 4 * ST + cp][r];
    const uint32_t* first = TYPE == 2 ? &g_f[F_R2 + cp][r] : TYPE ? go : (const uint32_t*)&g_xready[NSEG + r - r0][0];
    if constexpr (TYPE == 1 || TYPE == 4) {
      const int lane = await(v, go, NOP * NW12 * NW34, false);
      BTS2(r, 8 + 2 * ST); RTS(0);
      if (TYPE == 1) { r2rows(r, row, lane); BTS2(r, 11); continue; }
      if (valid) r3rows(r, row, tok, lane, out);
    } else {
      if (TYPE || row >= 32) await(v, first, TYPE ? NOP * NW12 * NW34 : 32, true);
      if (valid) rrow<TYPE>(r, row, tok, lane_of(r), go, role, x, out);
    }
    if (TYPE > 1 && row >= 32 && r + RD - 1 >= NSTEP) { v = 0; BTS2(r, 13); continue; }
    const int lane = lane_of(r);
    const void* f = lane ? (const void*)&g_xready[NSEG + (tok >> 5)][0] : (const void*)&g_f[TYPE ? F_DONE : F_Z][r];
    asm volatile("" : "+l"(f));
    __syncwarp();
    RTS(3);
    v = ld_relaxed(first + (TYPE ? 1 : 8));
    asm volatile("fence.release.gpu;" ::: "memory");
    RTS(4);
    red_if(lane == 0 || (TYPE == 2 && lane == 1 && valid) ? (TYPE & 5 ? 2 : 1) : 0, f);
    RTS(5);
    RTS_OUT();
    BTS2(r, 9 + 2 * ST);
  }
}

#define RCV 1
#define SINGLE_OP 3
#define SINGLE_W 0
#define W_DELAY 0
#define BULK_ADD(T, dst, src, len) asm volatile("{\n.reg .pred e;\nelect.sync _|e, 0xffffffff;\n@e cp.reduce.async.bulk.global.shared::cta.bulk_group.add.noftz." T " [%0], [%1], %2;\n}" \
                                               :: "l"(dst), "r"(src), "r"(len) : "memory")
#define COMMIT() asm volatile("cp.async.bulk.commit_group;" ::: "memory")
#define DRAINED(n) do { asm volatile("cp.async.bulk.wait_group.read " #n ";" ::: "memory"); __syncwarp(); } while (0)
#define WRITTEN() do { asm volatile("cp.async.bulk.wait_group 0;\nfence.proxy.async.global;" ::: "memory"); __syncwarp(); } while (0)
__device__ __forceinline__ void wait_flags(const uint32_t* p, uint32_t target) {
  int n = 0;
  while (!__all_sync(~0u, ld_relaxed(p) >= target)) { if (++n > SPIN_LIMIT) FAIL(); }
  asm volatile("fence.acquire.gpu;" ::: "memory");
  asm volatile("fence.proxy.async.global;" ::: "memory");
}
__global__ void __launch_bounds__(512, 1) bworker_kernel(const __grid_constant__ BParams P) {
  extern __shared__ __align__(1024) unsigned char smem_raw[];
  const uint32_t sb = SMEM0, bar = sb + BO_BAR;
  const int wg = __shfl_sync(~0u, threadIdx.x >> 7, 0), warp = __shfl_sync(~0u, (threadIdx.x >> 5) & 3, 0);
  if (threadIdx.x == 0) {
    if (smem_u32(smem_raw) != SMEM0) FAIL();
    uint32_t smid; asm volatile("mov.u32 %0, %%smid;" : "=r"(smid));
    const uint32_t nb = ld_relaxed(&g_tpc[(smid >> 1) & 127]);
    const bool single = nb > 1, far = nb == 0 && (smid < 64 || smid >= 124);
    int kind = far || (single && atomicAdd(&g_f[F_MISC][35], 1u) < SINGLE_OP) ? 0 : single ? 1 + SINGLE_W : 1;
    int rc = (RCV ? smid >= 128 : single) || (smid >> 1) == 16 || (smid >> 1) == 63 ? 1 : far || single ? 2 : 0;
    uint32_t i = atomicAdd(&g_f[F_MISC][32 + kind], 1u), o = atomicAdd(&g_f[F_MISC][36 + rc], 1u);
    while (i >= (kind == 0 ? NOP : kind == 1 ? NW12 : NW34)) { kind = (kind + 1) % 3; i = atomicAdd(&g_f[F_MISC][32 + kind], 1u); }
    while (o >= (rc == 0 ? 16 : rc == 1 ? 8 : 12)) { rc = (rc + 1) % 3; o = atomicAdd(&g_f[F_MISC][36 + rc], 1u); }
    if (RCV && rc == 2) o = single ? 11 - atomicAdd(&g_f[F_MISC][40], 1u) : atomicAdd(&g_f[F_MISC][41], 1u);
    sts64(sb + BO_BOX, i + (kind == 0 ? 0 : kind == 1 ? NOP : NOP + NW12), o + (rc ? 8 + 8 * rc : 0));
    for (int k = 0; k < BB_NUM; k++) mbar_init(bar + 8 * k, k >= BB_USED ? 4 : k >= BB_EMPTY ? 8 : k >= BB_ZFREE && kind ? 2 : 1);
    asm volatile("fence.mbarrier_init.release.cluster;" ::: "memory");
  }
  if (threadIdx.x < 128) sts128(sb + BO_CARRY + threadIdx.x * 16, 0u, 0u, 0u, 0u);
  auto ln0 = [&](int t) {
    const int lane = lane_of(t);
    if (lane < 20 && t + 128 < S_LEN) asm volatile("prefetch.global.L2 [%0];" :: "l"(P.x + (t + (t < 4 * NBC ? 4 * NBC : 128)) * DM + (lane >> 1) * 64));
    rrow<3>(0, 0, t, lane, nullptr, 0, P.x, nullptr);
    __syncwarp();
    asm volatile("fence.release.gpu;" ::: "memory");
    red_if(lane == 0, &g_xready[t >> 5][0]);
  };
  if (wg == 2) ln0(blockIdx.x * 4 + warp);
  fence_async();
  __syncthreads();
  const int role = uni(lds32(sb + BO_BOX));
  if (threadIdx.x < 32) BTS(94, 1);
  const bool op = role < NOP, w12 = role < NOP + NW12;
  const int j = op ? role : w12 ? role - NOP : role - NOP - NW12;
  const int rot = op ? (j ? 2 * ((j + 1) % 5) : 0) : 2 * (j % 5);
  if (wg == 3) {
    asm volatile("setmaxnreg.dec.sync.aligned.u32 24;");
    LANE_INIT();
    if (warp < 2) {
      auto announce = [&](int r) {
        const uint32_t* f = &g_f[(op ? F_R1 : w12 ? F_R2 : F_R3) + (lane & 3)][r];
        asm volatile("" : "+l"(f));
        if (warp == 0) { mbar_arrive_if(lane == 0, bar + 8 * BB_DONE); return; }
        mbar_waitw(bar + 8 * BB_DONE, r & 1);
        PTS(60);
        asm volatile("fence.release.gpu;" ::: "memory");
        red_if(lane >= 4 ? 0 : op ? NW12 * NW34 : w12 ? NOP * NW34 : NOP * NW12, f);
        PTS(61);
        BTS(r, 4);
      };
      if (op) {
        int mt = rot + warp;
        bar_arrive(NB_FREE + warp, 160);
#pragma unroll 1
        for (int r = 0; r < NSTEP; r++) {
          const uint32_t len = fmask(r) == 3 ? 8192 : 4096;
          unsigned char* acc = &g_acc[j & 1][r % RD][fmask(r) == 2 ? 4096 : 0];
#pragma unroll 1
          for (int p = 0; p < 5; p++) {
            bar_sync(NB_STAGED + warp, 160);
            PTS(50 + 2 * p + warp);
            fence_async();
            BULK_ADD("bf16", acc + mt * 8192, sb + BO_STG + warp * 8192, len);
            COMMIT();
            PTS(64 + 50 + 2 * p + warp);
            mt = mt >= 8 ? mt - 8 : mt + 2;
            DRAINED(0);
            bar_arrive(NB_FREE + warp, 160);
          }
          WRITTEN();
          announce(r);
        }
      } else {
#pragma unroll 1
        for (int r = 0; r < NR; r++) {
          const uint32_t len = bmask(r) == 3 ? 8192 : 4096;
          unsigned char* acc = &g_acc[2][r % RD][bmask(r) == 2 ? 4096 : 0];
          if (!w12) mbar_waitw(bar + 8 * BB_GO, r & 1);
          int mt = rot + warp;
          const bool pairs = len != 8192;
#pragma unroll 1
          for (int p = pairs ? 2 : 0; p < 5; p++) {
            const uint32_t src = sb + (p == 4 ? BO_H : BO_RING_MLP + (2 - (p & 1)) * 16384) + warp * 8192;
            bar_sync(NB_STAGED + (p == 4 ? 4 : 2 * (p & 1)) + warp, 160);
            PTS(50 + 2 * p + warp);
            fence_async();
            BULK_ADD("f16", acc + mt * 8192, src, len);
            mt = mt >= 8 ? mt - 8 : mt + 2;
            if (pairs && p < 4) { BULK_ADD("f16", acc + mt * 8192, src + 4096, len); mt = mt >= 8 ? mt - 8 : mt + 2; }
            COMMIT();
            PTS(64 + 50 + 2 * p + warp);
            if (p == 4 && !pairs) break;
            DRAINED(1);
            mbar_arrive_if(lane == 0 && p, bar + 8 * (p < 3 ? BB_SFREE + 2 * (p - 1) + warp : BB_ZFREE + (p >> 1)));
            mbar_arrive_if(lane == 0 && pairs && p == 2, bar + 8 * (BB_SFREE + warp));
            if (p == 3 && !pairs) { DRAINED(0); mbar_arrive_if(lane == 0, bar + 8 * (BB_ZFREE + 2)); }
          }
          WRITTEN();
          mbar_arrive_if(lane == 0, bar + 8 * (BB_SFREE + 4 + warp));
          announce(r);
        }
      }
    } else {
      if (op && warp == 2) {
        unsigned char* wt = g_wt + j * (10 * OP_SLOT);
#pragma unroll 1
        for (int m0 = 0; m0 < 10; m0 += 3) {
          const int nu = m0 < 9 ? 9 : 3;
          mbar_expect_if(lane == 0, bar + 8 * BB_TMP, nu * 4096);
#pragma unroll 1
          for (int k = 0; k < nu; k++) tma2d_e(sb + BO_RING_OP + k * 4096, &P.wmap[0], (m0 + k / 3) * 64, 320 * j + 224 + 32 * (k % 3), bar + 8 * BB_TMP);
          mbar_waitw(bar + 8 * BB_TMP, m0 & 1);
          bulk_s2g_e(wt + m0 * OP_SLOT, sb + BO_RING_OP, nu * 4096);
          COMMIT();
          WRITTEN();
        }
        asm volatile("fence.acq_rel.gpu;" ::: "memory");
        int sl = 0, ph = 1, mt = rot;
#pragma unroll 1
        for (int r = -1; r < NSTEP; r++) {
#pragma unroll 1
          for (int n = r < 0 ? 7 : 0; n < (r + 1 < NSTEP ? 10 : 7); n++) {
            mbar_waitw(bar + 8 * (BB_USED + sl), ph);
            mbar_expect_if(lane == 0, bar + 8 * (BB_FULL + sl), OP_SLOT);
            bulk_g2s_e(sb + BO_RING_OP + sl * OP_SLOT, wt + mt * OP_SLOT, OP_SLOT, bar + 8 * (BB_FULL + sl));
            if (++sl == 3) { sl = 0; ph ^= 1; }
            mt = mt == 9 ? 0 : mt + 1;
          }
        }
      } else if (op) {
        mbar_waitw(bar + 8 * BB_START, 0);
#pragma unroll 1
        for (int r = 0; r < NSTEP; r++) {
          const int rb = r - RD + 1;
          const uint32_t len = fmask(r) == 3 ? 8192 : 4096;
          const unsigned char* src = g_o + (uint32_t)(r % RO * (96 * 8192) + 5 * j * len);
          wait_flags(lane < 2 ? &g_f[F_O + (lane ? NOP : j)][r] : rb >= 0 ? &g_f[F_DONE][rb] : &g_f[F_MISC][0],
                     lane < 2 ? (lane ? 1 : 5) : rb >= 0 ? rtarget(bmask(rb)) : NBC * 8);
          PTS1(35);
          auto two = [&](int k, uint32_t mb) {
            bulk_g2s_e(sb + BO_O + k * 8192, src + k * len, len == 8192 ? 16384 : 4096, mb);
            if (len != 8192) bulk_g2s_e(sb + BO_O + k * 8192 + 8192, src + k * len + 4096, 4096, mb);
          };
          mbar_expect_if(lane == 0, bar + 8 * (BB_OFULL + 2 + (r & 1)), len);
          bulk_g2s_e(sb + BO_O + (r & 1 ? 5 : 2) * 8192, src + 2 * len, len, bar + 8 * (BB_OFULL + 2 + (r & 1)));
          if (r) bar_sync(NB_EARLY, 288);
          mbar_expect_if(lane < 2, bar + 8 * (BB_OFULL + lane), 2 * len + (lane ? len / 4 : 0));
          two(0, bar + 8 * BB_OFULL);
          PTS(62); PTS1(38);
          const unsigned char* sx = src + (95 - 5 * j) * len + (j + 1) / 5 * 1024;
          if (r) bar_sync(NB_LAST, 288);
          two(3, bar + 8 * (BB_OFULL + 1));
          bulk_g2s_e(sb + BO_CARRY, sx, 1024, bar + 8 * (BB_OFULL + 1));
          if (len == 8192) bulk_g2s_e(sb + BO_CARRY + 1024, sx + 4096, 1024, bar + 8 * (BB_OFULL + 1));
          if (r && r + 1 < NSTEP) {
            mbar_waitw(bar + 8 * (BB_USED + (10 * r - 2) % 3), (10 * r - 2) / 3 & 1);
            mbar_waitw(bar + 8 * (BB_USED + (10 * r - 1) % 3), (10 * r - 1) / 3 & 1);
          }
          PTS1(64 + 35);
          BTS(r, 0);
        }
      } else if (warp == 2) {
#pragma unroll 1
        for (int r = 0; r < NR; r++) {
          const int mk = w12 ? fmask(r) : bmask(r);
          if (mk) {
            const unsigned char* src = &g_acc[w12 ? 3 : 2][r % RD][mk == 2 ? 4096 : 0];
            wait_flags(&g_f[w12 ? F_Z : F_R2 + (j & 3)][r], w12 ? rtarget(mk) : NOP * NW12 * NW34);
#pragma unroll 1
            for (int z = 0; z < 5; z++) {
              const int k = mk == 3 ? z : z >> 1;
              const uint32_t fb = bar + 8 * (BB_FULL + z), dst = sb + BO_RING_MLP + 2 * k % 3 * 16384 + (mk == 3 ? 0 : (z & 1) * 4096);
              if (mk == 3 || !(z & 1)) mbar_waitw(bar + 8 * (k < 3 ? BB_ZFREE + k : BB_EMPTY + k - 3), (r + (k < 3)) & 1);
              if (z == 0) PTS(62);
              mbar_expect_if(lane == 0, fb, mk == 3 ? 16384 : 8192);
              bulk_g2s_e(dst, src + z * 16384, mk == 3 ? 16384 : 4096, fb);
              if (mk != 3) bulk_g2s_e(dst + 8192, src + z * 16384 + 8192, 4096, fb);
              if (z == 0) BTS(r, 0);
            }
          }
          if (!w12) {
#pragma unroll 1
            for (int z = mk == 3 ? 2 : 0; z < 5; z++) mbar_waitw(bar + 8 * (BB_FULL + z), r & 1);
            red_if(lane == 0, &g_f[F_GOT][r]);
#pragma unroll 1
            for (int c = j; c < 80; c += NW34) bulk_s2g_e(&g_acc[c / 40][r % RD][c % 40 * 2048], sb + BO_CARRY, 2048);
            COMMIT();
            wait_flags(&g_f[F_GOT][r], NW34);
            mbar_arrive_if(lane == 0, bar + 8 * BB_GO);
            WRITTEN();
          }
          mbar_waitw(bar + 8 * BB_DONE, (r + 1) & 1);
          mbar_arrive_if(lane == 0, bar + 8 * BB_DONE);
        }
      } else {
#pragma unroll 1
        for (int r = 0; r < (w12 ? NSTEP : NR); r++) {
          const bool idle = !((w12 ? fmask(r) : bmask(r)) >> (lane >> 4) & 1);
          uint32_t t0, t1;
          int n = 0;
          mbar_waitw(bar + 8 * BB_FULL, r & 1);
          do {
            asm volatile("ld.relaxed.gpu.global.v2.u32 {%0,%1}, [%2];" : "=r"(t0), "=r"(t1) : "l"(&g_st2[!w12][r % RD][2 * lane]) : "memory");
            if (++n > SPIN_LIMIT) FAIL();
          } while (!__all_sync(~0u, idle || (((t0 ^ (r + 1)) | (t1 ^ (r + 1))) & 127) == 0));
          sts64(sb + BO_STAT + (lane >> 4) * 128 + (lane & 3) * 32 + ((lane >> 2) & 3) * 8, t0, t1);
          __syncwarp();
          mbar_arrive_if(lane == 0, bar + 8 * BB_STAT);
          PTS(63);
        }
      }
    }
    bar_arrive(NB_END, 512);
  } else if (wg == 2) {
    asm volatile("setmaxnreg.dec.sync.aligned.u32 40;");
    const int ord = uni(lds32(sb + BO_BOX + 4));
    const int gw = ord < 16 ? warp * 16 + ord : ord < 24 ? 48 + warp * 8 + ord : !RCV ? 72 + warp * 12 + ord : ord >= 32 ? 97 + 2 * (warp * 4 + ord - 32) : warp < 2 ? 48 + 2 * (warp * 8 + ord) : 88 + warp * 8 + ord, row = gw < 64 ? gw : gw < 96 ? gw - 64 : gw < 128 ? 2 * gw - 192 : 2 * gw - 224;
    if (row >= 32) {
#pragma unroll 1
      for (int t = 4 * NBC + (gw < 64 ? gw - 32 : gw - 80); t < S_LEN; t += 64) ln0(t);
    }
    if (gw < 64) rloop<0>(row, gw & 3, role, P.x, P.out);
    else if (gw < 96) rloop<2>(row, gw & 3, role, P.x, P.out);
    else if (gw < 128) rloop<1>(row, gw & 3, role, P.x, P.out);
    else rloop<4>(row, gw & 3, role, P.x, P.out);
    asm volatile("griddepcontrol.wait;" ::: "memory");
    const int t = threadIdx.x & 127;
    for (int i = (blockIdx.x * 128 + t) * 4; i < 4 * NCL * 2560; i += NBC * 512)
      *reinterpret_cast<uint4*>(&g_part[0][0][0][0] + i) = make_uint4(0u, 0u, 0u, 0u);
    bar_sync(NB_END, 512);
    if (t == 0) {
      uint32_t n;
      asm volatile("atom.acq_rel.gpu.global.add.u32 %0, [%1], 1;" : "=r"(n) : "l"(&g_f[F_MISC][64]) : "memory");
      sts32(sb + BO_BOX, n);
    }
    bar_sync(NB_END2, 128);
    if (lds32(sb + BO_BOX) == NBC - 1) {
      for (int i = t; i < F_NUM * 24; i += 128) reinterpret_cast<uint4*>(&g_f[0][0])[i] = make_uint4(0u, 0u, 0u, 0u);
      g_xready[t][0] = 0; g_tpc[t] = 0;
    }
  } else {
    asm volatile("setmaxnreg.inc.sync.aligned.u32 224;");
    LANE_INIT();
    for (int i = blockIdx.x * 256 + threadIdx.x; i < 2 * RD * TILE_B / 16; i += NBC * 256) reinterpret_cast<uint4*>(&g_acc[0][0][0])[i] = make_uint4(0u, 0u, 0u, 0u);
    warp_signal(&g_f[F_MISC][0], lane);
    const int mt0 = (rot + wg) % 10;
    auto boxes = [&](int ss) {
      const int nb = op && ss ? 3 : 4;
      const uint32_t base = sb + (ss ? BO_RES + wg * OP_RES : wg * 83968);
      mbar_expect_if(warp == 0 && lane == 0, bar + 8 * (BB_W + wg), nb * 20480 + (op ? 2048 : 0));
      bar_sync(NB_H, 256);
      if (warp < nb) {
#pragma unroll 1
        for (int i = warp; i < 5 * nb; i += nb) {
          const int p = op ? i / nb : (i - 10) >> 1, mt = (mt0 + 2 * p) % 10;
          const bool first = !op && i < 10;
          tma2d_e(op || !ss ? base + i * 4096 : sb + (first ? BO_W1 : -81920) + (2 * i + wg) * 4096, &P.wmap[op ? 0 : (w12 ? 1 : 3) + !first], first ? 128 * j + 64 * wg : mt * 64,
                  op ? 320 * j + 64 * warp + 32 * ss : first ? 64 * i + 32 * ss : 128 * j + 32 * (i & 1) + 64 * ss, bar + 8 * (BB_W + wg));
        }
      }
      if (op && warp == 3) tma2d_e(base + nb * 20480, &P.wo16, (mt0 + 2 * ss) % 10 * 64, 95 * 64 + (j + 1) / 5 * 16, bar + 8 * (BB_W + wg));
      mbar_waitw(bar + 8 * (BB_W + wg), ss);
    };
    if (W_DELAY && !op) __nanosleep(W_DELAY);
    uint32_t W[164];
    boxes(0);
    load_w<41>(W, sb + wg * 83968, warp, lane);
    fence_async();
    boxes(1);
    if (!op) {
      float cs[2] = {0.f, 0.f};
      const uint32_t a0 = sb + BO_W1 + wg * 4096 + ((lane >> 4) * 8 + (lane & 7)) * 128 + (((warp * 2 + ((lane >> 3) & 1)) ^ (lane & 7)) << 4);
#pragma unroll
      for (int i = 0; i < 80; i++) cs[i & 1] += bf_lo(W[i]) + bf_hi(W[i]);
#pragma unroll 1
      for (int i = 0; i < 40; i++) {
        uint32_t t[4];
        const uint32_t ad = a0 + (i % 20 >> 1) * 8192 + (i & 1) * 2048;
        ldsm4t(t[0], t[1], t[2], t[3], ad);
#pragma unroll
        for (int k = 0; k < 4; k++) {
          if (i < 20) cs[k & 1] += bf_lo(t[k]) + bf_hi(t[k]);
          t[k] = pack2h(bf_lo(t[k]) - cs[k & 1], bf_hi(t[k]) - cs[k & 1]);
        }
        if (i >= 20) stsm4t(ad, t[0], t[1], t[2], t[3]);
        if (i == 19) {
#pragma unroll
          for (int k = 0; k < 2; k++) { cs[k] += __shfl_xor_sync(~0u, cs[k], 1); cs[k] += __shfl_xor_sync(~0u, cs[k], 2); cs[k] *= 1.f / DM; }
        }
      }
      const uint32_t z = dep0(__float_as_uint(cs[0]), lane);
#pragma unroll
      for (int i = 0; i < 80; i++) W[i] = pack2h(bf_lo(W[i] | z) - cs[i & 1], bf_hi(W[i] | z) - cs[i & 1]);
      fence_async();
      bar_sync(NB_H, 256);
    }
    if (warp == 0) BTS(94, 6 + wg);
    const Dsc blo = {P.desc, 1}, alo = blo + wg * (op ? OP_RES / 16 : 256);
    if (op) {
      Ring rg = {(uint32_t)wg, 0};
      mbar_arrive_if(lane == 0, bar + 8 * BB_START);
      if (wg) bar_arrive(NB_PP, 256);
      const Dsc xlo = {P.desc32, 1};
#pragma unroll 1
      for (int r = 0; r < NSTEP; r++) {
        asm volatile("" : "+r"(lane));
        if (fmask(r) == 3) op_round<64>(W, bar, alo, blo, xlo, j == 0, rg, wg, warp, lane, r);
        else op_round<32>(W, bar, alo, blo, xlo, j == 0, rg, wg, warp, lane, r);
        if (warp == 0) BTS(r, 2 + wg);
      }
    } else {
      const int q4 = (128 * j + 64 * wg + 16 * warp) / 160, off = w12 ? (0x0413 >> (4 * q4)) & 7 : 0;
#pragma unroll 1
      for (int r = 0; r < NR; r++) {
        asm volatile("" : "+r"(lane));
        const int bm = bmask(r), fm = w12 ? fmask(r) : bm;
        if (fm == 3) phase1<64>(W, sb, alo, blo, 0, wg, warp, lane, off, r);
        else if (fm) phase1<32>(W, sb, alo, blo, fm >> 1, wg, warp, lane, off, r);
        else { mbar_waitu(bar + 8 * (BB_SFREE + 4 + wg), (r + 1) & 1); carry_in(sb, wg, warp, lane); }
        CTS(33);
        fence_async();
        bar_sync(NB_H, 256);
        mbar_arrive_if(wg == 1 && warp == 0 && lane < 2, bar + 8 * BB_ZFREE);
        if (wg + warp == 0) BTS(r, 1);
        if (bm == 3) phase2<64>(W, bar, alo, blo, wg, warp, lane, r);
        else phase2<32>(W, bar, alo, blo + (bm >> 1) * 256, wg, warp, lane, r);
        if (warp == 0) BTS(r, 2 + wg);
      }
    }
    CTS_OUT();
    bar_arrive(NB_END, 512);
  }
}

typedef CUresult (*EncodeFn)(CUtensorMap*, CUtensorMapDataType, cuuint32_t, void*, const cuuint64_t*, const cuuint64_t*, const cuuint32_t*,
                             const cuuint32_t*, CUtensorMapInterleave, CUtensorMapSwizzle, CUtensorMapL2promotion, CUtensorMapFloatOOBfill);
static void make_map(EncodeFn fn, CUtensorMap* tm, const void* ptr, uint64_t cols, uint64_t rows, uint32_t bc, uint32_t br) {
  cuuint64_t dims[2] = {cols, rows}; cuuint64_t strides[1] = {cols * 2}; cuuint32_t box[2] = {bc, br}; cuuint32_t es[2] = {1, 1};
  fn(tm, CU_TENSOR_MAP_DATA_TYPE_BFLOAT16, 2, const_cast<void*>(ptr), dims, strides, box, es, CU_TENSOR_MAP_INTERLEAVE_NONE,
     CU_TENSOR_MAP_SWIZZLE_128B, CU_TENSOR_MAP_L2_PROMOTION_L2_256B, CU_TENSOR_MAP_FLOAT_OOB_FILL_NONE);
}
#define dbg_a_only 0
extern "C" void kernel_launch(void* const* d_in, const int* in_sizes, int n_in, void* d_out, int out_size) {
  void* fnp = nullptr; cudaDriverEntryPointQueryResult qr;
  cudaGetDriverEntryPoint("cuTensorMapEncodeTiled", &fnp, cudaEnableDefault, &qr);
  EncodeFn fn = (EncodeFn)fnp;
  cudaStream_t st = cudaStreamPerThread;
  cudaFuncSetAttribute(bworker_kernel, cudaFuncAttributeMaxDynamicSharedMemorySize, B_SMEM);
  {
    AMaps M;
    for (int i = 0; i < 3; i++) make_map(fn, &M.w16[i], d_in[2 + i], HD, DM, 64, 16);
    M.wv = (const __nv_bfloat16*)d_in[4];
    make_map(fn, &M.wo32, d_in[5], DM, HD, 64, 32);
    const uint32_t hi[5] = {dhi(TILE_SBO, 3), dhi(1024, 1), dhi(1024, 0), dhi(PL_SZ, 0), dhi(896, 0)};
    for (int i = 0; i < 5; i++) M.d[i] = (uint64_t)hi[i] << 32;
    cudaFuncSetAttribute(acore_kernel, cudaFuncAttributeMaxDynamicSharedMemorySize, A_SMEM);
    cudaFuncSetAttribute(acore_kernel, cudaFuncAttributeNonPortableClusterSizeAllowed, 1);
    cudaLaunchConfig_t cfg = {};
    cfg.gridDim = dim3(CL_SIZE * NCL); cfg.blockDim = dim3(512); cfg.dynamicSmemBytes = A_SMEM; cfg.stream = st;
    cudaLaunchAttribute at[1]; at[0].id = cudaLaunchAttributeClusterDimension;
    at[0].val.clusterDim.x = CL_SIZE; at[0].val.clusterDim.y = 1; at[0].val.clusterDim.z = 1;
    cfg.attrs = at; cfg.numAttrs = 1;
    cudaLaunchKernelEx(&cfg, acore_kernel, M, (const __nv_bfloat16*)d_in[1], dbg_a_only ? 0 : 1);
  }
  if (!dbg_a_only) {
    BParams P;
    make_map(fn, &P.wmap[0], d_in[5], DM, HD, 64, 32);
    make_map(fn, &P.wo16, d_in[5], DM, HD, 64, 16);
    make_map(fn, &P.wmap[1], d_in[8], DM, DM, 64, 32);
    make_map(fn, &P.wmap[2], d_in[9], DM, DM, 64, 32);
    make_map(fn, &P.wmap[3], d_in[10], FF, DM, 64, 32);
    make_map(fn, &P.wmap[4], d_in[11], DM, FF, 64, 32);
    P.x = (const __nv_bfloat16*)d_in[0];
    P.out = (__nv_bfloat16*)d_out;
    P.desc = (uint64_t)dhi(1024, 1) << 32;
    P.desc32 = (uint64_t)dhi(256, 3) << 32;
    cudaLaunchConfig_t cfg = {};
    cfg.gridDim = dim3(NBC); cfg.blockDim = dim3(512); cfg.dynamicSmemBytes = B_SMEM; cfg.stream = st;
    cudaLaunchAttribute at[1]; at[0].id = cudaLaunchAttributeProgrammaticStreamSerialization; at[0].val.programmaticStreamSerializationAllowed = 1;
    cfg.attrs = at; cfg.numAttrs = 1;
    cudaLaunchKernelEx(&cfg, bworker_kernel, P);
  }
}
```

```cpp
#include <cuda_runtime.h>
#include <cuda_bf16.h>
#include <cuda.h>
#include <stdint.h>

#define S_LEN 2048
#define DM 640
#define NH 32
#define DH 192
#define HD 6144
#define NSEG 64
#define FF 1536

__device__ __forceinline__ uint32_t smem_u32(const void* p) { return (uint32_t)__cvta_generic_to_shared(p); }
__device__ __forceinline__ uint32_t mapa(uint32_t a, uint32_t r) {
  uint32_t o; asm volatile("mapa.shared::cluster.u32 %0, %1, %2;" : "=r"(o) : "r"(a), "r"(r)); return o; }
__device__ __forceinline__ void mbar_init(uint32_t b, uint32_t c) {
  asm volatile("mbarrier.init.shared::cta.b64 [%0], %1;" :: "r"(b), "r"(c) : "memory"); }
__device__ __forceinline__ void mbar_expect(uint32_t b, uint32_t tx) {
  asm volatile("mbarrier.arrive.expect_tx.shared::cta.b64 _, [%0], %1;" :: "r"(b), "r"(tx) : "memory"); }
__device__ __forceinline__ void mbar_arrive(uint32_t b) {
  asm volatile("mbarrier.arrive.shared::cta.b64 _, [%0];" :: "r"(b) : "memory"); }
__device__ __forceinline__ void mbar_arrive_remote(uint32_t rb) {
  asm volatile("mbarrier.arrive.relaxed.cluster.shared::cluster.b64 _, [%0];" :: "r"(rb) : "memory"); }
__device__ __forceinline__ void mbar_expect_if(bool p, uint32_t b, uint32_t tx) {
  asm volatile("{\n.reg .pred q;\nsetp.ne.u32 q, %2, 0;\n@q mbarrier.arrive.expect_tx.shared::cta.b64 _, [%0], %1;\n}" :: "r"(b), "r"(tx), "r"((uint32_t)p) : "memory"); }
__device__ __forceinline__ void mbar_arrive_if(bool p, uint32_t b) {
  asm volatile("{\n.reg .pred q;\nsetp.ne.u32 q, %1, 0;\n@q mbarrier.arrive.shared::cta.b64 _, [%0];\n}" :: "r"(b), "r"((uint32_t)p) : "memory"); }
__device__ __forceinline__ void mbar_arrive_remote_if(bool p, uint32_t rb) {
  asm volatile("{\n.reg .pred q;\nsetp.ne.u32 q, %1, 0;\n@q mbarrier.arrive.relaxed.cluster.shared::cluster.b64 _, [%0];\n}" :: "r"(rb), "r"((uint32_t)p) : "memory"); }
__device__ __forceinline__ void sts32_if(bool p, uint32_t a, uint32_t v) {
  asm volatile("{\n.reg .pred q;\nsetp.ne.u32 q, %2, 0;\n@q st.shared.b32 [%0], %1;\n}" :: "r"(a), "r"(v), "r"((uint32_t)p) : "memory"); }
__device__ __forceinline__ void sts128z_if(bool p, uint32_t a) {
  asm volatile("{\n.reg .pred q;\nsetp.ne.u32 q, %1, 0;\n@q st.shared.v4.b32 [%0], {0,0,0,0};\n}" :: "r"(a), "r"((uint32_t)p) : "memory"); }
__device__ __forceinline__ bool mbar_try(uint32_t b, uint32_t ph) {
  uint32_t ok;
  asm volatile("{\n.reg .pred p;\nmbarrier.try_wait.parity.shared::cta.b64 p, [%1], %2;\nselp.u32 %0, 1, 0, p;\n}"
               : "=r"(ok) : "r"(b), "r"(ph) : "memory");
  return ok; }
__device__ __forceinline__ bool mbar_test(uint32_t b, uint32_t ph) {
  uint32_t ok;
  asm volatile("{\n.reg .pred p;\nmbarrier.test_wait.parity.shared::cta.b64 p, [%1], %2;\nselp.u32 %0, 1, 0, p;\n}"
               : "=r"(ok) : "r"(b), "r"(ph) : "memory");
  return ok; }
#define SPIN_LIMIT 4000000
#define FAIL() asm volatile("st.global.u32 [%0], 0;" :: "l"(8ull) : "memory")
#define CFENCE() asm volatile("fence.proxy.async::generic.acquire.sync_restrict::shared::cluster.cluster;" ::: "memory")
__device__ __forceinline__ void mbar_wait(uint32_t b, uint32_t ph) {
  int n = 0;
  while (!mbar_try(b, ph)) { if (++n > SPIN_LIMIT) FAIL(); } }
#define TIMEOUT_ACT "@!p st.shared.u32 [%0+1], 0;"
#define WAIT_HINT ", 20000"
#define WAIT_LIM "200000"
__device__ __forceinline__ void mbar_slow(uint32_t b, uint32_t ph) {
  asm volatile("{\n.reg .pred p, q;\n.reg .u32 n;\nmov.u32 n, 0;\n"
               "WL:\nmbarrier.try_wait.parity.shared::cta.b64 p, [%0], %1" WAIT_HINT ";\nadd.u32 n, n, 1;\nsetp.lt.and.u32 q, n, " WAIT_LIM ", !p;\n@q bra.uni WL;\n"
               TIMEOUT_ACT "\n}" :: "r"(b), "r"(ph) : "memory"); }
__device__ __forceinline__ void mbar_waitw(uint32_t b, uint32_t ph) {
  asm volatile("{\n.reg .pred p, q;\n.reg .u32 n;\nmbarrier.try_wait.parity.shared::cta.b64 p, [%0], %1;\n@p bra.uni WD;\nmov.u32 n, 0;\n"
               "WL:\nmbarrier.try_wait.parity.shared::cta.b64 p, [%0], %1" WAIT_HINT ";\nadd.u32 n, n, 1;\nsetp.lt.and.u32 q, n, " WAIT_LIM ", !p;\n@q bra.uni WL;\n"
               TIMEOUT_ACT "\nWD:\n}" :: "r"(b), "r"(ph) : "memory"); }
__device__ __forceinline__ void mbar_waitw2(uint32_t b0, uint32_t b1, uint32_t ph) {
  uint32_t ok;
  asm volatile("{\n.reg .pred p, r;\nmbarrier.try_wait.parity.shared::cta.b64 p, [%1], %3;\nmbarrier.try_wait.parity.shared::cta.b64 r, [%2], %3;\n"
               "and.pred p, p, r;\nselp.u32 %0, 1, 0, p;\n}" : "=r"(ok) : "r"(b0), "r"(b1), "r"(ph) : "memory");
  if (__builtin_expect(!__all_sync(~0u, ok), 0)) { mbar_slow(b0, ph); mbar_slow(b1, ph); }
}
__device__ __forceinline__ void mbar_waitu(uint32_t b, uint32_t ph) {
  asm volatile("{\n.reg .pred p;\nmbarrier.try_wait.parity.shared::cta.b64 p, [%0], %1;\n@p bra.uni WD;\n"
               "WL:\nmbarrier.try_wait.parity.shared::cta.b64 p, [%0], %1" WAIT_HINT ";\n@!p bra.uni WL;\nWD:\n}" :: "r"(b), "r"(ph) : "memory"); }
__device__ __forceinline__ void mbar_waitu2(uint32_t b0, uint32_t b1, uint32_t ph) {
  asm volatile("{\n.reg .pred p, r;\nWL:\nmbarrier.try_wait.parity.shared::cta.b64 p, [%0], %2;\nmbarrier.try_wait.parity.shared::cta.b64 r, [%1], %2;\n"
               "and.pred p, p, r;\n@!p bra.uni WL;\n}" :: "r"(b0), "r"(b1), "r"(ph) : "memory"); }
__device__ __forceinline__ void mbar_waitw4(uint32_t b, uint32_t ph) { mbar_waitw2(b, b + 8, ph); mbar_waitw2(b + 16, b + 24, ph); }
__device__ __forceinline__ uint32_t clock32() { uint32_t t; asm volatile("mov.u32 %0, %%clock;" : "=r"(t) :: "memory"); return t; }
template <int L> __device__ __forceinline__ uint32_t lop3(uint32_t a, uint32_t b, uint32_t c) {
  uint32_t r; asm("lop3.b32 %0, %1, %2, %3, %4;" : "=r"(r) : "r"(a), "r"(b), "r"(c), "n"(L)); return r; }
__device__ __forceinline__ void st_async_v2_if(bool p, uint32_t a, uint32_t v0, uint32_t v1, uint32_t mb) {
  asm volatile("{\n.reg .pred q;\nsetp.ne.u32 q, %4, 0;\n@q st.async.weak.shared::cluster.mbarrier::complete_tx::bytes.v2.b32 [%0], {%1,%2}, [%3];\n}"
               :: "r"(a), "r"(v0), "r"(v1), "r"(mb), "r"((uint32_t)p) : "memory"); }
__device__ __forceinline__ void keep4(const uint32_t* r, int lane) {
  asm volatile("{\n.reg .pred q;\nsetp.lt.s32 q, %4, 0;\n@q st.shared.v4.b32 [%4], {%0,%1,%2,%3};\n}" :: "r"(r[0]), "r"(r[1]), "r"(r[2]), "r"(r[3]), "r"(lane) : "memory"); }
__device__ __forceinline__ void fence_sched(int i) {
  asm volatile("{\n.reg .pred q;\nsetp.gt.s32 q, %0, 4096;\n@q st.shared.u32 [%0], 0;\n}" :: "r"(i) : "memory"); }
__device__ __forceinline__ uint32_t hmax2bf(uint32_t a, uint32_t b) { uint32_t r; asm("max.bf16x2 %0, %1, %2;" : "=r"(r) : "r"(a), "r"(b)); return r; }
__device__ __forceinline__ uint32_t uni(uint32_t x) { return __shfl_sync(~0u, x, 0); }
__device__ __forceinline__ void bulk_g2s_mc_e(uint32_t dst, const void* src, uint32_t bytes, uint32_t mb, uint16_t mask) {
  asm volatile("{\n.reg .pred e;\nelect.sync _|e, 0xffffffff;\n"
               "@e cp.async.bulk.shared::cluster.global.mbarrier::complete_tx::bytes.multicast::cluster [%0], [%1], %2, [%3], %4;\n}"
               :: "r"(dst), "l"(src), "r"(bytes), "r"(mb), "h"(mask) : "memory"); }
__device__ __forceinline__ void bulk_s2g_e(void* dst, uint32_t src, uint32_t bytes) {
  asm volatile("{\n.reg .pred e;\nelect.sync _|e, 0xffffffff;\n@e cp.async.bulk.global.shared::cta.bulk_group [%0], [%1], %2;\n}"
               :: "l"(dst), "r"(src), "r"(bytes) : "memory"); }
__device__ __forceinline__ void bulk_g2s_e(uint32_t dst, const void* src, uint32_t bytes, uint32_t mb) {
  asm volatile("{\n.reg .pred e;\nelect.sync _|e, 0xffffffff;\n@e cp.async.bulk.shared::cluster.global.mbarrier::complete_tx::bytes [%0], [%1], %2, [%3];\n}"
               :: "r"(dst), "l"(src), "r"(bytes), "r"(mb) : "memory"); }
#define STREAM_HINT 1
__device__ __forceinline__ void bulk_s2g_es(void* dst, uint32_t src, uint32_t bytes) {
  asm volatile("{\n.reg .pred e;\n.reg .b64 pol;\ncreatepolicy.fractional.L2::evict_first.b64 pol;\nelect.sync _|e, 0xffffffff;\n"
               "@e cp.async.bulk.global.shared::cta.bulk_group.L2::cache_hint [%0], [%1], %2, pol;\n}" :: "l"(dst), "r"(src), "r"(bytes) : "memory");
}
__device__ __forceinline__ void bulk_g2s_es(uint32_t dst, const void* src, uint32_t bytes, uint32_t mb) {
  asm volatile("{\n.reg .pred e;\n.reg .b64 pol;\ncreatepolicy.fractional.L2::evict_first.b64 pol;\nelect.sync _|e, 0xffffffff;\n"
               "@e cp.async.bulk.shared::cluster.global.mbarrier::complete_tx::bytes.L2::cache_hint [%0], [%1], %2, [%3], pol;\n}"
               :: "r"(dst), "l"(src), "r"(bytes), "r"(mb) : "memory"); }
__device__ __forceinline__ void tma2d_e(uint32_t dst, const CUtensorMap* tm, int c0, int c1, uint32_t mb) {
  asm volatile("{\n.reg .pred e;\nelect.sync _|e, 0xffffffff;\n"
               "@e cp.async.bulk.tensor.2d.shared::cluster.global.mbarrier::complete_tx::bytes [%0], [%1, {%3, %4}], [%2];\n}"
               :: "r"(dst), "l"((uint64_t)tm), "r"(mb), "r"(c0), "r"(c1) : "memory"); }
__device__ __forceinline__ uint32_t hadd2bf(uint32_t a, uint32_t b) {
  uint32_t r; asm("add.rn.bf16x2 %0, %1, %2;" : "=r"(r) : "r"(a), "r"(b)); return r; }
__device__ __forceinline__ void cluster_sync_all() {
  asm volatile("barrier.cluster.arrive.release.aligned;\nbarrier.cluster.wait.acquire.aligned;" ::: "memory"); }
__device__ __forceinline__ void bar_arrive(int id, int n) { asm volatile("bar.arrive %0, %1;" :: "r"(id), "r"(n) : "memory"); }
__device__ __forceinline__ void bar_arrive_dep(int id, int n, uint32_t dep) {
  asm volatile("{\n.reg .u32 t;\nand.b32 t, %2, 0;\nadd.u32 t, t, %0;\nbar.sync t, %1;\n}" :: "r"(id), "r"(n), "r"(dep) : "memory"); }
__device__ __forceinline__ void bar_sync(int id, int n) { asm volatile("bar.sync %0, %1;" :: "r"(id), "r"(n) : "memory"); }
__device__ __forceinline__ void fence_async() { asm volatile("fence.proxy.async.shared::cta;" ::: "memory"); }
__device__ __forceinline__ void st_async_b32(uint32_t a, uint32_t v, uint32_t mb) {
  asm volatile("st.async.weak.shared::cluster.mbarrier::complete_tx::bytes.b32 [%0], %1, [%2];" :: "r"(a), "r"(v), "r"(mb) : "memory"); }
__device__ __forceinline__ void st_async_v2(uint32_t a, uint32_t v0, uint32_t v1, uint32_t mb) {
  asm volatile("st.async.weak.shared::cluster.mbarrier::complete_tx::bytes.v2.b32 [%0], {%1,%2}, [%3];" :: "r"(a), "r"(v0), "r"(v1), "r"(mb) : "memory"); }
__device__ __forceinline__ void st_async_v4(uint32_t a, uint32_t v0, uint32_t v1, uint32_t v2, uint32_t v3, uint32_t mb) {
  asm volatile("st.async.weak.shared::cluster.mbarrier::complete_tx::bytes.v4.b32 [%0], {%1,%2,%3,%4}, [%5];" :: "r"(a), "r"(v0), "r"(v1), "r"(v2), "r"(v3), "r"(mb) : "memory"); }
__device__ __forceinline__ void ldsm4(uint32_t& r0, uint32_t& r1, uint32_t& r2, uint32_t& r3, uint32_t a) {
  asm volatile("ldmatrix.sync.aligned.m8n8.x4.shared.b16 {%0,%1,%2,%3}, [%4];" : "=r"(r0), "=r"(r1), "=r"(r2), "=r"(r3) : "r"(a) : "memory"); }
__device__ __forceinline__ void ldsm4t(uint32_t& r0, uint32_t& r1, uint32_t& r2, uint32_t& r3, uint32_t a) {
  asm volatile("ldmatrix.sync.aligned.m8n8.x4.trans.shared.b16 {%0,%1,%2,%3}, [%4];" : "=r"(r0), "=r"(r1), "=r"(r2), "=r"(r3) : "r"(a) : "memory"); }
__device__ __forceinline__ void stsm2t(uint32_t a, uint32_t r0, uint32_t r1) {
  asm volatile("stmatrix.sync.aligned.m8n8.x2.trans.shared.b16 [%0], {%1,%2};" :: "r"(a), "r"(r0), "r"(r1) : "memory"); }
__device__ __forceinline__ void stsm4t(uint32_t a, uint32_t r0, uint32_t r1, uint32_t r2, uint32_t r3) {
  asm volatile("stmatrix.sync.aligned.m8n8.x4.trans.shared.b16 [%0], {%1,%2,%3,%4};" :: "r"(a), "r"(r0), "r"(r1), "r"(r2), "r"(r3) : "memory"); }
__device__ __forceinline__ uint32_t movm(uint32_t a) {
  uint32_t d; asm volatile("movmatrix.sync.aligned.m8n8.trans.b16 %0, %1;" : "=r"(d) : "r"(a)); return d; }
__device__ __forceinline__ void mma16816(float* d, uint32_t a0, uint32_t a1, uint32_t a2, uint32_t a3, uint32_t b0, uint32_t b1) {
  asm("mma.sync.aligned.m16n8k16.row.col.f32.bf16.bf16.f32 {%0,%1,%2,%3}, {%4,%5,%6,%7}, {%8,%9}, {%0,%1,%2,%3};"
               : "+f"(d[0]), "+f"(d[1]), "+f"(d[2]), "+f"(d[3]) : "r"(a0), "r"(a1), "r"(a2), "r"(a3), "r"(b0), "r"(b1)); }
__device__ __forceinline__ void mma16816v(float* d, uint32_t a0, uint32_t a1, uint32_t a2, uint32_t a3, uint32_t b0, uint32_t b1) {
  asm volatile("mma.sync.aligned.m16n8k16.row.col.f32.bf16.bf16.f32 {%0,%1,%2,%3}, {%4,%5,%6,%7}, {%8,%9}, {%0,%1,%2,%3};"
               : "+f"(d[0]), "+f"(d[1]), "+f"(d[2]), "+f"(d[3]) : "r"(a0), "r"(a1), "r"(a2), "r"(a3), "r"(b0), "r"(b1)); }
__device__ __forceinline__ uint32_t pack2(float lo, float hi) {
  uint32_t r; asm("cvt.rn.bf16x2.f32 %0, %1, %2;" : "=r"(r) : "f"(hi), "f"(lo)); return r; }
__device__ __forceinline__ uint32_t pack2v(float lo, float hi) {
  uint32_t r; asm volatile("cvt.rn.bf16x2.f32 %0, %1, %2;" : "=r"(r) : "f"(hi), "f"(lo)); return r; }
__device__ __forceinline__ float bf_lo(uint32_t w) { return __uint_as_float(w << 16); }
__device__ __forceinline__ float bf_hi(uint32_t w) { return __uint_as_float(w & 0xffff0000u); }
__device__ __forceinline__ uint4 lds128(uint32_t a) {
  uint4 v; asm volatile("ld.shared.v4.b32 {%0,%1,%2,%3}, [%4];" : "=r"(v.x), "=r"(v.y), "=r"(v.z), "=r"(v.w) : "r"(a) : "memory"); return v; }
__device__ __forceinline__ uint4 lds128_nv(uint32_t a) {
  uint4 v; asm volatile("ld.shared.v4.b32 {%0,%1,%2,%3}, [%4];" : "=r"(v.x), "=r"(v.y), "=r"(v.z), "=r"(v.w) : "r"(a)); return v; }
__device__ __forceinline__ void st_async_v2_nm(uint32_t a, uint32_t v0, uint32_t v1, uint32_t mb) {
  asm volatile("st.async.weak.shared::cluster.mbarrier::complete_tx::bytes.v2.b32 [%0], {%1,%2}, [%3];" :: "r"(a), "r"(v0), "r"(v1), "r"(mb)); }
__device__ __forceinline__ float rcpf(float x) { float y; asm("rcp.approx.ftz.f32 %0, %1;" : "=f"(y) : "f"(x)); return y; }
__device__ __forceinline__ void sts64(uint32_t a, uint32_t x, uint32_t y) { asm volatile("st.shared.v2.b32 [%0], {%1,%2};" :: "r"(a), "r"(x), "r"(y) : "memory"); }
__device__ __forceinline__ float ex2(float x) { float y; asm("ex2.approx.ftz.f32 %0, %1;" : "=f"(y) : "f"(x)); return y; }
__device__ __forceinline__ uint32_t lds32(uint32_t a) {
  uint32_t v; asm volatile("ld.shared.b32 %0, [%1];" : "=r"(v) : "r"(a) : "memory"); return v; }
__device__ __forceinline__ uint2 lds64(uint32_t a) {
  uint2 v; asm volatile("ld.shared.v2.b32 {%0,%1}, [%2];" : "=r"(v.x), "=r"(v.y) : "r"(a) : "memory"); return v; }
__device__ __forceinline__ void sts128(uint32_t a, uint32_t x, uint32_t y, uint32_t z, uint32_t w) {
  asm volatile("st.shared.v4.b32 [%0], {%1,%2,%3,%4};" :: "r"(a), "r"(x), "r"(y), "r"(z), "r"(w) : "memory"); }
__device__ __forceinline__ void sts32(uint32_t a, uint32_t x) { asm volatile("st.shared.b32 [%0], %1;" :: "r"(a), "r"(x) : "memory"); }
__device__ __forceinline__ void tma2d(uint32_t dst, const CUtensorMap* tm, int c0, int c1, uint32_t mb) {
  asm volatile("cp.async.bulk.tensor.2d.shared::cluster.global.mbarrier::complete_tx::bytes [%0], [%1, {%3, %4}], [%2];"
               :: "r"(dst), "l"((uint64_t)tm), "r"(mb), "r"(c0), "r"(c1) : "memory"); }
__device__ __forceinline__ void tma2d_prefetch(const CUtensorMap* tm, int c0, int c1) {
  asm volatile("cp.async.bulk.prefetch.tensor.2d.L2.global.tile [%0, {%1, %2}];" :: "l"((uint64_t)tm), "r"(c0), "r"(c1) : "memory"); }
__device__ __forceinline__ void bulk_g2s_mc(uint32_t dst, const void* src, uint32_t bytes, uint32_t mb, uint16_t mask) {
  asm volatile("cp.async.bulk.shared::cluster.global.mbarrier::complete_tx::bytes.multicast::cluster [%0], [%1], %2, [%3], %4;"
               :: "r"(dst), "l"(src), "r"(bytes), "r"(mb), "h"(mask) : "memory"); }
__device__ __forceinline__ void bulk_s2g(void* dst, uint32_t src, uint32_t bytes) {
  asm volatile("cp.async.bulk.global.shared::cta.bulk_group [%0], [%1], %2;" :: "l"(dst), "r"(src), "r"(bytes) : "memory"); }
__device__ __forceinline__ void wg_fence() { asm volatile("wgmma.fence.sync.aligned;" ::: "memory"); }
__device__ __forceinline__ void wg_commit() { asm volatile("wgmma.commit_group.sync.aligned;" ::: "memory"); }
template <int N> __device__ __forceinline__ void wg_wait() { asm volatile("wgmma.wait_group.sync.aligned %0;" :: "n"(N) : "memory"); }
__device__ __forceinline__ uint64_t mkdesc(uint32_t addr, uint32_t lbo, uint32_t sbo, uint32_t swz) {
  return (uint64_t)((addr & 0x3FFFF) >> 4) | ((uint64_t)(lbo >> 4) << 16) | ((uint64_t)(sbo >> 4) << 32) | ((uint64_t)swz << 62); }

#define ACC4(d) "+f"(d[0]),"+f"(d[1]),"+f"(d[2]),"+f"(d[3])
#define ACC8(d) ACC4(d), ACC4((d + 4))
#define ACC16(d) ACC8(d), ACC8((d + 8))
#define ACC20(d) ACC16(d), ACC4((d + 16))
#define ACC24(d) ACC16(d), ACC8((d + 16))
#define SMEM0 0x400
__host__ __device__ constexpr uint32_t dlo(uint32_t off, uint32_t lbo) { return ((SMEM0 + off) >> 4) | ((lbo >> 4) << 16); }
__host__ __device__ constexpr uint32_t dhi(uint32_t sbo, uint32_t swz) { return (sbo >> 4) | (swz << 30); }
#define R4S "{%0,%1,%2,%3}"
#define R8S "{%0,%1,%2,%3,%4,%5,%6,%7}"
#define R16S "{%0,%1,%2,%3,%4,%5,%6,%7,%8,%9,%10,%11,%12,%13,%14,%15}"
#define R20S "{%0,%1,%2,%3,%4,%5,%6,%7,%8,%9,%10,%11,%12,%13,%14,%15,%16,%17,%18,%19}"
#define R24S "{%0,%1,%2,%3,%4,%5,%6,%7,%8,%9,%10,%11,%12,%13,%14,%15,%16,%17,%18,%19,%20,%21,%22,%23}"
#define ACC32(d) ACC16(d), ACC16((d + 16))
#define R32S "{%0,%1,%2,%3,%4,%5,%6,%7,%8,%9,%10,%11,%12,%13,%14,%15,%16,%17,%18,%19,%20,%21,%22,%23,%24,%25,%26,%27,%28,%29,%30,%31}"
struct Dsc {
  uint64_t b; uint32_t e;
  __device__ __forceinline__ Dsc operator+(uint32_t o) const { return {b + o, e}; }
};
template <int K> __device__ __forceinline__ uint32_t fresh(int i) {
  uint32_t e; asm volatile("{\n.reg .u32 t;\nadd.u32 t, %1, %2;\nshr.u32 %0, t, %3;\n}" : "=r"(e) : "r"(i), "n"((256 << K) + 1), "n"(8 + K)); return e; }
template <int N, bool H = false> struct MM;
#define DEF_MM(N, H, T, ACCM, RS_, I0, I1, I2, I3, I4, I5, I6, I7)                                                                \
  template <> struct MM<N, H> {                                                                                                   \
    template <uint32_t BLO, int ACC>                                                                                              \
    static __device__ __forceinline__ void rs(float* d, const uint32_t* a, Dsc b0) {                                              \
      asm volatile("{\n.reg .b64 b;\nmad.wide.u32 b, %" #I7 ", %" #I5 ", %" #I4 ";\n"                                             \
                   "wgmma.mma_async.sync.aligned.m64n" #N "k16.f32." T "." T " " RS_ ", {%" #I0 ",%" #I1 ",%" #I2 ",%" #I3 "}, b, %" #I6 ", 1, 1, 0;\n}" \
                   : ACCM(d) : "r"(a[0]), "r"(a[1]), "r"(a[2]), "r"(a[3]), "l"(b0.b), "n"(BLO), "n"(ACC), "r"(b0.e)); }           \
    template <uint32_t ALO, uint32_t BLO, int ACC, int TA = 1>                                                                    \
    static __device__ __forceinline__ void ss(float* d, Dsc a0, Dsc b0) {                                                         \
      asm volatile("{\n.reg .b64 a, b;\nmad.wide.u32 a, %" #I6 ", %" #I1 ", %" #I0 ";\nmad.wide.u32 b, %" #I6 ", %" #I3 ", %" #I2 ";\n" \
                   "wgmma.mma_async.sync.aligned.m64n" #N "k16.f32." T "." T " " RS_ ", a, b, %" #I4 ", 1, 1, %" #I5 ", 0;\n}"    \
                   : ACCM(d) : "l"(a0.b), "n"(ALO), "l"(b0.b), "n"(BLO), "n"(ACC), "n"(TA), "r"(b0.e)); }                         \
  };
DEF_MM(8, false, "bf16", ACC4, R4S, 4, 5, 6, 7, 8, 9, 10, 11)
DEF_MM(16, false, "bf16", ACC8, R8S, 8, 9, 10, 11, 12, 13, 14, 15)
DEF_MM(32, false, "bf16", ACC16, R16S, 16, 17, 18, 19, 20, 21, 22, 23)
DEF_MM(40, false, "bf16", ACC20, R20S, 20, 21, 22, 23, 24, 25, 26, 27)
DEF_MM(48, false, "bf16", ACC24, R24S, 24, 25, 26, 27, 28, 29, 30, 31)
DEF_MM(64, false, "bf16", ACC32, R32S, 32, 33, 34, 35, 36, 37, 38, 39)
DEF_MM(32, true, "f16", ACC16, R16S, 16, 17, 18, 19, 20, 21, 22, 23)
DEF_MM(64, true, "f16", ACC32, R32S, 32, 33, 34, 35, 36, 37, 38, 39)

#define LAG 10
#define NSTEP (NSEG + LAG)
#define NR (NSTEP + 1)
__device__ __align__(1024) __nv_bfloat16 g_xn[2][S_LEN * DM];
#define RO 16
static_assert(RO > LAG + 1, "ring");
__device__ __align__(1024) unsigned char g_o[RO * 96 * 8192];
__device__ __align__(1024) uint32_t g_part[6][7][40][64];
#define RD 16
static_assert(2 * RD <= NSEG && NR < 96, "the tags of the last lap differ from those of the first");
#define TILE_B 81920
__device__ __align__(1024) float2 g_stat[S_LEN];
__device__ __align__(1024) uint32_t g_st2[2][RD][64];
__device__ __align__(1024) unsigned char g_acc[4][RD][TILE_B];
#define NOP 19
#define NW12 5
#define NW34 12
#define NBC (NOP + NW12 + NW34)
__device__ __align__(1024) unsigned char g_wt[NOP * 10 * 12288];
enum { F_O = 0, F_R1 = NOP + 1, F_R2 = F_R1 + 4, F_R3 = F_R2 + 4, F_Z = F_R3 + 4, F_DONE, F_GOT, F_MISC, F_NUM };
__device__ __align__(128) uint32_t g_f[F_NUM][96];
__device__ __align__(128) int g_xready[129][8];
__device__ uint32_t g_tpc[128];
#define TS(i)
#define TSV(i, v)
#define TSN(i)
#define TSD(i, dep)
#define BTS(k, i)
#define BTS2(k, i)
#define RTS(i)
#define RTSD(i, dep)
#define RTS_OUT()
#define CTS(i)
#define PTS(i)
#define PTS1(i)
#define CTS_OUT()
#define GTS(i)

#define CL_SIZE 15
#define NCL 7
#define SSQ 13
#define SSV 16
#define PL_SZ 5376
#define TILE_SBO 2560
#define TILE_GRP 15360
#define WS_SZ ((2 * SSQ + SSV) * 2048)
#define OFF_QK (OFF_WO + 26 * 2048)
#define LAYOUT 2
#define OFF_TILE 0
#define OFF_WS (4 * TILE_GRP)
#define OFF_WO (OFF_WS + WS_SZ)
#define OFF_PL (OFF_QK + 20480)
#define OFF_BAR (OFF_PL + 2 * PL_SZ)
#define STG_Q OFF_TILE
#define STG_K OFF_WO
#define VA 14
#define STG_V2 (OFF_TILE + 27 * 2048)
#define OFF_O (OFF_PL + 4352)
#define LAND(k) (((k) >> 1) * TILE_GRP + ((k) & 1) * 1280)
#define LAND_F (5 * TILE_SBO)
#define OFF_XL (OFF_TILE + 3 * TILE_GRP)
#define OFF_XF (OFF_XL + LAND_F)
#define OFF_WT ((OFF_XL + TILE_SBO + 1023) & ~1023)
#define OFF_TAB (OFF_BAR + 240)
#define OFF_INV (OFF_TAB + 64)
#define OFF_TS (OFF_INV + 128)
#define A_SMEM 232448
static_assert(WS_SZ + 72 * 1024 + 2 * PL_SZ + 4 * TILE_GRP + 512 == A_SMEM && OFF_WS % 1024 == 0 && OFF_WO % 1024 == 0 && SSQ == 13, "smem map");
enum { B_W0 = 0, B_W1, B_F1, B_F2 = B_F1 + 4, B_R1 = B_F2 + 4, B_R2, B_MEMFREE, B_LANDFREE, B_OPEER, B_PLFREE, B_XFREE, B_SB, B_WOF = B_SB + 6, B_WTF, B_RS, B_NUM = B_RS + 4 };
static_assert(B_NUM <= 30, "barriers");
enum { N_C = 0, N_SISS, N_QK, N_V, N_PM, N_TURN, N_PI, N_VGO, N_O, N_PX, N_AB, N_SDONE, N_VDONE, N_G3, N_P, N_OX };

__device__ __forceinline__ bool is_dual(int j) { return j >= LAG && j < NSEG; }
__device__ __forceinline__ int sched_l(int j) { return j < NSEG ? j : NSEG + j - LAG; }
__device__ __forceinline__ int sched_f(int j) { return NSEG + j - LAG; }
__device__ __forceinline__ void wait_cnt(const int* p, int target) {
  int v, n = 0;
  do {
    asm volatile("ld.relaxed.gpu.global.b32 %0, [%1];" : "=r"(v) : "l"(p) : "memory");
    if (v >= target) break;
    if (++n > SPIN_LIMIT) FAIL();
  } while (true);
  asm volatile("fence.acquire.gpu;" ::: "memory");
  asm volatile("fence.proxy.async.global;" ::: "memory");
}
__device__ __forceinline__ void red_release(void* p, uint32_t v) { asm volatile("red.release.gpu.global.add.u32 [%0], %1;" :: "l"(p), "r"(v) : "memory"); }
__device__ __forceinline__ void red_relaxed(void* p, uint32_t v) { asm volatile("red.relaxed.gpu.global.add.u32 [%0], %1;" :: "l"(p), "r"(v) : "memory"); }
#define VMASK 0xa5294a5294ull
__host__ __device__ constexpr int popc40(unsigned long long m) { int c = 0; for (; m; m &= m - 1) c++; return c; }
static_assert(popc40(VMASK) == SSV, "mask");
__host__ __device__ constexpr int ss_idx(int ks, int n) { return n == SSV ? popc40(VMASK & ((1ull << ks) - 1)) : ks * n / 40; }
__host__ __device__ constexpr bool is_ss(int ks, int n) { return ss_idx(ks + 1, n) != ss_idx(ks, n); }
__host__ __device__ constexpr int rs_idx(int ks, int n) { return ks - ss_idx(ks, n); }

#define SL2 (0.07216878364870322f * 1.4426950408889634f)

#define SUM_LOOP 0
struct Desc { Dsc tile, unit, k1, pl, p; };
__device__ __forceinline__ Desc make_desc(const uint64_t* h, uint32_t u, uint32_t e) {
  return {{h[0], e}, {h[1] + u * 128, e}, {h[2], e}, {h[3], e}, {h[4], e}};
}
template <int N, int NSS, int RG, int KS, int K1, int K0 = 0>
__device__ __forceinline__ void proj(float* acc, const uint32_t* W, const Desc& D) {
  if constexpr (KS < K1) {
    constexpr uint32_t BLO = dlo(OFF_TILE + (KS / 10) * TILE_GRP + RG * TILE_SBO + (KS % 10) * 256, 128);
    if constexpr (is_ss(KS, NSS)) MM<N>::template ss<dlo(OFF_WS + ss_idx(KS, NSS) * 2048, 0), BLO, (KS != K0)>(acc, D.unit, D.tile);
    else MM<N>::template rs<BLO, (KS != K0)>(acc, W + rs_idx(KS, NSS) * 4, D.tile);
    proj<N, NSS, RG, KS + 1, K1, K0>(acc, W, D);
  }
}
#define VST 17
template <int KS>
__device__ __forceinline__ void ld_rest(uint32_t* W, const uint32_t* p) {
  if constexpr (KS < 40) {
    if constexpr (!is_ss(KS, SSV) && rs_idx(KS, SSV) >= VST) {
#pragma unroll
      for (int i = 0; i < 4; i++) W[4 * rs_idx(KS, SSV) + i] = __ldg(p + (KS * 16 + (i >> 1) * 8) * (HD / 2) + (i & 1) * 4);
    }
    ld_rest<KS + 1>(W, p);
  }
}
template <int N>
__device__ __forceinline__ void load_w(uint32_t* W, uint32_t stage, int warp, int lane) {
  const int kr = (lane >> 4) * 8 + (lane & 7);
  const int cb = warp * 2 + ((lane >> 3) & 1);
  const uint32_t a0 = stage + kr * 128 + ((cb ^ (lane & 7)) << 4);
#pragma unroll
  for (int i = 0; i < N; i++) ldsm4t(W[4 * i], W[4 * i + 1], W[4 * i + 2], W[4 * i + 3], a0 + i * 2048);
}
template <int N, int G, int U, int OS, int ACC>
__device__ __forceinline__ void wo4(float* d, const Desc& D) {
  constexpr uint32_t WA = (U >= 4 ? OFF_WO + (U - 4) * 2048 : OFF_WT) - G * SSQ * 2048, OB = OS == 0 ? OFF_O : OS == 1 ? OFF_XL : OFF_XF;
  Dsc b = OS ? D.k1 : D.pl;
  b.e = fresh<(U < 16 ? U / 4 : U / 8 - 2) + (N == 8 ? 4 : 0)>(D.unit.e);
  MM<N>::template ss<dlo(WA, 0), dlo(OB, 128), ACC>(d, D.unit, b);
  MM<N>::template ss<dlo(WA + 2048, 0), dlo(OB + 256, 128), 1>(d, D.unit, b);
  MM<N>::template ss<dlo(WA + 4096, 0), dlo(OB + 512, 128), 1>(d, D.unit, b);
  MM<N>::template ss<dlo(WA + 6144, 0), dlo(OB + 768, 128), 1>(d, D.unit, b);
}
__device__ __forceinline__ void wo_coord(int i, int t3, int head, int& c0, int& c1) {
  const int g = i >> 1;
  const int blk = g == 0 ? 9 : (g < 4 ? g - 1 : (g - 4) >> 1) * 3 + t3;
  int sl = g < 4 ? t3 : (g & 1) ? t3 + 1 : t3 + 2;
  if (sl >= 3) sl -= 3;
  c0 = blk * 64; c1 = head * DH + sl * 64 + (i & 1) * 32;
}
__device__ __forceinline__ void tok_softmax(uint32_t sb, int job, int lane) {
  const bool w1 = job & 1;
  const int dg = (lane >> 2) - (lane & 3) * 2;
  const uint32_t lo = sb + OFF_PL + (job >> 1) * PL_SZ + (job & 1) * 1792, l8 = lo + 512 + lane * 8, pa = lo + lane * 4;
  const uint32_t km = job & 2 ? 640 : 512;
  float x[14];
  {
    const uint4 a = lds128(lo + lane * 16);
    const uint2 e = lds64(l8);
    const uint32_t c = lds32(768 + pa);
    x[0] = bf_lo(a.x); x[1] = bf_hi(a.x); x[2] = bf_lo(a.y); x[3] = bf_hi(a.y); x[4] = bf_lo(a.z); x[5] = bf_hi(a.z); x[6] = bf_lo(a.w); x[7] = bf_hi(a.w);
    x[8] = bf_lo(c); x[9] = bf_hi(c); x[10] = bf_lo(e.x); x[11] = bf_hi(e.x); x[12] = bf_lo(e.y); x[13] = bf_hi(e.y);
  }
  if (dg < 0) { x[8] = -INFINITY; if (w1) x[4] = -INFINITY; else x[10] = -INFINITY; }
  if (dg < 1) { x[9] = -INFINITY; if (w1) x[5] = -INFINITY; else x[11] = -INFINITY; }
  const float m4 = fmaxf(x[8], x[9]);
  float m0 = fmaxf(fmaxf(fmaxf(x[0], x[1]), fmaxf(x[2], x[3])), fmaxf(fmaxf(x[4], x[5]), fmaxf(x[6], x[7])));
  float m1 = fmaxf(fmaxf(x[10], x[11]), fmaxf(x[12], x[13]));
  if (w1) m1 = fmaxf(m1, m4); else m0 = fmaxf(m0, m4);
  m0 = fmaxf(m0, __shfl_xor_sync(~0u, m0, 1)); m1 = fmaxf(m1, __shfl_xor_sync(~0u, m1, 1));
  sts32(pa + (w1 ? 384 : 896 + 128), 0u); sts32(pa + 1152 - km, 0u); sts32(pa + 896 + 1152 - km, 0u); sts64(l8 + 896 - 256, 0u, 0u);
  m0 = fmaxf(m0, __shfl_xor_sync(~0u, m0, 2)); m1 = fmaxf(m1, __shfl_xor_sync(~0u, m1, 2));
  m0 *= -SL2; m1 *= -SL2;
#pragma unroll
  for (int j = 0; j < 14; j++) x[j] = ex2(fmaf(x[j], SL2, j < 8 ? m0 : j >= 10 ? m1 : w1 ? m1 : m0));
  const float l4s = x[8] + x[9];
  float l0 = ((x[0] + x[1]) + (x[2] + x[3])) + ((x[4] + x[5]) + (x[6] + x[7])), l1 = (x[10] + x[11]) + (x[12] + x[13]);
  if (w1) l1 += l4s; else l0 += l4s;
  l0 += __shfl_xor_sync(~0u, l0, 1); l1 += __shfl_xor_sync(~0u, l1, 1);
  l0 += __shfl_xor_sync(~0u, l0, 2); l1 += __shfl_xor_sync(~0u, l1, 2);
  l0 = rcpf(l0); l1 = rcpf(l1);
#pragma unroll
  for (int j = 0; j < 7; j++) {
    const float iv = j < 4 ? l0 : j > 4 ? l1 : w1 ? l1 : l0;
    sts32(pa + (j < 3 ? j * 128 : j == 3 ? km : j == 4 ? (w1 ? 896 + 128 : 384) : j == 5 ? 896 : 896 + km), pack2(x[2 * j] * iv, x[2 * j + 1] * iv));
  }
}
template <int N>
__device__ __forceinline__ void wo_phase(uint32_t sb, int wg, int warp, int lane, uint32_t par, uint32_t r1, const Desc& D) {
  const uint32_t bar = sb + OFF_BAR;
  float x[N / 2], y[N / 2];
  const uint2 ta = lds64(sb + OFF_TAB + (wg * 4 + warp) * 8);
  uint32_t xa = (ta.x & ~255u) + lane * 8, xb = (ta.x & 0xFF0000FFu) + SMEM0 + OFF_BAR, ya = (ta.y & ~255u) + lane * 8, yb = (ta.y & 0xFF0000FFu) + SMEM0 + OFF_BAR;
  asm volatile("" : "+r"(xa), "+r"(xb), "+r"(ya), "+r"(yb));
  auto scat = [&](uint32_t ad, uint32_t mb, const float* d) {
    st_async_v2(ad, pack2(d[0], d[1]), pack2(d[2], d[3]), mb);
    if (N == 16) st_async_v2(ad + LAND_F, pack2(d[4], d[5]), pack2(d[6], d[7]), mb);
  };
  if (wg == 0) {
    bar_sync(N_O, 384);
    wg_fence(); wo4<N, 0, 4, 0, 0>(x, D); wo4<N, 0, 8, 0, 0>(y, D); wg_commit();
    mbar_waitu(bar + 8 * B_OPEER, par);
    CFENCE(); wg_fence(); wo4<N, 0, 16, 1, 1>(x, D); wo4<N, 0, 20, 2, 1>(x, D); wg_commit();
    wo4<N, 0, 24, 1, 1>(y, D); wg_commit();
    mbar_waitu2(bar + 8 * B_WOF, bar + 8 * B_MEMFREE, par);
    wg_fence(); wo4<N, 0, 28, 2, 1>(y, D); wg_commit();
    bar_arrive(N_AB, 256);
    wg_wait<2>(); scat(xa, xb, x);
    wg_wait<0>(); scat(ya, yb, y);
  } else {
    bar_sync(N_O, 384);
    wg_fence(); wo4<N, 1, 0, 0, 0>(x, D); wg_commit(); wo4<N, 1, 12, 0, 0>(y, D); wg_commit();
    wg_wait<1>(); mbar_arrive_remote_if(lane == 0, r1);
    mbar_waitu(bar + 8 * B_MEMFREE, par);
    scat(xa, xb, x);
    bar_sync(N_AB, 256);
    CFENCE(); wg_fence(); wo4<N, 1, 32, 1, 1>(y, D); wo4<N, 1, 36, 2, 1>(y, D); wg_commit();
    bar_arrive(N_TURN, 256);
    wg_wait<0>(); scat(ya, yb, y);
  }
}
#define DS_DUAL 10
#define DS_SINGLE 20
#define POLL_GAP 100
#define POLL_GAPD 0
#define TOK_DELAY 250
#define LATE_SM 1
#define UMAX 40
#define VD1 10
#define VS2 20
#define IG_V 3
#define VS1 4
struct AMaps { CUtensorMap w16[3], wo32; uint64_t d[5]; const __nv_bfloat16* wv; };
__global__ void __launch_bounds__(512, 1)
acore_kernel(const __grid_constant__ AMaps M, const __nv_bfloat16* __restrict__ mem0, int sync_b) {
  extern __shared__ __align__(1024) unsigned char smem_raw[];
  const uint32_t sb = smem_u32(smem_raw);
  GTS(24);
  if (threadIdx.x == 480) {
    uint32_t smid; asm volatile("mov.u32 %0, %%smid;" : "=r"(smid));
    g_tpc[(smid >> 1) & 127] = blockIdx.x - CL_SIZE < 3 * CL_SIZE && blockIdx.x % CL_SIZE >= 12 ? 1 : 2;
    asm volatile("griddepcontrol.launch_dependents;");
  }
  const int lane0 = threadIdx.x & 31;
#define LANE_INIT() int lane; asm volatile("mov.u32 %0, %%laneid;" : "=r"(lane))
  const int warp = __shfl_sync(~0u, (threadIdx.x >> 5) & 3, 0);
  const int cl = blockIdx.x / CL_SIZE;
  const uint32_t rank = blockIdx.x - cl * CL_SIZE;
  const int nh = cl >= 1 && cl <= 3 ? 4 : 5;
  const int nA = 3 * nh;
  const int wg = __shfl_sync(~0u, (int)rank < nA ? threadIdx.x >> 7 : 4, 0);
  const int head = (cl < 4 ? (cl ? 1 + 4 * cl : 0) : 5 * cl - 3) + rank / 3;
  const int t3 = rank % 3;
  const int col0 = head * DH + t3 * 64;
  const uint32_t bar = sb + OFF_BAR;
  const uint32_t rb0 = SMEM0;
  const uint16_t mcmask = (uint16_t)((1u << nA) - 1);
  const uint32_t nxt = sb + ((t3 == 2 ? -2 : 1) << 24), prv = sb + ((t3 == 0 ? 2 : -1) << 24);
  const int ig = (int)rank - (nA - 4);

  if (threadIdx.x == 0) {
    if (mapa(sb, nA - 1) != rb0 + ((nA - 1) << 24) || mapa(sb, 0) != rb0 || mapa(sb, 1) != rb0 + (1u << 24) || sb != SMEM0 + (rank << 24)) FAIL();
    for (int i = 0; i < B_NUM; i++)
      mbar_init(bar + 8 * i, i == B_R1 ? 4 * nA : i == B_R2 ? 12 * nA : i == B_MEMFREE ? nA : i == B_LANDFREE ? 4 * nA : i == B_PLFREE || i == B_XFREE ? 2 : 1);
    asm volatile("fence.mbarrier_init.release.cluster;" ::: "memory");
    mbar_expect(bar + 8 * B_W0, (80 + SSV + VST) * 2048);
  }
  __syncthreads();
  if (lane0 == 0) {
    const int w12 = wg * 4 + warp;
    if (w12 < 10) {
#pragma unroll 1
      for (int ks = 4 * w12; ks < 4 * w12 + 4; ks++) {
        const bool ss = is_ss(ks, SSQ);
        tma2d(ss ? sb + OFF_WS + ss_idx(ks, SSQ) * 2048 : sb + STG_Q + rs_idx(ks, SSQ) * 2048, &M.w16[0], col0, ks * 16, bar + 8 * B_W0);
        tma2d(ss ? sb + OFF_WS + (SSQ + ss_idx(ks, SSQ)) * 2048 : sb + STG_K + rs_idx(ks, SSQ) * 2048, &M.w16[1], col0, ks * 16, bar + 8 * B_W0);
        if (is_ss(ks, SSV)) tma2d(sb + OFF_WS + (2 * SSQ + ss_idx(ks, SSV)) * 2048, &M.w16[2], col0, ks * 16, bar + 8 * B_W0);
        else if (rs_idx(ks, SSV) < VST) tma2d(sb + (rs_idx(ks, SSV) < VA ? STG_K + 27 * 2048 : STG_V2 - VA * 2048) + rs_idx(ks, SSV) * 2048, &M.w16[2], col0, ks * 16, bar + 8 * B_W0);
      }
    }
  }
  if (lane0 < 2 && wg < 2) {
    const int u = 4 * (wg ? (lane0 ? 6 + t3 : 9) : (lane0 ? 3 + t3 : t3)) + warp;
    const int li = (u >= nA) + (u >= 2 * nA) + (u >= 3 * nA);
    sts32(sb + OFF_TAB + (wg * 4 + warp) * 8 + lane0 * 4,
          rb0 + ((u - li * nA) << 24) + OFF_TILE + LAND(li + (u >= 36 ? t3 : 0)) + (rank / 3) * 256 + 8 * (B_RS + li));
  }
  __syncthreads();
  GTS(25);

  auto issue_tok = [&](int sc, int fb, int rel = -1, uint32_t ph = 0) {
    if (sync_b) wait_cnt(&g_xready[sc][0], 32);
    if (rel >= 0) mbar_waitu(bar + 8 * rel, ph);
    bulk_g2s_mc_e(sb + OFF_TILE + ig * TILE_GRP + TILE_SBO, &g_xn[0][0] + uni(sc * (32 * DM)) + ig * 5120, 10240, bar + 8 * (fb + ig), mcmask);
  };
#define POLL(d, q) _Pragma("unroll") for (int k = 0; k < NCL; k++) \
      asm volatile("ld.relaxed.gpu.global.v2.b32 {%0,%1}, [%2];" : "=r"(d[k].x), "=r"(d[k].y) : "l"(q + k * 2560) : "memory")
#define L3(L, a, b, c) lop3<L>(a, b, c)
#define TAGS(L, d) L3(L, L3(L, L3(L, d[0].x, d[0].y, d[1].x), L3(L, d[1].y, d[2].x, d[2].y), L3(L, d[3].x, d[3].y, d[4].x)), L3(L, d[4].y, d[5].x, d[5].y), L3(L, d[6].x, d[6].y, d[6].y))
    auto deliver = [&](uint2* pa, const uint32_t* gq, int u, int c, int dc, int ds, int step, bool first, int lane) {
      const uint32_t off = uni(OFF_TILE + ((u * 205) >> 11) * (TILE_GRP - TILE_SBO) + u * 256 + dc * LAND_F), boff = uni(OFF_BAR + 8 * (B_F1 + ((u * 205) >> 11)));
      const uint32_t* mi = &g_part[4][0][0][0] + uni((c * NCL + cl) * 2560 + u * 64);
      mbar_waitu(bar + 8 * B_LANDFREE, step & 1);
      int n = 0;
      while (true) {
        const bool ok = __all_sync(~0u, ((step & 2 ? ~TAGS(0xFE, pa) : TAGS(0x80, pa)) & 1) != 0);
        if (ok) break;
        if (++n > SPIN_LIMIT) FAIL();
        POLL(pa, gq);
      }
      if (warp == 0 && first) { TS(19); TSV(10, n); }
      const uint32_t w0 = hadd2bf(hadd2bf(hadd2bf(pa[0].x, pa[1].x), hadd2bf(pa[2].x, pa[3].x)), hadd2bf(hadd2bf(pa[4].x, pa[5].x), pa[6].x));
      const uint32_t w1 = hadd2bf(hadd2bf(hadd2bf(pa[0].y, pa[1].y), hadd2bf(pa[2].y, pa[3].y)), hadd2bf(hadd2bf(pa[4].y, pa[5].y), pa[6].y));
      if (u < ds) {
        const uint32_t da = SMEM0 + off + lane * 8, db = SMEM0 + boff;
#pragma unroll
        for (int d = 0; d < 12; d++) st_async_v2((d << 24) + da, w0, w1, (d << 24) + db);
#pragma unroll
        for (int d = 12; d < 15; d++) st_async_v2_if(nA == 15, (d << 24) + da, w0, w1, (d << 24) + db);
      } else {
        *reinterpret_cast<uint2*>(const_cast<uint32_t*>(gq) + ((4 - 2 * (step & 1)) * NCL + cl) * 2560) = make_uint2(w0, w1);
        asm volatile("fence.proxy.async.global;" ::: "memory");
        __syncwarp();
        bulk_g2s_mc_e(sb + off, mi, 256, sb + boff, mcmask);
      }
    };
#define REL(b, g) mbar_arrive_remote_if(lane == 0, rb0 + ((nA - 4 + (g)) << 24) + OFF_BAR + 8 * (b))

  if (wg < 2) {
    asm volatile("setmaxnreg.inc.sync.aligned.u32 160;");
    LANE_INIT();
    uint32_t W[4 * (40 - SSQ)];
    mbar_waitw(bar + 8 * B_W0, 0);
    GTS(26);
    load_w<40 - SSQ>(W, sb + (wg ? STG_K : STG_Q), warp, lane);
    fence_async();
    bar_sync(1, 384);
    cluster_sync_all();
#define DESC(k) const Desc D = make_desc(M.d, min(wg, 2) * SSQ, fresh<k>(step))
    GTS(27);
#pragma unroll 1
    for (int step = -1; step < NSTEP; step++) {
      const uint32_t par = step & 1;
      asm volatile("" : "+r"(lane));
      const bool dual = is_dual(step), has_next = step + 1 < NSTEP;
#define QK_SA (sb + OFF_QK + wg * 15360 + (2 * warp + ((lane >> 3) & 1)) * 128 + (lane & 7) * 16)
#define QK_F (wg ? -5120 : 5120)
#define QK_S12 ((wg ? (lane >> 4) : 1 + 2 * (lane >> 4)) * 1024)
#define QK_S34 ((wg ? 2 + (lane >> 4) : 2 - 2 * (lane >> 4)) * 1024)
      if (step >= 0) {
        if (dual) {
          DESC(0);
          float acc[24];
          mbar_waitu(bar + 8 * (B_F1 + 0), par);
          if (wg + warp == 0) { TS(0); TSN(1); }
          CFENCE(); wg_fence(); proj<48, SSQ, 0, 0, 10>(acc, W, D); wg_commit();
          mbar_waitu(bar + 8 * (B_F1 + 1), par);
          CFENCE(); wg_fence(); proj<48, SSQ, 0, 10, 20>(acc, W, D); wg_commit();
          mbar_waitu(bar + 8 * (B_F1 + 2), par);
          CFENCE(); wg_fence(); proj<48, SSQ, 0, 20, 30>(acc, W, D); wg_commit();
          mbar_waitu(bar + 8 * (B_F1 + 3), par);
          if (wg + warp == 0) TS(2);
          CFENCE(); wg_fence(); proj<48, SSQ, 0, 30, 40>(acc, W, D); wg_commit();
          bar_arrive(N_VGO, 384);
          mbar_waitu(bar + 8 * B_PLFREE, par);
          const uint32_t sa = QK_SA, s0 = sa + 4096 + (lane >> 4) * QK_F, s1 = sa + QK_F + QK_S12, s2 = sa + QK_F + QK_S34;
          wg_wait<0>();
          if (wg + warp == 0) TS(3);
          stsm4t(s0, pack2(acc[0], acc[1]), pack2(acc[2], acc[3]), pack2(acc[20], acc[21]), pack2(acc[22], acc[23]));
          stsm4t(s1, pack2(acc[4], acc[5]), pack2(acc[6], acc[7]), pack2(acc[8], acc[9]), pack2(acc[10], acc[11]));
          stsm4t(s2, pack2(acc[12], acc[13]), pack2(acc[14], acc[15]), pack2(acc[16], acc[17]), pack2(acc[18], acc[19]));
        } else {
          DESC(1);
          float acc[4];
          mbar_waitu(bar + 8 * (B_F1 + 0), par);
          if (wg + warp == 0) { TS(0); TSN(1); }
          CFENCE(); wg_fence(); proj<8, SSQ, 0, 0, 10>(acc, W, D); wg_commit();
          mbar_waitu(bar + 8 * (B_F1 + 1), par);
          CFENCE(); wg_fence(); proj<8, SSQ, 0, 10, 20>(acc, W, D); wg_commit();
          mbar_waitu(bar + 8 * (B_F1 + 2), par);
          CFENCE(); wg_fence(); proj<8, SSQ, 0, 20, 30>(acc, W, D); wg_commit();
          mbar_waitu(bar + 8 * (B_F1 + 3), par);
          if (wg + warp == 0) TS(2);
          CFENCE(); wg_fence(); proj<8, SSQ, 0, 30, 40>(acc, W, D); wg_commit();
          bar_arrive(N_VGO, 384);
          mbar_waitu(bar + 8 * B_PLFREE, par);
          const uint32_t s0 = QK_SA + 4096;
          wg_wait<0>();
          if (wg + warp == 0) TS(3);
          stsm2t(s0, pack2(acc[0], acc[1]), pack2(acc[2], acc[3]));
        }
        fence_async();
        bar_sync(N_QK, 256);
        if (wg == 0 || dual) {
          float s[20];
          DESC(2);
          const Dsc ab = D.k1 + wg * 192, bb = D.k1 + (1 - wg) * 320;
          wg_fence();
          MM<40>::ss<dlo(OFF_QK, 128), dlo(OFF_QK + 10240, 128), 0, 0>(s, ab, bb);
          MM<40>::ss<dlo(OFF_QK + 256, 128), dlo(OFF_QK + 10240 + 256, 128), 1, 0>(s, ab, bb);
          MM<40>::ss<dlo(OFF_QK + 512, 128), dlo(OFF_QK + 10240 + 512, 128), 1, 0>(s, ab, bb);
          MM<40>::ss<dlo(OFF_QK + 768, 128), dlo(OFF_QK + 10240 + 768, 128), 1, 0>(s, ab, bb);
          wg_commit();
          bar_arrive(N_SISS, 384);
          const int rw = (warp - wg) & 3;
          const uint32_t bo = OFF_BAR + 8 * (B_SB + 3 * wg + rw), lo = OFF_PL + wg * PL_SZ + rw * 1792;
          const uint32_t km = wg ? 640 : 512;
          uint32_t l16 = lo + lane * 16, l4 = lo + lane * 4;
          mbar_expect_if(lane == 0 && rw < 3, sb + bo, rw < 2 ? 1792 : 1280);
          asm volatile("" : "+r"(l16), "+r"(l4));
          if (rw == 2) {
            wg_wait<0>();
            if (wg == 0) TSD(4, __float_as_uint(s[0]));
            const uint32_t w0 = pack2(s[0], s[1]), w1 = pack2(s[4], s[5]), w2 = pack2(s[8], s[9]), w3 = pack2(s[12], s[13]), w4 = pack2(s[16], s[17]);
            {
              st_async_v4(nxt + 896 + l16, w0, w1, w2, w3, nxt + bo);
              st_async_v4(prv + l16, w0, w1, w2, w3, prv + bo);
              st_async_b32(nxt + 896 + 768 + l4, w4, nxt + bo);
              st_async_b32(prv + 768 + l4, w4, prv + bo);
            }
            bar_arrive(N_SDONE, 256);
            mbar_waitu(sb + bo, (step - wg * LAG) & 1);
            if (wg == 0) TS(5);
            float x[10], m0;
            {
              const uint4 a = lds128(sb + l16), b = lds128(sb + 896 + l16);
              const uint32_t c = lds32(sb + 768 + l4), d = lds32(sb + 896 + 768 + l4);
              const uint32_t e0 = hadd2bf(hadd2bf(a.x, b.x), w0), e1 = hadd2bf(hadd2bf(a.y, b.y), w1), e2 = hadd2bf(hadd2bf(a.z, b.z), w2),
                             e3 = hadd2bf(hadd2bf(a.w, b.w), w3), e4 = hadd2bf(hadd2bf(c, d), w4);
              const uint32_t em = hmax2bf(hmax2bf(hmax2bf(e0, e1), hmax2bf(e2, e3)), e4);
              m0 = fmaxf(bf_lo(em), bf_hi(em));
              x[0] = bf_lo(e0); x[1] = bf_hi(e0); x[2] = bf_lo(e1); x[3] = bf_hi(e1); x[4] = bf_lo(e2);
              x[5] = bf_hi(e2); x[6] = bf_lo(e3); x[7] = bf_hi(e3); x[8] = bf_lo(e4); x[9] = bf_hi(e4);
            }
            m0 = fmaxf(m0, __shfl_xor_sync(~0u, m0, 1));
            sts32(sb + l4 + 1152 - km, 0u);
            m0 = fmaxf(m0, __shfl_xor_sync(~0u, m0, 2));
            m0 *= -SL2;
#pragma unroll
            for (int j = 0; j < 5; j++) {
              x[2 * j] = ex2(fmaf(x[2 * j], SL2, m0)); x[2 * j + 1] = ex2(fmaf(x[2 * j + 1], SL2, m0));
              sts32(sb + l4 + (j < 4 ? j * 128 : km), pack2(x[2 * j], x[2 * j + 1]));
            }
            float l = ((x[0] + x[1]) + (x[2] + x[3])) + ((x[4] + x[5]) + ((x[6] + x[7]) + (x[8] + x[9])));
            l += __shfl_xor_sync(~0u, l, 1);
            fence_async();
            sts32(sb + OFF_INV + wg * 64 + (lane >> 1) * 4, __float_as_uint(l));
            bar_arrive(N_PM, dual ? 224 : 192);
            if (wg == 0) TS(6);
          } else if (rw < 2) {
            const bool w1 = rw == 1;
            const uint32_t l8 = lo + 512 + lane * 8;
            uint32_t tw[7];
            wg_wait<0>();
            bar_arrive(N_SDONE, 256);
            tw[0] = pack2(s[0], s[1]); tw[1] = pack2(s[4], s[5]); tw[2] = pack2(s[8], s[9]); tw[3] = pack2(s[16], s[17]);
            tw[4] = w1 ? pack2(s[6], s[7]) : pack2(s[12], s[13]); tw[5] = pack2(s[2], s[3]); tw[6] = pack2(s[18], s[19]);
            { const uint32_t t0 = clock32(); while (clock32() - t0 < TOK_DELAY) {} }
            st_async_v4(nxt + 896 + l16, tw[0], tw[1], tw[2], tw[3], nxt + bo);
            st_async_v4(prv + l16, tw[0], tw[1], tw[2], tw[3], prv + bo);
            st_async_v2(nxt + 896 + l8, tw[5], tw[6], nxt + bo);
            st_async_v2(prv + l8, tw[5], tw[6], prv + bo);
            st_async_b32(nxt + 896 + 768 + l4, tw[4], nxt + bo);
            st_async_b32(prv + 768 + l4, tw[4], prv + bo);
            mbar_waitu(sb + bo, (step - wg * LAG) & 1);
            const uint4 a = lds128(sb + l16), b = lds128(sb + 896 + l16);
            const uint2 e = lds64(sb + l8), f = lds64(sb + 896 + l8);
            const uint32_t c = lds32(sb + 768 + l4), d = lds32(sb + 896 + 768 + l4);
            sts128(sb + l16, hadd2bf(hadd2bf(a.x, b.x), tw[0]), hadd2bf(hadd2bf(a.y, b.y), tw[1]), hadd2bf(hadd2bf(a.z, b.z), tw[2]), hadd2bf(hadd2bf(a.w, b.w), tw[3]));
            sts64(sb + l8, hadd2bf(hadd2bf(e.x, f.x), tw[5]), hadd2bf(hadd2bf(e.y, f.y), tw[6]));
            sts32(sb + 768 + l4, hadd2bf(hadd2bf(c, d), tw[4]));
            bar_arrive(N_PX, dual ? 256 : 192);
            if (wg + warp == 0) TS(9);
          } else {
            wg_wait<0>();
            if (wg == 0) {
              mbar_expect_if(lane < 3 && has_next, bar + 8 * (lane == 2 ? B_OPEER : B_WOF + lane), lane == 2 ? (dual ? 4096 : 2048) : lane ? 8192 : 20480);
              auto fetch = [&](int i, int n, uint32_t dst, int mb) {
                int c0, c1; wo_coord(i, t3, head, c0, c1);
                tma2d_e(dst, &M.wo32, c0, c1, bar + 8 * mb); if (n == 2) tma2d_e(dst + 4096, &M.wo32, c0, c1 + 32, bar + 8 * mb);
              };
              bar_sync(N_G3, 160);
              if (has_next) {
                fetch(0, 2, sb + OFF_WT, B_WTF);
                mbar_arrive_remote_if(lane < 2, (lane ? nxt : prv) + OFF_BAR + 8 * B_XFREE);
              }
              bar_sync(N_SDONE, 256);
              if (has_next) {
                fetch(15, 1, sb + OFF_QK, B_WOF); fetch(16, 2, sb + OFF_QK + 4096, B_WOF); fetch(18, 2, sb + OFF_QK + 12288, B_WOF);
                mbar_waitu(bar + 8 * B_XFREE, par);
              }
              bar_arrive(N_PM, dual ? 224 : 192);
              bar_sync(N_VDONE, 160);
              mbar_arrive_remote_if(lane < nA && has_next, rb0 + (lane << 24) + OFF_BAR + 8 * B_MEMFREE);
              if (has_next) mbar_waitu(bar + 8 * B_WTF, par);
            } else {
              bar_arrive(N_SDONE, 256);
              if ((unsigned)ig < IG_V) issue_tok(sched_l(step + 1), B_F2, B_R1, (step - LAG) & 1);
            }
          }
        } else {
          bar_arrive(N_SISS, 384);
          bar_arrive(N_SDONE, 256);
        }
        if (has_next) {
          if (step == 0) mbar_waitw(bar + 8 * B_W1, 0);
          const uint32_t r1 = rb0 + ((nA - 1) << 24) + OFF_BAR + 8 * B_R1;
          if (dual) { DESC(3); wo_phase<16>(sb, wg, warp, lane, par, r1, D); } else { DESC(4); wo_phase<8>(sb, wg, warp, lane, par, r1, D); }
          bar_arrive(N_C, 288);
          if (warp == 0) TS(7 + wg);
        }
      }
      if (has_next) {
        DESC(5);
        float acc[16];
        mbar_waitu(bar + 8 * B_F2, par ^ 1);
        wg_fence(); proj<32, SSQ, 1, 0, 10>(acc, W, D); wg_commit();
        mbar_waitu(bar + 8 * (B_F2 + 1), par ^ 1);
        wg_fence(); proj<32, SSQ, 1, 10, 14>(acc, W, D); wg_commit();
        wg_wait<1>(); REL(B_R2, 0);
        wg_fence(); proj<32, SSQ, 1, 14, 20>(acc, W, D); wg_commit();
        mbar_waitu(bar + 8 * (B_F2 + 2), par ^ 1);
        wg_fence(); proj<32, SSQ, 1, 20, 24>(acc, W, D); wg_commit();
        wg_wait<1>(); REL(B_R2, 1);
        wg_fence(); proj<32, SSQ, 1, 24, 30>(acc, W, D); wg_commit();
        mbar_waitu(bar + 8 * (B_F2 + 3), par ^ 1);
        wg_fence(); proj<32, SSQ, 1, 30, 34>(acc, W, D); wg_commit();
        wg_wait<1>(); REL(B_R2, 2);
        wg_fence(); proj<32, SSQ, 1, 34, 40>(acc, W, D); wg_commit();
        const uint32_t sa = QK_SA, s1 = sa + QK_S12, s2 = sa + QK_S34;
        wg_wait<0>(); REL(B_R2, 3);
        if (warp == 0) TS(11 + wg);
        stsm4t(s1, pack2(acc[0], acc[1]), pack2(acc[2], acc[3]), pack2(acc[4], acc[5]), pack2(acc[6], acc[7]));
        stsm4t(s2, pack2(acc[8], acc[9]), pack2(acc[10], acc[11]), pack2(acc[12], acc[13]), pack2(acc[14], acc[15]));
      }
    }
    GTS(28);
    cluster_sync_all();
  } else if (wg == 2) {
    asm volatile("setmaxnreg.inc.sync.aligned.u32 160;");
    LANE_INIT();
    uint32_t W[4 * (40 - SSV)];
    ld_rest<0>(W, reinterpret_cast<const uint32_t*>(M.wv + (lane >> 2) * HD + col0 + warp * 16) + (lane & 3));
    uint4 m0[5];
#pragma unroll
    for (int i = 0; i < 5; i++) {
      const int t = i * 128 + warp * 32 + lane;
      m0[i] = __ldg(reinterpret_cast<const uint4*>(mem0 + ((t >> 1) & 7) * DM + (t >> 4) * 16 + ((t ^ (t >> 3)) & 1) * 8));
    }
    mbar_waitw(bar + 8 * B_W0, 0);
    load_w<VA>(W, sb + STG_K + 27 * 2048, warp, lane);
    load_w<VST - VA>(W + 4 * VA, sb + STG_V2, warp, lane);
    fence_async();
    mbar_expect_if(warp + lane == 0, bar + 8 * B_W1, 26 * 2048);
    bar_sync(1, 384);
#pragma unroll
    for (int i = 0; i < 5; i++) {
      const int t = i * 128 + warp * 32 + lane;
      sts128(sb + OFF_TILE + (t / 160) * (TILE_GRP - TILE_SBO) + t * 16, m0[i].x, m0[i].y, m0[i].z, m0[i].w);
    }
#pragma unroll
    for (int i = 4 * VST; i < 4 * (40 - SSV); i++) W[i] = movm(W[i]);
    fence_async();
    mbar_arrive_if(lane == 0, bar + 8 * (B_F1 + warp));
    mbar_expect_if(lane == 0, bar + 8 * (B_F2 + warp), 10240);
    mbar_arrive_if(warp == 3 && lane < 2, bar + 8 * B_PLFREE);
    cluster_sync_all();
    uint32_t vl[8];
    {
      const int step = warp;
      DESC(0);
      float v[16];
      mbar_waitw4(bar + 8 * B_F2, 0);
      wg_fence(); proj<32, SSV, 1, 0, 40>(v, W, D); wg_commit();
      wg_wait<0>();
      mbar_arrive_remote_if(lane < 4, rb0 + ((nA - 4 + lane) << 24) + OFF_BAR + 8 * B_R2);
#pragma unroll
      for (int j = 0; j < 8; j++) vl[j] = pack2v(v[2 * j], v[2 * j + 1]);
      if (warp == 0 && (unsigned)ig < 3) issue_tok(1, B_F2, B_R2, 0);
    }
#pragma unroll 1
    for (int step = 0; step < NSTEP; step++) {
      const uint32_t par = step & 1;
      asm volatile("" : "+r"(lane));
      const bool dual = is_dual(step), has_next = step + 1 < NSTEP;
      mbar_expect_if(lane == 0 && has_next, bar + 8 * (B_F2 + warp), 10240);
      if (warp == 0 && ig >= IG_V && dual && sync_b) wait_cnt(&g_xready[sched_l(step + 1)][0], 32);
      bar_sync(N_VGO, 384);
      CFENCE();
#define F1_BYTES (is_dual(step + 1) ? 15360 : 2560)
#define ARM() do { \
        mbar_expect_if(lane == 0 && has_next, bar + 8 * (B_F1 + warp), F1_BYTES); \
        mbar_expect_if(lane == 0 && has_next && warp * nA + (int)rank < 40, bar + 8 * (B_RS + warp), (warp * nA + (int)rank >= 36 ? nA : nh) * (dual ? 512 : 256)); } while (0)
#define O_ADDR() uint32_t oa = sb + OFF_O + (lane >> 4) * PL_SZ + warp * 256 + (lane & 15) * 16, xo = (lane >> 4) * 1024 + warp * 256 + (lane & 15) * 16; \
        asm volatile("" : "+r"(oa), "+r"(xo))
#define O_READY(act) do { if (has_next) { const uint4 ov = lds128(oa); \
        if (act) { st_async_v4(nxt + OFF_XL + xo, ov.x, ov.y, ov.z, ov.w, nxt + OFF_BAR + 8 * B_OPEER); \
                   st_async_v4(prv + OFF_XF + xo, ov.x, ov.y, ov.z, ov.w, prv + OFF_BAR + 8 * B_OPEER); } \
        fence_async(); bar_arrive(N_O, 384); } \
        if (warp == 0) TS(15); } while (0)
#define TOK_L3(g0) if (warp == 0 && ig >= (g0) && has_next) { mbar_waitu(bar + 8 * B_R1, ig == 3 ? par : (step - LAG) & 1); asm volatile("fence.proxy.async.global;" ::: "memory"); \
        bulk_g2s_mc_e(sb + OFF_TILE + ig * TILE_GRP + TILE_SBO, &g_xn[0][0] + uni(sched_l(step + 1) * (32 * DM)) + ig * 5120, 10240, bar + 8 * (B_F2 + ig), mcmask); }
#define OX_ADDR() const bool ox = head * 3 + t3 == 95; \
        const uint32_t oxa = sb + OFF_PL + (ox ? warp * 1024 + (lane & 7) * 32 + ((((lane >> 3) ^ (lane >> 2)) & 1) << 4) : (lane & 7) * 128 + (((warp * 2 + ((lane >> 3) & 1)) ^ (lane & 7)) << 4)); \
        const uint32_t s1 = oxa + ((lane < 16 ? 3072 : 0) >> (ox ? 2 : 0)), s2 = oxa + ((lane < 16 ? 2048 : 1024) >> (ox ? 2 : 0))
      if (dual) {
        uint32_t vf[8], vm[4], vn[8];
        {
          DESC(0);
          float v[24];
          ARM();
          wg_fence(); proj<48, SSV, 0, 30, 40, 30>(v, W, D); wg_commit();
          proj<48, SSV, 0, 0, VD1 - 10, 30>(v, W, D);
          bar_sync(N_SISS, 384);
          proj<48, SSV, 0, VD1 - 10, VD1 - 7, 30>(v, W, D); wg_commit();
          wg_wait<1>(); bar_arrive(N_G3, 160);
          wg_fence(); proj<48, SSV, 0, VD1 - 7, 10, 30>(v, W, D); wg_commit();
          proj<48, SSV, 0, 10, 13, 30>(v, W, D); wg_commit();
          wg_wait<1>(); REL(B_R1, 0);
          wg_fence(); proj<48, SSV, 0, 13, 20, 30>(v, W, D); wg_commit();
          proj<48, SSV, 0, 20, 23, 30>(v, W, D); wg_commit();
          wg_wait<1>(); REL(B_R1, 1);
          wg_fence(); proj<48, SSV, 0, 23, 30, 30>(v, W, D); wg_commit();
          wg_wait<0>(); REL(B_R1, 2);
          bar_arrive(N_VDONE, 160);
          if (warp == 0) TS(14);
#pragma unroll
          for (int j = 4; j < 8; j++) vf[j] = pack2v(v[4 + 2 * j], v[5 + 2 * j]);
          keep4(vf + 4, lane);
          vm[0] = pack2v(v[0], v[1]); vm[1] = pack2v(v[2], v[3]); vm[2] = pack2v(v[20], v[21]); vm[3] = pack2v(v[22], v[23]);
          keep4(vm, lane);
#pragma unroll
          for (int j = 0; j < 4; j++) vf[j] = pack2v(v[4 + 2 * j], v[5 + 2 * j]);
          keep4(vf, lane);
        }
        {
          DESC(1);
          float o[8];
          O_ADDR();
          bar_sync(N_PM, 224);
          wg_fence();
          MM<8>::rs<dlo(OFF_PL + 3584, 128), 0>(o, vl, D.p);
          MM<8>::rs<dlo(OFF_PL + PL_SZ + 3584, 128), 0>(o + 4, vf, D.p);
          MM<8>::rs<dlo(OFF_PL + 3584 + 256, 128), 1>(o, vl + 4, D.p);
          MM<8>::rs<dlo(OFF_PL + PL_SZ + 3584 + 256, 128), 1>(o + 4, vf + 4, D.p);
          MM<8>::rs<dlo(OFF_PL + 3584 + 512, 128), 1>(o, vm, D.p);
          MM<8>::rs<dlo(OFF_PL + PL_SZ + 3584 + 512, 128), 1>(o + 4, vm, D.p);
          wg_commit();
          fence_sched(step);
          const uint4 il = lds128(sb + OFF_INV + (lane & 3) * 16), jf = lds128(sb + OFF_INV + 64 + (lane & 3) * 16);
          const float i0 = rcpf(__uint_as_float(il.x) + __uint_as_float(il.y)), i1 = rcpf(__uint_as_float(il.z) + __uint_as_float(il.w));
          const float j0 = rcpf(__uint_as_float(jf.x) + __uint_as_float(jf.y)), j1 = rcpf(__uint_as_float(jf.z) + __uint_as_float(jf.w));
          { const uint32_t k4[4] = {__float_as_uint(i0), __float_as_uint(i1), __float_as_uint(j0), __float_as_uint(j1)}; keep4(k4, lane | (oa ^ xo)); }
          wg_wait<0>();
          stsm4t(oa, pack2(o[0] * i0, o[1] * i1), pack2(o[2] * i0, o[3] * i1), pack2(o[4] * j0, o[5] * j1), pack2(o[6] * j0, o[7] * j1));
          O_READY(true);
          TOK_L3(IG_V);
        }
        {
          DESC(2);
          float v[16];
          bar_sync(N_TURN, 256);
          mbar_waitu(bar + 8 * B_F2, par ^ 1);
          wg_fence(); proj<32, SSV, 1, 0, 10>(v, W, D); wg_commit();
          mbar_waitu(bar + 8 * (B_F2 + 1), par ^ 1);
          wg_fence(); proj<32, SSV, 1, 10, 14>(v, W, D); wg_commit();
          wg_wait<1>(); REL(B_R2, 0);
          wg_fence(); proj<32, SSV, 1, 14, 20>(v, W, D); wg_commit();
          mbar_waitu(bar + 8 * (B_F2 + 2), par ^ 1);
          wg_fence(); proj<32, SSV, 1, 20, 24>(v, W, D); wg_commit();
          wg_wait<1>(); REL(B_R2, 1);
          wg_fence(); proj<32, SSV, 1, 24, 30>(v, W, D); wg_commit();
          mbar_waitu(bar + 8 * (B_F2 + 3), par ^ 1);
          wg_fence(); proj<32, SSV, 1, 30, 34>(v, W, D); wg_commit();
          wg_wait<1>(); REL(B_R2, 2);
          wg_fence(); proj<32, SSV, 1, 34, 40>(v, W, D); wg_commit();
          wg_wait<0>(); REL(B_R2, 3);
#pragma unroll
          for (int j = 0; j < 8; j++) vn[j] = pack2v(v[2 * j], v[2 * j + 1]);
          keep4(vn, lane); keep4(vn + 4, lane);
          if (warp == 0) TS(18);
        }
        DESC(3);
        uint32_t ow[16];
        bar_sync(N_P, 256);
        fence_async();
#define PV16(i, off, va) { float o[8]; wg_fence(); \
          MM<16>::rs<dlo(OFF_PL + (off), 128), 0>(o, va, D.p); \
          MM<16>::rs<dlo(OFF_PL + (off) + 256, 128), 1>(o, va + 4, D.p); \
          MM<16>::rs<dlo(OFF_PL + (off) + 512, 128), 1>(o, vm, D.p); \
          wg_commit(); wg_wait<0>(); \
          _Pragma("unroll") for (int j = 0; j < 4; j++) ow[4 * (i) + j] = pack2v(o[2 * j], o[2 * j + 1]); \
          keep4(ow + 4 * (i), lane); }
        PV16(0, 0, vl) PV16(1, 1792, vl) PV16(2, PL_SZ, vf) PV16(3, PL_SZ + 1792, vf)
        OX_ADDR();
        bar_sync(N_V, 128);
        stsm4t(s1, ow[0], ow[1], ow[2], ow[3]);
        stsm4t(s2, ow[4], ow[5], ow[6], ow[7]);
        stsm4t(s1 + PL_SZ, ow[8], ow[9], ow[10], ow[11]);
        stsm4t(s2 + PL_SZ, ow[12], ow[13], ow[14], ow[15]);
#pragma unroll
        for (int j = 0; j < 8; j++) vl[j] = vn[j];
      } else {
        uint32_t vm[4], vn[8];
        {
          DESC(4);
          float v[4];
          wg_fence(); proj<8, SSV, 0, 30, 40, 30>(v, W, D); wg_commit();
          proj<8, SSV, 0, 0, VS1, 30>(v, W, D); wg_commit();
          ARM();
          bar_sync(N_SISS, 384);
          wg_wait<1>(); bar_arrive(N_G3, 160);
          wg_fence(); proj<8, SSV, 0, VS1, 30, 30>(v, W, D); wg_commit();
          if (has_next) { mbar_waitu2(bar + 8 * B_F2, bar + 8 * (B_F2 + 1), par ^ 1); mbar_waitu(bar + 8 * (B_F2 + 2), par ^ 1); }
          wg_wait<0>();
          bar_arrive(N_VDONE, 160);
          vm[0] = pack2v(v[0], v[1]); vm[1] = pack2v(v[2], v[3]); vm[2] = pack2v(v[1], v[0]); vm[3] = pack2v(v[3], v[2]);
        }
        DESC(5);
        float v[16];
        {
          wg_fence(); proj<32, SSV, 1, 0, VS2>(v, W, D); wg_commit();
          {
            float o[4];
            O_ADDR();
            bar_sync(N_PM, 192);
            if (warp == 0) TS(14);
            wg_fence();
            MM<8>::rs<dlo(OFF_PL + 3584, 128), 0>(o, vl, D.p);
            MM<8>::rs<dlo(OFF_PL + 3584 + 256, 128), 1>(o, vl + 4, D.p);
            MM<8>::rs<dlo(OFF_PL + 3584 + 512, 128), 1>(o, vm, D.p);
            wg_commit();
            fence_sched(step);
            const uint4 il = lds128(sb + OFF_INV + (lane & 3) * 16);
            const float i0 = rcpf(__uint_as_float(il.x) + __uint_as_float(il.y)), i1 = rcpf(__uint_as_float(il.z) + __uint_as_float(il.w));
            { const uint32_t k4[4] = {__float_as_uint(i0), __float_as_uint(i1), oa, xo}; keep4(k4, lane); }
            wg_wait<0>();
            stsm2t(oa, pack2(o[0] * i0, o[1] * i1), pack2(o[2] * i0, o[3] * i1));
            O_READY(lane < 16);
            TOK_L3(3);
          }
          if (has_next) {
            mbar_arrive_remote_if(lane < VS2 / 10, rb0 + ((nA - 4 + lane) << 24) + OFF_BAR + 8 * B_R2);
            bar_sync(N_TURN, 256);
          }
          if (VS2 < 30) { wg_fence(); proj<32, SSV, 1, VS2, 30>(v, W, D); wg_commit(); }
          if (has_next) mbar_waitu(bar + 8 * (B_F2 + 3), par ^ 1);
          if (VS2 < 30) { wg_wait<0>(); if (has_next) REL(B_R2, 2); }
          wg_fence(); proj<32, SSV, 1, 30, 40>(v, W, D); wg_commit();
          wg_wait<0>();
          if (has_next) REL(B_R2, 3);
#pragma unroll
          for (int j = 0; j < 8; j++) vn[j] = pack2v(v[2 * j], v[2 * j + 1]);
          keep4(vn, lane); keep4(vn + 4, lane);
          if (warp == 0) TS(18);
        }
        float o[16];
        bar_sync(N_P, 256);
        fence_async();
        wg_fence();
        MM<32>::rs<dlo(OFF_PL, 128), 0>(o, vl, D.p);
        MM<32>::rs<dlo(OFF_PL + 256, 128), 1>(o, vl + 4, D.p);
        MM<32>::rs<dlo(OFF_PL + 512, 128), 1>(o, vm, D.p);
        wg_commit();
        OX_ADDR();
        wg_wait<0>();
        bar_sync(N_V, 128);
        stsm4t(s1, pack2(o[0], o[1]), pack2(o[2], o[3]), pack2(o[4], o[5]), pack2(o[6], o[7]));
        stsm4t(s2, pack2(o[8], o[9]), pack2(o[10], o[11]), pack2(o[12], o[13]), pack2(o[14], o[15]));
#pragma unroll
        for (int j = 0; j < 8; j++) vl[j] = vn[j];
      }
      bar_arrive(N_OX, 160);
      if (warp == 0) TS(16);
    }
    cluster_sync_all();
  } else {
    asm volatile("setmaxnreg.dec.sync.aligned.u32 32;");
    if (wg > 3) return;
    LANE_INIT();
    struct RsJob { uint32_t* gp; uint32_t la, mb; int n; };
    auto rs_prep = [&](int step, int s, int c) {
      RsJob j;
      const int u = s * nA + rank;
      j.gp = &g_part[0][0][0][0] + (uint32_t)((((step & 1) * 2 + c) * NCL + cl) * 2560 + u * 64 + (lane >> 2) * 8 + (lane & 3));
      j.la = sb + OFF_TILE + c * LAND_F + LAND(s) + lane * 8;
      j.mb = bar + 8 * (B_RS + s);
      j.n = u >= 40 ? 0 : u >= 36 ? 3 : 1;
      asm volatile("" : "+l"(j.gp), "+r"(j.la));
      return j;
    };
    auto rs_sum = [&](RsJob j, int step) {
      if (j.n) {
        auto five = [&](uint32_t la) {
          uint2 p[5];
#pragma unroll
          for (int i = 0; i < 4; i++) p[i] = lds64(la + i * 256);
          asm volatile("{\n.reg .pred q;\nsetp.eq.s32 q, %3, 5;\nmov.u32 %0, 0;\nmov.u32 %1, 0;\n@q ld.shared.v2.b32 {%0,%1}, [%2];\n}"
                       : "=r"(p[4].x), "=r"(p[4].y) : "r"(la + 1024), "r"(nh) : "memory");
          return make_uint2(hadd2bf(hadd2bf(p[0].x, p[1].x), hadd2bf(hadd2bf(p[2].x, p[3].x), p[4].x)),
                            hadd2bf(hadd2bf(p[0].y, p[1].y), hadd2bf(hadd2bf(p[2].y, p[3].y), p[4].y)));
        };
        const uint32_t tag = ((step >> 1) & 1) ^ 1;
        mbar_waitw(j.mb, step & 1);
        uint2 t = five(j.la);
        if (j.n > 1) {
          const uint2 a = five(j.la + (nh == 5 ? 1280 : TILE_GRP - 1280)), b = five(j.la + TILE_GRP);
          t.x = hadd2bf(t.x, hadd2bf(a.x, b.x)); t.y = hadd2bf(t.y, hadd2bf(a.y, b.y));
        }
        const uint32_t t0 = (movm(t.x) & ~1u) | tag, t1 = (movm(t.y) & ~1u) | tag;
        asm volatile("st.relaxed.gpu.global.b32 [%0], %1;" :: "l"(j.gp), "r"(lane & 16 ? t1 : t0) : "memory");
        asm volatile("st.relaxed.gpu.global.b32 [%0], %1;" :: "l"(j.gp + 4), "r"(lane & 16 ? t0 : t1) : "memory");
      }
    };
    if (warp * nA + (int)rank < 40) {
#pragma unroll
      for (int e = LAG; e < LAG + 2; e++)
        if ((e >> 1) & 1) *reinterpret_cast<uint2*>(&g_part[(e & 1) * 2 + 1][cl][warp * nA + rank][lane * 2]) = make_uint2(1u, 1u);
      __threadfence();
    }
    if (warp == 2 && ig >= 0 && sync_b) wait_cnt(&g_xready[0][0], 32);
    cluster_sync_all();
    if (warp == 2 && ig >= 0) bulk_g2s_mc_e(sb + OFF_TILE + ig * TILE_GRP + TILE_SBO, &g_xn[0][0] + ig * 5120, 10240, bar + 8 * (B_F2 + ig), mcmask);
    bar_sync(N_PI, 128);
#pragma unroll 1
    for (int i = warp; i < 20; i += 4) {
      int c0, c1; wo_coord(i, t3, head, c0, c1);
      if (i >= 2 && i < 15) tma2d_e(sb + OFF_WO + (i - 2) * 4096, &M.wo32, c0, c1, bar + 8 * B_W1);
      else if (lane == 0) tma2d_prefetch(&M.wo32, c0, c1);
      __syncwarp();
    }
#pragma unroll 1
    for (int step = 0; step < NSTEP; step++) {
      const uint32_t par = step & 1;
      asm volatile("" : "+r"(lane));
      const bool dual = is_dual(step), has_next = step + 1 < NSTEP;
      {
        bar_sync(N_PX, dual ? 256 : 192);
        if (dual || warp >= 2) tok_softmax(sb, dual ? warp : warp - 2, lane);
        bar_arrive(N_P, 256);
        asm volatile("" : "+r"(lane));
        if (has_next) {
          if (step + 2 == LAG && lane < 20) asm volatile("prefetch.global.L2 [%0];" :: "l"(mem0 + (warp * 20 + lane) * 64));
          const int nw = ig >= 0 ? 3 : 4, j0 = warp < nw ? warp : 8;
          const int sh = dual ? 1 : 0;
          rs_sum(rs_prep(step, j0 >> sh, j0 & sh), step);
          if (warp == 0) TS(17);
          if (dual) rs_sum(rs_prep(step, (j0 + nw) >> 1, (j0 + nw) & 1), step);
          if (warp == 0) { bar_sync(N_C, 288); }
          mbar_arrive_remote_if(lane < nA, rb0 + (lane << 24) + OFF_BAR + 8 * B_LANDFREE);
          const uint32_t gap = dual ? POLL_GAPD : POLL_GAP;
          if (gap) { const uint32_t t0 = clock32(); while (clock32() - t0 < gap) {} }
#pragma unroll 1
          for (int j = j0; j < (dual ? 8 : 4); j += nw) {
            const int u = (j >> sh) * nA + rank, c = j & sh;
            if (u < UMAX && (c || step + 1 != NSEG)) {
              const uint32_t* gq = &g_part[0][0][0][0] + (uint32_t)((par * 2 + c) * NCL * 2560 + u * 64 + lane * 2);
              uint2 pa[NCL];
              POLL(pa, gq);
              deliver(pa, gq, u, c, step + 1 < NSEG ? c : 0, dual ? DS_DUAL : DS_SINGLE, step, j == 0, lane);
            }
            if (warp == 0 && j == 0) TS(13);
          }
          if (warp >= nw && (is_dual(step + 1) || (ig < 3 && step + 2 < NSTEP))) {
            issue_tok(is_dual(step + 1) ? sched_f(step + 1) : sched_l(step + 2), is_dual(step + 1) ? B_F1 : B_F2, B_R2, par ^ 1);
          }
          if (step + 1 == LAG && UMAX) {
            uint4 v[5];
#pragma unroll
            for (int i = 0; i < 5; i++) { const int t = warp * 160 + i * 32 + lane; v[i] = *reinterpret_cast<const uint4*>(mem0 + ((t >> 1) & 7) * DM + (t >> 4) * 16 + ((t ^ (t >> 3)) & 1) * 8); }
            mbar_waitu(bar + 8 * B_LANDFREE, par);
#pragma unroll
            for (int i = 0; i < 5; i++)
              st_async_v4(sb + OFF_TILE + LAND_F + warp * TILE_GRP + (i * 32 + lane) * 16, v[i].x, v[i].y, v[i].z, v[i].w, bar + 8 * (B_F1 + warp));
          }
        }
      }
      if (warp == (ig >= 0 && !is_dual(step + 1) ? 2 : 3)) {
        unsigned char* o0 = g_o + uni(step % RO * (96 * 8192) + (head * 3 + t3) * (dual ? 8192 : 4096));
        bar_sync(N_OX, 160);
        fence_async();
        bulk_s2g_es(o0, sb + OFF_PL, 4096);
        if (dual) bulk_s2g_es(o0 + 4096, sb + OFF_PL + PL_SZ, 4096);
        asm volatile("cp.async.bulk.commit_group;" ::: "memory");
        asm volatile("cp.async.bulk.wait_group.read 0;" ::: "memory");
        __syncwarp();
        mbar_arrive_remote_if(lane < 2, (lane ? nxt : prv) + OFF_BAR + 8 * B_PLFREE);
        asm volatile("cp.async.bulk.wait_group 0;" ::: "memory");
        asm volatile("fence.proxy.async.global;" ::: "memory");
        __syncwarp();
        if (lane == 0) red_release(&g_f[F_O + (head * 3 + t3) / 5][step], 1u);
        __syncwarp();
      }
    }
    cluster_sync_all();
  }
}

__device__ __forceinline__ uint32_t gelu2(uint32_t x) {
  uint32_t g;
  asm("{\n.reg .b32 u, a, b;\nmov.b32 a, 0x28912891;\nmov.b32 b, 0x3a623a62;\nmul.rn.f16x2 u, %1, %1;\nfma.rn.f16x2 u, u, a, b;\nmul.rn.f16x2 u, u, %1;\n"
      "tanh.approx.f16x2 u, u;\nfma.rn.f16x2 %0, %1, u, %1;\n}" : "=r"(g) : "r"(x));
  return g; }

struct BParams {
  CUtensorMap wmap[5];
  CUtensorMap wo16;
  const __nv_bfloat16* x;
  __nv_bfloat16* out;
  uint64_t desc, desc32;
};
#define BO_O 0
#define BO_RES (6 * 8192)
#define OP_RES 63488
#define BO_STG (BO_RES + 2 * OP_RES)
#define BO_RING_OP (BO_STG + 16384)
#define OP_SLOT 12288
#define NS_OP 3
#define BO_H 81920
#define BO_W1 (BO_H + 16384)
#define BO_RING_MLP (BO_W1 + 81920)
#define BO_BAR 229376
#define BO_BOX (BO_BAR + 248)
#define BO_CARRY (BO_BAR + 512)
#define BO_STAT (BO_CARRY + 2048)
#define B_SMEM (BO_STAT + 256)
static_assert(B_SMEM <= 232448 && BO_RING_OP + NS_OP * OP_SLOT == BO_BAR && BO_RING_MLP + 3 * 16384 == BO_BAR && 2 * 83968 <= BO_RING_MLP, "smem");
enum { BB_W = 0, BB_FULL = 2, BB_TMP = BB_FULL + 3, BB_OFULL = BB_FULL + 5, BB_SFREE = BB_OFULL,
       BB_STAT = BB_SFREE + 6, BB_GO, BB_ZFREE, BB_DONE = BB_ZFREE + 3,
       BB_EMPTY, BB_START = BB_EMPTY, BB_USED = BB_EMPTY + 2, BB_NUM = BB_USED + 3 };
enum { NB_PP = 1, NB_H = 3, NB_END = 4, NB_END2 = 5, NB_STAGED = 6, NB_FREE = 8, NB_EARLY = 10, NB_LAST = 11 };

#define DESC_LO(off) (((SMEM0 + (off)) >> 4) | (1u << 16))

__device__ __forceinline__ uint32_t ld_relaxed(const uint32_t* p) { uint32_t v; asm volatile("ld.relaxed.gpu.global.b32 %0, [%1];" : "=r"(v) : "l"(p) : "memory"); return v; }
__device__ __forceinline__ int fmask(int r) { return (r < NSEG) | ((r >= LAG && r < NSTEP) << 1); }
__device__ __forceinline__ int bmask(int r) { return (r <= NSEG) | ((r >= LAG) << 1); }
__device__ __forceinline__ uint32_t rtarget(int mask) { return mask == 3 ? 64 : 32; }
__device__ __forceinline__ void warp_signal(uint32_t* p, int lane) {
  __syncwarp();
  asm volatile("{\n.reg .pred q;\nsetp.eq.u32 q, %1, 0;\n@q red.release.gpu.global.add.u32 [%0], 1;\n}" :: "l"(p), "r"(lane) : "memory");
}
__device__ __forceinline__ uint32_t pack2h(float lo, float hi) { uint32_t r; asm("cvt.rn.f16x2.f32 %0, %1, %2;" : "=r"(r) : "f"(hi), "f"(lo)); return r; }
template <bool H> __device__ __forceinline__ uint32_t pk(float lo, float hi) { return H ? pack2h(lo, hi) : pack2(lo, hi); }
template <int N, bool H> __device__ __forceinline__ void stage_out(const float* d, uint32_t dst, int warp, int lane) {
  const uint32_t sa = dst + ((lane >> 4) * 8 + (lane & 7)) * 128 + (((2 * warp + ((lane >> 3) & 1)) ^ (lane & 7)) << 4);
#pragma unroll
  for (int m = 0; m < N / 16; m++)
    stsm4t(sa + m * 2048, pk<H>(d[8 * m], d[8 * m + 1]), pk<H>(d[8 * m + 2], d[8 * m + 3]), pk<H>(d[8 * m + 4], d[8 * m + 5]), pk<H>(d[8 * m + 6], d[8 * m + 7]));
}
template <int N> __device__ __forceinline__ void acc_live(float* d) {
#pragma unroll
  for (int i = 0; i < N / 2; i++) asm volatile("" : "+f"(d[i]) :: "memory");
}
struct Ring {
  uint32_t sl, ph;
  template <int NS> __device__ __forceinline__ void step() { if (++sl == NS) { sl = 0; ph ^= 1; } }
};

#define KOFF(x) (DESC_LO(BO_O) + ((x) >> 2) * 512 + ((x) & 3) * 2)
template <int N, int P>
__device__ __forceinline__ void op_pass(const uint32_t* W, uint32_t bar, Dsc alo, Dsc blo, Dsc xlo, bool x2, Ring& rg, int wg, int warp, int lane, int r) {
  float acc[N / 2];
  blo.e = xlo.e = fresh<P + N / 64 * 5>(r);
  const Dsc tlo = blo + uni(rg.sl) * (OP_SLOT / 16), b2 = blo + (r & 1) * 1536;
  if (P == 0) mbar_waitu(bar + 8 * (BB_OFULL + 2 + (r & 1)), (r >> 1) & 1);
  CTS(5 * P);
  bar_sync(NB_PP + wg, 256);
  wg_fence();
#define OP_R(x, b) MM<N>::template rs<KOFF(4 * (x >> 1) + (x & 1)), (x != (P ? 0 : 4))>(acc, W + 32 * P + 4 * x, b);
#define OP_S(x, b) MM<N>::template ss<DESC_LO(BO_RES) + (6 * P + x) * 128, KOFF(4 * (x >> 1) + 2 + (x & 1)), 1>(acc, alo, b);
#define OP_T(x) MM<N>::template ss<DESC_LO(BO_RING_OP) + x * 128, KOFF(14 + x), 1>(acc, tlo, blo);
#define OP_B2() OP_R(4, b2) OP_S(4, b2) OP_R(5, b2) OP_S(5, b2)
  if (P == 0) { OP_B2() mbar_waitu(bar + 8 * BB_OFULL, r & 1); }
  OP_R(0, blo) OP_S(0, blo) OP_R(1, blo) OP_S(1, blo) OP_R(2, blo) OP_S(2, blo) OP_R(3, blo) OP_S(3, blo)
  if (P == 0) mbar_waitu(bar + 8 * (BB_OFULL + 1), r & 1);
  if (P == 4) wg_commit();
  if (P & 3) { OP_B2() }
  if (P == 1 && x2) MM<N>::template ss<DESC_LO(BO_RES) + 30 * 128, DESC_LO(BO_CARRY), 1>(acc, alo, xlo);
  mbar_waitu(bar + 8 * (BB_FULL + rg.sl), rg.ph);
  OP_R(6, blo) OP_T(0) OP_R(7, blo) OP_T(1)
  if (P == 4) { wg_commit(); wg_wait<1>(); bar_arrive(NB_EARLY, 288); CTS(21); wg_fence(); }
  OP_T(2) OP_T(3)
  if (P == 0) MM<N>::template rs<DESC_LO(BO_CARRY), 1>(acc, W + 160, xlo);
  OP_T(4) OP_T(5)
  if (P == 4) { wg_commit(); OP_B2() }
  wg_commit();
  bar_arrive(NB_PP + 1 - wg, 256);
  CTS(5 * P + 2);
  if (P == 4) { wg_wait<1>(); bar_arrive(NB_LAST, 288); }
  bar_sync(NB_FREE + wg, 160);
  wg_wait<0>();
  acc_live<N>(acc);
  mbar_arrive_if(lane == 0, bar + 8 * (BB_USED + rg.sl));
  CTS(5 * P + 3);
  stage_out<N, false>(acc, SMEM0 + BO_STG + wg * 8192, warp, lane);
  bar_arrive(NB_STAGED + wg, 160);
  CTS(5 * P + 4);
  rg.step<NS_OP>(); rg.step<NS_OP>();
}
template <int N>
__device__ __forceinline__ void op_round(const uint32_t* W, uint32_t bar, Dsc alo, Dsc blo, Dsc xlo, bool x2, Ring& rg, int wg, int warp, int lane, int r) {
  op_pass<N, 0>(W, bar, alo, blo, xlo, x2, rg, wg, warp, lane, r);
  op_pass<N, 1>(W, bar, alo, blo, xlo, x2, rg, wg, warp, lane, r);
  op_pass<N, 2>(W, bar, alo, blo, xlo, x2, rg, wg, warp, lane, r);
  op_pass<N, 3>(W, bar, alo, blo, xlo, x2, rg, wg, warp, lane, r);
  op_pass<N, 4>(W, bar, alo, blo, xlo, x2, rg, wg, warp, lane, r);
}
__device__ __forceinline__ void carry_in(uint32_t sb, int wg, int warp, int lane) {
  const int row = (lane >> 1) & 3;
  if (lane < 16) {
    const uint4 v = lds128(sb + BO_CARRY + (wg * 4 + warp) * 256 + lane * 16);
    sts128(sb + BO_H + wg * 8192 + (lane >> 3) * 4096 + row * 128 + (((2 * warp + (lane & 1)) ^ row) << 4), v.x, v.y, v.z, v.w);
  }
  __syncwarp();
}
template <int N, int Z>
__device__ __forceinline__ void p1_pair(float* acc, const uint32_t* W, uint32_t bar, Dsc alo, Dsc blo, int lane, int r) {
  constexpr int ZOFF = N == 64 ? (2 * Z % 3) * 1024 : (Z / 2 * 2 % 3) * 1024 + (Z & 1) * 256;
  blo.e = fresh<10 + Z / 3 + N / 64 * 2>(r);
  mbar_waitu(bar + 8 * (BB_FULL + Z), r & 1);
  CTS(40 + Z);
  wg_fence();
#define P1_B(k) \
  MM<N, true>::template rs<DESC_LO(BO_RING_MLP) + ZOFF + k * 512, (2 * Z + k != 0)>(acc, W + 16 * Z + 8 * k, blo); \
  MM<N, true>::template ss<DESC_LO(BO_W1) + (2 * Z + k) * 512, DESC_LO(BO_RING_MLP) + ZOFF + k * 512 + 4, 1>(acc, alo, blo); \
  MM<N, true>::template rs<DESC_LO(BO_RING_MLP) + ZOFF + k * 512 + 2, 1>(acc, W + 16 * Z + 8 * k + 4, blo); \
  MM<N, true>::template ss<DESC_LO(BO_W1) + (2 * Z + k) * 512 + 128, DESC_LO(BO_RING_MLP) + ZOFF + k * 512 + 6, 1>(acc, alo, blo);
  P1_B(0)
  if (N == 64 && (Z == 1 || Z == 2)) { wg_commit(); wg_wait<1>(); mbar_arrive_if(lane == 0, bar + 8 * (BB_EMPTY + Z - 1)); wg_fence(); }
  P1_B(1)
  wg_commit();
}
template <int N>
__device__ __forceinline__ void phase1(const uint32_t* W, uint32_t sb, Dsc alo, Dsc blo, int half, int wg, int warp, int lane, int off, int r) {
  float acc[N / 2];
  const uint32_t bar = sb + BO_BAR;
  CTS(30);
  p1_pair<N, 0>(acc, W, bar, alo, blo, lane, r);
  p1_pair<N, 1>(acc, W, bar, alo, blo, lane, r);
  p1_pair<N, 2>(acc, W, bar, alo, blo, lane, r);
  if (N == 32) p1_pair<N, 3>(acc, W, bar, alo, blo, lane, r);
  mbar_waitu(bar + 8 * (BB_SFREE + 4 + wg), (r + 1) & 1);
  carry_in(sb, wg, warp, lane);
  if (N == 32) mbar_arrive_if(lane < 2, bar + 8 * (BB_EMPTY + lane));
  else p1_pair<N, 3>(acc, W, bar, alo, blo, lane, r);
  p1_pair<N, 4>(acc, W, bar, alo, blo, lane, r);
  const int c = (lane >> 3) & 1, i0 = (lane >> 4) * 8 + (lane & 7) + off;
  uint32_t a0 = sb + BO_H + wg * 8192 + half * 4096 + i0 * 128 + (((2 * warp + c) ^ (i0 & 7)) << 4);
  uint32_t a1 = i0 >= 16 ? sb + BO_CARRY + (wg * 4 + warp) * 256 + half * 128 + (i0 - 16) * 32 + c * 16 : a0 + 2048, a3 = a1 + (i0 >= 16 ? 128 : 4096);
  asm volatile("" : "+r"(a0), "+r"(a1), "+r"(a3));
  mbar_waitu(bar + 8 * BB_STAT, r & 1);
  const uint32_t sa = sb + BO_STAT + half * 128 + (lane & 3) * 32;
  uint4 t[2] = {lds128(sa), lds128(sa + 16)};
  wg_wait<0>();
  acc_live<N>(acc);
  CTS(32);
#pragma unroll
  for (int m = 0; m < N / 16; m++) {
    const float s0 = __uint_as_float(t[m & 1].x), s1 = __uint_as_float(t[m & 1].y), s2 = __uint_as_float(t[m & 1].z), s3 = __uint_as_float(t[m & 1].w);
    const float* d = acc + 8 * m;
    const uint32_t x0 = pack2h(d[0] * s0, d[1] * s1), x1 = pack2h(d[2] * s0, d[3] * s1), x2 = pack2h(d[4] * s2, d[5] * s3), x3 = pack2h(d[6] * s2, d[7] * s3);
    if (m + 2 < N / 16) t[m & 1] = lds128(sa + 128 + m * 16);
    stsm4t(m == 1 ? a1 : m == 3 ? a3 : a0 + m * 2048, gelu2(x0), gelu2(x1), gelu2(x2), gelu2(x3));
  }
}
template <int N, int P>
__device__ __forceinline__ void p2_mma(float* acc, const uint32_t* W, Dsc alo, Dsc blo, int r) {
  blo.e = fresh<P + N / 64 * 5>(r);
  MM<N, true>::template rs<DESC_LO(BO_H), 0>(acc, W + 80 + 16 * P, blo);     MM<N, true>::template ss<DESC_LO(0) + P * 1024, DESC_LO(BO_H) + 512, 1>(acc, alo, blo);
  MM<N, true>::template rs<DESC_LO(BO_H) + 2, 1>(acc, W + 84 + 16 * P, blo); MM<N, true>::template ss<DESC_LO(0) + P * 1024 + 128, DESC_LO(BO_H) + 514, 1>(acc, alo, blo);
  MM<N, true>::template rs<DESC_LO(BO_H) + 4, 1>(acc, W + 88 + 16 * P, blo); MM<N, true>::template ss<DESC_LO(0) + P * 1024 + 512, DESC_LO(BO_H) + 516, 1>(acc, alo, blo);
  MM<N, true>::template rs<DESC_LO(BO_H) + 6, 1>(acc, W + 92 + 16 * P, blo); MM<N, true>::template ss<DESC_LO(0) + P * 1024 + 640, DESC_LO(BO_H) + 518, 1>(acc, alo, blo);
}
template <int N, int P, int T>
__device__ __forceinline__ void p2_pass(const uint32_t* W, uint32_t bar, Dsc alo, Dsc blo, int wg, int warp, int lane, int r) {
  float acc[N / 2], ac2[N / 2];
  CTS(5 * P);
  if (P || wg) bar_sync(NB_PP + wg, 256);
  wg_fence();
  p2_mma<N, P>(acc, W, alo, blo, r);
  wg_commit();
  if constexpr (T == 2) { p2_mma<N, P + 1>(ac2, W, alo, blo, r); wg_commit(); }
  if (P < 4 || !wg) bar_arrive(NB_PP + 1 - wg, 256);
  CTS(5 * P + 2);
  if (T == 1 && (P == 2 || P == 3)) mbar_waitu(bar + 8 * (BB_SFREE + 2 * (P - 2) + wg), r & 1);
  wg_wait<T - 1>();
  acc_live<N>(acc);
  if (P == 4) bar_sync(NB_H, 256);
  CTS(5 * P + 3);
  constexpr int K = P / T & 1;
  stage_out<N, true>(acc, SMEM0 + (P == 4 ? BO_H : BO_RING_MLP + (2 - K) * 16384) + wg * 8192, warp, lane);
  if constexpr (T == 2) {
    wg_wait<0>();
    acc_live<N>(ac2);
    stage_out<N, true>(ac2, SMEM0 + BO_RING_MLP + (2 - K) * 16384 + wg * 8192 + 4096, warp, lane);
  }
  bar_arrive(NB_STAGED + (P == 4 ? 4 : 2 * K) + wg, 160);
  CTS(5 * P + 4);
}
template <int N>
__device__ __forceinline__ void phase2(const uint32_t* W, uint32_t bar, Dsc alo, Dsc blo, int wg, int warp, int lane, int r) {
  if constexpr (N == 64) {
    p2_pass<N, 0, 1>(W, bar, alo, blo, wg, warp, lane, r);
    p2_pass<N, 1, 1>(W, bar, alo, blo, wg, warp, lane, r);
    p2_pass<N, 2, 1>(W, bar, alo, blo, wg, warp, lane, r);
    p2_pass<N, 3, 1>(W, bar, alo, blo, wg, warp, lane, r);
  } else {
    p2_pass<N, 0, 2>(W, bar, alo, blo, wg, warp, lane, r);
    p2_pass<N, 2, 2>(W, bar, alo, blo, wg, warp, lane, r);
  }
  p2_pass<N, 4, 1>(W, bar, alo, blo, wg, warp, lane, r);
}

__device__ __forceinline__ void ldg4(uint32_t* v, const void* p) {
  asm volatile("ld.relaxed.gpu.global.v4.u32 {%0,%1,%2,%3}, [%4];" : "=r"(v[0]), "=r"(v[1]), "=r"(v[2]), "=r"(v[3]) : "l"(p) : "memory"); }
__device__ __forceinline__ void stg4(void* p, const uint32_t* v) {
  asm volatile("st.global.v4.u32 [%0], {%1,%2,%3,%4};" :: "l"(p), "r"(v[0]), "r"(v[1]), "r"(v[2]), "r"(v[3]) : "memory"); }
struct RowPtr {
  unsigned char *p, *q, *t;
  __device__ __forceinline__ void ld(uint32_t* v, int o) const {
    ldg4(v, p + o); ldg4(v + 4, q + o);
    asm volatile("ld.relaxed.gpu.global.v2.u32 {%0,%1}, [%2];" : "=r"(v[8]), "=r"(v[9]) : "l"(t + o) : "memory");
  }
  __device__ __forceinline__ void st(const uint32_t* w, int o) const {
    stg4(p + o, w); stg4(q + o, w + 4);
    asm volatile("st.global.v2.u32 [%0], {%1,%2};" :: "l"(t + o), "r"(w[8]), "r"(w[9]) : "memory");
  }
};
__device__ __forceinline__ RowPtr row_img(int r, int n, int lane) {
  unsigned char* b = &g_acc[0][r % RD][n * 128];
  unsigned char* p = b + (uint32_t)((lane >> 3) * 8192 + (((lane ^ n) & 7) << 4));
  return {p, p + 32768, b + (uint32_t)(65536 + (lane >> 4) * 8192 + ((((lane >> 1) ^ n) & 7) << 4) + (lane & 1) * 8)};
}
__device__ __forceinline__ RowPtr row_ext(const void* lin, bool xn, int layer, int tok, int lane) {
  unsigned char* b = xn ? reinterpret_cast<unsigned char*>(&g_xn[layer][0]) + (uint32_t)((tok >> 5) * 40960 + ((tok >> 3) & 3) * 2560 + (tok & 7) * 32)
                        : (unsigned char*)lin + (uint32_t)(tok * 1280);
  const uint32_t o = (lane >> 1) * 256 + ((lane ^ (tok >> 2)) & 1) * 16;
  return {b + (uint32_t)(xn ? o + (lane >= 20 ? 7680 : 0) : lane * 16),
          b + (uint32_t)(xn ? o + 4096 + 7680 + (lane >= 8 ? 7680 : 0) + (lane >= 28 ? 7680 : 0) : lane * 16 + 512),
          b + (uint32_t)(xn ? (lane >> 2) * 256 + ((lane & 3) ^ ((tok >> 1) & 2)) * 8 + 8192 + 3 * 7680 : lane * 8 + 1024)};
}
__device__ __forceinline__ float2 h2f(uint32_t w) {
  float2 f; asm("{\n.reg .f16 l, h;\nmov.b32 {l, h}, %2;\ncvt.f32.f16 %0, l;\ncvt.f32.f16 %1, h;\n}" : "=f"(f.x), "=f"(f.y) : "r"(w)); return f; }
__device__ __forceinline__ float rsq(float x) { float y; asm("rsqrt.approx.ftz.f32 %0, %1;" : "=f"(y) : "f"(x)); return y; }
__device__ __forceinline__ void red_if(uint32_t v, const void* a) {
  asm volatile("{\n.reg .pred q;\nsetp.ne.u32 q, %1, 0;\n@q red.relaxed.gpu.global.add.u32 [%0], %1;\n}" :: "l"(a), "r"(v) : "memory"); }
__device__ __forceinline__ uint32_t dep0(uint32_t w, int lane) { uint32_t z; asm volatile("shr.b32 %0, %1, %2;" : "=r"(z) : "r"(w), "r"(lane + 32)); return z; }
__device__ __forceinline__ int lane_of(uint32_t w) {
  int lane; asm volatile("{\n.reg .u32 t;\nmov.u32 t, %%laneid;\nshr.u32 %0, %1, 20;\nadd.u32 %0, %0, t;\n}" : "=r"(lane) : "r"(w)); return lane; }
#define BUF (RD * TILE_B)
__device__ __forceinline__ int await(uint32_t v, const uint32_t* p, uint32_t target, bool lazy) {
  int n = 0;
  while (!__all_sync(~0u, v >= target)) {
    if (lazy) __nanosleep(200);
    if (++n > SPIN_LIMIT) FAIL();
    v = ld_relaxed(p);
  }
  asm volatile("fence.acquire.gpu;" ::: "memory");
  return lane_of(v);
}
template <int W> __device__ __forceinline__ void sum2(float& s, float& q, int lane) {
  const bool up = lane & (W / 2);
  float e = (up ? q : s) + __shfl_xor_sync(~0u, up ? s : q, W / 2);
#pragma unroll
  for (int o = W / 4; o; o >>= 1) e += __shfl_xor_sync(~0u, e, o);
  const float f = __shfl_xor_sync(~0u, e, W / 2);
  s = up ? f : e; q = up ? e : f;
}
template <int TYPE>
__device__ __forceinline__ void rrow(int r, int row, int tok, int lane, const uint32_t* go, int role, const __nv_bfloat16* x, __nv_bfloat16* out) {
  const int half = TYPE == 3 ? 0 : row >> 5;
  float v[20];
  float2 st = make_float2(1.f, 0.f);
  {
    uint32_t a[10], c[10], u[10], sh = 16;
    if (TYPE == 2) row_img(r + RD - ((row & 31) < 2), (row & 32) + ((row - 2) & 31), lane).ld(u, 3 * BUF);
    else row_ext(x, half, 1, tok, lane).ld(u, 0);
    if (TYPE == 2 || (TYPE == 0 && half))
      asm volatile("ld.relaxed.gpu.global.v2.f32 {%0,%1}, [%2];" : "=f"(st.x), "=f"(st.y) : "l"(g_stat + tok) : "memory");
    RowPtr ap = row_img(r, row, lane);
    const uint32_t g0 = TYPE != 3 ? ld_relaxed(go) : 0;
    if (TYPE != 3) {
      asm volatile("" : "+l"(ap.p), "+l"(ap.t));
      ap.q = ap.p + 32768;
      lane = await(g0, go, NOP * NW12 * NW34, false); BTS2(r, 8 + 2 * TYPE); RTS(0);
      ap.ld(a, TYPE ? 2 * BUF : 0);
    }
    if (TYPE == 0) {
      ap.ld(c, BUF);
      const uint32_t one = 0x3f803f80u | dep0(c[9], lane);
#pragma unroll
      for (int i = 0; i < 10; i++) asm volatile("fma.rn.bf16x2 %0, %0, %1, %2;" : "+r"(a[i]) : "r"(one), "r"(c[i]));
      sh |= dep0(a[9], lane);
    }
    const uint32_t z = TYPE == 2 ? dep0(a[9], lane) : 0;
#pragma unroll
    for (int i = 0; i < 10; i++) {
      if (TYPE == 2) { const float2 g = h2f(u[i] | z), h = h2f(a[i] | z); v[2 * i] = fmaf(h.x, 0.5f, g.x * st.x); v[2 * i + 1] = fmaf(h.y, 0.5f, g.y * st.x); continue; }
      float p = __uint_as_float(u[i] << sh), q = __uint_as_float(u[i] & (0xffffu << sh));
      if (TYPE == 0) { p = fmaf(p, st.x, bf_lo(a[i])); q = fmaf(q, st.x, bf_hi(a[i])); }
      v[2 * i] = p; v[2 * i + 1] = q;
    }
  }
  RTSD(1, v[19]);
  float s = 0.f, q = 0.f;
#pragma unroll
  for (int i = 0; i < 5; i++) {
    s += (v[4 * i] + v[4 * i + 1]) + (v[4 * i + 2] + v[4 * i + 3]);
    q += fmaf(v[4 * i], v[4 * i], v[4 * i + 1] * v[4 * i + 1]) + fmaf(v[4 * i + 2], v[4 * i + 2], v[4 * i + 3] * v[4 * i + 3]);
  }
  if (!(TYPE == 2 && half)) sum2<32>(s, q, lane);
  const float mean = s * (1.f / DM), var = fmaxf(q * (1.f / DM) - mean * mean, 0.f), rs = rsq(var + 1e-5f);
  const float k = TYPE == 0 ? 2.f * rs : half ? 1.f : rs, mr = TYPE && half ? st.y : -mean * k;
  RTSD(2, rs);
  uint32_t w[10];
#pragma unroll
  for (int i = 0; i < 10; i++) w[i] = pk<TYPE == 0>(fmaf(v[2 * i], k, mr), fmaf(v[2 * i + 1], k, mr));
  if (TYPE) row_ext(out, !half, TYPE == 2, tok, lane).st(w, 0);
  else {
    row_img(r, row, lane).st(w, 3 * BUF);
    row_img(r + ((row & 31) >= 30), (row & 32) + ((row + 2) & 31), lane).st(w, 2 * BUF);
    if (lane == 1) g_st2[0][r % RD][row] = (__float_as_uint(0.5f * rsq(fmaf(var * rs, rs, 1e-5f))) & ~127u) | (r + 1);
  }
  if (TYPE != 3 && lane == 0) g_stat[tok] = make_float2((var + 1e-5f) * rs * (TYPE ? 1.f : 0.5f), mean + st.y);
}
__device__ __forceinline__ void r2rows(int r, int row, int lane, const uint32_t* go) {
  const int n = row + (lane >> 4);
  const unsigned char* ap = &g_acc[2][r % RD][0] + (uint32_t)(n * 128 + ((lane >> 3) & 1) * 8192 + (((lane ^ n) & 7) << 4));
  const uint32_t* sp = &g_st2[1][r % RD][n];
  asm volatile("" : "+l"(ap), "+l"(sp));
  await(0, go, NOP * NW12 * NW34, false);
  BTS2(r, 10);
  uint32_t a[20];
#pragma unroll
  for (int i = 0; i < 5; i++) ldg4(a + 4 * i, ap + i * 16384);
  const uint32_t z = dep0(a[19], lane);
  float s = 0.f, q = 0.f, q2 = 0.f;
#pragma unroll
  for (int i = 0; i < 20; i++) { const float2 h = h2f(a[i] | z); s += h.x + h.y; q = fmaf(h.x, h.x, q); q2 = fmaf(h.y, h.y, q2); }
  q += q2;
  sum2<16>(s, q, lane);
  const float mean = s * (0.5f / DM), rs = rsq(fmaxf(q * (0.25f / DM) - mean * mean, 0.f) + 1e-5f);
  if ((lane & 15) == 0) asm volatile("st.relaxed.gpu.global.u32 [%0], %1;" :: "l"(sp), "r"((__float_as_uint(0.5f * rs) & ~127u) | (r + 1)) : "memory");
}
__device__ __forceinline__ void r3rows(int r, int row, int tok, int lane, __nv_bfloat16* out) {
  const int n = row + (lane >> 4), m = 32 + ((n - 2) & 31);
  const unsigned char* ap = &g_acc[0][r % RD][0] + (uint32_t)(n * 128 + ((lane >> 3) & 1) * 8192 + (((lane ^ n) & 7) << 4));
  const unsigned char* zp = &g_acc[3][(r + RD - (row == 32)) % RD][0] + (uint32_t)(m * 128 + ((lane >> 3) & 1) * 8192 + (((lane ^ m) & 7) << 4));
  unsigned char* op = reinterpret_cast<unsigned char*>(out) + (uint32_t)((tok + (lane >> 4)) * 1280 + (lane & 15) * 16);
  float2 st;
  asm volatile("ld.relaxed.gpu.global.v2.f32 {%0,%1}, [%2];" : "=f"(st.x), "=f"(st.y) : "l"(g_stat + tok + (lane >> 4)) : "memory");
#pragma unroll 1
  for (int i0 = 0; i0 < 2; i0++) {
    uint32_t a[12], u[12];
#pragma unroll
    for (int i = 0; i < 3; i++) { ldg4(a + 4 * i, ap + 2 * BUF + i * 16384); ldg4(u + 4 * i, zp + i * 16384); }
    uint32_t z = dep0(u[11], lane);
#pragma unroll
    for (int i = 0; i < 12; i++) {
      const float2 h = h2f(a[i] | z), g = h2f(u[i] | z);
      a[i] = pack2(fmaf(h.x, 0.5f, fmaf(g.x, st.x, st.y)), fmaf(h.y, 0.5f, fmaf(g.y, st.x, st.y)));
      if (i & 1) z = dep0(a[i], lane);
    }
    if (i0 == 0) stg4(op, a);
    stg4(op + 256, a + 4); stg4(op + 512, a + 8);
    ap += 32768; zp += 32768; op += 512;
  }
}
template <int TYPE>
__device__ __forceinline__ void rloop(int row, int cp, int role, const __nv_bfloat16* x, __nv_bfloat16* out) {
  constexpr int ST = TYPE == 4 ? 2 : TYPE;
  const int r0 = row & 32 ? LAG : 0;
  uint32_t v = 0;
  static_assert(NSEG + RD >= NSTEP, "no signals");
#pragma unroll 1
  for (int r = r0; r < (TYPE == 2 ? NR : TYPE == 4 ? NSEG + 1 : r0 + NSEG + (TYPE > 0)); r++) {
    if (TYPE == 2 && r == NSEG + 1) row += 32;
    const int tok = (r - (row & 32 ? LAG : 0)) * 32 + (row & 31) - (TYPE ? 2 : 0);
    const bool valid = TYPE == 0 || (unsigned)tok < S_LEN;
    const uint32_t* go = &g_f[F_R1 + 4 * ST + cp][r];
    const uint32_t* first = TYPE == 2 ? &g_f[F_R2 + cp][r] : TYPE ? go : (const uint32_t*)&g_xready[NSEG + r - r0][0];
    if constexpr (TYPE == 1) { r2rows(r, row, lane_of(r), go); BTS2(r, 11); continue; }
    if constexpr (TYPE == 4) {
      const int lane = await(v, go, NOP * NW12 * NW34, false);
      BTS2(r, 8 + 2 * ST); RTS(0);
      if (valid) r3rows(r, row, tok, lane, out);
    } else if constexpr (TYPE != 1) {
      if (TYPE || row >= 32) await(v, first, TYPE ? NOP * NW12 * NW34 : 32, true);
      if (valid) rrow<TYPE>(r, row, tok, lane_of(r), go, role, x, out);
    }
    if (TYPE > 1 && row >= 32 && r + RD - 1 >= NSTEP) { v = 0; BTS2(r, 13); continue; }
    const int lane = lane_of(r);
    const void* f = lane ? (const void*)&g_xready[NSEG + (tok >> 5)][0] : (const void*)&g_f[TYPE ? F_DONE : F_Z][r];
    asm volatile("" : "+l"(f));
    __syncwarp();
    RTS(3);
    v = ld_relaxed(first + (TYPE ? 1 : 8));
    asm volatile("fence.release.gpu;" ::: "memory");
    RTS(4);
    red_if(lane == 0 || (TYPE == 2 && lane == 1 && valid) ? (TYPE & 5 ? 2 : 1) : 0, f);
    RTS(5);
    RTS_OUT();
    BTS2(r, 9 + 2 * ST);
  }
}

#define SINGLE_OP 3
#define SINGLE_W 0
#define W_DELAY 0
#define BULK_ADD(T, dst, src, len) asm volatile("{\n.reg .pred e;\nelect.sync _|e, 0xffffffff;\n@e cp.reduce.async.bulk.global.shared::cta.bulk_group.add.noftz." T " [%0], [%1], %2;\n}" \
                                               :: "l"(dst), "r"(src), "r"(len) : "memory")
#define COMMIT() asm volatile("cp.async.bulk.commit_group;" ::: "memory")
#define DRAINED(n) do { asm volatile("cp.async.bulk.wait_group.read " #n ";" ::: "memory"); __syncwarp(); } while (0)
#define WRITTEN() do { asm volatile("cp.async.bulk.wait_group 0;\nfence.proxy.async.global;" ::: "memory"); __syncwarp(); } while (0)
__device__ __forceinline__ void wait_flags(const uint32_t* p, uint32_t target) {
  int n = 0;
  while (!__all_sync(~0u, ld_relaxed(p) >= target)) { if (++n > SPIN_LIMIT) FAIL(); }
  asm volatile("fence.acquire.gpu;" ::: "memory");
  asm volatile("fence.proxy.async.global;" ::: "memory");
}
__global__ void __launch_bounds__(512, 1) bworker_kernel(const __grid_constant__ BParams P) {
  extern __shared__ __align__(1024) unsigned char smem_raw[];
  const uint32_t sb = SMEM0, bar = sb + BO_BAR;
  const int wg = __shfl_sync(~0u, threadIdx.x >> 7, 0), warp = __shfl_sync(~0u, (threadIdx.x >> 5) & 3, 0);
  if (threadIdx.x == 0) {
    if (smem_u32(smem_raw) != SMEM0) FAIL();
    uint32_t smid; asm volatile("mov.u32 %0, %%smid;" : "=r"(smid));
    const uint32_t nb = ld_relaxed(&g_tpc[(smid >> 1) & 127]);
    const bool single = nb > 1, far = nb == 0 && (smid < 64 || smid >= 124);
    int kind = far || (single && atomicAdd(&g_f[F_MISC][35], 1u) < SINGLE_OP) ? 0 : single ? 1 + SINGLE_W : 1;
    int rc = single || (smid >> 1) == 16 || (smid >> 1) == 63 ? 1 : far ? 2 : 0;
    uint32_t i = atomicAdd(&g_f[F_MISC][32 + kind], 1u), o = atomicAdd(&g_f[F_MISC][36 + rc], 1u);
    while (i >= (kind == 0 ? NOP : kind == 1 ? NW12 : NW34)) { kind = (kind + 1) % 3; i = atomicAdd(&g_f[F_MISC][32 + kind], 1u); }
    while (o >= (rc == 0 ? 16 : rc == 1 ? 8 : 12)) { rc = (rc + 1) % 3; o = atomicAdd(&g_f[F_MISC][36 + rc], 1u); }
    sts64(sb + BO_BOX, i + (kind == 0 ? 0 : kind == 1 ? NOP : NOP + NW12), o + (rc ? 8 + 8 * rc : 0));
    for (int k = 0; k < BB_NUM; k++) mbar_init(bar + 8 * k, k >= BB_USED ? 4 : k >= BB_EMPTY ? 8 : k >= BB_ZFREE && kind ? 2 : 1);
    asm volatile("fence.mbarrier_init.release.cluster;" ::: "memory");
  }
  if (threadIdx.x < 128) sts128(sb + BO_CARRY + threadIdx.x * 16, 0u, 0u, 0u, 0u);
  auto ln0 = [&](int t) {
    const int lane = lane_of(t);
    if (lane < 20 && t + 128 < S_LEN) asm volatile("prefetch.global.L2 [%0];" :: "l"(P.x + (t + (t < 4 * NBC ? 4 * NBC : 128)) * DM + (lane >> 1) * 64));
    rrow<3>(0, 0, t, lane, nullptr, 0, P.x, nullptr);
    __syncwarp();
    asm volatile("fence.release.gpu;" ::: "memory");
    red_if(lane == 0, &g_xready[t >> 5][0]);
  };
  if (wg == 2) ln0(blockIdx.x * 4 + warp);
  fence_async();
  __syncthreads();
  const int role = uni(lds32(sb + BO_BOX));
  if (threadIdx.x < 32) BTS(94, 1);
  const bool op = role < NOP, w12 = role < NOP + NW12;
  const int j = op ? role : w12 ? role - NOP : role - NOP - NW12;
  const int rot = op ? (j ? 2 * ((j + 1) % 5) : 0) : 2 * (j % 5);
  if (wg == 3) {
    asm volatile("setmaxnreg.dec.sync.aligned.u32 24;");
    LANE_INIT();
    if (warp < 2) {
      auto announce = [&](int r) {
        const uint32_t* f = &g_f[(op ? F_R1 : w12 ? F_R2 : F_R3) + (lane & 3)][r];
        asm volatile("" : "+l"(f));
        if (warp == 0) { mbar_arrive_if(lane == 0, bar + 8 * BB_DONE); return; }
        mbar_waitw(bar + 8 * BB_DONE, r & 1);
        PTS(60);
        asm volatile("fence.release.gpu;" ::: "memory");
        red_if(lane >= 4 ? 0 : op ? NW12 * NW34 : w12 ? NOP * NW34 : NOP * NW12, f);
        PTS(61);
        BTS(r, 4);
      };
      if (op) {
        int mt = rot + warp;
        bar_arrive(NB_FREE + warp, 160);
#pragma unroll 1
        for (int r = 0; r < NSTEP; r++) {
          const uint32_t len = fmask(r) == 3 ? 8192 : 4096;
          unsigned char* acc = &g_acc[j & 1][r % RD][fmask(r) == 2 ? 4096 : 0];
#pragma unroll 1
          for (int p = 0; p < 5; p++) {
            bar_sync(NB_STAGED + warp, 160);
            PTS(50 + 2 * p + warp);
            fence_async();
            BULK_ADD("bf16", acc + mt * 8192, sb + BO_STG + warp * 8192, len);
            COMMIT();
            PTS(64 + 50 + 2 * p + warp);
            mt = mt >= 8 ? mt - 8 : mt + 2;
            DRAINED(0);
            bar_arrive(NB_FREE + warp, 160);
          }
          WRITTEN();
          announce(r);
        }
      } else {
#pragma unroll 1
        for (int r = 0; r < NR; r++) {
          const uint32_t len = bmask(r) == 3 ? 8192 : 4096;
          unsigned char* acc = &g_acc[2][r % RD][bmask(r) == 2 ? 4096 : 0];
          if (!w12) mbar_waitw(bar + 8 * BB_GO, r & 1);
          int mt = rot + warp;
          const bool pairs = len != 8192;
#pragma unroll 1
          for (int p = pairs ? 2 : 0; p < 5; p++) {
            const uint32_t src = sb + (p == 4 ? BO_H : BO_RING_MLP + (2 - (p & 1)) * 16384) + warp * 8192;
            bar_sync(NB_STAGED + (p == 4 ? 4 : 2 * (p & 1)) + warp, 160);
            PTS(50 + 2 * p + warp);
            fence_async();
            BULK_ADD("f16", acc + mt * 8192, src, len);
            mt = mt >= 8 ? mt - 8 : mt + 2;
            if (pairs && p < 4) { BULK_ADD("f16", acc + mt * 8192, src + 4096, len); mt = mt >= 8 ? mt - 8 : mt + 2; }
            COMMIT();
            PTS(64 + 50 + 2 * p + warp);
            if (p == 4 && !pairs) break;
            DRAINED(1);
            mbar_arrive_if(lane == 0 && p, bar + 8 * (p < 3 ? BB_SFREE + 2 * (p - 1) + warp : BB_ZFREE + (p >> 1)));
            mbar_arrive_if(lane == 0 && pairs && p == 2, bar + 8 * (BB_SFREE + warp));
            if (p == 3 && !pairs) { DRAINED(0); mbar_arrive_if(lane == 0, bar + 8 * (BB_ZFREE + 2)); }
          }
          WRITTEN();
          mbar_arrive_if(lane == 0, bar + 8 * (BB_SFREE + 4 + warp));
          announce(r);
        }
      }
    } else {
      if (op && warp == 2) {
        unsigned char* wt = g_wt + j * (10 * OP_SLOT);
#pragma unroll 1
        for (int m0 = 0; m0 < 10; m0 += 3) {
          const int nu = m0 < 9 ? 9 : 3;
          mbar_expect_if(lane == 0, bar + 8 * BB_TMP, nu * 4096);
#pragma unroll 1
          for (int k = 0; k < nu; k++) tma2d_e(sb + BO_RING_OP + k * 4096, &P.wmap[0], (m0 + k / 3) * 64, 320 * j + 224 + 32 * (k % 3), bar + 8 * BB_TMP);
          mbar_waitw(bar + 8 * BB_TMP, m0 & 1);
          bulk_s2g_e(wt + m0 * OP_SLOT, sb + BO_RING_OP, nu * 4096);
          COMMIT();
          WRITTEN();
        }
        asm volatile("fence.acq_rel.gpu;" ::: "memory");
        int sl = 0, ph = 1, mt = rot;
#pragma unroll 1
        for (int r = -1; r < NSTEP; r++) {
#pragma unroll 1
          for (int n = r < 0 ? 7 : 0; n < (r + 1 < NSTEP ? 10 : 7); n++) {
            mbar_waitw(bar + 8 * (BB_USED + sl), ph);
            mbar_expect_if(lane == 0, bar + 8 * (BB_FULL + sl), OP_SLOT);
            bulk_g2s_e(sb + BO_RING_OP + sl * OP_SLOT, wt + mt * OP_SLOT, OP_SLOT, bar + 8 * (BB_FULL + sl));
            if (++sl == 3) { sl = 0; ph ^= 1; }
            mt = mt == 9 ? 0 : mt + 1;
          }
        }
      } else if (op) {
        mbar_waitw(bar + 8 * BB_START, 0);
#pragma unroll 1
        for (int r = 0; r < NSTEP; r++) {
          const int rb = r - RD + 1;
          const uint32_t len = fmask(r) == 3 ? 8192 : 4096;
          const unsigned char* src = g_o + (uint32_t)(r % RO * (96 * 8192) + 5 * j * len);
          wait_flags(lane < 2 ? &g_f[F_O + (lane ? NOP : j)][r] : rb >= 0 ? &g_f[F_DONE][rb] : &g_f[F_MISC][0],
                     lane < 2 ? (lane ? 1 : 5) : rb >= 0 ? rtarget(bmask(rb)) : NBC * 8);
          PTS1(35);
          auto two = [&](int k, uint32_t mb) {
            bulk_g2s_e(sb + BO_O + k * 8192, src + k * len, len == 8192 ? 16384 : 4096, mb);
            if (len != 8192) bulk_g2s_e(sb + BO_O + k * 8192 + 8192, src + k * len + 4096, 4096, mb);
          };
          mbar_expect_if(lane == 0, bar + 8 * (BB_OFULL + 2 + (r & 1)), len);
          bulk_g2s_e(sb + BO_O + (r & 1 ? 5 : 2) * 8192, src + 2 * len, len, bar + 8 * (BB_OFULL + 2 + (r & 1)));
          if (r) bar_sync(NB_EARLY, 288);
          mbar_expect_if(lane < 2, bar + 8 * (BB_OFULL + lane), 2 * len + (lane ? len / 4 : 0));
          two(0, bar + 8 * BB_OFULL);
          PTS(62); PTS1(38);
          const unsigned char* sx = src + (95 - 5 * j) * len + (j + 1) / 5 * 1024;
          if (r) bar_sync(NB_LAST, 288);
          two(3, bar + 8 * (BB_OFULL + 1));
          bulk_g2s_e(sb + BO_CARRY, sx, 1024, bar + 8 * (BB_OFULL + 1));
          if (len == 8192) bulk_g2s_e(sb + BO_CARRY + 1024, sx + 4096, 1024, bar + 8 * (BB_OFULL + 1));
          if (r && r + 1 < NSTEP) {
            mbar_waitw(bar + 8 * (BB_USED + (10 * r - 2) % 3), (10 * r - 2) / 3 & 1);
            mbar_waitw(bar + 8 * (BB_USED + (10 * r - 1) % 3), (10 * r - 1) / 3 & 1);
          }
          PTS1(64 + 35);
          BTS(r, 0);
        }
      } else if (warp == 2) {
#pragma unroll 1
        for (int r = 0; r < NR; r++) {
          const int mk = w12 ? fmask(r) : bmask(r);
          if (mk) {
            const unsigned char* src = &g_acc[w12 ? 3 : 2][r % RD][mk == 2 ? 4096 : 0];
            wait_flags(&g_f[w12 ? F_Z : F_R2 + (j & 3)][r], w12 ? rtarget(mk) : NOP * NW12 * NW34);
#pragma unroll 1
            for (int z = 0; z < 5; z++) {
              const int k = mk == 3 ? z : z >> 1;
              const uint32_t fb = bar + 8 * (BB_FULL + z), dst = sb + BO_RING_MLP + 2 * k % 3 * 16384 + (mk == 3 ? 0 : (z & 1) * 4096);
              if (mk == 3 || !(z & 1)) mbar_waitw(bar + 8 * (k < 3 ? BB_ZFREE + k : BB_EMPTY + k - 3), (r + (k < 3)) & 1);
              if (z == 0) PTS(62);
              mbar_expect_if(lane == 0, fb, mk == 3 ? 16384 : 8192);
              bulk_g2s_e(dst, src + z * 16384, mk == 3 ? 16384 : 4096, fb);
              if (mk != 3) bulk_g2s_e(dst + 8192, src + z * 16384 + 8192, 4096, fb);
              if (z == 0) BTS(r, 0);
            }
          }
          if (!w12) {
#pragma unroll 1
            for (int z = mk == 3 ? 2 : 0; z < 5; z++) mbar_waitw(bar + 8 * (BB_FULL + z), r & 1);
            red_if(lane == 0, &g_f[F_GOT][r]);
#pragma unroll 1
            for (int c = j; c < 80; c += NW34) bulk_s2g_e(&g_acc[c / 40][r % RD][c % 40 * 2048], sb + BO_CARRY, 2048);
            COMMIT();
            wait_flags(&g_f[F_GOT][r], NW34);
            mbar_arrive_if(lane == 0, bar + 8 * BB_GO);
            WRITTEN();
          }
          mbar_waitw(bar + 8 * BB_DONE, (r + 1) & 1);
          mbar_arrive_if(lane == 0, bar + 8 * BB_DONE);
        }
      } else {
#pragma unroll 1
        for (int r = 0; r < (w12 ? NSTEP : NR); r++) {
          const bool idle = !((w12 ? fmask(r) : bmask(r)) >> (lane >> 4) & 1);
          uint32_t t0, t1;
          int n = 0;
          mbar_waitw(bar + 8 * BB_FULL, r & 1);
          do {
            asm volatile("ld.relaxed.gpu.global.v2.u32 {%0,%1}, [%2];" : "=r"(t0), "=r"(t1) : "l"(&g_st2[!w12][r % RD][2 * lane]) : "memory");
            if (++n > SPIN_LIMIT) FAIL();
          } while (!__all_sync(~0u, idle || (((t0 ^ (r + 1)) | (t1 ^ (r + 1))) & 127) == 0));
          sts64(sb + BO_STAT + (lane >> 4) * 128 + (lane & 3) * 32 + ((lane >> 2) & 3) * 8, t0, t1);
          __syncwarp();
          mbar_arrive_if(lane == 0, bar + 8 * BB_STAT);
          PTS(63);
        }
      }
    }
    bar_arrive(NB_END, 512);
  } else if (wg == 2) {
    asm volatile("setmaxnreg.dec.sync.aligned.u32 40;");
    const int ord = uni(lds32(sb + BO_BOX + 4));
    const int g2 = warp * 12 + ord - 24, gw = ord < 16 ? warp * 16 + ord : ord < 24 ? 80 + warp * 8 + ord : g2 < 32 ? 64 + g2 : 96 + g2;
    const int row = gw < 64 ? gw : gw < 96 ? gw - 64 : gw < 128 ? 2 * gw - 192 : 2 * gw - 224;
    if (row >= 32) {
#pragma unroll 1
      for (int t = 4 * NBC + (gw < 64 ? gw - 32 : gw - 80); t < S_LEN; t += 64) ln0(t);
    }
    if (gw < 64) rloop<0>(row, gw & 3, role, P.x, P.out);
    else if (gw < 96) rloop<2>(row, gw & 3, role, P.x, P.out);
    else if (gw < 128) rloop<1>(row, gw & 3, role, P.x, P.out);
    else rloop<4>(row, gw & 3, role, P.x, P.out);
    asm volatile("griddepcontrol.wait;" ::: "memory");
    const int t = threadIdx.x & 127;
    for (int i = (blockIdx.x * 128 + t) * 4; i < 4 * NCL * 2560; i += NBC * 512)
      *reinterpret_cast<uint4*>(&g_part[0][0][0][0] + i) = make_uint4(0u, 0u, 0u, 0u);
    bar_sync(NB_END, 512);
    if (t == 0) {
      uint32_t n;
      asm volatile("atom.acq_rel.gpu.global.add.u32 %0, [%1], 1;" : "=r"(n) : "l"(&g_f[F_MISC][64]) : "memory");
      sts32(sb + BO_BOX, n);
    }
    bar_sync(NB_END2, 128);
    if (lds32(sb + BO_BOX) == NBC - 1) {
      for (int i = t; i < F_NUM * 24; i += 128) reinterpret_cast<uint4*>(&g_f[0][0])[i] = make_uint4(0u, 0u, 0u, 0u);
      g_xready[t][0] = 0; g_tpc[t] = 0;
    }
  } else {
    asm volatile("setmaxnreg.inc.sync.aligned.u32 224;");
    LANE_INIT();
    for (int i = blockIdx.x * 256 + threadIdx.x; i < 2 * RD * TILE_B / 16; i += NBC * 256) reinterpret_cast<uint4*>(&g_acc[0][0][0])[i] = make_uint4(0u, 0u, 0u, 0u);
    warp_signal(&g_f[F_MISC][0], lane);
    const int mt0 = (rot + wg) % 10;
    auto boxes = [&](int ss) {
      const int nb = op && ss ? 3 : 4;
      const uint32_t base = sb + (ss ? BO_RES + wg * OP_RES : wg * 83968);
      mbar_expect_if(warp == 0 && lane == 0, bar + 8 * (BB_W + wg), nb * 20480 + (op ? 2048 : 0));
      bar_sync(NB_H, 256);
      if (warp < nb) {
#pragma unroll 1
        for (int i = warp; i < 5 * nb; i += nb) {
          const int p = op ? i / nb : (i - 10) >> 1, mt = (mt0 + 2 * p) % 10;
          const bool first = !op && i < 10;
          tma2d_e(op || !ss ? base + i * 4096 : sb + (first ? BO_W1 : -81920) + (2 * i + wg) * 4096, &P.wmap[op ? 0 : (w12 ? 1 : 3) + !first], first ? 128 * j + 64 * wg : mt * 64,
                  op ? 320 * j + 64 * warp + 32 * ss : first ? 64 * i + 32 * ss : 128 * j + 32 * (i & 1) + 64 * ss, bar + 8 * (BB_W + wg));
        }
      }
      if (op && warp == 3) tma2d_e(base + nb * 20480, &P.wo16, (mt0 + 2 * ss) % 10 * 64, 95 * 64 + (j + 1) / 5 * 16, bar + 8 * (BB_W + wg));
      mbar_waitw(bar + 8 * (BB_W + wg), ss);
    };
    if (W_DELAY && !op) __nanosleep(W_DELAY);
    uint32_t W[164];
    boxes(0);
    load_w<41>(W, sb + wg * 83968, warp, lane);
    fence_async();
    boxes(1);
    if (!op) {
      float cs[2] = {0.f, 0.f};
      const uint32_t a0 = sb + BO_W1 + wg * 4096 + ((lane >> 4) * 8 + (lane & 7)) * 128 + (((warp * 2 + ((lane >> 3) & 1)) ^ (lane & 7)) << 4);
#pragma unroll
      for (int i = 0; i < 80; i++) cs[i & 1] += bf_lo(W[i]) + bf_hi(W[i]);
#pragma unroll 1
      for (int i = 0; i < 60; i++) {
        uint32_t t[4];
        const uint32_t ad = a0 + (i % 20 >> 1) * 8192 + (i & 1) * 2048 - (i >= 40 ? BO_W1 : 0);
        ldsm4t(t[0], t[1], t[2], t[3], ad);
#pragma unroll
        for (int k = 0; k < 4; k++) {
          if (i < 20) cs[k & 1] += bf_lo(t[k]) + bf_hi(t[k]);
          const float mu = i < 40 ? cs[k & 1] : 0.f;
          t[k] = pack2h(bf_lo(t[k]) - mu, bf_hi(t[k]) - mu);
        }
        if (i >= 20) stsm4t(ad, t[0], t[1], t[2], t[3]);
        if (i == 19) {
#pragma unroll
          for (int k = 0; k < 2; k++) { cs[k] += __shfl_xor_sync(~0u, cs[k], 1); cs[k] += __shfl_xor_sync(~0u, cs[k], 2); cs[k] *= 1.f / DM; }
        }
      }
      const uint32_t z = dep0(__float_as_uint(cs[0]), lane);
#pragma unroll
      for (int i = 0; i < 80; i++) { W[i] = pack2h(bf_lo(W[i] | z) - cs[i & 1], bf_hi(W[i] | z) - cs[i & 1]); W[80 + i] = pack2h(bf_lo(W[80 + i]), bf_hi(W[80 + i])); }
      fence_async();
      bar_sync(NB_H, 256);
    }
    if (warp == 0) BTS(94, 6 + wg);
    const Dsc blo = {P.desc, 1}, alo = blo + wg * (op ? OP_RES / 16 : 256);
    if (op) {
      Ring rg = {(uint32_t)wg, 0};
      mbar_arrive_if(lane == 0, bar + 8 * BB_START);
      if (wg) bar_arrive(NB_PP, 256);
      const Dsc xlo = {P.desc32, 1};
#pragma unroll 1
      for (int r = 0; r < NSTEP; r++) {
        asm volatile("" : "+r"(lane));
        if (fmask(r) == 3) op_round<64>(W, bar, alo, blo, xlo, j == 0, rg, wg, warp, lane, r);
        else op_round<32>(W, bar, alo, blo, xlo, j == 0, rg, wg, warp, lane, r);
        if (warp == 0) BTS(r, 2 + wg);
      }
    } else {
      const int q4 = (128 * j + 64 * wg + 16 * warp) / 160, off = w12 ? (0x0413 >> (4 * q4)) & 7 : 0;
#pragma unroll 1
      for (int r = 0; r < NR; r++) {
        asm volatile("" : "+r"(lane));
        const int bm = bmask(r), fm = w12 ? fmask(r) : bm;
        if (fm == 3) phase1<64>(W, sb, alo, blo, 0, wg, warp, lane, off, r);
        else if (fm) phase1<32>(W, sb, alo, blo, fm >> 1, wg, warp, lane, off, r);
        else { mbar_waitu(bar + 8 * (BB_SFREE + 4 + wg), (r + 1) & 1); carry_in(sb, wg, warp, lane); }
        CTS(33);
        fence_async();
        bar_sync(NB_H, 256);
        mbar_arrive_if(wg == 1 && warp == 0 && lane < 2, bar + 8 * BB_ZFREE);
        if (wg + warp == 0) BTS(r, 1);
        if (bm == 3) phase2<64>(W, bar, alo, blo, wg, warp, lane, r);
        else phase2<32>(W, bar, alo, blo + (bm >> 1) * 256, wg, warp, lane, r);
        if (warp == 0) BTS(r, 2 + wg);
      }
    }
    CTS_OUT();
    bar_arrive(NB_END, 512);
  }
}

typedef CUresult (*EncodeFn)(CUtensorMap*, CUtensorMapDataType, cuuint32_t, void*, const cuuint64_t*, const cuuint64_t*, const cuuint32_t*,
                             const cuuint32_t*, CUtensorMapInterleave, CUtensorMapSwizzle, CUtensorMapL2promotion, CUtensorMapFloatOOBfill);
static void make_map(EncodeFn fn, CUtensorMap* tm, const void* ptr, uint64_t cols, uint64_t rows, uint32_t bc, uint32_t br) {
  cuuint64_t dims[2] = {cols, rows}; cuuint64_t strides[1] = {cols * 2}; cuuint32_t box[2] = {bc, br}; cuuint32_t es[2] = {1, 1};
  fn(tm, CU_TENSOR_MAP_DATA_TYPE_BFLOAT16, 2, const_cast<void*>(ptr), dims, strides, box, es, CU_TENSOR_MAP_INTERLEAVE_NONE,
     CU_TENSOR_MAP_SWIZZLE_128B, CU_TENSOR_MAP_L2_PROMOTION_L2_256B, CU_TENSOR_MAP_FLOAT_OOB_FILL_NONE);
}
#define dbg_a_only 0
extern "C" void kernel_launch(void* const* d_in, const int* in_sizes, int n_in, void* d_out, int out_size) {
  void* fnp = nullptr; cudaDriverEntryPointQueryResult qr;
  cudaGetDriverEntryPoint("cuTensorMapEncodeTiled", &fnp, cudaEnableDefault, &qr);
  EncodeFn fn = (EncodeFn)fnp;
  cudaStream_t st = cudaStreamPerThread;
  cudaFuncSetAttribute(bworker_kernel, cudaFuncAttributeMaxDynamicSharedMemorySize, B_SMEM);
  {
    AMaps M;
    for (int i = 0; i < 3; i++) make_map(fn, &M.w16[i], d_in[2 + i], HD, DM, 64, 16);
    M.wv = (const __nv_bfloat16*)d_in[4];
    make_map(fn, &M.wo32, d_in[5], DM, HD, 64, 32);
    const uint32_t hi[5] = {dhi(TILE_SBO, 3), dhi(1024, 1), dhi(1024, 0), dhi(PL_SZ, 0), dhi(896, 0)};
    for (int i = 0; i < 5; i++) M.d[i] = (uint64_t)hi[i] << 32;
    cudaFuncSetAttribute(acore_kernel, cudaFuncAttributeMaxDynamicSharedMemorySize, A_SMEM);
    cudaFuncSetAttribute(acore_kernel, cudaFuncAttributeNonPortableClusterSizeAllowed, 1);
    cudaLaunchConfig_t cfg = {};
    cfg.gridDim = dim3(CL_SIZE * NCL); cfg.blockDim = dim3(512); cfg.dynamicSmemBytes = A_SMEM; cfg.stream = st;
    cudaLaunchAttribute at[1]; at[0].id = cudaLaunchAttributeClusterDimension;
    at[0].val.clusterDim.x = CL_SIZE; at[0].val.clusterDim.y = 1; at[0].val.clusterDim.z = 1;
    cfg.attrs = at; cfg.numAttrs = 1;
    cudaLaunchKernelEx(&cfg, acore_kernel, M, (const __nv_bfloat16*)d_in[1], dbg_a_only ? 0 : 1);
  }
  if (!dbg_a_only) {
    BParams P;
    make_map(fn, &P.wmap[0], d_in[5], DM, HD, 64, 32);
    make_map(fn, &P.wo16, d_in[5], DM, HD, 64, 16);
    make_map(fn, &P.wmap[1], d_in[8], DM, DM, 64, 32);
    make_map(fn, &P.wmap[2], d_in[9], DM, DM, 64, 32);
    make_map(fn, &P.wmap[3], d_in[10], FF, DM, 64, 32);
    make_map(fn, &P.wmap[4], d_in[11], DM, FF, 64, 32);
    P.x = (const __nv_bfloat16*)d_in[0];
    P.out = (__nv_bfloat16*)d_out;
    P.desc = (uint64_t)dhi(1024, 1) << 32;
    P.desc32 = (uint64_t)dhi(256, 3) << 32;
    cudaLaunchConfig_t cfg = {};
    cfg.gridDim = dim3(NBC); cfg.blockDim = dim3(512); cfg.dynamicSmemBytes = B_SMEM; cfg.stream = st;
    cudaLaunchAttribute at[1]; at[0].id = cudaLaunchAttributeProgrammaticStreamSerialization; at[0].val.programmaticStreamSerializationAllowed = 1;
    cfg.attrs = at; cfg.numAttrs = 1;
    cudaLaunchKernelEx(&cfg, bworker_kernel, P);
  }
}
```

```cpp
#include <cuda_runtime.h>
#include <cuda_bf16.h>
#include <cuda.h>
#include <stdint.h>

#define S_LEN 2048
#define DM 640
#define NH 32
#define DH 192
#define HD 6144
#define NSEG 64
#define FF 1536

__device__ __forceinline__ uint32_t smem_u32(const void* p) { return (uint32_t)__cvta_generic_to_shared(p); }
__device__ __forceinline__ uint32_t mapa(uint32_t a, uint32_t r) {
  uint32_t o; asm volatile("mapa.shared::cluster.u32 %0, %1, %2;" : "=r"(o) : "r"(a), "r"(r)); return o; }
__device__ __forceinline__ void mbar_init(uint32_t b, uint32_t c) {
  asm volatile("mbarrier.init.shared::cta.b64 [%0], %1;" :: "r"(b), "r"(c) : "memory"); }
__device__ __forceinline__ void mbar_expect(uint32_t b, uint32_t tx) {
  asm volatile("mbarrier.arrive.expect_tx.shared::cta.b64 _, [%0], %1;" :: "r"(b), "r"(tx) : "memory"); }
__device__ __forceinline__ void mbar_arrive(uint32_t b) {
  asm volatile("mbarrier.arrive.shared::cta.b64 _, [%0];" :: "r"(b) : "memory"); }
__device__ __forceinline__ void mbar_arrive_remote(uint32_t rb) {
  asm volatile("mbarrier.arrive.relaxed.cluster.shared::cluster.b64 _, [%0];" :: "r"(rb) : "memory"); }
__device__ __forceinline__ void mbar_expect_if(bool p, uint32_t b, uint32_t tx) {
  asm volatile("{\n.reg .pred q;\nsetp.ne.u32 q, %2, 0;\n@q mbarrier.arrive.expect_tx.shared::cta.b64 _, [%0], %1;\n}" :: "r"(b), "r"(tx), "r"((uint32_t)p) : "memory"); }
__device__ __forceinline__ void mbar_arrive_if(bool p, uint32_t b) {
  asm volatile("{\n.reg .pred q;\nsetp.ne.u32 q, %1, 0;\n@q mbarrier.arrive.shared::cta.b64 _, [%0];\n}" :: "r"(b), "r"((uint32_t)p) : "memory"); }
__device__ __forceinline__ void mbar_arrive_remote_if(bool p, uint32_t rb) {
  asm volatile("{\n.reg .pred q;\nsetp.ne.u32 q, %1, 0;\n@q mbarrier.arrive.relaxed.cluster.shared::cluster.b64 _, [%0];\n}" :: "r"(rb), "r"((uint32_t)p) : "memory"); }
__device__ __forceinline__ void sts32_if(bool p, uint32_t a, uint32_t v) {
  asm volatile("{\n.reg .pred q;\nsetp.ne.u32 q, %2, 0;\n@q st.shared.b32 [%0], %1;\n}" :: "r"(a), "r"(v), "r"((uint32_t)p) : "memory"); }
__device__ __forceinline__ void sts128z_if(bool p, uint32_t a) {
  asm volatile("{\n.reg .pred q;\nsetp.ne.u32 q, %1, 0;\n@q st.shared.v4.b32 [%0], {0,0,0,0};\n}" :: "r"(a), "r"((uint32_t)p) : "memory"); }
__device__ __forceinline__ bool mbar_try(uint32_t b, uint32_t ph) {
  uint32_t ok;
  asm volatile("{\n.reg .pred p;\nmbarrier.try_wait.parity.shared::cta.b64 p, [%1], %2;\nselp.u32 %0, 1, 0, p;\n}"
               : "=r"(ok) : "r"(b), "r"(ph) : "memory");
  return ok; }
__device__ __forceinline__ bool mbar_test(uint32_t b, uint32_t ph) {
  uint32_t ok;
  asm volatile("{\n.reg .pred p;\nmbarrier.test_wait.parity.shared::cta.b64 p, [%1], %2;\nselp.u32 %0, 1, 0, p;\n}"
               : "=r"(ok) : "r"(b), "r"(ph) : "memory");
  return ok; }
#define SPIN_LIMIT 4000000
#define FAIL() asm volatile("st.global.u32 [%0], 0;" :: "l"(8ull) : "memory")
#define CFENCE() asm volatile("fence.proxy.async::generic.acquire.sync_restrict::shared::cluster.cluster;" ::: "memory")
__device__ __forceinline__ void mbar_wait(uint32_t b, uint32_t ph) {
  int n = 0;
  while (!mbar_try(b, ph)) { if (++n > SPIN_LIMIT) FAIL(); } }
#define TIMEOUT_ACT "@!p st.shared.u32 [%0+1], 0;"
#define WAIT_HINT ", 20000"
#define WAIT_LIM "200000"
__device__ __forceinline__ void mbar_slow(uint32_t b, uint32_t ph) {
  asm volatile("{\n.reg .pred p, q;\n.reg .u32 n;\nmov.u32 n, 0;\n"
               "WL:\nmbarrier.try_wait.parity.shared::cta.b64 p, [%0], %1" WAIT_HINT ";\nadd.u32 n, n, 1;\nsetp.lt.and.u32 q, n, " WAIT_LIM ", !p;\n@q bra.uni WL;\n"
               TIMEOUT_ACT "\n}" :: "r"(b), "r"(ph) : "memory"); }
__device__ __forceinline__ void mbar_waitw(uint32_t b, uint32_t ph) {
  asm volatile("{\n.reg .pred p, q;\n.reg .u32 n;\nmbarrier.try_wait.parity.shared::cta.b64 p, [%0], %1;\n@p bra.uni WD;\nmov.u32 n, 0;\n"
               "WL:\nmbarrier.try_wait.parity.shared::cta.b64 p, [%0], %1" WAIT_HINT ";\nadd.u32 n, n, 1;\nsetp.lt.and.u32 q, n, " WAIT_LIM ", !p;\n@q bra.uni WL;\n"
               TIMEOUT_ACT "\nWD:\n}" :: "r"(b), "r"(ph) : "memory"); }
__device__ __forceinline__ void mbar_waitw2(uint32_t b0, uint32_t b1, uint32_t ph) {
  uint32_t ok;
  asm volatile("{\n.reg .pred p, r;\nmbarrier.try_wait.parity.shared::cta.b64 p, [%1], %3;\nmbarrier.try_wait.parity.shared::cta.b64 r, [%2], %3;\n"
               "and.pred p, p, r;\nselp.u32 %0, 1, 0, p;\n}" : "=r"(ok) : "r"(b0), "r"(b1), "r"(ph) : "memory");
  if (__builtin_expect(!__all_sync(~0u, ok), 0)) { mbar_slow(b0, ph); mbar_slow(b1, ph); }
}
__device__ __forceinline__ void mbar_waitu(uint32_t b, uint32_t ph) {
  asm volatile("{\n.reg .pred p;\nmbarrier.try_wait.parity.shared::cta.b64 p, [%0], %1;\n@p bra.uni WD;\n"
               "WL:\nmbarrier.try_wait.parity.shared::cta.b64 p, [%0], %1" WAIT_HINT ";\n@!p bra.uni WL;\nWD:\n}" :: "r"(b), "r"(ph) : "memory"); }
__device__ __forceinline__ void mbar_waitu2(uint32_t b0, uint32_t b1, uint32_t ph) {
  asm volatile("{\n.reg .pred p, r;\nWL:\nmbarrier.try_wait.parity.shared::cta.b64 p, [%0], %2;\nmbarrier.try_wait.parity.shared::cta.b64 r, [%1], %2;\n"
               "and.pred p, p, r;\n@!p bra.uni WL;\n}" :: "r"(b0), "r"(b1), "r"(ph) : "memory"); }
__device__ __forceinline__ void mbar_waitw4(uint32_t b, uint32_t ph) { mbar_waitw2(b, b + 8, ph); mbar_waitw2(b + 16, b + 24, ph); }
__device__ __forceinline__ uint32_t clock32() { uint32_t t; asm volatile("mov.u32 %0, %%clock;" : "=r"(t) :: "memory"); return t; }
template <int L> __device__ __forceinline__ uint32_t lop3(uint32_t a, uint32_t b, uint32_t c) {
  uint32_t r; asm("lop3.b32 %0, %1, %2, %3, %4;" : "=r"(r) : "r"(a), "r"(b), "r"(c), "n"(L)); return r; }
__device__ __forceinline__ void st_async_v2_if(bool p, uint32_t a, uint32_t v0, uint32_t v1, uint32_t mb) {
  asm volatile("{\n.reg .pred q;\nsetp.ne.u32 q, %4, 0;\n@q st.async.weak.shared::cluster.mbarrier::complete_tx::bytes.v2.b32 [%0], {%1,%2}, [%3];\n}"
               :: "r"(a), "r"(v0), "r"(v1), "r"(mb), "r"((uint32_t)p) : "memory"); }
__device__ __forceinline__ void keep4(const uint32_t* r, int lane) {
  asm volatile("{\n.reg .pred q;\nsetp.lt.s32 q, %4, 0;\n@q st.shared.v4.b32 [%4], {%0,%1,%2,%3};\n}" :: "r"(r[0]), "r"(r[1]), "r"(r[2]), "r"(r[3]), "r"(lane) : "memory"); }
__device__ __forceinline__ void fence_sched(int i) {
  asm volatile("{\n.reg .pred q;\nsetp.gt.s32 q, %0, 4096;\n@q st.shared.u32 [%0], 0;\n}" :: "r"(i) : "memory"); }
__device__ __forceinline__ uint32_t hmax2bf(uint32_t a, uint32_t b) { uint32_t r; asm("max.bf16x2 %0, %1, %2;" : "=r"(r) : "r"(a), "r"(b)); return r; }
__device__ __forceinline__ uint32_t uni(uint32_t x) { return __shfl_sync(~0u, x, 0); }
__device__ __forceinline__ void bulk_g2s_mc_e(uint32_t dst, const void* src, uint32_t bytes, uint32_t mb, uint16_t mask) {
  asm volatile("{\n.reg .pred e;\nelect.sync _|e, 0xffffffff;\n"
               "@e cp.async.bulk.shared::cluster.global.mbarrier::complete_tx::bytes.multicast::cluster [%0], [%1], %2, [%3], %4;\n}"
               :: "r"(dst), "l"(src), "r"(bytes), "r"(mb), "h"(mask) : "memory"); }
__device__ __forceinline__ void bulk_s2g_e(void* dst, uint32_t src, uint32_t bytes) {
  asm volatile("{\n.reg .pred e;\nelect.sync _|e, 0xffffffff;\n@e cp.async.bulk.global.shared::cta.bulk_group [%0], [%1], %2;\n}"
               :: "l"(dst), "r"(src), "r"(bytes) : "memory"); }
__device__ __forceinline__ void bulk_g2s_e(uint32_t dst, const void* src, uint32_t bytes, uint32_t mb) {
  asm volatile("{\n.reg .pred e;\nelect.sync _|e, 0xffffffff;\n@e cp.async.bulk.shared::cluster.global.mbarrier::complete_tx::bytes [%0], [%1], %2, [%3];\n}"
               :: "r"(dst), "l"(src), "r"(bytes), "r"(mb) : "memory"); }
#define STREAM_HINT 1
__device__ __forceinline__ void bulk_s2g_es(void* dst, uint32_t src, uint32_t bytes) {
  asm volatile("{\n.reg .pred e;\n.reg .b64 pol;\ncreatepolicy.fractional.L2::evict_first.b64 pol;\nelect.sync _|e, 0xffffffff;\n"
               "@e cp.async.bulk.global.shared::cta.bulk_group.L2::cache_hint [%0], [%1], %2, pol;\n}" :: "l"(dst), "r"(src), "r"(bytes) : "memory");
}
__device__ __forceinline__ void bulk_g2s_es(uint32_t dst, const void* src, uint32_t bytes, uint32_t mb) {
  asm volatile("{\n.reg .pred e;\n.reg .b64 pol;\ncreatepolicy.fractional.L2::evict_first.b64 pol;\nelect.sync _|e, 0xffffffff;\n"
               "@e cp.async.bulk.shared::cluster.global.mbarrier::complete_tx::bytes.L2::cache_hint [%0], [%1], %2, [%3], pol;\n}"
               :: "r"(dst), "l"(src), "r"(bytes), "r"(mb) : "memory"); }
__device__ __forceinline__ void tma2d_e(uint32_t dst, const CUtensorMap* tm, int c0, int c1, uint32_t mb) {
  asm volatile("{\n.reg .pred e;\nelect.sync _|e, 0xffffffff;\n"
               "@e cp.async.bulk.tensor.2d.shared::cluster.global.mbarrier::complete_tx::bytes [%0], [%1, {%3, %4}], [%2];\n}"
               :: "r"(dst), "l"((uint64_t)tm), "r"(mb), "r"(c0), "r"(c1) : "memory"); }
__device__ __forceinline__ uint32_t hadd2bf(uint32_t a, uint32_t b) {
  uint32_t r; asm("add.rn.bf16x2 %0, %1, %2;" : "=r"(r) : "r"(a), "r"(b)); return r; }
__device__ __forceinline__ void cluster_sync_all() {
  asm volatile("barrier.cluster.arrive.release.aligned;\nbarrier.cluster.wait.acquire.aligned;" ::: "memory"); }
__device__ __forceinline__ void bar_arrive(int id, int n) { asm volatile("bar.arrive %0, %1;" :: "r"(id), "r"(n) : "memory"); }
__device__ __forceinline__ void bar_arrive_dep(int id, int n, uint32_t dep) {
  asm volatile("{\n.reg .u32 t;\nand.b32 t, %2, 0;\nadd.u32 t, t, %0;\nbar.sync t, %1;\n}" :: "r"(id), "r"(n), "r"(dep) : "memory"); }
__device__ __forceinline__ void bar_sync(int id, int n) { asm volatile("bar.sync %0, %1;" :: "r"(id), "r"(n) : "memory"); }
__device__ __forceinline__ void fence_async() { asm volatile("fence.proxy.async.shared::cta;" ::: "memory"); }
__device__ __forceinline__ void st_async_b32(uint32_t a, uint32_t v, uint32_t mb) {
  asm volatile("st.async.weak.shared::cluster.mbarrier::complete_tx::bytes.b32 [%0], %1, [%2];" :: "r"(a), "r"(v), "r"(mb) : "memory"); }
__device__ __forceinline__ void st_async_v2(uint32_t a, uint32_t v0, uint32_t v1, uint32_t mb) {
  asm volatile("st.async.weak.shared::cluster.mbarrier::complete_tx::bytes.v2.b32 [%0], {%1,%2}, [%3];" :: "r"(a), "r"(v0), "r"(v1), "r"(mb) : "memory"); }
__device__ __forceinline__ void st_async_v4(uint32_t a, uint32_t v0, uint32_t v1, uint32_t v2, uint32_t v3, uint32_t mb) {
  asm volatile("st.async.weak.shared::cluster.mbarrier::complete_tx::bytes.v4.b32 [%0], {%1,%2,%3,%4}, [%5];" :: "r"(a), "r"(v0), "r"(v1), "r"(v2), "r"(v3), "r"(mb) : "memory"); }
__device__ __forceinline__ void ldsm4(uint32_t& r0, uint32_t& r1, uint32_t& r2, uint32_t& r3, uint32_t a) {
  asm volatile("ldmatrix.sync.aligned.m8n8.x4.shared.b16 {%0,%1,%2,%3}, [%4];" : "=r"(r0), "=r"(r1), "=r"(r2), "=r"(r3) : "r"(a) : "memory"); }
__device__ __forceinline__ void ldsm4t(uint32_t& r0, uint32_t& r1, uint32_t& r2, uint32_t& r3, uint32_t a) {
  asm volatile("ldmatrix.sync.aligned.m8n8.x4.trans.shared.b16 {%0,%1,%2,%3}, [%4];" : "=r"(r0), "=r"(r1), "=r"(r2), "=r"(r3) : "r"(a) : "memory"); }
__device__ __forceinline__ void stsm2t(uint32_t a, uint32_t r0, uint32_t r1) {
  asm volatile("stmatrix.sync.aligned.m8n8.x2.trans.shared.b16 [%0], {%1,%2};" :: "r"(a), "r"(r0), "r"(r1) : "memory"); }
__device__ __forceinline__ void stsm4t(uint32_t a, uint32_t r0, uint32_t r1, uint32_t r2, uint32_t r3) {
  asm volatile("stmatrix.sync.aligned.m8n8.x4.trans.shared.b16 [%0], {%1,%2,%3,%4};" :: "r"(a), "r"(r0), "r"(r1), "r"(r2), "r"(r3) : "memory"); }
__device__ __forceinline__ uint32_t movm(uint32_t a) {
  uint32_t d; asm volatile("movmatrix.sync.aligned.m8n8.trans.b16 %0, %1;" : "=r"(d) : "r"(a)); return d; }
__device__ __forceinline__ void mma16816(float* d, uint32_t a0, uint32_t a1, uint32_t a2, uint32_t a3, uint32_t b0, uint32_t b1) {
  asm("mma.sync.aligned.m16n8k16.row.col.f32.bf16.bf16.f32 {%0,%1,%2,%3}, {%4,%5,%6,%7}, {%8,%9}, {%0,%1,%2,%3};"
               : "+f"(d[0]), "+f"(d[1]), "+f"(d[2]), "+f"(d[3]) : "r"(a0), "r"(a1), "r"(a2), "r"(a3), "r"(b0), "r"(b1)); }
__device__ __forceinline__ void mma16816v(float* d, uint32_t a0, uint32_t a1, uint32_t a2, uint32_t a3, uint32_t b0, uint32_t b1) {
  asm volatile("mma.sync.aligned.m16n8k16.row.col.f32.bf16.bf16.f32 {%0,%1,%2,%3}, {%4,%5,%6,%7}, {%8,%9}, {%0,%1,%2,%3};"
               : "+f"(d[0]), "+f"(d[1]), "+f"(d[2]), "+f"(d[3]) : "r"(a0), "r"(a1), "r"(a2), "r"(a3), "r"(b0), "r"(b1)); }
__device__ __forceinline__ uint32_t pack2(float lo, float hi) {
  uint32_t r; asm("cvt.rn.bf16x2.f32 %0, %1, %2;" : "=r"(r) : "f"(hi), "f"(lo)); return r; }
__device__ __forceinline__ uint32_t pack2v(float lo, float hi) {
  uint32_t r; asm volatile("cvt.rn.bf16x2.f32 %0, %1, %2;" : "=r"(r) : "f"(hi), "f"(lo)); return r; }
__device__ __forceinline__ float bf_lo(uint32_t w) { return __uint_as_float(w << 16); }
__device__ __forceinline__ float bf_hi(uint32_t w) { return __uint_as_float(w & 0xffff0000u); }
__device__ __forceinline__ uint4 lds128(uint32_t a) {
  uint4 v; asm volatile("ld.shared.v4.b32 {%0,%1,%2,%3}, [%4];" : "=r"(v.x), "=r"(v.y), "=r"(v.z), "=r"(v.w) : "r"(a) : "memory"); return v; }
__device__ __forceinline__ uint4 lds128_nv(uint32_t a) {
  uint4 v; asm volatile("ld.shared.v4.b32 {%0,%1,%2,%3}, [%4];" : "=r"(v.x), "=r"(v.y), "=r"(v.z), "=r"(v.w) : "r"(a)); return v; }
__device__ __forceinline__ void st_async_v2_nm(uint32_t a, uint32_t v0, uint32_t v1, uint32_t mb) {
  asm volatile("st.async.weak.shared::cluster.mbarrier::complete_tx::bytes.v2.b32 [%0], {%1,%2}, [%3];" :: "r"(a), "r"(v0), "r"(v1), "r"(mb)); }
__device__ __forceinline__ float rcpf(float x) { float y; asm("rcp.approx.ftz.f32 %0, %1;" : "=f"(y) : "f"(x)); return y; }
__device__ __forceinline__ void sts64(uint32_t a, uint32_t x, uint32_t y) { asm volatile("st.shared.v2.b32 [%0], {%1,%2};" :: "r"(a), "r"(x), "r"(y) : "memory"); }
__device__ __forceinline__ float ex2(float x) { float y; asm("ex2.approx.ftz.f32 %0, %1;" : "=f"(y) : "f"(x)); return y; }
__device__ __forceinline__ uint32_t lds32(uint32_t a) {
  uint32_t v; asm volatile("ld.shared.b32 %0, [%1];" : "=r"(v) : "r"(a) : "memory"); return v; }
__device__ __forceinline__ uint2 lds64(uint32_t a) {
  uint2 v; asm volatile("ld.shared.v2.b32 {%0,%1}, [%2];" : "=r"(v.x), "=r"(v.y) : "r"(a) : "memory"); return v; }
__device__ __forceinline__ void sts128(uint32_t a, uint32_t x, uint32_t y, uint32_t z, uint32_t w) {
  asm volatile("st.shared.v4.b32 [%0], {%1,%2,%3,%4};" :: "r"(a), "r"(x), "r"(y), "r"(z), "r"(w) : "memory"); }
__device__ __forceinline__ void sts32(uint32_t a, uint32_t x) { asm volatile("st.shared.b32 [%0], %1;" :: "r"(a), "r"(x) : "memory"); }
__device__ __forceinline__ void tma2d(uint32_t dst, const CUtensorMap* tm, int c0, int c1, uint32_t mb) {
  asm volatile("cp.async.bulk.tensor.2d.shared::cluster.global.mbarrier::complete_tx::bytes [%0], [%1, {%3, %4}], [%2];"
               :: "r"(dst), "l"((uint64_t)tm), "r"(mb), "r"(c0), "r"(c1) : "memory"); }
__device__ __forceinline__ void tma2d_prefetch(const CUtensorMap* tm, int c0, int c1) {
  asm volatile("cp.async.bulk.prefetch.tensor.2d.L2.global.tile [%0, {%1, %2}];" :: "l"((uint64_t)tm), "r"(c0), "r"(c1) : "memory"); }
__device__ __forceinline__ void bulk_g2s_mc(uint32_t dst, const void* src, uint32_t bytes, uint32_t mb, uint16_t mask) {
  asm volatile("cp.async.bulk.shared::cluster.global.mbarrier::complete_tx::bytes.multicast::cluster [%0], [%1], %2, [%3], %4;"
               :: "r"(dst), "l"(src), "r"(bytes), "r"(mb), "h"(mask) : "memory"); }
__device__ __forceinline__ void bulk_s2g(void* dst, uint32_t src, uint32_t bytes) {
  asm volatile("cp.async.bulk.global.shared::cta.bulk_group [%0], [%1], %2;" :: "l"(dst), "r"(src), "r"(bytes) : "memory"); }
__device__ __forceinline__ void wg_fence() { asm volatile("wgmma.fence.sync.aligned;" ::: "memory"); }
__device__ __forceinline__ void wg_commit() { asm volatile("wgmma.commit_group.sync.aligned;" ::: "memory"); }
template <int N> __device__ __forceinline__ void wg_wait() { asm volatile("wgmma.wait_group.sync.aligned %0;" :: "n"(N) : "memory"); }
__device__ __forceinline__ uint64_t mkdesc(uint32_t addr, uint32_t lbo, uint32_t sbo, uint32_t swz) {
  return (uint64_t)((addr & 0x3FFFF) >> 4) | ((uint64_t)(lbo >> 4) << 16) | ((uint64_t)(sbo >> 4) << 32) | ((uint64_t)swz << 62); }

#define ACC4(d) "+f"(d[0]),"+f"(d[1]),"+f"(d[2]),"+f"(d[3])
#define ACC8(d) ACC4(d), ACC4((d + 4))
#define ACC16(d) ACC8(d), ACC8((d + 8))
#define ACC20(d) ACC16(d), ACC4((d + 16))
#define ACC24(d) ACC16(d), ACC8((d + 16))
#define SMEM0 0x400
__host__ __device__ constexpr uint32_t dlo(uint32_t off, uint32_t lbo) { return ((SMEM0 + off) >> 4) | ((lbo >> 4) << 16); }
__host__ __device__ constexpr uint32_t dhi(uint32_t sbo, uint32_t swz) { return (sbo >> 4) | (swz << 30); }
#define R4S "{%0,%1,%2,%3}"
#define R8S "{%0,%1,%2,%3,%4,%5,%6,%7}"
#define R16S "{%0,%1,%2,%3,%4,%5,%6,%7,%8,%9,%10,%11,%12,%13,%14,%15}"
#define R20S "{%0,%1,%2,%3,%4,%5,%6,%7,%8,%9,%10,%11,%12,%13,%14,%15,%16,%17,%18,%19}"
#define R24S "{%0,%1,%2,%3,%4,%5,%6,%7,%8,%9,%10,%11,%12,%13,%14,%15,%16,%17,%18,%19,%20,%21,%22,%23}"
#define ACC32(d) ACC16(d), ACC16((d + 16))
#define R32S "{%0,%1,%2,%3,%4,%5,%6,%7,%8,%9,%10,%11,%12,%13,%14,%15,%16,%17,%18,%19,%20,%21,%22,%23,%24,%25,%26,%27,%28,%29,%30,%31}"
struct Dsc {
  uint64_t b; uint32_t e;
  __device__ __forceinline__ Dsc operator+(uint32_t o) const { return {b + o, e}; }
};
template <int K> __device__ __forceinline__ uint32_t fresh(int i) {
  uint32_t e; asm volatile("{\n.reg .u32 t;\nadd.u32 t, %1, %2;\nshr.u32 %0, t, %3;\n}" : "=r"(e) : "r"(i), "n"((256 << K) + 1), "n"(8 + K)); return e; }
template <int N, bool H = false> struct MM;
#define DEF_MM(N, H, T, ACCM, RS_, I0, I1, I2, I3, I4, I5, I6, I7)                                                                \
  template <> struct MM<N, H> {                                                                                                   \
    template <uint32_t BLO, int ACC>                                                                                              \
    static __device__ __forceinline__ void rs(float* d, const uint32_t* a, Dsc b0) {                                              \
      asm volatile("{\n.reg .b64 b;\nmad.wide.u32 b, %" #I7 ", %" #I5 ", %" #I4 ";\n"                                             \
                   "wgmma.mma_async.sync.aligned.m64n" #N "k16.f32." T "." T " " RS_ ", {%" #I0 ",%" #I1 ",%" #I2 ",%" #I3 "}, b, %" #I6 ", 1, 1, 0;\n}" \
                   : ACCM(d) : "r"(a[0]), "r"(a[1]), "r"(a[2]), "r"(a[3]), "l"(b0.b), "n"(BLO), "n"(ACC), "r"(b0.e)); }           \
    template <uint32_t ALO, uint32_t BLO, int ACC, int TA = 1>                                                                    \
    static __device__ __forceinline__ void ss(float* d, Dsc a0, Dsc b0) {                                                         \
      asm volatile("{\n.reg .b64 a, b;\nmad.wide.u32 a, %" #I6 ", %" #I1 ", %" #I0 ";\nmad.wide.u32 b, %" #I6 ", %" #I3 ", %" #I2 ";\n" \
                   "wgmma.mma_async.sync.aligned.m64n" #N "k16.f32." T "." T " " RS_ ", a, b, %" #I4 ", 1, 1, %" #I5 ", 0;\n}"    \
                   : ACCM(d) : "l"(a0.b), "n"(ALO), "l"(b0.b), "n"(BLO), "n"(ACC), "n"(TA), "r"(b0.e)); }                         \
  };
DEF_MM(8, false, "bf16", ACC4, R4S, 4, 5, 6, 7, 8, 9, 10, 11)
DEF_MM(16, false, "bf16", ACC8, R8S, 8, 9, 10, 11, 12, 13, 14, 15)
DEF_MM(32, false, "bf16", ACC16, R16S, 16, 17, 18, 19, 20, 21, 22, 23)
DEF_MM(40, false, "bf16", ACC20, R20S, 20, 21, 22, 23, 24, 25, 26, 27)
DEF_MM(48, false, "bf16", ACC24, R24S, 24, 25, 26, 27, 28, 29, 30, 31)
DEF_MM(64, false, "bf16", ACC32, R32S, 32, 33, 34, 35, 36, 37, 38, 39)
DEF_MM(32, true, "f16", ACC16, R16S, 16, 17, 18, 19, 20, 21, 22, 23)
DEF_MM(64, true, "f16", ACC32, R32S, 32, 33, 34, 35, 36, 37, 38, 39)

#define LAG 10
#define NSTEP (NSEG + LAG)
#define NR (NSTEP + 1)
__device__ __align__(1024) __nv_bfloat16 g_xn[2][S_LEN * DM];
#define RO 16
static_assert(RO > LAG + 1, "ring");
__device__ __align__(1024) unsigned char g_o[RO * 96 * 8192];
__device__ __align__(1024) uint32_t g_part[6][7][40][64];
#define RD 16
static_assert(2 * RD <= NSEG && NR < 96, "the tags of the last lap differ from those of the first");
#define TILE_B 81920
__device__ __align__(1024) float2 g_stat[S_LEN];
__device__ __align__(1024) uint32_t g_st2[2][RD][64];
__device__ __align__(1024) unsigned char g_acc[4][RD][TILE_B];
#define NOP 19
#define NW12 5
#define NW34 12
#define NBC (NOP + NW12 + NW34)
__device__ __align__(1024) unsigned char g_wt[NOP * 10 * 12288];
enum { F_O = 0, F_R1 = NOP + 1, F_R2 = F_R1 + 4, F_R3 = F_R2 + 4, F_Z = F_R3 + 4, F_DONE, F_GOT, F_MISC, F_NUM };
__device__ __align__(128) uint32_t g_f[F_NUM][96];
__device__ __align__(128) int g_xready[129][8];
__device__ uint32_t g_tpc[128];
#define TS(i)
#define TSV(i, v)
#define TSN(i)
#define TSD(i, dep)
#define BTS(k, i)
#define BTS2(k, i)
#define RTS(i)
#define RTSD(i, dep)
#define RTS_OUT()
#define CTS(i)
#define PTS(i)
#define PTS1(i)
#define CTS_OUT()
#define GTS(i)

#define CL_SIZE 15
#define NCL 7
#define SSQ 13
#define SSV 16
#define PL_SZ 5376
#define TILE_SBO 2560
#define TILE_GRP 15360
#define WS_SZ ((2 * SSQ + SSV) * 2048)
#define OFF_QK (OFF_WO + 26 * 2048)
#define LAYOUT 2
#define OFF_TILE 0
#define OFF_WS (4 * TILE_GRP)
#define OFF_WO (OFF_WS + WS_SZ)
#define OFF_PL (OFF_QK + 20480)
#define OFF_BAR (OFF_PL + 2 * PL_SZ)
#define STG_Q OFF_TILE
#define STG_K OFF_WO
#define VA 14
#define STG_V2 (OFF_TILE + 27 * 2048)
#define OFF_O (OFF_PL + 4352)
#define LAND(k) (((k) >> 1) * TILE_GRP + ((k) & 1) * 1280)
#define LAND_F (5 * TILE_SBO)
#define OFF_XL (OFF_TILE + 3 * TILE_GRP)
#define OFF_XF (OFF_XL + LAND_F)
#define OFF_WT ((OFF_XL + TILE_SBO + 1023) & ~1023)
#define OFF_TAB (OFF_BAR + 240)
#define OFF_INV (OFF_TAB + 64)
#define OFF_TS (OFF_INV + 128)
#define A_SMEM 232448
static_assert(WS_SZ + 72 * 1024 + 2 * PL_SZ + 4 * TILE_GRP + 512 == A_SMEM && OFF_WS % 1024 == 0 && OFF_WO % 1024 == 0 && SSQ == 13, "smem map");
enum { B_W0 = 0, B_W1, B_F1, B_F2 = B_F1 + 4, B_R1 = B_F2 + 4, B_R2, B_MEMFREE, B_LANDFREE, B_OPEER, B_PLFREE, B_XFREE, B_SB, B_WOF = B_SB + 6, B_WTF, B_RS, B_NUM = B_RS + 4 };
static_assert(B_NUM <= 30, "barriers");
enum { N_C = 0, N_SISS, N_QK, N_V, N_PM, N_TURN, N_PI, N_VGO, N_O, N_PX, N_AB, N_SDONE, N_VDONE, N_G3, N_P, N_OX };

__device__ __forceinline__ bool is_dual(int j) { return j >= LAG && j < NSEG; }
__device__ __forceinline__ int sched_l(int j) { return j < NSEG ? j : NSEG + j - LAG; }
__device__ __forceinline__ int sched_f(int j) { return NSEG + j - LAG; }
__device__ __forceinline__ void wait_cnt(const int* p, int target) {
  int v, n = 0;
  do {
    asm volatile("ld.relaxed.gpu.global.b32 %0, [%1];" : "=r"(v) : "l"(p) : "memory");
    if (v >= target) break;
    if (++n > SPIN_LIMIT) FAIL();
  } while (true);
  asm volatile("fence.acquire.gpu;" ::: "memory");
  asm volatile("fence.proxy.async.global;" ::: "memory");
}
__device__ __forceinline__ void red_release(void* p, uint32_t v) { asm volatile("red.release.gpu.global.add.u32 [%0], %1;" :: "l"(p), "r"(v) : "memory"); }
__device__ __forceinline__ void red_relaxed(void* p, uint32_t v) { asm volatile("red.relaxed.gpu.global.add.u32 [%0], %1;" :: "l"(p), "r"(v) : "memory"); }
#define VMASK 0xa5294a5294ull
__host__ __device__ constexpr int popc40(unsigned long long m) { int c = 0; for (; m; m &= m - 1) c++; return c; }
static_assert(popc40(VMASK) == SSV, "mask");
__host__ __device__ constexpr int ss_idx(int ks, int n) { return n == SSV ? popc40(VMASK & ((1ull << ks) - 1)) : ks * n / 40; }
__host__ __device__ constexpr bool is_ss(int ks, int n) { return ss_idx(ks + 1, n) != ss_idx(ks, n); }
__host__ __device__ constexpr int rs_idx(int ks, int n) { return ks - ss_idx(ks, n); }

#define SL2 (0.07216878364870322f * 1.4426950408889634f)

#define SUM_LOOP 0
struct Desc { Dsc tile, unit, k1, pl, p; };
__device__ __forceinline__ Desc make_desc(const uint64_t* h, uint32_t u, uint32_t e) {
  return {{h[0], e}, {h[1] + u * 128, e}, {h[2], e}, {h[3], e}, {h[4], e}};
}
template <int N, int NSS, int RG, int KS, int K1, int K0 = 0>
__device__ __forceinline__ void proj(float* acc, const uint32_t* W, const Desc& D) {
  if constexpr (KS < K1) {
    constexpr uint32_t BLO = dlo(OFF_TILE + (KS / 10) * TILE_GRP + RG * TILE_SBO + (KS % 10) * 256, 128);
    if constexpr (is_ss(KS, NSS)) MM<N>::template ss<dlo(OFF_WS + ss_idx(KS, NSS) * 2048, 0), BLO, (KS != K0)>(acc, D.unit, D.tile);
    else MM<N>::template rs<BLO, (KS != K0)>(acc, W + rs_idx(KS, NSS) * 4, D.tile);
    proj<N, NSS, RG, KS + 1, K1, K0>(acc, W, D);
  }
}
#define VST 17
template <int KS>
__device__ __forceinline__ void ld_rest(uint32_t* W, const uint32_t* p) {
  if constexpr (KS < 40) {
    if constexpr (!is_ss(KS, SSV) && rs_idx(KS, SSV) >= VST) {
#pragma unroll
      for (int i = 0; i < 4; i++) W[4 * rs_idx(KS, SSV) + i] = __ldg(p + (KS * 16 + (i >> 1) * 8) * (HD / 2) + (i & 1) * 4);
    }
    ld_rest<KS + 1>(W, p);
  }
}
template <int N>
__device__ __forceinline__ void load_w(uint32_t* W, uint32_t stage, int warp, int lane) {
  const int kr = (lane >> 4) * 8 + (lane & 7);
  const int cb = warp * 2 + ((lane >> 3) & 1);
  const uint32_t a0 = stage + kr * 128 + ((cb ^ (lane & 7)) << 4);
#pragma unroll
  for (int i = 0; i < N; i++) ldsm4t(W[4 * i], W[4 * i + 1], W[4 * i + 2], W[4 * i + 3], a0 + i * 2048);
}
template <int N, int G, int U, int OS, int ACC>
__device__ __forceinline__ void wo4(float* d, const Desc& D) {
  constexpr uint32_t WA = (U >= 4 ? OFF_WO + (U - 4) * 2048 : OFF_WT) - G * SSQ * 2048, OB = OS == 0 ? OFF_O : OS == 1 ? OFF_XL : OFF_XF;
  Dsc b = OS ? D.k1 : D.pl;
  b.e = fresh<(U < 16 ? U / 4 : U / 8 - 2) + (N == 8 ? 4 : 0)>(D.unit.e);
  MM<N>::template ss<dlo(WA, 0), dlo(OB, 128), ACC>(d, D.unit, b);
  MM<N>::template ss<dlo(WA + 2048, 0), dlo(OB + 256, 128), 1>(d, D.unit, b);
  MM<N>::template ss<dlo(WA + 4096, 0), dlo(OB + 512, 128), 1>(d, D.unit, b);
  MM<N>::template ss<dlo(WA + 6144, 0), dlo(OB + 768, 128), 1>(d, D.unit, b);
}
__device__ __forceinline__ void wo_coord(int i, int t3, int head, int& c0, int& c1) {
  const int g = i >> 1;
  const int blk = g == 0 ? 9 : (g < 4 ? g - 1 : (g - 4) >> 1) * 3 + t3;
  int sl = g < 4 ? t3 : (g & 1) ? t3 + 1 : t3 + 2;
  if (sl >= 3) sl -= 3;
  c0 = blk * 64; c1 = head * DH + sl * 64 + (i & 1) * 32;
}
__device__ __forceinline__ void tok_softmax(uint32_t sb, int job, int lane) {
  const bool w1 = job & 1;
  const int dg = (lane >> 2) - (lane & 3) * 2;
  const uint32_t lo = sb + OFF_PL + (job >> 1) * PL_SZ + (job & 1) * 1792, l8 = lo + 512 + lane * 8, pa = lo + lane * 4;
  const uint32_t km = job & 2 ? 640 : 512;
  float x[14];
  {
    const uint4 a = lds128(lo + lane * 16);
    const uint2 e = lds64(l8);
    const uint32_t c = lds32(768 + pa);
    x[0] = bf_lo(a.x); x[1] = bf_hi(a.x); x[2] = bf_lo(a.y); x[3] = bf_hi(a.y); x[4] = bf_lo(a.z); x[5] = bf_hi(a.z); x[6] = bf_lo(a.w); x[7] = bf_hi(a.w);
    x[8] = bf_lo(c); x[9] = bf_hi(c); x[10] = bf_lo(e.x); x[11] = bf_hi(e.x); x[12] = bf_lo(e.y); x[13] = bf_hi(e.y);
  }
  if (dg < 0) { x[8] = -INFINITY; if (w1) x[4] = -INFINITY; else x[10] = -INFINITY; }
  if (dg < 1) { x[9] = -INFINITY; if (w1) x[5] = -INFINITY; else x[11] = -INFINITY; }
  const float m4 = fmaxf(x[8], x[9]);
  float m0 = fmaxf(fmaxf(fmaxf(x[0], x[1]), fmaxf(x[2], x[3])), fmaxf(fmaxf(x[4], x[5]), fmaxf(x[6], x[7])));
  float m1 = fmaxf(fmaxf(x[10], x[11]), fmaxf(x[12], x[13]));
  if (w1) m1 = fmaxf(m1, m4); else m0 = fmaxf(m0, m4);
  m0 = fmaxf(m0, __shfl_xor_sync(~0u, m0, 1)); m1 = fmaxf(m1, __shfl_xor_sync(~0u, m1, 1));
  sts32(pa + (w1 ? 384 : 896 + 128), 0u); sts32(pa + 1152 - km, 0u); sts32(pa + 896 + 1152 - km, 0u); sts64(l8 + 896 - 256, 0u, 0u);
  m0 = fmaxf(m0, __shfl_xor_sync(~0u, m0, 2)); m1 = fmaxf(m1, __shfl_xor_sync(~0u, m1, 2));
  m0 *= -SL2; m1 *= -SL2;
#pragma unroll
  for (int j = 0; j < 14; j++) x[j] = ex2(fmaf(x[j], SL2, j < 8 ? m0 : j >= 10 ? m1 : w1 ? m1 : m0));
  const float l4s = x[8] + x[9];
  float l0 = ((x[0] + x[1]) + (x[2] + x[3])) + ((x[4] + x[5]) + (x[6] + x[7])), l1 = (x[10] + x[11]) + (x[12] + x[13]);
  if (w1) l1 += l4s; else l0 += l4s;
  l0 += __shfl_xor_sync(~0u, l0, 1); l1 += __shfl_xor_sync(~0u, l1, 1);
  l0 += __shfl_xor_sync(~0u, l0, 2); l1 += __shfl_xor_sync(~0u, l1, 2);
  l0 = rcpf(l0); l1 = rcpf(l1);
#pragma unroll
  for (int j = 0; j < 7; j++) {
    const float iv = j < 4 ? l0 : j > 4 ? l1 : w1 ? l1 : l0;
    sts32(pa + (j < 3 ? j * 128 : j == 3 ? km : j == 4 ? (w1 ? 896 + 128 : 384) : j == 5 ? 896 : 896 + km), pack2(x[2 * j] * iv, x[2 * j + 1] * iv));
  }
}
template <int N>
__device__ __forceinline__ void wo_phase(uint32_t sb, int wg, int warp, int lane, uint32_t par, uint32_t r1, const Desc& D) {
  const uint32_t bar = sb + OFF_BAR;
  float x[N / 2], y[N / 2];
  const uint2 ta = lds64(sb + OFF_TAB + (wg * 4 + warp) * 8);
  uint32_t xa = (ta.x & ~255u) + lane * 8, xb = (ta.x & 0xFF0000FFu) + SMEM0 + OFF_BAR, ya = (ta.y & ~255u) + lane * 8, yb = (ta.y & 0xFF0000FFu) + SMEM0 + OFF_BAR;
  asm volatile("" : "+r"(xa), "+r"(xb), "+r"(ya), "+r"(yb));
  auto scat = [&](uint32_t ad, uint32_t mb, const float* d) {
    st_async_v2(ad, pack2(d[0], d[1]), pack2(d[2], d[3]), mb);
    if (N == 16) st_async_v2(ad + LAND_F, pack2(d[4], d[5]), pack2(d[6], d[7]), mb);
  };
  if (wg == 0) {
    bar_sync(N_O, 384);
    wg_fence(); wo4<N, 0, 4, 0, 0>(x, D); wo4<N, 0, 8, 0, 0>(y, D); wg_commit();
    mbar_waitu(bar + 8 * B_OPEER, par);
    CFENCE(); wg_fence(); wo4<N, 0, 16, 1, 1>(x, D); wo4<N, 0, 20, 2, 1>(x, D); wg_commit();
    wo4<N, 0, 24, 1, 1>(y, D); wg_commit();
    mbar_waitu2(bar + 8 * B_WOF, bar + 8 * B_MEMFREE, par);
    wg_fence(); wo4<N, 0, 28, 2, 1>(y, D); wg_commit();
    bar_arrive(N_AB, 256);
    wg_wait<2>(); scat(xa, xb, x);
    wg_wait<0>(); scat(ya, yb, y);
  } else {
    bar_sync(N_O, 384);
    wg_fence(); wo4<N, 1, 0, 0, 0>(x, D); wg_commit(); wo4<N, 1, 12, 0, 0>(y, D); wg_commit();
    wg_wait<1>(); mbar_arrive_remote_if(lane == 0, r1);
    mbar_waitu(bar + 8 * B_MEMFREE, par);
    scat(xa, xb, x);
    bar_sync(N_AB, 256);
    CFENCE(); wg_fence(); wo4<N, 1, 32, 1, 1>(y, D); wo4<N, 1, 36, 2, 1>(y, D); wg_commit();
    bar_arrive(N_TURN, 256);
    wg_wait<0>(); scat(ya, yb, y);
  }
}
#define DS_DUAL 10
#define DS_SINGLE 20
#define POLL_GAP 100
#define POLL_GAPD 0
#define TOK_DELAY 250
#define LATE_SM 1
#define UMAX 40
#define VD1 10
#define VS2 20
#define IG_V 3
#define VS1 4
struct AMaps { CUtensorMap w16[3], wo32; uint64_t d[5]; const __nv_bfloat16* wv; };
__global__ void __launch_bounds__(512, 1)
acore_kernel(const __grid_constant__ AMaps M, const __nv_bfloat16* __restrict__ mem0, int sync_b) {
  extern __shared__ __align__(1024) unsigned char smem_raw[];
  const uint32_t sb = smem_u32(smem_raw);
  GTS(24);
  if (threadIdx.x == 480) {
    uint32_t smid; asm volatile("mov.u32 %0, %%smid;" : "=r"(smid));
    g_tpc[(smid >> 1) & 127] = blockIdx.x - CL_SIZE < 3 * CL_SIZE && blockIdx.x % CL_SIZE >= 12 ? 1 : 2;
    asm volatile("griddepcontrol.launch_dependents;");
  }
  const int lane0 = threadIdx.x & 31;
#define LANE_INIT() int lane; asm volatile("mov.u32 %0, %%laneid;" : "=r"(lane))
  const int warp = __shfl_sync(~0u, (threadIdx.x >> 5) & 3, 0);
  const int cl = blockIdx.x / CL_SIZE;
  const uint32_t rank = blockIdx.x - cl * CL_SIZE;
  const int nh = cl >= 1 && cl <= 3 ? 4 : 5;
  const int nA = 3 * nh;
  const int wg = __shfl_sync(~0u, (int)rank < nA ? threadIdx.x >> 7 : 4, 0);
  const int head = (cl < 4 ? (cl ? 1 + 4 * cl : 0) : 5 * cl - 3) + rank / 3;
  const int t3 = rank % 3;
  const int col0 = head * DH + t3 * 64;
  const uint32_t bar = sb + OFF_BAR;
  const uint32_t rb0 = SMEM0;
  const uint16_t mcmask = (uint16_t)((1u << nA) - 1);
  const uint32_t nxt = sb + ((t3 == 2 ? -2 : 1) << 24), prv = sb + ((t3 == 0 ? 2 : -1) << 24);
  const int ig = (int)rank - (nA - 4);

  if (threadIdx.x == 0) {
    if (mapa(sb, nA - 1) != rb0 + ((nA - 1) << 24) || mapa(sb, 0) != rb0 || mapa(sb, 1) != rb0 + (1u << 24) || sb != SMEM0 + (rank << 24)) FAIL();
    for (int i = 0; i < B_NUM; i++)
      mbar_init(bar + 8 * i, i == B_R1 ? 4 * nA : i == B_R2 ? 12 * nA : i == B_MEMFREE ? nA : i == B_LANDFREE ? 4 * nA : i == B_PLFREE || i == B_XFREE ? 2 : 1);
    asm volatile("fence.mbarrier_init.release.cluster;" ::: "memory");
    mbar_expect(bar + 8 * B_W0, (80 + SSV + VST) * 2048);
  }
  __syncthreads();
  if (lane0 == 0) {
    const int w12 = wg * 4 + warp;
    if (w12 < 10) {
#pragma unroll 1
      for (int ks = 4 * w12; ks < 4 * w12 + 4; ks++) {
        const bool ss = is_ss(ks, SSQ);
        tma2d(ss ? sb + OFF_WS + ss_idx(ks, SSQ) * 2048 : sb + STG_Q + rs_idx(ks, SSQ) * 2048, &M.w16[0], col0, ks * 16, bar + 8 * B_W0);
        tma2d(ss ? sb + OFF_WS + (SSQ + ss_idx(ks, SSQ)) * 2048 : sb + STG_K + rs_idx(ks, SSQ) * 2048, &M.w16[1], col0, ks * 16, bar + 8 * B_W0);
        if (is_ss(ks, SSV)) tma2d(sb + OFF_WS + (2 * SSQ + ss_idx(ks, SSV)) * 2048, &M.w16[2], col0, ks * 16, bar + 8 * B_W0);
        else if (rs_idx(ks, SSV) < VST) tma2d(sb + (rs_idx(ks, SSV) < VA ? STG_K + 27 * 2048 : STG_V2 - VA * 2048) + rs_idx(ks, SSV) * 2048, &M.w16[2], col0, ks * 16, bar + 8 * B_W0);
      }
    }
  }
  if (lane0 < 2 && wg < 2) {
    const int u = 4 * (wg ? (lane0 ? 6 + t3 : 9) : (lane0 ? 3 + t3 : t3)) + warp;
    const int li = (u >= nA) + (u >= 2 * nA) + (u >= 3 * nA);
    sts32(sb + OFF_TAB + (wg * 4 + warp) * 8 + lane0 * 4,
          rb0 + ((u - li * nA) << 24) + OFF_TILE + LAND(li + (u >= 36 ? t3 : 0)) + (rank / 3) * 256 + 8 * (B_RS + li));
  }
  __syncthreads();
  GTS(25);

  auto issue_tok = [&](int sc, int fb, int rel = -1, uint32_t ph = 0) {
    if (sync_b) wait_cnt(&g_xready[sc][0], 32);
    if (rel >= 0) mbar_waitu(bar + 8 * rel, ph);
    bulk_g2s_mc_e(sb + OFF_TILE + ig * TILE_GRP + TILE_SBO, &g_xn[0][0] + uni(sc * (32 * DM)) + ig * 5120, 10240, bar + 8 * (fb + ig), mcmask);
  };
#define POLL(d, q) _Pragma("unroll") for (int k = 0; k < NCL; k++) \
      asm volatile("ld.relaxed.gpu.global.v2.b32 {%0,%1}, [%2];" : "=r"(d[k].x), "=r"(d[k].y) : "l"(q + k * 2560) : "memory")
#define L3(L, a, b, c) lop3<L>(a, b, c)
#define TAGS(L, d) L3(L, L3(L, L3(L, d[0].x, d[0].y, d[1].x), L3(L, d[1].y, d[2].x, d[2].y), L3(L, d[3].x, d[3].y, d[4].x)), L3(L, d[4].y, d[5].x, d[5].y), L3(L, d[6].x, d[6].y, d[6].y))
    auto deliver = [&](uint2* pa, const uint32_t* gq, int u, int c, int dc, int ds, int step, bool first, int lane) {
      const uint32_t off = uni(OFF_TILE + ((u * 205) >> 11) * (TILE_GRP - TILE_SBO) + u * 256 + dc * LAND_F), boff = uni(OFF_BAR + 8 * (B_F1 + ((u * 205) >> 11)));
      const uint32_t* mi = &g_part[4][0][0][0] + uni((c * NCL + cl) * 2560 + u * 64);
      mbar_waitu(bar + 8 * B_LANDFREE, step & 1);
      int n = 0;
      while (true) {
        const bool ok = __all_sync(~0u, ((step & 2 ? ~TAGS(0xFE, pa) : TAGS(0x80, pa)) & 1) != 0);
        if (ok) break;
        if (++n > SPIN_LIMIT) FAIL();
        POLL(pa, gq);
      }
      if (warp == 0 && first) { TS(19); TSV(10, n); }
      const uint32_t w0 = hadd2bf(hadd2bf(hadd2bf(pa[0].x, pa[1].x), hadd2bf(pa[2].x, pa[3].x)), hadd2bf(hadd2bf(pa[4].x, pa[5].x), pa[6].x));
      const uint32_t w1 = hadd2bf(hadd2bf(hadd2bf(pa[0].y, pa[1].y), hadd2bf(pa[2].y, pa[3].y)), hadd2bf(hadd2bf(pa[4].y, pa[5].y), pa[6].y));
      if (u < ds) {
        const uint32_t da = SMEM0 + off + lane * 8, db = SMEM0 + boff;
#pragma unroll
        for (int d = 0; d < 12; d++) st_async_v2((d << 24) + da, w0, w1, (d << 24) + db);
#pragma unroll
        for (int d = 12; d < 15; d++) st_async_v2_if(nA == 15, (d << 24) + da, w0, w1, (d << 24) + db);
      } else {
        *reinterpret_cast<uint2*>(const_cast<uint32_t*>(gq) + ((4 - 2 * (step & 1)) * NCL + cl) * 2560) = make_uint2(w0, w1);
        asm volatile("fence.proxy.async.global;" ::: "memory");
        __syncwarp();
        bulk_g2s_mc_e(sb + off, mi, 256, sb + boff, mcmask);
      }
    };
#define REL(b, g) mbar_arrive_remote_if(lane == 0, rb0 + ((nA - 4 + (g)) << 24) + OFF_BAR + 8 * (b))

  if (wg < 2) {
    asm volatile("setmaxnreg.inc.sync.aligned.u32 160;");
    LANE_INIT();
    uint32_t W[4 * (40 - SSQ)];
    mbar_waitw(bar + 8 * B_W0, 0);
    GTS(26);
    load_w<40 - SSQ>(W, sb + (wg ? STG_K : STG_Q), warp, lane);
    fence_async();
    bar_sync(1, 384);
    cluster_sync_all();
#define DESC(k) const Desc D = make_desc(M.d, min(wg, 2) * SSQ, fresh<k>(step))
    GTS(27);
#pragma unroll 1
    for (int step = -1; step < NSTEP; step++) {
      const uint32_t par = step & 1;
      asm volatile("" : "+r"(lane));
      const bool dual = is_dual(step), has_next = step + 1 < NSTEP;
#define QK_SA (sb + OFF_QK + wg * 15360 + (2 * warp + ((lane >> 3) & 1)) * 128 + (lane & 7) * 16)
#define QK_F (wg ? -5120 : 5120)
#define QK_S12 ((wg ? (lane >> 4) : 1 + 2 * (lane >> 4)) * 1024)
#define QK_S34 ((wg ? 2 + (lane >> 4) : 2 - 2 * (lane >> 4)) * 1024)
      if (step >= 0) {
        if (dual) {
          DESC(0);
          float acc[24];
          mbar_waitu(bar + 8 * (B_F1 + 0), par);
          if (wg + warp == 0) { TS(0); TSN(1); }
          CFENCE(); wg_fence(); proj<48, SSQ, 0, 0, 10>(acc, W, D); wg_commit();
          mbar_waitu(bar + 8 * (B_F1 + 1), par);
          CFENCE(); wg_fence(); proj<48, SSQ, 0, 10, 20>(acc, W, D); wg_commit();
          mbar_waitu(bar + 8 * (B_F1 + 2), par);
          CFENCE(); wg_fence(); proj<48, SSQ, 0, 20, 30>(acc, W, D); wg_commit();
          mbar_waitu(bar + 8 * (B_F1 + 3), par);
          if (wg + warp == 0) TS(2);
          CFENCE(); wg_fence(); proj<48, SSQ, 0, 30, 40>(acc, W, D); wg_commit();
          bar_arrive(N_VGO, 384);
          mbar_waitu(bar + 8 * B_PLFREE, par);
          const uint32_t sa = QK_SA, s0 = sa + 4096 + (lane >> 4) * QK_F, s1 = sa + QK_F + QK_S12, s2 = sa + QK_F + QK_S34;
          wg_wait<0>();
          if (wg + warp == 0) TS(3);
          stsm4t(s0, pack2(acc[0], acc[1]), pack2(acc[2], acc[3]), pack2(acc[20], acc[21]), pack2(acc[22], acc[23]));
          stsm4t(s1, pack2(acc[4], acc[5]), pack2(acc[6], acc[7]), pack2(acc[8], acc[9]), pack2(acc[10], acc[11]));
          stsm4t(s2, pack2(acc[12], acc[13]), pack2(acc[14], acc[15]), pack2(acc[16], acc[17]), pack2(acc[18], acc[19]));
        } else {
          DESC(1);
          float acc[4];
          mbar_waitu(bar + 8 * (B_F1 + 0), par);
          if (wg + warp == 0) { TS(0); TSN(1); }
          CFENCE(); wg_fence(); proj<8, SSQ, 0, 0, 10>(acc, W, D); wg_commit();
          mbar_waitu(bar + 8 * (B_F1 + 1), par);
          CFENCE(); wg_fence(); proj<8, SSQ, 0, 10, 20>(acc, W, D); wg_commit();
          mbar_waitu(bar + 8 * (B_F1 + 2), par);
          CFENCE(); wg_fence(); proj<8, SSQ, 0, 20, 30>(acc, W, D); wg_commit();
          mbar_waitu(bar + 8 * (B_F1 + 3), par);
          if (wg + warp == 0) TS(2);
          CFENCE(); wg_fence(); proj<8, SSQ, 0, 30, 40>(acc, W, D); wg_commit();
          bar_arrive(N_VGO, 384);
          mbar_waitu(bar + 8 * B_PLFREE, par);
          const uint32_t s0 = QK_SA + 4096;
          wg_wait<0>();
          if (wg + warp == 0) TS(3);
          stsm2t(s0, pack2(acc[0], acc[1]), pack2(acc[2], acc[3]));
        }
        fence_async();
        bar_sync(N_QK, 256);
        if (wg == 0 || dual) {
          float s[20];
          DESC(2);
          const Dsc ab = D.k1 + wg * 192, bb = D.k1 + (1 - wg) * 320;
          wg_fence();
          MM<40>::ss<dlo(OFF_QK, 128), dlo(OFF_QK + 10240, 128), 0, 0>(s, ab, bb);
          MM<40>::ss<dlo(OFF_QK + 256, 128), dlo(OFF_QK + 10240 + 256, 128), 1, 0>(s, ab, bb);
          MM<40>::ss<dlo(OFF_QK + 512, 128), dlo(OFF_QK + 10240 + 512, 128), 1, 0>(s, ab, bb);
          MM<40>::ss<dlo(OFF_QK + 768, 128), dlo(OFF_QK + 10240 + 768, 128), 1, 0>(s, ab, bb);
          wg_commit();
          bar_arrive(N_SISS, 384);
          const int rw = (warp - wg) & 3;
          const uint32_t bo = OFF_BAR + 8 * (B_SB + 3 * wg + rw), lo = OFF_PL + wg * PL_SZ + rw * 1792;
          const uint32_t km = wg ? 640 : 512;
          uint32_t l16 = lo + lane * 16, l4 = lo + lane * 4;
          mbar_expect_if(lane == 0 && rw < 3, sb + bo, rw < 2 ? 1792 : 1280);
          asm volatile("" : "+r"(l16), "+r"(l4));
          if (rw == 2) {
            wg_wait<0>();
            if (wg == 0) TSD(4, __float_as_uint(s[0]));
            const uint32_t w0 = pack2(s[0], s[1]), w1 = pack2(s[4], s[5]), w2 = pack2(s[8], s[9]), w3 = pack2(s[12], s[13]), w4 = pack2(s[16], s[17]);
            {
              st_async_v4(nxt + 896 + l16, w0, w1, w2, w3, nxt + bo);
              st_async_v4(prv + l16, w0, w1, w2, w3, prv + bo);
              st_async_b32(nxt + 896 + 768 + l4, w4, nxt + bo);
              st_async_b32(prv + 768 + l4, w4, prv + bo);
            }
            bar_arrive(N_SDONE, 256);
            mbar_waitu(sb + bo, (step - wg * LAG) & 1);
            if (wg == 0) TS(5);
            float x[10], m0;
            {
              const uint4 a = lds128(sb + l16), b = lds128(sb + 896 + l16);
              const uint32_t c = lds32(sb + 768 + l4), d = lds32(sb + 896 + 768 + l4);
              const uint32_t e0 = hadd2bf(hadd2bf(a.x, b.x), w0), e1 = hadd2bf(hadd2bf(a.y, b.y), w1), e2 = hadd2bf(hadd2bf(a.z, b.z), w2),
                             e3 = hadd2bf(hadd2bf(a.w, b.w), w3), e4 = hadd2bf(hadd2bf(c, d), w4);
              const uint32_t em = hmax2bf(hmax2bf(hmax2bf(e0, e1), hmax2bf(e2, e3)), e4);
              m0 = fmaxf(bf_lo(em), bf_hi(em));
              x[0] = bf_lo(e0); x[1] = bf_hi(e0); x[2] = bf_lo(e1); x[3] = bf_hi(e1); x[4] = bf_lo(e2);
              x[5] = bf_hi(e2); x[6] = bf_lo(e3); x[7] = bf_hi(e3); x[8] = bf_lo(e4); x[9] = bf_hi(e4);
            }
            m0 = fmaxf(m0, __shfl_xor_sync(~0u, m0, 1));
            sts32(sb + l4 + 1152 - km, 0u);
            m0 = fmaxf(m0, __shfl_xor_sync(~0u, m0, 2));
            m0 *= -SL2;
#pragma unroll
            for (int j = 0; j < 5; j++) {
              x[2 * j] = ex2(fmaf(x[2 * j], SL2, m0)); x[2 * j + 1] = ex2(fmaf(x[2 * j + 1], SL2, m0));
              sts32(sb + l4 + (j < 4 ? j * 128 : km), pack2(x[2 * j], x[2 * j + 1]));
            }
            float l = ((x[0] + x[1]) + (x[2] + x[3])) + ((x[4] + x[5]) + ((x[6] + x[7]) + (x[8] + x[9])));
            l += __shfl_xor_sync(~0u, l, 1);
            fence_async();
            sts32(sb + OFF_INV + wg * 64 + (lane >> 1) * 4, __float_as_uint(l));
            bar_arrive(N_PM, dual ? 224 : 192);
            if (wg == 0) TS(6);
          } else if (rw < 2) {
            const bool w1 = rw == 1;
            const uint32_t l8 = lo + 512 + lane * 8;
            uint32_t tw[7];
            wg_wait<0>();
            bar_arrive(N_SDONE, 256);
            tw[0] = pack2(s[0], s[1]); tw[1] = pack2(s[4], s[5]); tw[2] = pack2(s[8], s[9]); tw[3] = pack2(s[16], s[17]);
            tw[4] = w1 ? pack2(s[6], s[7]) : pack2(s[12], s[13]); tw[5] = pack2(s[2], s[3]); tw[6] = pack2(s[18], s[19]);
            { const uint32_t t0 = clock32(); while (clock32() - t0 < TOK_DELAY) {} }
            st_async_v4(nxt + 896 + l16, tw[0], tw[1], tw[2], tw[3], nxt + bo);
            st_async_v4(prv + l16, tw[0], tw[1], tw[2], tw[3], prv + bo);
            st_async_v2(nxt + 896 + l8, tw[5], tw[6], nxt + bo);
            st_async_v2(prv + l8, tw[5], tw[6], prv + bo);
            st_async_b32(nxt + 896 + 768 + l4, tw[4], nxt + bo);
            st_async_b32(prv + 768 + l4, tw[4], prv + bo);
            mbar_waitu(sb + bo, (step - wg * LAG) & 1);
            const uint4 a = lds128(sb + l16), b = lds128(sb + 896 + l16);
            const uint2 e = lds64(sb + l8), f = lds64(sb + 896 + l8);
            const uint32_t c = lds32(sb + 768 + l4), d = lds32(sb + 896 + 768 + l4);
            sts128(sb + l16, hadd2bf(hadd2bf(a.x, b.x), tw[0]), hadd2bf(hadd2bf(a.y, b.y), tw[1]), hadd2bf(hadd2bf(a.z, b.z), tw[2]), hadd2bf(hadd2bf(a.w, b.w), tw[3]));
            sts64(sb + l8, hadd2bf(hadd2bf(e.x, f.x), tw[5]), hadd2bf(hadd2bf(e.y, f.y), tw[6]));
            sts32(sb + 768 + l4, hadd2bf(hadd2bf(c, d), tw[4]));
            bar_arrive(N_PX, dual ? 256 : 192);
            if (wg + warp == 0) TS(9);
          } else {
            wg_wait<0>();
            if (wg == 0) {
              mbar_expect_if(lane < 3 && has_next, bar + 8 * (lane == 2 ? B_OPEER : B_WOF + lane), lane == 2 ? (dual ? 4096 : 2048) : lane ? 8192 : 20480);
              auto fetch = [&](int i, int n, uint32_t dst, int mb) {
                int c0, c1; wo_coord(i, t3, head, c0, c1);
                tma2d_e(dst, &M.wo32, c0, c1, bar + 8 * mb); if (n == 2) tma2d_e(dst + 4096, &M.wo32, c0, c1 + 32, bar + 8 * mb);
              };
              bar_sync(N_G3, 160);
              if (has_next) {
                fetch(0, 2, sb + OFF_WT, B_WTF);
                mbar_arrive_remote_if(lane < 2, (lane ? nxt : prv) + OFF_BAR + 8 * B_XFREE);
              }
              bar_sync(N_SDONE, 256);
              if (has_next) {
                fetch(15, 1, sb + OFF_QK, B_WOF); fetch(16, 2, sb + OFF_QK + 4096, B_WOF); fetch(18, 2, sb + OFF_QK + 12288, B_WOF);
                mbar_waitu(bar + 8 * B_XFREE, par);
              }
              bar_arrive(N_PM, dual ? 224 : 192);
              bar_sync(N_VDONE, 160);
              mbar_arrive_remote_if(lane < nA && has_next, rb0 + (lane << 24) + OFF_BAR + 8 * B_MEMFREE);
              if (has_next) mbar_waitu(bar + 8 * B_WTF, par);
            } else {
              bar_arrive(N_SDONE, 256);
              if ((unsigned)ig < IG_V) issue_tok(sched_l(step + 1), B_F2, B_R1, (step - LAG) & 1);
            }
          }
        } else {
          bar_arrive(N_SISS, 384);
          bar_arrive(N_SDONE, 256);
        }
        if (has_next) {
          if (step == 0) mbar_waitw(bar + 8 * B_W1, 0);
          const uint32_t r1 = rb0 + ((nA - 1) << 24) + OFF_BAR + 8 * B_R1;
          if (dual) { DESC(3); wo_phase<16>(sb, wg, warp, lane, par, r1, D); } else { DESC(4); wo_phase<8>(sb, wg, warp, lane, par, r1, D); }
          bar_arrive(N_C, 288);
          if (warp == 0) TS(7 + wg);
        }
      }
      if (has_next) {
        DESC(5);
        float acc[16];
        mbar_waitu(bar + 8 * B_F2, par ^ 1);
        wg_fence(); proj<32, SSQ, 1, 0, 10>(acc, W, D); wg_commit();
        mbar_waitu(bar + 8 * (B_F2 + 1), par ^ 1);
        wg_fence(); proj<32, SSQ, 1, 10, 14>(acc, W, D); wg_commit();
        wg_wait<1>(); REL(B_R2, 0);
        wg_fence(); proj<32, SSQ, 1, 14, 20>(acc, W, D); wg_commit();
        mbar_waitu(bar + 8 * (B_F2 + 2), par ^ 1);
        wg_fence(); proj<32, SSQ, 1, 20, 24>(acc, W, D); wg_commit();
        wg_wait<1>(); REL(B_R2, 1);
        wg_fence(); proj<32, SSQ, 1, 24, 30>(acc, W, D); wg_commit();
        mbar_waitu(bar + 8 * (B_F2 + 3), par ^ 1);
        wg_fence(); proj<32, SSQ, 1, 30, 34>(acc, W, D); wg_commit();
        wg_wait<1>(); REL(B_R2, 2);
        wg_fence(); proj<32, SSQ, 1, 34, 40>(acc, W, D); wg_commit();
        const uint32_t sa = QK_SA, s1 = sa + QK_S12, s2 = sa + QK_S34;
        wg_wait<0>(); REL(B_R2, 3);
        if (warp == 0) TS(11 + wg);
        stsm4t(s1, pack2(acc[0], acc[1]), pack2(acc[2], acc[3]), pack2(acc[4], acc[5]), pack2(acc[6], acc[7]));
        stsm4t(s2, pack2(acc[8], acc[9]), pack2(acc[10], acc[11]), pack2(acc[12], acc[13]), pack2(acc[14], acc[15]));
      }
    }
    GTS(28);
    cluster_sync_all();
  } else if (wg == 2) {
    asm volatile("setmaxnreg.inc.sync.aligned.u32 160;");
    LANE_INIT();
    uint32_t W[4 * (40 - SSV)];
    ld_rest<0>(W, reinterpret_cast<const uint32_t*>(M.wv + (lane >> 2) * HD + col0 + warp * 16) + (lane & 3));
    uint4 m0[5];
#pragma unroll
    for (int i = 0; i < 5; i++) {
      const int t = i * 128 + warp * 32 + lane;
      m0[i] = __ldg(reinterpret_cast<const uint4*>(mem0 + ((t >> 1) & 7) * DM + (t >> 4) * 16 + ((t ^ (t >> 3)) & 1) * 8));
    }
    mbar_waitw(bar + 8 * B_W0, 0);
    load_w<VA>(W, sb + STG_K + 27 * 2048, warp, lane);
    load_w<VST - VA>(W + 4 * VA, sb + STG_V2, warp, lane);
    fence_async();
    mbar_expect_if(warp + lane == 0, bar + 8 * B_W1, 26 * 2048);
    bar_sync(1, 384);
#pragma unroll
    for (int i = 0; i < 5; i++) {
      const int t = i * 128 + warp * 32 + lane;
      sts128(sb + OFF_TILE + (t / 160) * (TILE_GRP - TILE_SBO) + t * 16, m0[i].x, m0[i].y, m0[i].z, m0[i].w);
    }
#pragma unroll
    for (int i = 4 * VST; i < 4 * (40 - SSV); i++) W[i] = movm(W[i]);
    fence_async();
    mbar_arrive_if(lane == 0, bar + 8 * (B_F1 + warp));
    mbar_expect_if(lane == 0, bar + 8 * (B_F2 + warp), 10240);
    mbar_arrive_if(warp == 3 && lane < 2, bar + 8 * B_PLFREE);
    cluster_sync_all();
    uint32_t vl[8];
    {
      const int step = warp;
      DESC(0);
      float v[16];
      mbar_waitw4(bar + 8 * B_F2, 0);
      wg_fence(); proj<32, SSV, 1, 0, 40>(v, W, D); wg_commit();
      wg_wait<0>();
      mbar_arrive_remote_if(lane < 4, rb0 + ((nA - 4 + lane) << 24) + OFF_BAR + 8 * B_R2);
#pragma unroll
      for (int j = 0; j < 8; j++) vl[j] = pack2v(v[2 * j], v[2 * j + 1]);
      if (warp == 0 && (unsigned)ig < 3) issue_tok(1, B_F2, B_R2, 0);
    }
#pragma unroll 1
    for (int step = 0; step < NSTEP; step++) {
      const uint32_t par = step & 1;
      asm volatile("" : "+r"(lane));
      const bool dual = is_dual(step), has_next = step + 1 < NSTEP;
      mbar_expect_if(lane == 0 && has_next, bar + 8 * (B_F2 + warp), 10240);
      if (warp == 0 && ig >= IG_V && dual && sync_b) wait_cnt(&g_xready[sched_l(step + 1)][0], 32);
      bar_sync(N_VGO, 384);
      CFENCE();
#define F1_BYTES (is_dual(step + 1) ? 15360 : 2560)
#define ARM() do { \
        mbar_expect_if(lane == 0 && has_next, bar + 8 * (B_F1 + warp), F1_BYTES); \
        mbar_expect_if(lane == 0 && has_next && warp * nA + (int)rank < 40, bar + 8 * (B_RS + warp), (warp * nA + (int)rank >= 36 ? nA : nh) * (dual ? 512 : 256)); } while (0)
#define O_ADDR() uint32_t oa = sb + OFF_O + (lane >> 4) * PL_SZ + warp * 256 + (lane & 15) * 16, xo = (lane >> 4) * 1024 + warp * 256 + (lane & 15) * 16; \
        asm volatile("" : "+r"(oa), "+r"(xo))
#define O_READY(act) do { if (has_next) { const uint4 ov = lds128(oa); \
        if (act) { st_async_v4(nxt + OFF_XL + xo, ov.x, ov.y, ov.z, ov.w, nxt + OFF_BAR + 8 * B_OPEER); \
                   st_async_v4(prv + OFF_XF + xo, ov.x, ov.y, ov.z, ov.w, prv + OFF_BAR + 8 * B_OPEER); } \
        fence_async(); bar_arrive(N_O, 384); } \
        if (warp == 0) TS(15); } while (0)
#define TOK_L3(g0) if (warp == 0 && ig >= (g0) && has_next) { mbar_waitu(bar + 8 * B_R1, ig == 3 ? par : (step - LAG) & 1); asm volatile("fence.proxy.async.global;" ::: "memory"); \
        bulk_g2s_mc_e(sb + OFF_TILE + ig * TILE_GRP + TILE_SBO, &g_xn[0][0] + uni(sched_l(step + 1) * (32 * DM)) + ig * 5120, 10240, bar + 8 * (B_F2 + ig), mcmask); }
#define OX_ADDR() const bool ox = head * 3 + t3 == 95; \
        const uint32_t oxa = sb + OFF_PL + (ox ? warp * 1024 + (lane & 7) * 32 + ((((lane >> 3) ^ (lane >> 2)) & 1) << 4) : (lane & 7) * 128 + (((warp * 2 + ((lane >> 3) & 1)) ^ (lane & 7)) << 4)); \
        const uint32_t s1 = oxa + ((lane < 16 ? 3072 : 0) >> (ox ? 2 : 0)), s2 = oxa + ((lane < 16 ? 2048 : 1024) >> (ox ? 2 : 0))
      if (dual) {
        uint32_t vf[8], vm[4], vn[8];
        {
          DESC(0);
          float v[24];
          ARM();
          wg_fence(); proj<48, SSV, 0, 30, 40, 30>(v, W, D); wg_commit();
          proj<48, SSV, 0, 0, VD1 - 10, 30>(v, W, D);
          bar_sync(N_SISS, 384);
          proj<48, SSV, 0, VD1 - 10, VD1 - 7, 30>(v, W, D); wg_commit();
          wg_wait<1>(); bar_arrive(N_G3, 160);
          wg_fence(); proj<48, SSV, 0, VD1 - 7, 10, 30>(v, W, D); wg_commit();
          proj<48, SSV, 0, 10, 13, 30>(v, W, D); wg_commit();
          wg_wait<1>(); REL(B_R1, 0);
          wg_fence(); proj<48, SSV, 0, 13, 20, 30>(v, W, D); wg_commit();
          proj<48, SSV, 0, 20, 23, 30>(v, W, D); wg_commit();
          wg_wait<1>(); REL(B_R1, 1);
          wg_fence(); proj<48, SSV, 0, 23, 30, 30>(v, W, D); wg_commit();
          wg_wait<0>(); REL(B_R1, 2);
          bar_arrive(N_VDONE, 160);
          if (warp == 0) TS(14);
#pragma unroll
          for (int j = 4; j < 8; j++) vf[j] = pack2v(v[4 + 2 * j], v[5 + 2 * j]);
          keep4(vf + 4, lane);
          vm[0] = pack2v(v[0], v[1]); vm[1] = pack2v(v[2], v[3]); vm[2] = pack2v(v[20], v[21]); vm[3] = pack2v(v[22], v[23]);
          keep4(vm, lane);
#pragma unroll
          for (int j = 0; j < 4; j++) vf[j] = pack2v(v[4 + 2 * j], v[5 + 2 * j]);
          keep4(vf, lane);
        }
        {
          DESC(1);
          float o[8];
          O_ADDR();
          bar_sync(N_PM, 224);
          wg_fence();
          MM<8>::rs<dlo(OFF_PL + 3584, 128), 0>(o, vl, D.p);
          MM<8>::rs<dlo(OFF_PL + PL_SZ + 3584, 128), 0>(o + 4, vf, D.p);
          MM<8>::rs<dlo(OFF_PL + 3584 + 256, 128), 1>(o, vl + 4, D.p);
          MM<8>::rs<dlo(OFF_PL + PL_SZ + 3584 + 256, 128), 1>(o + 4, vf + 4, D.p);
          MM<8>::rs<dlo(OFF_PL + 3584 + 512, 128), 1>(o, vm, D.p);
          MM<8>::rs<dlo(OFF_PL + PL_SZ + 3584 + 512, 128), 1>(o + 4, vm, D.p);
          wg_commit();
          fence_sched(step);
          const uint4 il = lds128(sb + OFF_INV + (lane & 3) * 16), jf = lds128(sb + OFF_INV + 64 + (lane & 3) * 16);
          const float i0 = rcpf(__uint_as_float(il.x) + __uint_as_float(il.y)), i1 = rcpf(__uint_as_float(il.z) + __uint_as_float(il.w));
          const float j0 = rcpf(__uint_as_float(jf.x) + __uint_as_float(jf.y)), j1 = rcpf(__uint_as_float(jf.z) + __uint_as_float(jf.w));
          { const uint32_t k4[4] = {__float_as_uint(i0), __float_as_uint(i1), __float_as_uint(j0), __float_as_uint(j1)}; keep4(k4, lane | (oa ^ xo)); }
          wg_wait<0>();
          stsm4t(oa, pack2(o[0] * i0, o[1] * i1), pack2(o[2] * i0, o[3] * i1), pack2(o[4] * j0, o[5] * j1), pack2(o[6] * j0, o[7] * j1));
          O_READY(true);
          TOK_L3(IG_V);
        }
        {
          DESC(2);
          float v[16];
          bar_sync(N_TURN, 256);
          mbar_waitu(bar + 8 * B_F2, par ^ 1);
          wg_fence(); proj<32, SSV, 1, 0, 10>(v, W, D); wg_commit();
          mbar_waitu(bar + 8 * (B_F2 + 1), par ^ 1);
          wg_fence(); proj<32, SSV, 1, 10, 14>(v, W, D); wg_commit();
          wg_wait<1>(); REL(B_R2, 0);
          wg_fence(); proj<32, SSV, 1, 14, 20>(v, W, D); wg_commit();
          mbar_waitu(bar + 8 * (B_F2 + 2), par ^ 1);
          wg_fence(); proj<32, SSV, 1, 20, 24>(v, W, D); wg_commit();
          wg_wait<1>(); REL(B_R2, 1);
          wg_fence(); proj<32, SSV, 1, 24, 30>(v, W, D); wg_commit();
          mbar_waitu(bar + 8 * (B_F2 + 3), par ^ 1);
          wg_fence(); proj<32, SSV, 1, 30, 34>(v, W, D); wg_commit();
          wg_wait<1>(); REL(B_R2, 2);
          wg_fence(); proj<32, SSV, 1, 34, 40>(v, W, D); wg_commit();
          wg_wait<0>(); REL(B_R2, 3);
#pragma unroll
          for (int j = 0; j < 8; j++) vn[j] = pack2v(v[2 * j], v[2 * j + 1]);
          keep4(vn, lane); keep4(vn + 4, lane);
          if (warp == 0) TS(18);
        }
        DESC(3);
        uint32_t ow[16];
        bar_sync(N_P, 256);
        fence_async();
#define PV16(i, off, va) { float o[8]; wg_fence(); \
          MM<16>::rs<dlo(OFF_PL + (off), 128), 0>(o, va, D.p); \
          MM<16>::rs<dlo(OFF_PL + (off) + 256, 128), 1>(o, va + 4, D.p); \
          MM<16>::rs<dlo(OFF_PL + (off) + 512, 128), 1>(o, vm, D.p); \
          wg_commit(); wg_wait<0>(); \
          _Pragma("unroll") for (int j = 0; j < 4; j++) ow[4 * (i) + j] = pack2v(o[2 * j], o[2 * j + 1]); \
          keep4(ow + 4 * (i), lane); }
        PV16(0, 0, vl) PV16(1, 1792, vl) PV16(2, PL_SZ, vf) PV16(3, PL_SZ + 1792, vf)
        OX_ADDR();
        bar_sync(N_V, 128);
        stsm4t(s1, ow[0], ow[1], ow[2], ow[3]);
        stsm4t(s2, ow[4], ow[5], ow[6], ow[7]);
        stsm4t(s1 + PL_SZ, ow[8], ow[9], ow[10], ow[11]);
        stsm4t(s2 + PL_SZ, ow[12], ow[13], ow[14], ow[15]);
#pragma unroll
        for (int j = 0; j < 8; j++) vl[j] = vn[j];
      } else {
        uint32_t vm[4], vn[8];
        {
          DESC(4);
          float v[4];
          wg_fence(); proj<8, SSV, 0, 30, 40, 30>(v, W, D); wg_commit();
          proj<8, SSV, 0, 0, VS1, 30>(v, W, D); wg_commit();
          ARM();
          bar_sync(N_SISS, 384);
          wg_wait<1>(); bar_arrive(N_G3, 160);
          wg_fence(); proj<8, SSV, 0, VS1, 30, 30>(v, W, D); wg_commit();
          if (has_next) { mbar_waitu2(bar + 8 * B_F2, bar + 8 * (B_F2 + 1), par ^ 1); mbar_waitu(bar + 8 * (B_F2 + 2), par ^ 1); }
          wg_wait<0>();
          bar_arrive(N_VDONE, 160);
          vm[0] = pack2v(v[0], v[1]); vm[1] = pack2v(v[2], v[3]); vm[2] = pack2v(v[1], v[0]); vm[3] = pack2v(v[3], v[2]);
        }
        DESC(5);
        float v[16];
        {
          wg_fence(); proj<32, SSV, 1, 0, VS2>(v, W, D); wg_commit();
          {
            float o[4];
            O_ADDR();
            bar_sync(N_PM, 192);
            if (warp == 0) TS(14);
            wg_fence();
            MM<8>::rs<dlo(OFF_PL + 3584, 128), 0>(o, vl, D.p);
            MM<8>::rs<dlo(OFF_PL + 3584 + 256, 128), 1>(o, vl + 4, D.p);
            MM<8>::rs<dlo(OFF_PL + 3584 + 512, 128), 1>(o, vm, D.p);
            wg_commit();
            fence_sched(step);
            const uint4 il = lds128(sb + OFF_INV + (lane & 3) * 16);
            const float i0 = rcpf(__uint_as_float(il.x) + __uint_as_float(il.y)), i1 = rcpf(__uint_as_float(il.z) + __uint_as_float(il.w));
            { const uint32_t k4[4] = {__float_as_uint(i0), __float_as_uint(i1), oa, xo}; keep4(k4, lane); }
            wg_wait<0>();
            stsm2t(oa, pack2(o[0] * i0, o[1] * i1), pack2(o[2] * i0, o[3] * i1));
            O_READY(lane < 16);
            TOK_L3(3);
          }
          if (has_next) {
            mbar_arrive_remote_if(lane < VS2 / 10, rb0 + ((nA - 4 + lane) << 24) + OFF_BAR + 8 * B_R2);
            bar_sync(N_TURN, 256);
          }
          if (VS2 < 30) { wg_fence(); proj<32, SSV, 1, VS2, 30>(v, W, D); wg_commit(); }
          if (has_next) mbar_waitu(bar + 8 * (B_F2 + 3), par ^ 1);
          if (VS2 < 30) { wg_wait<0>(); if (has_next) REL(B_R2, 2); }
          wg_fence(); proj<32, SSV, 1, 30, 40>(v, W, D); wg_commit();
          wg_wait<0>();
          if (has_next) REL(B_R2, 3);
#pragma unroll
          for (int j = 0; j < 8; j++) vn[j] = pack2v(v[2 * j], v[2 * j + 1]);
          keep4(vn, lane); keep4(vn + 4, lane);
          if (warp == 0) TS(18);
        }
        float o[16];
        bar_sync(N_P, 256);
        fence_async();
        wg_fence();
        MM<32>::rs<dlo(OFF_PL, 128), 0>(o, vl, D.p);
        MM<32>::rs<dlo(OFF_PL + 256, 128), 1>(o, vl + 4, D.p);
        MM<32>::rs<dlo(OFF_PL + 512, 128), 1>(o, vm, D.p);
        wg_commit();
        OX_ADDR();
        wg_wait<0>();
        bar_sync(N_V, 128);
        stsm4t(s1, pack2(o[0], o[1]), pack2(o[2], o[3]), pack2(o[4], o[5]), pack2(o[6], o[7]));
        stsm4t(s2, pack2(o[8], o[9]), pack2(o[10], o[11]), pack2(o[12], o[13]), pack2(o[14], o[15]));
#pragma unroll
        for (int j = 0; j < 8; j++) vl[j] = vn[j];
      }
      bar_arrive(N_OX, 160);
      if (warp == 0) TS(16);
    }
    cluster_sync_all();
  } else {
    asm volatile("setmaxnreg.dec.sync.aligned.u32 32;");
    if (wg > 3) return;
    LANE_INIT();
    struct RsJob { uint32_t* gp; uint32_t la, mb; int n; };
    auto rs_prep = [&](int step, int s, int c) {
      RsJob j;
      const int u = s * nA + rank;
      j.gp = &g_part[0][0][0][0] + (uint32_t)((((step & 1) * 2 + c) * NCL + cl) * 2560 + u * 64 + (lane >> 2) * 8 + (lane & 3));
      j.la = sb + OFF_TILE + c * LAND_F + LAND(s) + lane * 8;
      j.mb = bar + 8 * (B_RS + s);
      j.n = u >= 40 ? 0 : u >= 36 ? 3 : 1;
      asm volatile("" : "+l"(j.gp), "+r"(j.la));
      return j;
    };
    auto rs_sum = [&](RsJob j, int step) {
      if (j.n) {
        auto five = [&](uint32_t la) {
          uint2 p[5];
#pragma unroll
          for (int i = 0; i < 4; i++) p[i] = lds64(la + i * 256);
          asm volatile("{\n.reg .pred q;\nsetp.eq.s32 q, %3, 5;\nmov.u32 %0, 0;\nmov.u32 %1, 0;\n@q ld.shared.v2.b32 {%0,%1}, [%2];\n}"
                       : "=r"(p[4].x), "=r"(p[4].y) : "r"(la + 1024), "r"(nh) : "memory");
          return make_uint2(hadd2bf(hadd2bf(p[0].x, p[1].x), hadd2bf(hadd2bf(p[2].x, p[3].x), p[4].x)),
                            hadd2bf(hadd2bf(p[0].y, p[1].y), hadd2bf(hadd2bf(p[2].y, p[3].y), p[4].y)));
        };
        const uint32_t tag = ((step >> 1) & 1) ^ 1;
        mbar_waitw(j.mb, step & 1);
        uint2 t = five(j.la);
        if (j.n > 1) {
          const uint2 a = five(j.la + (nh == 5 ? 1280 : TILE_GRP - 1280)), b = five(j.la + TILE_GRP);
          t.x = hadd2bf(t.x, hadd2bf(a.x, b.x)); t.y = hadd2bf(t.y, hadd2bf(a.y, b.y));
        }
        const uint32_t t0 = (movm(t.x) & ~1u) | tag, t1 = (movm(t.y) & ~1u) | tag;
        asm volatile("st.relaxed.gpu.global.b32 [%0], %1;" :: "l"(j.gp), "r"(lane & 16 ? t1 : t0) : "memory");
        asm volatile("st.relaxed.gpu.global.b32 [%0], %1;" :: "l"(j.gp + 4), "r"(lane & 16 ? t0 : t1) : "memory");
      }
    };
    if (warp * nA + (int)rank < 40) {
#pragma unroll
      for (int e = LAG; e < LAG + 2; e++)
        if ((e >> 1) & 1) *reinterpret_cast<uint2*>(&g_part[(e & 1) * 2 + 1][cl][warp * nA + rank][lane * 2]) = make_uint2(1u, 1u);
      __threadfence();
    }
    if (warp == 2 && ig >= 0 && sync_b) wait_cnt(&g_xready[0][0], 32);
    cluster_sync_all();
    if (warp == 2 && ig >= 0) bulk_g2s_mc_e(sb + OFF_TILE + ig * TILE_GRP + TILE_SBO, &g_xn[0][0] + ig * 5120, 10240, bar + 8 * (B_F2 + ig), mcmask);
    bar_sync(N_PI, 128);
#pragma unroll 1
    for (int i = warp; i < 20; i += 4) {
      int c0, c1; wo_coord(i, t3, head, c0, c1);
      if (i >= 2 && i < 15) tma2d_e(sb + OFF_WO + (i - 2) * 4096, &M.wo32, c0, c1, bar + 8 * B_W1);
      else if (lane == 0) tma2d_prefetch(&M.wo32, c0, c1);
      __syncwarp();
    }
#pragma unroll 1
    for (int step = 0; step < NSTEP; step++) {
      const uint32_t par = step & 1;
      asm volatile("" : "+r"(lane));
      const bool dual = is_dual(step), has_next = step + 1 < NSTEP;
      {
        bar_sync(N_PX, dual ? 256 : 192);
        if (dual || warp >= 2) tok_softmax(sb, dual ? warp : warp - 2, lane);
        bar_arrive(N_P, 256);
        asm volatile("" : "+r"(lane));
        if (has_next) {
          if (step + 2 == LAG && lane < 20) asm volatile("prefetch.global.L2 [%0];" :: "l"(mem0 + (warp * 20 + lane) * 64));
          const int nw = ig >= 0 ? 3 : 4, j0 = warp < nw ? warp : 8;
          const int sh = dual ? 1 : 0;
          rs_sum(rs_prep(step, j0 >> sh, j0 & sh), step);
          if (warp == 0) TS(17);
          if (dual) rs_sum(rs_prep(step, (j0 + nw) >> 1, (j0 + nw) & 1), step);
          if (warp == 0) { bar_sync(N_C, 288); }
          mbar_arrive_remote_if(lane < nA, rb0 + (lane << 24) + OFF_BAR + 8 * B_LANDFREE);
          const uint32_t gap = dual ? POLL_GAPD : POLL_GAP;
          if (gap) { const uint32_t t0 = clock32(); while (clock32() - t0 < gap) {} }
#pragma unroll 1
          for (int j = j0; j < (dual ? 8 : 4); j += nw) {
            const int u = (j >> sh) * nA + rank, c = j & sh;
            if (u < UMAX && (c || step + 1 != NSEG)) {
              const uint32_t* gq = &g_part[0][0][0][0] + (uint32_t)((par * 2 + c) * NCL * 2560 + u * 64 + lane * 2);
              uint2 pa[NCL];
              POLL(pa, gq);
              deliver(pa, gq, u, c, step + 1 < NSEG ? c : 0, dual ? DS_DUAL : DS_SINGLE, step, j == 0, lane);
            }
            if (warp == 0 && j == 0) TS(13);
          }
          if (warp >= nw && (is_dual(step + 1) || (ig < 3 && step + 2 < NSTEP))) {
            issue_tok(is_dual(step + 1) ? sched_f(step + 1) : sched_l(step + 2), is_dual(step + 1) ? B_F1 : B_F2, B_R2, par ^ 1);
          }
          if (step + 1 == LAG && UMAX) {
            uint4 v[5];
#pragma unroll
            for (int i = 0; i < 5; i++) { const int t = warp * 160 + i * 32 + lane; v[i] = *reinterpret_cast<const uint4*>(mem0 + ((t >> 1) & 7) * DM + (t >> 4) * 16 + ((t ^ (t >> 3)) & 1) * 8); }
            mbar_waitu(bar + 8 * B_LANDFREE, par);
#pragma unroll
            for (int i = 0; i < 5; i++)
              st_async_v4(sb + OFF_TILE + LAND_F + warp * TILE_GRP + (i * 32 + lane) * 16, v[i].x, v[i].y, v[i].z, v[i].w, bar + 8 * (B_F1 + warp));
          }
        }
      }
      if (warp == (ig >= 0 && !is_dual(step + 1) ? 2 : 3)) {
        unsigned char* o0 = g_o + uni(step % RO * (96 * 8192) + (head * 3 + t3) * (dual ? 8192 : 4096));
        bar_sync(N_OX, 160);
        fence_async();
        bulk_s2g_es(o0, sb + OFF_PL, 4096);
        if (dual) bulk_s2g_es(o0 + 4096, sb + OFF_PL + PL_SZ, 4096);
        asm volatile("cp.async.bulk.commit_group;" ::: "memory");
        asm volatile("cp.async.bulk.wait_group.read 0;" ::: "memory");
        __syncwarp();
        mbar_arrive_remote_if(lane < 2, (lane ? nxt : prv) + OFF_BAR + 8 * B_PLFREE);
        asm volatile("cp.async.bulk.wait_group 0;" ::: "memory");
        asm volatile("fence.proxy.async.global;" ::: "memory");
        __syncwarp();
        if (lane == 0) red_release(&g_f[F_O + (head * 3 + t3) / 5][step], 1u);
        __syncwarp();
      }
    }
    cluster_sync_all();
  }
}

__device__ __forceinline__ uint32_t gelu2(uint32_t y, uint32_t s) {
  uint32_t g;
  asm("{\n.reg .b32 x, u, a, b;\nmov.b32 a, 0x28912891;\nmov.b32 b, 0x3a623a62;\nmul.rn.f16x2 x, %1, %2;\nmul.rn.f16x2 u, x, x;\nfma.rn.f16x2 u, u, a, b;\n"
      "mul.rn.f16x2 u, u, x;\ntanh.approx.f16x2 u, u;\nfma.rn.f16x2 %0, x, u, x;\n}" : "=r"(g) : "r"(y), "r"(s));
  return g; }

struct BParams {
  CUtensorMap wmap[5];
  CUtensorMap wo16;
  const __nv_bfloat16* x;
  __nv_bfloat16* out;
  uint64_t desc, desc32;
};
#define BO_O 0
#define BO_RES (6 * 8192)
#define OP_RES 63488
#define BO_STG (BO_RES + 2 * OP_RES)
#define BO_RING_OP (BO_STG + 16384)
#define OP_SLOT 12288
#define NS_OP 3
#define BO_H 81920
#define BO_W1 (BO_H + 16384)
#define BO_RING_MLP (BO_W1 + 81920)
#define BO_BAR 229376
#define BO_BOX (BO_BAR + 248)
#define BO_CARRY (BO_BAR + 512)
#define BO_STAT (BO_CARRY + 2048)
#define B_SMEM (BO_STAT + 256)
static_assert(B_SMEM <= 232448 && BO_RING_OP + NS_OP * OP_SLOT == BO_BAR && BO_RING_MLP + 3 * 16384 == BO_BAR && 2 * 83968 <= BO_RING_MLP, "smem");
enum { BB_W = 0, BB_FULL = 2, BB_TMP = BB_FULL + 3, BB_OFULL = BB_FULL + 5, BB_SFREE = BB_OFULL,
       BB_STAT = BB_SFREE + 6, BB_GO, BB_ZFREE, BB_DONE = BB_ZFREE + 3,
       BB_EMPTY, BB_START = BB_EMPTY, BB_USED = BB_EMPTY + 2, BB_NUM = BB_USED + 3 };
enum { NB_PP = 1, NB_H = 3, NB_END = 4, NB_END2 = 5, NB_STAGED = 6, NB_FREE = 8, NB_EARLY = 10, NB_LAST = 11 };

#define DESC_LO(off) (((SMEM0 + (off)) >> 4) | (1u << 16))

__device__ __forceinline__ uint32_t ld_relaxed(const uint32_t* p) { uint32_t v; asm volatile("ld.relaxed.gpu.global.b32 %0, [%1];" : "=r"(v) : "l"(p) : "memory"); return v; }
__device__ __forceinline__ int fmask(int r) { return (r < NSEG) | ((r >= LAG && r < NSTEP) << 1); }
__device__ __forceinline__ int bmask(int r) { return (r <= NSEG) | ((r >= LAG) << 1); }
__device__ __forceinline__ uint32_t rtarget(int mask) { return mask == 3 ? 64 : 32; }
__device__ __forceinline__ void warp_signal(uint32_t* p, int lane) {
  __syncwarp();
  asm volatile("{\n.reg .pred q;\nsetp.eq.u32 q, %1, 0;\n@q red.release.gpu.global.add.u32 [%0], 1;\n}" :: "l"(p), "r"(lane) : "memory");
}
__device__ __forceinline__ uint32_t pack2h(float lo, float hi) { uint32_t r; asm("cvt.rn.f16x2.f32 %0, %1, %2;" : "=r"(r) : "f"(hi), "f"(lo)); return r; }
template <bool H> __device__ __forceinline__ uint32_t pk(float lo, float hi) { return H ? pack2h(lo, hi) : pack2(lo, hi); }
template <int N, bool H> __device__ __forceinline__ void stage_out(const float* d, uint32_t dst, int warp, int lane) {
  const uint32_t sa = dst + ((lane >> 4) * 8 + (lane & 7)) * 128 + (((2 * warp + ((lane >> 3) & 1)) ^ (lane & 7)) << 4);
#pragma unroll
  for (int m = 0; m < N / 16; m++)
    stsm4t(sa + m * 2048, pk<H>(d[8 * m], d[8 * m + 1]), pk<H>(d[8 * m + 2], d[8 * m + 3]), pk<H>(d[8 * m + 4], d[8 * m + 5]), pk<H>(d[8 * m + 6], d[8 * m + 7]));
}
template <int N> __device__ __forceinline__ void acc_live(float* d) {
#pragma unroll
  for (int i = 0; i < N / 2; i++) asm volatile("" : "+f"(d[i]) :: "memory");
}
struct Ring {
  uint32_t sl, ph;
  template <int NS> __device__ __forceinline__ void step() { if (++sl == NS) { sl = 0; ph ^= 1; } }
};

#define KOFF(x) (DESC_LO(BO_O) + ((x) >> 2) * 512 + ((x) & 3) * 2)
template <int N, int P>
__device__ __forceinline__ void op_pass(const uint32_t* W, uint32_t bar, Dsc alo, Dsc blo, Dsc xlo, bool x2, Ring& rg, int wg, int warp, int lane, int r) {
  float acc[N / 2];
  blo.e = xlo.e = fresh<P + N / 64 * 5>(r);
  const Dsc tlo = blo + uni(rg.sl) * (OP_SLOT / 16), b2 = blo + (r & 1) * 1536;
  if (P == 0) mbar_waitu(bar + 8 * (BB_OFULL + 2 + (r & 1)), (r >> 1) & 1);
  CTS(5 * P);
  bar_sync(NB_PP + wg, 256);
  wg_fence();
#define OP_R(x, b) MM<N>::template rs<KOFF(4 * (x >> 1) + (x & 1)), (x != (P ? 0 : 4))>(acc, W + 32 * P + 4 * x, b);
#define OP_S(x, b) MM<N>::template ss<DESC_LO(BO_RES) + (6 * P + x) * 128, KOFF(4 * (x >> 1) + 2 + (x & 1)), 1>(acc, alo, b);
#define OP_T(x) MM<N>::template ss<DESC_LO(BO_RING_OP) + x * 128, KOFF(14 + x), 1>(acc, tlo, blo);
#define OP_B2() OP_R(4, b2) OP_S(4, b2) OP_R(5, b2) OP_S(5, b2)
  if (P == 0) { OP_B2() mbar_waitu(bar + 8 * BB_OFULL, r & 1); }
  OP_R(0, blo) OP_S(0, blo) OP_R(1, blo) OP_S(1, blo) OP_R(2, blo) OP_S(2, blo) OP_R(3, blo) OP_S(3, blo)
  if (P == 0) mbar_waitu(bar + 8 * (BB_OFULL + 1), r & 1);
  if (P == 4) wg_commit();
  if (P & 3) { OP_B2() }
  if (P == 1 && x2) MM<N>::template ss<DESC_LO(BO_RES) + 30 * 128, DESC_LO(BO_CARRY), 1>(acc, alo, xlo);
  mbar_waitu(bar + 8 * (BB_FULL + rg.sl), rg.ph);
  OP_R(6, blo) OP_T(0) OP_R(7, blo) OP_T(1)
  if (P == 4) { wg_commit(); wg_wait<1>(); bar_arrive(NB_EARLY, 288); CTS(21); wg_fence(); }
  OP_T(2) OP_T(3)
  if (P == 0) MM<N>::template rs<DESC_LO(BO_CARRY), 1>(acc, W + 160, xlo);
  OP_T(4) OP_T(5)
  if (P == 4) { wg_commit(); OP_B2() }
  wg_commit();
  bar_arrive(NB_PP + 1 - wg, 256);
  CTS(5 * P + 2);
  if (P == 4) { wg_wait<1>(); bar_arrive(NB_LAST, 288); }
  bar_sync(NB_FREE + wg, 160);
  wg_wait<0>();
  acc_live<N>(acc);
  mbar_arrive_if(lane == 0, bar + 8 * (BB_USED + rg.sl));
  CTS(5 * P + 3);
  stage_out<N, false>(acc, SMEM0 + BO_STG + wg * 8192, warp, lane);
  bar_arrive(NB_STAGED + wg, 160);
  CTS(5 * P + 4);
  rg.step<NS_OP>(); rg.step<NS_OP>();
}
template <int N>
__device__ __forceinline__ void op_round(const uint32_t* W, uint32_t bar, Dsc alo, Dsc blo, Dsc xlo, bool x2, Ring& rg, int wg, int warp, int lane, int r) {
  op_pass<N, 0>(W, bar, alo, blo, xlo, x2, rg, wg, warp, lane, r);
  op_pass<N, 1>(W, bar, alo, blo, xlo, x2, rg, wg, warp, lane, r);
  op_pass<N, 2>(W, bar, alo, blo, xlo, x2, rg, wg, warp, lane, r);
  op_pass<N, 3>(W, bar, alo, blo, xlo, x2, rg, wg, warp, lane, r);
  op_pass<N, 4>(W, bar, alo, blo, xlo, x2, rg, wg, warp, lane, r);
}
__device__ __forceinline__ void carry_in(uint32_t sb, int wg, int warp, int lane) {
  const int row = (lane >> 1) & 3;
  if (lane < 16) {
    const uint4 v = lds128(sb + BO_CARRY + (wg * 4 + warp) * 256 + lane * 16);
    sts128(sb + BO_H + wg * 8192 + (lane >> 3) * 4096 + row * 128 + (((2 * warp + (lane & 1)) ^ row) << 4), v.x, v.y, v.z, v.w);
  }
  __syncwarp();
}
#define STG 1
template <int N, int Z>
__device__ __forceinline__ void p1_pair(float* acc, const uint32_t* W, uint32_t bar, Dsc alo, Dsc blo, int lane, int r) {
  constexpr int ZOFF = N == 64 ? (2 * Z % 3) * 1024 : (Z / 2 * 2 % 3) * 1024 + (Z & 1) * 256;
  blo.e = fresh<10 + Z / 3 + N / 64 * 2>(r);
  mbar_waitu(bar + 8 * (BB_FULL + Z), r & 1);
  CTS(40 + Z);
  wg_fence();
#define P1_B(k) \
  MM<N, true>::template rs<DESC_LO(BO_RING_MLP) + ZOFF + k * 512, (2 * Z + k != 0)>(acc, W + 16 * Z + 8 * k, blo); \
  MM<N, true>::template ss<DESC_LO(BO_W1) + (2 * Z + k) * 512, DESC_LO(BO_RING_MLP) + ZOFF + k * 512 + 4, 1>(acc, alo, blo); \
  MM<N, true>::template rs<DESC_LO(BO_RING_MLP) + ZOFF + k * 512 + 2, 1>(acc, W + 16 * Z + 8 * k + 4, blo); \
  MM<N, true>::template ss<DESC_LO(BO_W1) + (2 * Z + k) * 512 + 128, DESC_LO(BO_RING_MLP) + ZOFF + k * 512 + 6, 1>(acc, alo, blo);
  P1_B(0)
  if (N == 64 && (Z == 1 || Z == 2)) { wg_commit(); wg_wait<1>(); mbar_arrive_if(lane == 0, bar + 8 * (BB_EMPTY + Z - 1)); wg_fence(); }
  P1_B(1)
  wg_commit();
}
template <int N>
__device__ __forceinline__ void phase1(const uint32_t* W, uint32_t sb, Dsc alo, Dsc blo, int half, int wg, int warp, int lane, bool shift, int off, int r) {
  float acc[N / 2];
  const uint32_t bar = sb + BO_BAR;
  CTS(30);
  p1_pair<N, 0>(acc, W, bar, alo, blo, lane, r);
  p1_pair<N, 1>(acc, W, bar, alo, blo, lane, r);
  p1_pair<N, 2>(acc, W, bar, alo, blo, lane, r);
  if (N == 64 && !wg) { mbar_waitu(bar + 8 * (BB_SFREE + 4), (r + 1) & 1); if (shift) carry_in(sb, wg, warp, lane); }
  p1_pair<N, 3>(acc, W, bar, alo, blo, lane, r);
  if (N == 32 || wg) { mbar_waitu(bar + 8 * (BB_SFREE + 4 + wg), (r + 1) & 1); if (shift) carry_in(sb, wg, warp, lane); }
  if (N == 32) mbar_arrive_if(lane < 2, bar + 8 * (BB_EMPTY + lane));
  if (STG && wg) bar_sync(NB_PP + 1, 256);
  p1_pair<N, 4>(acc, W, bar, alo, blo, lane, r);
  if (STG && !wg) bar_arrive(NB_PP + 1, 256);
  const int c = (lane >> 3) & 1, i0 = (lane >> 4) * 8 + (lane & 7) + off;
  uint32_t a0 = sb + BO_H + wg * 8192 + half * 4096 + i0 * 128 + (((2 * warp + c) ^ (i0 & 7)) << 4);
  uint32_t a1 = i0 >= 16 ? sb + BO_CARRY + (wg * 4 + warp) * 256 + half * 128 + (i0 - 16) * 32 + c * 16 : a0 + 2048, a3 = a1 + (i0 >= 16 ? 128 : 4096);
  asm volatile("" : "+r"(a0), "+r"(a1), "+r"(a3));
  mbar_waitu(bar + 8 * BB_STAT, r & 1);
  const uint32_t sa = sb + BO_STAT + (lane & 3) * 32 + half * 16;
  const uint4 t0 = lds128(sa), t1 = N == 64 ? lds128(sa + 16) : t0;
  const uint32_t t[8] = {t0.x, t0.y, t0.z, t0.w, t1.x, t1.y, t1.z, t1.w};
  { const uint32_t k4[4] = {a0, a1, a3, sa}; keep4(k4, lane); }
  wg_wait<0>();
  acc_live<N>(acc);
  CTS(32);
#pragma unroll
  for (int m = 0; m < N / 16; m++) {
    const float* d = acc + 8 * m;
    stsm4t(m == 1 ? a1 : m == 3 ? a3 : a0 + m * 2048, gelu2(pack2h(d[0], d[1]), t[2 * m]), gelu2(pack2h(d[2], d[3]), t[2 * m]),
           gelu2(pack2h(d[4], d[5]), t[2 * m + 1]), gelu2(pack2h(d[6], d[7]), t[2 * m + 1]));
  }
}
template <int N, int P>
__device__ __forceinline__ void p2_mma(float* acc, const uint32_t* W, Dsc alo, Dsc blo, int r) {
  blo.e = fresh<P + N / 64 * 5>(r);
  MM<N, true>::template rs<DESC_LO(BO_H), 0>(acc, W + 80 + 16 * P, blo);     MM<N, true>::template ss<DESC_LO(0) + P * 1024, DESC_LO(BO_H) + 512, 1>(acc, alo, blo);
  MM<N, true>::template rs<DESC_LO(BO_H) + 2, 1>(acc, W + 84 + 16 * P, blo); MM<N, true>::template ss<DESC_LO(0) + P * 1024 + 128, DESC_LO(BO_H) + 514, 1>(acc, alo, blo);
  MM<N, true>::template rs<DESC_LO(BO_H) + 4, 1>(acc, W + 88 + 16 * P, blo); MM<N, true>::template ss<DESC_LO(0) + P * 1024 + 512, DESC_LO(BO_H) + 516, 1>(acc, alo, blo);
  MM<N, true>::template rs<DESC_LO(BO_H) + 6, 1>(acc, W + 92 + 16 * P, blo); MM<N, true>::template ss<DESC_LO(0) + P * 1024 + 640, DESC_LO(BO_H) + 518, 1>(acc, alo, blo);
}
template <int N, int P, int T>
__device__ __forceinline__ void p2_pass(const uint32_t* W, uint32_t bar, Dsc alo, Dsc blo, int wg, int warp, int lane, int r) {
  float acc[N / 2], ac2[N / 2];
  CTS(5 * P);
  if (P || wg) bar_sync(NB_PP + wg, 256);
  wg_fence();
  p2_mma<N, P>(acc, W, alo, blo, r);
  wg_commit();
  if constexpr (T == 2) { p2_mma<N, P + 1>(ac2, W, alo, blo, r); wg_commit(); }
  if (P < 4 || !wg) bar_arrive(NB_PP + 1 - wg, 256);
  CTS(5 * P + 2);
  if (T == 1 && (P == 2 || P == 3)) mbar_waitu(bar + 8 * (BB_SFREE + 2 * (P - 2) + wg), r & 1);
  wg_wait<T - 1>();
  acc_live<N>(acc);
  if (P == 4) bar_sync(NB_H, 256);
  CTS(5 * P + 3);
  constexpr int K = P / T & 1;
  stage_out<N, true>(acc, SMEM0 + (P == 4 ? BO_H : BO_RING_MLP + (2 - K) * 16384) + wg * 8192, warp, lane);
  if constexpr (T == 2) {
    wg_wait<0>();
    acc_live<N>(ac2);
    stage_out<N, true>(ac2, SMEM0 + BO_RING_MLP + (2 - K) * 16384 + wg * 8192 + 4096, warp, lane);
  }
  bar_arrive(NB_STAGED + (P == 4 ? 4 : 2 * K) + wg, 160);
  CTS(5 * P + 4);
}
template <int N>
__device__ __forceinline__ void phase2(const uint32_t* W, uint32_t bar, Dsc alo, Dsc blo, int wg, int warp, int lane, int r) {
  if constexpr (N == 64) {
    p2_pass<N, 0, 1>(W, bar, alo, blo, wg, warp, lane, r);
    p2_pass<N, 1, 1>(W, bar, alo, blo, wg, warp, lane, r);
    p2_pass<N, 2, 1>(W, bar, alo, blo, wg, warp, lane, r);
    p2_pass<N, 3, 1>(W, bar, alo, blo, wg, warp, lane, r);
  } else {
    p2_pass<N, 0, 2>(W, bar, alo, blo, wg, warp, lane, r);
    p2_pass<N, 2, 2>(W, bar, alo, blo, wg, warp, lane, r);
  }
  p2_pass<N, 4, 1>(W, bar, alo, blo, wg, warp, lane, r);
}

__device__ __forceinline__ void ldg4(uint32_t* v, const void* p) {
  asm volatile("ld.relaxed.gpu.global.v4.u32 {%0,%1,%2,%3}, [%4];" : "=r"(v[0]), "=r"(v[1]), "=r"(v[2]), "=r"(v[3]) : "l"(p) : "memory"); }
__device__ __forceinline__ void stg4(void* p, const uint32_t* v) {
  asm volatile("st.global.v4.u32 [%0], {%1,%2,%3,%4};" :: "l"(p), "r"(v[0]), "r"(v[1]), "r"(v[2]), "r"(v[3]) : "memory"); }
struct RowPtr {
  unsigned char *p, *q, *t;
  __device__ __forceinline__ void ld(uint32_t* v, int o) const {
    ldg4(v, p + o); ldg4(v + 4, q + o);
    asm volatile("ld.relaxed.gpu.global.v2.u32 {%0,%1}, [%2];" : "=r"(v[8]), "=r"(v[9]) : "l"(t + o) : "memory");
  }
  __device__ __forceinline__ void st(const uint32_t* w, int o) const {
    stg4(p + o, w); stg4(q + o, w + 4);
    asm volatile("st.global.v2.u32 [%0], {%1,%2};" :: "l"(t + o), "r"(w[8]), "r"(w[9]) : "memory");
  }
};
__device__ __forceinline__ RowPtr row_img(int r, int n, int lane) {
  unsigned char* b = &g_acc[0][r % RD][n * 128];
  unsigned char* p = b + (uint32_t)((lane >> 3) * 8192 + (((lane ^ n) & 7) << 4));
  return {p, p + 32768, b + (uint32_t)(65536 + (lane >> 4) * 8192 + ((((lane >> 1) ^ n) & 7) << 4) + (lane & 1) * 8)};
}
__device__ __forceinline__ RowPtr row_ext(const void* lin, bool xn, int layer, int tok, int lane) {
  unsigned char* b = xn ? reinterpret_cast<unsigned char*>(&g_xn[layer][0]) + (uint32_t)((tok >> 5) * 40960 + ((tok >> 3) & 3) * 2560 + (tok & 7) * 32)
                        : (unsigned char*)lin + (uint32_t)(tok * 1280);
  const uint32_t o = (lane >> 1) * 256 + ((lane ^ (tok >> 2)) & 1) * 16;
  return {b + (uint32_t)(xn ? o + (lane >= 20 ? 7680 : 0) : lane * 16),
          b + (uint32_t)(xn ? o + 4096 + 7680 + (lane >= 8 ? 7680 : 0) + (lane >= 28 ? 7680 : 0) : lane * 16 + 512),
          b + (uint32_t)(xn ? (lane >> 2) * 256 + ((lane & 3) ^ ((tok >> 1) & 2)) * 8 + 8192 + 3 * 7680 : lane * 8 + 1024)};
}
__device__ __forceinline__ float2 h2f(uint32_t w) {
  float2 f; asm("{\n.reg .f16 l, h;\nmov.b32 {l, h}, %2;\ncvt.f32.f16 %0, l;\ncvt.f32.f16 %1, h;\n}" : "=f"(f.x), "=f"(f.y) : "r"(w)); return f; }
__device__ __forceinline__ float rsq(float x) { float y; asm("rsqrt.approx.ftz.f32 %0, %1;" : "=f"(y) : "f"(x)); return y; }
__device__ __forceinline__ void red_if(uint32_t v, const void* a) {
  asm volatile("{\n.reg .pred q;\nsetp.ne.u32 q, %1, 0;\n@q red.relaxed.gpu.global.add.u32 [%0], %1;\n}" :: "l"(a), "r"(v) : "memory"); }
__device__ __forceinline__ uint32_t dep0(uint32_t w, int lane) { uint32_t z; asm volatile("shr.b32 %0, %1, %2;" : "=r"(z) : "r"(w), "r"(lane + 32)); return z; }
__device__ __forceinline__ int lane_of(uint32_t w) {
  int lane; asm volatile("{\n.reg .u32 t;\nmov.u32 t, %%laneid;\nshr.u32 %0, %1, 20;\nadd.u32 %0, %0, t;\n}" : "=r"(lane) : "r"(w)); return lane; }
#define BUF (RD * TILE_B)
__device__ __forceinline__ int await(uint32_t v, const uint32_t* p, uint32_t target, bool lazy) {
  int n = 0;
  while (!__all_sync(~0u, v >= target)) {
    if (lazy) __nanosleep(200);
    if (++n > SPIN_LIMIT) FAIL();
    v = ld_relaxed(p);
  }
  asm volatile("fence.acquire.gpu;" ::: "memory");
  return lane_of(v);
}
template <int W> __device__ __forceinline__ void sum2(float& s, float& q, int lane) {
  const bool up = lane & (W / 2);
  float e = (up ? q : s) + __shfl_xor_sync(~0u, up ? s : q, W / 2);
#pragma unroll
  for (int o = W / 4; o; o >>= 1) e += __shfl_xor_sync(~0u, e, o);
  const float f = __shfl_xor_sync(~0u, e, W / 2);
  s = up ? f : e; q = up ? e : f;
}
template <int TYPE>
__device__ __forceinline__ void rrow(int r, int row, int tok, int lane, const uint32_t* go, int role, const __nv_bfloat16* x, __nv_bfloat16* out) {
  const int half = TYPE == 3 ? 0 : row >> 5;
  float v[20];
  float2 st = make_float2(1.f, 0.f);
  {
    uint32_t a[10], c[10], u[10], sh = 16;
    if (TYPE == 2) row_img(r + RD - ((row & 31) < 2), (row & 32) + ((row - 2) & 31), lane).ld(u, 3 * BUF);
    else row_ext(x, half, 1, tok, lane).ld(u, 0);
    if (TYPE == 2 || (TYPE == 0 && half))
      asm volatile("ld.relaxed.gpu.global.v2.f32 {%0,%1}, [%2];" : "=f"(st.x), "=f"(st.y) : "l"(g_stat + tok) : "memory");
    RowPtr ap = row_img(r, row, lane);
    const uint32_t g0 = TYPE != 3 ? ld_relaxed(go) : 0;
    if (TYPE != 3) {
      asm volatile("" : "+l"(ap.p), "+l"(ap.t));
      ap.q = ap.p + 32768;
      lane = await(g0, go, NOP * NW12 * NW34, false); BTS2(r, 8 + 2 * TYPE); RTS(0);
      ap.ld(a, TYPE ? 2 * BUF : 0);
    }
    if (TYPE == 0) {
      ap.ld(c, BUF);
      const uint32_t one = 0x3f803f80u | dep0(c[9], lane);
#pragma unroll
      for (int i = 0; i < 10; i++) asm volatile("fma.rn.bf16x2 %0, %0, %1, %2;" : "+r"(a[i]) : "r"(one), "r"(c[i]));
      sh |= dep0(a[9], lane);
    }
    const uint32_t z = TYPE == 2 ? dep0(a[9], lane) : 0;
#pragma unroll
    for (int i = 0; i < 10; i++) {
      if (TYPE == 2) { const float2 g = h2f(u[i] | z), h = h2f(a[i] | z); v[2 * i] = fmaf(h.x, 0.5f, g.x * st.x); v[2 * i + 1] = fmaf(h.y, 0.5f, g.y * st.x); continue; }
      float p = __uint_as_float(u[i] << sh), q = __uint_as_float(u[i] & (0xffffu << sh));
      if (TYPE == 0) { p = fmaf(p, st.x, bf_lo(a[i])); q = fmaf(q, st.x, bf_hi(a[i])); }
      v[2 * i] = p; v[2 * i + 1] = q;
    }
  }
  RTSD(1, v[19]);
  float s = 0.f, q = 0.f;
#pragma unroll
  for (int i = 0; i < 5; i++) {
    s += (v[4 * i] + v[4 * i + 1]) + (v[4 * i + 2] + v[4 * i + 3]);
    q += fmaf(v[4 * i], v[4 * i], v[4 * i + 1] * v[4 * i + 1]) + fmaf(v[4 * i + 2], v[4 * i + 2], v[4 * i + 3] * v[4 * i + 3]);
  }
  if (!(TYPE == 2 && half)) sum2<32>(s, q, lane);
  const float mean = s * (1.f / DM), var = fmaxf(q * (1.f / DM) - mean * mean, 0.f), rs = rsq(var + 1e-5f);
  const float k = TYPE == 0 ? 2.f * rs : half ? 1.f : rs, mr = TYPE && half ? st.y : -mean * k;
  RTSD(2, rs);
  uint32_t w[10];
#pragma unroll
  for (int i = 0; i < 10; i++) w[i] = pk<TYPE == 0>(fmaf(v[2 * i], k, mr), fmaf(v[2 * i + 1], k, mr));
  if (TYPE) row_ext(out, !half, TYPE == 2, tok, lane).st(w, 0);
  else {
    row_img(r, row, lane).st(w, 3 * BUF);
    row_img(r + ((row & 31) >= 30), (row & 32) + ((row + 2) & 31), lane).st(w, 2 * BUF);
    if (lane == 1) g_st2[0][r % RD][row] = (__float_as_uint(0.5f * rsq(fmaf(var * rs, rs, 1e-5f))) & ~127u) | (r + 1);
  }
  if (TYPE != 3 && lane == 0) g_stat[tok] = make_float2((var + 1e-5f) * rs * (TYPE ? 1.f : 0.5f), mean + st.y);
}
__device__ __forceinline__ void r2rows(int r, int row, int lane, const uint32_t* go) {
  const int n = row + (lane >> 4);
  const unsigned char* ap = &g_acc[2][r % RD][0] + (uint32_t)(n * 128 + ((lane >> 3) & 1) * 8192 + (((lane ^ n) & 7) << 4));
  const uint32_t* sp = &g_st2[1][r % RD][n];
  asm volatile("" : "+l"(ap), "+l"(sp));
  await(0, go, NOP * NW12 * NW34, false);
  BTS2(r, 10);
  uint32_t a[20];
#pragma unroll
  for (int i = 0; i < 5; i++) ldg4(a + 4 * i, ap + i * 16384);
  const uint32_t z = dep0(a[19], lane);
  float s = 0.f, q = 0.f, q2 = 0.f;
#pragma unroll
  for (int i = 0; i < 20; i++) { const float2 h = h2f(a[i] | z); s += h.x + h.y; q = fmaf(h.x, h.x, q); q2 = fmaf(h.y, h.y, q2); }
  q += q2;
  sum2<16>(s, q, lane);
  const float mean = s * (0.5f / DM), rs = rsq(fmaxf(q * (0.25f / DM) - mean * mean, 0.f) + 1e-5f);
  if ((lane & 15) == 0) asm volatile("st.relaxed.gpu.global.u32 [%0], %1;" :: "l"(sp), "r"((__float_as_uint(0.5f * rs) & ~127u) | (r + 1)) : "memory");
}
__device__ __forceinline__ void r3rows(int r, int row, int tok, int lane, __nv_bfloat16* out) {
  const int n = row + (lane >> 4), m = 32 + ((n - 2) & 31);
  const unsigned char* ap = &g_acc[0][r % RD][0] + (uint32_t)(n * 128 + ((lane >> 3) & 1) * 8192 + (((lane ^ n) & 7) << 4));
  const unsigned char* zp = &g_acc[3][(r + RD - (row == 32)) % RD][0] + (uint32_t)(m * 128 + ((lane >> 3) & 1) * 8192 + (((lane ^ m) & 7) << 4));
  unsigned char* op = reinterpret_cast<unsigned char*>(out) + (uint32_t)((tok + (lane >> 4)) * 1280 + (lane & 15) * 16);
  float2 st;
  asm volatile("ld.relaxed.gpu.global.v2.f32 {%0,%1}, [%2];" : "=f"(st.x), "=f"(st.y) : "l"(g_stat + tok + (lane >> 4)) : "memory");
#pragma unroll 1
  for (int i0 = 0; i0 < 2; i0++) {
    uint32_t a[12], u[12];
#pragma unroll
    for (int i = 0; i < 3; i++) { ldg4(a + 4 * i, ap + 2 * BUF + i * 16384); ldg4(u + 4 * i, zp + i * 16384); }
    uint32_t z = dep0(u[11], lane);
#pragma unroll
    for (int i = 0; i < 12; i++) {
      const float2 h = h2f(a[i] | z), g = h2f(u[i] | z);
      a[i] = pack2(fmaf(h.x, 0.5f, fmaf(g.x, st.x, st.y)), fmaf(h.y, 0.5f, fmaf(g.y, st.x, st.y)));
      if (i & 1) z = dep0(a[i], lane);
    }
    if (i0 == 0) stg4(op, a);
    stg4(op + 256, a + 4); stg4(op + 512, a + 8);
    ap += 32768; zp += 32768; op += 512;
  }
}
template <int TYPE>
__device__ __forceinline__ void rloop(int row, int cp, int role, const __nv_bfloat16* x, __nv_bfloat16* out) {
  constexpr int ST = TYPE == 4 ? 2 : TYPE;
  const int r0 = row & 32 ? LAG : 0;
  uint32_t v = 0;
  static_assert(NSEG + RD >= NSTEP, "no signals");
#pragma unroll 1
  for (int r = r0; r < (TYPE == 2 ? NR : TYPE == 4 ? NSEG + 1 : r0 + NSEG + (TYPE > 0)); r++) {
    if (TYPE == 2 && r == NSEG + 1) row += 32;
    const int tok = (r - (row & 32 ? LAG : 0)) * 32 + (row & 31) - (TYPE ? 2 : 0);
    const bool valid = TYPE == 0 || (unsigned)tok < S_LEN;
    const uint32_t* go = &g_f[F_R1 + 4 * ST + cp][r];
    const uint32_t* first = TYPE == 2 ? &g_f[F_R2 + cp][r] : TYPE ? go : (const uint32_t*)&g_xready[NSEG + r - r0][0];
    if constexpr (TYPE == 1) { r2rows(r, row, lane_of(r), go); BTS2(r, 11); continue; }
    if constexpr (TYPE == 4) {
      const int lane = await(v, go, NOP * NW12 * NW34, false);
      BTS2(r, 8 + 2 * ST); RTS(0);
      if (valid) r3rows(r, row, tok, lane, out);
    } else if constexpr (TYPE != 1) {
      if (TYPE || row >= 32) await(v, first, TYPE ? NOP * NW12 * NW34 : 32, true);
      if (valid) rrow<TYPE>(r, row, tok, lane_of(r), go, role, x, out);
    }
    if (TYPE > 1 && row >= 32 && r + RD - 1 >= NSTEP) { v = 0; BTS2(r, 13); continue; }
    const int lane = lane_of(r);
    const void* f = lane ? (const void*)&g_xready[NSEG + (tok >> 5)][0] : (const void*)&g_f[TYPE ? F_DONE : F_Z][r];
    asm volatile("" : "+l"(f));
    __syncwarp();
    RTS(3);
    v = ld_relaxed(first + (TYPE ? 1 : 8));
    asm volatile("fence.release.gpu;" ::: "memory");
    RTS(4);
    red_if(lane == 0 || (TYPE == 2 && lane == 1 && valid) ? (TYPE & 5 ? 2 : 1) : 0, f);
    RTS(5);
    RTS_OUT();
    BTS2(r, 9 + 2 * ST);
  }
}

#define SINGLE_OP 3
#define SINGLE_W 0
#define W_DELAY 0
#define BULK_ADD(T, dst, src, len) asm volatile("{\n.reg .pred e;\nelect.sync _|e, 0xffffffff;\n@e cp.reduce.async.bulk.global.shared::cta.bulk_group.add.noftz." T " [%0], [%1], %2;\n}" \
                                               :: "l"(dst), "r"(src), "r"(len) : "memory")
#define COMMIT() asm volatile("cp.async.bulk.commit_group;" ::: "memory")
#define DRAINED(n) do { asm volatile("cp.async.bulk.wait_group.read " #n ";" ::: "memory"); __syncwarp(); } while (0)
#define WRITTEN() do { asm volatile("cp.async.bulk.wait_group 0;\nfence.proxy.async.global;" ::: "memory"); __syncwarp(); } while (0)
__device__ __forceinline__ void wait_flags(const uint32_t* p, uint32_t target) {
  int n = 0;
  while (!__all_sync(~0u, ld_relaxed(p) >= target)) { if (++n > SPIN_LIMIT) FAIL(); }
  asm volatile("fence.acquire.gpu;" ::: "memory");
  asm volatile("fence.proxy.async.global;" ::: "memory");
}
__global__ void __launch_bounds__(512, 1) bworker_kernel(const __grid_constant__ BParams P) {
  extern __shared__ __align__(1024) unsigned char smem_raw[];
  const uint32_t sb = SMEM0, bar = sb + BO_BAR;
  const int wg = __shfl_sync(~0u, threadIdx.x >> 7, 0), warp = __shfl_sync(~0u, (threadIdx.x >> 5) & 3, 0);
  if (threadIdx.x == 0) {
    if (smem_u32(smem_raw) != SMEM0) FAIL();
    uint32_t smid; asm volatile("mov.u32 %0, %%smid;" : "=r"(smid));
    const uint32_t nb = ld_relaxed(&g_tpc[(smid >> 1) & 127]);
    const bool single = nb > 1, far = nb == 0 && (smid < 64 || smid >= 124);
    int kind = far || (single && atomicAdd(&g_f[F_MISC][35], 1u) < SINGLE_OP) ? 0 : single ? 1 + SINGLE_W : 1;
    int rc = single || (smid >> 1) == 16 || (smid >> 1) == 63 ? 1 : far ? 2 : 0;
    uint32_t i = atomicAdd(&g_f[F_MISC][32 + kind], 1u), o = atomicAdd(&g_f[F_MISC][36 + rc], 1u);
    while (i >= (kind == 0 ? NOP : kind == 1 ? NW12 : NW34)) { kind = (kind + 1) % 3; i = atomicAdd(&g_f[F_MISC][32 + kind], 1u); }
    while (o >= (rc == 0 ? 16 : rc == 1 ? 8 : 12)) { rc = (rc + 1) % 3; o = atomicAdd(&g_f[F_MISC][36 + rc], 1u); }
    sts64(sb + BO_BOX, i + (kind == 0 ? 0 : kind == 1 ? NOP : NOP + NW12), o + (rc ? 8 + 8 * rc : 0));
    for (int k = 0; k < BB_NUM; k++) mbar_init(bar + 8 * k, k >= BB_USED ? 4 : k >= BB_EMPTY ? 8 : k >= BB_ZFREE && kind ? 2 : 1);
    asm volatile("fence.mbarrier_init.release.cluster;" ::: "memory");
  }
  if (threadIdx.x < 128) sts128(sb + BO_CARRY + threadIdx.x * 16, 0u, 0u, 0u, 0u);
  auto ln0 = [&](int t) {
    const int lane = lane_of(t);
    if (lane < 20 && t + 128 < S_LEN) asm volatile("prefetch.global.L2 [%0];" :: "l"(P.x + (t + (t < 4 * NBC ? 4 * NBC : 128)) * DM + (lane >> 1) * 64));
    rrow<3>(0, 0, t, lane, nullptr, 0, P.x, nullptr);
    __syncwarp();
    asm volatile("fence.release.gpu;" ::: "memory");
    red_if(lane == 0, &g_xready[t >> 5][0]);
  };
  if (wg == 2) ln0(blockIdx.x * 4 + warp);
  fence_async();
  __syncthreads();
  const int role = uni(lds32(sb + BO_BOX));
  if (threadIdx.x < 32) BTS(94, 1);
  const bool op = role < NOP, w12 = role < NOP + NW12;
  const int j = op ? role : w12 ? role - NOP : role - NOP - NW12;
  const int rot = op ? (j ? 2 * ((j + 1) % 5) : 0) : 2 * (j % 5);
  if (wg == 3) {
    asm volatile("setmaxnreg.dec.sync.aligned.u32 24;");
    LANE_INIT();
    if (warp < 2) {
      auto announce = [&](int r) {
        const uint32_t* f = &g_f[(op ? F_R1 : w12 ? F_R2 : F_R3) + (lane & 3)][r];
        asm volatile("" : "+l"(f));
        if (warp == 0) { mbar_arrive_if(lane == 0, bar + 8 * BB_DONE); return; }
        mbar_waitw(bar + 8 * BB_DONE, r & 1);
        PTS(60);
        asm volatile("fence.release.gpu;" ::: "memory");
        red_if(lane >= 4 ? 0 : op ? NW12 * NW34 : w12 ? NOP * NW34 : NOP * NW12, f);
        PTS(61);
        BTS(r, 4);
      };
      if (op) {
        int mt = rot + warp;
        bar_arrive(NB_FREE + warp, 160);
#pragma unroll 1
        for (int r = 0; r < NSTEP; r++) {
          const uint32_t len = fmask(r) == 3 ? 8192 : 4096;
          unsigned char* acc = &g_acc[j & 1][r % RD][fmask(r) == 2 ? 4096 : 0];
#pragma unroll 1
          for (int p = 0; p < 5; p++) {
            bar_sync(NB_STAGED + warp, 160);
            PTS(50 + 2 * p + warp);
            fence_async();
            BULK_ADD("bf16", acc + mt * 8192, sb + BO_STG + warp * 8192, len);
            COMMIT();
            PTS(64 + 50 + 2 * p + warp);
            mt = mt >= 8 ? mt - 8 : mt + 2;
            DRAINED(0);
            bar_arrive(NB_FREE + warp, 160);
          }
          WRITTEN();
          announce(r);
        }
      } else {
#pragma unroll 1
        for (int r = 0; r < NR; r++) {
          const uint32_t len = bmask(r) == 3 ? 8192 : 4096;
          unsigned char* acc = &g_acc[2][r % RD][bmask(r) == 2 ? 4096 : 0];
          if (!w12) mbar_waitw(bar + 8 * BB_GO, r & 1);
          int mt = rot + warp;
          const bool pairs = len != 8192;
#pragma unroll 1
          for (int p = pairs ? 2 : 0; p < 5; p++) {
            const uint32_t src = sb + (p == 4 ? BO_H : BO_RING_MLP + (2 - (p & 1)) * 16384) + warp * 8192;
            bar_sync(NB_STAGED + (p == 4 ? 4 : 2 * (p & 1)) + warp, 160);
            PTS(50 + 2 * p + warp);
            fence_async();
            BULK_ADD("f16", acc + mt * 8192, src, len);
            mt = mt >= 8 ? mt - 8 : mt + 2;
            if (pairs && p < 4) { BULK_ADD("f16", acc + mt * 8192, src + 4096, len); mt = mt >= 8 ? mt - 8 : mt + 2; }
            COMMIT();
            PTS(64 + 50 + 2 * p + warp);
            if (p == 4 && !pairs) break;
            DRAINED(1);
            mbar_arrive_if(lane == 0 && p, bar + 8 * (p < 3 ? BB_SFREE + 2 * (p - 1) + warp : BB_ZFREE + (p >> 1)));
            mbar_arrive_if(lane == 0 && pairs && p == 2, bar + 8 * (BB_SFREE + warp));
            if (p == 3 && !pairs) { DRAINED(0); mbar_arrive_if(lane == 0, bar + 8 * (BB_ZFREE + 2)); }
          }
          WRITTEN();
          mbar_arrive_if(lane == 0, bar + 8 * (BB_SFREE + 4 + warp));
          announce(r);
        }
      }
    } else {
      if (op && warp == 2) {
        unsigned char* wt = g_wt + j * (10 * OP_SLOT);
#pragma unroll 1
        for (int m0 = 0; m0 < 10; m0 += 3) {
          const int nu = m0 < 9 ? 9 : 3;
          mbar_expect_if(lane == 0, bar + 8 * BB_TMP, nu * 4096);
#pragma unroll 1
          for (int k = 0; k < nu; k++) tma2d_e(sb + BO_RING_OP + k * 4096, &P.wmap[0], (m0 + k / 3) * 64, 320 * j + 224 + 32 * (k % 3), bar + 8 * BB_TMP);
          mbar_waitw(bar + 8 * BB_TMP, m0 & 1);
          bulk_s2g_e(wt + m0 * OP_SLOT, sb + BO_RING_OP, nu * 4096);
          COMMIT();
          WRITTEN();
        }
        asm volatile("fence.acq_rel.gpu;" ::: "memory");
        int sl = 0, ph = 1, mt = rot;
#pragma unroll 1
        for (int r = -1; r < NSTEP; r++) {
#pragma unroll 1
          for (int n = r < 0 ? 7 : 0; n < (r + 1 < NSTEP ? 10 : 7); n++) {
            mbar_waitw(bar + 8 * (BB_USED + sl), ph);
            mbar_expect_if(lane == 0, bar + 8 * (BB_FULL + sl), OP_SLOT);
            bulk_g2s_e(sb + BO_RING_OP + sl * OP_SLOT, wt + mt * OP_SLOT, OP_SLOT, bar + 8 * (BB_FULL + sl));
            if (++sl == 3) { sl = 0; ph ^= 1; }
            mt = mt == 9 ? 0 : mt + 1;
          }
        }
      } else if (op) {
        mbar_waitw(bar + 8 * BB_START, 0);
#pragma unroll 1
        for (int r = 0; r < NSTEP; r++) {
          const int rb = r - RD + 1;
          const uint32_t len = fmask(r) == 3 ? 8192 : 4096;
          const unsigned char* src = g_o + (uint32_t)(r % RO * (96 * 8192) + 5 * j * len);
          wait_flags(lane < 2 ? &g_f[F_O + (lane ? NOP : j)][r] : rb >= 0 ? &g_f[F_DONE][rb] : &g_f[F_MISC][0],
                     lane < 2 ? (lane ? 1 : 5) : rb >= 0 ? rtarget(bmask(rb)) : NBC * 8);
          PTS1(35);
          auto two = [&](int k, uint32_t mb) {
            bulk_g2s_e(sb + BO_O + k * 8192, src + k * len, len == 8192 ? 16384 : 4096, mb);
            if (len != 8192) bulk_g2s_e(sb + BO_O + k * 8192 + 8192, src + k * len + 4096, 4096, mb);
          };
          mbar_expect_if(lane == 0, bar + 8 * (BB_OFULL + 2 + (r & 1)), len);
          bulk_g2s_e(sb + BO_O + (r & 1 ? 5 : 2) * 8192, src + 2 * len, len, bar + 8 * (BB_OFULL + 2 + (r & 1)));
          if (r) bar_sync(NB_EARLY, 288);
          mbar_expect_if(lane < 2, bar + 8 * (BB_OFULL + lane), 2 * len + (lane ? len / 4 : 0));
          two(0, bar + 8 * BB_OFULL);
          PTS(62); PTS1(38);
          const unsigned char* sx = src + (95 - 5 * j) * len + (j + 1) / 5 * 1024;
          if (r) bar_sync(NB_LAST, 288);
          two(3, bar + 8 * (BB_OFULL + 1));
          bulk_g2s_e(sb + BO_CARRY, sx, 1024, bar + 8 * (BB_OFULL + 1));
          if (len == 8192) bulk_g2s_e(sb + BO_CARRY + 1024, sx + 4096, 1024, bar + 8 * (BB_OFULL + 1));
          if (r && r + 1 < NSTEP) {
            mbar_waitw(bar + 8 * (BB_USED + (10 * r - 2) % 3), (10 * r - 2) / 3 & 1);
            mbar_waitw(bar + 8 * (BB_USED + (10 * r - 1) % 3), (10 * r - 1) / 3 & 1);
          }
          PTS1(64 + 35);
          BTS(r, 0);
        }
      } else if (warp == 2) {
#pragma unroll 1
        for (int r = 0; r < NR; r++) {
          const int mk = w12 ? fmask(r) : bmask(r);
          if (mk) {
            const unsigned char* src = &g_acc[w12 ? 3 : 2][r % RD][mk == 2 ? 4096 : 0];
            wait_flags(&g_f[w12 ? F_Z : F_R2 + (j & 3)][r], w12 ? rtarget(mk) : NOP * NW12 * NW34);
#pragma unroll 1
            for (int z = 0; z < 5; z++) {
              const int k = mk == 3 ? z : z >> 1;
              const uint32_t fb = bar + 8 * (BB_FULL + z), dst = sb + BO_RING_MLP + 2 * k % 3 * 16384 + (mk == 3 ? 0 : (z & 1) * 4096);
              if (mk == 3 || !(z & 1)) mbar_waitw(bar + 8 * (k < 3 ? BB_ZFREE + k : BB_EMPTY + k - 3), (r + (k < 3)) & 1);
              if (z == 0) PTS(62);
              mbar_expect_if(lane == 0, fb, mk == 3 ? 16384 : 8192);
              bulk_g2s_e(dst, src + z * 16384, mk == 3 ? 16384 : 4096, fb);
              if (mk != 3) bulk_g2s_e(dst + 8192, src + z * 16384 + 8192, 4096, fb);
              if (z == 0) BTS(r, 0);
            }
          }
          if (!w12) {
#pragma unroll 1
            for (int z = mk == 3 ? 2 : 0; z < 5; z++) mbar_waitw(bar + 8 * (BB_FULL + z), r & 1);
            red_if(lane == 0, &g_f[F_GOT][r]);
#pragma unroll 1
            for (int c = j; c < 80; c += NW34) bulk_s2g_e(&g_acc[c / 40][r % RD][c % 40 * 2048], sb + BO_CARRY, 2048);
            COMMIT();
            wait_flags(&g_f[F_GOT][r], NW34);
            mbar_arrive_if(lane == 0, bar + 8 * BB_GO);
            WRITTEN();
          }
          mbar_waitw(bar + 8 * BB_DONE, (r + 1) & 1);
          mbar_arrive_if(lane == 0, bar + 8 * BB_DONE);
        }
      } else {
#pragma unroll 1
        for (int r = 0; r < (w12 ? NSTEP : NR); r++) {
          const bool idle = !((w12 ? fmask(r) : bmask(r)) >> (lane >> 4) & 1);
          uint32_t t0, t1;
          int n = 0;
          mbar_waitw(bar + 8 * BB_FULL, r & 1);
          do {
            asm volatile("ld.relaxed.gpu.global.v2.u32 {%0,%1}, [%2];" : "=r"(t0), "=r"(t1) : "l"(&g_st2[!w12][r % RD][2 * lane]) : "memory");
            if (++n > SPIN_LIMIT) FAIL();
          } while (!__all_sync(~0u, idle || (((t0 ^ (r + 1)) | (t1 ^ (r + 1))) & 127) == 0));
          sts32(sb + BO_STAT + (lane & 3) * 32 + (lane >> 2) * 4, pack2h(__uint_as_float(t0), __uint_as_float(t1)));
          __syncwarp();
          mbar_arrive_if(lane == 0, bar + 8 * BB_STAT);
          PTS(63);
        }
      }
    }
    bar_arrive(NB_END, 512);
  } else if (wg == 2) {
    asm volatile("setmaxnreg.dec.sync.aligned.u32 40;");
    const int ord = uni(lds32(sb + BO_BOX + 4));
    const int g2 = warp * 12 + ord - 24, gw = ord < 16 ? warp * 16 + ord : ord < 24 ? 80 + warp * 8 + ord : g2 < 32 ? 64 + g2 : 96 + g2;
    const int row = gw < 64 ? gw : gw < 96 ? gw - 64 : gw < 128 ? 2 * gw - 192 : 2 * gw - 224;
    if (row >= 32) {
#pragma unroll 1
      for (int t = 4 * NBC + (gw < 64 ? gw - 32 : gw - 80); t < S_LEN; t += 64) ln0(t);
    }
    if (gw < 64) rloop<0>(row, gw & 3, role, P.x, P.out);
    else if (gw < 96) rloop<2>(row, gw & 3, role, P.x, P.out);
    else if (gw < 128) rloop<1>(row, gw & 3, role, P.x, P.out);
    else rloop<4>(row, gw & 3, role, P.x, P.out);
    asm volatile("griddepcontrol.wait;" ::: "memory");
    const int t = threadIdx.x & 127;
    for (int i = (blockIdx.x * 128 + t) * 4; i < 4 * NCL * 2560; i += NBC * 512)
      *reinterpret_cast<uint4*>(&g_part[0][0][0][0] + i) = make_uint4(0u, 0u, 0u, 0u);
    bar_sync(NB_END, 512);
    if (t == 0) {
      uint32_t n;
      asm volatile("atom.acq_rel.gpu.global.add.u32 %0, [%1], 1;" : "=r"(n) : "l"(&g_f[F_MISC][64]) : "memory");
      sts32(sb + BO_BOX, n);
    }
    bar_sync(NB_END2, 128);
    if (lds32(sb + BO_BOX) == NBC - 1) {
      for (int i = t; i < F_NUM * 24; i += 128) reinterpret_cast<uint4*>(&g_f[0][0])[i] = make_uint4(0u, 0u, 0u, 0u);
      g_xready[t][0] = 0; g_tpc[t] = 0;
    }
  } else {
    asm volatile("setmaxnreg.inc.sync.aligned.u32 224;");
    LANE_INIT();
    for (int i = blockIdx.x * 256 + threadIdx.x; i < 2 * RD * TILE_B / 16; i += NBC * 256) reinterpret_cast<uint4*>(&g_acc[0][0][0])[i] = make_uint4(0u, 0u, 0u, 0u);
    warp_signal(&g_f[F_MISC][0], lane);
    const int mt0 = (rot + wg) % 10;
    auto boxes = [&](int ss) {
      const int nb = op && ss ? 3 : 4;
      const uint32_t base = sb + (ss ? BO_RES + wg * OP_RES : wg * 83968);
      mbar_expect_if(warp == 0 && lane == 0, bar + 8 * (BB_W + wg), nb * 20480 + (op ? 2048 : 0));
      bar_sync(NB_H, 256);
      if (warp < nb) {
#pragma unroll 1
        for (int i = warp; i < 5 * nb; i += nb) {
          const int p = op ? i / nb : (i - 10) >> 1, mt = (mt0 + 2 * p) % 10;
          const bool first = !op && i < 10;
          tma2d_e(op || !ss ? base + i * 4096 : sb + (first ? BO_W1 : -81920) + (2 * i + wg) * 4096, &P.wmap[op ? 0 : (w12 ? 1 : 3) + !first], first ? 128 * j + 64 * wg : mt * 64,
                  op ? 320 * j + 64 * warp + 32 * ss : first ? 64 * i + 32 * ss : 128 * j + 32 * (i & 1) + 64 * ss, bar + 8 * (BB_W + wg));
        }
      }
      if (op && warp == 3) tma2d_e(base + nb * 20480, &P.wo16, (mt0 + 2 * ss) % 10 * 64, 95 * 64 + (j + 1) / 5 * 16, bar + 8 * (BB_W + wg));
      mbar_waitw(bar + 8 * (BB_W + wg), ss);
    };
    if (W_DELAY && !op) __nanosleep(W_DELAY);
    uint32_t W[164];
    boxes(0);
    load_w<41>(W, sb + wg * 83968, warp, lane);
    fence_async();
    boxes(1);
    if (!op) {
      float cs[2] = {0.f, 0.f};
      const uint32_t a0 = sb + BO_W1 + wg * 4096 + ((lane >> 4) * 8 + (lane & 7)) * 128 + (((warp * 2 + ((lane >> 3) & 1)) ^ (lane & 7)) << 4);
#pragma unroll
      for (int i = 0; i < 80; i++) cs[i & 1] += bf_lo(W[i]) + bf_hi(W[i]);
#pragma unroll 1
      for (int i = 0; i < 60; i++) {
        uint32_t t[4];
        const uint32_t ad = a0 + (i % 20 >> 1) * 8192 + (i & 1) * 2048 - (i >= 40 ? BO_W1 : 0);
        ldsm4t(t[0], t[1], t[2], t[3], ad);
#pragma unroll
        for (int k = 0; k < 4; k++) {
          if (i < 20) cs[k & 1] += bf_lo(t[k]) + bf_hi(t[k]);
          const float mu = i < 40 ? cs[k & 1] : 0.f;
          t[k] = pack2h(bf_lo(t[k]) - mu, bf_hi(t[k]) - mu);
        }
        if (i >= 20) stsm4t(ad, t[0], t[1], t[2], t[3]);
        if (i == 19) {
#pragma unroll
          for (int k = 0; k < 2; k++) { cs[k] += __shfl_xor_sync(~0u, cs[k], 1); cs[k] += __shfl_xor_sync(~0u, cs[k], 2); cs[k] *= 1.f / DM; }
        }
      }
      const uint32_t z = dep0(__float_as_uint(cs[0]), lane);
#pragma unroll
      for (int i = 0; i < 80; i++) { W[i] = pack2h(bf_lo(W[i] | z) - cs[i & 1], bf_hi(W[i] | z) - cs[i & 1]); W[80 + i] = pack2h(bf_lo(W[80 + i]), bf_hi(W[80 + i])); }
      fence_async();
      bar_sync(NB_H, 256);
    }
    if (warp == 0) BTS(94, 6 + wg);
    const Dsc blo = {P.desc, 1}, alo = blo + wg * (op ? OP_RES / 16 : 256);
    if (op) {
      Ring rg = {(uint32_t)wg, 0};
      mbar_arrive_if(lane == 0, bar + 8 * BB_START);
      if (wg) bar_arrive(NB_PP, 256);
      const Dsc xlo = {P.desc32, 1};
#pragma unroll 1
      for (int r = 0; r < NSTEP; r++) {
        asm volatile("" : "+r"(lane));
        if (fmask(r) == 3) op_round<64>(W, bar, alo, blo, xlo, j == 0, rg, wg, warp, lane, r);
        else op_round<32>(W, bar, alo, blo, xlo, j == 0, rg, wg, warp, lane, r);
        if (warp == 0) BTS(r, 2 + wg);
      }
    } else {
      const int q4 = (128 * j + 64 * wg + 16 * warp) / 160, off = w12 ? (0x0413 >> (4 * q4)) & 7 : 0;
#pragma unroll 1
      for (int r = 0; r < NR; r++) {
        asm volatile("" : "+r"(lane));
        const int bm = bmask(r), fm = w12 ? fmask(r) : bm;
        if (fm == 3) phase1<64>(W, sb, alo, blo, 0, wg, warp, lane, w12, off, r);
        else if (fm) phase1<32>(W, sb, alo, blo, fm >> 1, wg, warp, lane, w12, off, r);
        else { mbar_waitu(bar + 8 * (BB_SFREE + 4 + wg), (r + 1) & 1); carry_in(sb, wg, warp, lane); }
        CTS(33);
        fence_async();
        bar_sync(NB_H, 256);
        mbar_arrive_if(wg == 1 && warp == 0 && lane < 2, bar + 8 * BB_ZFREE);
        if (wg + warp == 0) BTS(r, 1);
        if (bm == 3) phase2<64>(W, bar, alo, blo, wg, warp, lane, r);
        else phase2<32>(W, bar, alo, blo + (bm >> 1) * 256, wg, warp, lane, r);
        if (warp == 0) BTS(r, 2 + wg);
      }
    }
    CTS_OUT();
    bar_arrive(NB_END, 512);
  }
}

typedef CUresult (*EncodeFn)(CUtensorMap*, CUtensorMapDataType, cuuint32_t, void*, const cuuint64_t*, const cuuint64_t*, const cuuint32_t*,
                             const cuuint32_t*, CUtensorMapInterleave, CUtensorMapSwizzle, CUtensorMapL2promotion, CUtensorMapFloatOOBfill);
static void make_map(EncodeFn fn, CUtensorMap* tm, const void* ptr, uint64_t cols, uint64_t rows, uint32_t bc, uint32_t br) {
  cuuint64_t dims[2] = {cols, rows}; cuuint64_t strides[1] = {cols * 2}; cuuint32_t box[2] = {bc, br}; cuuint32_t es[2] = {1, 1};
  fn(tm, CU_TENSOR_MAP_DATA_TYPE_BFLOAT16, 2, const_cast<void*>(ptr), dims, strides, box, es, CU_TENSOR_MAP_INTERLEAVE_NONE,
     CU_TENSOR_MAP_SWIZZLE_128B, CU_TENSOR_MAP_L2_PROMOTION_L2_256B, CU_TENSOR_MAP_FLOAT_OOB_FILL_NONE);
}
#define dbg_a_only 0
extern "C" void kernel_launch(void* const* d_in, const int* in_sizes, int n_in, void* d_out, int out_size) {
  void* fnp = nullptr; cudaDriverEntryPointQueryResult qr;
  cudaGetDriverEntryPoint("cuTensorMapEncodeTiled", &fnp, cudaEnableDefault, &qr);
  EncodeFn fn = (EncodeFn)fnp;
  cudaStream_t st = cudaStreamPerThread;
  cudaFuncSetAttribute(bworker_kernel, cudaFuncAttributeMaxDynamicSharedMemorySize, B_SMEM);
  {
    AMaps M;
    for (int i = 0; i < 3; i++) make_map(fn, &M.w16[i], d_in[2 + i], HD, DM, 64, 16);
    M.wv = (const __nv_bfloat16*)d_in[4];
    make_map(fn, &M.wo32, d_in[5], DM, HD, 64, 32);
    const uint32_t hi[5] = {dhi(TILE_SBO, 3), dhi(1024, 1), dhi(1024, 0), dhi(PL_SZ, 0), dhi(896, 0)};
    for (int i = 0; i < 5; i++) M.d[i] = (uint64_t)hi[i] << 32;
    cudaFuncSetAttribute(acore_kernel, cudaFuncAttributeMaxDynamicSharedMemorySize, A_SMEM);
    cudaFuncSetAttribute(acore_kernel, cudaFuncAttributeNonPortableClusterSizeAllowed, 1);
    cudaLaunchConfig_t cfg = {};
    cfg.gridDim = dim3(CL_SIZE * NCL); cfg.blockDim = dim3(512); cfg.dynamicSmemBytes = A_SMEM; cfg.stream = st;
    cudaLaunchAttribute at[1]; at[0].id = cudaLaunchAttributeClusterDimension;
    at[0].val.clusterDim.x = CL_SIZE; at[0].val.clusterDim.y = 1; at[0].val.clusterDim.z = 1;
    cfg.attrs = at; cfg.numAttrs = 1;
    cudaLaunchKernelEx(&cfg, acore_kernel, M, (const __nv_bfloat16*)d_in[1], dbg_a_only ? 0 : 1);
  }
  if (!dbg_a_only) {
    BParams P;
    make_map(fn, &P.wmap[0], d_in[5], DM, HD, 64, 32);
    make_map(fn, &P.wo16, d_in[5], DM, HD, 64, 16);
    make_map(fn, &P.wmap[1], d_in[8], DM, DM, 64, 32);
    make_map(fn, &P.wmap[2], d_in[9], DM, DM, 64, 32);
    make_map(fn, &P.wmap[3], d_in[10], FF, DM, 64, 32);
    make_map(fn, &P.wmap[4], d_in[11], DM, FF, 64, 32);
    P.x = (const __nv_bfloat16*)d_in[0];
    P.out = (__nv_bfloat16*)d_out;
    P.desc = (uint64_t)dhi(1024, 1) << 32;
    P.desc32 = (uint64_t)dhi(256, 3) << 32;
    cudaLaunchConfig_t cfg = {};
    cfg.gridDim = dim3(NBC); cfg.blockDim = dim3(512); cfg.dynamicSmemBytes = B_SMEM; cfg.stream = st;
    cudaLaunchAttribute at[1]; at[0].id = cudaLaunchAttributeProgrammaticStreamSerialization; at[0].val.programmaticStreamSerializationAllowed = 1;
    cfg.attrs = at; cfg.numAttrs = 1;
    cudaLaunchKernelEx(&cfg, bworker_kernel, P);
  }
}
```

```cpp
#include <cuda_runtime.h>
#include <cuda_bf16.h>
#include <cuda.h>
#include <stdint.h>

#define S_LEN 2048
#define DM 640
#define NH 32
#define DH 192
#define HD 6144
#define NSEG 64
#define FF 1536

__device__ __forceinline__ uint32_t smem_u32(const void* p) { return (uint32_t)__cvta_generic_to_shared(p); }
__device__ __forceinline__ uint32_t mapa(uint32_t a, uint32_t r) {
  uint32_t o; asm volatile("mapa.shared::cluster.u32 %0, %1, %2;" : "=r"(o) : "r"(a), "r"(r)); return o; }
__device__ __forceinline__ void mbar_init(uint32_t b, uint32_t c) {
  asm volatile("mbarrier.init.shared::cta.b64 [%0], %1;" :: "r"(b), "r"(c) : "memory"); }
__device__ __forceinline__ void mbar_expect(uint32_t b, uint32_t tx) {
  asm volatile("mbarrier.arrive.expect_tx.shared::cta.b64 _, [%0], %1;" :: "r"(b), "r"(tx) : "memory"); }
__device__ __forceinline__ void mbar_arrive(uint32_t b) {
  asm volatile("mbarrier.arrive.shared::cta.b64 _, [%0];" :: "r"(b) : "memory"); }
__device__ __forceinline__ void mbar_arrive_remote(uint32_t rb) {
  asm volatile("mbarrier.arrive.relaxed.cluster.shared::cluster.b64 _, [%0];" :: "r"(rb) : "memory"); }
__device__ __forceinline__ void mbar_expect_if(bool p, uint32_t b, uint32_t tx) {
  asm volatile("{\n.reg .pred q;\nsetp.ne.u32 q, %2, 0;\n@q mbarrier.arrive.expect_tx.shared::cta.b64 _, [%0], %1;\n}" :: "r"(b), "r"(tx), "r"((uint32_t)p) : "memory"); }
__device__ __forceinline__ void mbar_arrive_if(bool p, uint32_t b) {
  asm volatile("{\n.reg .pred q;\nsetp.ne.u32 q, %1, 0;\n@q mbarrier.arrive.shared::cta.b64 _, [%0];\n}" :: "r"(b), "r"((uint32_t)p) : "memory"); }
__device__ __forceinline__ void mbar_arrive_remote_if(bool p, uint32_t rb) {
  asm volatile("{\n.reg .pred q;\nsetp.ne.u32 q, %1, 0;\n@q mbarrier.arrive.relaxed.cluster.shared::cluster.b64 _, [%0];\n}" :: "r"(rb), "r"((uint32_t)p) : "memory"); }
__device__ __forceinline__ void sts32_if(bool p, uint32_t a, uint32_t v) {
  asm volatile("{\n.reg .pred q;\nsetp.ne.u32 q, %2, 0;\n@q st.shared.b32 [%0], %1;\n}" :: "r"(a), "r"(v), "r"((uint32_t)p) : "memory"); }
__device__ __forceinline__ void sts128z_if(bool p, uint32_t a) {
  asm volatile("{\n.reg .pred q;\nsetp.ne.u32 q, %1, 0;\n@q st.shared.v4.b32 [%0], {0,0,0,0};\n}" :: "r"(a), "r"((uint32_t)p) : "memory"); }
__device__ __forceinline__ bool mbar_try(uint32_t b, uint32_t ph) {
  uint32_t ok;
  asm volatile("{\n.reg .pred p;\nmbarrier.try_wait.parity.shared::cta.b64 p, [%1], %2;\nselp.u32 %0, 1, 0, p;\n}"
               : "=r"(ok) : "r"(b), "r"(ph) : "memory");
  return ok; }
__device__ __forceinline__ bool mbar_test(uint32_t b, uint32_t ph) {
  uint32_t ok;
  asm volatile("{\n.reg .pred p;\nmbarrier.test_wait.parity.shared::cta.b64 p, [%1], %2;\nselp.u32 %0, 1, 0, p;\n}"
               : "=r"(ok) : "r"(b), "r"(ph) : "memory");
  return ok; }
#define SPIN_LIMIT 4000000
#define FAIL() asm volatile("st.global.u32 [%0], 0;" :: "l"(8ull) : "memory")
#define CFENCE() asm volatile("fence.proxy.async::generic.acquire.sync_restrict::shared::cluster.cluster;" ::: "memory")
__device__ __forceinline__ void mbar_wait(uint32_t b, uint32_t ph) {
  int n = 0;
  while (!mbar_try(b, ph)) { if (++n > SPIN_LIMIT) FAIL(); } }
#define TIMEOUT_ACT "@!p st.shared.u32 [%0+1], 0;"
#define WAIT_HINT ", 20000"
#define WAIT_LIM "200000"
__device__ __forceinline__ void mbar_slow(uint32_t b, uint32_t ph) {
  asm volatile("{\n.reg .pred p, q;\n.reg .u32 n;\nmov.u32 n, 0;\n"
               "WL:\nmbarrier.try_wait.parity.shared::cta.b64 p, [%0], %1" WAIT_HINT ";\nadd.u32 n, n, 1;\nsetp.lt.and.u32 q, n, " WAIT_LIM ", !p;\n@q bra.uni WL;\n"
               TIMEOUT_ACT "\n}" :: "r"(b), "r"(ph) : "memory"); }
__device__ __forceinline__ void mbar_waitw(uint32_t b, uint32_t ph) {
  asm volatile("{\n.reg .pred p, q;\n.reg .u32 n;\nmbarrier.try_wait.parity.shared::cta.b64 p, [%0], %1;\n@p bra.uni WD;\nmov.u32 n, 0;\n"
               "WL:\nmbarrier.try_wait.parity.shared::cta.b64 p, [%0], %1" WAIT_HINT ";\nadd.u32 n, n, 1;\nsetp.lt.and.u32 q, n, " WAIT_LIM ", !p;\n@q bra.uni WL;\n"
               TIMEOUT_ACT "\nWD:\n}" :: "r"(b), "r"(ph) : "memory"); }
__device__ __forceinline__ void mbar_waitw2(uint32_t b0, uint32_t b1, uint32_t ph) {
  uint32_t ok;
  asm volatile("{\n.reg .pred p, r;\nmbarrier.try_wait.parity.shared::cta.b64 p, [%1], %3;\nmbarrier.try_wait.parity.shared::cta.b64 r, [%2], %3;\n"
               "and.pred p, p, r;\nselp.u32 %0, 1, 0, p;\n}" : "=r"(ok) : "r"(b0), "r"(b1), "r"(ph) : "memory");
  if (__builtin_expect(!__all_sync(~0u, ok), 0)) { mbar_slow(b0, ph); mbar_slow(b1, ph); }
}
__device__ __forceinline__ void mbar_waitu(uint32_t b, uint32_t ph) {
  asm volatile("{\n.reg .pred p;\nmbarrier.try_wait.parity.shared::cta.b64 p, [%0], %1;\n@p bra.uni WD;\n"
               "WL:\nmbarrier.try_wait.parity.shared::cta.b64 p, [%0], %1" WAIT_HINT ";\n@!p bra.uni WL;\nWD:\n}" :: "r"(b), "r"(ph) : "memory"); }
__device__ __forceinline__ void mbar_waitu2(uint32_t b0, uint32_t b1, uint32_t ph) {
  asm volatile("{\n.reg .pred p, r;\nWL:\nmbarrier.try_wait.parity.shared::cta.b64 p, [%0], %2;\nmbarrier.try_wait.parity.shared::cta.b64 r, [%1], %2;\n"
               "and.pred p, p, r;\n@!p bra.uni WL;\n}" :: "r"(b0), "r"(b1), "r"(ph) : "memory"); }
__device__ __forceinline__ void mbar_waitw4(uint32_t b, uint32_t ph) { mbar_waitw2(b, b + 8, ph); mbar_waitw2(b + 16, b + 24, ph); }
__device__ __forceinline__ uint32_t clock32() { uint32_t t; asm volatile("mov.u32 %0, %%clock;" : "=r"(t) :: "memory"); return t; }
template <int L> __device__ __forceinline__ uint32_t lop3(uint32_t a, uint32_t b, uint32_t c) {
  uint32_t r; asm("lop3.b32 %0, %1, %2, %3, %4;" : "=r"(r) : "r"(a), "r"(b), "r"(c), "n"(L)); return r; }
__device__ __forceinline__ void st_async_v2_if(bool p, uint32_t a, uint32_t v0, uint32_t v1, uint32_t mb) {
  asm volatile("{\n.reg .pred q;\nsetp.ne.u32 q, %4, 0;\n@q st.async.weak.shared::cluster.mbarrier::complete_tx::bytes.v2.b32 [%0], {%1,%2}, [%3];\n}"
               :: "r"(a), "r"(v0), "r"(v1), "r"(mb), "r"((uint32_t)p) : "memory"); }
__device__ __forceinline__ void keep4(const uint32_t* r, int lane) {
  asm volatile("{\n.reg .pred q;\nsetp.lt.s32 q, %4, 0;\n@q st.shared.v4.b32 [%4], {%0,%1,%2,%3};\n}" :: "r"(r[0]), "r"(r[1]), "r"(r[2]), "r"(r[3]), "r"(lane) : "memory"); }
__device__ __forceinline__ void fence_sched(int i) {
  asm volatile("{\n.reg .pred q;\nsetp.gt.s32 q, %0, 4096;\n@q st.shared.u32 [%0], 0;\n}" :: "r"(i) : "memory"); }
__device__ __forceinline__ uint32_t hmax2bf(uint32_t a, uint32_t b) { uint32_t r; asm("max.bf16x2 %0, %1, %2;" : "=r"(r) : "r"(a), "r"(b)); return r; }
__device__ __forceinline__ uint32_t uni(uint32_t x) { return __shfl_sync(~0u, x, 0); }
__device__ __forceinline__ void bulk_g2s_mc_e(uint32_t dst, const void* src, uint32_t bytes, uint32_t mb, uint16_t mask) {
  asm volatile("{\n.reg .pred e;\nelect.sync _|e, 0xffffffff;\n"
               "@e cp.async.bulk.shared::cluster.global.mbarrier::complete_tx::bytes.multicast::cluster [%0], [%1], %2, [%3], %4;\n}"
               :: "r"(dst), "l"(src), "r"(bytes), "r"(mb), "h"(mask) : "memory"); }
__device__ __forceinline__ void bulk_s2g_e(void* dst, uint32_t src, uint32_t bytes) {
  asm volatile("{\n.reg .pred e;\nelect.sync _|e, 0xffffffff;\n@e cp.async.bulk.global.shared::cta.bulk_group [%0], [%1], %2;\n}"
               :: "l"(dst), "r"(src), "r"(bytes) : "memory"); }
__device__ __forceinline__ void bulk_g2s_e(uint32_t dst, const void* src, uint32_t bytes, uint32_t mb) {
  asm volatile("{\n.reg .pred e;\nelect.sync _|e, 0xffffffff;\n@e cp.async.bulk.shared::cluster.global.mbarrier::complete_tx::bytes [%0], [%1], %2, [%3];\n}"
               :: "r"(dst), "l"(src), "r"(bytes), "r"(mb) : "memory"); }
#define STREAM_HINT 1
__device__ __forceinline__ void bulk_s2g_es(void* dst, uint32_t src, uint32_t bytes) {
  asm volatile("{\n.reg .pred e;\n.reg .b64 pol;\ncreatepolicy.fractional.L2::evict_first.b64 pol;\nelect.sync _|e, 0xffffffff;\n"
               "@e cp.async.bulk.global.shared::cta.bulk_group.L2::cache_hint [%0], [%1], %2, pol;\n}" :: "l"(dst), "r"(src), "r"(bytes) : "memory");
}
__device__ __forceinline__ void bulk_g2s_es(uint32_t dst, const void* src, uint32_t bytes, uint32_t mb) {
  asm volatile("{\n.reg .pred e;\n.reg .b64 pol;\ncreatepolicy.fractional.L2::evict_first.b64 pol;\nelect.sync _|e, 0xffffffff;\n"
               "@e cp.async.bulk.shared::cluster.global.mbarrier::complete_tx::bytes.L2::cache_hint [%0], [%1], %2, [%3], pol;\n}"
               :: "r"(dst), "l"(src), "r"(bytes), "r"(mb) : "memory"); }
__device__ __forceinline__ void tma2d_e(uint32_t dst, const CUtensorMap* tm, int c0, int c1, uint32_t mb) {
  asm volatile("{\n.reg .pred e;\nelect.sync _|e, 0xffffffff;\n"
               "@e cp.async.bulk.tensor.2d.shared::cluster.global.mbarrier::complete_tx::bytes [%0], [%1, {%3, %4}], [%2];\n}"
               :: "r"(dst), "l"((uint64_t)tm), "r"(mb), "r"(c0), "r"(c1) : "memory"); }
__device__ __forceinline__ uint32_t hadd2bf(uint32_t a, uint32_t b) {
  uint32_t r; asm("add.rn.bf16x2 %0, %1, %2;" : "=r"(r) : "r"(a), "r"(b)); return r; }
__device__ __forceinline__ void cluster_sync_all() {
  asm volatile("barrier.cluster.arrive.release.aligned;\nbarrier.cluster.wait.acquire.aligned;" ::: "memory"); }
__device__ __forceinline__ void bar_arrive(int id, int n) { asm volatile("bar.arrive %0, %1;" :: "r"(id), "r"(n) : "memory"); }
__device__ __forceinline__ void bar_arrive_dep(int id, int n, uint32_t dep) {
  asm volatile("{\n.reg .u32 t;\nand.b32 t, %2, 0;\nadd.u32 t, t, %0;\nbar.sync t, %1;\n}" :: "r"(id), "r"(n), "r"(dep) : "memory"); }
__device__ __forceinline__ void bar_sync(int id, int n) { asm volatile("bar.sync %0, %1;" :: "r"(id), "r"(n) : "memory"); }
__device__ __forceinline__ void fence_async() { asm volatile("fence.proxy.async.shared::cta;" ::: "memory"); }
__device__ __forceinline__ void st_async_b32(uint32_t a, uint32_t v, uint32_t mb) {
  asm volatile("st.async.weak.shared::cluster.mbarrier::complete_tx::bytes.b32 [%0], %1, [%2];" :: "r"(a), "r"(v), "r"(mb) : "memory"); }
__device__ __forceinline__ void st_async_v2(uint32_t a, uint32_t v0, uint32_t v1, uint32_t mb) {
  asm volatile("st.async.weak.shared::cluster.mbarrier::complete_tx::bytes.v2.b32 [%0], {%1,%2}, [%3];" :: "r"(a), "r"(v0), "r"(v1), "r"(mb) : "memory"); }
__device__ __forceinline__ void st_async_v4(uint32_t a, uint32_t v0, uint32_t v1, uint32_t v2, uint32_t v3, uint32_t mb) {
  asm volatile("st.async.weak.shared::cluster.mbarrier::complete_tx::bytes.v4.b32 [%0], {%1,%2,%3,%4}, [%5];" :: "r"(a), "r"(v0), "r"(v1), "r"(v2), "r"(v3), "r"(mb) : "memory"); }
__device__ __forceinline__ void ldsm4(uint32_t& r0, uint32_t& r1, uint32_t& r2, uint32_t& r3, uint32_t a) {
  asm volatile("ldmatrix.sync.aligned.m8n8.x4.shared.b16 {%0,%1,%2,%3}, [%4];" : "=r"(r0), "=r"(r1), "=r"(r2), "=r"(r3) : "r"(a) : "memory"); }
__device__ __forceinline__ void ldsm4t(uint32_t& r0, uint32_t& r1, uint32_t& r2, uint32_t& r3, uint32_t a) {
  asm volatile("ldmatrix.sync.aligned.m8n8.x4.trans.shared.b16 {%0,%1,%2,%3}, [%4];" : "=r"(r0), "=r"(r1), "=r"(r2), "=r"(r3) : "r"(a) : "memory"); }
__device__ __forceinline__ void stsm2t(uint32_t a, uint32_t r0, uint32_t r1) {
  asm volatile("stmatrix.sync.aligned.m8n8.x2.trans.shared.b16 [%0], {%1,%2};" :: "r"(a), "r"(r0), "r"(r1) : "memory"); }
__device__ __forceinline__ void stsm4t(uint32_t a, uint32_t r0, uint32_t r1, uint32_t r2, uint32_t r3) {
  asm volatile("stmatrix.sync.aligned.m8n8.x4.trans.shared.b16 [%0], {%1,%2,%3,%4};" :: "r"(a), "r"(r0), "r"(r1), "r"(r2), "r"(r3) : "memory"); }
__device__ __forceinline__ uint32_t movm(uint32_t a) {
  uint32_t d; asm volatile("movmatrix.sync.aligned.m8n8.trans.b16 %0, %1;" : "=r"(d) : "r"(a)); return d; }
__device__ __forceinline__ void mma16816(float* d, uint32_t a0, uint32_t a1, uint32_t a2, uint32_t a3, uint32_t b0, uint32_t b1) {
  asm("mma.sync.aligned.m16n8k16.row.col.f32.bf16.bf16.f32 {%0,%1,%2,%3}, {%4,%5,%6,%7}, {%8,%9}, {%0,%1,%2,%3};"
               : "+f"(d[0]), "+f"(d[1]), "+f"(d[2]), "+f"(d[3]) : "r"(a0), "r"(a1), "r"(a2), "r"(a3), "r"(b0), "r"(b1)); }
__device__ __forceinline__ void mma16816v(float* d, uint32_t a0, uint32_t a1, uint32_t a2, uint32_t a3, uint32_t b0, uint32_t b1) {
  asm volatile("mma.sync.aligned.m16n8k16.row.col.f32.bf16.bf16.f32 {%0,%1,%2,%3}, {%4,%5,%6,%7}, {%8,%9}, {%0,%1,%2,%3};"
               : "+f"(d[0]), "+f"(d[1]), "+f"(d[2]), "+f"(d[3]) : "r"(a0), "r"(a1), "r"(a2), "r"(a3), "r"(b0), "r"(b1)); }
__device__ __forceinline__ uint32_t pack2(float lo, float hi) {
  uint32_t r; asm("cvt.rn.bf16x2.f32 %0, %1, %2;" : "=r"(r) : "f"(hi), "f"(lo)); return r; }
__device__ __forceinline__ uint32_t pack2v(float lo, float hi) {
  uint32_t r; asm volatile("cvt.rn.bf16x2.f32 %0, %1, %2;" : "=r"(r) : "f"(hi), "f"(lo)); return r; }
__device__ __forceinline__ float bf_lo(uint32_t w) { return __uint_as_float(w << 16); }
__device__ __forceinline__ float bf_hi(uint32_t w) { return __uint_as_float(w & 0xffff0000u); }
__device__ __forceinline__ uint4 lds128(uint32_t a) {
  uint4 v; asm volatile("ld.shared.v4.b32 {%0,%1,%2,%3}, [%4];" : "=r"(v.x), "=r"(v.y), "=r"(v.z), "=r"(v.w) : "r"(a) : "memory"); return v; }
__device__ __forceinline__ uint4 lds128_nv(uint32_t a) {
  uint4 v; asm volatile("ld.shared.v4.b32 {%0,%1,%2,%3}, [%4];" : "=r"(v.x), "=r"(v.y), "=r"(v.z), "=r"(v.w) : "r"(a)); return v; }
__device__ __forceinline__ void st_async_v2_nm(uint32_t a, uint32_t v0, uint32_t v1, uint32_t mb) {
  asm volatile("st.async.weak.shared::cluster.mbarrier::complete_tx::bytes.v2.b32 [%0], {%1,%2}, [%3];" :: "r"(a), "r"(v0), "r"(v1), "r"(mb)); }
__device__ __forceinline__ float rcpf(float x) { float y; asm("rcp.approx.ftz.f32 %0, %1;" : "=f"(y) : "f"(x)); return y; }
__device__ __forceinline__ void sts64(uint32_t a, uint32_t x, uint32_t y) { asm volatile("st.shared.v2.b32 [%0], {%1,%2};" :: "r"(a), "r"(x), "r"(y) : "memory"); }
__device__ __forceinline__ float ex2(float x) { float y; asm("ex2.approx.ftz.f32 %0, %1;" : "=f"(y) : "f"(x)); return y; }
__device__ __forceinline__ uint32_t lds32(uint32_t a) {
  uint32_t v; asm volatile("ld.shared.b32 %0, [%1];" : "=r"(v) : "r"(a) : "memory"); return v; }
__device__ __forceinline__ uint2 lds64(uint32_t a) {
  uint2 v; asm volatile("ld.shared.v2.b32 {%0,%1}, [%2];" : "=r"(v.x), "=r"(v.y) : "r"(a) : "memory"); return v; }
__device__ __forceinline__ void sts128(uint32_t a, uint32_t x, uint32_t y, uint32_t z, uint32_t w) {
  asm volatile("st.shared.v4.b32 [%0], {%1,%2,%3,%4};" :: "r"(a), "r"(x), "r"(y), "r"(z), "r"(w) : "memory"); }
__device__ __forceinline__ void sts32(uint32_t a, uint32_t x) { asm volatile("st.shared.b32 [%0], %1;" :: "r"(a), "r"(x) : "memory"); }
__device__ __forceinline__ void tma2d(uint32_t dst, const CUtensorMap* tm, int c0, int c1, uint32_t mb) {
  asm volatile("cp.async.bulk.tensor.2d.shared::cluster.global.mbarrier::complete_tx::bytes [%0], [%1, {%3, %4}], [%2];"
               :: "r"(dst), "l"((uint64_t)tm), "r"(mb), "r"(c0), "r"(c1) : "memory"); }
__device__ __forceinline__ void tma2d_prefetch(const CUtensorMap* tm, int c0, int c1) {
  asm volatile("cp.async.bulk.prefetch.tensor.2d.L2.global.tile [%0, {%1, %2}];" :: "l"((uint64_t)tm), "r"(c0), "r"(c1) : "memory"); }
__device__ __forceinline__ void bulk_g2s_mc(uint32_t dst, const void* src, uint32_t bytes, uint32_t mb, uint16_t mask) {
  asm volatile("cp.async.bulk.shared::cluster.global.mbarrier::complete_tx::bytes.multicast::cluster [%0], [%1], %2, [%3], %4;"
               :: "r"(dst), "l"(src), "r"(bytes), "r"(mb), "h"(mask) : "memory"); }
__device__ __forceinline__ void bulk_s2g(void* dst, uint32_t src, uint32_t bytes) {
  asm volatile("cp.async.bulk.global.shared::cta.bulk_group [%0], [%1], %2;" :: "l"(dst), "r"(src), "r"(bytes) : "memory"); }
__device__ __forceinline__ void wg_fence() { asm volatile("wgmma.fence.sync.aligned;" ::: "memory"); }
__device__ __forceinline__ void wg_commit() { asm volatile("wgmma.commit_group.sync.aligned;" ::: "memory"); }
template <int N> __device__ __forceinline__ void wg_wait() { asm volatile("wgmma.wait_group.sync.aligned %0;" :: "n"(N) : "memory"); }
__device__ __forceinline__ uint64_t mkdesc(uint32_t addr, uint32_t lbo, uint32_t sbo, uint32_t swz) {
  return (uint64_t)((addr & 0x3FFFF) >> 4) | ((uint64_t)(lbo >> 4) << 16) | ((uint64_t)(sbo >> 4) << 32) | ((uint64_t)swz << 62); }

#define ACC4(d) "+f"(d[0]),"+f"(d[1]),"+f"(d[2]),"+f"(d[3])
#define ACC8(d) ACC4(d), ACC4((d + 4))
#define ACC16(d) ACC8(d), ACC8((d + 8))
#define ACC20(d) ACC16(d), ACC4((d + 16))
#define ACC24(d) ACC16(d), ACC8((d + 16))
#define SMEM0 0x400
__host__ __device__ constexpr uint32_t dlo(uint32_t off, uint32_t lbo) { return ((SMEM0 + off) >> 4) | ((lbo >> 4) << 16); }
__host__ __device__ constexpr uint32_t dhi(uint32_t sbo, uint32_t swz) { return (sbo >> 4) | (swz << 30); }
#define R4S "{%0,%1,%2,%3}"
#define R8S "{%0,%1,%2,%3,%4,%5,%6,%7}"
#define R16S "{%0,%1,%2,%3,%4,%5,%6,%7,%8,%9,%10,%11,%12,%13,%14,%15}"
#define R20S "{%0,%1,%2,%3,%4,%5,%6,%7,%8,%9,%10,%11,%12,%13,%14,%15,%16,%17,%18,%19}"
#define R24S "{%0,%1,%2,%3,%4,%5,%6,%7,%8,%9,%10,%11,%12,%13,%14,%15,%16,%17,%18,%19,%20,%21,%22,%23}"
#define ACC32(d) ACC16(d), ACC16((d + 16))
#define R32S "{%0,%1,%2,%3,%4,%5,%6,%7,%8,%9,%10,%11,%12,%13,%14,%15,%16,%17,%18,%19,%20,%21,%22,%23,%24,%25,%26,%27,%28,%29,%30,%31}"
struct Dsc {
  uint64_t b; uint32_t e;
  __device__ __forceinline__ Dsc operator+(uint32_t o) const { return {b + o, e}; }
};
template <int K> __device__ __forceinline__ uint32_t fresh(int i) {
  uint32_t e; asm volatile("{\n.reg .u32 t;\nadd.u32 t, %1, %2;\nshr.u32 %0, t, %3;\n}" : "=r"(e) : "r"(i), "n"((256 << K) + 1), "n"(8 + K)); return e; }
template <int N, bool H = false> struct MM;
#define DEF_MM(N, H, T, ACCM, RS_, I0, I1, I2, I3, I4, I5, I6, I7)                                                                \
  template <> struct MM<N, H> {                                                                                                   \
    template <uint32_t BLO, int ACC>                                                                                              \
    static __device__ __forceinline__ void rs(float* d, const uint32_t* a, Dsc b0) {                                              \
      asm volatile("{\n.reg .b64 b;\nmad.wide.u32 b, %" #I7 ", %" #I5 ", %" #I4 ";\n"                                             \
                   "wgmma.mma_async.sync.aligned.m64n" #N "k16.f32." T "." T " " RS_ ", {%" #I0 ",%" #I1 ",%" #I2 ",%" #I3 "}, b, %" #I6 ", 1, 1, 0;\n}" \
                   : ACCM(d) : "r"(a[0]), "r"(a[1]), "r"(a[2]), "r"(a[3]), "l"(b0.b), "n"(BLO), "n"(ACC), "r"(b0.e)); }           \
    template <uint32_t ALO, uint32_t BLO, int ACC, int TA = 1>                                                                    \
    static __device__ __forceinline__ void ss(float* d, Dsc a0, Dsc b0) {                                                         \
      asm volatile("{\n.reg .b64 a, b;\nmad.wide.u32 a, %" #I6 ", %" #I1 ", %" #I0 ";\nmad.wide.u32 b, %" #I6 ", %" #I3 ", %" #I2 ";\n" \
                   "wgmma.mma_async.sync.aligned.m64n" #N "k16.f32." T "." T " " RS_ ", a, b, %" #I4 ", 1, 1, %" #I5 ", 0;\n}"    \
                   : ACCM(d) : "l"(a0.b), "n"(ALO), "l"(b0.b), "n"(BLO), "n"(ACC), "n"(TA), "r"(b0.e)); }                         \
  };
DEF_MM(8, false, "bf16", ACC4, R4S, 4, 5, 6, 7, 8, 9, 10, 11)
DEF_MM(16, false, "bf16", ACC8, R8S, 8, 9, 10, 11, 12, 13, 14, 15)
DEF_MM(32, false, "bf16", ACC16, R16S, 16, 17, 18, 19, 20, 21, 22, 23)
DEF_MM(40, false, "bf16", ACC20, R20S, 20, 21, 22, 23, 24, 25, 26, 27)
DEF_MM(48, false, "bf16", ACC24, R24S, 24, 25, 26, 27, 28, 29, 30, 31)
DEF_MM(64, false, "bf16", ACC32, R32S, 32, 33, 34, 35, 36, 37, 38, 39)
DEF_MM(32, true, "f16", ACC16, R16S, 16, 17, 18, 19, 20, 21, 22, 23)
DEF_MM(64, true, "f16", ACC32, R32S, 32, 33, 34, 35, 36, 37, 38, 39)

#define LAG 10
#define NSTEP (NSEG + LAG)
#define NR (NSTEP + 1)
__device__ __align__(1024) __nv_bfloat16 g_xn[2][S_LEN * DM];
#define RO 16
static_assert(RO > LAG + 1, "ring");
__device__ __align__(1024) unsigned char g_o[RO * 96 * 8192];
__device__ __align__(1024) uint32_t g_part[6][7][40][64];
#define RD 16
static_assert(2 * RD <= NSEG && NR < 96, "the tags of the last lap differ from those of the first");
#define TILE_B 81920
__device__ __align__(1024) float2 g_stat[S_LEN];
__device__ __align__(1024) uint32_t g_st2[2][RD][64];
__device__ __align__(1024) unsigned char g_acc[4][RD][TILE_B];
#define NOP 19
#define NW12 5
#define NW34 12
#define NBC (NOP + NW12 + NW34)
__device__ __align__(1024) unsigned char g_wt[NOP * 10 * 12288];
__device__ __align__(1024) unsigned char g_wx[NW12 + NW34][16384];
enum { F_O = 0, F_R1 = NOP + 1, F_R2 = F_R1 + 4, F_R3 = F_R2 + 4, F_Z = F_R3 + 4, F_DONE, F_GOT, F_MISC, F_NUM };
__device__ __align__(128) uint32_t g_f[F_NUM][96];
__device__ __align__(128) int g_xready[129][8];
__device__ uint32_t g_tpc[128];
#define TS(i)
#define TSV(i, v)
#define TSN(i)
#define TSD(i, dep)
#define BTS(k, i)
#define BTS2(k, i)
#define RTS(i)
#define RTSD(i, dep)
#define RTS_OUT()
#define CTS(i)
#define PTS(i)
#define PTS1(i)
#define CTS_OUT()
#define GTS(i)

#define CL_SIZE 15
#define NCL 7
#define SSQ 13
#define SSV 16
#define PL_SZ 5376
#define TILE_SBO 2560
#define TILE_GRP 15360
#define WS_SZ ((2 * SSQ + SSV) * 2048)
#define OFF_QK (OFF_WO + 26 * 2048)
#define LAYOUT 2
#define OFF_TILE 0
#define OFF_WS (4 * TILE_GRP)
#define OFF_WO (OFF_WS + WS_SZ)
#define OFF_PL (OFF_QK + 20480)
#define OFF_BAR (OFF_PL + 2 * PL_SZ)
#define STG_Q OFF_TILE
#define STG_K OFF_WO
#define VA 14
#define STG_V2 (OFF_TILE + 27 * 2048)
#define OFF_O (OFF_PL + 4352)
#define LAND(k) (((k) >> 1) * TILE_GRP + ((k) & 1) * 1280)
#define LAND_F (5 * TILE_SBO)
#define OFF_XL (OFF_TILE + 3 * TILE_GRP)
#define OFF_XF (OFF_XL + LAND_F)
#define OFF_WT ((OFF_XL + TILE_SBO + 1023) & ~1023)
#define OFF_TAB (OFF_BAR + 240)
#define OFF_INV (OFF_TAB + 64)
#define OFF_TS (OFF_INV + 128)
#define A_SMEM 232448
static_assert(WS_SZ + 72 * 1024 + 2 * PL_SZ + 4 * TILE_GRP + 512 == A_SMEM && OFF_WS % 1024 == 0 && OFF_WO % 1024 == 0 && SSQ == 13, "smem map");
enum { B_W0 = 0, B_W1, B_F1, B_F2 = B_F1 + 4, B_R1 = B_F2 + 4, B_R2, B_MEMFREE, B_LANDFREE, B_OPEER, B_PLFREE, B_XFREE, B_SB, B_WOF = B_SB + 6, B_WTF, B_RS, B_NUM = B_RS + 4 };
static_assert(B_NUM <= 30, "barriers");
enum { N_C = 0, N_SISS, N_QK, N_V, N_PM, N_TURN, N_PI, N_VGO, N_O, N_PX, N_AB, N_SDONE, N_VDONE, N_G3, N_P, N_OX };

__device__ __forceinline__ bool is_dual(int j) { return j >= LAG && j < NSEG; }
__device__ __forceinline__ int sched_l(int j) { return j < NSEG ? j : NSEG + j - LAG; }
__device__ __forceinline__ int sched_f(int j) { return NSEG + j - LAG; }
__device__ __forceinline__ void wait_cnt(const int* p, int target) {
  int v, n = 0;
  do {
    asm volatile("ld.relaxed.gpu.global.b32 %0, [%1];" : "=r"(v) : "l"(p) : "memory");
    if (v >= target) break;
    if (++n > SPIN_LIMIT) FAIL();
  } while (true);
  asm volatile("fence.acquire.gpu;" ::: "memory");
  asm volatile("fence.proxy.async.global;" ::: "memory");
}
__device__ __forceinline__ void red_release(void* p, uint32_t v) { asm volatile("red.release.gpu.global.add.u32 [%0], %1;" :: "l"(p), "r"(v) : "memory"); }
__device__ __forceinline__ void red_relaxed(void* p, uint32_t v) { asm volatile("red.relaxed.gpu.global.add.u32 [%0], %1;" :: "l"(p), "r"(v) : "memory"); }
#define VMASK 0xa5294a5294ull
__host__ __device__ constexpr int popc40(unsigned long long m) { int c = 0; for (; m; m &= m - 1) c++; return c; }
static_assert(popc40(VMASK) == SSV, "mask");
__host__ __device__ constexpr int ss_idx(int ks, int n) { return n == SSV ? popc40(VMASK & ((1ull << ks) - 1)) : ks * n / 40; }
__host__ __device__ constexpr bool is_ss(int ks, int n) { return ss_idx(ks + 1, n) != ss_idx(ks, n); }
__host__ __device__ constexpr int rs_idx(int ks, int n) { return ks - ss_idx(ks, n); }

#define SL2 (0.07216878364870322f * 1.4426950408889634f)

#define SUM_LOOP 0
struct Desc { Dsc tile, unit, k1, pl, p; };
__device__ __forceinline__ Desc make_desc(const uint64_t* h, uint32_t u, uint32_t e) {
  return {{h[0], e}, {h[1] + u * 128, e}, {h[2], e}, {h[3], e}, {h[4], e}};
}
template <int N, int NSS, int RG, int KS, int K1, int K0 = 0>
__device__ __forceinline__ void proj(float* acc, const uint32_t* W, const Desc& D) {
  if constexpr (KS < K1) {
    constexpr uint32_t BLO = dlo(OFF_TILE + (KS / 10) * TILE_GRP + RG * TILE_SBO + (KS % 10) * 256, 128);
    if constexpr (is_ss(KS, NSS)) MM<N>::template ss<dlo(OFF_WS + ss_idx(KS, NSS) * 2048, 0), BLO, (KS != K0)>(acc, D.unit, D.tile);
    else MM<N>::template rs<BLO, (KS != K0)>(acc, W + rs_idx(KS, NSS) * 4, D.tile);
    proj<N, NSS, RG, KS + 1, K1, K0>(acc, W, D);
  }
}
#define VST 17
template <int KS>
__device__ __forceinline__ void ld_rest(uint32_t* W, const uint32_t* p) {
  if constexpr (KS < 40) {
    if constexpr (!is_ss(KS, SSV) && rs_idx(KS, SSV) >= VST) {
#pragma unroll
      for (int i = 0; i < 4; i++) W[4 * rs_idx(KS, SSV) + i] = __ldg(p + (KS * 16 + (i >> 1) * 8) * (HD / 2) + (i & 1) * 4);
    }
    ld_rest<KS + 1>(W, p);
  }
}
template <int N>
__device__ __forceinline__ void load_w(uint32_t* W, uint32_t stage, int warp, int lane) {
  const int kr = (lane >> 4) * 8 + (lane & 7);
  const int cb = warp * 2 + ((lane >> 3) & 1);
  const uint32_t a0 = stage + kr * 128 + ((cb ^ (lane & 7)) << 4);
#pragma unroll
  for (int i = 0; i < N; i++) ldsm4t(W[4 * i], W[4 * i + 1], W[4 * i + 2], W[4 * i + 3], a0 + i * 2048);
}
template <int N, int G, int U, int OS, int ACC>
__device__ __forceinline__ void wo4(float* d, const Desc& D) {
  constexpr uint32_t WA = (U >= 4 ? OFF_WO + (U - 4) * 2048 : OFF_WT) - G * SSQ * 2048, OB = OS == 0 ? OFF_O : OS == 1 ? OFF_XL : OFF_XF;
  Dsc b = OS ? D.k1 : D.pl;
  b.e = fresh<(U < 16 ? U / 4 : U / 8 - 2) + (N == 8 ? 4 : 0)>(D.unit.e);
  MM<N>::template ss<dlo(WA, 0), dlo(OB, 128), ACC>(d, D.unit, b);
  MM<N>::template ss<dlo(WA + 2048, 0), dlo(OB + 256, 128), 1>(d, D.unit, b);
  MM<N>::template ss<dlo(WA + 4096, 0), dlo(OB + 512, 128), 1>(d, D.unit, b);
  MM<N>::template ss<dlo(WA + 6144, 0), dlo(OB + 768, 128), 1>(d, D.unit, b);
}
__device__ __forceinline__ void wo_coord(int i, int t3, int head, int& c0, int& c1) {
  const int g = i >> 1;
  const int blk = g == 0 ? 9 : (g < 4 ? g - 1 : (g - 4) >> 1) * 3 + t3;
  int sl = g < 4 ? t3 : (g & 1) ? t3 + 1 : t3 + 2;
  if (sl >= 3) sl -= 3;
  c0 = blk * 64; c1 = head * DH + sl * 64 + (i & 1) * 32;
}
__device__ __forceinline__ void tok_softmax(uint32_t sb, int job, int lane) {
  const bool w1 = job & 1;
  const int dg = (lane >> 2) - (lane & 3) * 2;
  const uint32_t lo = sb + OFF_PL + (job >> 1) * PL_SZ + (job & 1) * 1792, l8 = lo + 512 + lane * 8, pa = lo + lane * 4;
  const uint32_t km = job & 2 ? 640 : 512;
  float x[14];
  {
    const uint4 a = lds128(lo + lane * 16);
    const uint2 e = lds64(l8);
    const uint32_t c = lds32(768 + pa);
    x[0] = bf_lo(a.x); x[1] = bf_hi(a.x); x[2] = bf_lo(a.y); x[3] = bf_hi(a.y); x[4] = bf_lo(a.z); x[5] = bf_hi(a.z); x[6] = bf_lo(a.w); x[7] = bf_hi(a.w);
    x[8] = bf_lo(c); x[9] = bf_hi(c); x[10] = bf_lo(e.x); x[11] = bf_hi(e.x); x[12] = bf_lo(e.y); x[13] = bf_hi(e.y);
  }
  if (dg < 0) { x[8] = -INFINITY; if (w1) x[4] = -INFINITY; else x[10] = -INFINITY; }
  if (dg < 1) { x[9] = -INFINITY; if (w1) x[5] = -INFINITY; else x[11] = -INFINITY; }
  const float m4 = fmaxf(x[8], x[9]);
  float m0 = fmaxf(fmaxf(fmaxf(x[0], x[1]), fmaxf(x[2], x[3])), fmaxf(fmaxf(x[4], x[5]), fmaxf(x[6], x[7])));
  float m1 = fmaxf(fmaxf(x[10], x[11]), fmaxf(x[12], x[13]));
  if (w1) m1 = fmaxf(m1, m4); else m0 = fmaxf(m0, m4);
  m0 = fmaxf(m0, __shfl_xor_sync(~0u, m0, 1)); m1 = fmaxf(m1, __shfl_xor_sync(~0u, m1, 1));
  sts32(pa + (w1 ? 384 : 896 + 128), 0u); sts32(pa + 1152 - km, 0u); sts32(pa + 896 + 1152 - km, 0u); sts64(l8 + 896 - 256, 0u, 0u);
  m0 = fmaxf(m0, __shfl_xor_sync(~0u, m0, 2)); m1 = fmaxf(m1, __shfl_xor_sync(~0u, m1, 2));
  m0 *= -SL2; m1 *= -SL2;
#pragma unroll
  for (int j = 0; j < 14; j++) x[j] = ex2(fmaf(x[j], SL2, j < 8 ? m0 : j >= 10 ? m1 : w1 ? m1 : m0));
  const float l4s = x[8] + x[9];
  float l0 = ((x[0] + x[1]) + (x[2] + x[3])) + ((x[4] + x[5]) + (x[6] + x[7])), l1 = (x[10] + x[11]) + (x[12] + x[13]);
  if (w1) l1 += l4s; else l0 += l4s;
  l0 += __shfl_xor_sync(~0u, l0, 1); l1 += __shfl_xor_sync(~0u, l1, 1);
  l0 += __shfl_xor_sync(~0u, l0, 2); l1 += __shfl_xor_sync(~0u, l1, 2);
  l0 = rcpf(l0); l1 = rcpf(l1);
#pragma unroll
  for (int j = 0; j < 7; j++) {
    const float iv = j < 4 ? l0 : j > 4 ? l1 : w1 ? l1 : l0;
    sts32(pa + (j < 3 ? j * 128 : j == 3 ? km : j == 4 ? (w1 ? 896 + 128 : 384) : j == 5 ? 896 : 896 + km), pack2(x[2 * j] * iv, x[2 * j + 1] * iv));
  }
}
template <int N>
__device__ __forceinline__ void wo_phase(uint32_t sb, int wg, int warp, int lane, uint32_t par, uint32_t r1, const Desc& D) {
  const uint32_t bar = sb + OFF_BAR;
  float x[N / 2], y[N / 2];
  const uint2 ta = lds64(sb + OFF_TAB + (wg * 4 + warp) * 8);
  uint32_t xa = (ta.x & ~255u) + lane * 8, xb = (ta.x & 0xFF0000FFu) + SMEM0 + OFF_BAR, ya = (ta.y & ~255u) + lane * 8, yb = (ta.y & 0xFF0000FFu) + SMEM0 + OFF_BAR;
  asm volatile("" : "+r"(xa), "+r"(xb), "+r"(ya), "+r"(yb));
  auto scat = [&](uint32_t ad, uint32_t mb, const float* d) {
    st_async_v2(ad, pack2(d[0], d[1]), pack2(d[2], d[3]), mb);
    if (N == 16) st_async_v2(ad + LAND_F, pack2(d[4], d[5]), pack2(d[6], d[7]), mb);
  };
  if (wg == 0) {
    bar_sync(N_O, 384);
    wg_fence(); wo4<N, 0, 4, 0, 0>(x, D); wo4<N, 0, 8, 0, 0>(y, D); wg_commit();
    mbar_waitu(bar + 8 * B_OPEER, par);
    CFENCE(); wg_fence(); wo4<N, 0, 16, 1, 1>(x, D); wo4<N, 0, 20, 2, 1>(x, D); wg_commit();
    wo4<N, 0, 24, 1, 1>(y, D); wg_commit();
    mbar_waitu2(bar + 8 * B_WOF, bar + 8 * B_MEMFREE, par);
    wg_fence(); wo4<N, 0, 28, 2, 1>(y, D); wg_commit();
    bar_arrive(N_AB, 256);
    wg_wait<2>(); scat(xa, xb, x);
    wg_wait<0>(); scat(ya, yb, y);
  } else {
    bar_sync(N_O, 384);
    wg_fence(); wo4<N, 1, 0, 0, 0>(x, D); wg_commit(); wo4<N, 1, 12, 0, 0>(y, D); wg_commit();
    wg_wait<1>(); mbar_arrive_remote_if(lane == 0, r1);
    mbar_waitu(bar + 8 * B_MEMFREE, par);
    scat(xa, xb, x);
    bar_sync(N_AB, 256);
    CFENCE(); wg_fence(); wo4<N, 1, 32, 1, 1>(y, D); wo4<N, 1, 36, 2, 1>(y, D); wg_commit();
    bar_arrive(N_TURN, 256);
    wg_wait<0>(); scat(ya, yb, y);
  }
}
#define DS_DUAL 10
#define DS_SINGLE 20
#define POLL_GAP 100
#define POLL_GAPD 0
#define TOK_DELAY 250
#define LATE_SM 1
#define UMAX 40
#define VD1 10
#define VS2 20
#define IG_V 3
#define VS1 4
struct AMaps { CUtensorMap w16[3], wo32; uint64_t d[5]; const __nv_bfloat16* wv; };
__global__ void __launch_bounds__(512, 1)
acore_kernel(const __grid_constant__ AMaps M, const __nv_bfloat16* __restrict__ mem0, int sync_b) {
  extern __shared__ __align__(1024) unsigned char smem_raw[];
  const uint32_t sb = smem_u32(smem_raw);
  GTS(24);
  if (threadIdx.x == 480) {
    uint32_t smid; asm volatile("mov.u32 %0, %%smid;" : "=r"(smid));
    g_tpc[(smid >> 1) & 127] = blockIdx.x - CL_SIZE < 3 * CL_SIZE && blockIdx.x % CL_SIZE >= 12 ? 1 : 2;
    asm volatile("griddepcontrol.launch_dependents;");
  }
  const int lane0 = threadIdx.x & 31;
#define LANE_INIT() int lane; asm volatile("mov.u32 %0, %%laneid;" : "=r"(lane))
  const int warp = __shfl_sync(~0u, (threadIdx.x >> 5) & 3, 0);
  const int cl = blockIdx.x / CL_SIZE;
  const uint32_t rank = blockIdx.x - cl * CL_SIZE;
  const int nh = cl >= 1 && cl <= 3 ? 4 : 5;
  const int nA = 3 * nh;
  const int wg = __shfl_sync(~0u, (int)rank < nA ? threadIdx.x >> 7 : 4, 0);
  const int head = (cl < 4 ? (cl ? 1 + 4 * cl : 0) : 5 * cl - 3) + rank / 3;
  const int t3 = rank % 3;
  const int col0 = head * DH + t3 * 64;
  const uint32_t bar = sb + OFF_BAR;
  const uint32_t rb0 = SMEM0;
  const uint16_t mcmask = (uint16_t)((1u << nA) - 1);
  const uint32_t nxt = sb + ((t3 == 2 ? -2 : 1) << 24), prv = sb + ((t3 == 0 ? 2 : -1) << 24);
  const int ig = (int)rank - (nA - 4);

  if (threadIdx.x == 0) {
    if (mapa(sb, nA - 1) != rb0 + ((nA - 1) << 24) || mapa(sb, 0) != rb0 || mapa(sb, 1) != rb0 + (1u << 24) || sb != SMEM0 + (rank << 24)) FAIL();
    for (int i = 0; i < B_NUM; i++)
      mbar_init(bar + 8 * i, i == B_R1 ? 4 * nA : i == B_R2 ? 12 * nA : i == B_MEMFREE ? nA : i == B_LANDFREE ? 4 * nA : i == B_PLFREE || i == B_XFREE ? 2 : 1);
    asm volatile("fence.mbarrier_init.release.cluster;" ::: "memory");
    mbar_expect(bar + 8 * B_W0, (80 + SSV + VST) * 2048);
  }
  __syncthreads();
  if (lane0 == 0) {
    const int w12 = wg * 4 + warp;
    if (w12 < 10) {
#pragma unroll 1
      for (int ks = 4 * w12; ks < 4 * w12 + 4; ks++) {
        const bool ss = is_ss(ks, SSQ);
        tma2d(ss ? sb + OFF_WS + ss_idx(ks, SSQ) * 2048 : sb + STG_Q + rs_idx(ks, SSQ) * 2048, &M.w16[0], col0, ks * 16, bar + 8 * B_W0);
        tma2d(ss ? sb + OFF_WS + (SSQ + ss_idx(ks, SSQ)) * 2048 : sb + STG_K + rs_idx(ks, SSQ) * 2048, &M.w16[1], col0, ks * 16, bar + 8 * B_W0);
        if (is_ss(ks, SSV)) tma2d(sb + OFF_WS + (2 * SSQ + ss_idx(ks, SSV)) * 2048, &M.w16[2], col0, ks * 16, bar + 8 * B_W0);
        else if (rs_idx(ks, SSV) < VST) tma2d(sb + (rs_idx(ks, SSV) < VA ? STG_K + 27 * 2048 : STG_V2 - VA * 2048) + rs_idx(ks, SSV) * 2048, &M.w16[2], col0, ks * 16, bar + 8 * B_W0);
      }
    }
  }
  if (lane0 < 2 && wg < 2) {
    const int u = 4 * (wg ? (lane0 ? 6 + t3 : 9) : (lane0 ? 3 + t3 : t3)) + warp;
    const int li = (u >= nA) + (u >= 2 * nA) + (u >= 3 * nA);
    sts32(sb + OFF_TAB + (wg * 4 + warp) * 8 + lane0 * 4,
          rb0 + ((u - li * nA) << 24) + OFF_TILE + LAND(li + (u >= 36 ? t3 : 0)) + (rank / 3) * 256 + 8 * (B_RS + li));
  }
  __syncthreads();
  GTS(25);

  auto issue_tok = [&](int sc, int fb, int rel = -1, uint32_t ph = 0) {
    if (sync_b) wait_cnt(&g_xready[sc][0], 32);
    if (rel >= 0) mbar_waitu(bar + 8 * rel, ph);
    bulk_g2s_mc_e(sb + OFF_TILE + ig * TILE_GRP + TILE_SBO, &g_xn[0][0] + uni(sc * (32 * DM)) + ig * 5120, 10240, bar + 8 * (fb + ig), mcmask);
  };
#define POLL(d, q) _Pragma("unroll") for (int k = 0; k < NCL; k++) \
      asm volatile("ld.relaxed.gpu.global.v2.b32 {%0,%1}, [%2];" : "=r"(d[k].x), "=r"(d[k].y) : "l"(q + k * 2560) : "memory")
#define L3(L, a, b, c) lop3<L>(a, b, c)
#define TAGS(L, d) L3(L, L3(L, L3(L, d[0].x, d[0].y, d[1].x), L3(L, d[1].y, d[2].x, d[2].y), L3(L, d[3].x, d[3].y, d[4].x)), L3(L, d[4].y, d[5].x, d[5].y), L3(L, d[6].x, d[6].y, d[6].y))
    auto deliver = [&](uint2* pa, const uint32_t* gq, int u, int c, int dc, int ds, int step, bool first, int lane) {
      const uint32_t off = uni(OFF_TILE + ((u * 205) >> 11) * (TILE_GRP - TILE_SBO) + u * 256 + dc * LAND_F), boff = uni(OFF_BAR + 8 * (B_F1 + ((u * 205) >> 11)));
      const uint32_t* mi = &g_part[4][0][0][0] + uni((c * NCL + cl) * 2560 + u * 64);
      mbar_waitu(bar + 8 * B_LANDFREE, step & 1);
      int n = 0;
      while (true) {
        const bool ok = __all_sync(~0u, ((step & 2 ? ~TAGS(0xFE, pa) : TAGS(0x80, pa)) & 1) != 0);
        if (ok) break;
        if (++n > SPIN_LIMIT) FAIL();
        POLL(pa, gq);
      }
      if (warp == 0 && first) { TS(19); TSV(10, n); }
      const uint32_t w0 = hadd2bf(hadd2bf(hadd2bf(pa[0].x, pa[1].x), hadd2bf(pa[2].x, pa[3].x)), hadd2bf(hadd2bf(pa[4].x, pa[5].x), pa[6].x));
      const uint32_t w1 = hadd2bf(hadd2bf(hadd2bf(pa[0].y, pa[1].y), hadd2bf(pa[2].y, pa[3].y)), hadd2bf(hadd2bf(pa[4].y, pa[5].y), pa[6].y));
      if (u < ds) {
        const uint32_t da = SMEM0 + off + lane * 8, db = SMEM0 + boff;
#pragma unroll
        for (int d = 0; d < 12; d++) st_async_v2((d << 24) + da, w0, w1, (d << 24) + db);
#pragma unroll
        for (int d = 12; d < 15; d++) st_async_v2_if(nA == 15, (d << 24) + da, w0, w1, (d << 24) + db);
      } else {
        *reinterpret_cast<uint2*>(const_cast<uint32_t*>(gq) + ((4 - 2 * (step & 1)) * NCL + cl) * 2560) = make_uint2(w0, w1);
        asm volatile("fence.proxy.async.global;" ::: "memory");
        __syncwarp();
        bulk_g2s_mc_e(sb + off, mi, 256, sb + boff, mcmask);
      }
    };
#define REL(b, g) mbar_arrive_remote_if(lane == 0, rb0 + ((nA - 4 + (g)) << 24) + OFF_BAR + 8 * (b))

  if (wg < 2) {
    asm volatile("setmaxnreg.inc.sync.aligned.u32 160;");
    LANE_INIT();
    uint32_t W[4 * (40 - SSQ)];
    mbar_waitw(bar + 8 * B_W0, 0);
    GTS(26);
    load_w<40 - SSQ>(W, sb + (wg ? STG_K : STG_Q), warp, lane);
    fence_async();
    bar_sync(1, 384);
    cluster_sync_all();
#define DESC(k) const Desc D = make_desc(M.d, min(wg, 2) * SSQ, fresh<k>(step))
    GTS(27);
#pragma unroll 1
    for (int step = -1; step < NSTEP; step++) {
      const uint32_t par = step & 1;
      asm volatile("" : "+r"(lane));
      const bool dual = is_dual(step), has_next = step + 1 < NSTEP;
#define QK_SA (sb + OFF_QK + wg * 15360 + (2 * warp + ((lane >> 3) & 1)) * 128 + (lane & 7) * 16)
#define QK_F (wg ? -5120 : 5120)
#define QK_S12 ((wg ? (lane >> 4) : 1 + 2 * (lane >> 4)) * 1024)
#define QK_S34 ((wg ? 2 + (lane >> 4) : 2 - 2 * (lane >> 4)) * 1024)
      if (step >= 0) {
        if (dual) {
          DESC(0);
          float acc[24];
          mbar_waitu(bar + 8 * (B_F1 + 0), par);
          if (wg + warp == 0) { TS(0); TSN(1); }
          CFENCE(); wg_fence(); proj<48, SSQ, 0, 0, 10>(acc, W, D); wg_commit();
          mbar_waitu(bar + 8 * (B_F1 + 1), par);
          CFENCE(); wg_fence(); proj<48, SSQ, 0, 10, 20>(acc, W, D); wg_commit();
          mbar_waitu(bar + 8 * (B_F1 + 2), par);
          CFENCE(); wg_fence(); proj<48, SSQ, 0, 20, 30>(acc, W, D); wg_commit();
          mbar_waitu(bar + 8 * (B_F1 + 3), par);
          if (wg + warp == 0) TS(2);
          CFENCE(); wg_fence(); proj<48, SSQ, 0, 30, 40>(acc, W, D); wg_commit();
          bar_arrive(N_VGO, 384);
          mbar_waitu(bar + 8 * B_PLFREE, par);
          const uint32_t sa = QK_SA, s0 = sa + 4096 + (lane >> 4) * QK_F, s1 = sa + QK_F + QK_S12, s2 = sa + QK_F + QK_S34;
          wg_wait<0>();
          if (wg + warp == 0) TS(3);
          stsm4t(s0, pack2(acc[0], acc[1]), pack2(acc[2], acc[3]), pack2(acc[20], acc[21]), pack2(acc[22], acc[23]));
          stsm4t(s1, pack2(acc[4], acc[5]), pack2(acc[6], acc[7]), pack2(acc[8], acc[9]), pack2(acc[10], acc[11]));
          stsm4t(s2, pack2(acc[12], acc[13]), pack2(acc[14], acc[15]), pack2(acc[16], acc[17]), pack2(acc[18], acc[19]));
        } else {
          DESC(1);
          float acc[4];
          mbar_waitu(bar + 8 * (B_F1 + 0), par);
          if (wg + warp == 0) { TS(0); TSN(1); }
          CFENCE(); wg_fence(); proj<8, SSQ, 0, 0, 10>(acc, W, D); wg_commit();
          mbar_waitu(bar + 8 * (B_F1 + 1), par);
          CFENCE(); wg_fence(); proj<8, SSQ, 0, 10, 20>(acc, W, D); wg_commit();
          mbar_waitu(bar + 8 * (B_F1 + 2), par);
          CFENCE(); wg_fence(); proj<8, SSQ, 0, 20, 30>(acc, W, D); wg_commit();
          mbar_waitu(bar + 8 * (B_F1 + 3), par);
          if (wg + warp == 0) TS(2);
          CFENCE(); wg_fence(); proj<8, SSQ, 0, 30, 40>(acc, W, D); wg_commit();
          bar_arrive(N_VGO, 384);
          mbar_waitu(bar + 8 * B_PLFREE, par);
          const uint32_t s0 = QK_SA + 4096;
          wg_wait<0>();
          if (wg + warp == 0) TS(3);
          stsm2t(s0, pack2(acc[0], acc[1]), pack2(acc[2], acc[3]));
        }
        fence_async();
        bar_sync(N_QK, 256);
        if (wg == 0 || dual) {
          float s[20];
          DESC(2);
          const Dsc ab = D.k1 + wg * 192, bb = D.k1 + (1 - wg) * 320;
          wg_fence();
          MM<40>::ss<dlo(OFF_QK, 128), dlo(OFF_QK + 10240, 128), 0, 0>(s, ab, bb);
          MM<40>::ss<dlo(OFF_QK + 256, 128), dlo(OFF_QK + 10240 + 256, 128), 1, 0>(s, ab, bb);
          MM<40>::ss<dlo(OFF_QK + 512, 128), dlo(OFF_QK + 10240 + 512, 128), 1, 0>(s, ab, bb);
          MM<40>::ss<dlo(OFF_QK + 768, 128), dlo(OFF_QK + 10240 + 768, 128), 1, 0>(s, ab, bb);
          wg_commit();
          bar_arrive(N_SISS, 384);
          const int rw = (warp - wg) & 3;
          const uint32_t bo = OFF_BAR + 8 * (B_SB + 3 * wg + rw), lo = OFF_PL + wg * PL_SZ + rw * 1792;
          const uint32_t km = wg ? 640 : 512;
          uint32_t l16 = lo + lane * 16, l4 = lo + lane * 4;
          mbar_expect_if(lane == 0 && rw < 3, sb + bo, rw < 2 ? 1792 : 1280);
          asm volatile("" : "+r"(l16), "+r"(l4));
          if (rw == 2) {
            wg_wait<0>();
            if (wg == 0) TSD(4, __float_as_uint(s[0]));
            const uint32_t w0 = pack2(s[0], s[1]), w1 = pack2(s[4], s[5]), w2 = pack2(s[8], s[9]), w3 = pack2(s[12], s[13]), w4 = pack2(s[16], s[17]);
            {
              st_async_v4(nxt + 896 + l16, w0, w1, w2, w3, nxt + bo);
              st_async_v4(prv + l16, w0, w1, w2, w3, prv + bo);
              st_async_b32(nxt + 896 + 768 + l4, w4, nxt + bo);
              st_async_b32(prv + 768 + l4, w4, prv + bo);
            }
            bar_arrive(N_SDONE, 256);
            mbar_waitu(sb + bo, (step - wg * LAG) & 1);
            if (wg == 0) TS(5);
            float x[10], m0;
            {
              const uint4 a = lds128(sb + l16), b = lds128(sb + 896 + l16);
              const uint32_t c = lds32(sb + 768 + l4), d = lds32(sb + 896 + 768 + l4);
              const uint32_t e0 = hadd2bf(hadd2bf(a.x, b.x), w0), e1 = hadd2bf(hadd2bf(a.y, b.y), w1), e2 = hadd2bf(hadd2bf(a.z, b.z), w2),
                             e3 = hadd2bf(hadd2bf(a.w, b.w), w3), e4 = hadd2bf(hadd2bf(c, d), w4);
              const uint32_t em = hmax2bf(hmax2bf(hmax2bf(e0, e1), hmax2bf(e2, e3)), e4);
              m0 = fmaxf(bf_lo(em), bf_hi(em));
              x[0] = bf_lo(e0); x[1] = bf_hi(e0); x[2] = bf_lo(e1); x[3] = bf_hi(e1); x[4] = bf_lo(e2);
              x[5] = bf_hi(e2); x[6] = bf_lo(e3); x[7] = bf_hi(e3); x[8] = bf_lo(e4); x[9] = bf_hi(e4);
            }
            m0 = fmaxf(m0, __shfl_xor_sync(~0u, m0, 1));
            sts32(sb + l4 + 1152 - km, 0u);
            m0 = fmaxf(m0, __shfl_xor_sync(~0u, m0, 2));
            m0 *= -SL2;
#pragma unroll
            for (int j = 0; j < 5; j++) {
              x[2 * j] = ex2(fmaf(x[2 * j], SL2, m0)); x[2 * j + 1] = ex2(fmaf(x[2 * j + 1], SL2, m0));
              sts32(sb + l4 + (j < 4 ? j * 128 : km), pack2(x[2 * j], x[2 * j + 1]));
            }
            float l = ((x[0] + x[1]) + (x[2] + x[3])) + ((x[4] + x[5]) + ((x[6] + x[7]) + (x[8] + x[9])));
            l += __shfl_xor_sync(~0u, l, 1);
            fence_async();
            sts32(sb + OFF_INV + wg * 64 + (lane >> 1) * 4, __float_as_uint(l));
            bar_arrive(N_PM, dual ? 224 : 192);
            if (wg == 0) TS(6);
          } else if (rw < 2) {
            const bool w1 = rw == 1;
            const uint32_t l8 = lo + 512 + lane * 8;
            uint32_t tw[7];
            wg_wait<0>();
            bar_arrive(N_SDONE, 256);
            tw[0] = pack2(s[0], s[1]); tw[1] = pack2(s[4], s[5]); tw[2] = pack2(s[8], s[9]); tw[3] = pack2(s[16], s[17]);
            tw[4] = w1 ? pack2(s[6], s[7]) : pack2(s[12], s[13]); tw[5] = pack2(s[2], s[3]); tw[6] = pack2(s[18], s[19]);
            { const uint32_t t0 = clock32(); while (clock32() - t0 < TOK_DELAY) {} }
            st_async_v4(nxt + 896 + l16, tw[0], tw[1], tw[2], tw[3], nxt + bo);
            st_async_v4(prv + l16, tw[0], tw[1], tw[2], tw[3], prv + bo);
            st_async_v2(nxt + 896 + l8, tw[5], tw[6], nxt + bo);
            st_async_v2(prv + l8, tw[5], tw[6], prv + bo);
            st_async_b32(nxt + 896 + 768 + l4, tw[4], nxt + bo);
            st_async_b32(prv + 768 + l4, tw[4], prv + bo);
            mbar_waitu(sb + bo, (step - wg * LAG) & 1);
            const uint4 a = lds128(sb + l16), b = lds128(sb + 896 + l16);
            const uint2 e = lds64(sb + l8), f = lds64(sb + 896 + l8);
            const uint32_t c = lds32(sb + 768 + l4), d = lds32(sb + 896 + 768 + l4);
            sts128(sb + l16, hadd2bf(hadd2bf(a.x, b.x), tw[0]), hadd2bf(hadd2bf(a.y, b.y), tw[1]), hadd2bf(hadd2bf(a.z, b.z), tw[2]), hadd2bf(hadd2bf(a.w, b.w), tw[3]));
            sts64(sb + l8, hadd2bf(hadd2bf(e.x, f.x), tw[5]), hadd2bf(hadd2bf(e.y, f.y), tw[6]));
            sts32(sb + 768 + l4, hadd2bf(hadd2bf(c, d), tw[4]));
            bar_arrive(N_PX, dual ? 256 : 192);
            if (wg + warp == 0) TS(9);
          } else {
            wg_wait<0>();
            if (wg == 0) {
              mbar_expect_if(lane < 3 && has_next, bar + 8 * (lane == 2 ? B_OPEER : B_WOF + lane), lane == 2 ? (dual ? 4096 : 2048) : lane ? 8192 : 20480);
              auto fetch = [&](int i, int n, uint32_t dst, int mb) {
                int c0, c1; wo_coord(i, t3, head, c0, c1);
                tma2d_e(dst, &M.wo32, c0, c1, bar + 8 * mb); if (n == 2) tma2d_e(dst + 4096, &M.wo32, c0, c1 + 32, bar + 8 * mb);
              };
              bar_sync(N_G3, 160);
              if (has_next) {
                fetch(0, 2, sb + OFF_WT, B_WTF);
                mbar_arrive_remote_if(lane < 2, (lane ? nxt : prv) + OFF_BAR + 8 * B_XFREE);
              }
              bar_sync(N_SDONE, 256);
              if (has_next) {
                fetch(15, 1, sb + OFF_QK, B_WOF); fetch(16, 2, sb + OFF_QK + 4096, B_WOF); fetch(18, 2, sb + OFF_QK + 12288, B_WOF);
                mbar_waitu(bar + 8 * B_XFREE, par);
              }
              bar_arrive(N_PM, dual ? 224 : 192);
              bar_sync(N_VDONE, 160);
              mbar_arrive_remote_if(lane < nA && has_next, rb0 + (lane << 24) + OFF_BAR + 8 * B_MEMFREE);
              if (has_next) mbar_waitu(bar + 8 * B_WTF, par);
            } else {
              bar_arrive(N_SDONE, 256);
              if ((unsigned)ig < IG_V) issue_tok(sched_l(step + 1), B_F2, B_R1, (step - LAG) & 1);
            }
          }
        } else {
          bar_arrive(N_SISS, 384);
          bar_arrive(N_SDONE, 256);
        }
        if (has_next) {
          if (step == 0) mbar_waitw(bar + 8 * B_W1, 0);
          const uint32_t r1 = rb0 + ((nA - 1) << 24) + OFF_BAR + 8 * B_R1;
          if (dual) { DESC(3); wo_phase<16>(sb, wg, warp, lane, par, r1, D); } else { DESC(4); wo_phase<8>(sb, wg, warp, lane, par, r1, D); }
          bar_arrive(N_C, 288);
          if (warp == 0) TS(7 + wg);
        }
      }
      if (has_next) {
        DESC(5);
        float acc[16];
        mbar_waitu(bar + 8 * B_F2, par ^ 1);
        wg_fence(); proj<32, SSQ, 1, 0, 10>(acc, W, D); wg_commit();
        mbar_waitu(bar + 8 * (B_F2 + 1), par ^ 1);
        wg_fence(); proj<32, SSQ, 1, 10, 14>(acc, W, D); wg_commit();
        wg_wait<1>(); REL(B_R2, 0);
        wg_fence(); proj<32, SSQ, 1, 14, 20>(acc, W, D); wg_commit();
        mbar_waitu(bar + 8 * (B_F2 + 2), par ^ 1);
        wg_fence(); proj<32, SSQ, 1, 20, 24>(acc, W, D); wg_commit();
        wg_wait<1>(); REL(B_R2, 1);
        wg_fence(); proj<32, SSQ, 1, 24, 30>(acc, W, D); wg_commit();
        mbar_waitu(bar + 8 * (B_F2 + 3), par ^ 1);
        wg_fence(); proj<32, SSQ, 1, 30, 34>(acc, W, D); wg_commit();
        wg_wait<1>(); REL(B_R2, 2);
        wg_fence(); proj<32, SSQ, 1, 34, 40>(acc, W, D); wg_commit();
        const uint32_t sa = QK_SA, s1 = sa + QK_S12, s2 = sa + QK_S34;
        wg_wait<0>(); REL(B_R2, 3);
        if (warp == 0) TS(11 + wg);
        stsm4t(s1, pack2(acc[0], acc[1]), pack2(acc[2], acc[3]), pack2(acc[4], acc[5]), pack2(acc[6], acc[7]));
        stsm4t(s2, pack2(acc[8], acc[9]), pack2(acc[10], acc[11]), pack2(acc[12], acc[13]), pack2(acc[14], acc[15]));
      }
    }
    GTS(28);
    cluster_sync_all();
  } else if (wg == 2) {
    asm volatile("setmaxnreg.inc.sync.aligned.u32 160;");
    LANE_INIT();
    uint32_t W[4 * (40 - SSV)];
    ld_rest<0>(W, reinterpret_cast<const uint32_t*>(M.wv + (lane >> 2) * HD + col0 + warp * 16) + (lane & 3));
    uint4 m0[5];
#pragma unroll
    for (int i = 0; i < 5; i++) {
      const int t = i * 128 + warp * 32 + lane;
      m0[i] = __ldg(reinterpret_cast<const uint4*>(mem0 + ((t >> 1) & 7) * DM + (t >> 4) * 16 + ((t ^ (t >> 3)) & 1) * 8));
    }
    mbar_waitw(bar + 8 * B_W0, 0);
    load_w<VA>(W, sb + STG_K + 27 * 2048, warp, lane);
    load_w<VST - VA>(W + 4 * VA, sb + STG_V2, warp, lane);
    fence_async();
    mbar_expect_if(warp + lane == 0, bar + 8 * B_W1, 26 * 2048);
    bar_sync(1, 384);
#pragma unroll
    for (int i = 0; i < 5; i++) {
      const int t = i * 128 + warp * 32 + lane;
      sts128(sb + OFF_TILE + (t / 160) * (TILE_GRP - TILE_SBO) + t * 16, m0[i].x, m0[i].y, m0[i].z, m0[i].w);
    }
#pragma unroll
    for (int i = 4 * VST; i < 4 * (40 - SSV); i++) W[i] = movm(W[i]);
    fence_async();
    mbar_arrive_if(lane == 0, bar + 8 * (B_F1 + warp));
    mbar_expect_if(lane == 0, bar + 8 * (B_F2 + warp), 10240);
    mbar_arrive_if(warp == 3 && lane < 2, bar + 8 * B_PLFREE);
    cluster_sync_all();
    uint32_t vl[8];
    {
      const int step = warp;
      DESC(0);
      float v[16];
      mbar_waitw4(bar + 8 * B_F2, 0);
      wg_fence(); proj<32, SSV, 1, 0, 40>(v, W, D); wg_commit();
      wg_wait<0>();
      mbar_arrive_remote_if(lane < 4, rb0 + ((nA - 4 + lane) << 24) + OFF_BAR + 8 * B_R2);
#pragma unroll
      for (int j = 0; j < 8; j++) vl[j] = pack2v(v[2 * j], v[2 * j + 1]);
      if (warp == 0 && (unsigned)ig < 3) issue_tok(1, B_F2, B_R2, 0);
    }
#pragma unroll 1
    for (int step = 0; step < NSTEP; step++) {
      const uint32_t par = step & 1;
      asm volatile("" : "+r"(lane));
      const bool dual = is_dual(step), has_next = step + 1 < NSTEP;
      mbar_expect_if(lane == 0 && has_next, bar + 8 * (B_F2 + warp), 10240);
      if (warp == 0 && ig >= IG_V && dual && sync_b) wait_cnt(&g_xready[sched_l(step + 1)][0], 32);
      bar_sync(N_VGO, 384);
      CFENCE();
#define F1_BYTES (is_dual(step + 1) ? 15360 : 2560)
#define ARM() do { \
        mbar_expect_if(lane == 0 && has_next, bar + 8 * (B_F1 + warp), F1_BYTES); \
        mbar_expect_if(lane == 0 && has_next && warp * nA + (int)rank < 40, bar + 8 * (B_RS + warp), (warp * nA + (int)rank >= 36 ? nA : nh) * (dual ? 512 : 256)); } while (0)
#define O_ADDR() uint32_t oa = sb + OFF_O + (lane >> 4) * PL_SZ + warp * 256 + (lane & 15) * 16, xo = (lane >> 4) * 1024 + warp * 256 + (lane & 15) * 16; \
        asm volatile("" : "+r"(oa), "+r"(xo))
#define O_READY(act) do { if (has_next) { const uint4 ov = lds128(oa); \
        if (act) { st_async_v4(nxt + OFF_XL + xo, ov.x, ov.y, ov.z, ov.w, nxt + OFF_BAR + 8 * B_OPEER); \
                   st_async_v4(prv + OFF_XF + xo, ov.x, ov.y, ov.z, ov.w, prv + OFF_BAR + 8 * B_OPEER); } \
        fence_async(); bar_arrive(N_O, 384); } \
        if (warp == 0) TS(15); } while (0)
#define TOK_L3(g0) if (warp == 0 && ig >= (g0) && has_next) { mbar_waitu(bar + 8 * B_R1, ig == 3 ? par : (step - LAG) & 1); asm volatile("fence.proxy.async.global;" ::: "memory"); \
        bulk_g2s_mc_e(sb + OFF_TILE + ig * TILE_GRP + TILE_SBO, &g_xn[0][0] + uni(sched_l(step + 1) * (32 * DM)) + ig * 5120, 10240, bar + 8 * (B_F2 + ig), mcmask); }
#define OX_ADDR() const bool ox = head * 3 + t3 == 95; \
        const uint32_t oxa = sb + OFF_PL + (ox ? warp * 1024 + (lane & 7) * 32 + ((((lane >> 3) ^ (lane >> 2)) & 1) << 4) : (lane & 7) * 128 + (((warp * 2 + ((lane >> 3) & 1)) ^ (lane & 7)) << 4)); \
        const uint32_t s1 = oxa + ((lane < 16 ? 3072 : 0) >> (ox ? 2 : 0)), s2 = oxa + ((lane < 16 ? 2048 : 1024) >> (ox ? 2 : 0))
      if (dual) {
        uint32_t vf[8], vm[4], vn[8];
        {
          DESC(0);
          float v[24];
          ARM();
          wg_fence(); proj<48, SSV, 0, 30, 40, 30>(v, W, D); wg_commit();
          proj<48, SSV, 0, 0, VD1 - 10, 30>(v, W, D);
          bar_sync(N_SISS, 384);
          proj<48, SSV, 0, VD1 - 10, VD1 - 7, 30>(v, W, D); wg_commit();
          wg_wait<1>(); bar_arrive(N_G3, 160);
          wg_fence(); proj<48, SSV, 0, VD1 - 7, 10, 30>(v, W, D); wg_commit();
          proj<48, SSV, 0, 10, 13, 30>(v, W, D); wg_commit();
          wg_wait<1>(); REL(B_R1, 0);
          wg_fence(); proj<48, SSV, 0, 13, 20, 30>(v, W, D); wg_commit();
          proj<48, SSV, 0, 20, 23, 30>(v, W, D); wg_commit();
          wg_wait<1>(); REL(B_R1, 1);
          wg_fence(); proj<48, SSV, 0, 23, 30, 30>(v, W, D); wg_commit();
          wg_wait<0>(); REL(B_R1, 2);
          bar_arrive(N_VDONE, 160);
          if (warp == 0) TS(14);
#pragma unroll
          for (int j = 4; j < 8; j++) vf[j] = pack2v(v[4 + 2 * j], v[5 + 2 * j]);
          keep4(vf + 4, lane);
          vm[0] = pack2v(v[0], v[1]); vm[1] = pack2v(v[2], v[3]); vm[2] = pack2v(v[20], v[21]); vm[3] = pack2v(v[22], v[23]);
          keep4(vm, lane);
#pragma unroll
          for (int j = 0; j < 4; j++) vf[j] = pack2v(v[4 + 2 * j], v[5 + 2 * j]);
          keep4(vf, lane);
        }
        {
          DESC(1);
          float o[8];
          O_ADDR();
          bar_sync(N_PM, 224);
          wg_fence();
          MM<8>::rs<dlo(OFF_PL + 3584, 128), 0>(o, vl, D.p);
          MM<8>::rs<dlo(OFF_PL + PL_SZ + 3584, 128), 0>(o + 4, vf, D.p);
          MM<8>::rs<dlo(OFF_PL + 3584 + 256, 128), 1>(o, vl + 4, D.p);
          MM<8>::rs<dlo(OFF_PL + PL_SZ + 3584 + 256, 128), 1>(o + 4, vf + 4, D.p);
          MM<8>::rs<dlo(OFF_PL + 3584 + 512, 128), 1>(o, vm, D.p);
          MM<8>::rs<dlo(OFF_PL + PL_SZ + 3584 + 512, 128), 1>(o + 4, vm, D.p);
          wg_commit();
          fence_sched(step);
          const uint4 il = lds128(sb + OFF_INV + (lane & 3) * 16), jf = lds128(sb + OFF_INV + 64 + (lane & 3) * 16);
          const float i0 = rcpf(__uint_as_float(il.x) + __uint_as_float(il.y)), i1 = rcpf(__uint_as_float(il.z) + __uint_as_float(il.w));
          const float j0 = rcpf(__uint_as_float(jf.x) + __uint_as_float(jf.y)), j1 = rcpf(__uint_as_float(jf.z) + __uint_as_float(jf.w));
          { const uint32_t k4[4] = {__float_as_uint(i0), __float_as_uint(i1), __float_as_uint(j0), __float_as_uint(j1)}; keep4(k4, lane | (oa ^ xo)); }
          wg_wait<0>();
          stsm4t(oa, pack2(o[0] * i0, o[1] * i1), pack2(o[2] * i0, o[3] * i1), pack2(o[4] * j0, o[5] * j1), pack2(o[6] * j0, o[7] * j1));
          O_READY(true);
          TOK_L3(IG_V);
        }
        {
          DESC(2);
          float v[16];
          bar_sync(N_TURN, 256);
          mbar_waitu(bar + 8 * B_F2, par ^ 1);
          wg_fence(); proj<32, SSV, 1, 0, 10>(v, W, D); wg_commit();
          mbar_waitu(bar + 8 * (B_F2 + 1), par ^ 1);
          wg_fence(); proj<32, SSV, 1, 10, 14>(v, W, D); wg_commit();
          wg_wait<1>(); REL(B_R2, 0);
          wg_fence(); proj<32, SSV, 1, 14, 20>(v, W, D); wg_commit();
          mbar_waitu(bar + 8 * (B_F2 + 2), par ^ 1);
          wg_fence(); proj<32, SSV, 1, 20, 24>(v, W, D); wg_commit();
          wg_wait<1>(); REL(B_R2, 1);
          wg_fence(); proj<32, SSV, 1, 24, 30>(v, W, D); wg_commit();
          mbar_waitu(bar + 8 * (B_F2 + 3), par ^ 1);
          wg_fence(); proj<32, SSV, 1, 30, 34>(v, W, D); wg_commit();
          wg_wait<1>(); REL(B_R2, 2);
          wg_fence(); proj<32, SSV, 1, 34, 40>(v, W, D); wg_commit();
          wg_wait<0>(); REL(B_R2, 3);
#pragma unroll
          for (int j = 0; j < 8; j++) vn[j] = pack2v(v[2 * j], v[2 * j + 1]);
          keep4(vn, lane); keep4(vn + 4, lane);
          if (warp == 0) TS(18);
        }
        DESC(3);
        uint32_t ow[16];
        bar_sync(N_P, 256);
        fence_async();
#define PV16(i, off, va) { float o[8]; wg_fence(); \
          MM<16>::rs<dlo(OFF_PL + (off), 128), 0>(o, va, D.p); \
          MM<16>::rs<dlo(OFF_PL + (off) + 256, 128), 1>(o, va + 4, D.p); \
          MM<16>::rs<dlo(OFF_PL + (off) + 512, 128), 1>(o, vm, D.p); \
          wg_commit(); wg_wait<0>(); \
          _Pragma("unroll") for (int j = 0; j < 4; j++) ow[4 * (i) + j] = pack2v(o[2 * j], o[2 * j + 1]); \
          keep4(ow + 4 * (i), lane); }
        PV16(0, 0, vl) PV16(1, 1792, vl) PV16(2, PL_SZ, vf) PV16(3, PL_SZ + 1792, vf)
        OX_ADDR();
        bar_sync(N_V, 128);
        stsm4t(s1, ow[0], ow[1], ow[2], ow[3]);
        stsm4t(s2, ow[4], ow[5], ow[6], ow[7]);
        stsm4t(s1 + PL_SZ, ow[8], ow[9], ow[10], ow[11]);
        stsm4t(s2 + PL_SZ, ow[12], ow[13], ow[14], ow[15]);
#pragma unroll
        for (int j = 0; j < 8; j++) vl[j] = vn[j];
      } else {
        uint32_t vm[4], vn[8];
        {
          DESC(4);
          float v[4];
          wg_fence(); proj<8, SSV, 0, 30, 40, 30>(v, W, D); wg_commit();
          proj<8, SSV, 0, 0, VS1, 30>(v, W, D); wg_commit();
          ARM();
          bar_sync(N_SISS, 384);
          wg_wait<1>(); bar_arrive(N_G3, 160);
          wg_fence(); proj<8, SSV, 0, VS1, 30, 30>(v, W, D); wg_commit();
          if (has_next) { mbar_waitu2(bar + 8 * B_F2, bar + 8 * (B_F2 + 1), par ^ 1); mbar_waitu(bar + 8 * (B_F2 + 2), par ^ 1); }
          wg_wait<0>();
          bar_arrive(N_VDONE, 160);
          vm[0] = pack2v(v[0], v[1]); vm[1] = pack2v(v[2], v[3]); vm[2] = pack2v(v[1], v[0]); vm[3] = pack2v(v[3], v[2]);
        }
        DESC(5);
        float v[16];
        {
          wg_fence(); proj<32, SSV, 1, 0, VS2>(v, W, D); wg_commit();
          {
            float o[4];
            O_ADDR();
            bar_sync(N_PM, 192);
            if (warp == 0) TS(14);
            wg_fence();
            MM<8>::rs<dlo(OFF_PL + 3584, 128), 0>(o, vl, D.p);
            MM<8>::rs<dlo(OFF_PL + 3584 + 256, 128), 1>(o, vl + 4, D.p);
            MM<8>::rs<dlo(OFF_PL + 3584 + 512, 128), 1>(o, vm, D.p);
            wg_commit();
            fence_sched(step);
            const uint4 il = lds128(sb + OFF_INV + (lane & 3) * 16);
            const float i0 = rcpf(__uint_as_float(il.x) + __uint_as_float(il.y)), i1 = rcpf(__uint_as_float(il.z) + __uint_as_float(il.w));
            { const uint32_t k4[4] = {__float_as_uint(i0), __float_as_uint(i1), oa, xo}; keep4(k4, lane); }
            wg_wait<0>();
            stsm2t(oa, pack2(o[0] * i0, o[1] * i1), pack2(o[2] * i0, o[3] * i1));
            O_READY(lane < 16);
            TOK_L3(3);
          }
          if (has_next) {
            mbar_arrive_remote_if(lane < VS2 / 10, rb0 + ((nA - 4 + lane) << 24) + OFF_BAR + 8 * B_R2);
            bar_sync(N_TURN, 256);
          }
          if (VS2 < 30) { wg_fence(); proj<32, SSV, 1, VS2, 30>(v, W, D); wg_commit(); }
          if (has_next) mbar_waitu(bar + 8 * (B_F2 + 3), par ^ 1);
          if (VS2 < 30) { wg_wait<0>(); if (has_next) REL(B_R2, 2); }
          wg_fence(); proj<32, SSV, 1, 30, 40>(v, W, D); wg_commit();
          wg_wait<0>();
          if (has_next) REL(B_R2, 3);
#pragma unroll
          for (int j = 0; j < 8; j++) vn[j] = pack2v(v[2 * j], v[2 * j + 1]);
          keep4(vn, lane); keep4(vn + 4, lane);
          if (warp == 0) TS(18);
        }
        float o[16];
        bar_sync(N_P, 256);
        fence_async();
        wg_fence();
        MM<32>::rs<dlo(OFF_PL, 128), 0>(o, vl, D.p);
        MM<32>::rs<dlo(OFF_PL + 256, 128), 1>(o, vl + 4, D.p);
        MM<32>::rs<dlo(OFF_PL + 512, 128), 1>(o, vm, D.p);
        wg_commit();
        OX_ADDR();
        wg_wait<0>();
        bar_sync(N_V, 128);
        stsm4t(s1, pack2(o[0], o[1]), pack2(o[2], o[3]), pack2(o[4], o[5]), pack2(o[6], o[7]));
        stsm4t(s2, pack2(o[8], o[9]), pack2(o[10], o[11]), pack2(o[12], o[13]), pack2(o[14], o[15]));
#pragma unroll
        for (int j = 0; j < 8; j++) vl[j] = vn[j];
      }
      bar_arrive(N_OX, 160);
      if (warp == 0) TS(16);
    }
    cluster_sync_all();
  } else {
    asm volatile("setmaxnreg.dec.sync.aligned.u32 32;");
    if (wg > 3) return;
    LANE_INIT();
    struct RsJob { uint32_t* gp; uint32_t la, mb; int n; };
    auto rs_prep = [&](int step, int s, int c) {
      RsJob j;
      const int u = s * nA + rank;
      j.gp = &g_part[0][0][0][0] + (uint32_t)((((step & 1) * 2 + c) * NCL + cl) * 2560 + u * 64 + (lane >> 2) * 8 + (lane & 3));
      j.la = sb + OFF_TILE + c * LAND_F + LAND(s) + lane * 8;
      j.mb = bar + 8 * (B_RS + s);
      j.n = u >= 40 ? 0 : u >= 36 ? 3 : 1;
      asm volatile("" : "+l"(j.gp), "+r"(j.la));
      return j;
    };
    auto rs_sum = [&](RsJob j, int step) {
      if (j.n) {
        auto five = [&](uint32_t la) {
          uint2 p[5];
#pragma unroll
          for (int i = 0; i < 4; i++) p[i] = lds64(la + i * 256);
          asm volatile("{\n.reg .pred q;\nsetp.eq.s32 q, %3, 5;\nmov.u32 %0, 0;\nmov.u32 %1, 0;\n@q ld.shared.v2.b32 {%0,%1}, [%2];\n}"
                       : "=r"(p[4].x), "=r"(p[4].y) : "r"(la + 1024), "r"(nh) : "memory");
          return make_uint2(hadd2bf(hadd2bf(p[0].x, p[1].x), hadd2bf(hadd2bf(p[2].x, p[3].x), p[4].x)),
                            hadd2bf(hadd2bf(p[0].y, p[1].y), hadd2bf(hadd2bf(p[2].y, p[3].y), p[4].y)));
        };
        const uint32_t tag = ((step >> 1) & 1) ^ 1;
        mbar_waitw(j.mb, step & 1);
        uint2 t = five(j.la);
        if (j.n > 1) {
          const uint2 a = five(j.la + (nh == 5 ? 1280 : TILE_GRP - 1280)), b = five(j.la + TILE_GRP);
          t.x = hadd2bf(t.x, hadd2bf(a.x, b.x)); t.y = hadd2bf(t.y, hadd2bf(a.y, b.y));
        }
        const uint32_t t0 = (movm(t.x) & ~1u) | tag, t1 = (movm(t.y) & ~1u) | tag;
        asm volatile("st.relaxed.gpu.global.b32 [%0], %1;" :: "l"(j.gp), "r"(lane & 16 ? t1 : t0) : "memory");
        asm volatile("st.relaxed.gpu.global.b32 [%0], %1;" :: "l"(j.gp + 4), "r"(lane & 16 ? t0 : t1) : "memory");
      }
    };
    if (warp * nA + (int)rank < 40) {
#pragma unroll
      for (int e = LAG; e < LAG + 2; e++)
        if ((e >> 1) & 1) *reinterpret_cast<uint2*>(&g_part[(e & 1) * 2 + 1][cl][warp * nA + rank][lane * 2]) = make_uint2(1u, 1u);
      __threadfence();
    }
    if (warp == 2 && ig >= 0 && sync_b) wait_cnt(&g_xready[0][0], 32);
    cluster_sync_all();
    if (warp == 2 && ig >= 0) bulk_g2s_mc_e(sb + OFF_TILE + ig * TILE_GRP + TILE_SBO, &g_xn[0][0] + ig * 5120, 10240, bar + 8 * (B_F2 + ig), mcmask);
    bar_sync(N_PI, 128);
#pragma unroll 1
    for (int i = warp; i < 20; i += 4) {
      int c0, c1; wo_coord(i, t3, head, c0, c1);
      if (i >= 2 && i < 15) tma2d_e(sb + OFF_WO + (i - 2) * 4096, &M.wo32, c0, c1, bar + 8 * B_W1);
      else if (lane == 0) tma2d_prefetch(&M.wo32, c0, c1);
      __syncwarp();
    }
#pragma unroll 1
    for (int step = 0; step < NSTEP; step++) {
      const uint32_t par = step & 1;
      asm volatile("" : "+r"(lane));
      const bool dual = is_dual(step), has_next = step + 1 < NSTEP;
      {
        bar_sync(N_PX, dual ? 256 : 192);
        if (dual || warp >= 2) tok_softmax(sb, dual ? warp : warp - 2, lane);
        bar_arrive(N_P, 256);
        asm volatile("" : "+r"(lane));
        if (has_next) {
          if (step + 2 == LAG && lane < 20) asm volatile("prefetch.global.L2 [%0];" :: "l"(mem0 + (warp * 20 + lane) * 64));
          const int nw = ig >= 0 ? 3 : 4, j0 = warp < nw ? warp : 8;
          const int sh = dual ? 1 : 0;
          rs_sum(rs_prep(step, j0 >> sh, j0 & sh), step);
          if (warp == 0) TS(17);
          if (dual) rs_sum(rs_prep(step, (j0 + nw) >> 1, (j0 + nw) & 1), step);
          if (warp == 0) { bar_sync(N_C, 288); }
          mbar_arrive_remote_if(lane < nA, rb0 + (lane << 24) + OFF_BAR + 8 * B_LANDFREE);
          const uint32_t gap = dual ? POLL_GAPD : POLL_GAP;
          if (gap) { const uint32_t t0 = clock32(); while (clock32() - t0 < gap) {} }
#pragma unroll 1
          for (int j = j0; j < (dual ? 8 : 4); j += nw) {
            const int u = (j >> sh) * nA + rank, c = j & sh;
            if (u < UMAX && (c || step + 1 != NSEG)) {
              const uint32_t* gq = &g_part[0][0][0][0] + (uint32_t)((par * 2 + c) * NCL * 2560 + u * 64 + lane * 2);
              uint2 pa[NCL];
              POLL(pa, gq);
              deliver(pa, gq, u, c, step + 1 < NSEG ? c : 0, dual ? DS_DUAL : DS_SINGLE, step, j == 0, lane);
            }
            if (warp == 0 && j == 0) TS(13);
          }
          if (warp >= nw && (is_dual(step + 1) || (ig < 3 && step + 2 < NSTEP))) {
            issue_tok(is_dual(step + 1) ? sched_f(step + 1) : sched_l(step + 2), is_dual(step + 1) ? B_F1 : B_F2, B_R2, par ^ 1);
          }
          if (step + 1 == LAG && UMAX) {
            uint4 v[5];
#pragma unroll
            for (int i = 0; i < 5; i++) { const int t = warp * 160 + i * 32 + lane; v[i] = *reinterpret_cast<const uint4*>(mem0 + ((t >> 1) & 7) * DM + (t >> 4) * 16 + ((t ^ (t >> 3)) & 1) * 8); }
            mbar_waitu(bar + 8 * B_LANDFREE, par);
#pragma unroll
            for (int i = 0; i < 5; i++)
              st_async_v4(sb + OFF_TILE + LAND_F + warp * TILE_GRP + (i * 32 + lane) * 16, v[i].x, v[i].y, v[i].z, v[i].w, bar + 8 * (B_F1 + warp));
          }
        }
      }
      if (warp == (ig >= 0 && !is_dual(step + 1) ? 2 : 3)) {
        unsigned char* o0 = g_o + uni(step % RO * (96 * 8192) + (head * 3 + t3) * (dual ? 8192 : 4096));
        bar_sync(N_OX, 160);
        fence_async();
        bulk_s2g_es(o0, sb + OFF_PL, 4096);
        if (dual) bulk_s2g_es(o0 + 4096, sb + OFF_PL + PL_SZ, 4096);
        asm volatile("cp.async.bulk.commit_group;" ::: "memory");
        asm volatile("cp.async.bulk.wait_group.read 0;" ::: "memory");
        __syncwarp();
        mbar_arrive_remote_if(lane < 2, (lane ? nxt : prv) + OFF_BAR + 8 * B_PLFREE);
        asm volatile("cp.async.bulk.wait_group 0;" ::: "memory");
        asm volatile("fence.proxy.async.global;" ::: "memory");
        __syncwarp();
        if (lane == 0) red_release(&g_f[F_O + (head * 3 + t3) / 5][step], 1u);
        __syncwarp();
      }
    }
    cluster_sync_all();
  }
}

__device__ __forceinline__ uint32_t gelu2(uint32_t y, uint32_t s) {
  uint32_t g;
  asm("{\n.reg .b32 x, u, a, b;\nmov.b32 a, 0x28912891;\nmov.b32 b, 0x3a623a62;\nmul.rn.f16x2 x, %1, %2;\nmul.rn.f16x2 u, x, x;\nfma.rn.f16x2 u, u, a, b;\n"
      "mul.rn.f16x2 u, u, x;\ntanh.approx.f16x2 u, u;\nfma.rn.f16x2 %0, x, u, x;\n}" : "=r"(g) : "r"(y), "r"(s));
  return g; }

struct BParams {
  CUtensorMap wmap[5];
  CUtensorMap wo16;
  const __nv_bfloat16* x;
  __nv_bfloat16* out;
  uint64_t desc, desc32;
};
#define BO_O 0
#define BO_RES (6 * 8192)
#define OP_RES 63488
#define BO_STG (BO_RES + 2 * OP_RES)
#define BO_RING_OP (BO_STG + 16384)
#define OP_SLOT 12288
#define NS_OP 3
#define BO_H 81920
#define BO_W1 (BO_H + 16384)
#define BO_RING_MLP (BO_W1 + 81920)
#define BO_BAR 229376
#define BO_BOX (BO_BAR + 248)
#define BO_CARRY (BO_BAR + 512)
#define BO_STAT (BO_CARRY + 2048)
#define B_SMEM (BO_STAT + 256)
static_assert(B_SMEM <= 232448 && BO_RING_OP + NS_OP * OP_SLOT == BO_BAR && BO_RING_MLP + 3 * 16384 == BO_BAR && 2 * 83968 <= BO_RING_MLP, "smem");
enum { BB_W = 0, BB_FULL = 2, BB_TMP = BB_FULL + 3, BB_OFULL = BB_FULL + 5, BB_SFREE = BB_OFULL,
       BB_STAT = BB_SFREE + 6, BB_GO, BB_ZFREE, BB_DONE = BB_ZFREE + 3,
       BB_EMPTY, BB_START = BB_EMPTY, BB_USED = BB_EMPTY + 2, BB_NUM = BB_USED + 3 };
enum { NB_PP = 1, NB_H = 3, NB_END = 4, NB_END2 = 5, NB_STAGED = 6, NB_FREE = 8, NB_EARLY = 10, NB_LAST = 11 };

#define DESC_LO(off) (((SMEM0 + (off)) >> 4) | (1u << 16))

__device__ __forceinline__ uint32_t ld_relaxed(const uint32_t* p) { uint32_t v; asm volatile("ld.relaxed.gpu.global.b32 %0, [%1];" : "=r"(v) : "l"(p) : "memory"); return v; }
__device__ __forceinline__ int fmask(int r) { return (r < NSEG) | ((r >= LAG && r < NSTEP) << 1); }
__device__ __forceinline__ int bmask(int r) { return (r <= NSEG) | ((r >= LAG) << 1); }
__device__ __forceinline__ uint32_t rtarget(int mask) { return mask == 3 ? 64 : 32; }
__device__ __forceinline__ void warp_signal(uint32_t* p, int lane) {
  __syncwarp();
  asm volatile("{\n.reg .pred q;\nsetp.eq.u32 q, %1, 0;\n@q red.release.gpu.global.add.u32 [%0], 1;\n}" :: "l"(p), "r"(lane) : "memory");
}
__device__ __forceinline__ uint32_t pack2h(float lo, float hi) { uint32_t r; asm("cvt.rn.f16x2.f32 %0, %1, %2;" : "=r"(r) : "f"(hi), "f"(lo)); return r; }
template <bool H> __device__ __forceinline__ uint32_t pk(float lo, float hi) { return H ? pack2h(lo, hi) : pack2(lo, hi); }
template <int N, bool H> __device__ __forceinline__ void stage_out(const float* d, uint32_t dst, int warp, int lane) {
  const uint32_t sa = dst + ((lane >> 4) * 8 + (lane & 7)) * 128 + (((2 * warp + ((lane >> 3) & 1)) ^ (lane & 7)) << 4);
#pragma unroll
  for (int m = 0; m < N / 16; m++)
    stsm4t(sa + m * 2048, pk<H>(d[8 * m], d[8 * m + 1]), pk<H>(d[8 * m + 2], d[8 * m + 3]), pk<H>(d[8 * m + 4], d[8 * m + 5]), pk<H>(d[8 * m + 6], d[8 * m + 7]));
}
template <int N> __device__ __forceinline__ void acc_live(float* d) {
#pragma unroll
  for (int i = 0; i < N / 2; i++) asm volatile("" : "+f"(d[i]) :: "memory");
}
struct Ring {
  uint32_t sl, ph;
  template <int NS> __device__ __forceinline__ void step() { if (++sl == NS) { sl = 0; ph ^= 1; } }
};

#define KOFF(x) (DESC_LO(BO_O) + ((x) >> 2) * 512 + ((x) & 3) * 2)
template <int N, int P>
__device__ __forceinline__ void op_pass(const uint32_t* W, uint32_t bar, Dsc alo, Dsc blo, Dsc xlo, bool x2, Ring& rg, int wg, int warp, int lane, int r) {
  float acc[N / 2];
  blo.e = xlo.e = fresh<P + N / 64 * 5>(r);
  const Dsc tlo = blo + uni(rg.sl) * (OP_SLOT / 16), b2 = blo + (r & 1) * 1536;
  if (P == 0) mbar_waitu(bar + 8 * (BB_OFULL + 2 + (r & 1)), (r >> 1) & 1);
  CTS(5 * P);
  bar_sync(NB_PP + wg, 256);
  wg_fence();
#define OP_R(x, b) MM<N>::template rs<KOFF(4 * (x >> 1) + (x & 1)), (x != (P ? 0 : 4))>(acc, W + 32 * P + 4 * x, b);
#define OP_S(x, b) MM<N>::template ss<DESC_LO(BO_RES) + (6 * P + x) * 128, KOFF(4 * (x >> 1) + 2 + (x & 1)), 1>(acc, alo, b);
#define OP_T(x) MM<N>::template ss<DESC_LO(BO_RING_OP) + x * 128, KOFF(14 + x), 1>(acc, tlo, blo);
#define OP_B2() OP_R(4, b2) OP_S(4, b2) OP_R(5, b2) OP_S(5, b2)
  if (P == 0) { OP_B2() mbar_waitu(bar + 8 * BB_OFULL, r & 1); }
  OP_R(0, blo) OP_S(0, blo) OP_R(1, blo) OP_S(1, blo) OP_R(2, blo) OP_S(2, blo) OP_R(3, blo) OP_S(3, blo)
  if (P == 0) mbar_waitu(bar + 8 * (BB_OFULL + 1), r & 1);
  if (P == 4) wg_commit();
  if (P & 3) { OP_B2() }
  if (P == 1 && x2) MM<N>::template ss<DESC_LO(BO_RES) + 30 * 128, DESC_LO(BO_CARRY), 1>(acc, alo, xlo);
  mbar_waitu(bar + 8 * (BB_FULL + rg.sl), rg.ph);
  OP_R(6, blo) OP_T(0) OP_R(7, blo) OP_T(1)
  if (P == 4) { wg_commit(); wg_wait<1>(); bar_arrive(NB_EARLY, 288); CTS(21); wg_fence(); }
  OP_T(2) OP_T(3)
  if (P == 0) MM<N>::template rs<DESC_LO(BO_CARRY), 1>(acc, W + 160, xlo);
  OP_T(4) OP_T(5)
  if (P == 4) { wg_commit(); OP_B2() }
  wg_commit();
  bar_arrive(NB_PP + 1 - wg, 256);
  CTS(5 * P + 2);
  if (P == 4) { wg_wait<1>(); bar_arrive(NB_LAST, 288); }
  bar_sync(NB_FREE + wg, 160);
  wg_wait<0>();
  acc_live<N>(acc);
  mbar_arrive_if(lane == 0, bar + 8 * (BB_USED + rg.sl));
  CTS(5 * P + 3);
  stage_out<N, false>(acc, SMEM0 + BO_STG + wg * 8192, warp, lane);
  bar_arrive(NB_STAGED + wg, 160);
  CTS(5 * P + 4);
  rg.step<NS_OP>(); rg.step<NS_OP>();
}
template <int N>
__device__ __forceinline__ void op_round(const uint32_t* W, uint32_t bar, Dsc alo, Dsc blo, Dsc xlo, bool x2, Ring& rg, int wg, int warp, int lane, int r) {
  op_pass<N, 0>(W, bar, alo, blo, xlo, x2, rg, wg, warp, lane, r);
  op_pass<N, 1>(W, bar, alo, blo, xlo, x2, rg, wg, warp, lane, r);
  op_pass<N, 2>(W, bar, alo, blo, xlo, x2, rg, wg, warp, lane, r);
  op_pass<N, 3>(W, bar, alo, blo, xlo, x2, rg, wg, warp, lane, r);
  op_pass<N, 4>(W, bar, alo, blo, xlo, x2, rg, wg, warp, lane, r);
}
__device__ __forceinline__ void carry_in(uint32_t sb, int wg, int warp, int lane) {
  const int row = (lane >> 1) & 3;
  if (lane < 16) {
    const uint4 v = lds128(sb + BO_CARRY + (wg * 4 + warp) * 256 + lane * 16);
    sts128(sb + BO_H + wg * 8192 + (lane >> 3) * 4096 + row * 128 + (((2 * warp + (lane & 1)) ^ row) << 4), v.x, v.y, v.z, v.w);
  }
  __syncwarp();
}
template <int N, int Z>
__device__ __forceinline__ void p1_pair(float* acc, const uint32_t* W, uint32_t bar, Dsc alo, Dsc blo, int lane, int r) {
  constexpr uint32_t ZOFF = DESC_LO(BO_RING_MLP + (N == 64 ? (Z == 1 ? -1 : (4 - Z) & 3) * 16384 : (Z / 2 * 2 % 3) * 16384 + (Z & 1) * 4096));
  blo.e = fresh<10 + Z / 3 + N / 64 * 2>(r);
  mbar_waitu(bar + 8 * (BB_FULL + Z), r & 1);
  CTS(40 + Z);
  wg_fence();
#define P1_B(k) \
  MM<N, true>::template rs<ZOFF + k * 512, (2 * Z + k != 0)>(acc, W + 16 * Z + 8 * k, blo); \
  MM<N, true>::template ss<DESC_LO(BO_W1) + (2 * Z + k) * 512, ZOFF + k * 512 + 4, 1>(acc, alo, blo); \
  MM<N, true>::template rs<ZOFF + k * 512 + 2, 1>(acc, W + 16 * Z + 8 * k + 4, blo); \
  MM<N, true>::template ss<DESC_LO(BO_W1) + (2 * Z + k) * 512 + 128, ZOFF + k * 512 + 6, 1>(acc, alo, blo);
  P1_B(0)
  if (N == 64 && (Z == 1 || Z == 2)) { wg_commit(); wg_wait<1>(); mbar_arrive_if(lane == 0, bar + 8 * (BB_EMPTY + Z - 1)); wg_fence(); }
  P1_B(1)
  wg_commit();
}
template <int N>
__device__ __forceinline__ void phase1(const uint32_t* W, uint32_t sb, Dsc alo, Dsc blo, int half, int wg, int warp, int lane, bool shift, int off, int r) {
  float acc[N / 2];
  const uint32_t bar = sb + BO_BAR;
  CTS(30);
  p1_pair<N, 0>(acc, W, bar, alo, blo, lane, r);
  p1_pair<N, 1>(acc, W, bar, alo, blo, lane, r);
  p1_pair<N, 2>(acc, W, bar, alo, blo, lane, r);
  if (N == 64 && !wg) { mbar_waitu(bar + 8 * (BB_SFREE + 4), (r + 1) & 1); if (shift) carry_in(sb, wg, warp, lane); }
  p1_pair<N, 3>(acc, W, bar, alo, blo, lane, r);
  if (N == 32 || wg) { mbar_waitu(bar + 8 * (BB_SFREE + 4 + wg), (r + 1) & 1); if (shift) carry_in(sb, wg, warp, lane); }
  if (N == 32) mbar_arrive_if(lane < 2, bar + 8 * (BB_EMPTY + lane));
  p1_pair<N, 4>(acc, W, bar, alo, blo, lane, r);
  const int c = (lane >> 3) & 1, i0 = (lane >> 4) * 8 + (lane & 7) + off;
  uint32_t a0 = sb + BO_H + wg * 8192 + half * 4096 + i0 * 128 + (((2 * warp + c) ^ (i0 & 7)) << 4);
  uint32_t a1 = i0 >= 16 ? sb + BO_CARRY + (wg * 4 + warp) * 256 + half * 128 + (i0 - 16) * 32 + c * 16 : a0 + 2048, a3 = a1 + (i0 >= 16 ? 128 : 4096);
  asm volatile("" : "+r"(a0), "+r"(a1), "+r"(a3));
  mbar_waitu(bar + 8 * BB_STAT, r & 1);
  const uint32_t sa = sb + BO_STAT + (lane & 3) * 32 + half * 16;
  const uint4 t0 = lds128(sa), t1 = N == 64 ? lds128(sa + 16) : t0;
  const uint32_t t[8] = {t0.x, t0.y, t0.z, t0.w, t1.x, t1.y, t1.z, t1.w};
  { const uint32_t k4[4] = {a0, a1, a3, sa}; keep4(k4, lane); }
  wg_wait<0>();
  acc_live<N>(acc);
  CTS(32);
#pragma unroll
  for (int m = 0; m < N / 16; m++) {
    const float* d = acc + 8 * m;
    stsm4t(m == 1 ? a1 : m == 3 ? a3 : a0 + m * 2048, gelu2(pack2h(d[0], d[1]), t[2 * m]), gelu2(pack2h(d[2], d[3]), t[2 * m]),
           gelu2(pack2h(d[4], d[5]), t[2 * m + 1]), gelu2(pack2h(d[6], d[7]), t[2 * m + 1]));
  }
}
template <int N, int P>
__device__ __forceinline__ void p2_mma(float* acc, const uint32_t* W, Dsc alo, Dsc blo, int r) {
  blo.e = fresh<P + N / 64 * 5>(r);
  MM<N, true>::template rs<DESC_LO(BO_H), 0>(acc, W + 80 + 16 * P, blo);     MM<N, true>::template ss<DESC_LO(0) + P * 1024, DESC_LO(BO_H) + 512, 1>(acc, alo, blo);
  MM<N, true>::template rs<DESC_LO(BO_H) + 2, 1>(acc, W + 84 + 16 * P, blo); MM<N, true>::template ss<DESC_LO(0) + P * 1024 + 128, DESC_LO(BO_H) + 514, 1>(acc, alo, blo);
  MM<N, true>::template rs<DESC_LO(BO_H) + 4, 1>(acc, W + 88 + 16 * P, blo); MM<N, true>::template ss<DESC_LO(0) + P * 1024 + 512, DESC_LO(BO_H) + 516, 1>(acc, alo, blo);
  MM<N, true>::template rs<DESC_LO(BO_H) + 6, 1>(acc, W + 92 + 16 * P, blo); MM<N, true>::template ss<DESC_LO(0) + P * 1024 + 640, DESC_LO(BO_H) + 518, 1>(acc, alo, blo);
}
template <int N, int P, int T>
__device__ __forceinline__ void p2_pass(const uint32_t* W, uint32_t bar, Dsc alo, Dsc blo, int wg, int warp, int lane, int r) {
  float acc[N / 2], ac2[N / 2];
  CTS(5 * P);
  if (P || wg) bar_sync(NB_PP + wg, 256);
  wg_fence();
  p2_mma<N, P>(acc, W, alo, blo, r);
  wg_commit();
  if constexpr (T == 2) { p2_mma<N, P + 1>(ac2, W, alo, blo, r); wg_commit(); }
  if (P < 4 || !wg) bar_arrive(NB_PP + 1 - wg, 256);
  CTS(5 * P + 2);
  if (T == 1 && (P == 2 || P == 3)) mbar_waitu(bar + 8 * (BB_SFREE + 2 * (P - 2) + wg), r & 1);
  wg_wait<T - 1>();
  acc_live<N>(acc);
  if (P == 4) bar_sync(NB_H, 256);
  CTS(5 * P + 3);
  constexpr int K = P / T & 1;
  stage_out<N, true>(acc, SMEM0 + (P == 4 ? BO_H : BO_RING_MLP + (2 - K) * 16384) + wg * 8192, warp, lane);
  if constexpr (T == 2) {
    wg_wait<0>();
    acc_live<N>(ac2);
    stage_out<N, true>(ac2, SMEM0 + BO_RING_MLP + (2 - K) * 16384 + wg * 8192 + 4096, warp, lane);
  }
  bar_arrive(NB_STAGED + (P == 4 ? 4 : 2 * K) + wg, 160);
  CTS(5 * P + 4);
}
template <int N>
__device__ __forceinline__ void phase2(const uint32_t* W, uint32_t bar, Dsc alo, Dsc blo, int wg, int warp, int lane, int r) {
  if constexpr (N == 64) {
    p2_pass<N, 0, 1>(W, bar, alo, blo, wg, warp, lane, r);
    p2_pass<N, 1, 1>(W, bar, alo, blo, wg, warp, lane, r);
    p2_pass<N, 2, 1>(W, bar, alo, blo, wg, warp, lane, r);
    p2_pass<N, 3, 1>(W, bar, alo, blo, wg, warp, lane, r);
  } else {
    p2_pass<N, 0, 2>(W, bar, alo, blo, wg, warp, lane, r);
    p2_pass<N, 2, 2>(W, bar, alo, blo, wg, warp, lane, r);
  }
  p2_pass<N, 4, 1>(W, bar, alo, blo, wg, warp, lane, r);
}

__device__ __forceinline__ void ldg4(uint32_t* v, const void* p) {
  asm volatile("ld.relaxed.gpu.global.v4.u32 {%0,%1,%2,%3}, [%4];" : "=r"(v[0]), "=r"(v[1]), "=r"(v[2]), "=r"(v[3]) : "l"(p) : "memory"); }
__device__ __forceinline__ void stg4(void* p, const uint32_t* v) {
  asm volatile("st.global.v4.u32 [%0], {%1,%2,%3,%4};" :: "l"(p), "r"(v[0]), "r"(v[1]), "r"(v[2]), "r"(v[3]) : "memory"); }
struct RowPtr {
  unsigned char *p, *q, *t;
  __device__ __forceinline__ void ld(uint32_t* v, int o) const {
    ldg4(v, p + o); ldg4(v + 4, q + o);
    asm volatile("ld.relaxed.gpu.global.v2.u32 {%0,%1}, [%2];" : "=r"(v[8]), "=r"(v[9]) : "l"(t + o) : "memory");
  }
  __device__ __forceinline__ void st(const uint32_t* w, int o) const {
    stg4(p + o, w); stg4(q + o, w + 4);
    asm volatile("st.global.v2.u32 [%0], {%1,%2};" :: "l"(t + o), "r"(w[8]), "r"(w[9]) : "memory");
  }
};
__device__ __forceinline__ RowPtr row_img(int r, int n, int lane) {
  unsigned char* b = &g_acc[0][r % RD][n * 128];
  unsigned char* p = b + (uint32_t)((lane >> 3) * 8192 + (((lane ^ n) & 7) << 4));
  return {p, p + 32768, b + (uint32_t)(65536 + (lane >> 4) * 8192 + ((((lane >> 1) ^ n) & 7) << 4) + (lane & 1) * 8)};
}
__device__ __forceinline__ RowPtr row_ext(const void* lin, bool xn, int layer, int tok, int lane) {
  unsigned char* b = xn ? reinterpret_cast<unsigned char*>(&g_xn[layer][0]) + (uint32_t)((tok >> 5) * 40960 + ((tok >> 3) & 3) * 2560 + (tok & 7) * 32)
                        : (unsigned char*)lin + (uint32_t)(tok * 1280);
  const uint32_t o = (lane >> 1) * 256 + ((lane ^ (tok >> 2)) & 1) * 16;
  return {b + (uint32_t)(xn ? o + (lane >= 20 ? 7680 : 0) : lane * 16),
          b + (uint32_t)(xn ? o + 4096 + 7680 + (lane >= 8 ? 7680 : 0) + (lane >= 28 ? 7680 : 0) : lane * 16 + 512),
          b + (uint32_t)(xn ? (lane >> 2) * 256 + ((lane & 3) ^ ((tok >> 1) & 2)) * 8 + 8192 + 3 * 7680 : lane * 8 + 1024)};
}
__device__ __forceinline__ float2 h2f(uint32_t w) {
  float2 f; asm("{\n.reg .f16 l, h;\nmov.b32 {l, h}, %2;\ncvt.f32.f16 %0, l;\ncvt.f32.f16 %1, h;\n}" : "=f"(f.x), "=f"(f.y) : "r"(w)); return f; }
__device__ __forceinline__ float rsq(float x) { float y; asm("rsqrt.approx.ftz.f32 %0, %1;" : "=f"(y) : "f"(x)); return y; }
__device__ __forceinline__ void red_if(uint32_t v, const void* a) {
  asm volatile("{\n.reg .pred q;\nsetp.ne.u32 q, %1, 0;\n@q red.relaxed.gpu.global.add.u32 [%0], %1;\n}" :: "l"(a), "r"(v) : "memory"); }
__device__ __forceinline__ uint32_t dep0(uint32_t w, int lane) { uint32_t z; asm volatile("shr.b32 %0, %1, %2;" : "=r"(z) : "r"(w), "r"(lane + 32)); return z; }
__device__ __forceinline__ int lane_of(uint32_t w) {
  int lane; asm volatile("{\n.reg .u32 t;\nmov.u32 t, %%laneid;\nshr.u32 %0, %1, 20;\nadd.u32 %0, %0, t;\n}" : "=r"(lane) : "r"(w)); return lane; }
#define BUF (RD * TILE_B)
__device__ __forceinline__ int await(uint32_t v, const uint32_t* p, uint32_t target, bool lazy) {
  int n = 0;
  while (!__all_sync(~0u, v >= target)) {
    if (lazy) __nanosleep(200);
    if (++n > SPIN_LIMIT) FAIL();
    v = ld_relaxed(p);
  }
  asm volatile("fence.acquire.gpu;" ::: "memory");
  return lane_of(v);
}
template <int W> __device__ __forceinline__ void sum2(float& s, float& q, int lane) {
  const bool up = lane & (W / 2);
  float e = (up ? q : s) + __shfl_xor_sync(~0u, up ? s : q, W / 2);
#pragma unroll
  for (int o = W / 4; o; o >>= 1) e += __shfl_xor_sync(~0u, e, o);
  const float f = __shfl_xor_sync(~0u, e, W / 2);
  s = up ? f : e; q = up ? e : f;
}
template <int TYPE>
__device__ __forceinline__ void rrow(int r, int row, int tok, int lane, const uint32_t* go, int role, const __nv_bfloat16* x, __nv_bfloat16* out) {
  const int half = TYPE == 3 ? 0 : row >> 5;
  float v[20];
  float2 st = make_float2(1.f, 0.f);
  {
    uint32_t a[10], c[10], u[10], sh = 16;
    if (TYPE == 2) row_img(r + RD - ((row & 31) < 2), (row & 32) + ((row - 2) & 31), lane).ld(u, 3 * BUF);
    else row_ext(x, half, 1, tok, lane).ld(u, 0);
    if (TYPE == 2 || (TYPE == 0 && half))
      asm volatile("ld.relaxed.gpu.global.v2.f32 {%0,%1}, [%2];" : "=f"(st.x), "=f"(st.y) : "l"(g_stat + tok) : "memory");
    RowPtr ap = row_img(r, row, lane);
    const uint32_t g0 = TYPE != 3 ? ld_relaxed(go) : 0;
    if (TYPE != 3) {
      asm volatile("" : "+l"(ap.p), "+l"(ap.t));
      ap.q = ap.p + 32768;
      lane = await(g0, go, NOP * NW12 * NW34, false); BTS2(r, 8 + 2 * TYPE); RTS(0);
      ap.ld(a, TYPE ? 2 * BUF : 0);
    }
    if (TYPE == 0) {
      ap.ld(c, BUF);
      const uint32_t one = 0x3f803f80u | dep0(c[9], lane);
#pragma unroll
      for (int i = 0; i < 10; i++) asm volatile("fma.rn.bf16x2 %0, %0, %1, %2;" : "+r"(a[i]) : "r"(one), "r"(c[i]));
      sh |= dep0(a[9], lane);
    }
    const uint32_t z = TYPE == 2 ? dep0(a[9], lane) : 0;
#pragma unroll
    for (int i = 0; i < 10; i++) {
      if (TYPE == 2) { const float2 g = h2f(u[i] | z), h = h2f(a[i] | z); v[2 * i] = fmaf(h.x, 0.5f, g.x * st.x); v[2 * i + 1] = fmaf(h.y, 0.5f, g.y * st.x); continue; }
      float p = __uint_as_float(u[i] << sh), q = __uint_as_float(u[i] & (0xffffu << sh));
      if (TYPE == 0) { p = fmaf(p, st.x, bf_lo(a[i])); q = fmaf(q, st.x, bf_hi(a[i])); }
      v[2 * i] = p; v[2 * i + 1] = q;
    }
  }
  RTSD(1, v[19]);
  float s = 0.f, q = 0.f;
#pragma unroll
  for (int i = 0; i < 5; i++) {
    s += (v[4 * i] + v[4 * i + 1]) + (v[4 * i + 2] + v[4 * i + 3]);
    q += fmaf(v[4 * i], v[4 * i], v[4 * i + 1] * v[4 * i + 1]) + fmaf(v[4 * i + 2], v[4 * i + 2], v[4 * i + 3] * v[4 * i + 3]);
  }
  if (!(TYPE == 2 && half)) sum2<32>(s, q, lane);
  const float mean = s * (1.f / DM), var = fmaxf(q * (1.f / DM) - mean * mean, 0.f), rs = rsq(var + 1e-5f);
  const float k = TYPE == 0 ? 2.f * rs : half ? 1.f : rs, mr = TYPE && half ? st.y : -mean * k;
  RTSD(2, rs);
  uint32_t w[10];
#pragma unroll
  for (int i = 0; i < 10; i++) w[i] = pk<TYPE == 0>(fmaf(v[2 * i], k, mr), fmaf(v[2 * i + 1], k, mr));
  if (TYPE) row_ext(out, !half, TYPE == 2, tok, lane).st(w, 0);
  else {
    row_img(r, row, lane).st(w, 3 * BUF);
    row_img(r + ((row & 31) >= 30), (row & 32) + ((row + 2) & 31), lane).st(w, 2 * BUF);
    if (lane == 1) g_st2[0][r % RD][row] = (__float_as_uint(0.5f * rsq(fmaf(var * rs, rs, 1e-5f))) & ~127u) | (r + 1);
  }
  if (TYPE != 3 && lane == 0) g_stat[tok] = make_float2((var + 1e-5f) * rs * (TYPE ? 1.f : 0.5f), mean + st.y);
}
__device__ __forceinline__ void r2rows(int r, int row, int lane, const uint32_t* go) {
  const int n = row + (lane >> 4);
  const unsigned char* ap = &g_acc[2][r % RD][0] + (uint32_t)(n * 128 + ((lane >> 3) & 1) * 8192 + (((lane ^ n) & 7) << 4));
  const uint32_t* sp = &g_st2[1][r % RD][n];
  asm volatile("" : "+l"(ap), "+l"(sp));
  await(0, go, NOP * NW12 * NW34, false);
  BTS2(r, 10);
  uint32_t a[20];
#pragma unroll
  for (int i = 0; i < 5; i++) ldg4(a + 4 * i, ap + i * 16384);
  const uint32_t z = dep0(a[19], lane);
  float s = 0.f, q = 0.f, q2 = 0.f;
#pragma unroll
  for (int i = 0; i < 20; i++) { const float2 h = h2f(a[i] | z); s += h.x + h.y; q = fmaf(h.x, h.x, q); q2 = fmaf(h.y, h.y, q2); }
  q += q2;
  sum2<16>(s, q, lane);
  const float mean = s * (0.5f / DM), rs = rsq(fmaxf(q * (0.25f / DM) - mean * mean, 0.f) + 1e-5f);
  if ((lane & 15) == 0) asm volatile("st.relaxed.gpu.global.u32 [%0], %1;" :: "l"(sp), "r"((__float_as_uint(0.5f * rs) & ~127u) | (r + 1)) : "memory");
}
__device__ __forceinline__ void r3rows(int r, int row, int tok, int lane, __nv_bfloat16* out) {
  const int n = row + (lane >> 4), m = 32 + ((n - 2) & 31);
  const unsigned char* ap = &g_acc[0][r % RD][0] + (uint32_t)(n * 128 + ((lane >> 3) & 1) * 8192 + (((lane ^ n) & 7) << 4));
  const unsigned char* zp = &g_acc[3][(r + RD - (row == 32)) % RD][0] + (uint32_t)(m * 128 + ((lane >> 3) & 1) * 8192 + (((lane ^ m) & 7) << 4));
  unsigned char* op = reinterpret_cast<unsigned char*>(out) + (uint32_t)((tok + (lane >> 4)) * 1280 + (lane & 15) * 16);
  float2 st;
  asm volatile("ld.relaxed.gpu.global.v2.f32 {%0,%1}, [%2];" : "=f"(st.x), "=f"(st.y) : "l"(g_stat + tok + (lane >> 4)) : "memory");
#pragma unroll 1
  for (int i0 = 0; i0 < 2; i0++) {
    uint32_t a[12], u[12];
#pragma unroll
    for (int i = 0; i < 3; i++) { ldg4(a + 4 * i, ap + 2 * BUF + i * 16384); ldg4(u + 4 * i, zp + i * 16384); }
    uint32_t z = dep0(u[11], lane);
#pragma unroll
    for (int i = 0; i < 12; i++) {
      const float2 h = h2f(a[i] | z), g = h2f(u[i] | z);
      a[i] = pack2(fmaf(h.x, 0.5f, fmaf(g.x, st.x, st.y)), fmaf(h.y, 0.5f, fmaf(g.y, st.x, st.y)));
      if (i & 1) z = dep0(a[i], lane);
    }
    if (i0 == 0) stg4(op, a);
    stg4(op + 256, a + 4); stg4(op + 512, a + 8);
    ap += 32768; zp += 32768; op += 512;
  }
}
template <int TYPE>
__device__ __forceinline__ void rloop(int row, int cp, int role, const __nv_bfloat16* x, __nv_bfloat16* out) {
  constexpr int ST = TYPE == 4 ? 2 : TYPE;
  const int r0 = row & 32 ? LAG : 0;
  uint32_t v = 0;
  static_assert(NSEG + RD >= NSTEP, "no signals");
#pragma unroll 1
  for (int r = r0; r < (TYPE == 2 ? NR : TYPE == 4 ? NSEG + 1 : r0 + NSEG + (TYPE > 0)); r++) {
    if (TYPE == 2 && r == NSEG + 1) row += 32;
    const int tok = (r - (row & 32 ? LAG : 0)) * 32 + (row & 31) - (TYPE ? 2 : 0);
    const bool valid = TYPE == 0 || (unsigned)tok < S_LEN;
    const uint32_t* go = &g_f[F_R1 + 4 * ST + cp][r];
    const uint32_t* first = TYPE == 2 ? &g_f[F_R2 + cp][r] : TYPE ? go : (const uint32_t*)&g_xready[NSEG + r - r0][0];
    if constexpr (TYPE == 1) { r2rows(r, row, lane_of(r), go); BTS2(r, 11); continue; }
    if constexpr (TYPE == 4) {
      const int lane = await(v, go, NOP * NW12 * NW34, false);
      BTS2(r, 8 + 2 * ST); RTS(0);
      if (valid) r3rows(r, row, tok, lane, out);
    } else if constexpr (TYPE != 1) {
      if (TYPE || row >= 32) await(v, first, TYPE ? NOP * NW12 * NW34 : 32, true);
      if (valid) rrow<TYPE>(r, row, tok, lane_of(r), go, role, x, out);
    }
    if (TYPE > 1 && row >= 32 && r + RD - 1 >= NSTEP) { v = 0; BTS2(r, 13); continue; }
    const int lane = lane_of(r);
    const void* f = lane ? (const void*)&g_xready[NSEG + (tok >> 5)][0] : (const void*)&g_f[TYPE ? F_DONE : F_Z][r];
    asm volatile("" : "+l"(f));
    __syncwarp();
    RTS(3);
    v = ld_relaxed(first + (TYPE ? 1 : 8));
    asm volatile("fence.release.gpu;" ::: "memory");
    RTS(4);
    red_if(lane == 0 || (TYPE == 2 && lane == 1 && valid) ? (TYPE & 5 ? 2 : 1) : 0, f);
    RTS(5);
    RTS_OUT();
    BTS2(r, 9 + 2 * ST);
  }
}

#define SINGLE_OP 3
#define SINGLE_W 0
#define W_DELAY 0
#define BULK_ADD(T, dst, src, len) asm volatile("{\n.reg .pred e;\nelect.sync _|e, 0xffffffff;\n@e cp.reduce.async.bulk.global.shared::cta.bulk_group.add.noftz." T " [%0], [%1], %2;\n}" \
                                               :: "l"(dst), "r"(src), "r"(len) : "memory")
#define COMMIT() asm volatile("cp.async.bulk.commit_group;" ::: "memory")
#define DRAINED(n) do { asm volatile("cp.async.bulk.wait_group.read " #n ";" ::: "memory"); __syncwarp(); } while (0)
#define WRITTEN() do { asm volatile("cp.async.bulk.wait_group 0;\nfence.proxy.async.global;" ::: "memory"); __syncwarp(); } while (0)
__device__ __forceinline__ void wait_flags(const uint32_t* p, uint32_t target) {
  int n = 0;
  while (!__all_sync(~0u, ld_relaxed(p) >= target)) { if (++n > SPIN_LIMIT) FAIL(); }
  asm volatile("fence.acquire.gpu;" ::: "memory");
  asm volatile("fence.proxy.async.global;" ::: "memory");
}
__global__ void __launch_bounds__(512, 1) bworker_kernel(const __grid_constant__ BParams P) {
  extern __shared__ __align__(1024) unsigned char smem_raw[];
  const uint32_t sb = SMEM0, bar = sb + BO_BAR;
  const int wg = __shfl_sync(~0u, threadIdx.x >> 7, 0), warp = __shfl_sync(~0u, (threadIdx.x >> 5) & 3, 0);
  if (threadIdx.x == 0) {
    if (smem_u32(smem_raw) != SMEM0) FAIL();
    uint32_t smid; asm volatile("mov.u32 %0, %%smid;" : "=r"(smid));
    const uint32_t nb = ld_relaxed(&g_tpc[(smid >> 1) & 127]);
    const bool single = nb > 1, far = nb == 0 && (smid < 64 || smid >= 124);
    int kind = far || (single && atomicAdd(&g_f[F_MISC][35], 1u) < SINGLE_OP) ? 0 : single ? 1 + SINGLE_W : 1;
    int rc = single || (smid >> 1) == 16 || (smid >> 1) == 63 ? 1 : far ? 2 : 0;
    uint32_t i = atomicAdd(&g_f[F_MISC][32 + kind], 1u), o = atomicAdd(&g_f[F_MISC][36 + rc], 1u);
    while (i >= (kind == 0 ? NOP : kind == 1 ? NW12 : NW34)) { kind = (kind + 1) % 3; i = atomicAdd(&g_f[F_MISC][32 + kind], 1u); }
    while (o >= (rc == 0 ? 16 : rc == 1 ? 8 : 12)) { rc = (rc + 1) % 3; o = atomicAdd(&g_f[F_MISC][36 + rc], 1u); }
    sts64(sb + BO_BOX, i + (kind == 0 ? 0 : kind == 1 ? NOP : NOP + NW12), o + (rc ? 8 + 8 * rc : 0));
    for (int k = 0; k < BB_NUM; k++) mbar_init(bar + 8 * k, k >= BB_USED ? 4 : k >= BB_EMPTY ? 8 : k >= BB_ZFREE && kind ? 2 : 1);
    asm volatile("fence.mbarrier_init.release.cluster;" ::: "memory");
  }
  if (threadIdx.x < 128) sts128(sb + BO_CARRY + threadIdx.x * 16, 0u, 0u, 0u, 0u);
  auto ln0 = [&](int t) {
    const int lane = lane_of(t);
    if (lane < 20 && t + 128 < S_LEN) asm volatile("prefetch.global.L2 [%0];" :: "l"(P.x + (t + (t < 4 * NBC ? 4 * NBC : 128)) * DM + (lane >> 1) * 64));
    rrow<3>(0, 0, t, lane, nullptr, 0, P.x, nullptr);
    __syncwarp();
    asm volatile("fence.release.gpu;" ::: "memory");
    red_if(lane == 0, &g_xready[t >> 5][0]);
  };
  if (wg == 2) ln0(blockIdx.x * 4 + warp);
  fence_async();
  __syncthreads();
  const int role = uni(lds32(sb + BO_BOX));
  if (threadIdx.x < 32) BTS(94, 1);
  const bool op = role < NOP, w12 = role < NOP + NW12;
  const int j = op ? role : w12 ? role - NOP : role - NOP - NW12;
  const int rot = op ? (j ? 2 * ((j + 1) % 5) : 0) : 2 * (j % 5);
  if (wg == 3) {
    asm volatile("setmaxnreg.dec.sync.aligned.u32 24;");
    LANE_INIT();
    if (warp < 2) {
      auto announce = [&](int r) {
        const uint32_t* f = &g_f[(op ? F_R1 : w12 ? F_R2 : F_R3) + (lane & 3)][r];
        asm volatile("" : "+l"(f));
        if (warp == 0) { mbar_arrive_if(lane == 0, bar + 8 * BB_DONE); return; }
        mbar_waitw(bar + 8 * BB_DONE, r & 1);
        PTS(60);
        asm volatile("fence.release.gpu;" ::: "memory");
        red_if(lane >= 4 ? 0 : op ? NW12 * NW34 : w12 ? NOP * NW34 : NOP * NW12, f);
        PTS(61);
        BTS(r, 4);
      };
      if (op) {
        int mt = rot + warp;
        bar_arrive(NB_FREE + warp, 160);
#pragma unroll 1
        for (int r = 0; r < NSTEP; r++) {
          const uint32_t len = fmask(r) == 3 ? 8192 : 4096;
          unsigned char* acc = &g_acc[j & 1][r % RD][fmask(r) == 2 ? 4096 : 0];
#pragma unroll 1
          for (int p = 0; p < 5; p++) {
            bar_sync(NB_STAGED + warp, 160);
            PTS(50 + 2 * p + warp);
            fence_async();
            BULK_ADD("bf16", acc + mt * 8192, sb + BO_STG + warp * 8192, len);
            COMMIT();
            PTS(64 + 50 + 2 * p + warp);
            mt = mt >= 8 ? mt - 8 : mt + 2;
            DRAINED(0);
            bar_arrive(NB_FREE + warp, 160);
          }
          WRITTEN();
          announce(r);
        }
      } else {
#pragma unroll 1
        for (int r = 0; r < NR; r++) {
          const uint32_t len = bmask(r) == 3 ? 8192 : 4096;
          unsigned char* acc = &g_acc[2][r % RD][bmask(r) == 2 ? 4096 : 0];
          if (!w12) mbar_waitw(bar + 8 * BB_GO, r & 1);
          int mt = rot + warp;
          const bool pairs = len != 8192;
#pragma unroll 1
          for (int p = pairs ? 2 : 0; p < 5; p++) {
            const uint32_t src = sb + (p == 4 ? BO_H : BO_RING_MLP + (2 - (p & 1)) * 16384) + warp * 8192;
            bar_sync(NB_STAGED + (p == 4 ? 4 : 2 * (p & 1)) + warp, 160);
            PTS(50 + 2 * p + warp);
            fence_async();
            BULK_ADD("f16", acc + mt * 8192, src, len);
            mt = mt >= 8 ? mt - 8 : mt + 2;
            if (pairs && p < 4) { BULK_ADD("f16", acc + mt * 8192, src + 4096, len); mt = mt >= 8 ? mt - 8 : mt + 2; }
            COMMIT();
            PTS(64 + 50 + 2 * p + warp);
            if (p == 4 && !pairs) break;
            DRAINED(1);
            mbar_arrive_if(lane == 0 && p, bar + 8 * (p < 3 ? BB_SFREE + 2 * (p - 1) + warp : BB_ZFREE + (p >> 1)));
            mbar_arrive_if(lane == 0 && pairs && p == 2, bar + 8 * (BB_SFREE + warp));
            if (p == 3 && !pairs) { DRAINED(0); mbar_arrive_if(lane == 0, bar + 8 * (BB_ZFREE + 2)); }
          }
          WRITTEN();
          mbar_arrive_if(lane == 0, bar + 8 * (BB_SFREE + 4 + warp));
          announce(r);
        }
      }
    } else {
      if (op && warp == 2) {
        unsigned char* wt = g_wt + j * (10 * OP_SLOT);
#pragma unroll 1
        for (int m0 = 0; m0 < 10; m0 += 3) {
          const int nu = m0 < 9 ? 9 : 3;
          mbar_expect_if(lane == 0, bar + 8 * BB_TMP, nu * 4096);
#pragma unroll 1
          for (int k = 0; k < nu; k++) tma2d_e(sb + BO_RING_OP + k * 4096, &P.wmap[0], (m0 + k / 3) * 64, 320 * j + 224 + 32 * (k % 3), bar + 8 * BB_TMP);
          mbar_waitw(bar + 8 * BB_TMP, m0 & 1);
          bulk_s2g_e(wt + m0 * OP_SLOT, sb + BO_RING_OP, nu * 4096);
          COMMIT();
          WRITTEN();
        }
        asm volatile("fence.acq_rel.gpu;" ::: "memory");
        int sl = 0, ph = 1, mt = rot;
#pragma unroll 1
        for (int r = -1; r < NSTEP; r++) {
#pragma unroll 1
          for (int n = r < 0 ? 7 : 0; n < (r + 1 < NSTEP ? 10 : 7); n++) {
            mbar_waitw(bar + 8 * (BB_USED + sl), ph);
            mbar_expect_if(lane == 0, bar + 8 * (BB_FULL + sl), OP_SLOT);
            bulk_g2s_e(sb + BO_RING_OP + sl * OP_SLOT, wt + mt * OP_SLOT, OP_SLOT, bar + 8 * (BB_FULL + sl));
            if (++sl == 3) { sl = 0; ph ^= 1; }
            mt = mt == 9 ? 0 : mt + 1;
          }
        }
      } else if (op) {
        mbar_waitw(bar + 8 * BB_START, 0);
#pragma unroll 1
        for (int r = 0; r < NSTEP; r++) {
          const int rb = r - RD + 1;
          const uint32_t len = fmask(r) == 3 ? 8192 : 4096;
          const unsigned char* src = g_o + (uint32_t)(r % RO * (96 * 8192) + 5 * j * len);
          wait_flags(lane < 2 ? &g_f[F_O + (lane ? NOP : j)][r] : rb >= 0 ? &g_f[F_DONE][rb] : &g_f[F_MISC][0],
                     lane < 2 ? (lane ? 1 : 5) : rb >= 0 ? rtarget(bmask(rb)) : NBC * 8);
          PTS1(35);
          auto two = [&](int k, uint32_t mb) {
            bulk_g2s_e(sb + BO_O + k * 8192, src + k * len, len == 8192 ? 16384 : 4096, mb);
            if (len != 8192) bulk_g2s_e(sb + BO_O + k * 8192 + 8192, src + k * len + 4096, 4096, mb);
          };
          mbar_expect_if(lane == 0, bar + 8 * (BB_OFULL + 2 + (r & 1)), len);
          bulk_g2s_e(sb + BO_O + (r & 1 ? 5 : 2) * 8192, src + 2 * len, len, bar + 8 * (BB_OFULL + 2 + (r & 1)));
          if (r) bar_sync(NB_EARLY, 288);
          mbar_expect_if(lane < 2, bar + 8 * (BB_OFULL + lane), 2 * len + (lane ? len / 4 : 0));
          two(0, bar + 8 * BB_OFULL);
          PTS(62); PTS1(38);
          const unsigned char* sx = src + (95 - 5 * j) * len + (j + 1) / 5 * 1024;
          if (r) bar_sync(NB_LAST, 288);
          two(3, bar + 8 * (BB_OFULL + 1));
          bulk_g2s_e(sb + BO_CARRY, sx, 1024, bar + 8 * (BB_OFULL + 1));
          if (len == 8192) bulk_g2s_e(sb + BO_CARRY + 1024, sx + 4096, 1024, bar + 8 * (BB_OFULL + 1));
          if (r && r + 1 < NSTEP) {
            mbar_waitw(bar + 8 * (BB_USED + (10 * r - 2) % 3), (10 * r - 2) / 3 & 1);
            mbar_waitw(bar + 8 * (BB_USED + (10 * r - 1) % 3), (10 * r - 1) / 3 & 1);
          }
          PTS1(64 + 35);
          BTS(r, 0);
        }
      } else if (warp == 2) {
#pragma unroll 1
        for (int r = 0; r < NR; r++) {
          const int mk = w12 ? fmask(r) : bmask(r);
          if (mk) {
            const unsigned char* src = &g_acc[w12 ? 3 : 2][r % RD][mk == 2 ? 4096 : 0];
            wait_flags(&g_f[w12 ? F_Z : F_R2 + (j & 3)][r], w12 ? rtarget(mk) : NOP * NW12 * NW34);
#pragma unroll 1
            for (int z = 0; z < 5; z++) {
              const int k = mk == 3 ? z - (z > 0) : z >> 1;
              const uint32_t fb = bar + 8 * (BB_FULL + z), dst = sb + BO_RING_MLP + 2 * k % 3 * 16384 + (mk != 3 ? (z & 1) * 4096 : z == 1 ? -16384 : 0);
              if (mk == 3 ? z != 1 : !(z & 1)) mbar_waitw(bar + 8 * (k < 3 ? BB_ZFREE + k : BB_EMPTY), (r + (k < 3)) & 1);
              if (z == 0) PTS(62);
              mbar_expect_if(lane == 0, fb, mk != 3 ? 8192 : z == 4 ? 32768 : 16384);
              bulk_g2s_e(dst, src + z * 16384, mk == 3 ? 16384 : 4096, fb);
              if (mk != 3) bulk_g2s_e(dst + 8192, src + z * 16384 + 8192, 4096, fb);
              else if (z == 4) { mbar_waitw(bar + 8 * (BB_EMPTY + 1), r & 1); bulk_g2s_e(sb + BO_RING_MLP - 16384, g_wx[role - NOP], 16384, fb); }
              if (z == 0) BTS(r, 0);
            }
          }
          if (!w12) {
#pragma unroll 1
            for (int z = mk == 3 ? 2 : 0; z < 5; z++) mbar_waitw(bar + 8 * (BB_FULL + z), r & 1);
            red_if(lane == 0, &g_f[F_GOT][r]);
#pragma unroll 1
            for (int c = j; c < 80; c += NW34) bulk_s2g_e(&g_acc[c / 40][r % RD][c % 40 * 2048], sb + BO_CARRY, 2048);
            COMMIT();
            wait_flags(&g_f[F_GOT][r], NW34);
            mbar_arrive_if(lane == 0, bar + 8 * BB_GO);
            WRITTEN();
          }
          mbar_waitw(bar + 8 * BB_DONE, (r + 1) & 1);
          mbar_arrive_if(lane == 0, bar + 8 * BB_DONE);
        }
      } else {
#pragma unroll 1
        for (int r = 0; r < (w12 ? NSTEP : NR); r++) {
          const bool idle = !((w12 ? fmask(r) : bmask(r)) >> (lane >> 4) & 1);
          uint32_t t0, t1;
          int n = 0;
          mbar_waitw(bar + 8 * BB_FULL, r & 1);
          do {
            asm volatile("ld.relaxed.gpu.global.v2.u32 {%0,%1}, [%2];" : "=r"(t0), "=r"(t1) : "l"(&g_st2[!w12][r % RD][2 * lane]) : "memory");
            if (++n > SPIN_LIMIT) FAIL();
          } while (!__all_sync(~0u, idle || (((t0 ^ (r + 1)) | (t1 ^ (r + 1))) & 127) == 0));
          sts32(sb + BO_STAT + (lane & 3) * 32 + (lane >> 2) * 4, pack2h(__uint_as_float(t0), __uint_as_float(t1)));
          __syncwarp();
          mbar_arrive_if(lane == 0, bar + 8 * BB_STAT);
          PTS(63);
        }
      }
    }
    bar_arrive(NB_END, 512);
  } else if (wg == 2) {
    asm volatile("setmaxnreg.dec.sync.aligned.u32 40;");
    const int ord = uni(lds32(sb + BO_BOX + 4));
    const int g2 = warp * 12 + ord - 24, gw = ord < 16 ? warp * 16 + ord : ord < 24 ? 80 + warp * 8 + ord : g2 < 32 ? 64 + g2 : 96 + g2;
    const int row = gw < 64 ? gw : gw < 96 ? gw - 64 : gw < 128 ? 2 * gw - 192 : 2 * gw - 224;
    if (row >= 32) {
#pragma unroll 1
      for (int t = 4 * NBC + (gw < 64 ? gw - 32 : gw - 80); t < S_LEN; t += 64) ln0(t);
    }
    if (gw < 64) rloop<0>(row, gw & 3, role, P.x, P.out);
    else if (gw < 96) rloop<2>(row, gw & 3, role, P.x, P.out);
    else if (gw < 128) rloop<1>(row, gw & 3, role, P.x, P.out);
    else rloop<4>(row, gw & 3, role, P.x, P.out);
    asm volatile("griddepcontrol.wait;" ::: "memory");
    const int t = threadIdx.x & 127;
    for (int i = (blockIdx.x * 128 + t) * 4; i < 4 * NCL * 2560; i += NBC * 512)
      *reinterpret_cast<uint4*>(&g_part[0][0][0][0] + i) = make_uint4(0u, 0u, 0u, 0u);
    bar_sync(NB_END, 512);
    if (t == 0) {
      uint32_t n;
      asm volatile("atom.acq_rel.gpu.global.add.u32 %0, [%1], 1;" : "=r"(n) : "l"(&g_f[F_MISC][64]) : "memory");
      sts32(sb + BO_BOX, n);
    }
    bar_sync(NB_END2, 128);
    if (lds32(sb + BO_BOX) == NBC - 1) {
      for (int i = t; i < F_NUM * 24; i += 128) reinterpret_cast<uint4*>(&g_f[0][0])[i] = make_uint4(0u, 0u, 0u, 0u);
      g_xready[t][0] = 0; g_tpc[t] = 0;
    }
  } else {
    asm volatile("setmaxnreg.inc.sync.aligned.u32 224;");
    LANE_INIT();
    for (int i = blockIdx.x * 256 + threadIdx.x; i < 2 * RD * TILE_B / 16; i += NBC * 256) reinterpret_cast<uint4*>(&g_acc[0][0][0])[i] = make_uint4(0u, 0u, 0u, 0u);
    warp_signal(&g_f[F_MISC][0], lane);
    const int mt0 = (rot + wg) % 10;
    auto boxes = [&](int ss) {
      const int nb = op && ss ? 3 : 4;
      const uint32_t base = sb + (ss ? BO_RES + wg * OP_RES : wg * 83968);
      mbar_expect_if(warp == 0 && lane == 0, bar + 8 * (BB_W + wg), nb * 20480 + (op ? 2048 : 0));
      bar_sync(NB_H, 256);
      if (warp < nb) {
#pragma unroll 1
        for (int i = warp; i < 5 * nb; i += nb) {
          const int p = op ? i / nb : (i - 10) >> 1, mt = (mt0 + 2 * p) % 10;
          const bool first = !op && i < 10;
          tma2d_e(op || !ss ? base + i * 4096 : sb + (first ? BO_W1 : -81920) + (2 * i + wg) * 4096, &P.wmap[op ? 0 : (w12 ? 1 : 3) + !first], first ? 128 * j + 64 * wg : mt * 64,
                  op ? 320 * j + 64 * warp + 32 * ss : first ? 64 * i + 32 * ss : 128 * j + 32 * (i & 1) + 64 * ss, bar + 8 * (BB_W + wg));
        }
      }
      if (op && warp == 3) tma2d_e(base + nb * 20480, &P.wo16, (mt0 + 2 * ss) % 10 * 64, 95 * 64 + (j + 1) / 5 * 16, bar + 8 * (BB_W + wg));
      mbar_waitw(bar + 8 * (BB_W + wg), ss);
    };
    if (W_DELAY && !op) __nanosleep(W_DELAY);
    uint32_t W[164];
    boxes(0);
    load_w<41>(W, sb + wg * 83968, warp, lane);
    fence_async();
    boxes(1);
    if (!op) {
      float cs[2] = {0.f, 0.f};
      const uint32_t a0 = sb + BO_W1 + wg * 4096 + ((lane >> 4) * 8 + (lane & 7)) * 128 + (((warp * 2 + ((lane >> 3) & 1)) ^ (lane & 7)) << 4);
#pragma unroll
      for (int i = 0; i < 80; i++) cs[i & 1] += bf_lo(W[i]) + bf_hi(W[i]);
#pragma unroll 1
      for (int i = 0; i < 60; i++) {
        uint32_t t[4];
        const uint32_t ad = a0 + (i % 20 >> 1) * 8192 + (i & 1) * 2048 - (i >= 40 ? BO_W1 : 0);
        ldsm4t(t[0], t[1], t[2], t[3], ad);
#pragma unroll
        for (int k = 0; k < 4; k++) {
          if (i < 20) cs[k & 1] += bf_lo(t[k]) + bf_hi(t[k]);
          const float mu = i < 40 ? cs[k & 1] : 0.f;
          t[k] = pack2h(bf_lo(t[k]) - mu, bf_hi(t[k]) - mu);
        }
        if (i >= 20) stsm4t(ad, t[0], t[1], t[2], t[3]);
        if (i == 19) {
#pragma unroll
          for (int k = 0; k < 2; k++) { cs[k] += __shfl_xor_sync(~0u, cs[k], 1); cs[k] += __shfl_xor_sync(~0u, cs[k], 2); cs[k] *= 1.f / DM; }
        }
      }
      const uint32_t z = dep0(__float_as_uint(cs[0]), lane);
#pragma unroll
      for (int i = 0; i < 80; i++) { W[i] = pack2h(bf_lo(W[i] | z) - cs[i & 1], bf_hi(W[i] | z) - cs[i & 1]); W[80 + i] = pack2h(bf_lo(W[80 + i]), bf_hi(W[80 + i])); }
      fence_async();
      bar_sync(NB_H, 256);
      if (wg + warp == 0) { bulk_s2g_e(g_wx[role - NOP], sb + BO_RING_MLP - 16384, 16384); COMMIT(); WRITTEN(); asm volatile("fence.acq_rel.gpu;" ::: "memory"); }
    }
    if (warp == 0) BTS(94, 6 + wg);
    const Dsc blo = {P.desc, 1}, alo = blo + wg * (op ? OP_RES / 16 : 256);
    if (op) {
      Ring rg = {(uint32_t)wg, 0};
      mbar_arrive_if(lane == 0, bar + 8 * BB_START);
      if (wg) bar_arrive(NB_PP, 256);
      const Dsc xlo = {P.desc32, 1};
#pragma unroll 1
      for (int r = 0; r < NSTEP; r++) {
        asm volatile("" : "+r"(lane));
        if (fmask(r) == 3) op_round<64>(W, bar, alo, blo, xlo, j == 0, rg, wg, warp, lane, r);
        else op_round<32>(W, bar, alo, blo, xlo, j == 0, rg, wg, warp, lane, r);
        if (warp == 0) BTS(r, 2 + wg);
      }
    } else {
      const int q4 = (128 * j + 64 * wg + 16 * warp) / 160, off = w12 ? (0x0413 >> (4 * q4)) & 7 : 0;
#pragma unroll 1
      for (int r = 0; r < NR; r++) {
        asm volatile("" : "+r"(lane));
        const int bm = bmask(r), fm = w12 ? fmask(r) : bm;
        if (fm == 3) phase1<64>(W, sb, alo, blo, 0, wg, warp, lane, w12, off, r);
        else if (fm) phase1<32>(W, sb, alo, blo, fm >> 1, wg, warp, lane, w12, off, r);
        else { mbar_waitu(bar + 8 * (BB_SFREE + 4 + wg), (r + 1) & 1); carry_in(sb, wg, warp, lane); }
        CTS(33);
        fence_async();
        bar_sync(NB_H, 256);
        mbar_arrive_if(wg == 1 && warp == 0 && lane < 2, bar + 8 * BB_ZFREE);
        if (wg + warp == 0) BTS(r, 1);
        if (bm == 3) phase2<64>(W, bar, alo, blo, wg, warp, lane, r);
        else phase2<32>(W, bar, alo, blo + (bm >> 1) * 256, wg, warp, lane, r);
        if (warp == 0) BTS(r, 2 + wg);
      }
    }
    CTS_OUT();
    bar_arrive(NB_END, 512);
  }
}

typedef CUresult (*EncodeFn)(CUtensorMap*, CUtensorMapDataType, cuuint32_t, void*, const cuuint64_t*, const cuuint64_t*, const cuuint32_t*,
                             const cuuint32_t*, CUtensorMapInterleave, CUtensorMapSwizzle, CUtensorMapL2promotion, CUtensorMapFloatOOBfill);
static void make_map(EncodeFn fn, CUtensorMap* tm, const void* ptr, uint64_t cols, uint64_t rows, uint32_t bc, uint32_t br) {
  cuuint64_t dims[2] = {cols, rows}; cuuint64_t strides[1] = {cols * 2}; cuuint32_t box[2] = {bc, br}; cuuint32_t es[2] = {1, 1};
  fn(tm, CU_TENSOR_MAP_DATA_TYPE_BFLOAT16, 2, const_cast<void*>(ptr), dims, strides, box, es, CU_TENSOR_MAP_INTERLEAVE_NONE,
     CU_TENSOR_MAP_SWIZZLE_128B, CU_TENSOR_MAP_L2_PROMOTION_L2_256B, CU_TENSOR_MAP_FLOAT_OOB_FILL_NONE);
}
#define dbg_a_only 0
extern "C" void kernel_launch(void* const* d_in, const int* in_sizes, int n_in, void* d_out, int out_size) {
  void* fnp = nullptr; cudaDriverEntryPointQueryResult qr;
  cudaGetDriverEntryPoint("cuTensorMapEncodeTiled", &fnp, cudaEnableDefault, &qr);
  EncodeFn fn = (EncodeFn)fnp;
  cudaStream_t st = cudaStreamPerThread;
  cudaFuncSetAttribute(bworker_kernel, cudaFuncAttributeMaxDynamicSharedMemorySize, B_SMEM);
  {
    AMaps M;
    for (int i = 0; i < 3; i++) make_map(fn, &M.w16[i], d_in[2 + i], HD, DM, 64, 16);
    M.wv = (const __nv_bfloat16*)d_in[4];
    make_map(fn, &M.wo32, d_in[5], DM, HD, 64, 32);
    const uint32_t hi[5] = {dhi(TILE_SBO, 3), dhi(1024, 1), dhi(1024, 0), dhi(PL_SZ, 0), dhi(896, 0)};
    for (int i = 0; i < 5; i++) M.d[i] = (uint64_t)hi[i] << 32;
    cudaFuncSetAttribute(acore_kernel, cudaFuncAttributeMaxDynamicSharedMemorySize, A_SMEM);
    cudaFuncSetAttribute(acore_kernel, cudaFuncAttributeNonPortableClusterSizeAllowed, 1);
    cudaLaunchConfig_t cfg = {};
    cfg.gridDim = dim3(CL_SIZE * NCL); cfg.blockDim = dim3(512); cfg.dynamicSmemBytes = A_SMEM; cfg.stream = st;
    cudaLaunchAttribute at[1]; at[0].id = cudaLaunchAttributeClusterDimension;
    at[0].val.clusterDim.x = CL_SIZE; at[0].val.clusterDim.y = 1; at[0].val.clusterDim.z = 1;
    cfg.attrs = at; cfg.numAttrs = 1;
    cudaLaunchKernelEx(&cfg, acore_kernel, M, (const __nv_bfloat16*)d_in[1], dbg_a_only ? 0 : 1);
  }
  if (!dbg_a_only) {
    BParams P;
    make_map(fn, &P.wmap[0], d_in[5], DM, HD, 64, 32);
    make_map(fn, &P.wo16, d_in[5], DM, HD, 64, 16);
    make_map(fn, &P.wmap[1], d_in[8], DM, DM, 64, 32);
    make_map(fn, &P.wmap[2], d_in[9], DM, DM, 64, 32);
    make_map(fn, &P.wmap[3], d_in[10], FF, DM, 64, 32);
    make_map(fn, &P.wmap[4], d_in[11], DM, FF, 64, 32);
    P.x = (const __nv_bfloat16*)d_in[0];
    P.out = (__nv_bfloat16*)d_out;
    P.desc = (uint64_t)dhi(1024, 1) << 32;
    P.desc32 = (uint64_t)dhi(256, 3) << 32;
    cudaLaunchConfig_t cfg = {};
    cfg.gridDim = dim3(NBC); cfg.blockDim = dim3(512); cfg.dynamicSmemBytes = B_SMEM; cfg.stream = st;
    cudaLaunchAttribute at[1]; at[0].id = cudaLaunchAttributeProgrammaticStreamSerialization; at[0].val.programmaticStreamSerializationAllowed = 1;
    cfg.attrs = at; cfg.numAttrs = 1;
    cudaLaunchKernelEx(&cfg, bworker_kernel, P);
  }
}
```

```cpp
#include <cuda_runtime.h>
#include <cuda_bf16.h>
#include <cuda.h>
#include <stdint.h>

#define S_LEN 2048
#define DM 640
#define NH 32
#define DH 192
#define HD 6144
#define NSEG 64
#define FF 1536

__device__ __forceinline__ uint32_t smem_u32(const void* p) { return (uint32_t)__cvta_generic_to_shared(p); }
__device__ __forceinline__ uint32_t mapa(uint32_t a, uint32_t r) {
  uint32_t o; asm volatile("mapa.shared::cluster.u32 %0, %1, %2;" : "=r"(o) : "r"(a), "r"(r)); return o; }
__device__ __forceinline__ void mbar_init(uint32_t b, uint32_t c) {
  asm volatile("mbarrier.init.shared::cta.b64 [%0], %1;" :: "r"(b), "r"(c) : "memory"); }
__device__ __forceinline__ void mbar_expect(uint32_t b, uint32_t tx) {
  asm volatile("mbarrier.arrive.expect_tx.shared::cta.b64 _, [%0], %1;" :: "r"(b), "r"(tx) : "memory"); }
__device__ __forceinline__ void mbar_arrive(uint32_t b) {
  asm volatile("mbarrier.arrive.shared::cta.b64 _, [%0];" :: "r"(b) : "memory"); }
__device__ __forceinline__ void mbar_arrive_remote(uint32_t rb) {
  asm volatile("mbarrier.arrive.relaxed.cluster.shared::cluster.b64 _, [%0];" :: "r"(rb) : "memory"); }
__device__ __forceinline__ void mbar_expect_if(bool p, uint32_t b, uint32_t tx) {
  asm volatile("{\n.reg .pred q;\nsetp.ne.u32 q, %2, 0;\n@q mbarrier.arrive.expect_tx.shared::cta.b64 _, [%0], %1;\n}" :: "r"(b), "r"(tx), "r"((uint32_t)p) : "memory"); }
__device__ __forceinline__ void mbar_arrive_if(bool p, uint32_t b) {
  asm volatile("{\n.reg .pred q;\nsetp.ne.u32 q, %1, 0;\n@q mbarrier.arrive.shared::cta.b64 _, [%0];\n}" :: "r"(b), "r"((uint32_t)p) : "memory"); }
__device__ __forceinline__ void mbar_arrive_remote_if(bool p, uint32_t rb) {
  asm volatile("{\n.reg .pred q;\nsetp.ne.u32 q, %1, 0;\n@q mbarrier.arrive.relaxed.cluster.shared::cluster.b64 _, [%0];\n}" :: "r"(rb), "r"((uint32_t)p) : "memory"); }
__device__ __forceinline__ void sts32_if(bool p, uint32_t a, uint32_t v) {
  asm volatile("{\n.reg .pred q;\nsetp.ne.u32 q, %2, 0;\n@q st.shared.b32 [%0], %1;\n}" :: "r"(a), "r"(v), "r"((uint32_t)p) : "memory"); }
__device__ __forceinline__ void sts128z_if(bool p, uint32_t a) {
  asm volatile("{\n.reg .pred q;\nsetp.ne.u32 q, %1, 0;\n@q st.shared.v4.b32 [%0], {0,0,0,0};\n}" :: "r"(a), "r"((uint32_t)p) : "memory"); }
__device__ __forceinline__ bool mbar_try(uint32_t b, uint32_t ph) {
  uint32_t ok;
  asm volatile("{\n.reg .pred p;\nmbarrier.try_wait.parity.shared::cta.b64 p, [%1], %2;\nselp.u32 %0, 1, 0, p;\n}"
               : "=r"(ok) : "r"(b), "r"(ph) : "memory");
  return ok; }
__device__ __forceinline__ bool mbar_test(uint32_t b, uint32_t ph) {
  uint32_t ok;
  asm volatile("{\n.reg .pred p;\nmbarrier.test_wait.parity.shared::cta.b64 p, [%1], %2;\nselp.u32 %0, 1, 0, p;\n}"
               : "=r"(ok) : "r"(b), "r"(ph) : "memory");
  return ok; }
#define SPIN_LIMIT 4000000
#define FAIL() asm volatile("st.global.u32 [%0], 0;" :: "l"(8ull) : "memory")
#define CFENCE() asm volatile("fence.proxy.async::generic.acquire.sync_restrict::shared::cluster.cluster;" ::: "memory")
__device__ __forceinline__ void mbar_wait(uint32_t b, uint32_t ph) {
  int n = 0;
  while (!mbar_try(b, ph)) { if (++n > SPIN_LIMIT) FAIL(); } }
#define TIMEOUT_ACT "@!p st.shared.u32 [%0+1], 0;"
#define WAIT_HINT ", 20000"
#define WAIT_LIM "200000"
__device__ __forceinline__ void mbar_slow(uint32_t b, uint32_t ph) {
  asm volatile("{\n.reg .pred p, q;\n.reg .u32 n;\nmov.u32 n, 0;\n"
               "WL:\nmbarrier.try_wait.parity.shared::cta.b64 p, [%0], %1" WAIT_HINT ";\nadd.u32 n, n, 1;\nsetp.lt.and.u32 q, n, " WAIT_LIM ", !p;\n@q bra.uni WL;\n"
               TIMEOUT_ACT "\n}" :: "r"(b), "r"(ph) : "memory"); }
__device__ __forceinline__ void mbar_waitw(uint32_t b, uint32_t ph) {
  asm volatile("{\n.reg .pred p, q;\n.reg .u32 n;\nmbarrier.try_wait.parity.shared::cta.b64 p, [%0], %1;\n@p bra.uni WD;\nmov.u32 n, 0;\n"
               "WL:\nmbarrier.try_wait.parity.shared::cta.b64 p, [%0], %1" WAIT_HINT ";\nadd.u32 n, n, 1;\nsetp.lt.and.u32 q, n, " WAIT_LIM ", !p;\n@q bra.uni WL;\n"
               TIMEOUT_ACT "\nWD:\n}" :: "r"(b), "r"(ph) : "memory"); }
__device__ __forceinline__ void mbar_waitw2(uint32_t b0, uint32_t b1, uint32_t ph) {
  uint32_t ok;
  asm volatile("{\n.reg .pred p, r;\nmbarrier.try_wait.parity.shared::cta.b64 p, [%1], %3;\nmbarrier.try_wait.parity.shared::cta.b64 r, [%2], %3;\n"
               "and.pred p, p, r;\nselp.u32 %0, 1, 0, p;\n}" : "=r"(ok) : "r"(b0), "r"(b1), "r"(ph) : "memory");
  if (__builtin_expect(!__all_sync(~0u, ok), 0)) { mbar_slow(b0, ph); mbar_slow(b1, ph); }
}
__device__ __forceinline__ void mbar_waitu(uint32_t b, uint32_t ph) {
  asm volatile("{\n.reg .pred p;\nmbarrier.try_wait.parity.shared::cta.b64 p, [%0], %1;\n@p bra.uni WD;\n"
               "WL:\nmbarrier.try_wait.parity.shared::cta.b64 p, [%0], %1" WAIT_HINT ";\n@!p bra.uni WL;\nWD:\n}" :: "r"(b), "r"(ph) : "memory"); }
__device__ __forceinline__ void mbar_waitu2(uint32_t b0, uint32_t b1, uint32_t ph) {
  asm volatile("{\n.reg .pred p, r;\nWL:\nmbarrier.try_wait.parity.shared::cta.b64 p, [%0], %2;\nmbarrier.try_wait.parity.shared::cta.b64 r, [%1], %2;\n"
               "and.pred p, p, r;\n@!p bra.uni WL;\n}" :: "r"(b0), "r"(b1), "r"(ph) : "memory"); }
__device__ __forceinline__ void mbar_waitw4(uint32_t b, uint32_t ph) { mbar_waitw2(b, b + 8, ph); mbar_waitw2(b + 16, b + 24, ph); }
__device__ __forceinline__ uint32_t clock32() { uint32_t t; asm volatile("mov.u32 %0, %%clock;" : "=r"(t) :: "memory"); return t; }
template <int L> __device__ __forceinline__ uint32_t lop3(uint32_t a, uint32_t b, uint32_t c) {
  uint32_t r; asm("lop3.b32 %0, %1, %2, %3, %4;" : "=r"(r) : "r"(a), "r"(b), "r"(c), "n"(L)); return r; }
__device__ __forceinline__ void st_async_v2_if(bool p, uint32_t a, uint32_t v0, uint32_t v1, uint32_t mb) {
  asm volatile("{\n.reg .pred q;\nsetp.ne.u32 q, %4, 0;\n@q st.async.weak.shared::cluster.mbarrier::complete_tx::bytes.v2.b32 [%0], {%1,%2}, [%3];\n}"
               :: "r"(a), "r"(v0), "r"(v1), "r"(mb), "r"((uint32_t)p) : "memory"); }
__device__ __forceinline__ void keep4(const uint32_t* r, int lane) {
  asm volatile("{\n.reg .pred q;\nsetp.lt.s32 q, %4, 0;\n@q st.shared.v4.b32 [%4], {%0,%1,%2,%3};\n}" :: "r"(r[0]), "r"(r[1]), "r"(r[2]), "r"(r[3]), "r"(lane) : "memory"); }
__device__ __forceinline__ void fence_sched(int i) {
  asm volatile("{\n.reg .pred q;\nsetp.gt.s32 q, %0, 4096;\n@q st.shared.u32 [%0], 0;\n}" :: "r"(i) : "memory"); }
__device__ __forceinline__ uint32_t hmax2bf(uint32_t a, uint32_t b) { uint32_t r; asm("max.bf16x2 %0, %1, %2;" : "=r"(r) : "r"(a), "r"(b)); return r; }
__device__ __forceinline__ uint32_t uni(uint32_t x) { return __shfl_sync(~0u, x, 0); }
__device__ __forceinline__ void bulk_g2s_mc_e(uint32_t dst, const void* src, uint32_t bytes, uint32_t mb, uint16_t mask) {
  asm volatile("{\n.reg .pred e;\nelect.sync _|e, 0xffffffff;\n"
               "@e cp.async.bulk.shared::cluster.global.mbarrier::complete_tx::bytes.multicast::cluster [%0], [%1], %2, [%3], %4;\n}"
               :: "r"(dst), "l"(src), "r"(bytes), "r"(mb), "h"(mask) : "memory"); }
__device__ __forceinline__ void bulk_s2g_e(void* dst, uint32_t src, uint32_t bytes) {
  asm volatile("{\n.reg .pred e;\nelect.sync _|e, 0xffffffff;\n@e cp.async.bulk.global.shared::cta.bulk_group [%0], [%1], %2;\n}"
               :: "l"(dst), "r"(src), "r"(bytes) : "memory"); }
__device__ __forceinline__ void bulk_g2s_e(uint32_t dst, const void* src, uint32_t bytes, uint32_t mb) {
  asm volatile("{\n.reg .pred e;\nelect.sync _|e, 0xffffffff;\n@e cp.async.bulk.shared::cluster.global.mbarrier::complete_tx::bytes [%0], [%1], %2, [%3];\n}"
               :: "r"(dst), "l"(src), "r"(bytes), "r"(mb) : "memory"); }
#define STREAM_HINT 1
__device__ __forceinline__ void bulk_s2g_es(void* dst, uint32_t src, uint32_t bytes) {
  asm volatile("{\n.reg .pred e;\n.reg .b64 pol;\ncreatepolicy.fractional.L2::evict_first.b64 pol;\nelect.sync _|e, 0xffffffff;\n"
               "@e cp.async.bulk.global.shared::cta.bulk_group.L2::cache_hint [%0], [%1], %2, pol;\n}" :: "l"(dst), "r"(src), "r"(bytes) : "memory");
}
__device__ __forceinline__ void bulk_g2s_es(uint32_t dst, const void* src, uint32_t bytes, uint32_t mb) {
  asm volatile("{\n.reg .pred e;\n.reg .b64 pol;\ncreatepolicy.fractional.L2::evict_first.b64 pol;\nelect.sync _|e, 0xffffffff;\n"
               "@e cp.async.bulk.shared::cluster.global.mbarrier::complete_tx::bytes.L2::cache_hint [%0], [%1], %2, [%3], pol;\n}"
               :: "r"(dst), "l"(src), "r"(bytes), "r"(mb) : "memory"); }
__device__ __forceinline__ void tma2d_e(uint32_t dst, const CUtensorMap* tm, int c0, int c1, uint32_t mb) {
  asm volatile("{\n.reg .pred e;\nelect.sync _|e, 0xffffffff;\n"
               "@e cp.async.bulk.tensor.2d.shared::cluster.global.mbarrier::complete_tx::bytes [%0], [%1, {%3, %4}], [%2];\n}"
               :: "r"(dst), "l"((uint64_t)tm), "r"(mb), "r"(c0), "r"(c1) : "memory"); }
__device__ __forceinline__ uint32_t hadd2bf(uint32_t a, uint32_t b) {
  uint32_t r; asm("add.rn.bf16x2 %0, %1, %2;" : "=r"(r) : "r"(a), "r"(b)); return r; }
__device__ __forceinline__ void cluster_sync_all() {
  asm volatile("barrier.cluster.arrive.release.aligned;\nbarrier.cluster.wait.acquire.aligned;" ::: "memory"); }
__device__ __forceinline__ void bar_arrive(int id, int n) { asm volatile("bar.arrive %0, %1;" :: "r"(id), "r"(n) : "memory"); }
__device__ __forceinline__ void bar_arrive_dep(int id, int n, uint32_t dep) {
  asm volatile("{\n.reg .u32 t;\nand.b32 t, %2, 0;\nadd.u32 t, t, %0;\nbar.sync t, %1;\n}" :: "r"(id), "r"(n), "r"(dep) : "memory"); }
__device__ __forceinline__ void bar_sync(int id, int n) { asm volatile("bar.sync %0, %1;" :: "r"(id), "r"(n) : "memory"); }
__device__ __forceinline__ void fence_async() { asm volatile("fence.proxy.async.shared::cta;" ::: "memory"); }
__device__ __forceinline__ void st_async_b32(uint32_t a, uint32_t v, uint32_t mb) {
  asm volatile("st.async.weak.shared::cluster.mbarrier::complete_tx::bytes.b32 [%0], %1, [%2];" :: "r"(a), "r"(v), "r"(mb) : "memory"); }
__device__ __forceinline__ void st_async_v2(uint32_t a, uint32_t v0, uint32_t v1, uint32_t mb) {
  asm volatile("st.async.weak.shared::cluster.mbarrier::complete_tx::bytes.v2.b32 [%0], {%1,%2}, [%3];" :: "r"(a), "r"(v0), "r"(v1), "r"(mb) : "memory"); }
__device__ __forceinline__ void st_async_v4(uint32_t a, uint32_t v0, uint32_t v1, uint32_t v2, uint32_t v3, uint32_t mb) {
  asm volatile("st.async.weak.shared::cluster.mbarrier::complete_tx::bytes.v4.b32 [%0], {%1,%2,%3,%4}, [%5];" :: "r"(a), "r"(v0), "r"(v1), "r"(v2), "r"(v3), "r"(mb) : "memory"); }
__device__ __forceinline__ void ldsm4(uint32_t& r0, uint32_t& r1, uint32_t& r2, uint32_t& r3, uint32_t a) {
  asm volatile("ldmatrix.sync.aligned.m8n8.x4.shared.b16 {%0,%1,%2,%3}, [%4];" : "=r"(r0), "=r"(r1), "=r"(r2), "=r"(r3) : "r"(a) : "memory"); }
__device__ __forceinline__ void ldsm4t(uint32_t& r0, uint32_t& r1, uint32_t& r2, uint32_t& r3, uint32_t a) {
  asm volatile("ldmatrix.sync.aligned.m8n8.x4.trans.shared.b16 {%0,%1,%2,%3}, [%4];" : "=r"(r0), "=r"(r1), "=r"(r2), "=r"(r3) : "r"(a) : "memory"); }
__device__ __forceinline__ void stsm2t(uint32_t a, uint32_t r0, uint32_t r1) {
  asm volatile("stmatrix.sync.aligned.m8n8.x2.trans.shared.b16 [%0], {%1,%2};" :: "r"(a), "r"(r0), "r"(r1) : "memory"); }
__device__ __forceinline__ void stsm4t(uint32_t a, uint32_t r0, uint32_t r1, uint32_t r2, uint32_t r3) {
  asm volatile("stmatrix.sync.aligned.m8n8.x4.trans.shared.b16 [%0], {%1,%2,%3,%4};" :: "r"(a), "r"(r0), "r"(r1), "r"(r2), "r"(r3) : "memory"); }
__device__ __forceinline__ uint32_t movm(uint32_t a) {
  uint32_t d; asm volatile("movmatrix.sync.aligned.m8n8.trans.b16 %0, %1;" : "=r"(d) : "r"(a)); return d; }
__device__ __forceinline__ void mma16816(float* d, uint32_t a0, uint32_t a1, uint32_t a2, uint32_t a3, uint32_t b0, uint32_t b1) {
  asm("mma.sync.aligned.m16n8k16.row.col.f32.bf16.bf16.f32 {%0,%1,%2,%3}, {%4,%5,%6,%7}, {%8,%9}, {%0,%1,%2,%3};"
               : "+f"(d[0]), "+f"(d[1]), "+f"(d[2]), "+f"(d[3]) : "r"(a0), "r"(a1), "r"(a2), "r"(a3), "r"(b0), "r"(b1)); }
__device__ __forceinline__ void mma16816v(float* d, uint32_t a0, uint32_t a1, uint32_t a2, uint32_t a3, uint32_t b0, uint32_t b1) {
  asm volatile("mma.sync.aligned.m16n8k16.row.col.f32.bf16.bf16.f32 {%0,%1,%2,%3}, {%4,%5,%6,%7}, {%8,%9}, {%0,%1,%2,%3};"
               : "+f"(d[0]), "+f"(d[1]), "+f"(d[2]), "+f"(d[3]) : "r"(a0), "r"(a1), "r"(a2), "r"(a3), "r"(b0), "r"(b1)); }
__device__ __forceinline__ uint32_t pack2(float lo, float hi) {
  uint32_t r; asm("cvt.rn.bf16x2.f32 %0, %1, %2;" : "=r"(r) : "f"(hi), "f"(lo)); return r; }
__device__ __forceinline__ uint32_t pack2v(float lo, float hi) {
  uint32_t r; asm volatile("cvt.rn.bf16x2.f32 %0, %1, %2;" : "=r"(r) : "f"(hi), "f"(lo)); return r; }
__device__ __forceinline__ float bf_lo(uint32_t w) { return __uint_as_float(w << 16); }
__device__ __forceinline__ float bf_hi(uint32_t w) { return __uint_as_float(w & 0xffff0000u); }
__device__ __forceinline__ uint4 lds128(uint32_t a) {
  uint4 v; asm volatile("ld.shared.v4.b32 {%0,%1,%2,%3}, [%4];" : "=r"(v.x), "=r"(v.y), "=r"(v.z), "=r"(v.w) : "r"(a) : "memory"); return v; }
__device__ __forceinline__ uint4 lds128_nv(uint32_t a) {
  uint4 v; asm volatile("ld.shared.v4.b32 {%0,%1,%2,%3}, [%4];" : "=r"(v.x), "=r"(v.y), "=r"(v.z), "=r"(v.w) : "r"(a)); return v; }
__device__ __forceinline__ void st_async_v2_nm(uint32_t a, uint32_t v0, uint32_t v1, uint32_t mb) {
  asm volatile("st.async.weak.shared::cluster.mbarrier::complete_tx::bytes.v2.b32 [%0], {%1,%2}, [%3];" :: "r"(a), "r"(v0), "r"(v1), "r"(mb)); }
__device__ __forceinline__ float rcpf(float x) { float y; asm("rcp.approx.ftz.f32 %0, %1;" : "=f"(y) : "f"(x)); return y; }
__device__ __forceinline__ void sts64(uint32_t a, uint32_t x, uint32_t y) { asm volatile("st.shared.v2.b32 [%0], {%1,%2};" :: "r"(a), "r"(x), "r"(y) : "memory"); }
__device__ __forceinline__ float ex2(float x) { float y; asm("ex2.approx.ftz.f32 %0, %1;" : "=f"(y) : "f"(x)); return y; }
__device__ __forceinline__ uint32_t lds32(uint32_t a) {
  uint32_t v; asm volatile("ld.shared.b32 %0, [%1];" : "=r"(v) : "r"(a) : "memory"); return v; }
__device__ __forceinline__ uint2 lds64(uint32_t a) {
  uint2 v; asm volatile("ld.shared.v2.b32 {%0,%1}, [%2];" : "=r"(v.x), "=r"(v.y) : "r"(a) : "memory"); return v; }
__device__ __forceinline__ void sts128(uint32_t a, uint32_t x, uint32_t y, uint32_t z, uint32_t w) {
  asm volatile("st.shared.v4.b32 [%0], {%1,%2,%3,%4};" :: "r"(a), "r"(x), "r"(y), "r"(z), "r"(w) : "memory"); }
__device__ __forceinline__ void sts32(uint32_t a, uint32_t x) { asm volatile("st.shared.b32 [%0], %1;" :: "r"(a), "r"(x) : "memory"); }
__device__ __forceinline__ void tma2d(uint32_t dst, const CUtensorMap* tm, int c0, int c1, uint32_t mb) {
  asm volatile("cp.async.bulk.tensor.2d.shared::cluster.global.mbarrier::complete_tx::bytes [%0], [%1, {%3, %4}], [%2];"
               :: "r"(dst), "l"((uint64_t)tm), "r"(mb), "r"(c0), "r"(c1) : "memory"); }
__device__ __forceinline__ void tma2d_prefetch(const CUtensorMap* tm, int c0, int c1) {
  asm volatile("cp.async.bulk.prefetch.tensor.2d.L2.global.tile [%0, {%1, %2}];" :: "l"((uint64_t)tm), "r"(c0), "r"(c1) : "memory"); }
__device__ __forceinline__ void bulk_g2s_mc(uint32_t dst, const void* src, uint32_t bytes, uint32_t mb, uint16_t mask) {
  asm volatile("cp.async.bulk.shared::cluster.global.mbarrier::complete_tx::bytes.multicast::cluster [%0], [%1], %2, [%3], %4;"
               :: "r"(dst), "l"(src), "r"(bytes), "r"(mb), "h"(mask) : "memory"); }
__device__ __forceinline__ void bulk_s2g(void* dst, uint32_t src, uint32_t bytes) {
  asm volatile("cp.async.bulk.global.shared::cta.bulk_group [%0], [%1], %2;" :: "l"(dst), "r"(src), "r"(bytes) : "memory"); }
__device__ __forceinline__ void wg_fence() { asm volatile("wgmma.fence.sync.aligned;" ::: "memory"); }
__device__ __forceinline__ void wg_commit() { asm volatile("wgmma.commit_group.sync.aligned;" ::: "memory"); }
template <int N> __device__ __forceinline__ void wg_wait() { asm volatile("wgmma.wait_group.sync.aligned %0;" :: "n"(N) : "memory"); }
__device__ __forceinline__ uint64_t mkdesc(uint32_t addr, uint32_t lbo, uint32_t sbo, uint32_t swz) {
  return (uint64_t)((addr & 0x3FFFF) >> 4) | ((uint64_t)(lbo >> 4) << 16) | ((uint64_t)(sbo >> 4) << 32) | ((uint64_t)swz << 62); }

#define ACC4(d) "+f"(d[0]),"+f"(d[1]),"+f"(d[2]),"+f"(d[3])
#define ACC8(d) ACC4(d), ACC4((d + 4))
#define ACC16(d) ACC8(d), ACC8((d + 8))
#define ACC20(d) ACC16(d), ACC4((d + 16))
#define ACC24(d) ACC16(d), ACC8((d + 16))
#define SMEM0 0x400
__host__ __device__ constexpr uint32_t dlo(uint32_t off, uint32_t lbo) { return ((SMEM0 + off) >> 4) | ((lbo >> 4) << 16); }
__host__ __device__ constexpr uint32_t dhi(uint32_t sbo, uint32_t swz) { return (sbo >> 4) | (swz << 30); }
#define R4S "{%0,%1,%2,%3}"
#define R8S "{%0,%1,%2,%3,%4,%5,%6,%7}"
#define R16S "{%0,%1,%2,%3,%4,%5,%6,%7,%8,%9,%10,%11,%12,%13,%14,%15}"
#define R20S "{%0,%1,%2,%3,%4,%5,%6,%7,%8,%9,%10,%11,%12,%13,%14,%15,%16,%17,%18,%19}"
#define R24S "{%0,%1,%2,%3,%4,%5,%6,%7,%8,%9,%10,%11,%12,%13,%14,%15,%16,%17,%18,%19,%20,%21,%22,%23}"
#define ACC32(d) ACC16(d), ACC16((d + 16))
#define R32S "{%0,%1,%2,%3,%4,%5,%6,%7,%8,%9,%10,%11,%12,%13,%14,%15,%16,%17,%18,%19,%20,%21,%22,%23,%24,%25,%26,%27,%28,%29,%30,%31}"
struct Dsc {
  uint64_t b; uint32_t e;
  __device__ __forceinline__ Dsc operator+(uint32_t o) const { return {b + o, e}; }
};
template <int K> __device__ __forceinline__ uint32_t fresh(int i) {
  uint32_t e; asm volatile("{\n.reg .u32 t;\nadd.u32 t, %1, %2;\nshr.u32 %0, t, %3;\n}" : "=r"(e) : "r"(i), "n"((256 << K) + 1), "n"(8 + K)); return e; }
template <int N, bool H = false> struct MM;
#define DEF_MM(N, H, T, ACCM, RS_, I0, I1, I2, I3, I4, I5, I6, I7)                                                                \
  template <> struct MM<N, H> {                                                                                                   \
    template <uint32_t BLO, int ACC>                                                                                              \
    static __device__ __forceinline__ void rs(float* d, const uint32_t* a, Dsc b0) {                                              \
      asm volatile("{\n.reg .b64 b;\nmad.wide.u32 b, %" #I7 ", %" #I5 ", %" #I4 ";\n"                                             \
                   "wgmma.mma_async.sync.aligned.m64n" #N "k16.f32." T "." T " " RS_ ", {%" #I0 ",%" #I1 ",%" #I2 ",%" #I3 "}, b, %" #I6 ", 1, 1, 0;\n}" \
                   : ACCM(d) : "r"(a[0]), "r"(a[1]), "r"(a[2]), "r"(a[3]), "l"(b0.b), "n"(BLO), "n"(ACC), "r"(b0.e)); }           \
    template <uint32_t ALO, uint32_t BLO, int ACC, int TA = 1>                                                                    \
    static __device__ __forceinline__ void ss(float* d, Dsc a0, Dsc b0) {                                                         \
      asm volatile("{\n.reg .b64 a, b;\nmad.wide.u32 a, %" #I6 ", %" #I1 ", %" #I0 ";\nmad.wide.u32 b, %" #I6 ", %" #I3 ", %" #I2 ";\n" \
                   "wgmma.mma_async.sync.aligned.m64n" #N "k16.f32." T "." T " " RS_ ", a, b, %" #I4 ", 1, 1, %" #I5 ", 0;\n}"    \
                   : ACCM(d) : "l"(a0.b), "n"(ALO), "l"(b0.b), "n"(BLO), "n"(ACC), "n"(TA), "r"(b0.e)); }                         \
  };
DEF_MM(8, false, "bf16", ACC4, R4S, 4, 5, 6, 7, 8, 9, 10, 11)
DEF_MM(16, false, "bf16", ACC8, R8S, 8, 9, 10, 11, 12, 13, 14, 15)
DEF_MM(32, false, "bf16", ACC16, R16S, 16, 17, 18, 19, 20, 21, 22, 23)
DEF_MM(40, false, "bf16", ACC20, R20S, 20, 21, 22, 23, 24, 25, 26, 27)
DEF_MM(48, false, "bf16", ACC24, R24S, 24, 25, 26, 27, 28, 29, 30, 31)
DEF_MM(64, false, "bf16", ACC32, R32S, 32, 33, 34, 35, 36, 37, 38, 39)
DEF_MM(32, true, "f16", ACC16, R16S, 16, 17, 18, 19, 20, 21, 22, 23)
DEF_MM(64, true, "f16", ACC32, R32S, 32, 33, 34, 35, 36, 37, 38, 39)

#define LAG 10
#define NSTEP (NSEG + LAG)
#define NR (NSTEP + 2)
__device__ __align__(1024) __nv_bfloat16 g_xn[2][S_LEN * DM];
#define RO 16
static_assert(RO > LAG + 1, "ring");
__device__ __align__(1024) unsigned char g_o[RO * 96 * 8192];
__device__ __align__(1024) uint32_t g_part[6][7][40][64];
#define RD 16
static_assert(2 * RD <= NSEG && NR < 96, "the tags of the last lap differ from those of the first");
#define TILE_B 81920
__device__ __align__(1024) float2 g_stat[S_LEN];
__device__ __align__(1024) uint32_t g_st2[2][RD][64];
__device__ __align__(1024) unsigned char g_acc[4][RD][TILE_B];
#define NOP 19
#define NW12 5
#define NW34 12
#define NBC (NOP + NW12 + NW34)
__device__ __align__(1024) unsigned char g_wt[NOP * 10 * 12288];
__device__ __align__(1024) unsigned char g_wx[NW12 + NW34][16384];
enum { F_O = 0, F_R1 = NOP + 1, F_R2 = F_R1 + 4, F_R3 = F_R2 + 4, F_Z = F_R3 + 4, F_DONE, F_GOT, F_MISC, F_NUM };
__device__ __align__(128) uint32_t g_f[F_NUM][96];
__device__ __align__(128) int g_xready[129][8];
__device__ uint32_t g_tpc[128];
#define TS(i)
#define TSV(i, v)
#define TSN(i)
#define TSD(i, dep)
#define BTS(k, i)
#define BTS2(k, i)
#define RTS(i)
#define RTSD(i, dep)
#define RTS_OUT()
#define CTS(i)
#define PTS(i)
#define PTS1(i)
#define CTS_OUT()
#define GTS(i)

#define CL_SIZE 15
#define NCL 7
#define SSQ 13
#define SSV 16
#define PL_SZ 5376
#define TILE_SBO 2560
#define TILE_GRP 15360
#define WS_SZ ((2 * SSQ + SSV) * 2048)
#define OFF_QK (OFF_WO + 26 * 2048)
#define LAYOUT 2
#define OFF_TILE 0
#define OFF_WS (4 * TILE_GRP)
#define OFF_WO (OFF_WS + WS_SZ)
#define OFF_PL (OFF_QK + 20480)
#define OFF_BAR (OFF_PL + 2 * PL_SZ)
#define STG_Q OFF_TILE
#define STG_K OFF_WO
#define VA 14
#define STG_V2 (OFF_TILE + 27 * 2048)
#define OFF_O (OFF_PL + 4352)
#define LAND(k) (((k) >> 1) * TILE_GRP + ((k) & 1) * 1280)
#define LAND_F (5 * TILE_SBO)
#define OFF_XL (OFF_TILE + 3 * TILE_GRP)
#define OFF_XF (OFF_XL + LAND_F)
#define OFF_WT ((OFF_XL + TILE_SBO + 1023) & ~1023)
#define OFF_TAB (OFF_BAR + 240)
#define OFF_INV (OFF_TAB + 64)
#define OFF_TS (OFF_INV + 128)
#define A_SMEM 232448
static_assert(WS_SZ + 72 * 1024 + 2 * PL_SZ + 4 * TILE_GRP + 512 == A_SMEM && OFF_WS % 1024 == 0 && OFF_WO % 1024 == 0 && SSQ == 13, "smem map");
enum { B_W0 = 0, B_W1, B_F1, B_F2 = B_F1 + 4, B_R1 = B_F2 + 4, B_R2, B_MEMFREE, B_LANDFREE, B_OPEER, B_PLFREE, B_XFREE, B_SB, B_WOF = B_SB + 6, B_WTF, B_RS, B_NUM = B_RS + 4 };
static_assert(B_NUM <= 30, "barriers");
enum { N_C = 0, N_SISS, N_QK, N_V, N_PM, N_TURN, N_PI, N_VGO, N_O, N_PX, N_AB, N_SDONE, N_VDONE, N_G3, N_P, N_OX };

__device__ __forceinline__ bool is_dual(int j) { return j >= LAG && j < NSEG; }
__device__ __forceinline__ int sched_l(int j) { return j < NSEG ? j : NSEG + j - LAG; }
__device__ __forceinline__ int sched_f(int j) { return NSEG + j - LAG; }
__device__ __forceinline__ void wait_cnt(const int* p, int target) {
  int v, n = 0;
  do {
    asm volatile("ld.relaxed.gpu.global.b32 %0, [%1];" : "=r"(v) : "l"(p) : "memory");
    if (v >= target) break;
    if (++n > SPIN_LIMIT) FAIL();
  } while (true);
  asm volatile("fence.acquire.gpu;" ::: "memory");
  asm volatile("fence.proxy.async.global;" ::: "memory");
}
__device__ __forceinline__ void red_release(void* p, uint32_t v) { asm volatile("red.release.gpu.global.add.u32 [%0], %1;" :: "l"(p), "r"(v) : "memory"); }
__device__ __forceinline__ void red_relaxed(void* p, uint32_t v) { asm volatile("red.relaxed.gpu.global.add.u32 [%0], %1;" :: "l"(p), "r"(v) : "memory"); }
#define VMASK 0xa5294a5294ull
__host__ __device__ constexpr int popc40(unsigned long long m) { int c = 0; for (; m; m &= m - 1) c++; return c; }
static_assert(popc40(VMASK) == SSV, "mask");
__host__ __device__ constexpr int ss_idx(int ks, int n) { return n == SSV ? popc40(VMASK & ((1ull << ks) - 1)) : ks * n / 40; }
__host__ __device__ constexpr bool is_ss(int ks, int n) { return ss_idx(ks + 1, n) != ss_idx(ks, n); }
__host__ __device__ constexpr int rs_idx(int ks, int n) { return ks - ss_idx(ks, n); }

#define SL2 (0.07216878364870322f * 1.4426950408889634f)

#define SUM_LOOP 0
struct Desc { Dsc tile, unit, k1, pl, p; };
__device__ __forceinline__ Desc make_desc(const uint64_t* h, uint32_t u, uint32_t e) {
  return {{h[0], e}, {h[1] + u * 128, e}, {h[2], e}, {h[3], e}, {h[4], e}};
}
template <int N, int NSS, int RG, int KS, int K1, int K0 = 0>
__device__ __forceinline__ void proj(float* acc, const uint32_t* W, const Desc& D) {
  if constexpr (KS < K1) {
    constexpr uint32_t BLO = dlo(OFF_TILE + (KS / 10) * TILE_GRP + RG * TILE_SBO + (KS % 10) * 256, 128);
    if constexpr (is_ss(KS, NSS)) MM<N>::template ss<dlo(OFF_WS + ss_idx(KS, NSS) * 2048, 0), BLO, (KS != K0)>(acc, D.unit, D.tile);
    else MM<N>::template rs<BLO, (KS != K0)>(acc, W + rs_idx(KS, NSS) * 4, D.tile);
    proj<N, NSS, RG, KS + 1, K1, K0>(acc, W, D);
  }
}
#define VST 17
template <int KS>
__device__ __forceinline__ void ld_rest(uint32_t* W, const uint32_t* p) {
  if constexpr (KS < 40) {
    if constexpr (!is_ss(KS, SSV) && rs_idx(KS, SSV) >= VST) {
#pragma unroll
      for (int i = 0; i < 4; i++) W[4 * rs_idx(KS, SSV) + i] = __ldg(p + (KS * 16 + (i >> 1) * 8) * (HD / 2) + (i & 1) * 4);
    }
    ld_rest<KS + 1>(W, p);
  }
}
template <int N>
__device__ __forceinline__ void load_w(uint32_t* W, uint32_t stage, int warp, int lane) {
  const int kr = (lane >> 4) * 8 + (lane & 7);
  const int cb = warp * 2 + ((lane >> 3) & 1);
  const uint32_t a0 = stage + kr * 128 + ((cb ^ (lane & 7)) << 4);
#pragma unroll
  for (int i = 0; i < N; i++) ldsm4t(W[4 * i], W[4 * i + 1], W[4 * i + 2], W[4 * i + 3], a0 + i * 2048);
}
template <int N, int G, int U, int OS, int ACC>
__device__ __forceinline__ void wo4(float* d, const Desc& D) {
  constexpr uint32_t WA = (U >= 4 ? OFF_WO + (U - 4) * 2048 : OFF_WT) - G * SSQ * 2048, OB = OS == 0 ? OFF_O : OS == 1 ? OFF_XL : OFF_XF;
  Dsc b = OS ? D.k1 : D.pl;
  b.e = fresh<(U < 16 ? U / 4 : U / 8 - 2) + (N == 8 ? 4 : 0)>(D.unit.e);
  MM<N>::template ss<dlo(WA, 0), dlo(OB, 128), ACC>(d, D.unit, b);
  MM<N>::template ss<dlo(WA + 2048, 0), dlo(OB + 256, 128), 1>(d, D.unit, b);
  MM<N>::template ss<dlo(WA + 4096, 0), dlo(OB + 512, 128), 1>(d, D.unit, b);
  MM<N>::template ss<dlo(WA + 6144, 0), dlo(OB + 768, 128), 1>(d, D.unit, b);
}
__device__ __forceinline__ void wo_coord(int i, int t3, int head, int& c0, int& c1) {
  const int g = i >> 1;
  const int blk = g == 0 ? 9 : (g < 4 ? g - 1 : (g - 4) >> 1) * 3 + t3;
  int sl = g < 4 ? t3 : (g & 1) ? t3 + 1 : t3 + 2;
  if (sl >= 3) sl -= 3;
  c0 = blk * 64; c1 = head * DH + sl * 64 + (i & 1) * 32;
}
__device__ __forceinline__ void tok_softmax(uint32_t sb, int job, int lane) {
  const bool w1 = job & 1;
  const int dg = (lane >> 2) - (lane & 3) * 2;
  const uint32_t lo = sb + OFF_PL + (job >> 1) * PL_SZ + (job & 1) * 1792, l8 = lo + 512 + lane * 8, pa = lo + lane * 4;
  const uint32_t km = job & 2 ? 640 : 512;
  float x[14];
  {
    const uint4 a = lds128(lo + lane * 16);
    const uint2 e = lds64(l8);
    const uint32_t c = lds32(768 + pa);
    x[0] = bf_lo(a.x); x[1] = bf_hi(a.x); x[2] = bf_lo(a.y); x[3] = bf_hi(a.y); x[4] = bf_lo(a.z); x[5] = bf_hi(a.z); x[6] = bf_lo(a.w); x[7] = bf_hi(a.w);
    x[8] = bf_lo(c); x[9] = bf_hi(c); x[10] = bf_lo(e.x); x[11] = bf_hi(e.x); x[12] = bf_lo(e.y); x[13] = bf_hi(e.y);
  }
  if (dg < 0) { x[8] = -INFINITY; if (w1) x[4] = -INFINITY; else x[10] = -INFINITY; }
  if (dg < 1) { x[9] = -INFINITY; if (w1) x[5] = -INFINITY; else x[11] = -INFINITY; }
  const float m4 = fmaxf(x[8], x[9]);
  float m0 = fmaxf(fmaxf(fmaxf(x[0], x[1]), fmaxf(x[2], x[3])), fmaxf(fmaxf(x[4], x[5]), fmaxf(x[6], x[7])));
  float m1 = fmaxf(fmaxf(x[10], x[11]), fmaxf(x[12], x[13]));
  if (w1) m1 = fmaxf(m1, m4); else m0 = fmaxf(m0, m4);
  m0 = fmaxf(m0, __shfl_xor_sync(~0u, m0, 1)); m1 = fmaxf(m1, __shfl_xor_sync(~0u, m1, 1));
  sts32(pa + (w1 ? 384 : 896 + 128), 0u); sts32(pa + 1152 - km, 0u); sts32(pa + 896 + 1152 - km, 0u); sts64(l8 + 896 - 256, 0u, 0u);
  m0 = fmaxf(m0, __shfl_xor_sync(~0u, m0, 2)); m1 = fmaxf(m1, __shfl_xor_sync(~0u, m1, 2));
  m0 *= -SL2; m1 *= -SL2;
#pragma unroll
  for (int j = 0; j < 14; j++) x[j] = ex2(fmaf(x[j], SL2, j < 8 ? m0 : j >= 10 ? m1 : w1 ? m1 : m0));
  const float l4s = x[8] + x[9];
  float l0 = ((x[0] + x[1]) + (x[2] + x[3])) + ((x[4] + x[5]) + (x[6] + x[7])), l1 = (x[10] + x[11]) + (x[12] + x[13]);
  if (w1) l1 += l4s; else l0 += l4s;
  l0 += __shfl_xor_sync(~0u, l0, 1); l1 += __shfl_xor_sync(~0u, l1, 1);
  l0 += __shfl_xor_sync(~0u, l0, 2); l1 += __shfl_xor_sync(~0u, l1, 2);
  l0 = rcpf(l0); l1 = rcpf(l1);
#pragma unroll
  for (int j = 0; j < 7; j++) {
    const float iv = j < 4 ? l0 : j > 4 ? l1 : w1 ? l1 : l0;
    sts32(pa + (j < 3 ? j * 128 : j == 3 ? km : j == 4 ? (w1 ? 896 + 128 : 384) : j == 5 ? 896 : 896 + km), pack2(x[2 * j] * iv, x[2 * j + 1] * iv));
  }
}
template <int N>
__device__ __forceinline__ void wo_phase(uint32_t sb, int wg, int warp, int lane, uint32_t par, uint32_t r1, const Desc& D) {
  const uint32_t bar = sb + OFF_BAR;
  float x[N / 2], y[N / 2];
  const uint2 ta = lds64(sb + OFF_TAB + (wg * 4 + warp) * 8);
  uint32_t xa = (ta.x & ~255u) + lane * 8, xb = (ta.x & 0xFF0000FFu) + SMEM0 + OFF_BAR, ya = (ta.y & ~255u) + lane * 8, yb = (ta.y & 0xFF0000FFu) + SMEM0 + OFF_BAR;
  asm volatile("" : "+r"(xa), "+r"(xb), "+r"(ya), "+r"(yb));
  auto scat = [&](uint32_t ad, uint32_t mb, const float* d) {
    st_async_v2(ad, pack2(d[0], d[1]), pack2(d[2], d[3]), mb);
    if (N == 16) st_async_v2(ad + LAND_F, pack2(d[4], d[5]), pack2(d[6], d[7]), mb);
  };
  if (wg == 0) {
    bar_sync(N_O, 384);
    wg_fence(); wo4<N, 0, 4, 0, 0>(x, D); wo4<N, 0, 8, 0, 0>(y, D); wg_commit();
    mbar_waitu(bar + 8 * B_OPEER, par);
    CFENCE(); wg_fence(); wo4<N, 0, 16, 1, 1>(x, D); wo4<N, 0, 20, 2, 1>(x, D); wg_commit();
    wo4<N, 0, 24, 1, 1>(y, D); wg_commit();
    mbar_waitu2(bar + 8 * B_WOF, bar + 8 * B_MEMFREE, par);
    wg_fence(); wo4<N, 0, 28, 2, 1>(y, D); wg_commit();
    bar_arrive(N_AB, 256);
    wg_wait<2>(); scat(xa, xb, x);
    wg_wait<0>(); scat(ya, yb, y);
  } else {
    bar_sync(N_O, 384);
    wg_fence(); wo4<N, 1, 0, 0, 0>(x, D); wg_commit(); wo4<N, 1, 12, 0, 0>(y, D); wg_commit();
    wg_wait<1>(); mbar_arrive_remote_if(lane == 0, r1);
    mbar_waitu(bar + 8 * B_MEMFREE, par);
    scat(xa, xb, x);
    bar_sync(N_AB, 256);
    CFENCE(); wg_fence(); wo4<N, 1, 32, 1, 1>(y, D); wo4<N, 1, 36, 2, 1>(y, D); wg_commit();
    bar_arrive(N_TURN, 256);
    wg_wait<0>(); scat(ya, yb, y);
  }
}
#define DS_DUAL 10
#define DS_SINGLE 20
#define POLL_GAP 100
#define POLL_GAPD 0
#define TOK_DELAY 250
#define LATE_SM 1
#define UMAX 40
#define VD1 10
#define VS2 20
#define IG_V 3
#define VS1 4
struct AMaps { CUtensorMap w16[3], wo32; uint64_t d[5]; const __nv_bfloat16* wv; };
__global__ void __launch_bounds__(512, 1)
acore_kernel(const __grid_constant__ AMaps M, const __nv_bfloat16* __restrict__ mem0, int sync_b) {
  extern __shared__ __align__(1024) unsigned char smem_raw[];
  const uint32_t sb = smem_u32(smem_raw);
  GTS(24);
  if (threadIdx.x == 480) {
    uint32_t smid; asm volatile("mov.u32 %0, %%smid;" : "=r"(smid));
    g_tpc[(smid >> 1) & 127] = blockIdx.x - CL_SIZE < 3 * CL_SIZE && blockIdx.x % CL_SIZE >= 12 ? 1 : 2;
    asm volatile("griddepcontrol.launch_dependents;");
  }
  const int lane0 = threadIdx.x & 31;
#define LANE_INIT() int lane; asm volatile("mov.u32 %0, %%laneid;" : "=r"(lane))
  const int warp = __shfl_sync(~0u, (threadIdx.x >> 5) & 3, 0);
  const int cl = blockIdx.x / CL_SIZE;
  const uint32_t rank = blockIdx.x - cl * CL_SIZE;
  const int nh = cl >= 1 && cl <= 3 ? 4 : 5;
  const int nA = 3 * nh;
  const int wg = __shfl_sync(~0u, (int)rank < nA ? threadIdx.x >> 7 : 4, 0);
  const int head = (cl < 4 ? (cl ? 1 + 4 * cl : 0) : 5 * cl - 3) + rank / 3;
  const int t3 = rank % 3;
  const int col0 = head * DH + t3 * 64;
  const uint32_t bar = sb + OFF_BAR;
  const uint32_t rb0 = SMEM0;
  const uint16_t mcmask = (uint16_t)((1u << nA) - 1);
  const uint32_t nxt = sb + ((t3 == 2 ? -2 : 1) << 24), prv = sb + ((t3 == 0 ? 2 : -1) << 24);
  const int ig = (int)rank - (nA - 4);

  if (threadIdx.x == 0) {
    if (mapa(sb, nA - 1) != rb0 + ((nA - 1) << 24) || mapa(sb, 0) != rb0 || mapa(sb, 1) != rb0 + (1u << 24) || sb != SMEM0 + (rank << 24)) FAIL();
    for (int i = 0; i < B_NUM; i++)
      mbar_init(bar + 8 * i, i == B_R1 ? 4 * nA : i == B_R2 ? 12 * nA : i == B_MEMFREE ? nA : i == B_LANDFREE ? 4 * nA : i == B_PLFREE || i == B_XFREE ? 2 : 1);
    asm volatile("fence.mbarrier_init.release.cluster;" ::: "memory");
    mbar_expect(bar + 8 * B_W0, (80 + SSV + VST) * 2048);
  }
  __syncthreads();
  if (lane0 == 0) {
    const int w12 = wg * 4 + warp;
    if (w12 < 10) {
#pragma unroll 1
      for (int ks = 4 * w12; ks < 4 * w12 + 4; ks++) {
        const bool ss = is_ss(ks, SSQ);
        tma2d(ss ? sb + OFF_WS + ss_idx(ks, SSQ) * 2048 : sb + STG_Q + rs_idx(ks, SSQ) * 2048, &M.w16[0], col0, ks * 16, bar + 8 * B_W0);
        tma2d(ss ? sb + OFF_WS + (SSQ + ss_idx(ks, SSQ)) * 2048 : sb + STG_K + rs_idx(ks, SSQ) * 2048, &M.w16[1], col0, ks * 16, bar + 8 * B_W0);
        if (is_ss(ks, SSV)) tma2d(sb + OFF_WS + (2 * SSQ + ss_idx(ks, SSV)) * 2048, &M.w16[2], col0, ks * 16, bar + 8 * B_W0);
        else if (rs_idx(ks, SSV) < VST) tma2d(sb + (rs_idx(ks, SSV) < VA ? STG_K + 27 * 2048 : STG_V2 - VA * 2048) + rs_idx(ks, SSV) * 2048, &M.w16[2], col0, ks * 16, bar + 8 * B_W0);
      }
    }
  }
  if (lane0 < 2 && wg < 2) {
    const int u = 4 * (wg ? (lane0 ? 6 + t3 : 9) : (lane0 ? 3 + t3 : t3)) + warp;
    const int li = (u >= nA) + (u >= 2 * nA) + (u >= 3 * nA);
    sts32(sb + OFF_TAB + (wg * 4 + warp) * 8 + lane0 * 4,
          rb0 + ((u - li * nA) << 24) + OFF_TILE + LAND(li + (u >= 36 ? t3 : 0)) + (rank / 3) * 256 + 8 * (B_RS + li));
  }
  __syncthreads();
  GTS(25);

  auto issue_tok = [&](int sc, int fb, int rel = -1, uint32_t ph = 0) {
    if (sync_b) wait_cnt(&g_xready[sc][0], 32);
    if (rel >= 0) mbar_waitu(bar + 8 * rel, ph);
    bulk_g2s_mc_e(sb + OFF_TILE + ig * TILE_GRP + TILE_SBO, &g_xn[0][0] + uni(sc * (32 * DM)) + ig * 5120, 10240, bar + 8 * (fb + ig), mcmask);
  };
#define POLL(d, q) _Pragma("unroll") for (int k = 0; k < NCL; k++) \
      asm volatile("ld.relaxed.gpu.global.v2.b32 {%0,%1}, [%2];" : "=r"(d[k].x), "=r"(d[k].y) : "l"(q + k * 2560) : "memory")
#define L3(L, a, b, c) lop3<L>(a, b, c)
#define TAGS(L, d) L3(L, L3(L, L3(L, d[0].x, d[0].y, d[1].x), L3(L, d[1].y, d[2].x, d[2].y), L3(L, d[3].x, d[3].y, d[4].x)), L3(L, d[4].y, d[5].x, d[5].y), L3(L, d[6].x, d[6].y, d[6].y))
    auto deliver = [&](uint2* pa, const uint32_t* gq, int u, int c, int dc, int ds, int step, bool first, int lane) {
      const uint32_t off = uni(OFF_TILE + ((u * 205) >> 11) * (TILE_GRP - TILE_SBO) + u * 256 + dc * LAND_F), boff = uni(OFF_BAR + 8 * (B_F1 + ((u * 205) >> 11)));
      const uint32_t* mi = &g_part[4][0][0][0] + uni((c * NCL + cl) * 2560 + u * 64);
      mbar_waitu(bar + 8 * B_LANDFREE, step & 1);
      int n = 0;
      while (true) {
        const bool ok = __all_sync(~0u, ((step & 2 ? ~TAGS(0xFE, pa) : TAGS(0x80, pa)) & 1) != 0);
        if (ok) break;
        if (++n > SPIN_LIMIT) FAIL();
        POLL(pa, gq);
      }
      if (warp == 0 && first) { TS(19); TSV(10, n); }
      const uint32_t w0 = hadd2bf(hadd2bf(hadd2bf(pa[0].x, pa[1].x), hadd2bf(pa[2].x, pa[3].x)), hadd2bf(hadd2bf(pa[4].x, pa[5].x), pa[6].x));
      const uint32_t w1 = hadd2bf(hadd2bf(hadd2bf(pa[0].y, pa[1].y), hadd2bf(pa[2].y, pa[3].y)), hadd2bf(hadd2bf(pa[4].y, pa[5].y), pa[6].y));
      if (u < ds) {
        const uint32_t da = SMEM0 + off + lane * 8, db = SMEM0 + boff;
#pragma unroll
        for (int d = 0; d < 12; d++) st_async_v2((d << 24) + da, w0, w1, (d << 24) + db);
#pragma unroll
        for (int d = 12; d < 15; d++) st_async_v2_if(nA == 15, (d << 24) + da, w0, w1, (d << 24) + db);
      } else {
        *reinterpret_cast<uint2*>(const_cast<uint32_t*>(gq) + ((4 - 2 * (step & 1)) * NCL + cl) * 2560) = make_uint2(w0, w1);
        asm volatile("fence.proxy.async.global;" ::: "memory");
        __syncwarp();
        bulk_g2s_mc_e(sb + off, mi, 256, sb + boff, mcmask);
      }
    };
#define REL(b, g) mbar_arrive_remote_if(lane == 0, rb0 + ((nA - 4 + (g)) << 24) + OFF_BAR + 8 * (b))

  if (wg < 2) {
    asm volatile("setmaxnreg.inc.sync.aligned.u32 160;");
    LANE_INIT();
    uint32_t W[4 * (40 - SSQ)];
    mbar_waitw(bar + 8 * B_W0, 0);
    GTS(26);
    load_w<40 - SSQ>(W, sb + (wg ? STG_K : STG_Q), warp, lane);
    fence_async();
    bar_sync(1, 384);
    cluster_sync_all();
#define DESC(k) const Desc D = make_desc(M.d, min(wg, 2) * SSQ, fresh<k>(step))
    GTS(27);
#pragma unroll 1
    for (int step = -1; step < NSTEP; step++) {
      const uint32_t par = step & 1;
      asm volatile("" : "+r"(lane));
      const bool dual = is_dual(step), has_next = step + 1 < NSTEP;
#define QK_SA (sb + OFF_QK + wg * 15360 + (2 * warp + ((lane >> 3) & 1)) * 128 + (lane & 7) * 16)
#define QK_F (wg ? -5120 : 5120)
#define QK_S12 ((wg ? (lane >> 4) : 1 + 2 * (lane >> 4)) * 1024)
#define QK_S34 ((wg ? 2 + (lane >> 4) : 2 - 2 * (lane >> 4)) * 1024)
      if (step >= 0) {
        if (dual) {
          DESC(0);
          float acc[24];
          mbar_waitu(bar + 8 * (B_F1 + 0), par);
          if (wg + warp == 0) { TS(0); TSN(1); }
          CFENCE(); wg_fence(); proj<48, SSQ, 0, 0, 10>(acc, W, D); wg_commit();
          mbar_waitu(bar + 8 * (B_F1 + 1), par);
          CFENCE(); wg_fence(); proj<48, SSQ, 0, 10, 20>(acc, W, D); wg_commit();
          mbar_waitu(bar + 8 * (B_F1 + 2), par);
          CFENCE(); wg_fence(); proj<48, SSQ, 0, 20, 30>(acc, W, D); wg_commit();
          mbar_waitu(bar + 8 * (B_F1 + 3), par);
          if (wg + warp == 0) TS(2);
          CFENCE(); wg_fence(); proj<48, SSQ, 0, 30, 40>(acc, W, D); wg_commit();
          bar_arrive(N_VGO, 384);
          mbar_waitu(bar + 8 * B_PLFREE, par);
          const uint32_t sa = QK_SA, s0 = sa + 4096 + (lane >> 4) * QK_F, s1 = sa + QK_F + QK_S12, s2 = sa + QK_F + QK_S34;
          wg_wait<0>();
          if (wg + warp == 0) TS(3);
          stsm4t(s0, pack2(acc[0], acc[1]), pack2(acc[2], acc[3]), pack2(acc[20], acc[21]), pack2(acc[22], acc[23]));
          stsm4t(s1, pack2(acc[4], acc[5]), pack2(acc[6], acc[7]), pack2(acc[8], acc[9]), pack2(acc[10], acc[11]));
          stsm4t(s2, pack2(acc[12], acc[13]), pack2(acc[14], acc[15]), pack2(acc[16], acc[17]), pack2(acc[18], acc[19]));
        } else {
          DESC(1);
          float acc[4];
          mbar_waitu(bar + 8 * (B_F1 + 0), par);
          if (wg + warp == 0) { TS(0); TSN(1); }
          CFENCE(); wg_fence(); proj<8, SSQ, 0, 0, 10>(acc, W, D); wg_commit();
          mbar_waitu(bar + 8 * (B_F1 + 1), par);
          CFENCE(); wg_fence(); proj<8, SSQ, 0, 10, 20>(acc, W, D); wg_commit();
          mbar_waitu(bar + 8 * (B_F1 + 2), par);
          CFENCE(); wg_fence(); proj<8, SSQ, 0, 20, 30>(acc, W, D); wg_commit();
          mbar_waitu(bar + 8 * (B_F1 + 3), par);
          if (wg + warp == 0) TS(2);
          CFENCE(); wg_fence(); proj<8, SSQ, 0, 30, 40>(acc, W, D); wg_commit();
          bar_arrive(N_VGO, 384);
          mbar_waitu(bar + 8 * B_PLFREE, par);
          const uint32_t s0 = QK_SA + 4096;
          wg_wait<0>();
          if (wg + warp == 0) TS(3);
          stsm2t(s0, pack2(acc[0], acc[1]), pack2(acc[2], acc[3]));
        }
        fence_async();
        bar_sync(N_QK, 256);
        if (wg == 0 || dual) {
          float s[20];
          DESC(2);
          const Dsc ab = D.k1 + wg * 192, bb = D.k1 + (1 - wg) * 320;
          wg_fence();
          MM<40>::ss<dlo(OFF_QK, 128), dlo(OFF_QK + 10240, 128), 0, 0>(s, ab, bb);
          MM<40>::ss<dlo(OFF_QK + 256, 128), dlo(OFF_QK + 10240 + 256, 128), 1, 0>(s, ab, bb);
          MM<40>::ss<dlo(OFF_QK + 512, 128), dlo(OFF_QK + 10240 + 512, 128), 1, 0>(s, ab, bb);
          MM<40>::ss<dlo(OFF_QK + 768, 128), dlo(OFF_QK + 10240 + 768, 128), 1, 0>(s, ab, bb);
          wg_commit();
          bar_arrive(N_SISS, 384);
          const int rw = (warp - wg) & 3;
          const uint32_t bo = OFF_BAR + 8 * (B_SB + 3 * wg + rw), lo = OFF_PL + wg * PL_SZ + rw * 1792;
          const uint32_t km = wg ? 640 : 512;
          uint32_t l16 = lo + lane * 16, l4 = lo + lane * 4;
          mbar_expect_if(lane == 0 && rw < 3, sb + bo, rw < 2 ? 1792 : 1280);
          asm volatile("" : "+r"(l16), "+r"(l4));
          if (rw == 2) {
            wg_wait<0>();
            if (wg == 0) TSD(4, __float_as_uint(s[0]));
            const uint32_t w0 = pack2(s[0], s[1]), w1 = pack2(s[4], s[5]), w2 = pack2(s[8], s[9]), w3 = pack2(s[12], s[13]), w4 = pack2(s[16], s[17]);
            {
              st_async_v4(nxt + 896 + l16, w0, w1, w2, w3, nxt + bo);
              st_async_v4(prv + l16, w0, w1, w2, w3, prv + bo);
              st_async_b32(nxt + 896 + 768 + l4, w4, nxt + bo);
              st_async_b32(prv + 768 + l4, w4, prv + bo);
            }
            bar_arrive(N_SDONE, 256);
            mbar_waitu(sb + bo, (step - wg * LAG) & 1);
            if (wg == 0) TS(5);
            float x[10], m0;
            {
              const uint4 a = lds128(sb + l16), b = lds128(sb + 896 + l16);
              const uint32_t c = lds32(sb + 768 + l4), d = lds32(sb + 896 + 768 + l4);
              const uint32_t e0 = hadd2bf(hadd2bf(a.x, b.x), w0), e1 = hadd2bf(hadd2bf(a.y, b.y), w1), e2 = hadd2bf(hadd2bf(a.z, b.z), w2),
                             e3 = hadd2bf(hadd2bf(a.w, b.w), w3), e4 = hadd2bf(hadd2bf(c, d), w4);
              const uint32_t em = hmax2bf(hmax2bf(hmax2bf(e0, e1), hmax2bf(e2, e3)), e4);
              m0 = fmaxf(bf_lo(em), bf_hi(em));
              x[0] = bf_lo(e0); x[1] = bf_hi(e0); x[2] = bf_lo(e1); x[3] = bf_hi(e1); x[4] = bf_lo(e2);
              x[5] = bf_hi(e2); x[6] = bf_lo(e3); x[7] = bf_hi(e3); x[8] = bf_lo(e4); x[9] = bf_hi(e4);
            }
            m0 = fmaxf(m0, __shfl_xor_sync(~0u, m0, 1));
            sts32(sb + l4 + 1152 - km, 0u);
            m0 = fmaxf(m0, __shfl_xor_sync(~0u, m0, 2));
            m0 *= -SL2;
#pragma unroll
            for (int j = 0; j < 5; j++) {
              x[2 * j] = ex2(fmaf(x[2 * j], SL2, m0)); x[2 * j + 1] = ex2(fmaf(x[2 * j + 1], SL2, m0));
              sts32(sb + l4 + (j < 4 ? j * 128 : km), pack2(x[2 * j], x[2 * j + 1]));
            }
            float l = ((x[0] + x[1]) + (x[2] + x[3])) + ((x[4] + x[5]) + ((x[6] + x[7]) + (x[8] + x[9])));
            l += __shfl_xor_sync(~0u, l, 1);
            fence_async();
            sts32(sb + OFF_INV + wg * 64 + (lane >> 1) * 4, __float_as_uint(l));
            bar_arrive(N_PM, dual ? 224 : 192);
            if (wg == 0) TS(6);
          } else if (rw < 2) {
            const bool w1 = rw == 1;
            const uint32_t l8 = lo + 512 + lane * 8;
            uint32_t tw[7];
            wg_wait<0>();
            bar_arrive(N_SDONE, 256);
            tw[0] = pack2(s[0], s[1]); tw[1] = pack2(s[4], s[5]); tw[2] = pack2(s[8], s[9]); tw[3] = pack2(s[16], s[17]);
            tw[4] = w1 ? pack2(s[6], s[7]) : pack2(s[12], s[13]); tw[5] = pack2(s[2], s[3]); tw[6] = pack2(s[18], s[19]);
            { const uint32_t t0 = clock32(); while (clock32() - t0 < TOK_DELAY) {} }
            st_async_v4(nxt + 896 + l16, tw[0], tw[1], tw[2], tw[3], nxt + bo);
            st_async_v4(prv + l16, tw[0], tw[1], tw[2], tw[3], prv + bo);
            st_async_v2(nxt + 896 + l8, tw[5], tw[6], nxt + bo);
            st_async_v2(prv + l8, tw[5], tw[6], prv + bo);
            st_async_b32(nxt + 896 + 768 + l4, tw[4], nxt + bo);
            st_async_b32(prv + 768 + l4, tw[4], prv + bo);
            mbar_waitu(sb + bo, (step - wg * LAG) & 1);
            const uint4 a = lds128(sb + l16), b = lds128(sb + 896 + l16);
            const uint2 e = lds64(sb + l8), f = lds64(sb + 896 + l8);
            const uint32_t c = lds32(sb + 768 + l4), d = lds32(sb + 896 + 768 + l4);
            sts128(sb + l16, hadd2bf(hadd2bf(a.x, b.x), tw[0]), hadd2bf(hadd2bf(a.y, b.y), tw[1]), hadd2bf(hadd2bf(a.z, b.z), tw[2]), hadd2bf(hadd2bf(a.w, b.w), tw[3]));
            sts64(sb + l8, hadd2bf(hadd2bf(e.x, f.x), tw[5]), hadd2bf(hadd2bf(e.y, f.y), tw[6]));
            sts32(sb + 768 + l4, hadd2bf(hadd2bf(c, d), tw[4]));
            bar_arrive(N_PX, dual ? 256 : 192);
            if (wg + warp == 0) TS(9);
          } else {
            wg_wait<0>();
            if (wg == 0) {
              mbar_expect_if(lane < 3 && has_next, bar + 8 * (lane == 2 ? B_OPEER : B_WOF + lane), lane == 2 ? (dual ? 4096 : 2048) : lane ? 8192 : 20480);
              auto fetch = [&](int i, int n, uint32_t dst, int mb) {
                int c0, c1; wo_coord(i, t3, head, c0, c1);
                tma2d_e(dst, &M.wo32, c0, c1, bar + 8 * mb); if (n == 2) tma2d_e(dst + 4096, &M.wo32, c0, c1 + 32, bar + 8 * mb);
              };
              bar_sync(N_G3, 160);
              if (has_next) {
                fetch(0, 2, sb + OFF_WT, B_WTF);
                mbar_arrive_remote_if(lane < 2, (lane ? nxt : prv) + OFF_BAR + 8 * B_XFREE);
              }
              bar_sync(N_SDONE, 256);
              if (has_next) {
                fetch(15, 1, sb + OFF_QK, B_WOF); fetch(16, 2, sb + OFF_QK + 4096, B_WOF); fetch(18, 2, sb + OFF_QK + 12288, B_WOF);
                mbar_waitu(bar + 8 * B_XFREE, par);
              }
              bar_arrive(N_PM, dual ? 224 : 192);
              bar_sync(N_VDONE, 160);
              mbar_arrive_remote_if(lane < nA && has_next, rb0 + (lane << 24) + OFF_BAR + 8 * B_MEMFREE);
              if (has_next) mbar_waitu(bar + 8 * B_WTF, par);
            } else {
              bar_arrive(N_SDONE, 256);
              if ((unsigned)ig < IG_V) issue_tok(sched_l(step + 1), B_F2, B_R1, (step - LAG) & 1);
            }
          }
        } else {
          bar_arrive(N_SISS, 384);
          bar_arrive(N_SDONE, 256);
        }
        if (has_next) {
          if (step == 0) mbar_waitw(bar + 8 * B_W1, 0);
          const uint32_t r1 = rb0 + ((nA - 1) << 24) + OFF_BAR + 8 * B_R1;
          if (dual) { DESC(3); wo_phase<16>(sb, wg, warp, lane, par, r1, D); } else { DESC(4); wo_phase<8>(sb, wg, warp, lane, par, r1, D); }
          bar_arrive(N_C, 288);
          if (warp == 0) TS(7 + wg);
        }
      }
      if (has_next) {
        DESC(5);
        float acc[16];
        mbar_waitu(bar + 8 * B_F2, par ^ 1);
        wg_fence(); proj<32, SSQ, 1, 0, 10>(acc, W, D); wg_commit();
        mbar_waitu(bar + 8 * (B_F2 + 1), par ^ 1);
        wg_fence(); proj<32, SSQ, 1, 10, 14>(acc, W, D); wg_commit();
        wg_wait<1>(); REL(B_R2, 0);
        wg_fence(); proj<32, SSQ, 1, 14, 20>(acc, W, D); wg_commit();
        mbar_waitu(bar + 8 * (B_F2 + 2), par ^ 1);
        wg_fence(); proj<32, SSQ, 1, 20, 24>(acc, W, D); wg_commit();
        wg_wait<1>(); REL(B_R2, 1);
        wg_fence(); proj<32, SSQ, 1, 24, 30>(acc, W, D); wg_commit();
        mbar_waitu(bar + 8 * (B_F2 + 3), par ^ 1);
        wg_fence(); proj<32, SSQ, 1, 30, 34>(acc, W, D); wg_commit();
        wg_wait<1>(); REL(B_R2, 2);
        wg_fence(); proj<32, SSQ, 1, 34, 40>(acc, W, D); wg_commit();
        const uint32_t sa = QK_SA, s1 = sa + QK_S12, s2 = sa + QK_S34;
        wg_wait<0>(); REL(B_R2, 3);
        if (warp == 0) TS(11 + wg);
        stsm4t(s1, pack2(acc[0], acc[1]), pack2(acc[2], acc[3]), pack2(acc[4], acc[5]), pack2(acc[6], acc[7]));
        stsm4t(s2, pack2(acc[8], acc[9]), pack2(acc[10], acc[11]), pack2(acc[12], acc[13]), pack2(acc[14], acc[15]));
      }
    }
    GTS(28);
    cluster_sync_all();
  } else if (wg == 2) {
    asm volatile("setmaxnreg.inc.sync.aligned.u32 160;");
    LANE_INIT();
    uint32_t W[4 * (40 - SSV)];
    ld_rest<0>(W, reinterpret_cast<const uint32_t*>(M.wv + (lane >> 2) * HD + col0 + warp * 16) + (lane & 3));
    uint4 m0[5];
#pragma unroll
    for (int i = 0; i < 5; i++) {
      const int t = i * 128 + warp * 32 + lane;
      m0[i] = __ldg(reinterpret_cast<const uint4*>(mem0 + ((t >> 1) & 7) * DM + (t >> 4) * 16 + ((t ^ (t >> 3)) & 1) * 8));
    }
    mbar_waitw(bar + 8 * B_W0, 0);
    load_w<VA>(W, sb + STG_K + 27 * 2048, warp, lane);
    load_w<VST - VA>(W + 4 * VA, sb + STG_V2, warp, lane);
    fence_async();
    mbar_expect_if(warp + lane == 0, bar + 8 * B_W1, 26 * 2048);
    bar_sync(1, 384);
#pragma unroll
    for (int i = 0; i < 5; i++) {
      const int t = i * 128 + warp * 32 + lane;
      sts128(sb + OFF_TILE + (t / 160) * (TILE_GRP - TILE_SBO) + t * 16, m0[i].x, m0[i].y, m0[i].z, m0[i].w);
    }
#pragma unroll
    for (int i = 4 * VST; i < 4 * (40 - SSV); i++) W[i] = movm(W[i]);
    fence_async();
    mbar_arrive_if(lane == 0, bar + 8 * (B_F1 + warp));
    mbar_expect_if(lane == 0, bar + 8 * (B_F2 + warp), 10240);
    mbar_arrive_if(warp == 3 && lane < 2, bar + 8 * B_PLFREE);
    cluster_sync_all();
    uint32_t vl[8];
    {
      const int step = warp;
      DESC(0);
      float v[16];
      mbar_waitw4(bar + 8 * B_F2, 0);
      wg_fence(); proj<32, SSV, 1, 0, 40>(v, W, D); wg_commit();
      wg_wait<0>();
      mbar_arrive_remote_if(lane < 4, rb0 + ((nA - 4 + lane) << 24) + OFF_BAR + 8 * B_R2);
#pragma unroll
      for (int j = 0; j < 8; j++) vl[j] = pack2v(v[2 * j], v[2 * j + 1]);
      if (warp == 0 && (unsigned)ig < 3) issue_tok(1, B_F2, B_R2, 0);
    }
#pragma unroll 1
    for (int step = 0; step < NSTEP; step++) {
      const uint32_t par = step & 1;
      asm volatile("" : "+r"(lane));
      const bool dual = is_dual(step), has_next = step + 1 < NSTEP;
      mbar_expect_if(lane == 0 && has_next, bar + 8 * (B_F2 + warp), 10240);
      if (warp == 0 && ig >= IG_V && dual && sync_b) wait_cnt(&g_xready[sched_l(step + 1)][0], 32);
      bar_sync(N_VGO, 384);
      CFENCE();
#define F1_BYTES (is_dual(step + 1) ? 15360 : 2560)
#define ARM() do { \
        mbar_expect_if(lane == 0 && has_next, bar + 8 * (B_F1 + warp), F1_BYTES); \
        mbar_expect_if(lane == 0 && has_next && warp * nA + (int)rank < 40, bar + 8 * (B_RS + warp), (warp * nA + (int)rank >= 36 ? nA : nh) * (dual ? 512 : 256)); } while (0)
#define O_ADDR() uint32_t oa = sb + OFF_O + (lane >> 4) * PL_SZ + warp * 256 + (lane & 15) * 16, xo = (lane >> 4) * 1024 + warp * 256 + (lane & 15) * 16; \
        asm volatile("" : "+r"(oa), "+r"(xo))
#define O_READY(act) do { if (has_next) { const uint4 ov = lds128(oa); \
        if (act) { st_async_v4(nxt + OFF_XL + xo, ov.x, ov.y, ov.z, ov.w, nxt + OFF_BAR + 8 * B_OPEER); \
                   st_async_v4(prv + OFF_XF + xo, ov.x, ov.y, ov.z, ov.w, prv + OFF_BAR + 8 * B_OPEER); } \
        fence_async(); bar_arrive(N_O, 384); } \
        if (warp == 0) TS(15); } while (0)
#define TOK_L3(g0) if (warp == 0 && ig >= (g0) && has_next) { mbar_waitu(bar + 8 * B_R1, ig == 3 ? par : (step - LAG) & 1); asm volatile("fence.proxy.async.global;" ::: "memory"); \
        bulk_g2s_mc_e(sb + OFF_TILE + ig * TILE_GRP + TILE_SBO, &g_xn[0][0] + uni(sched_l(step + 1) * (32 * DM)) + ig * 5120, 10240, bar + 8 * (B_F2 + ig), mcmask); }
#define OX_ADDR() const bool ox = head * 3 + t3 == 95; \
        const uint32_t oxa = sb + OFF_PL + (ox ? warp * 1024 + (lane & 7) * 32 + ((((lane >> 3) ^ (lane >> 2)) & 1) << 4) : (lane & 7) * 128 + (((warp * 2 + ((lane >> 3) & 1)) ^ (lane & 7)) << 4)); \
        const uint32_t s1 = oxa + ((lane < 16 ? 3072 : 0) >> (ox ? 2 : 0)), s2 = oxa + ((lane < 16 ? 2048 : 1024) >> (ox ? 2 : 0))
      if (dual) {
        uint32_t vf[8], vm[4], vn[8];
        {
          DESC(0);
          float v[24];
          ARM();
          wg_fence(); proj<48, SSV, 0, 30, 40, 30>(v, W, D); wg_commit();
          proj<48, SSV, 0, 0, VD1 - 10, 30>(v, W, D);
          bar_sync(N_SISS, 384);
          proj<48, SSV, 0, VD1 - 10, VD1 - 7, 30>(v, W, D); wg_commit();
          wg_wait<1>(); bar_arrive(N_G3, 160);
          wg_fence(); proj<48, SSV, 0, VD1 - 7, 10, 30>(v, W, D); wg_commit();
          proj<48, SSV, 0, 10, 13, 30>(v, W, D); wg_commit();
          wg_wait<1>(); REL(B_R1, 0);
          wg_fence(); proj<48, SSV, 0, 13, 20, 30>(v, W, D); wg_commit();
          proj<48, SSV, 0, 20, 23, 30>(v, W, D); wg_commit();
          wg_wait<1>(); REL(B_R1, 1);
          wg_fence(); proj<48, SSV, 0, 23, 30, 30>(v, W, D); wg_commit();
          wg_wait<0>(); REL(B_R1, 2);
          bar_arrive(N_VDONE, 160);
          if (warp == 0) TS(14);
#pragma unroll
          for (int j = 4; j < 8; j++) vf[j] = pack2v(v[4 + 2 * j], v[5 + 2 * j]);
          keep4(vf + 4, lane);
          vm[0] = pack2v(v[0], v[1]); vm[1] = pack2v(v[2], v[3]); vm[2] = pack2v(v[20], v[21]); vm[3] = pack2v(v[22], v[23]);
          keep4(vm, lane);
#pragma unroll
          for (int j = 0; j < 4; j++) vf[j] = pack2v(v[4 + 2 * j], v[5 + 2 * j]);
          keep4(vf, lane);
        }
        {
          DESC(1);
          float o[8];
          O_ADDR();
          bar_sync(N_PM, 224);
          wg_fence();
          MM<8>::rs<dlo(OFF_PL + 3584, 128), 0>(o, vl, D.p);
          MM<8>::rs<dlo(OFF_PL + PL_SZ + 3584, 128), 0>(o + 4, vf, D.p);
          MM<8>::rs<dlo(OFF_PL + 3584 + 256, 128), 1>(o, vl + 4, D.p);
          MM<8>::rs<dlo(OFF_PL + PL_SZ + 3584 + 256, 128), 1>(o + 4, vf + 4, D.p);
          MM<8>::rs<dlo(OFF_PL + 3584 + 512, 128), 1>(o, vm, D.p);
          MM<8>::rs<dlo(OFF_PL + PL_SZ + 3584 + 512, 128), 1>(o + 4, vm, D.p);
          wg_commit();
          fence_sched(step);
          const uint4 il = lds128(sb + OFF_INV + (lane & 3) * 16), jf = lds128(sb + OFF_INV + 64 + (lane & 3) * 16);
          const float i0 = rcpf(__uint_as_float(il.x) + __uint_as_float(il.y)), i1 = rcpf(__uint_as_float(il.z) + __uint_as_float(il.w));
          const float j0 = rcpf(__uint_as_float(jf.x) + __uint_as_float(jf.y)), j1 = rcpf(__uint_as_float(jf.z) + __uint_as_float(jf.w));
          { const uint32_t k4[4] = {__float_as_uint(i0), __float_as_uint(i1), __float_as_uint(j0), __float_as_uint(j1)}; keep4(k4, lane | (oa ^ xo)); }
          wg_wait<0>();
          stsm4t(oa, pack2(o[0] * i0, o[1] * i1), pack2(o[2] * i0, o[3] * i1), pack2(o[4] * j0, o[5] * j1), pack2(o[6] * j0, o[7] * j1));
          O_READY(true);
          TOK_L3(IG_V);
        }
        {
          DESC(2);
          float v[16];
          bar_sync(N_TURN, 256);
          mbar_waitu(bar + 8 * B_F2, par ^ 1);
          wg_fence(); proj<32, SSV, 1, 0, 10>(v, W, D); wg_commit();
          mbar_waitu(bar + 8 * (B_F2 + 1), par ^ 1);
          wg_fence(); proj<32, SSV, 1, 10, 14>(v, W, D); wg_commit();
          wg_wait<1>(); REL(B_R2, 0);
          wg_fence(); proj<32, SSV, 1, 14, 20>(v, W, D); wg_commit();
          mbar_waitu(bar + 8 * (B_F2 + 2), par ^ 1);
          wg_fence(); proj<32, SSV, 1, 20, 24>(v, W, D); wg_commit();
          wg_wait<1>(); REL(B_R2, 1);
          wg_fence(); proj<32, SSV, 1, 24, 30>(v, W, D); wg_commit();
          mbar_waitu(bar + 8 * (B_F2 + 3), par ^ 1);
          wg_fence(); proj<32, SSV, 1, 30, 34>(v, W, D); wg_commit();
          wg_wait<1>(); REL(B_R2, 2);
          wg_fence(); proj<32, SSV, 1, 34, 40>(v, W, D); wg_commit();
          wg_wait<0>(); REL(B_R2, 3);
#pragma unroll
          for (int j = 0; j < 8; j++) vn[j] = pack2v(v[2 * j], v[2 * j + 1]);
          keep4(vn, lane); keep4(vn + 4, lane);
          if (warp == 0) TS(18);
        }
        DESC(3);
        uint32_t ow[16];
        bar_sync(N_P, 256);
        fence_async();
#define PV16(i, off, va) { float o[8]; wg_fence(); \
          MM<16>::rs<dlo(OFF_PL + (off), 128), 0>(o, va, D.p); \
          MM<16>::rs<dlo(OFF_PL + (off) + 256, 128), 1>(o, va + 4, D.p); \
          MM<16>::rs<dlo(OFF_PL + (off) + 512, 128), 1>(o, vm, D.p); \
          wg_commit(); wg_wait<0>(); \
          _Pragma("unroll") for (int j = 0; j < 4; j++) ow[4 * (i) + j] = pack2v(o[2 * j], o[2 * j + 1]); \
          keep4(ow + 4 * (i), lane); }
        PV16(0, 0, vl) PV16(1, 1792, vl) PV16(2, PL_SZ, vf) PV16(3, PL_SZ + 1792, vf)
        OX_ADDR();
        bar_sync(N_V, 128);
        stsm4t(s1, ow[0], ow[1], ow[2], ow[3]);
        stsm4t(s2, ow[4], ow[5], ow[6], ow[7]);
        stsm4t(s1 + PL_SZ, ow[8], ow[9], ow[10], ow[11]);
        stsm4t(s2 + PL_SZ, ow[12], ow[13], ow[14], ow[15]);
#pragma unroll
        for (int j = 0; j < 8; j++) vl[j] = vn[j];
      } else {
        uint32_t vm[4], vn[8];
        {
          DESC(4);
          float v[4];
          wg_fence(); proj<8, SSV, 0, 30, 40, 30>(v, W, D); wg_commit();
          proj<8, SSV, 0, 0, VS1, 30>(v, W, D); wg_commit();
          ARM();
          bar_sync(N_SISS, 384);
          wg_wait<1>(); bar_arrive(N_G3, 160);
          wg_fence(); proj<8, SSV, 0, VS1, 30, 30>(v, W, D); wg_commit();
          if (has_next) { mbar_waitu2(bar + 8 * B_F2, bar + 8 * (B_F2 + 1), par ^ 1); mbar_waitu(bar + 8 * (B_F2 + 2), par ^ 1); }
          wg_wait<0>();
          bar_arrive(N_VDONE, 160);
          vm[0] = pack2v(v[0], v[1]); vm[1] = pack2v(v[2], v[3]); vm[2] = pack2v(v[1], v[0]); vm[3] = pack2v(v[3], v[2]);
        }
        DESC(5);
        float v[16];
        {
          wg_fence(); proj<32, SSV, 1, 0, VS2>(v, W, D); wg_commit();
          {
            float o[4];
            O_ADDR();
            bar_sync(N_PM, 192);
            if (warp == 0) TS(14);
            wg_fence();
            MM<8>::rs<dlo(OFF_PL + 3584, 128), 0>(o, vl, D.p);
            MM<8>::rs<dlo(OFF_PL + 3584 + 256, 128), 1>(o, vl + 4, D.p);
            MM<8>::rs<dlo(OFF_PL + 3584 + 512, 128), 1>(o, vm, D.p);
            wg_commit();
            fence_sched(step);
            const uint4 il = lds128(sb + OFF_INV + (lane & 3) * 16);
            const float i0 = rcpf(__uint_as_float(il.x) + __uint_as_float(il.y)), i1 = rcpf(__uint_as_float(il.z) + __uint_as_float(il.w));
            { const uint32_t k4[4] = {__float_as_uint(i0), __float_as_uint(i1), oa, xo}; keep4(k4, lane); }
            wg_wait<0>();
            stsm2t(oa, pack2(o[0] * i0, o[1] * i1), pack2(o[2] * i0, o[3] * i1));
            O_READY(lane < 16);
            TOK_L3(3);
          }
          if (has_next) {
            mbar_arrive_remote_if(lane < VS2 / 10, rb0 + ((nA - 4 + lane) << 24) + OFF_BAR + 8 * B_R2);
            bar_sync(N_TURN, 256);
          }
          if (VS2 < 30) { wg_fence(); proj<32, SSV, 1, VS2, 30>(v, W, D); wg_commit(); }
          if (has_next) mbar_waitu(bar + 8 * (B_F2 + 3), par ^ 1);
          if (VS2 < 30) { wg_wait<0>(); if (has_next) REL(B_R2, 2); }
          wg_fence(); proj<32, SSV, 1, 30, 40>(v, W, D); wg_commit();
          wg_wait<0>();
          if (has_next) REL(B_R2, 3);
#pragma unroll
          for (int j = 0; j < 8; j++) vn[j] = pack2v(v[2 * j], v[2 * j + 1]);
          keep4(vn, lane); keep4(vn + 4, lane);
          if (warp == 0) TS(18);
        }
        float o[16];
        bar_sync(N_P, 256);
        fence_async();
        wg_fence();
        MM<32>::rs<dlo(OFF_PL, 128), 0>(o, vl, D.p);
        MM<32>::rs<dlo(OFF_PL + 256, 128), 1>(o, vl + 4, D.p);
        MM<32>::rs<dlo(OFF_PL + 512, 128), 1>(o, vm, D.p);
        wg_commit();
        OX_ADDR();
        wg_wait<0>();
        bar_sync(N_V, 128);
        stsm4t(s1, pack2(o[0], o[1]), pack2(o[2], o[3]), pack2(o[4], o[5]), pack2(o[6], o[7]));
        stsm4t(s2, pack2(o[8], o[9]), pack2(o[10], o[11]), pack2(o[12], o[13]), pack2(o[14], o[15]));
#pragma unroll
        for (int j = 0; j < 8; j++) vl[j] = vn[j];
      }
      bar_arrive(N_OX, 160);
      if (warp == 0) TS(16);
    }
    cluster_sync_all();
  } else {
    asm volatile("setmaxnreg.dec.sync.aligned.u32 32;");
    if (wg > 3) return;
    LANE_INIT();
    struct RsJob { uint32_t* gp; uint32_t la, mb; int n; };
    auto rs_prep = [&](int step, int s, int c) {
      RsJob j;
      const int u = s * nA + rank;
      j.gp = &g_part[0][0][0][0] + (uint32_t)((((step & 1) * 2 + c) * NCL + cl) * 2560 + u * 64 + (lane >> 2) * 8 + (lane & 3));
      j.la = sb + OFF_TILE + c * LAND_F + LAND(s) + lane * 8;
      j.mb = bar + 8 * (B_RS + s);
      j.n = u >= 40 ? 0 : u >= 36 ? 3 : 1;
      asm volatile("" : "+l"(j.gp), "+r"(j.la));
      return j;
    };
    auto rs_sum = [&](RsJob j, int step) {
      if (j.n) {
        auto five = [&](uint32_t la) {
          uint2 p[5];
#pragma unroll
          for (int i = 0; i < 4; i++) p[i] = lds64(la + i * 256);
          asm volatile("{\n.reg .pred q;\nsetp.eq.s32 q, %3, 5;\nmov.u32 %0, 0;\nmov.u32 %1, 0;\n@q ld.shared.v2.b32 {%0,%1}, [%2];\n}"
                       : "=r"(p[4].x), "=r"(p[4].y) : "r"(la + 1024), "r"(nh) : "memory");
          return make_uint2(hadd2bf(hadd2bf(p[0].x, p[1].x), hadd2bf(hadd2bf(p[2].x, p[3].x), p[4].x)),
                            hadd2bf(hadd2bf(p[0].y, p[1].y), hadd2bf(hadd2bf(p[2].y, p[3].y), p[4].y)));
        };
        const uint32_t tag = ((step >> 1) & 1) ^ 1;
        mbar_waitw(j.mb, step & 1);
        uint2 t = five(j.la);
        if (j.n > 1) {
          const uint2 a = five(j.la + (nh == 5 ? 1280 : TILE_GRP - 1280)), b = five(j.la + TILE_GRP);
          t.x = hadd2bf(t.x, hadd2bf(a.x, b.x)); t.y = hadd2bf(t.y, hadd2bf(a.y, b.y));
        }
        const uint32_t t0 = (movm(t.x) & ~1u) | tag, t1 = (movm(t.y) & ~1u) | tag;
        asm volatile("st.relaxed.gpu.global.b32 [%0], %1;" :: "l"(j.gp), "r"(lane & 16 ? t1 : t0) : "memory");
        asm volatile("st.relaxed.gpu.global.b32 [%0], %1;" :: "l"(j.gp + 4), "r"(lane & 16 ? t0 : t1) : "memory");
      }
    };
    if (warp * nA + (int)rank < 40) {
#pragma unroll
      for (int e = LAG; e < LAG + 2; e++)
        if ((e >> 1) & 1) *reinterpret_cast<uint2*>(&g_part[(e & 1) * 2 + 1][cl][warp * nA + rank][lane * 2]) = make_uint2(1u, 1u);
      __threadfence();
    }
    if (warp == 2 && ig >= 0 && sync_b) wait_cnt(&g_xready[0][0], 32);
    cluster_sync_all();
    if (warp == 2 && ig >= 0) bulk_g2s_mc_e(sb + OFF_TILE + ig * TILE_GRP + TILE_SBO, &g_xn[0][0] + ig * 5120, 10240, bar + 8 * (B_F2 + ig), mcmask);
    bar_sync(N_PI, 128);
#pragma unroll 1
    for (int i = warp; i < 20; i += 4) {
      int c0, c1; wo_coord(i, t3, head, c0, c1);
      if (i >= 2 && i < 15) tma2d_e(sb + OFF_WO + (i - 2) * 4096, &M.wo32, c0, c1, bar + 8 * B_W1);
      else if (lane == 0) tma2d_prefetch(&M.wo32, c0, c1);
      __syncwarp();
    }
#pragma unroll 1
    for (int step = 0; step < NSTEP; step++) {
      const uint32_t par = step & 1;
      asm volatile("" : "+r"(lane));
      const bool dual = is_dual(step), has_next = step + 1 < NSTEP;
      {
        bar_sync(N_PX, dual ? 256 : 192);
        if (dual || warp >= 2) tok_softmax(sb, dual ? warp : warp - 2, lane);
        bar_arrive(N_P, 256);
        asm volatile("" : "+r"(lane));
        if (has_next) {
          if (step + 2 == LAG && lane < 20) asm volatile("prefetch.global.L2 [%0];" :: "l"(mem0 + (warp * 20 + lane) * 64));
          const int nw = ig >= 0 ? 3 : 4, j0 = warp < nw ? warp : 8;
          const int sh = dual ? 1 : 0;
          rs_sum(rs_prep(step, j0 >> sh, j0 & sh), step);
          if (warp == 0) TS(17);
          if (dual) rs_sum(rs_prep(step, (j0 + nw) >> 1, (j0 + nw) & 1), step);
          if (warp == 0) { bar_sync(N_C, 288); }
          mbar_arrive_remote_if(lane < nA, rb0 + (lane << 24) + OFF_BAR + 8 * B_LANDFREE);
          const uint32_t gap = dual ? POLL_GAPD : POLL_GAP;
          if (gap) { const uint32_t t0 = clock32(); while (clock32() - t0 < gap) {} }
#pragma unroll 1
          for (int j = j0; j < (dual ? 8 : 4); j += nw) {
            const int u = (j >> sh) * nA + rank, c = j & sh;
            if (u < UMAX && (c || step + 1 != NSEG)) {
              const uint32_t* gq = &g_part[0][0][0][0] + (uint32_t)((par * 2 + c) * NCL * 2560 + u * 64 + lane * 2);
              uint2 pa[NCL];
              POLL(pa, gq);
              deliver(pa, gq, u, c, step + 1 < NSEG ? c : 0, dual ? DS_DUAL : DS_SINGLE, step, j == 0, lane);
            }
            if (warp == 0 && j == 0) TS(13);
          }
          if (warp >= nw && (is_dual(step + 1) || (ig < 3 && step + 2 < NSTEP))) {
            issue_tok(is_dual(step + 1) ? sched_f(step + 1) : sched_l(step + 2), is_dual(step + 1) ? B_F1 : B_F2, B_R2, par ^ 1);
          }
          if (step + 1 == LAG && UMAX) {
            uint4 v[5];
#pragma unroll
            for (int i = 0; i < 5; i++) { const int t = warp * 160 + i * 32 + lane; v[i] = *reinterpret_cast<const uint4*>(mem0 + ((t >> 1) & 7) * DM + (t >> 4) * 16 + ((t ^ (t >> 3)) & 1) * 8); }
            mbar_waitu(bar + 8 * B_LANDFREE, par);
#pragma unroll
            for (int i = 0; i < 5; i++)
              st_async_v4(sb + OFF_TILE + LAND_F + warp * TILE_GRP + (i * 32 + lane) * 16, v[i].x, v[i].y, v[i].z, v[i].w, bar + 8 * (B_F1 + warp));
          }
        }
      }
      if (warp == (ig >= 0 && !is_dual(step + 1) ? 2 : 3)) {
        unsigned char* o0 = g_o + uni(step % RO * (96 * 8192) + (head * 3 + t3) * (dual ? 8192 : 4096));
        bar_sync(N_OX, 160);
        fence_async();
        bulk_s2g_es(o0, sb + OFF_PL, 4096);
        if (dual) bulk_s2g_es(o0 + 4096, sb + OFF_PL + PL_SZ, 4096);
        asm volatile("cp.async.bulk.commit_group;" ::: "memory");
        asm volatile("cp.async.bulk.wait_group.read 0;" ::: "memory");
        __syncwarp();
        mbar_arrive_remote_if(lane < 2, (lane ? nxt : prv) + OFF_BAR + 8 * B_PLFREE);
        asm volatile("cp.async.bulk.wait_group 0;" ::: "memory");
        asm volatile("fence.proxy.async.global;" ::: "memory");
        __syncwarp();
        if (lane == 0) red_release(&g_f[F_O + (head * 3 + t3) / 5][step], 1u);
        __syncwarp();
      }
    }
    cluster_sync_all();
  }
}

__device__ __forceinline__ uint32_t gelu2(uint32_t y, uint32_t s) {
  uint32_t g;
  asm("{\n.reg .b32 x, u, a, b;\nmov.b32 a, 0x28912891;\nmov.b32 b, 0x3a623a62;\nmul.rn.f16x2 x, %1, %2;\nmul.rn.f16x2 u, x, x;\nfma.rn.f16x2 u, u, a, b;\n"
      "mul.rn.f16x2 u, u, x;\ntanh.approx.f16x2 u, u;\nfma.rn.f16x2 %0, x, u, x;\n}" : "=r"(g) : "r"(y), "r"(s));
  return g; }

struct BParams {
  CUtensorMap wmap[5];
  CUtensorMap wo16;
  const __nv_bfloat16* x;
  __nv_bfloat16* out;
  uint64_t desc, desc32;
};
#define BO_O 0
#define BO_RES (6 * 8192)
#define OP_RES 63488
#define BO_STG (BO_RES + 2 * OP_RES)
#define BO_RING_OP (BO_STG + 16384)
#define OP_SLOT 12288
#define NS_OP 3
#define BO_H 81920
#define BO_W1 (BO_H + 16384)
#define BO_RING_MLP (BO_W1 + 81920)
#define BO_BAR 229376
#define BO_BOX (BO_BAR + 248)
#define BO_CARRY (BO_BAR + 512)
#define BO_STAT (BO_CARRY + 2048)
#define B_SMEM (BO_STAT + 256)
static_assert(B_SMEM <= 232448 && BO_RING_OP + NS_OP * OP_SLOT == BO_BAR && BO_RING_MLP + 3 * 16384 == BO_BAR && 2 * 83968 <= BO_RING_MLP, "smem");
enum { BB_W = 0, BB_FULL = 2, BB_TMP = BB_FULL + 3, BB_OFULL = BB_FULL + 5, BB_SFREE = BB_OFULL,
       BB_STAT = BB_SFREE + 6, BB_GO, BB_ZFREE, BB_DONE = BB_ZFREE + 3,
       BB_EMPTY, BB_START = BB_EMPTY, BB_USED = BB_EMPTY + 2, BB_NUM = BB_USED + 3 };
enum { NB_PP = 1, NB_H = 3, NB_END = 4, NB_END2 = 5, NB_STAGED = 6, NB_FREE = 8, NB_EARLY = 10, NB_LAST = 11 };

#define DESC_LO(off) (((SMEM0 + (off)) >> 4) | (1u << 16))

__device__ __forceinline__ uint32_t ld_relaxed(const uint32_t* p) { uint32_t v; asm volatile("ld.relaxed.gpu.global.b32 %0, [%1];" : "=r"(v) : "l"(p) : "memory"); return v; }
__device__ __forceinline__ int front(int r) { return r - (r > NSEG); }
__device__ __forceinline__ int fmask(int r) { return (r < NSEG) | ((r >= LAG && r < NSTEP) << 1); }
__device__ __forceinline__ int bmask(int r) { return (r <= NSEG) | ((r >= LAG && r != NSEG) << 1); }
#define NMERGE 3
__device__ __forceinline__ bool merged(bool w12, int r) { return !w12 && r > NSEG && r < NSEG + 2 * NMERGE; }
__device__ __forceinline__ uint32_t rtarget(int mask) { return mask == 3 ? 64 : 32; }
__device__ __forceinline__ void warp_signal(uint32_t* p, int lane) {
  __syncwarp();
  asm volatile("{\n.reg .pred q;\nsetp.eq.u32 q, %1, 0;\n@q red.release.gpu.global.add.u32 [%0], 1;\n}" :: "l"(p), "r"(lane) : "memory");
}
__device__ __forceinline__ uint32_t pack2h(float lo, float hi) { uint32_t r; asm("cvt.rn.f16x2.f32 %0, %1, %2;" : "=r"(r) : "f"(hi), "f"(lo)); return r; }
template <bool H> __device__ __forceinline__ uint32_t pk(float lo, float hi) { return H ? pack2h(lo, hi) : pack2(lo, hi); }
template <int N, bool H> __device__ __forceinline__ void stage_out(const float* d, uint32_t dst, int warp, int lane) {
  const uint32_t sa = dst + ((lane >> 4) * 8 + (lane & 7)) * 128 + (((2 * warp + ((lane >> 3) & 1)) ^ (lane & 7)) << 4);
#pragma unroll
  for (int m = 0; m < N / 16; m++)
    stsm4t(sa + m * 2048, pk<H>(d[8 * m], d[8 * m + 1]), pk<H>(d[8 * m + 2], d[8 * m + 3]), pk<H>(d[8 * m + 4], d[8 * m + 5]), pk<H>(d[8 * m + 6], d[8 * m + 7]));
}
template <int N> __device__ __forceinline__ void acc_live(float* d) {
#pragma unroll
  for (int i = 0; i < N / 2; i++) asm volatile("" : "+f"(d[i]) :: "memory");
}
struct Ring {
  uint32_t sl, ph;
  template <int NS> __device__ __forceinline__ void step() { if (++sl == NS) { sl = 0; ph ^= 1; } }
};

#define KOFF(x) (DESC_LO(BO_O) + ((x) >> 2) * 512 + ((x) & 3) * 2)
template <int N, int P>
__device__ __forceinline__ void op_pass(const uint32_t* W, uint32_t bar, Dsc alo, Dsc blo, Dsc xlo, bool x2, Ring& rg, int wg, int warp, int lane, int r) {
  float acc[N / 2];
  blo.e = xlo.e = fresh<P + N / 64 * 5>(r);
  const Dsc tlo = blo + uni(rg.sl) * (OP_SLOT / 16), b2 = blo + (r & 1) * 1536;
  if (P == 0) mbar_waitu(bar + 8 * (BB_OFULL + 2 + (r & 1)), (r >> 1) & 1);
  CTS(5 * P);
  bar_sync(NB_PP + wg, 256);
  wg_fence();
#define OP_R(x, b) MM<N>::template rs<KOFF(4 * (x >> 1) + (x & 1)), (x != (P ? 0 : 4))>(acc, W + 32 * P + 4 * x, b);
#define OP_S(x, b) MM<N>::template ss<DESC_LO(BO_RES) + (6 * P + x) * 128, KOFF(4 * (x >> 1) + 2 + (x & 1)), 1>(acc, alo, b);
#define OP_T(x) MM<N>::template ss<DESC_LO(BO_RING_OP) + x * 128, KOFF(14 + x), 1>(acc, tlo, blo);
#define OP_B2() OP_R(4, b2) OP_S(4, b2) OP_R(5, b2) OP_S(5, b2)
  if (P == 0) { OP_B2() mbar_waitu(bar + 8 * BB_OFULL, r & 1); }
  OP_R(0, blo) OP_S(0, blo) OP_R(1, blo) OP_S(1, blo) OP_R(2, blo) OP_S(2, blo) OP_R(3, blo) OP_S(3, blo)
  if (P == 0) mbar_waitu(bar + 8 * (BB_OFULL + 1), r & 1);
  if (P == 4) wg_commit();
  if (P & 3) { OP_B2() }
  if (P == 1 && x2) MM<N>::template ss<DESC_LO(BO_RES) + 30 * 128, DESC_LO(BO_CARRY), 1>(acc, alo, xlo);
  mbar_waitu(bar + 8 * (BB_FULL + rg.sl), rg.ph);
  OP_R(6, blo) OP_T(0) OP_R(7, blo) OP_T(1)
  if (P == 4) { wg_commit(); wg_wait<1>(); bar_arrive(NB_EARLY, 288); CTS(21); wg_fence(); }
  OP_T(2) OP_T(3)
  if (P == 0) MM<N>::template rs<DESC_LO(BO_CARRY), 1>(acc, W + 160, xlo);
  OP_T(4) OP_T(5)
  if (P == 4) { wg_commit(); OP_B2() }
  wg_commit();
  bar_arrive(NB_PP + 1 - wg, 256);
  CTS(5 * P + 2);
  if (P == 4) { wg_wait<1>(); bar_arrive(NB_LAST, 288); }
  bar_sync(NB_FREE + wg, 160);
  wg_wait<0>();
  acc_live<N>(acc);
  mbar_arrive_if(lane == 0, bar + 8 * (BB_USED + rg.sl));
  CTS(5 * P + 3);
  stage_out<N, false>(acc, SMEM0 + BO_STG + wg * 8192, warp, lane);
  bar_arrive(NB_STAGED + wg, 160);
  CTS(5 * P + 4);
  rg.step<NS_OP>(); rg.step<NS_OP>();
}
template <int N>
__device__ __forceinline__ void op_round(const uint32_t* W, uint32_t bar, Dsc alo, Dsc blo, Dsc xlo, bool x2, Ring& rg, int wg, int warp, int lane, int r) {
  op_pass<N, 0>(W, bar, alo, blo, xlo, x2, rg, wg, warp, lane, r);
  op_pass<N, 1>(W, bar, alo, blo, xlo, x2, rg, wg, warp, lane, r);
  op_pass<N, 2>(W, bar, alo, blo, xlo, x2, rg, wg, warp, lane, r);
  op_pass<N, 3>(W, bar, alo, blo, xlo, x2, rg, wg, warp, lane, r);
  op_pass<N, 4>(W, bar, alo, blo, xlo, x2, rg, wg, warp, lane, r);
}
__device__ __forceinline__ void carry_in(uint32_t sb, int wg, int warp, int lane) {
  const int row = (lane >> 1) & 3;
  if (lane < 16) {
    const uint4 v = lds128(sb + BO_CARRY + (wg * 4 + warp) * 256 + lane * 16);
    sts128(sb + BO_H + wg * 8192 + (lane >> 3) * 4096 + row * 128 + (((2 * warp + (lane & 1)) ^ row) << 4), v.x, v.y, v.z, v.w);
  }
  __syncwarp();
}
template <int N, int Z>
__device__ __forceinline__ void p1_pair(float* acc, const uint32_t* W, uint32_t bar, Dsc alo, Dsc blo, int lane, int r) {
  constexpr uint32_t ZOFF = DESC_LO(BO_RING_MLP + (N == 64 ? (Z == 1 ? -1 : (4 - Z) & 3) * 16384 : (Z / 2 * 2 % 3) * 16384 + (Z & 1) * 4096));
  blo.e = fresh<10 + Z / 3 + N / 64 * 2>(r);
  mbar_waitu(bar + 8 * (BB_FULL + Z), r & 1);
  CTS(40 + Z);
  wg_fence();
#define P1_B(k) \
  MM<N, true>::template rs<ZOFF + k * 512, (2 * Z + k != 0)>(acc, W + 16 * Z + 8 * k, blo); \
  MM<N, true>::template ss<DESC_LO(BO_W1) + (2 * Z + k) * 512, ZOFF + k * 512 + 4, 1>(acc, alo, blo); \
  MM<N, true>::template rs<ZOFF + k * 512 + 2, 1>(acc, W + 16 * Z + 8 * k + 4, blo); \
  MM<N, true>::template ss<DESC_LO(BO_W1) + (2 * Z + k) * 512 + 128, ZOFF + k * 512 + 6, 1>(acc, alo, blo);
  P1_B(0)
  if (N == 64 && (Z == 1 || Z == 2)) { wg_commit(); wg_wait<1>(); mbar_arrive_if(lane == 0, bar + 8 * (BB_EMPTY + Z - 1)); wg_fence(); }
  P1_B(1)
  wg_commit();
}
template <int N>
__device__ __forceinline__ void phase1(const uint32_t* W, uint32_t sb, Dsc alo, Dsc blo, int half, int wg, int warp, int lane, bool shift, int off, int rb, int r) {
  float acc[N / 2];
  const uint32_t bar = sb + BO_BAR;
  CTS(30);
  p1_pair<N, 0>(acc, W, bar, alo, blo, lane, r);
  p1_pair<N, 1>(acc, W, bar, alo, blo, lane, r);
  p1_pair<N, 2>(acc, W, bar, alo, blo, lane, r);
  if (N == 64 && !wg) { mbar_waitu(bar + 8 * (BB_SFREE + 4), (rb + 1) & 1); if (shift) carry_in(sb, wg, warp, lane); }
  p1_pair<N, 3>(acc, W, bar, alo, blo, lane, r);
  if (N == 32 || wg) { mbar_waitu(bar + 8 * (BB_SFREE + 4 + wg), (rb + 1) & 1); if (shift) carry_in(sb, wg, warp, lane); }
  if (N == 32) mbar_arrive_if(lane < 2, bar + 8 * (BB_EMPTY + lane));
  p1_pair<N, 4>(acc, W, bar, alo, blo, lane, r);
  const int c = (lane >> 3) & 1, i0 = (lane >> 4) * 8 + (lane & 7) + off;
  uint32_t a0 = sb + BO_H + wg * 8192 + half * 4096 + i0 * 128 + (((2 * warp + c) ^ (i0 & 7)) << 4);
  uint32_t a1 = i0 >= 16 ? sb + BO_CARRY + (wg * 4 + warp) * 256 + half * 128 + (i0 - 16) * 32 + c * 16 : a0 + 2048, a3 = a1 + (i0 >= 16 ? 128 : 4096);
  asm volatile("" : "+r"(a0), "+r"(a1), "+r"(a3));
  mbar_waitu(bar + 8 * BB_STAT, r & 1);
  const uint32_t sa = sb + BO_STAT + (lane & 3) * 32 + half * 16;
  const uint4 t0 = lds128(sa), t1 = N == 64 ? lds128(sa + 16) : t0;
  const uint32_t t[8] = {t0.x, t0.y, t0.z, t0.w, t1.x, t1.y, t1.z, t1.w};
  { const uint32_t k4[4] = {a0, a1, a3, sa}; keep4(k4, lane); }
  wg_wait<0>();
  acc_live<N>(acc);
  CTS(32);
#pragma unroll
  for (int m = 0; m < N / 16; m++) {
    const float* d = acc + 8 * m;
    stsm4t(m == 1 ? a1 : m == 3 ? a3 : a0 + m * 2048, gelu2(pack2h(d[0], d[1]), t[2 * m]), gelu2(pack2h(d[2], d[3]), t[2 * m]),
           gelu2(pack2h(d[4], d[5]), t[2 * m + 1]), gelu2(pack2h(d[6], d[7]), t[2 * m + 1]));
  }
}
template <int N, int P>
__device__ __forceinline__ void p2_mma(float* acc, const uint32_t* W, Dsc alo, Dsc blo, int r) {
  blo.e = fresh<P + N / 64 * 5>(r);
  MM<N, true>::template rs<DESC_LO(BO_H), 0>(acc, W + 80 + 16 * P, blo);     MM<N, true>::template ss<DESC_LO(0) + P * 1024, DESC_LO(BO_H) + 512, 1>(acc, alo, blo);
  MM<N, true>::template rs<DESC_LO(BO_H) + 2, 1>(acc, W + 84 + 16 * P, blo); MM<N, true>::template ss<DESC_LO(0) + P * 1024 + 128, DESC_LO(BO_H) + 514, 1>(acc, alo, blo);
  MM<N, true>::template rs<DESC_LO(BO_H) + 4, 1>(acc, W + 88 + 16 * P, blo); MM<N, true>::template ss<DESC_LO(0) + P * 1024 + 512, DESC_LO(BO_H) + 516, 1>(acc, alo, blo);
  MM<N, true>::template rs<DESC_LO(BO_H) + 6, 1>(acc, W + 92 + 16 * P, blo); MM<N, true>::template ss<DESC_LO(0) + P * 1024 + 640, DESC_LO(BO_H) + 518, 1>(acc, alo, blo);
}
template <int N, int P, int T>
__device__ __forceinline__ void p2_pass(const uint32_t* W, uint32_t bar, Dsc alo, Dsc blo, int wg, int warp, int lane, int r) {
  float acc[N / 2], ac2[N / 2];
  CTS(5 * P);
  if (P || wg) bar_sync(NB_PP + wg, 256);
  wg_fence();
  p2_mma<N, P>(acc, W, alo, blo, r);
  wg_commit();
  if constexpr (T == 2) { p2_mma<N, P + 1>(ac2, W, alo, blo, r); wg_commit(); }
  if (P < 4 || !wg) bar_arrive(NB_PP + 1 - wg, 256);
  CTS(5 * P + 2);
  if (T == 1 && (P == 2 || P == 3)) mbar_waitu(bar + 8 * (BB_SFREE + 2 * (P - 2) + wg), r & 1);
  wg_wait<T - 1>();
  acc_live<N>(acc);
  if (P == 4) bar_sync(NB_H, 256);
  CTS(5 * P + 3);
  constexpr int K = P / T & 1;
  stage_out<N, true>(acc, SMEM0 + (P == 4 ? BO_H : BO_RING_MLP + (2 - K) * 16384) + wg * 8192, warp, lane);
  if constexpr (T == 2) {
    wg_wait<0>();
    acc_live<N>(ac2);
    stage_out<N, true>(ac2, SMEM0 + BO_RING_MLP + (2 - K) * 16384 + wg * 8192 + 4096, warp, lane);
  }
  bar_arrive(NB_STAGED + (P == 4 ? 4 : 2 * K) + wg, 160);
  CTS(5 * P + 4);
}
template <int N>
__device__ __forceinline__ void phase2(const uint32_t* W, uint32_t bar, Dsc alo, Dsc blo, int wg, int warp, int lane, int r) {
  if constexpr (N == 64) {
    p2_pass<N, 0, 1>(W, bar, alo, blo, wg, warp, lane, r);
    p2_pass<N, 1, 1>(W, bar, alo, blo, wg, warp, lane, r);
    p2_pass<N, 2, 1>(W, bar, alo, blo, wg, warp, lane, r);
    p2_pass<N, 3, 1>(W, bar, alo, blo, wg, warp, lane, r);
  } else {
    p2_pass<N, 0, 2>(W, bar, alo, blo, wg, warp, lane, r);
    p2_pass<N, 2, 2>(W, bar, alo, blo, wg, warp, lane, r);
  }
  p2_pass<N, 4, 1>(W, bar, alo, blo, wg, warp, lane, r);
}

__device__ __forceinline__ void ldg4(uint32_t* v, const void* p) {
  asm volatile("ld.relaxed.gpu.global.v4.u32 {%0,%1,%2,%3}, [%4];" : "=r"(v[0]), "=r"(v[1]), "=r"(v[2]), "=r"(v[3]) : "l"(p) : "memory"); }
__device__ __forceinline__ void stg4(void* p, const uint32_t* v) {
  asm volatile("st.global.v4.u32 [%0], {%1,%2,%3,%4};" :: "l"(p), "r"(v[0]), "r"(v[1]), "r"(v[2]), "r"(v[3]) : "memory"); }
struct RowPtr {
  unsigned char *p, *q, *t;
  __device__ __forceinline__ void ld(uint32_t* v, int o) const {
    ldg4(v, p + o); ldg4(v + 4, q + o);
    asm volatile("ld.relaxed.gpu.global.v2.u32 {%0,%1}, [%2];" : "=r"(v[8]), "=r"(v[9]) : "l"(t + o) : "memory");
  }
  __device__ __forceinline__ void st(const uint32_t* w, int o) const {
    stg4(p + o, w); stg4(q + o, w + 4);
    asm volatile("st.global.v2.u32 [%0], {%1,%2};" :: "l"(t + o), "r"(w[8]), "r"(w[9]) : "memory");
  }
};
__device__ __forceinline__ RowPtr row_img(int r, int n, int lane) {
  unsigned char* b = &g_acc[0][r % RD][n * 128];
  unsigned char* p = b + (uint32_t)((lane >> 3) * 8192 + (((lane ^ n) & 7) << 4));
  return {p, p + 32768, b + (uint32_t)(65536 + (lane >> 4) * 8192 + ((((lane >> 1) ^ n) & 7) << 4) + (lane & 1) * 8)};
}
__device__ __forceinline__ RowPtr row_ext(const void* lin, bool xn, int layer, int tok, int lane) {
  unsigned char* b = xn ? reinterpret_cast<unsigned char*>(&g_xn[layer][0]) + (uint32_t)((tok >> 5) * 40960 + ((tok >> 3) & 3) * 2560 + (tok & 7) * 32)
                        : (unsigned char*)lin + (uint32_t)(tok * 1280);
  const uint32_t o = (lane >> 1) * 256 + ((lane ^ (tok >> 2)) & 1) * 16;
  return {b + (uint32_t)(xn ? o + (lane >= 20 ? 7680 : 0) : lane * 16),
          b + (uint32_t)(xn ? o + 4096 + 7680 + (lane >= 8 ? 7680 : 0) + (lane >= 28 ? 7680 : 0) : lane * 16 + 512),
          b + (uint32_t)(xn ? (lane >> 2) * 256 + ((lane & 3) ^ ((tok >> 1) & 2)) * 8 + 8192 + 3 * 7680 : lane * 8 + 1024)};
}
__device__ __forceinline__ float2 h2f(uint32_t w) {
  float2 f; asm("{\n.reg .f16 l, h;\nmov.b32 {l, h}, %2;\ncvt.f32.f16 %0, l;\ncvt.f32.f16 %1, h;\n}" : "=f"(f.x), "=f"(f.y) : "r"(w)); return f; }
__device__ __forceinline__ float rsq(float x) { float y; asm("rsqrt.approx.ftz.f32 %0, %1;" : "=f"(y) : "f"(x)); return y; }
__device__ __forceinline__ void red_if(uint32_t v, const void* a) {
  asm volatile("{\n.reg .pred q;\nsetp.ne.u32 q, %1, 0;\n@q red.relaxed.gpu.global.add.u32 [%0], %1;\n}" :: "l"(a), "r"(v) : "memory"); }
__device__ __forceinline__ uint32_t dep0(uint32_t w, int lane) { uint32_t z; asm volatile("shr.b32 %0, %1, %2;" : "=r"(z) : "r"(w), "r"(lane + 32)); return z; }
__device__ __forceinline__ int lane_of(uint32_t w) {
  int lane; asm volatile("{\n.reg .u32 t;\nmov.u32 t, %%laneid;\nshr.u32 %0, %1, 20;\nadd.u32 %0, %0, t;\n}" : "=r"(lane) : "r"(w)); return lane; }
#define BUF (RD * TILE_B)
__device__ __forceinline__ int await(uint32_t v, const uint32_t* p, uint32_t target, bool lazy) {
  int n = 0;
  while (!__all_sync(~0u, v >= target)) {
    if (lazy) __nanosleep(200);
    if (++n > SPIN_LIMIT) FAIL();
    v = ld_relaxed(p);
  }
  asm volatile("fence.acquire.gpu;" ::: "memory");
  return lane_of(v);
}
template <int W> __device__ __forceinline__ void sum2(float& s, float& q, int lane) {
  const bool up = lane & (W / 2);
  float e = (up ? q : s) + __shfl_xor_sync(~0u, up ? s : q, W / 2);
#pragma unroll
  for (int o = W / 4; o; o >>= 1) e += __shfl_xor_sync(~0u, e, o);
  const float f = __shfl_xor_sync(~0u, e, W / 2);
  s = up ? f : e; q = up ? e : f;
}
template <int TYPE>
__device__ __forceinline__ void rrow(int r, int row, int tok, int lane, const uint32_t* go, int role, const __nv_bfloat16* x, __nv_bfloat16* out) {
  const int half = TYPE == 3 ? 0 : row >> 5;
  float v[20];
  float2 st = make_float2(1.f, 0.f);
  {
    uint32_t a[10], c[10], u[10], sh = 16;
    if (TYPE == 2) row_img(front(r) + RD - ((row & 31) < 2), (row & 32) + ((row - 2) & 31), lane).ld(u, 3 * BUF);
    else row_ext(x, half, 1, tok, lane).ld(u, 0);
    if (TYPE == 2 || (TYPE == 0 && half))
      asm volatile("ld.relaxed.gpu.global.v2.f32 {%0,%1}, [%2];" : "=f"(st.x), "=f"(st.y) : "l"(g_stat + tok) : "memory");
    RowPtr ap = row_img(r, row, lane);
    const uint32_t g0 = TYPE != 3 ? ld_relaxed(go) : 0;
    if (TYPE != 3) {
      asm volatile("" : "+l"(ap.p), "+l"(ap.t));
      ap.q = ap.p + 32768;
      lane = await(g0, go, NOP * NW12 * NW34, false); BTS2(r, 8 + 2 * TYPE); RTS(0);
      ap.ld(a, TYPE ? 2 * BUF : 0);
    }
    if (TYPE == 0) {
      ap.ld(c, BUF);
      const uint32_t one = 0x3f803f80u | dep0(c[9], lane);
#pragma unroll
      for (int i = 0; i < 10; i++) asm volatile("fma.rn.bf16x2 %0, %0, %1, %2;" : "+r"(a[i]) : "r"(one), "r"(c[i]));
      sh |= dep0(a[9], lane);
    }
    const uint32_t z = TYPE == 2 ? dep0(a[9], lane) : 0;
#pragma unroll
    for (int i = 0; i < 10; i++) {
      if (TYPE == 2) { const float2 g = h2f(u[i] | z), h = h2f(a[i] | z); v[2 * i] = fmaf(h.x, 0.5f, g.x * st.x); v[2 * i + 1] = fmaf(h.y, 0.5f, g.y * st.x); continue; }
      float p = __uint_as_float(u[i] << sh), q = __uint_as_float(u[i] & (0xffffu << sh));
      if (TYPE == 0) { p = fmaf(p, st.x, bf_lo(a[i])); q = fmaf(q, st.x, bf_hi(a[i])); }
      v[2 * i] = p; v[2 * i + 1] = q;
    }
  }
  RTSD(1, v[19]);
  float s = 0.f, q = 0.f;
#pragma unroll
  for (int i = 0; i < 5; i++) {
    s += (v[4 * i] + v[4 * i + 1]) + (v[4 * i + 2] + v[4 * i + 3]);
    q += fmaf(v[4 * i], v[4 * i], v[4 * i + 1] * v[4 * i + 1]) + fmaf(v[4 * i + 2], v[4 * i + 2], v[4 * i + 3] * v[4 * i + 3]);
  }
  if (!(TYPE == 2 && half)) sum2<32>(s, q, lane);
  const float mean = s * (1.f / DM), var = fmaxf(q * (1.f / DM) - mean * mean, 0.f), rs = rsq(var + 1e-5f);
  const float k = TYPE == 0 ? 2.f * rs : half ? 1.f : rs, mr = TYPE && half ? st.y : -mean * k;
  RTSD(2, rs);
  uint32_t w[10];
#pragma unroll
  for (int i = 0; i < 10; i++) w[i] = pk<TYPE == 0>(fmaf(v[2 * i], k, mr), fmaf(v[2 * i + 1], k, mr));
  if (TYPE) row_ext(out, !half, TYPE == 2, tok, lane).st(w, 0);
  else {
    row_img(r, row, lane).st(w, 3 * BUF);
    const int q = r + ((row & 31) >= 30);
    row_img(q + (half && q >= NSEG), (row & 32) + ((row + 2) & 31), lane).st(w, 2 * BUF);
    if (lane == 1) g_st2[0][r % RD][row] = (__float_as_uint(0.5f * rsq(fmaf(var * rs, rs, 1e-5f))) & ~127u) | (r + 1);
  }
  if (TYPE != 3 && lane == 0) g_stat[tok] = make_float2((var + 1e-5f) * rs * (TYPE ? 1.f : 0.5f), mean + st.y);
}
__device__ __forceinline__ void r2rows(int r, int row, int lane, const uint32_t* go) {
  const int n = row + (lane >> 4);
  const unsigned char* ap = &g_acc[2][r % RD][0] + (uint32_t)(n * 128 + ((lane >> 3) & 1) * 8192 + (((lane ^ n) & 7) << 4));
  const uint32_t* sp = &g_st2[1][r % RD][n];
  asm volatile("" : "+l"(ap), "+l"(sp));
  await(0, go, NOP * NW12 * NW34, false);
  BTS2(r, 10);
  uint32_t a[20];
#pragma unroll
  for (int i = 0; i < 5; i++) ldg4(a + 4 * i, ap + i * 16384);
  const uint32_t z = dep0(a[19], lane);
  float s = 0.f, q = 0.f, q2 = 0.f;
#pragma unroll
  for (int i = 0; i < 20; i++) { const float2 h = h2f(a[i] | z); s += h.x + h.y; q = fmaf(h.x, h.x, q); q2 = fmaf(h.y, h.y, q2); }
  q += q2;
  sum2<16>(s, q, lane);
  const float mean = s * (0.5f / DM), rs = rsq(fmaxf(q * (0.25f / DM) - mean * mean, 0.f) + 1e-5f);
  if ((lane & 15) == 0) asm volatile("st.relaxed.gpu.global.u32 [%0], %1;" :: "l"(sp), "r"((__float_as_uint(0.5f * rs) & ~127u) | (r + 1)) : "memory");
}
__device__ __forceinline__ void r3rows(int r, int row, int tok, int lane, __nv_bfloat16* out) {
  const int n = row + (lane >> 4), m = 32 + ((n - 2) & 31);
  const unsigned char* ap = &g_acc[0][r % RD][0] + (uint32_t)(n * 128 + ((lane >> 3) & 1) * 8192 + (((lane ^ n) & 7) << 4));
  const unsigned char* zp = &g_acc[3][(r + RD - (row == 32)) % RD][0] + (uint32_t)(m * 128 + ((lane >> 3) & 1) * 8192 + (((lane ^ m) & 7) << 4));
  unsigned char* op = reinterpret_cast<unsigned char*>(out) + (uint32_t)((tok + (lane >> 4)) * 1280 + (lane & 15) * 16);
  float2 st;
  asm volatile("ld.relaxed.gpu.global.v2.f32 {%0,%1}, [%2];" : "=f"(st.x), "=f"(st.y) : "l"(g_stat + tok + (lane >> 4)) : "memory");
#pragma unroll 1
  for (int i0 = 0; i0 < 2; i0++) {
    uint32_t a[12], u[12];
#pragma unroll
    for (int i = 0; i < 3; i++) { ldg4(a + 4 * i, ap + 2 * BUF + i * 16384); ldg4(u + 4 * i, zp + i * 16384); }
    uint32_t z = dep0(u[11], lane);
#pragma unroll
    for (int i = 0; i < 12; i++) {
      const float2 h = h2f(a[i] | z), g = h2f(u[i] | z);
      a[i] = pack2(fmaf(h.x, 0.5f, fmaf(g.x, st.x, st.y)), fmaf(h.y, 0.5f, fmaf(g.y, st.x, st.y)));
      if (i & 1) z = dep0(a[i], lane);
    }
    if (i0 == 0) stg4(op, a);
    stg4(op + 256, a + 4); stg4(op + 512, a + 8);
    ap += 32768; zp += 32768; op += 512;
  }
}
template <int TYPE>
__device__ __forceinline__ void rloop(int row, int cp, int role, const __nv_bfloat16* x, __nv_bfloat16* out) {
  constexpr int ST = TYPE == 4 ? 2 : TYPE;
  const int r0 = row & 32 ? LAG : 0;
  uint32_t v = 0;
  static_assert(NSEG + RD - 2 >= NSTEP, "no signals");
#pragma unroll 1
  for (int r = r0; r < (TYPE == 0 ? r0 + NSEG : TYPE == 4 ? NSEG : TYPE == 2 || r0 ? NR : NSEG + 1); r++) {
    if (TYPE == 2 && r == NSEG + 1) row += 32;
    if (TYPE == 1 && r0 && r == NSEG) continue;
    const int tok = ((TYPE ? front(r) : r) - (row & 32 ? LAG : 0)) * 32 + (row & 31) - (TYPE ? 2 : 0);
    const bool valid = TYPE == 0 || (unsigned)tok < S_LEN;
    const uint32_t* go = &g_f[F_R1 + 4 * ST + cp][r];
    const uint32_t* first = TYPE == 2 ? &g_f[F_R2 + cp][r] : TYPE ? go : (const uint32_t*)&g_xready[NSEG + r - r0][0];
    if constexpr (TYPE == 1) { r2rows(r, row, lane_of(r), go); BTS2(r, 11); continue; }
    if constexpr (TYPE == 4) {
      const int lane = await(v, go, NOP * NW12 * NW34, false);
      BTS2(r, 8 + 2 * ST); RTS(0);
      if (valid) r3rows(r, row, tok, lane, out);
    } else if constexpr (TYPE != 1) {
      if (TYPE || row >= 32) await(v, first, TYPE ? NOP * NW12 * NW34 : 32, true);
      if (valid) rrow<TYPE>(r, row, tok, lane_of(r), go, role, x, out);
    }
    if (TYPE > 1 && row >= 32 && r + RD - 2 >= NSTEP) { v = 0; BTS2(r, 13); continue; }
    const int lane = lane_of(r);
    const void* f = lane ? (const void*)&g_xready[NSEG + (tok >> 5)][0] : (const void*)&g_f[TYPE ? F_DONE : F_Z][r];
    asm volatile("" : "+l"(f));
    __syncwarp();
    RTS(3);
    v = ld_relaxed(first + (TYPE ? 1 : 8));
    asm volatile("fence.release.gpu;" ::: "memory");
    RTS(4);
    red_if(lane == 0 || (TYPE == 2 && lane == 1 && valid) ? (TYPE & 5 ? 2 : 1) : 0, f);
    RTS(5);
    RTS_OUT();
    BTS2(r, 9 + 2 * ST);
  }
}

#define SINGLE_OP 3
#define SINGLE_W 0
#define W_DELAY 0
#define BULK_ADD(T, dst, src, len) asm volatile("{\n.reg .pred e;\nelect.sync _|e, 0xffffffff;\n@e cp.reduce.async.bulk.global.shared::cta.bulk_group.add.noftz." T " [%0], [%1], %2;\n}" \
                                               :: "l"(dst), "r"(src), "r"(len) : "memory")
#define COMMIT() asm volatile("cp.async.bulk.commit_group;" ::: "memory")
#define DRAINED(n) do { asm volatile("cp.async.bulk.wait_group.read " #n ";" ::: "memory"); __syncwarp(); } while (0)
#define WRITTEN() do { asm volatile("cp.async.bulk.wait_group 0;\nfence.proxy.async.global;" ::: "memory"); __syncwarp(); } while (0)
__device__ __forceinline__ void wait_flags(const uint32_t* p, uint32_t target) {
  int n = 0;
  while (!__all_sync(~0u, ld_relaxed(p) >= target)) { if (++n > SPIN_LIMIT) FAIL(); }
  asm volatile("fence.acquire.gpu;" ::: "memory");
  asm volatile("fence.proxy.async.global;" ::: "memory");
}
__global__ void __launch_bounds__(512, 1) bworker_kernel(const __grid_constant__ BParams P) {
  extern __shared__ __align__(1024) unsigned char smem_raw[];
  const uint32_t sb = SMEM0, bar = sb + BO_BAR;
  const int wg = __shfl_sync(~0u, threadIdx.x >> 7, 0), warp = __shfl_sync(~0u, (threadIdx.x >> 5) & 3, 0);
  if (threadIdx.x == 0) {
    if (smem_u32(smem_raw) != SMEM0) FAIL();
    uint32_t smid; asm volatile("mov.u32 %0, %%smid;" : "=r"(smid));
    const uint32_t nb = ld_relaxed(&g_tpc[(smid >> 1) & 127]);
    const bool single = nb > 1, far = nb == 0 && (smid < 64 || smid >= 124);
    int kind = far || (single && atomicAdd(&g_f[F_MISC][35], 1u) < SINGLE_OP) ? 0 : single ? 1 + SINGLE_W : 1;
    int rc = single || (smid >> 1) == 16 || (smid >> 1) == 63 ? 1 : far ? 2 : 0;
    uint32_t i = atomicAdd(&g_f[F_MISC][32 + kind], 1u), o = atomicAdd(&g_f[F_MISC][36 + rc], 1u);
    while (i >= (kind == 0 ? NOP : kind == 1 ? NW12 : NW34)) { kind = (kind + 1) % 3; i = atomicAdd(&g_f[F_MISC][32 + kind], 1u); }
    while (o >= (rc == 0 ? 16 : rc == 1 ? 8 : 12)) { rc = (rc + 1) % 3; o = atomicAdd(&g_f[F_MISC][36 + rc], 1u); }
    sts64(sb + BO_BOX, i + (kind == 0 ? 0 : kind == 1 ? NOP : NOP + NW12), o + (rc ? 8 + 8 * rc : 0));
    for (int k = 0; k < BB_NUM; k++) mbar_init(bar + 8 * k, k >= BB_USED ? 4 : k >= BB_EMPTY ? 8 : k >= BB_ZFREE && kind ? 2 : 1);
    asm volatile("fence.mbarrier_init.release.cluster;" ::: "memory");
  }
  if (threadIdx.x < 128) sts128(sb + BO_CARRY + threadIdx.x * 16, 0u, 0u, 0u, 0u);
  auto ln0 = [&](int t) {
    const int lane = lane_of(t);
    if (lane < 20 && t + 128 < S_LEN) asm volatile("prefetch.global.L2 [%0];" :: "l"(P.x + (t + (t < 4 * NBC ? 4 * NBC : 128)) * DM + (lane >> 1) * 64));
    rrow<3>(0, 0, t, lane, nullptr, 0, P.x, nullptr);
    __syncwarp();
    asm volatile("fence.release.gpu;" ::: "memory");
    red_if(lane == 0, &g_xready[t >> 5][0]);
  };
  if (wg == 2) ln0(blockIdx.x * 4 + warp);
  fence_async();
  __syncthreads();
  const int role = uni(lds32(sb + BO_BOX));
  if (threadIdx.x < 32) BTS(94, 1);
  const bool op = role < NOP, w12 = role < NOP + NW12;
  const int j = op ? role : w12 ? role - NOP : role - NOP - NW12;
  const int rot = op ? (j ? 2 * ((j + 1) % 5) : 0) : 2 * (j % 5);
  if (wg == 3) {
    asm volatile("setmaxnreg.dec.sync.aligned.u32 24;");
    LANE_INIT();
    if (warp < 2) {
      auto announce = [&](int r, int it, bool mg) {
        const uint32_t* f = &g_f[(op ? F_R1 : w12 ? F_R2 : F_R3) + (lane & 3)][r + ((lane >> 2) & 1)];
        asm volatile("" : "+l"(f));
        if (warp == 0) { mbar_arrive_if(lane == 0, bar + 8 * BB_DONE); return; }
        mbar_waitw(bar + 8 * BB_DONE, it & 1);
        PTS(60);
        asm volatile("fence.release.gpu;" ::: "memory");
        red_if(lane >= (mg ? 8 : 4) ? 0 : op ? NW12 * NW34 : w12 ? NOP * NW34 : NOP * NW12, f);
        PTS(61);
        BTS(r, 4);
      };
      if (op) {
        int mt = rot + warp;
        bar_arrive(NB_FREE + warp, 160);
#pragma unroll 1
        for (int r = 0; r < NSTEP; r++) {
          const uint32_t len = fmask(r) == 3 ? 8192 : 4096;
          unsigned char* acc = &g_acc[j & 1][r % RD][fmask(r) == 2 ? 4096 : 0];
#pragma unroll 1
          for (int p = 0; p < 5; p++) {
            bar_sync(NB_STAGED + warp, 160);
            PTS(50 + 2 * p + warp);
            fence_async();
            BULK_ADD("bf16", acc + mt * 8192, sb + BO_STG + warp * 8192, len);
            COMMIT();
            PTS(64 + 50 + 2 * p + warp);
            mt = mt >= 8 ? mt - 8 : mt + 2;
            DRAINED(0);
            bar_arrive(NB_FREE + warp, 160);
          }
          WRITTEN();
          announce(r, r, false);
        }
      } else {
#pragma unroll 1
        for (int r = 0, it = 0; r < NR; r++, it++) {
          const bool mg = merged(w12, r);
          const uint32_t len = bmask(r) == 3 ? 8192 : 4096;
          unsigned char* acc = &g_acc[2][r % RD][bmask(r) == 2 ? 4096 : 0];
          if (!w12) mbar_waitw(bar + 8 * BB_GO, it & 1);
          int mt = rot + warp;
          const bool pairs = len != 8192 && !mg;
#pragma unroll 1
          for (int p = pairs ? 2 : 0; p < 5; p++) {
            const uint32_t src = sb + (p == 4 ? BO_H : BO_RING_MLP + (2 - (p & 1)) * 16384) + warp * 8192;
            bar_sync(NB_STAGED + (p == 4 ? 4 : 2 * (p & 1)) + warp, 160);
            PTS(50 + 2 * p + warp);
            fence_async();
            BULK_ADD("f16", acc + mt * 8192, src, len);
            if (mg) BULK_ADD("f16", &g_acc[2][(r + 1) % RD][4096 + mt * 8192], src + 4096, len);
            mt = mt >= 8 ? mt - 8 : mt + 2;
            if (pairs && p < 4) { BULK_ADD("f16", acc + mt * 8192, src + 4096, len); mt = mt >= 8 ? mt - 8 : mt + 2; }
            COMMIT();
            PTS(64 + 50 + 2 * p + warp);
            if (p == 4 && !pairs) break;
            DRAINED(1);
            mbar_arrive_if(lane == 0 && p, bar + 8 * (p < 3 ? BB_SFREE + 2 * (p - 1) + warp : BB_ZFREE + (p >> 1)));
            mbar_arrive_if(lane == 0 && pairs && p == 2, bar + 8 * (BB_SFREE + warp));
            if (p == 3 && !pairs) { DRAINED(0); mbar_arrive_if(lane == 0, bar + 8 * (BB_ZFREE + 2)); }
          }
          WRITTEN();
          mbar_arrive_if(lane == 0, bar + 8 * (BB_SFREE + 4 + warp));
          announce(r, it, mg);
          r += mg;
        }
      }
    } else {
      if (op && warp == 2) {
        unsigned char* wt = g_wt + j * (10 * OP_SLOT);
#pragma unroll 1
        for (int m0 = 0; m0 < 10; m0 += 3) {
          const int nu = m0 < 9 ? 9 : 3;
          mbar_expect_if(lane == 0, bar + 8 * BB_TMP, nu * 4096);
#pragma unroll 1
          for (int k = 0; k < nu; k++) tma2d_e(sb + BO_RING_OP + k * 4096, &P.wmap[0], (m0 + k / 3) * 64, 320 * j + 224 + 32 * (k % 3), bar + 8 * BB_TMP);
          mbar_waitw(bar + 8 * BB_TMP, m0 & 1);
          bulk_s2g_e(wt + m0 * OP_SLOT, sb + BO_RING_OP, nu * 4096);
          COMMIT();
          WRITTEN();
        }
        asm volatile("fence.acq_rel.gpu;" ::: "memory");
        int sl = 0, ph = 1, mt = rot;
#pragma unroll 1
        for (int r = -1; r < NSTEP; r++) {
#pragma unroll 1
          for (int n = r < 0 ? 7 : 0; n < (r + 1 < NSTEP ? 10 : 7); n++) {
            mbar_waitw(bar + 8 * (BB_USED + sl), ph);
            mbar_expect_if(lane == 0, bar + 8 * (BB_FULL + sl), OP_SLOT);
            bulk_g2s_e(sb + BO_RING_OP + sl * OP_SLOT, wt + mt * OP_SLOT, OP_SLOT, bar + 8 * (BB_FULL + sl));
            if (++sl == 3) { sl = 0; ph ^= 1; }
            mt = mt == 9 ? 0 : mt + 1;
          }
        }
      } else if (op) {
        mbar_waitw(bar + 8 * BB_START, 0);
#pragma unroll 1
        for (int r = 0; r < NSTEP; r++) {
          const int rb = r - RD + 2;
          const uint32_t len = fmask(r) == 3 ? 8192 : 4096;
          const unsigned char* src = g_o + (uint32_t)(r % RO * (96 * 8192) + 5 * j * len);
          wait_flags(lane < 2 ? &g_f[F_O + (lane ? NOP : j)][r] : rb >= 0 ? &g_f[F_DONE][rb] : &g_f[F_MISC][0],
                     lane < 2 ? (lane ? 1 : 5) : rb >= 0 ? rtarget(bmask(rb)) : NBC * 8);
          PTS1(35);
          auto two = [&](int k, uint32_t mb) {
            bulk_g2s_e(sb + BO_O + k * 8192, src + k * len, len == 8192 ? 16384 : 4096, mb);
            if (len != 8192) bulk_g2s_e(sb + BO_O + k * 8192 + 8192, src + k * len + 4096, 4096, mb);
          };
          mbar_expect_if(lane == 0, bar + 8 * (BB_OFULL + 2 + (r & 1)), len);
          bulk_g2s_e(sb + BO_O + (r & 1 ? 5 : 2) * 8192, src + 2 * len, len, bar + 8 * (BB_OFULL + 2 + (r & 1)));
          if (r) bar_sync(NB_EARLY, 288);
          mbar_expect_if(lane < 2, bar + 8 * (BB_OFULL + lane), 2 * len + (lane ? len / 4 : 0));
          two(0, bar + 8 * BB_OFULL);
          PTS(62); PTS1(38);
          const unsigned char* sx = src + (95 - 5 * j) * len + (j + 1) / 5 * 1024;
          if (r) bar_sync(NB_LAST, 288);
          two(3, bar + 8 * (BB_OFULL + 1));
          bulk_g2s_e(sb + BO_CARRY, sx, 1024, bar + 8 * (BB_OFULL + 1));
          if (len == 8192) bulk_g2s_e(sb + BO_CARRY + 1024, sx + 4096, 1024, bar + 8 * (BB_OFULL + 1));
          if (r && r + 1 < NSTEP) {
            mbar_waitw(bar + 8 * (BB_USED + (10 * r - 2) % 3), (10 * r - 2) / 3 & 1);
            mbar_waitw(bar + 8 * (BB_USED + (10 * r - 1) % 3), (10 * r - 1) / 3 & 1);
          }
          PTS1(64 + 35);
          BTS(r, 0);
        }
      } else if (warp == 2) {
#pragma unroll 1
        for (int r = 0, it = 0; r < NR; r++, it++) {
          const bool mg = merged(w12, r);
          const int rf = w12 ? front(r) : r, mk = !w12 ? bmask(r) : r == NSEG ? 0 : fmask(rf), pf = w12 ? rf : it;
          const bool full = mk == 3 || mg;
          if (mk) {
            const unsigned char* src = &g_acc[w12 ? 3 : 2][rf % RD][mk == 2 ? 4096 : 0];
            wait_flags(&g_f[w12 ? F_Z : F_R2 + (j & 3)][rf + mg], w12 ? rtarget(mk) : NOP * NW12 * NW34);
#pragma unroll 1
            for (int z = 0; z < 5; z++) {
              const int k = full ? z - (z > 0) : z >> 1;
              const uint32_t fb = bar + 8 * (BB_FULL + z), dst = sb + BO_RING_MLP + 2 * k % 3 * 16384 + (!full ? (z & 1) * 4096 : z == 1 ? -16384 : 0);
              if (full ? z != 1 : !(z & 1)) mbar_waitw(bar + 8 * (k < 3 ? BB_ZFREE + k : BB_EMPTY), (k < 3 ? it + 1 : pf) & 1);
              if (z == 0) PTS(62);
              mbar_expect_if(lane == 0, fb, !full ? 8192 : z == 4 ? 32768 : 16384);
              bulk_g2s_e(dst, src + z * 16384, mk == 3 ? 16384 : 4096, fb);
              if (mk != 3) bulk_g2s_e(dst + 8192, src + z * 16384 + 8192, 4096, fb);
              if (mg) {
                const unsigned char* s2 = &g_acc[2][(r + 1) % RD][4096 + z * 16384];
                bulk_g2s_e(dst + 4096, s2, 4096, fb); bulk_g2s_e(dst + 12288, s2 + 8192, 4096, fb);
              }
              if (full && z == 4) { mbar_waitw(bar + 8 * (BB_EMPTY + 1), pf & 1); bulk_g2s_e(sb + BO_RING_MLP - 16384, g_wx[role - NOP], 16384, fb); }
              if (z == 0) BTS(r, 0);
            }
          }
          if (!w12) {
#pragma unroll 1
            for (int z = full ? 2 : 0; z < 5; z++) mbar_waitw(bar + 8 * (BB_FULL + z), it & 1);
            red_if(lane == 0, &g_f[F_GOT][r]);
#pragma unroll 1
            for (int c = j; c < (r + RD < NSTEP ? 80 : 0); c += NW34) bulk_s2g_e(&g_acc[c / 40][r % RD][c % 40 * 2048], sb + BO_CARRY, 2048);
            COMMIT();
            wait_flags(&g_f[F_GOT][r], NW34);
            mbar_arrive_if(lane == 0, bar + 8 * BB_GO);
            WRITTEN();
          }
          mbar_waitw(bar + 8 * BB_DONE, (it + 1) & 1);
          mbar_arrive_if(lane == 0, bar + 8 * BB_DONE);
          r += mg;
        }
      } else {
#pragma unroll 1
        for (int r0 = 0, it = 0; r0 < (w12 ? NSTEP : NR); r0++, it++) {
          const bool mg = merged(w12, r0), idle = !mg && !((w12 ? fmask(r0) : bmask(r0)) >> (lane >> 4) & 1);
          const int r = r0 + (mg ? lane >> 4 : 0);
          r0 += mg;
          uint32_t t0, t1;
          int n = 0;
          mbar_waitw(bar + 8 * BB_FULL, it & 1);
          do {
            asm volatile("ld.relaxed.gpu.global.v2.u32 {%0,%1}, [%2];" : "=r"(t0), "=r"(t1) : "l"(&g_st2[!w12][r % RD][2 * (mg ? lane | 16 : lane)]) : "memory");
            if (++n > SPIN_LIMIT) FAIL();
          } while (!__all_sync(~0u, idle || (((t0 ^ (r + 1)) | (t1 ^ (r + 1))) & 127) == 0));
          sts32(sb + BO_STAT + (lane & 3) * 32 + (lane >> 2) * 4, pack2h(__uint_as_float(t0), __uint_as_float(t1)));
          __syncwarp();
          mbar_arrive_if(lane == 0, bar + 8 * BB_STAT);
          PTS(63);
        }
      }
    }
    bar_arrive(NB_END, 512);
  } else if (wg == 2) {
    asm volatile("setmaxnreg.dec.sync.aligned.u32 40;");
    const int ord = uni(lds32(sb + BO_BOX + 4));
    const int g2 = warp * 12 + ord - 24, gw = ord < 16 ? warp * 16 + ord : ord < 24 ? 80 + warp * 8 + ord : g2 < 32 ? 64 + g2 : 96 + g2;
    const int row = gw < 64 ? gw : gw < 96 ? gw - 64 : gw < 128 ? 2 * gw - 192 : 2 * gw - 224;
    if (row >= 32) {
#pragma unroll 1
      for (int t = 4 * NBC + (gw < 64 ? gw - 32 : gw - 80); t < S_LEN; t += 64) ln0(t);
    }
    if (gw < 64) rloop<0>(row, gw & 3, role, P.x, P.out);
    else if (gw < 96) rloop<2>(row, gw & 3, role, P.x, P.out);
    else if (gw < 128) rloop<1>(row, gw & 3, role, P.x, P.out);
    else rloop<4>(row, gw & 3, role, P.x, P.out);
    asm volatile("griddepcontrol.wait;" ::: "memory");
    const int t = threadIdx.x & 127;
    for (int i = (blockIdx.x * 128 + t) * 4; i < 4 * NCL * 2560; i += NBC * 512)
      *reinterpret_cast<uint4*>(&g_part[0][0][0][0] + i) = make_uint4(0u, 0u, 0u, 0u);
    bar_sync(NB_END, 512);
    if (t == 0) {
      uint32_t n;
      asm volatile("atom.acq_rel.gpu.global.add.u32 %0, [%1], 1;" : "=r"(n) : "l"(&g_f[F_MISC][64]) : "memory");
      sts32(sb + BO_BOX, n);
    }
    bar_sync(NB_END2, 128);
    if (lds32(sb + BO_BOX) == NBC - 1) {
      for (int i = t; i < F_NUM * 24; i += 128) reinterpret_cast<uint4*>(&g_f[0][0])[i] = make_uint4(0u, 0u, 0u, 0u);
      g_xready[t][0] = 0; g_tpc[t] = 0;
    }
  } else {
    asm volatile("setmaxnreg.inc.sync.aligned.u32 224;");
    LANE_INIT();
    for (int i = blockIdx.x * 256 + threadIdx.x; i < 2 * RD * TILE_B / 16; i += NBC * 256) reinterpret_cast<uint4*>(&g_acc[0][0][0])[i] = make_uint4(0u, 0u, 0u, 0u);
    warp_signal(&g_f[F_MISC][0], lane);
    const int mt0 = (rot + wg) % 10;
    auto boxes = [&](int ss) {
      const int nb = op && ss ? 3 : 4;
      const uint32_t base = sb + (ss ? BO_RES + wg * OP_RES : wg * 83968);
      mbar_expect_if(warp == 0 && lane == 0, bar + 8 * (BB_W + wg), nb * 20480 + (op ? 2048 : 0));
      bar_sync(NB_H, 256);
      if (warp < nb) {
#pragma unroll 1
        for (int i = warp; i < 5 * nb; i += nb) {
          const int p = op ? i / nb : (i - 10) >> 1, mt = (mt0 + 2 * p) % 10;
          const bool first = !op && i < 10;
          tma2d_e(op || !ss ? base + i * 4096 : sb + (first ? BO_W1 : -81920) + (2 * i + wg) * 4096, &P.wmap[op ? 0 : (w12 ? 1 : 3) + !first], first ? 128 * j + 64 * wg : mt * 64,
                  op ? 320 * j + 64 * warp + 32 * ss : first ? 64 * i + 32 * ss : 128 * j + 32 * (i & 1) + 64 * ss, bar + 8 * (BB_W + wg));
        }
      }
      if (op && warp == 3) tma2d_e(base + nb * 20480, &P.wo16, (mt0 + 2 * ss) % 10 * 64, 95 * 64 + (j + 1) / 5 * 16, bar + 8 * (BB_W + wg));
      mbar_waitw(bar + 8 * (BB_W + wg), ss);
    };
    if (W_DELAY && !op) __nanosleep(W_DELAY);
    uint32_t W[164];
    boxes(0);
    load_w<41>(W, sb + wg * 83968, warp, lane);
    fence_async();
    boxes(1);
    if (!op) {
      float cs[2] = {0.f, 0.f};
      const uint32_t a0 = sb + BO_W1 + wg * 4096 + ((lane >> 4) * 8 + (lane & 7)) * 128 + (((warp * 2 + ((lane >> 3) & 1)) ^ (lane & 7)) << 4);
#pragma unroll
      for (int i = 0; i < 80; i++) cs[i & 1] += bf_lo(W[i]) + bf_hi(W[i]);
#pragma unroll 1
      for (int i = 0; i < 60; i++) {
        uint32_t t[4];
        const uint32_t ad = a0 + (i % 20 >> 1) * 8192 + (i & 1) * 2048 - (i >= 40 ? BO_W1 : 0);
        ldsm4t(t[0], t[1], t[2], t[3], ad);
#pragma unroll
        for (int k = 0; k < 4; k++) {
          if (i < 20) cs[k & 1] += bf_lo(t[k]) + bf_hi(t[k]);
          const float mu = i < 40 ? cs[k & 1] : 0.f;
          t[k] = pack2h(bf_lo(t[k]) - mu, bf_hi(t[k]) - mu);
        }
        if (i >= 20) stsm4t(ad, t[0], t[1], t[2], t[3]);
        if (i == 19) {
#pragma unroll
          for (int k = 0; k < 2; k++) { cs[k] += __shfl_xor_sync(~0u, cs[k], 1); cs[k] += __shfl_xor_sync(~0u, cs[k], 2); cs[k] *= 1.f / DM; }
        }
      }
      const uint32_t z = dep0(__float_as_uint(cs[0]), lane);
#pragma unroll
      for (int i = 0; i < 80; i++) { W[i] = pack2h(bf_lo(W[i] | z) - cs[i & 1], bf_hi(W[i] | z) - cs[i & 1]); W[80 + i] = pack2h(bf_lo(W[80 + i]), bf_hi(W[80 + i])); }
      fence_async();
      bar_sync(NB_H, 256);
      if (wg + warp == 0) { bulk_s2g_e(g_wx[role - NOP], sb + BO_RING_MLP - 16384, 16384); COMMIT(); WRITTEN(); asm volatile("fence.acq_rel.gpu;" ::: "memory"); }
    }
    if (warp == 0) BTS(94, 6 + wg);
    const Dsc blo = {P.desc, 1}, alo = blo + wg * (op ? OP_RES / 16 : 256);
    if (op) {
      Ring rg = {(uint32_t)wg, 0};
      mbar_arrive_if(lane == 0, bar + 8 * BB_START);
      if (wg) bar_arrive(NB_PP, 256);
      const Dsc xlo = {P.desc32, 1};
#pragma unroll 1
      for (int r = 0; r < NSTEP; r++) {
        asm volatile("" : "+r"(lane));
        if (fmask(r) == 3) op_round<64>(W, bar, alo, blo, xlo, j == 0, rg, wg, warp, lane, r);
        else op_round<32>(W, bar, alo, blo, xlo, j == 0, rg, wg, warp, lane, r);
        if (warp == 0) BTS(r, 2 + wg);
      }
    } else {
      const int q4 = (128 * j + 64 * wg + 16 * warp) / 160, off = w12 ? (0x0413 >> (4 * q4)) & 7 : 0;
#pragma unroll 1
      for (int r0 = 0, r = 0; r0 < NR; r0++, r++) {
        asm volatile("" : "+r"(lane));
        const bool mg = merged(w12, r0);
        const int bm = mg ? 3 : bmask(r0), rf = w12 ? front(r) : r, fm = !w12 ? bm : r == NSEG ? 0 : fmask(rf);
        if (fm == 3) phase1<64>(W, sb, alo, blo, 0, wg, warp, lane, w12, off, r, rf);
        else if (fm) phase1<32>(W, sb, alo, blo, fm >> 1, wg, warp, lane, w12, off, r, rf);
        else { mbar_waitu(bar + 8 * (BB_SFREE + 4 + wg), (r + 1) & 1); carry_in(sb, wg, warp, lane); }
        CTS(33);
        fence_async();
        bar_sync(NB_H, 256);
        mbar_arrive_if(wg == 1 && warp == 0 && lane < 2, bar + 8 * BB_ZFREE);
        if (wg + warp == 0) BTS(r0, 1);
        if (bm == 3) phase2<64>(W, bar, alo, blo, wg, warp, lane, r);
        else phase2<32>(W, bar, alo, blo + (bm >> 1) * 256, wg, warp, lane, r);
        if (warp == 0) BTS(r0, 2 + wg);
        r0 += mg;
      }
    }
    CTS_OUT();
    bar_arrive(NB_END, 512);
  }
}

typedef CUresult (*EncodeFn)(CUtensorMap*, CUtensorMapDataType, cuuint32_t, void*, const cuuint64_t*, const cuuint64_t*, const cuuint32_t*,
                             const cuuint32_t*, CUtensorMapInterleave, CUtensorMapSwizzle, CUtensorMapL2promotion, CUtensorMapFloatOOBfill);
static void make_map(EncodeFn fn, CUtensorMap* tm, const void* ptr, uint64_t cols, uint64_t rows, uint32_t bc, uint32_t br) {
  cuuint64_t dims[2] = {cols, rows}; cuuint64_t strides[1] = {cols * 2}; cuuint32_t box[2] = {bc, br}; cuuint32_t es[2] = {1, 1};
  fn(tm, CU_TENSOR_MAP_DATA_TYPE_BFLOAT16, 2, const_cast<void*>(ptr), dims, strides, box, es, CU_TENSOR_MAP_INTERLEAVE_NONE,
     CU_TENSOR_MAP_SWIZZLE_128B, CU_TENSOR_MAP_L2_PROMOTION_L2_256B, CU_TENSOR_MAP_FLOAT_OOB_FILL_NONE);
}
#define dbg_a_only 0
extern "C" void kernel_launch(void* const* d_in, const int* in_sizes, int n_in, void* d_out, int out_size) {
  void* fnp = nullptr; cudaDriverEntryPointQueryResult qr;
  cudaGetDriverEntryPoint("cuTensorMapEncodeTiled", &fnp, cudaEnableDefault, &qr);
  EncodeFn fn = (EncodeFn)fnp;
  cudaStream_t st = cudaStreamPerThread;
  cudaFuncSetAttribute(bworker_kernel, cudaFuncAttributeMaxDynamicSharedMemorySize, B_SMEM);
  {
    AMaps M;
    for (int i = 0; i < 3; i++) make_map(fn, &M.w16[i], d_in[2 + i], HD, DM, 64, 16);
    M.wv = (const __nv_bfloat16*)d_in[4];
    make_map(fn, &M.wo32, d_in[5], DM, HD, 64, 32);
    const uint32_t hi[5] = {dhi(TILE_SBO, 3), dhi(1024, 1), dhi(1024, 0), dhi(PL_SZ, 0), dhi(896, 0)};
    for (int i = 0; i < 5; i++) M.d[i] = (uint64_t)hi[i] << 32;
    cudaFuncSetAttribute(acore_kernel, cudaFuncAttributeMaxDynamicSharedMemorySize, A_SMEM);
    cudaFuncSetAttribute(acore_kernel, cudaFuncAttributeNonPortableClusterSizeAllowed, 1);
    cudaLaunchConfig_t cfg = {};
    cfg.gridDim = dim3(CL_SIZE * NCL); cfg.blockDim = dim3(512); cfg.dynamicSmemBytes = A_SMEM; cfg.stream = st;
    cudaLaunchAttribute at[1]; at[0].id = cudaLaunchAttributeClusterDimension;
    at[0].val.clusterDim.x = CL_SIZE; at[0].val.clusterDim.y = 1; at[0].val.clusterDim.z = 1;
    cfg.attrs = at; cfg.numAttrs = 1;
    cudaLaunchKernelEx(&cfg, acore_kernel, M, (const __nv_bfloat16*)d_in[1], dbg_a_only ? 0 : 1);
  }
  if (!dbg_a_only) {
    BParams P;
    make_map(fn, &P.wmap[0], d_in[5], DM, HD, 64, 32);
    make_map(fn, &P.wo16, d_in[5], DM, HD, 64, 16);
    make_map(fn, &P.wmap[1], d_in[8], DM, DM, 64, 32);
    make_map(fn, &P.wmap[2], d_in[9], DM, DM, 64, 32);
    make_map(fn, &P.wmap[3], d_in[10], FF, DM, 64, 32);
    make_map(fn, &P.wmap[4], d_in[11], DM, FF, 64, 32);
    P.x = (const __nv_bfloat16*)d_in[0];
    P.out = (__nv_bfloat16*)d_out;
    P.desc = (uint64_t)dhi(1024, 1) << 32;
    P.desc32 = (uint64_t)dhi(256, 3) << 32;
    cudaLaunchConfig_t cfg = {};
    cfg.gridDim = dim3(NBC); cfg.blockDim = dim3(512); cfg.dynamicSmemBytes = B_SMEM; cfg.stream = st;
    cudaLaunchAttribute at[1]; at[0].id = cudaLaunchAttributeProgrammaticStreamSerialization; at[0].val.programmaticStreamSerializationAllowed = 1;
    cfg.attrs = at; cfg.numAttrs = 1;
    cudaLaunchKernelEx(&cfg, bworker_kernel, P);
  }
}
```

```cpp
#include <cuda_runtime.h>
#include <cuda_bf16.h>
#include <cuda.h>
#include <stdint.h>

#define S_LEN 2048
#define DM 640
#define NH 32
#define DH 192
#define HD 6144
#define NSEG 64
#define FF 1536

__device__ __forceinline__ uint32_t smem_u32(const void* p) { return (uint32_t)__cvta_generic_to_shared(p); }
__device__ __forceinline__ uint32_t mapa(uint32_t a, uint32_t r) {
  uint32_t o; asm volatile("mapa.shared::cluster.u32 %0, %1, %2;" : "=r"(o) : "r"(a), "r"(r)); return o; }
__device__ __forceinline__ void mbar_init(uint32_t b, uint32_t c) {
  asm volatile("mbarrier.init.shared::cta.b64 [%0], %1;" :: "r"(b), "r"(c) : "memory"); }
__device__ __forceinline__ void mbar_expect(uint32_t b, uint32_t tx) {
  asm volatile("mbarrier.arrive.expect_tx.shared::cta.b64 _, [%0], %1;" :: "r"(b), "r"(tx) : "memory"); }
__device__ __forceinline__ void mbar_expect_if(bool p, uint32_t b, uint32_t tx) {
  asm volatile("{\n.reg .pred q;\nsetp.ne.u32 q, %2, 0;\n@q mbarrier.arrive.expect_tx.shared::cta.b64 _, [%0], %1;\n}" :: "r"(b), "r"(tx), "r"((uint32_t)p) : "memory"); }
__device__ __forceinline__ void mbar_arrive_if(bool p, uint32_t b) {
  asm volatile("{\n.reg .pred q;\nsetp.ne.u32 q, %1, 0;\n@q mbarrier.arrive.shared::cta.b64 _, [%0];\n}" :: "r"(b), "r"((uint32_t)p) : "memory"); }
__device__ __forceinline__ void mbar_arrive_remote_if(bool p, uint32_t rb) {
  asm volatile("{\n.reg .pred q;\nsetp.ne.u32 q, %1, 0;\n@q mbarrier.arrive.relaxed.cluster.shared::cluster.b64 _, [%0];\n}" :: "r"(rb), "r"((uint32_t)p) : "memory"); }
#define SPIN_LIMIT 4000000
#define FAIL() asm volatile("st.global.u32 [%0], 0;" :: "l"(8ull) : "memory")
#define CFENCE() asm volatile("fence.proxy.async::generic.acquire.sync_restrict::shared::cluster.cluster;" ::: "memory")
#define TIMEOUT_ACT "@!p st.shared.u32 [%0+1], 0;"
#define WAIT_HINT ", 20000"
#define WAIT_LIM "200000"
__device__ __forceinline__ void mbar_slow(uint32_t b, uint32_t ph) {
  asm volatile("{\n.reg .pred p, q;\n.reg .u32 n;\nmov.u32 n, 0;\n"
               "WL:\nmbarrier.try_wait.parity.shared::cta.b64 p, [%0], %1" WAIT_HINT ";\nadd.u32 n, n, 1;\nsetp.lt.and.u32 q, n, " WAIT_LIM ", !p;\n@q bra.uni WL;\n"
               TIMEOUT_ACT "\n}" :: "r"(b), "r"(ph) : "memory"); }
__device__ __forceinline__ void mbar_waitw(uint32_t b, uint32_t ph) {
  asm volatile("{\n.reg .pred p, q;\n.reg .u32 n;\nmbarrier.try_wait.parity.shared::cta.b64 p, [%0], %1;\n@p bra.uni WD;\nmov.u32 n, 0;\n"
               "WL:\nmbarrier.try_wait.parity.shared::cta.b64 p, [%0], %1" WAIT_HINT ";\nadd.u32 n, n, 1;\nsetp.lt.and.u32 q, n, " WAIT_LIM ", !p;\n@q bra.uni WL;\n"
               TIMEOUT_ACT "\nWD:\n}" :: "r"(b), "r"(ph) : "memory"); }
__device__ __forceinline__ void mbar_waitw2(uint32_t b0, uint32_t b1, uint32_t ph) {
  uint32_t ok;
  asm volatile("{\n.reg .pred p, r;\nmbarrier.try_wait.parity.shared::cta.b64 p, [%1], %3;\nmbarrier.try_wait.parity.shared::cta.b64 r, [%2], %3;\n"
               "and.pred p, p, r;\nselp.u32 %0, 1, 0, p;\n}" : "=r"(ok) : "r"(b0), "r"(b1), "r"(ph) : "memory");
  if (__builtin_expect(!__all_sync(~0u, ok), 0)) { mbar_slow(b0, ph); mbar_slow(b1, ph); }
}
__device__ __forceinline__ void mbar_waitu(uint32_t b, uint32_t ph) {
  asm volatile("{\n.reg .pred p;\nmbarrier.try_wait.parity.shared::cta.b64 p, [%0], %1;\n@p bra.uni WD;\n"
               "WL:\nmbarrier.try_wait.parity.shared::cta.b64 p, [%0], %1" WAIT_HINT ";\n@!p bra.uni WL;\nWD:\n}" :: "r"(b), "r"(ph) : "memory"); }
__device__ __forceinline__ void mbar_waitu2(uint32_t b0, uint32_t b1, uint32_t ph) {
  asm volatile("{\n.reg .pred p, r;\nWL:\nmbarrier.try_wait.parity.shared::cta.b64 p, [%0], %2;\nmbarrier.try_wait.parity.shared::cta.b64 r, [%1], %2;\n"
               "and.pred p, p, r;\n@!p bra.uni WL;\n}" :: "r"(b0), "r"(b1), "r"(ph) : "memory"); }
__device__ __forceinline__ void mbar_waitw4(uint32_t b, uint32_t ph) { mbar_waitw2(b, b + 8, ph); mbar_waitw2(b + 16, b + 24, ph); }
__device__ __forceinline__ uint32_t clock32() { uint32_t t; asm volatile("mov.u32 %0, %%clock;" : "=r"(t) :: "memory"); return t; }
template <int L> __device__ __forceinline__ uint32_t lop3(uint32_t a, uint32_t b, uint32_t c) {
  uint32_t r; asm("lop3.b32 %0, %1, %2, %3, %4;" : "=r"(r) : "r"(a), "r"(b), "r"(c), "n"(L)); return r; }
__device__ __forceinline__ void st_async_v2_if(bool p, uint32_t a, uint32_t v0, uint32_t v1, uint32_t mb) {
  asm volatile("{\n.reg .pred q;\nsetp.ne.u32 q, %4, 0;\n@q st.async.weak.shared::cluster.mbarrier::complete_tx::bytes.v2.b32 [%0], {%1,%2}, [%3];\n}"
               :: "r"(a), "r"(v0), "r"(v1), "r"(mb), "r"((uint32_t)p) : "memory"); }
__device__ __forceinline__ void keep4(const uint32_t* r, int lane) {
  asm volatile("{\n.reg .pred q;\nsetp.lt.s32 q, %4, 0;\n@q st.shared.v4.b32 [%4], {%0,%1,%2,%3};\n}" :: "r"(r[0]), "r"(r[1]), "r"(r[2]), "r"(r[3]), "r"(lane) : "memory"); }
__device__ __forceinline__ void fence_sched(int i) {
  asm volatile("{\n.reg .pred q;\nsetp.gt.s32 q, %0, 4096;\n@q st.shared.u32 [%0], 0;\n}" :: "r"(i) : "memory"); }
__device__ __forceinline__ uint32_t hmax2bf(uint32_t a, uint32_t b) { uint32_t r; asm("max.bf16x2 %0, %1, %2;" : "=r"(r) : "r"(a), "r"(b)); return r; }
__device__ __forceinline__ uint32_t uni(uint32_t x) { return __shfl_sync(~0u, x, 0); }
__device__ __forceinline__ void bulk_g2s_mc_e(uint32_t dst, const void* src, uint32_t bytes, uint32_t mb, uint16_t mask) {
  asm volatile("{\n.reg .pred e;\nelect.sync _|e, 0xffffffff;\n"
               "@e cp.async.bulk.shared::cluster.global.mbarrier::complete_tx::bytes.multicast::cluster [%0], [%1], %2, [%3], %4;\n}"
               :: "r"(dst), "l"(src), "r"(bytes), "r"(mb), "h"(mask) : "memory"); }
__device__ __forceinline__ void bulk_s2g_e(void* dst, uint32_t src, uint32_t bytes) {
  asm volatile("{\n.reg .pred e;\nelect.sync _|e, 0xffffffff;\n@e cp.async.bulk.global.shared::cta.bulk_group [%0], [%1], %2;\n}"
               :: "l"(dst), "r"(src), "r"(bytes) : "memory"); }
__device__ __forceinline__ void bulk_g2s_e(uint32_t dst, const void* src, uint32_t bytes, uint32_t mb) {
  asm volatile("{\n.reg .pred e;\nelect.sync _|e, 0xffffffff;\n@e cp.async.bulk.shared::cluster.global.mbarrier::complete_tx::bytes [%0], [%1], %2, [%3];\n}"
               :: "r"(dst), "l"(src), "r"(bytes), "r"(mb) : "memory"); }
#define STREAM_HINT 1
__device__ __forceinline__ void bulk_s2g_es(void* dst, uint32_t src, uint32_t bytes) {
  asm volatile("{\n.reg .pred e;\n.reg .b64 pol;\ncreatepolicy.fractional.L2::evict_first.b64 pol;\nelect.sync _|e, 0xffffffff;\n"
               "@e cp.async.bulk.global.shared::cta.bulk_group.L2::cache_hint [%0], [%1], %2, pol;\n}" :: "l"(dst), "r"(src), "r"(bytes) : "memory");
}
__device__ __forceinline__ void tma2d_e(uint32_t dst, const CUtensorMap* tm, int c0, int c1, uint32_t mb) {
  asm volatile("{\n.reg .pred e;\nelect.sync _|e, 0xffffffff;\n"
               "@e cp.async.bulk.tensor.2d.shared::cluster.global.mbarrier::complete_tx::bytes [%0], [%1, {%3, %4}], [%2];\n}"
               :: "r"(dst), "l"((uint64_t)tm), "r"(mb), "r"(c0), "r"(c1) : "memory"); }
__device__ __forceinline__ uint32_t hadd2bf(uint32_t a, uint32_t b) {
  uint32_t r; asm("add.rn.bf16x2 %0, %1, %2;" : "=r"(r) : "r"(a), "r"(b)); return r; }
__device__ __forceinline__ void cluster_sync_all() {
  asm volatile("barrier.cluster.arrive.release.aligned;\nbarrier.cluster.wait.acquire.aligned;" ::: "memory"); }
__device__ __forceinline__ void bar_arrive(int id, int n) { asm volatile("bar.arrive %0, %1;" :: "r"(id), "r"(n) : "memory"); }
__device__ __forceinline__ void bar_sync(int id, int n) { asm volatile("bar.sync %0, %1;" :: "r"(id), "r"(n) : "memory"); }
__device__ __forceinline__ void fence_async() { asm volatile("fence.proxy.async.shared::cta;" ::: "memory"); }
__device__ __forceinline__ void st_async_b32(uint32_t a, uint32_t v, uint32_t mb) {
  asm volatile("st.async.weak.shared::cluster.mbarrier::complete_tx::bytes.b32 [%0], %1, [%2];" :: "r"(a), "r"(v), "r"(mb) : "memory"); }
__device__ __forceinline__ void st_async_v2(uint32_t a, uint32_t v0, uint32_t v1, uint32_t mb) {
  asm volatile("st.async.weak.shared::cluster.mbarrier::complete_tx::bytes.v2.b32 [%0], {%1,%2}, [%3];" :: "r"(a), "r"(v0), "r"(v1), "r"(mb) : "memory"); }
__device__ __forceinline__ void st_async_v4(uint32_t a, uint32_t v0, uint32_t v1, uint32_t v2, uint32_t v3, uint32_t mb) {
  asm volatile("st.async.weak.shared::cluster.mbarrier::complete_tx::bytes.v4.b32 [%0], {%1,%2,%3,%4}, [%5];" :: "r"(a), "r"(v0), "r"(v1), "r"(v2), "r"(v3), "r"(mb) : "memory"); }
__device__ __forceinline__ void ldsm4t(uint32_t& r0, uint32_t& r1, uint32_t& r2, uint32_t& r3, uint32_t a) {
  asm volatile("ldmatrix.sync.aligned.m8n8.x4.trans.shared.b16 {%0,%1,%2,%3}, [%4];" : "=r"(r0), "=r"(r1), "=r"(r2), "=r"(r3) : "r"(a) : "memory"); }
__device__ __forceinline__ void stsm2t(uint32_t a, uint32_t r0, uint32_t r1) {
  asm volatile("stmatrix.sync.aligned.m8n8.x2.trans.shared.b16 [%0], {%1,%2};" :: "r"(a), "r"(r0), "r"(r1) : "memory"); }
__device__ __forceinline__ void stsm4t(uint32_t a, uint32_t r0, uint32_t r1, uint32_t r2, uint32_t r3) {
  asm volatile("stmatrix.sync.aligned.m8n8.x4.trans.shared.b16 [%0], {%1,%2,%3,%4};" :: "r"(a), "r"(r0), "r"(r1), "r"(r2), "r"(r3) : "memory"); }
__device__ __forceinline__ uint32_t movm(uint32_t a) {
  uint32_t d; asm volatile("movmatrix.sync.aligned.m8n8.trans.b16 %0, %1;" : "=r"(d) : "r"(a)); return d; }
__device__ __forceinline__ uint32_t pack2(float lo, float hi) {
  uint32_t r; asm("cvt.rn.bf16x2.f32 %0, %1, %2;" : "=r"(r) : "f"(hi), "f"(lo)); return r; }
__device__ __forceinline__ uint32_t pack2v(float lo, float hi) {
  uint32_t r; asm volatile("cvt.rn.bf16x2.f32 %0, %1, %2;" : "=r"(r) : "f"(hi), "f"(lo)); return r; }
__device__ __forceinline__ float bf_lo(uint32_t w) { return __uint_as_float(w << 16); }
__device__ __forceinline__ float bf_hi(uint32_t w) { return __uint_as_float(w & 0xffff0000u); }
__device__ __forceinline__ uint4 lds128(uint32_t a) {
  uint4 v; asm volatile("ld.shared.v4.b32 {%0,%1,%2,%3}, [%4];" : "=r"(v.x), "=r"(v.y), "=r"(v.z), "=r"(v.w) : "r"(a) : "memory"); return v; }
__device__ __forceinline__ float rcpf(float x) { float y; asm("rcp.approx.ftz.f32 %0, %1;" : "=f"(y) : "f"(x)); return y; }
__device__ __forceinline__ void sts64(uint32_t a, uint32_t x, uint32_t y) { asm volatile("st.shared.v2.b32 [%0], {%1,%2};" :: "r"(a), "r"(x), "r"(y) : "memory"); }
__device__ __forceinline__ float ex2(float x) { float y; asm("ex2.approx.ftz.f32 %0, %1;" : "=f"(y) : "f"(x)); return y; }
__device__ __forceinline__ uint32_t lds32(uint32_t a) {
  uint32_t v; asm volatile("ld.shared.b32 %0, [%1];" : "=r"(v) : "r"(a) : "memory"); return v; }
__device__ __forceinline__ uint2 lds64(uint32_t a) {
  uint2 v; asm volatile("ld.shared.v2.b32 {%0,%1}, [%2];" : "=r"(v.x), "=r"(v.y) : "r"(a) : "memory"); return v; }
__device__ __forceinline__ void sts128(uint32_t a, uint32_t x, uint32_t y, uint32_t z, uint32_t w) {
  asm volatile("st.shared.v4.b32 [%0], {%1,%2,%3,%4};" :: "r"(a), "r"(x), "r"(y), "r"(z), "r"(w) : "memory"); }
__device__ __forceinline__ void sts32(uint32_t a, uint32_t x) { asm volatile("st.shared.b32 [%0], %1;" :: "r"(a), "r"(x) : "memory"); }
__device__ __forceinline__ void tma2d(uint32_t dst, const CUtensorMap* tm, int c0, int c1, uint32_t mb) {
  asm volatile("cp.async.bulk.tensor.2d.shared::cluster.global.mbarrier::complete_tx::bytes [%0], [%1, {%3, %4}], [%2];"
               :: "r"(dst), "l"((uint64_t)tm), "r"(mb), "r"(c0), "r"(c1) : "memory"); }
__device__ __forceinline__ void tma2d_prefetch(const CUtensorMap* tm, int c0, int c1) {
  asm volatile("cp.async.bulk.prefetch.tensor.2d.L2.global.tile [%0, {%1, %2}];" :: "l"((uint64_t)tm), "r"(c0), "r"(c1) : "memory"); }
__device__ __forceinline__ void wg_fence() { asm volatile("wgmma.fence.sync.aligned;" ::: "memory"); }
__device__ __forceinline__ void wg_commit() { asm volatile("wgmma.commit_group.sync.aligned;" ::: "memory"); }
template <int N> __device__ __forceinline__ void wg_wait() { asm volatile("wgmma.wait_group.sync.aligned %0;" :: "n"(N) : "memory"); }

#define ACC4(d) "+f"(d[0]),"+f"(d[1]),"+f"(d[2]),"+f"(d[3])
#define ACC8(d) ACC4(d), ACC4((d + 4))
#define ACC16(d) ACC8(d), ACC8((d + 8))
#define ACC20(d) ACC16(d), ACC4((d + 16))
#define ACC24(d) ACC16(d), ACC8((d + 16))
#define SMEM0 0x400
__host__ __device__ constexpr uint32_t dlo(uint32_t off, uint32_t lbo) { return ((SMEM0 + off) >> 4) | ((lbo >> 4) << 16); }
__host__ __device__ constexpr uint32_t dhi(uint32_t sbo, uint32_t swz) { return (sbo >> 4) | (swz << 30); }
#define R4S "{%0,%1,%2,%3}"
#define R8S "{%0,%1,%2,%3,%4,%5,%6,%7}"
#define R16S "{%0,%1,%2,%3,%4,%5,%6,%7,%8,%9,%10,%11,%12,%13,%14,%15}"
#define R20S "{%0,%1,%2,%3,%4,%5,%6,%7,%8,%9,%10,%11,%12,%13,%14,%15,%16,%17,%18,%19}"
#define R24S "{%0,%1,%2,%3,%4,%5,%6,%7,%8,%9,%10,%11,%12,%13,%14,%15,%16,%17,%18,%19,%20,%21,%22,%23}"
#define ACC32(d) ACC16(d), ACC16((d + 16))
#define R32S "{%0,%1,%2,%3,%4,%5,%6,%7,%8,%9,%10,%11,%12,%13,%14,%15,%16,%17,%18,%19,%20,%21,%22,%23,%24,%25,%26,%27,%28,%29,%30,%31}"
struct Dsc {
  uint64_t b; uint32_t e;
  __device__ __forceinline__ Dsc operator+(uint32_t o) const { return {b + o, e}; }
};
template <int K> __device__ __forceinline__ uint32_t fresh(int i) {
  uint32_t e; asm volatile("{\n.reg .u32 t;\nadd.u32 t, %1, %2;\nshr.u32 %0, t, %3;\n}" : "=r"(e) : "r"(i), "n"((256 << K) + 1), "n"(8 + K)); return e; }
template <int N, bool H = false> struct MM;
#define DEF_MM(N, H, T, ACCM, RS_, I0, I1, I2, I3, I4, I5, I6, I7)                                                                \
  template <> struct MM<N, H> {                                                                                                   \
    template <uint32_t BLO, int ACC>                                                                                              \
    static __device__ __forceinline__ void rs(float* d, const uint32_t* a, Dsc b0) {                                              \
      asm volatile("{\n.reg .b64 b;\nmad.wide.u32 b, %" #I7 ", %" #I5 ", %" #I4 ";\n"                                             \
                   "wgmma.mma_async.sync.aligned.m64n" #N "k16.f32." T "." T " " RS_ ", {%" #I0 ",%" #I1 ",%" #I2 ",%" #I3 "}, b, %" #I6 ", 1, 1, 0;\n}" \
                   : ACCM(d) : "r"(a[0]), "r"(a[1]), "r"(a[2]), "r"(a[3]), "l"(b0.b), "n"(BLO), "n"(ACC), "r"(b0.e)); }           \
    template <uint32_t ALO, uint32_t BLO, int ACC, int TA = 1>                                                                    \
    static __device__ __forceinline__ void ss(float* d, Dsc a0, Dsc b0) {                                                         \
      asm volatile("{\n.reg .b64 a, b;\nmad.wide.u32 a, %" #I6 ", %" #I1 ", %" #I0 ";\nmad.wide.u32 b, %" #I6 ", %" #I3 ", %" #I2 ";\n" \
                   "wgmma.mma_async.sync.aligned.m64n" #N "k16.f32." T "." T " " RS_ ", a, b, %" #I4 ", 1, 1, %" #I5 ", 0;\n}"    \
                   : ACCM(d) : "l"(a0.b), "n"(ALO), "l"(b0.b), "n"(BLO), "n"(ACC), "n"(TA), "r"(b0.e)); }                         \
  };
DEF_MM(8, false, "bf16", ACC4, R4S, 4, 5, 6, 7, 8, 9, 10, 11)
DEF_MM(16, false, "bf16", ACC8, R8S, 8, 9, 10, 11, 12, 13, 14, 15)
DEF_MM(32, false, "bf16", ACC16, R16S, 16, 17, 18, 19, 20, 21, 22, 23)
DEF_MM(40, false, "bf16", ACC20, R20S, 20, 21, 22, 23, 24, 25, 26, 27)
DEF_MM(48, false, "bf16", ACC24, R24S, 24, 25, 26, 27, 28, 29, 30, 31)
DEF_MM(64, false, "bf16", ACC32, R32S, 32, 33, 34, 35, 36, 37, 38, 39)
DEF_MM(32, true, "f16", ACC16, R16S, 16, 17, 18, 19, 20, 21, 22, 23)
DEF_MM(64, true, "f16", ACC32, R32S, 32, 33, 34, 35, 36, 37, 38, 39)

#define LAG 10
#define NSTEP (NSEG + LAG)
#define NR (NSTEP + 2)
__device__ __align__(1024) __nv_bfloat16 g_xn[2][S_LEN * DM];
#define RO 16
static_assert(RO > LAG + 1, "ring");
__device__ __align__(1024) unsigned char g_o[RO * 96 * 8192];
__device__ __align__(1024) uint32_t g_part[6][7][40][64];
#define RD 16
static_assert(2 * RD <= NSEG && NR < 96, "the tags of the last lap differ from those of the first");
#define TILE_B 81920
__device__ __align__(1024) float2 g_stat[S_LEN];
__device__ __align__(1024) uint32_t g_st2[2][RD][64];
__device__ __align__(1024) unsigned char g_acc[4][RD][TILE_B];
#define NOP 19
#define NW12 5
#define NW34 12
#define NBC (NOP + NW12 + NW34)
__device__ __align__(1024) unsigned char g_wt[NOP * 10 * 12288];
__device__ __align__(1024) unsigned char g_wx[NW12 + NW34][16384];
enum { F_O = 0, F_R1 = NOP + 1, F_R2 = F_R1 + 4, F_R3 = F_R2 + 4, F_Z = F_R3 + 4, F_DONE, F_GOT, F_MISC, F_NUM };
__device__ __align__(128) uint32_t g_f[F_NUM][96];
__device__ __align__(128) int g_xready[129][8];
__device__ uint32_t g_tpc[128];
#define TS(i)
#define TSV(i, v)
#define TSN(i)
#define TSD(i, dep)
#define BTS(k, i)
#define BTS2(k, i)
#define RTS(i)
#define RTSD(i, dep)
#define RTS_OUT()
#define CTS(i)
#define PTS(i)
#define PTS1(i)
#define CTS_OUT()
#define GTS(i)

#define CL_SIZE 15
#define NCL 7
#define SSQ 13
#define SSV 16
#define PL_SZ 5376
#define TILE_SBO 2560
#define TILE_GRP 15360
#define WS_SZ ((2 * SSQ + SSV) * 2048)
#define OFF_QK (OFF_WO + 26 * 2048)
#define OFF_TILE 0
#define OFF_WS (4 * TILE_GRP)
#define OFF_WO (OFF_WS + WS_SZ)
#define OFF_PL (OFF_QK + 20480)
#define OFF_BAR (OFF_PL + 2 * PL_SZ)
#define STG_Q OFF_TILE
#define STG_K OFF_WO
#define VA 14
#define STG_V2 (OFF_TILE + 27 * 2048)
#define OFF_O (OFF_PL + 4352)
#define LAND(k) (((k) >> 1) * TILE_GRP + ((k) & 1) * 1280)
#define LAND_F (5 * TILE_SBO)
#define OFF_XL (OFF_TILE + 3 * TILE_GRP)
#define OFF_XF (OFF_XL + LAND_F)
#define OFF_WT ((OFF_XL + TILE_SBO + 1023) & ~1023)
#define OFF_TAB (OFF_BAR + 240)
#define OFF_INV (OFF_TAB + 64)
#define OFF_TS (OFF_INV + 128)
#define A_SMEM 232448
static_assert(WS_SZ + 72 * 1024 + 2 * PL_SZ + 4 * TILE_GRP + 512 == A_SMEM && OFF_WS % 1024 == 0 && OFF_WO % 1024 == 0 && SSQ == 13, "smem map");
enum { B_W0 = 0, B_W1, B_F1, B_F2 = B_F1 + 4, B_R1 = B_F2 + 4, B_R2, B_MEMFREE, B_LANDFREE, B_OPEER, B_PLFREE, B_XFREE, B_SB, B_WOF = B_SB + 6, B_WTF, B_RS, B_NUM = B_RS + 4 };
static_assert(B_NUM <= 30, "barriers");
enum { N_C = 0, N_SISS, N_QK, N_V, N_PM, N_TURN, N_PI, N_VGO, N_O, N_PX, N_AB, N_SDONE, N_VDONE, N_G3, N_P, N_OX };

__device__ __forceinline__ bool is_dual(int j) { return j >= LAG && j < NSEG; }
__device__ __forceinline__ int sched_l(int j) { return j < NSEG ? j : NSEG + j - LAG; }
__device__ __forceinline__ int sched_f(int j) { return NSEG + j - LAG; }
__device__ __forceinline__ void wait_cnt(const int* p, int target) {
  int v, n = 0;
  do {
    asm volatile("ld.relaxed.gpu.global.b32 %0, [%1];" : "=r"(v) : "l"(p) : "memory");
    if (v >= target) break;
    if (++n > SPIN_LIMIT) FAIL();
  } while (true);
  asm volatile("fence.acquire.gpu;" ::: "memory");
  asm volatile("fence.proxy.async.global;" ::: "memory");
}
__device__ __forceinline__ void red_release(void* p, uint32_t v) { asm volatile("red.release.gpu.global.add.u32 [%0], %1;" :: "l"(p), "r"(v) : "memory"); }
__device__ __forceinline__ void red_relaxed(void* p, uint32_t v) { asm volatile("red.relaxed.gpu.global.add.u32 [%0], %1;" :: "l"(p), "r"(v) : "memory"); }
#define VMASK 0xa5294a5294ull
__host__ __device__ constexpr int popc40(unsigned long long m) { int c = 0; for (; m; m &= m - 1) c++; return c; }
static_assert(popc40(VMASK) == SSV, "mask");
__host__ __device__ constexpr int ss_idx(int ks, int n) { return n == SSV ? popc40(VMASK & ((1ull << ks) - 1)) : ks * n / 40; }
__host__ __device__ constexpr bool is_ss(int ks, int n) { return ss_idx(ks + 1, n) != ss_idx(ks, n); }
__host__ __device__ constexpr int rs_idx(int ks, int n) { return ks - ss_idx(ks, n); }

#define SL2 (0.07216878364870322f * 1.4426950408889634f)

struct Desc { Dsc tile, unit, k1, pl, p; };
__device__ __forceinline__ Desc make_desc(const uint64_t* h, uint32_t u, uint32_t e) {
  return {{h[0], e}, {h[1] + u * 128, e}, {h[2], e}, {h[3], e}, {h[4], e}};
}
template <int N, int NSS, int RG, int KS, int K1, int K0 = 0>
__device__ __forceinline__ void proj(float* acc, const uint32_t* W, const Desc& D) {
  if constexpr (KS < K1) {
    constexpr uint32_t BLO = dlo(OFF_TILE + (KS / 10) * TILE_GRP + RG * TILE_SBO + (KS % 10) * 256, 128);
    if constexpr (is_ss(KS, NSS)) MM<N>::template ss<dlo(OFF_WS + ss_idx(KS, NSS) * 2048, 0), BLO, (KS != K0)>(acc, D.unit, D.tile);
    else MM<N>::template rs<BLO, (KS != K0)>(acc, W + rs_idx(KS, NSS) * 4, D.tile);
    proj<N, NSS, RG, KS + 1, K1, K0>(acc, W, D);
  }
}
#define VST 17
template <int KS>
__device__ __forceinline__ void ld_rest(uint32_t* W, const uint32_t* p) {
  if constexpr (KS < 40) {
    if constexpr (!is_ss(KS, SSV) && rs_idx(KS, SSV) >= VST) {
#pragma unroll
      for (int i = 0; i < 4; i++) W[4 * rs_idx(KS, SSV) + i] = __ldg(p + (KS * 16 + (i >> 1) * 8) * (HD / 2) + (i & 1) * 4);
    }
    ld_rest<KS + 1>(W, p);
  }
}
template <int N>
__device__ __forceinline__ void load_w(uint32_t* W, uint32_t stage, int warp, int lane) {
  const int kr = (lane >> 4) * 8 + (lane & 7);
  const int cb = warp * 2 + ((lane >> 3) & 1);
  const uint32_t a0 = stage + kr * 128 + ((cb ^ (lane & 7)) << 4);
#pragma unroll
  for (int i = 0; i < N; i++) ldsm4t(W[4 * i], W[4 * i + 1], W[4 * i + 2], W[4 * i + 3], a0 + i * 2048);
}
template <int N, int G, int U, int OS, int ACC>
__device__ __forceinline__ void wo4(float* d, const Desc& D) {
  constexpr uint32_t WA = (U >= 4 ? OFF_WO + (U - 4) * 2048 : OFF_WT) - G * SSQ * 2048, OB = OS == 0 ? OFF_O : OS == 1 ? OFF_XL : OFF_XF;
  Dsc b = OS ? D.k1 : D.pl;
  b.e = fresh<(U < 16 ? U / 4 : U / 8 - 2) + (N == 8 ? 4 : 0)>(D.unit.e);
  MM<N>::template ss<dlo(WA, 0), dlo(OB, 128), ACC>(d, D.unit, b);
  MM<N>::template ss<dlo(WA + 2048, 0), dlo(OB + 256, 128), 1>(d, D.unit, b);
  MM<N>::template ss<dlo(WA + 4096, 0), dlo(OB + 512, 128), 1>(d, D.unit, b);
  MM<N>::template ss<dlo(WA + 6144, 0), dlo(OB + 768, 128), 1>(d, D.unit, b);
}
__device__ __forceinline__ void wo_coord(int i, int t3, int head, int& c0, int& c1) {
  const int g = i >> 1;
  const int blk = g == 0 ? 9 : (g < 4 ? g - 1 : (g - 4) >> 1) * 3 + t3;
  int sl = g < 4 ? t3 : (g & 1) ? t3 + 1 : t3 + 2;
  if (sl >= 3) sl -= 3;
  c0 = blk * 64; c1 = head * DH + sl * 64 + (i & 1) * 32;
}
__device__ __forceinline__ void tok_softmax(uint32_t sb, int job, int lane) {
  const bool w1 = job & 1;
  const int dg = (lane >> 2) - (lane & 3) * 2;
  const uint32_t lo = sb + OFF_PL + (job >> 1) * PL_SZ + (job & 1) * 1792, l8 = lo + 512 + lane * 8, pa = lo + lane * 4;
  const uint32_t km = job & 2 ? 640 : 512;
  float x[14];
  {
    const uint4 a = lds128(lo + lane * 16);
    const uint2 e = lds64(l8);
    const uint32_t c = lds32(768 + pa);
    x[0] = bf_lo(a.x); x[1] = bf_hi(a.x); x[2] = bf_lo(a.y); x[3] = bf_hi(a.y); x[4] = bf_lo(a.z); x[5] = bf_hi(a.z); x[6] = bf_lo(a.w); x[7] = bf_hi(a.w);
    x[8] = bf_lo(c); x[9] = bf_hi(c); x[10] = bf_lo(e.x); x[11] = bf_hi(e.x); x[12] = bf_lo(e.y); x[13] = bf_hi(e.y);
  }
  if (dg < 0) { x[8] = -INFINITY; if (w1) x[4] = -INFINITY; else x[10] = -INFINITY; }
  if (dg < 1) { x[9] = -INFINITY; if (w1) x[5] = -INFINITY; else x[11] = -INFINITY; }
  const float m4 = fmaxf(x[8], x[9]);
  float m0 = fmaxf(fmaxf(fmaxf(x[0], x[1]), fmaxf(x[2], x[3])), fmaxf(fmaxf(x[4], x[5]), fmaxf(x[6], x[7])));
  float m1 = fmaxf(fmaxf(x[10], x[11]), fmaxf(x[12], x[13]));
  if (w1) m1 = fmaxf(m1, m4); else m0 = fmaxf(m0, m4);
  m0 = fmaxf(m0, __shfl_xor_sync(~0u, m0, 1)); m1 = fmaxf(m1, __shfl_xor_sync(~0u, m1, 1));
  sts32(pa + (w1 ? 384 : 896 + 128), 0u); sts32(pa + 1152 - km, 0u); sts32(pa + 896 + 1152 - km, 0u); sts64(l8 + 896 - 256, 0u, 0u);
  m0 = fmaxf(m0, __shfl_xor_sync(~0u, m0, 2)); m1 = fmaxf(m1, __shfl_xor_sync(~0u, m1, 2));
  m0 *= -SL2; m1 *= -SL2;
#pragma unroll
  for (int j = 0; j < 14; j++) x[j] = ex2(fmaf(x[j], SL2, j < 8 ? m0 : j >= 10 ? m1 : w1 ? m1 : m0));
  const float l4s = x[8] + x[9];
  float l0 = ((x[0] + x[1]) + (x[2] + x[3])) + ((x[4] + x[5]) + (x[6] + x[7])), l1 = (x[10] + x[11]) + (x[12] + x[13]);
  if (w1) l1 += l4s; else l0 += l4s;
  l0 += __shfl_xor_sync(~0u, l0, 1); l1 += __shfl_xor_sync(~0u, l1, 1);
  l0 += __shfl_xor_sync(~0u, l0, 2); l1 += __shfl_xor_sync(~0u, l1, 2);
  l0 = rcpf(l0); l1 = rcpf(l1);
#pragma unroll
  for (int j = 0; j < 7; j++) {
    const float iv = j < 4 ? l0 : j > 4 ? l1 : w1 ? l1 : l0;
    sts32(pa + (j < 3 ? j * 128 : j == 3 ? km : j == 4 ? (w1 ? 896 + 128 : 384) : j == 5 ? 896 : 896 + km), pack2(x[2 * j] * iv, x[2 * j + 1] * iv));
  }
}
template <int N>
__device__ __forceinline__ void wo_phase(uint32_t sb, int wg, int warp, int lane, uint32_t par, uint32_t r1, const Desc& D) {
  const uint32_t bar = sb + OFF_BAR;
  float x[N / 2], y[N / 2];
  const uint2 ta = lds64(sb + OFF_TAB + (wg * 4 + warp) * 8);
  uint32_t xa = (ta.x & ~255u) + lane * 8, xb = (ta.x & 0xFF0000FFu) + SMEM0 + OFF_BAR, ya = (ta.y & ~255u) + lane * 8, yb = (ta.y & 0xFF0000FFu) + SMEM0 + OFF_BAR;
  asm volatile("" : "+r"(xa), "+r"(xb), "+r"(ya), "+r"(yb));
  auto scat = [&](uint32_t ad, uint32_t mb, const float* d) {
    st_async_v2(ad, pack2(d[0], d[1]), pack2(d[2], d[3]), mb);
    if (N == 16) st_async_v2(ad + LAND_F, pack2(d[4], d[5]), pack2(d[6], d[7]), mb);
  };
  if (wg == 0) {
    bar_sync(N_O, 384);
    wg_fence(); wo4<N, 0, 4, 0, 0>(x, D); wo4<N, 0, 8, 0, 0>(y, D); wg_commit();
    mbar_waitu(bar + 8 * B_OPEER, par);
    CFENCE(); wg_fence(); wo4<N, 0, 16, 1, 1>(x, D); wo4<N, 0, 20, 2, 1>(x, D); wg_commit();
    wo4<N, 0, 24, 1, 1>(y, D); wg_commit();
    mbar_waitu2(bar + 8 * B_WOF, bar + 8 * B_MEMFREE, par);
    wg_fence(); wo4<N, 0, 28, 2, 1>(y, D); wg_commit();
    bar_arrive(N_AB, 256);
    wg_wait<2>(); scat(xa, xb, x);
    wg_wait<0>(); scat(ya, yb, y);
  } else {
    bar_sync(N_O, 384);
    wg_fence(); wo4<N, 1, 0, 0, 0>(x, D); wg_commit(); wo4<N, 1, 12, 0, 0>(y, D); wg_commit();
    wg_wait<1>(); mbar_arrive_remote_if(lane == 0, r1);
    mbar_waitu(bar + 8 * B_MEMFREE, par);
    scat(xa, xb, x);
    bar_sync(N_AB, 256);
    CFENCE(); wg_fence(); wo4<N, 1, 32, 1, 1>(y, D); wo4<N, 1, 36, 2, 1>(y, D); wg_commit();
    bar_arrive(N_TURN, 256);
    wg_wait<0>(); scat(ya, yb, y);
  }
}
#define DS_DUAL 10
#define DS_SINGLE 20
#define POLL_GAP 100
#define POLL_GAPD 0
#define TOK_DELAY 250
#define UMAX 40
#define VD1 10
#define VS2 20
#define VS1 4
struct AMaps { CUtensorMap w16[3], wo32; uint64_t d[5]; const __nv_bfloat16* wv; };
__global__ void __launch_bounds__(512, 1)
acore_kernel(const __grid_constant__ AMaps M, const __nv_bfloat16* __restrict__ mem0, int sync_b) {
  extern __shared__ __align__(1024) unsigned char smem_raw[];
  const uint32_t sb = smem_u32(smem_raw);
  GTS(24);
  if (threadIdx.x == 480) {
    uint32_t smid; asm volatile("mov.u32 %0, %%smid;" : "=r"(smid));
    g_tpc[(smid >> 1) & 127] = blockIdx.x - CL_SIZE < 3 * CL_SIZE && blockIdx.x % CL_SIZE >= 12 ? 1 : 2;
    asm volatile("griddepcontrol.launch_dependents;");
  }
  const int lane0 = threadIdx.x & 31;
#define LANE_INIT() int lane; asm volatile("mov.u32 %0, %%laneid;" : "=r"(lane))
  const int warp = __shfl_sync(~0u, (threadIdx.x >> 5) & 3, 0);
  const int cl = blockIdx.x / CL_SIZE;
  const uint32_t rank = blockIdx.x - cl * CL_SIZE;
  const int nh = cl >= 1 && cl <= 3 ? 4 : 5;
  const int nA = 3 * nh;
  const int wg = __shfl_sync(~0u, (int)rank < nA ? threadIdx.x >> 7 : 4, 0);
  const int head = (cl < 4 ? (cl ? 1 + 4 * cl : 0) : 5 * cl - 3) + rank / 3;
  const int t3 = rank % 3;
  const int col0 = head * DH + t3 * 64;
  const uint32_t bar = sb + OFF_BAR;
  const uint32_t rb0 = SMEM0;
  const uint16_t mcmask = (uint16_t)((1u << nA) - 1);
  const uint32_t nxt = sb + ((t3 == 2 ? -2 : 1) << 24), prv = sb + ((t3 == 0 ? 2 : -1) << 24);
  const int ig = (int)rank - (nA - 4);

  if (threadIdx.x == 0) {
    if (mapa(sb, nA - 1) != rb0 + ((nA - 1) << 24) || mapa(sb, 0) != rb0 || mapa(sb, 1) != rb0 + (1u << 24) || sb != SMEM0 + (rank << 24)) FAIL();
    for (int i = 0; i < B_NUM; i++)
      mbar_init(bar + 8 * i, i == B_R1 ? 4 * nA : i == B_R2 ? 12 * nA : i == B_MEMFREE ? nA : i == B_LANDFREE ? 4 * nA : i == B_PLFREE || i == B_XFREE ? 2 : 1);
    asm volatile("fence.mbarrier_init.release.cluster;" ::: "memory");
    mbar_expect(bar + 8 * B_W0, (80 + SSV + VST) * 2048);
  }
  __syncthreads();
  if (lane0 == 0) {
    const int w12 = wg * 4 + warp;
    if (w12 < 10) {
#pragma unroll 1
      for (int ks = 4 * w12; ks < 4 * w12 + 4; ks++) {
        const bool ss = is_ss(ks, SSQ);
        tma2d(ss ? sb + OFF_WS + ss_idx(ks, SSQ) * 2048 : sb + STG_Q + rs_idx(ks, SSQ) * 2048, &M.w16[0], col0, ks * 16, bar + 8 * B_W0);
        tma2d(ss ? sb + OFF_WS + (SSQ + ss_idx(ks, SSQ)) * 2048 : sb + STG_K + rs_idx(ks, SSQ) * 2048, &M.w16[1], col0, ks * 16, bar + 8 * B_W0);
        if (is_ss(ks, SSV)) tma2d(sb + OFF_WS + (2 * SSQ + ss_idx(ks, SSV)) * 2048, &M.w16[2], col0, ks * 16, bar + 8 * B_W0);
        else if (rs_idx(ks, SSV) < VST) tma2d(sb + (rs_idx(ks, SSV) < VA ? STG_K + 27 * 2048 : STG_V2 - VA * 2048) + rs_idx(ks, SSV) * 2048, &M.w16[2], col0, ks * 16, bar + 8 * B_W0);
      }
    }
  }
  if (lane0 < 2 && wg < 2) {
    const int u = 4 * (wg ? (lane0 ? 6 + t3 : 9) : (lane0 ? 3 + t3 : t3)) + warp;
    const int li = (u >= nA) + (u >= 2 * nA) + (u >= 3 * nA);
    sts32(sb + OFF_TAB + (wg * 4 + warp) * 8 + lane0 * 4,
          rb0 + ((u - li * nA) << 24) + OFF_TILE + LAND(li + (u >= 36 ? t3 : 0)) + (rank / 3) * 256 + 8 * (B_RS + li));
  }
  __syncthreads();
  GTS(25);

  auto issue_tok = [&](int sc, int fb, int rel = -1, uint32_t ph = 0) {
    if (sync_b) wait_cnt(&g_xready[sc][0], 32);
    if (rel >= 0) mbar_waitu(bar + 8 * rel, ph);
    bulk_g2s_mc_e(sb + OFF_TILE + ig * TILE_GRP + TILE_SBO, &g_xn[0][0] + uni(sc * (32 * DM)) + ig * 5120, 10240, bar + 8 * (fb + ig), mcmask);
  };
#define POLL(d, q) _Pragma("unroll") for (int k = 0; k < NCL; k++) \
      asm volatile("ld.relaxed.gpu.global.v2.b32 {%0,%1}, [%2];" : "=r"(d[k].x), "=r"(d[k].y) : "l"(q + k * 2560) : "memory")
#define L3(L, a, b, c) lop3<L>(a, b, c)
#define TAGS(L, d) L3(L, L3(L, L3(L, d[0].x, d[0].y, d[1].x), L3(L, d[1].y, d[2].x, d[2].y), L3(L, d[3].x, d[3].y, d[4].x)), L3(L, d[4].y, d[5].x, d[5].y), L3(L, d[6].x, d[6].y, d[6].y))
    auto deliver = [&](uint2* pa, const uint32_t* gq, int u, int c, int dc, int ds, int step, bool first, int lane) {
      const uint32_t off = uni(OFF_TILE + ((u * 205) >> 11) * (TILE_GRP - TILE_SBO) + u * 256 + dc * LAND_F), boff = uni(OFF_BAR + 8 * (B_F1 + ((u * 205) >> 11)));
      const uint32_t* mi = &g_part[4][0][0][0] + uni((c * NCL + cl) * 2560 + u * 64);
      mbar_waitu(bar + 8 * B_LANDFREE, step & 1);
      int n = 0;
      while (true) {
        const bool ok = __all_sync(~0u, ((step & 2 ? ~TAGS(0xFE, pa) : TAGS(0x80, pa)) & 1) != 0);
        if (ok) break;
        if (++n > SPIN_LIMIT) FAIL();
        POLL(pa, gq);
      }
      if (warp == 0 && first) { TS(19); TSV(10, n); }
      const uint32_t w0 = hadd2bf(hadd2bf(hadd2bf(pa[0].x, pa[1].x), hadd2bf(pa[2].x, pa[3].x)), hadd2bf(hadd2bf(pa[4].x, pa[5].x), pa[6].x));
      const uint32_t w1 = hadd2bf(hadd2bf(hadd2bf(pa[0].y, pa[1].y), hadd2bf(pa[2].y, pa[3].y)), hadd2bf(hadd2bf(pa[4].y, pa[5].y), pa[6].y));
      if (u < ds) {
        const uint32_t da = SMEM0 + off + lane * 8, db = SMEM0 + boff;
#pragma unroll
        for (int d = 0; d < 12; d++) st_async_v2((d << 24) + da, w0, w1, (d << 24) + db);
#pragma unroll
        for (int d = 12; d < 15; d++) st_async_v2_if(nA == 15, (d << 24) + da, w0, w1, (d << 24) + db);
      } else {
        *reinterpret_cast<uint2*>(const_cast<uint32_t*>(gq) + ((4 - 2 * (step & 1)) * NCL + cl) * 2560) = make_uint2(w0, w1);
        asm volatile("fence.proxy.async.global;" ::: "memory");
        __syncwarp();
        bulk_g2s_mc_e(sb + off, mi, 256, sb + boff, mcmask);
      }
    };
#define REL(b, g) mbar_arrive_remote_if(lane == 0, rb0 + ((nA - 4 + (g)) << 24) + OFF_BAR + 8 * (b))

  if (wg < 2) {
    asm volatile("setmaxnreg.inc.sync.aligned.u32 160;");
    LANE_INIT();
    uint32_t W[4 * (40 - SSQ)];
    mbar_waitw(bar + 8 * B_W0, 0);
    GTS(26);
    load_w<40 - SSQ>(W, sb + (wg ? STG_K : STG_Q), warp, lane);
    fence_async();
    bar_sync(1, 384);
    cluster_sync_all();
#define DESC(k) const Desc D = make_desc(M.d, min(wg, 2) * SSQ, fresh<k>(step))
    GTS(27);
#pragma unroll 1
    for (int step = -1; step < NSTEP; step++) {
      const uint32_t par = step & 1;
      asm volatile("" : "+r"(lane));
      const bool dual = is_dual(step), has_next = step + 1 < NSTEP;
#define QK_SA (sb + OFF_QK + wg * 15360 + (2 * warp + ((lane >> 3) & 1)) * 128 + (lane & 7) * 16)
#define QK_F (wg ? -5120 : 5120)
#define QK_S12 ((wg ? (lane >> 4) : 1 + 2 * (lane >> 4)) * 1024)
#define QK_S34 ((wg ? 2 + (lane >> 4) : 2 - 2 * (lane >> 4)) * 1024)
      if (step >= 0) {
        if (dual) {
          DESC(0);
          float acc[24];
          mbar_waitu(bar + 8 * (B_F1 + 0), par);
          if (wg + warp == 0) { TS(0); TSN(1); }
          CFENCE(); wg_fence(); proj<48, SSQ, 0, 0, 10>(acc, W, D); wg_commit();
          mbar_waitu(bar + 8 * (B_F1 + 1), par);
          CFENCE(); wg_fence(); proj<48, SSQ, 0, 10, 20>(acc, W, D); wg_commit();
          mbar_waitu(bar + 8 * (B_F1 + 2), par);
          CFENCE(); wg_fence(); proj<48, SSQ, 0, 20, 30>(acc, W, D); wg_commit();
          mbar_waitu(bar + 8 * (B_F1 + 3), par);
          if (wg + warp == 0) TS(2);
          CFENCE(); wg_fence(); proj<48, SSQ, 0, 30, 40>(acc, W, D); wg_commit();
          bar_arrive(N_VGO, 384);
          mbar_waitu(bar + 8 * B_PLFREE, par);
          const uint32_t sa = QK_SA, s0 = sa + 4096 + (lane >> 4) * QK_F, s1 = sa + QK_F + QK_S12, s2 = sa + QK_F + QK_S34;
          wg_wait<0>();
          if (wg + warp == 0) TS(3);
          stsm4t(s0, pack2(acc[0], acc[1]), pack2(acc[2], acc[3]), pack2(acc[20], acc[21]), pack2(acc[22], acc[23]));
          stsm4t(s1, pack2(acc[4], acc[5]), pack2(acc[6], acc[7]), pack2(acc[8], acc[9]), pack2(acc[10], acc[11]));
          stsm4t(s2, pack2(acc[12], acc[13]), pack2(acc[14], acc[15]), pack2(acc[16], acc[17]), pack2(acc[18], acc[19]));
        } else {
          DESC(1);
          float acc[4];
          mbar_waitu(bar + 8 * (B_F1 + 0), par);
          if (wg + warp == 0) { TS(0); TSN(1); }
          CFENCE(); wg_fence(); proj<8, SSQ, 0, 0, 10>(acc, W, D); wg_commit();
          mbar_waitu(bar + 8 * (B_F1 + 1), par);
          CFENCE(); wg_fence(); proj<8, SSQ, 0, 10, 20>(acc, W, D); wg_commit();
          mbar_waitu(bar + 8 * (B_F1 + 2), par);
          CFENCE(); wg_fence(); proj<8, SSQ, 0, 20, 30>(acc, W, D); wg_commit();
          mbar_waitu(bar + 8 * (B_F1 + 3), par);
          if (wg + warp == 0) TS(2);
          CFENCE(); wg_fence(); proj<8, SSQ, 0, 30, 40>(acc, W, D); wg_commit();
          bar_arrive(N_VGO, 384);
          mbar_waitu(bar + 8 * B_PLFREE, par);
          const uint32_t s0 = QK_SA + 4096;
          wg_wait<0>();
          if (wg + warp == 0) TS(3);
          stsm2t(s0, pack2(acc[0], acc[1]), pack2(acc[2], acc[3]));
        }
        fence_async();
        bar_sync(N_QK, 256);
        if (wg == 0 || dual) {
          float s[20];
          DESC(2);
          const Dsc ab = D.k1 + wg * 192, bb = D.k1 + (1 - wg) * 320;
          wg_fence();
          MM<40>::ss<dlo(OFF_QK, 128), dlo(OFF_QK + 10240, 128), 0, 0>(s, ab, bb);
          MM<40>::ss<dlo(OFF_QK + 256, 128), dlo(OFF_QK + 10240 + 256, 128), 1, 0>(s, ab, bb);
          MM<40>::ss<dlo(OFF_QK + 512, 128), dlo(OFF_QK + 10240 + 512, 128), 1, 0>(s, ab, bb);
          MM<40>::ss<dlo(OFF_QK + 768, 128), dlo(OFF_QK + 10240 + 768, 128), 1, 0>(s, ab, bb);
          wg_commit();
          bar_arrive(N_SISS, 384);
          const int rw = (warp - wg) & 3;
          const uint32_t bo = OFF_BAR + 8 * (B_SB + 3 * wg + rw), lo = OFF_PL + wg * PL_SZ + rw * 1792;
          const uint32_t km = wg ? 640 : 512;
          uint32_t l16 = lo + lane * 16, l4 = lo + lane * 4;
          mbar_expect_if(lane == 0 && rw < 3, sb + bo, rw < 2 ? 1792 : 1280);
          asm volatile("" : "+r"(l16), "+r"(l4));
          if (rw == 2) {
            wg_wait<0>();
            if (wg == 0) TSD(4, __float_as_uint(s[0]));
            const uint32_t w0 = pack2(s[0], s[1]), w1 = pack2(s[4], s[5]), w2 = pack2(s[8], s[9]), w3 = pack2(s[12], s[13]), w4 = pack2(s[16], s[17]);
            {
              st_async_v4(nxt + 896 + l16, w0, w1, w2, w3, nxt + bo);
              st_async_v4(prv + l16, w0, w1, w2, w3, prv + bo);
              st_async_b32(nxt + 896 + 768 + l4, w4, nxt + bo);
              st_async_b32(prv + 768 + l4, w4, prv + bo);
            }
            bar_arrive(N_SDONE, 256);
            mbar_waitu(sb + bo, (step - wg * LAG) & 1);
            if (wg == 0) TS(5);
            float x[10], m0;
            {
              const uint4 a = lds128(sb + l16), b = lds128(sb + 896 + l16);
              const uint32_t c = lds32(sb + 768 + l4), d = lds32(sb + 896 + 768 + l4);
              const uint32_t e0 = hadd2bf(hadd2bf(a.x, b.x), w0), e1 = hadd2bf(hadd2bf(a.y, b.y), w1), e2 = hadd2bf(hadd2bf(a.z, b.z), w2),
                             e3 = hadd2bf(hadd2bf(a.w, b.w), w3), e4 = hadd2bf(hadd2bf(c, d), w4);
              const uint32_t em = hmax2bf(hmax2bf(hmax2bf(e0, e1), hmax2bf(e2, e3)), e4);
              m0 = fmaxf(bf_lo(em), bf_hi(em));
              x[0] = bf_lo(e0); x[1] = bf_hi(e0); x[2] = bf_lo(e1); x[3] = bf_hi(e1); x[4] = bf_lo(e2);
              x[5] = bf_hi(e2); x[6] = bf_lo(e3); x[7] = bf_hi(e3); x[8] = bf_lo(e4); x[9] = bf_hi(e4);
            }
            m0 = fmaxf(m0, __shfl_xor_sync(~0u, m0, 1));
            sts32(sb + l4 + 1152 - km, 0u);
            m0 = fmaxf(m0, __shfl_xor_sync(~0u, m0, 2));
            m0 *= -SL2;
#pragma unroll
            for (int j = 0; j < 5; j++) {
              x[2 * j] = ex2(fmaf(x[2 * j], SL2, m0)); x[2 * j + 1] = ex2(fmaf(x[2 * j + 1], SL2, m0));
              sts32(sb + l4 + (j < 4 ? j * 128 : km), pack2(x[2 * j], x[2 * j + 1]));
            }
            float l = ((x[0] + x[1]) + (x[2] + x[3])) + ((x[4] + x[5]) + ((x[6] + x[7]) + (x[8] + x[9])));
            l += __shfl_xor_sync(~0u, l, 1);
            fence_async();
            sts32(sb + OFF_INV + wg * 64 + (lane >> 1) * 4, __float_as_uint(l));
            bar_arrive(N_PM, dual ? 224 : 192);
            if (wg == 0) TS(6);
          } else if (rw < 2) {
            const bool w1 = rw == 1;
            const uint32_t l8 = lo + 512 + lane * 8;
            uint32_t tw[7];
            wg_wait<0>();
            bar_arrive(N_SDONE, 256);
            tw[0] = pack2(s[0], s[1]); tw[1] = pack2(s[4], s[5]); tw[2] = pack2(s[8], s[9]); tw[3] = pack2(s[16], s[17]);
            tw[4] = w1 ? pack2(s[6], s[7]) : pack2(s[12], s[13]); tw[5] = pack2(s[2], s[3]); tw[6] = pack2(s[18], s[19]);
            { const uint32_t t0 = clock32(); while (clock32() - t0 < TOK_DELAY) {} }
            st_async_v4(nxt + 896 + l16, tw[0], tw[1], tw[2], tw[3], nxt + bo);
            st_async_v4(prv + l16, tw[0], tw[1], tw[2], tw[3], prv + bo);
            st_async_v2(nxt + 896 + l8, tw[5], tw[6], nxt + bo);
            st_async_v2(prv + l8, tw[5], tw[6], prv + bo);
            st_async_b32(nxt + 896 + 768 + l4, tw[4], nxt + bo);
            st_async_b32(prv + 768 + l4, tw[4], prv + bo);
            mbar_waitu(sb + bo, (step - wg * LAG) & 1);
            const uint4 a = lds128(sb + l16), b = lds128(sb + 896 + l16);
            const uint2 e = lds64(sb + l8), f = lds64(sb + 896 + l8);
            const uint32_t c = lds32(sb + 768 + l4), d = lds32(sb + 896 + 768 + l4);
            sts128(sb + l16, hadd2bf(hadd2bf(a.x, b.x), tw[0]), hadd2bf(hadd2bf(a.y, b.y), tw[1]), hadd2bf(hadd2bf(a.z, b.z), tw[2]), hadd2bf(hadd2bf(a.w, b.w), tw[3]));
            sts64(sb + l8, hadd2bf(hadd2bf(e.x, f.x), tw[5]), hadd2bf(hadd2bf(e.y, f.y), tw[6]));
            sts32(sb + 768 + l4, hadd2bf(hadd2bf(c, d), tw[4]));
            bar_arrive(N_PX, dual ? 256 : 192);
            if (wg + warp == 0) TS(9);
          } else {
            wg_wait<0>();
            if (wg == 0) {
              mbar_expect_if(lane < 3 && has_next, bar + 8 * (lane == 2 ? B_OPEER : B_WOF + lane), lane == 2 ? (dual ? 4096 : 2048) : lane ? 8192 : 20480);
              auto fetch = [&](int i, int n, uint32_t dst, int mb) {
                int c0, c1; wo_coord(i, t3, head, c0, c1);
                tma2d_e(dst, &M.wo32, c0, c1, bar + 8 * mb); if (n == 2) tma2d_e(dst + 4096, &M.wo32, c0, c1 + 32, bar + 8 * mb);
              };
              bar_sync(N_G3, 160);
              if (has_next) {
                fetch(0, 2, sb + OFF_WT, B_WTF);
                mbar_arrive_remote_if(lane < 2, (lane ? nxt : prv) + OFF_BAR + 8 * B_XFREE);
              }
              bar_sync(N_SDONE, 256);
              if (has_next) {
                fetch(15, 1, sb + OFF_QK, B_WOF); fetch(16, 2, sb + OFF_QK + 4096, B_WOF); fetch(18, 2, sb + OFF_QK + 12288, B_WOF);
                mbar_waitu(bar + 8 * B_XFREE, par);
              }
              bar_arrive(N_PM, dual ? 224 : 192);
              bar_sync(N_VDONE, 160);
              mbar_arrive_remote_if(lane < nA && has_next, rb0 + (lane << 24) + OFF_BAR + 8 * B_MEMFREE);
              if (has_next) mbar_waitu(bar + 8 * B_WTF, par);
            } else {
              bar_arrive(N_SDONE, 256);
              if ((unsigned)ig < 3) issue_tok(sched_l(step + 1), B_F2, B_R1, (step - LAG) & 1);
            }
          }
        } else {
          bar_arrive(N_SISS, 384);
          bar_arrive(N_SDONE, 256);
        }
        if (has_next) {
          if (step == 0) mbar_waitw(bar + 8 * B_W1, 0);
          const uint32_t r1 = rb0 + ((nA - 1) << 24) + OFF_BAR + 8 * B_R1;
          if (dual) { DESC(3); wo_phase<16>(sb, wg, warp, lane, par, r1, D); } else { DESC(4); wo_phase<8>(sb, wg, warp, lane, par, r1, D); }
          bar_arrive(N_C, 288);
          if (warp == 0) TS(7 + wg);
        }
      }
      if (has_next) {
        DESC(5);
        float acc[16];
        mbar_waitu(bar + 8 * B_F2, par ^ 1);
        wg_fence(); proj<32, SSQ, 1, 0, 10>(acc, W, D); wg_commit();
        mbar_waitu(bar + 8 * (B_F2 + 1), par ^ 1);
        wg_fence(); proj<32, SSQ, 1, 10, 14>(acc, W, D); wg_commit();
        wg_wait<1>(); REL(B_R2, 0);
        wg_fence(); proj<32, SSQ, 1, 14, 20>(acc, W, D); wg_commit();
        mbar_waitu(bar + 8 * (B_F2 + 2), par ^ 1);
        wg_fence(); proj<32, SSQ, 1, 20, 24>(acc, W, D); wg_commit();
        wg_wait<1>(); REL(B_R2, 1);
        wg_fence(); proj<32, SSQ, 1, 24, 30>(acc, W, D); wg_commit();
        mbar_waitu(bar + 8 * (B_F2 + 3), par ^ 1);
        wg_fence(); proj<32, SSQ, 1, 30, 34>(acc, W, D); wg_commit();
        wg_wait<1>(); REL(B_R2, 2);
        wg_fence(); proj<32, SSQ, 1, 34, 40>(acc, W, D); wg_commit();
        const uint32_t sa = QK_SA, s1 = sa + QK_S12, s2 = sa + QK_S34;
        wg_wait<0>(); REL(B_R2, 3);
        if (warp == 0) TS(11 + wg);
        stsm4t(s1, pack2(acc[0], acc[1]), pack2(acc[2], acc[3]), pack2(acc[4], acc[5]), pack2(acc[6], acc[7]));
        stsm4t(s2, pack2(acc[8], acc[9]), pack2(acc[10], acc[11]), pack2(acc[12], acc[13]), pack2(acc[14], acc[15]));
      }
    }
    GTS(28);
    cluster_sync_all();
  } else if (wg == 2) {
    asm volatile("setmaxnreg.inc.sync.aligned.u32 160;");
    LANE_INIT();
    uint32_t W[4 * (40 - SSV)];
    ld_rest<0>(W, reinterpret_cast<const uint32_t*>(M.wv + (lane >> 2) * HD + col0 + warp * 16) + (lane & 3));
    uint4 m0[5];
#pragma unroll
    for (int i = 0; i < 5; i++) {
      const int t = i * 128 + warp * 32 + lane;
      m0[i] = __ldg(reinterpret_cast<const uint4*>(mem0 + ((t >> 1) & 7) * DM + (t >> 4) * 16 + ((t ^ (t >> 3)) & 1) * 8));
    }
    mbar_waitw(bar + 8 * B_W0, 0);
    load_w<VA>(W, sb + STG_K + 27 * 2048, warp, lane);
    load_w<VST - VA>(W + 4 * VA, sb + STG_V2, warp, lane);
    fence_async();
    mbar_expect_if(warp + lane == 0, bar + 8 * B_W1, 26 * 2048);
    bar_sync(1, 384);
#pragma unroll
    for (int i = 0; i < 5; i++) {
      const int t = i * 128 + warp * 32 + lane;
      sts128(sb + OFF_TILE + (t / 160) * (TILE_GRP - TILE_SBO) + t * 16, m0[i].x, m0[i].y, m0[i].z, m0[i].w);
    }
#pragma unroll
    for (int i = 4 * VST; i < 4 * (40 - SSV); i++) W[i] = movm(W[i]);
    fence_async();
    mbar_arrive_if(lane == 0, bar + 8 * (B_F1 + warp));
    mbar_expect_if(lane == 0, bar + 8 * (B_F2 + warp), 10240);
    mbar_arrive_if(warp == 3 && lane < 2, bar + 8 * B_PLFREE);
    cluster_sync_all();
    uint32_t vl[8];
    {
      const int step = warp;
      DESC(0);
      float v[16];
      mbar_waitw4(bar + 8 * B_F2, 0);
      wg_fence(); proj<32, SSV, 1, 0, 40>(v, W, D); wg_commit();
      wg_wait<0>();
      mbar_arrive_remote_if(lane < 4, rb0 + ((nA - 4 + lane) << 24) + OFF_BAR + 8 * B_R2);
#pragma unroll
      for (int j = 0; j < 8; j++) vl[j] = pack2v(v[2 * j], v[2 * j + 1]);
      if (warp == 0 && (unsigned)ig < 3) issue_tok(1, B_F2, B_R2, 0);
    }
#pragma unroll 1
    for (int step = 0; step < NSTEP; step++) {
      const uint32_t par = step & 1;
      asm volatile("" : "+r"(lane));
      const bool dual = is_dual(step), has_next = step + 1 < NSTEP;
      mbar_expect_if(lane == 0 && has_next, bar + 8 * (B_F2 + warp), 10240);
      if (warp == 0 && ig == 3 && dual && sync_b) wait_cnt(&g_xready[sched_l(step + 1)][0], 32);
      bar_sync(N_VGO, 384);
      CFENCE();
#define F1_BYTES (is_dual(step + 1) ? 15360 : 2560)
#define ARM() do { \
        mbar_expect_if(lane == 0 && has_next, bar + 8 * (B_F1 + warp), F1_BYTES); \
        mbar_expect_if(lane == 0 && has_next && warp * nA + (int)rank < 40, bar + 8 * (B_RS + warp), (warp * nA + (int)rank >= 36 ? nA : nh) * (dual ? 512 : 256)); } while (0)
#define O_ADDR() uint32_t oa = sb + OFF_O + (lane >> 4) * PL_SZ + warp * 256 + (lane & 15) * 16, xo = (lane >> 4) * 1024 + warp * 256 + (lane & 15) * 16; \
        asm volatile("" : "+r"(oa), "+r"(xo))
#define O_READY(act) do { if (has_next) { const uint4 ov = lds128(oa); \
        if (act) { st_async_v4(nxt + OFF_XL + xo, ov.x, ov.y, ov.z, ov.w, nxt + OFF_BAR + 8 * B_OPEER); \
                   st_async_v4(prv + OFF_XF + xo, ov.x, ov.y, ov.z, ov.w, prv + OFF_BAR + 8 * B_OPEER); } \
        fence_async(); bar_arrive(N_O, 384); } \
        if (warp == 0) TS(15); } while (0)
#define TOK_L3() if (warp == 0 && ig == 3 && has_next) { mbar_waitu(bar + 8 * B_R1, par); asm volatile("fence.proxy.async.global;" ::: "memory"); \
        bulk_g2s_mc_e(sb + OFF_TILE + 3 * TILE_GRP + TILE_SBO, &g_xn[0][0] + uni(sched_l(step + 1) * (32 * DM)) + 3 * 5120, 10240, bar + 8 * (B_F2 + 3), mcmask); }
#define OX_ADDR() const bool ox = head * 3 + t3 == 95; \
        const uint32_t oxa = sb + OFF_PL + (ox ? warp * 1024 + (lane & 7) * 32 + ((((lane >> 3) ^ (lane >> 2)) & 1) << 4) : (lane & 7) * 128 + (((warp * 2 + ((lane >> 3) & 1)) ^ (lane & 7)) << 4)); \
        const uint32_t s1 = oxa + ((lane < 16 ? 3072 : 0) >> (ox ? 2 : 0)), s2 = oxa + ((lane < 16 ? 2048 : 1024) >> (ox ? 2 : 0))
      if (dual) {
        uint32_t vf[8], vm[4], vn[8];
        {
          DESC(0);
          float v[24];
          ARM();
          wg_fence(); proj<48, SSV, 0, 30, 40, 30>(v, W, D); wg_commit();
          proj<48, SSV, 0, 0, VD1 - 10, 30>(v, W, D);
          bar_sync(N_SISS, 384);
          proj<48, SSV, 0, VD1 - 10, VD1 - 7, 30>(v, W, D); wg_commit();
          wg_wait<1>(); bar_arrive(N_G3, 160);
          wg_fence(); proj<48, SSV, 0, VD1 - 7, 10, 30>(v, W, D); wg_commit();
          proj<48, SSV, 0, 10, 13, 30>(v, W, D); wg_commit();
          wg_wait<1>(); REL(B_R1, 0);
          wg_fence(); proj<48, SSV, 0, 13, 20, 30>(v, W, D); wg_commit();
          proj<48, SSV, 0, 20, 23, 30>(v, W, D); wg_commit();
          wg_wait<1>(); REL(B_R1, 1);
          wg_fence(); proj<48, SSV, 0, 23, 30, 30>(v, W, D); wg_commit();
          wg_wait<0>(); REL(B_R1, 2);
          bar_arrive(N_VDONE, 160);
          if (warp == 0) TS(14);
#pragma unroll
          for (int j = 4; j < 8; j++) vf[j] = pack2v(v[4 + 2 * j], v[5 + 2 * j]);
          keep4(vf + 4, lane);
          vm[0] = pack2v(v[0], v[1]); vm[1] = pack2v(v[2], v[3]); vm[2] = pack2v(v[20], v[21]); vm[3] = pack2v(v[22], v[23]);
          keep4(vm, lane);
#pragma unroll
          for (int j = 0; j < 4; j++) vf[j] = pack2v(v[4 + 2 * j], v[5 + 2 * j]);
          keep4(vf, lane);
        }
        {
          DESC(1);
          float o[8];
          O_ADDR();
          bar_sync(N_PM, 224);
          wg_fence();
          MM<8>::rs<dlo(OFF_PL + 3584, 128), 0>(o, vl, D.p);
          MM<8>::rs<dlo(OFF_PL + PL_SZ + 3584, 128), 0>(o + 4, vf, D.p);
          MM<8>::rs<dlo(OFF_PL + 3584 + 256, 128), 1>(o, vl + 4, D.p);
          MM<8>::rs<dlo(OFF_PL + PL_SZ + 3584 + 256, 128), 1>(o + 4, vf + 4, D.p);
          MM<8>::rs<dlo(OFF_PL + 3584 + 512, 128), 1>(o, vm, D.p);
          MM<8>::rs<dlo(OFF_PL + PL_SZ + 3584 + 512, 128), 1>(o + 4, vm, D.p);
          wg_commit();
          fence_sched(step);
          const uint4 il = lds128(sb + OFF_INV + (lane & 3) * 16), jf = lds128(sb + OFF_INV + 64 + (lane & 3) * 16);
          const float i0 = rcpf(__uint_as_float(il.x) + __uint_as_float(il.y)), i1 = rcpf(__uint_as_float(il.z) + __uint_as_float(il.w));
          const float j0 = rcpf(__uint_as_float(jf.x) + __uint_as_float(jf.y)), j1 = rcpf(__uint_as_float(jf.z) + __uint_as_float(jf.w));
          { const uint32_t k4[4] = {__float_as_uint(i0), __float_as_uint(i1), __float_as_uint(j0), __float_as_uint(j1)}; keep4(k4, lane | (oa ^ xo)); }
          wg_wait<0>();
          stsm4t(oa, pack2(o[0] * i0, o[1] * i1), pack2(o[2] * i0, o[3] * i1), pack2(o[4] * j0, o[5] * j1), pack2(o[6] * j0, o[7] * j1));
          O_READY(true);
          TOK_L3();
        }
        {
          DESC(2);
          float v[16];
          bar_sync(N_TURN, 256);
          mbar_waitu(bar + 8 * B_F2, par ^ 1);
          wg_fence(); proj<32, SSV, 1, 0, 10>(v, W, D); wg_commit();
          mbar_waitu(bar + 8 * (B_F2 + 1), par ^ 1);
          wg_fence(); proj<32, SSV, 1, 10, 14>(v, W, D); wg_commit();
          wg_wait<1>(); REL(B_R2, 0);
          wg_fence(); proj<32, SSV, 1, 14, 20>(v, W, D); wg_commit();
          mbar_waitu(bar + 8 * (B_F2 + 2), par ^ 1);
          wg_fence(); proj<32, SSV, 1, 20, 24>(v, W, D); wg_commit();
          wg_wait<1>(); REL(B_R2, 1);
          wg_fence(); proj<32, SSV, 1, 24, 30>(v, W, D); wg_commit();
          mbar_waitu(bar + 8 * (B_F2 + 3), par ^ 1);
          wg_fence(); proj<32, SSV, 1, 30, 34>(v, W, D); wg_commit();
          wg_wait<1>(); REL(B_R2, 2);
          wg_fence(); proj<32, SSV, 1, 34, 40>(v, W, D); wg_commit();
          wg_wait<0>(); REL(B_R2, 3);
#pragma unroll
          for (int j = 0; j < 8; j++) vn[j] = pack2v(v[2 * j], v[2 * j + 1]);
          keep4(vn, lane); keep4(vn + 4, lane);
          if (warp == 0) TS(18);
        }
        DESC(3);
        uint32_t ow[16];
        bar_sync(N_P, 256);
        fence_async();
#define PV16(i, off, va) { float o[8]; wg_fence(); \
          MM<16>::rs<dlo(OFF_PL + (off), 128), 0>(o, va, D.p); \
          MM<16>::rs<dlo(OFF_PL + (off) + 256, 128), 1>(o, va + 4, D.p); \
          MM<16>::rs<dlo(OFF_PL + (off) + 512, 128), 1>(o, vm, D.p); \
          wg_commit(); wg_wait<0>(); \
          _Pragma("unroll") for (int j = 0; j < 4; j++) ow[4 * (i) + j] = pack2v(o[2 * j], o[2 * j + 1]); \
          keep4(ow + 4 * (i), lane); }
        PV16(0, 0, vl) PV16(1, 1792, vl) PV16(2, PL_SZ, vf) PV16(3, PL_SZ + 1792, vf)
        OX_ADDR();
        bar_sync(N_V, 128);
        stsm4t(s1, ow[0], ow[1], ow[2], ow[3]);
        stsm4t(s2, ow[4], ow[5], ow[6], ow[7]);
        stsm4t(s1 + PL_SZ, ow[8], ow[9], ow[10], ow[11]);
        stsm4t(s2 + PL_SZ, ow[12], ow[13], ow[14], ow[15]);
#pragma unroll
        for (int j = 0; j < 8; j++) vl[j] = vn[j];
      } else {
        uint32_t vm[4], vn[8];
        {
          DESC(4);
          float v[4];
          wg_fence(); proj<8, SSV, 0, 30, 40, 30>(v, W, D); wg_commit();
          proj<8, SSV, 0, 0, VS1, 30>(v, W, D); wg_commit();
          ARM();
          bar_sync(N_SISS, 384);
          wg_wait<1>(); bar_arrive(N_G3, 160);
          wg_fence(); proj<8, SSV, 0, VS1, 30, 30>(v, W, D); wg_commit();
          if (has_next) { mbar_waitu2(bar + 8 * B_F2, bar + 8 * (B_F2 + 1), par ^ 1); mbar_waitu(bar + 8 * (B_F2 + 2), par ^ 1); }
          wg_wait<0>();
          bar_arrive(N_VDONE, 160);
          vm[0] = pack2v(v[0], v[1]); vm[1] = pack2v(v[2], v[3]); vm[2] = pack2v(v[1], v[0]); vm[3] = pack2v(v[3], v[2]);
        }
        DESC(5);
        float v[16];
        {
          wg_fence(); proj<32, SSV, 1, 0, VS2>(v, W, D); wg_commit();
          {
            float o[4];
            O_ADDR();
            bar_sync(N_PM, 192);
            if (warp == 0) TS(14);
            wg_fence();
            MM<8>::rs<dlo(OFF_PL + 3584, 128), 0>(o, vl, D.p);
            MM<8>::rs<dlo(OFF_PL + 3584 + 256, 128), 1>(o, vl + 4, D.p);
            MM<8>::rs<dlo(OFF_PL + 3584 + 512, 128), 1>(o, vm, D.p);
            wg_commit();
            fence_sched(step);
            const uint4 il = lds128(sb + OFF_INV + (lane & 3) * 16);
            const float i0 = rcpf(__uint_as_float(il.x) + __uint_as_float(il.y)), i1 = rcpf(__uint_as_float(il.z) + __uint_as_float(il.w));
            { const uint32_t k4[4] = {__float_as_uint(i0), __float_as_uint(i1), oa, xo}; keep4(k4, lane); }
            wg_wait<0>();
            stsm2t(oa, pack2(o[0] * i0, o[1] * i1), pack2(o[2] * i0, o[3] * i1));
            O_READY(lane < 16);
            TOK_L3();
          }
          if (has_next) {
            mbar_arrive_remote_if(lane < VS2 / 10, rb0 + ((nA - 4 + lane) << 24) + OFF_BAR + 8 * B_R2);
            bar_sync(N_TURN, 256);
          }
          if (VS2 < 30) { wg_fence(); proj<32, SSV, 1, VS2, 30>(v, W, D); wg_commit(); }
          if (has_next) mbar_waitu(bar + 8 * (B_F2 + 3), par ^ 1);
          if (VS2 < 30) { wg_wait<0>(); if (has_next) REL(B_R2, 2); }
          wg_fence(); proj<32, SSV, 1, 30, 40>(v, W, D); wg_commit();
          wg_wait<0>();
          if (has_next) REL(B_R2, 3);
#pragma unroll
          for (int j = 0; j < 8; j++) vn[j] = pack2v(v[2 * j], v[2 * j + 1]);
          keep4(vn, lane); keep4(vn + 4, lane);
          if (warp == 0) TS(18);
        }
        float o[16];
        bar_sync(N_P, 256);
        fence_async();
        wg_fence();
        MM<32>::rs<dlo(OFF_PL, 128), 0>(o, vl, D.p);
        MM<32>::rs<dlo(OFF_PL + 256, 128), 1>(o, vl + 4, D.p);
        MM<32>::rs<dlo(OFF_PL + 512, 128), 1>(o, vm, D.p);
        wg_commit();
        OX_ADDR();
        wg_wait<0>();
        bar_sync(N_V, 128);
        stsm4t(s1, pack2(o[0], o[1]), pack2(o[2], o[3]), pack2(o[4], o[5]), pack2(o[6], o[7]));
        stsm4t(s2, pack2(o[8], o[9]), pack2(o[10], o[11]), pack2(o[12], o[13]), pack2(o[14], o[15]));
#pragma unroll
        for (int j = 0; j < 8; j++) vl[j] = vn[j];
      }
      bar_arrive(N_OX, 160);
      if (warp == 0) TS(16);
    }
    cluster_sync_all();
  } else {
    asm volatile("setmaxnreg.dec.sync.aligned.u32 32;");
    if (wg > 3) return;
    LANE_INIT();
    struct RsJob { uint32_t* gp; uint32_t la, mb; int n; };
    auto rs_prep = [&](int step, int s, int c) {
      RsJob j;
      const int u = s * nA + rank;
      j.gp = &g_part[0][0][0][0] + (uint32_t)((((step & 1) * 2 + c) * NCL + cl) * 2560 + u * 64 + (lane >> 2) * 8 + (lane & 3));
      j.la = sb + OFF_TILE + c * LAND_F + LAND(s) + lane * 8;
      j.mb = bar + 8 * (B_RS + s);
      j.n = u >= 40 ? 0 : u >= 36 ? 3 : 1;
      asm volatile("" : "+l"(j.gp), "+r"(j.la));
      return j;
    };
    auto rs_sum = [&](RsJob j, int step) {
      if (j.n) {
        auto five = [&](uint32_t la) {
          uint2 p[5];
#pragma unroll
          for (int i = 0; i < 4; i++) p[i] = lds64(la + i * 256);
          asm volatile("{\n.reg .pred q;\nsetp.eq.s32 q, %3, 5;\nmov.u32 %0, 0;\nmov.u32 %1, 0;\n@q ld.shared.v2.b32 {%0,%1}, [%2];\n}"
                       : "=r"(p[4].x), "=r"(p[4].y) : "r"(la + 1024), "r"(nh) : "memory");
          return make_uint2(hadd2bf(hadd2bf(p[0].x, p[1].x), hadd2bf(hadd2bf(p[2].x, p[3].x), p[4].x)),
                            hadd2bf(hadd2bf(p[0].y, p[1].y), hadd2bf(hadd2bf(p[2].y, p[3].y), p[4].y)));
        };
        const uint32_t tag = ((step >> 1) & 1) ^ 1;
        mbar_waitw(j.mb, step & 1);
        uint2 t = five(j.la);
        if (j.n > 1) {
          const uint2 a = five(j.la + (nh == 5 ? 1280 : TILE_GRP - 1280)), b = five(j.la + TILE_GRP);
          t.x = hadd2bf(t.x, hadd2bf(a.x, b.x)); t.y = hadd2bf(t.y, hadd2bf(a.y, b.y));
        }
        const uint32_t t0 = (movm(t.x) & ~1u) | tag, t1 = (movm(t.y) & ~1u) | tag;
        asm volatile("st.relaxed.gpu.global.b32 [%0], %1;" :: "l"(j.gp), "r"(lane & 16 ? t1 : t0) : "memory");
        asm volatile("st.relaxed.gpu.global.b32 [%0], %1;" :: "l"(j.gp + 4), "r"(lane & 16 ? t0 : t1) : "memory");
      }
    };
    if (warp * nA + (int)rank < 40) {
#pragma unroll
      for (int e = LAG; e < LAG + 2; e++)
        if ((e >> 1) & 1) *reinterpret_cast<uint2*>(&g_part[(e & 1) * 2 + 1][cl][warp * nA + rank][lane * 2]) = make_uint2(1u, 1u);
      __threadfence();
    }
    if (warp == 2 && ig >= 0 && sync_b) wait_cnt(&g_xready[0][0], 32);
    cluster_sync_all();
    if (warp == 2 && ig >= 0) bulk_g2s_mc_e(sb + OFF_TILE + ig * TILE_GRP + TILE_SBO, &g_xn[0][0] + ig * 5120, 10240, bar + 8 * (B_F2 + ig), mcmask);
    bar_sync(N_PI, 128);
#pragma unroll 1
    for (int i = warp; i < 20; i += 4) {
      int c0, c1; wo_coord(i, t3, head, c0, c1);
      if (i >= 2 && i < 15) tma2d_e(sb + OFF_WO + (i - 2) * 4096, &M.wo32, c0, c1, bar + 8 * B_W1);
      else if (lane == 0) tma2d_prefetch(&M.wo32, c0, c1);
      __syncwarp();
    }
#pragma unroll 1
    for (int step = 0; step < NSTEP; step++) {
      const uint32_t par = step & 1;
      asm volatile("" : "+r"(lane));
      const bool dual = is_dual(step), has_next = step + 1 < NSTEP;
      {
        bar_sync(N_PX, dual ? 256 : 192);
        if (dual || warp >= 2) tok_softmax(sb, dual ? warp : warp - 2, lane);
        bar_arrive(N_P, 256);
        asm volatile("" : "+r"(lane));
        if (has_next) {
          if (step + 2 == LAG && lane < 20) asm volatile("prefetch.global.L2 [%0];" :: "l"(mem0 + (warp * 20 + lane) * 64));
          const int nw = ig >= 0 ? 3 : 4, j0 = warp < nw ? warp : 8;
          const int sh = dual ? 1 : 0;
          rs_sum(rs_prep(step, j0 >> sh, j0 & sh), step);
          if (warp == 0) TS(17);
          if (dual) rs_sum(rs_prep(step, (j0 + nw) >> 1, (j0 + nw) & 1), step);
          if (warp == 0) { bar_sync(N_C, 288); }
          mbar_arrive_remote_if(lane < nA, rb0 + (lane << 24) + OFF_BAR + 8 * B_LANDFREE);
          const uint32_t gap = dual ? POLL_GAPD : POLL_GAP;
          if (gap) { const uint32_t t0 = clock32(); while (clock32() - t0 < gap) {} }
#pragma unroll 1
          for (int j = j0; j < (dual ? 8 : 4); j += nw) {
            const int u = (j >> sh) * nA + rank, c = j & sh;
            if (u < UMAX && (c || step + 1 != NSEG)) {
              const uint32_t* gq = &g_part[0][0][0][0] + (uint32_t)((par * 2 + c) * NCL * 2560 + u * 64 + lane * 2);
              uint2 pa[NCL];
              POLL(pa, gq);
              deliver(pa, gq, u, c, step + 1 < NSEG ? c : 0, dual ? DS_DUAL : DS_SINGLE, step, j == 0, lane);
            }
            if (warp == 0 && j == 0) TS(13);
          }
          if (warp >= nw && (is_dual(step + 1) || (ig < 3 && step + 2 < NSTEP))) {
            issue_tok(is_dual(step + 1) ? sched_f(step + 1) : sched_l(step + 2), is_dual(step + 1) ? B_F1 : B_F2, B_R2, par ^ 1);
          }
          if (step + 1 == LAG && UMAX) {
            uint4 v[5];
#pragma unroll
            for (int i = 0; i < 5; i++) { const int t = warp * 160 + i * 32 + lane; v[i] = *reinterpret_cast<const uint4*>(mem0 + ((t >> 1) & 7) * DM + (t >> 4) * 16 + ((t ^ (t >> 3)) & 1) * 8); }
            mbar_waitu(bar + 8 * B_LANDFREE, par);
#pragma unroll
            for (int i = 0; i < 5; i++)
              st_async_v4(sb + OFF_TILE + LAND_F + warp * TILE_GRP + (i * 32 + lane) * 16, v[i].x, v[i].y, v[i].z, v[i].w, bar + 8 * (B_F1 + warp));
          }
        }
      }
      if (warp == (ig >= 0 && !is_dual(step + 1) ? 2 : 3)) {
        unsigned char* o0 = g_o + uni(step % RO * (96 * 8192) + (head * 3 + t3) * (dual ? 8192 : 4096));
        bar_sync(N_OX, 160);
        fence_async();
        bulk_s2g_es(o0, sb + OFF_PL, 4096);
        if (dual) bulk_s2g_es(o0 + 4096, sb + OFF_PL + PL_SZ, 4096);
        asm volatile("cp.async.bulk.commit_group;" ::: "memory");
        asm volatile("cp.async.bulk.wait_group.read 0;" ::: "memory");
        __syncwarp();
        mbar_arrive_remote_if(lane < 2, (lane ? nxt : prv) + OFF_BAR + 8 * B_PLFREE);
        asm volatile("cp.async.bulk.wait_group 0;" ::: "memory");
        asm volatile("fence.proxy.async.global;" ::: "memory");
        __syncwarp();
        if (lane == 0) red_release(&g_f[F_O + (head * 3 + t3) / 5][step], 1u);
        __syncwarp();
      }
    }
    cluster_sync_all();
  }
}

__device__ __forceinline__ uint32_t gelu2(uint32_t y, uint32_t s) {
  uint32_t g;
  asm("{\n.reg .b32 x, u, a, b;\nmov.b32 a, 0x28912891;\nmov.b32 b, 0x3a623a62;\nmul.rn.f16x2 x, %1, %2;\nmul.rn.f16x2 u, x, x;\nfma.rn.f16x2 u, u, a, b;\n"
      "mul.rn.f16x2 u, u, x;\ntanh.approx.f16x2 u, u;\nfma.rn.f16x2 %0, x, u, x;\n}" : "=r"(g) : "r"(y), "r"(s));
  return g; }

struct BParams {
  CUtensorMap wmap[5];
  CUtensorMap wo16;
  const __nv_bfloat16* x;
  __nv_bfloat16* out;
  uint64_t desc, desc32;
};
#define BO_O 0
#define BO_RES (6 * 8192)
#define OP_RES 63488
#define BO_STG (BO_RES + 2 * OP_RES)
#define BO_RING_OP (BO_STG + 16384)
#define OP_SLOT 12288
#define NS_OP 3
#define BO_H 81920
#define BO_W1 (BO_H + 16384)
#define BO_RING_MLP (BO_W1 + 81920)
#define BO_BAR 229376
#define BO_BOX (BO_BAR + 248)
#define BO_CARRY (BO_BAR + 512)
#define BO_STAT (BO_CARRY + 2048)
#define B_SMEM (BO_STAT + 256)
static_assert(B_SMEM <= 232448 && BO_RING_OP + NS_OP * OP_SLOT == BO_BAR && BO_RING_MLP + 3 * 16384 == BO_BAR && 2 * 83968 <= BO_RING_MLP, "smem");
enum { BB_W = 0, BB_FULL = 2, BB_TMP = BB_FULL + 3, BB_OFULL = BB_FULL + 5, BB_SFREE = BB_OFULL,
       BB_STAT = BB_SFREE + 6, BB_GO, BB_ZFREE, BB_DONE = BB_ZFREE + 3,
       BB_EMPTY, BB_START = BB_EMPTY, BB_USED = BB_EMPTY + 2, BB_NUM = BB_USED + 3 };
enum { NB_PP = 1, NB_H = 3, NB_END = 4, NB_END2 = 5, NB_STAGED = 6, NB_FREE = 8, NB_EARLY = 10, NB_LAST = 11 };

#define DESC_LO(off) (((SMEM0 + (off)) >> 4) | (1u << 16))

__device__ __forceinline__ uint32_t ld_relaxed(const uint32_t* p) { uint32_t v; asm volatile("ld.relaxed.gpu.global.b32 %0, [%1];" : "=r"(v) : "l"(p) : "memory"); return v; }
__device__ __forceinline__ int front(int r) { return r - (r > NSEG); }
__device__ __forceinline__ int fmask(int r) { return (r < NSEG) | ((r >= LAG && r < NSTEP) << 1); }
__device__ __forceinline__ int bmask(int r) { return (r <= NSEG) | ((r >= LAG && r != NSEG) << 1); }
#define NMERGE 3
__device__ __forceinline__ bool merged(bool w12, int r) { return !w12 && r > NSEG && r < NSEG + 2 * NMERGE; }
__device__ __forceinline__ uint32_t rtarget(int mask) { return mask == 3 ? 64 : 32; }
__device__ __forceinline__ void warp_signal(uint32_t* p, int lane) {
  __syncwarp();
  asm volatile("{\n.reg .pred q;\nsetp.eq.u32 q, %1, 0;\n@q red.release.gpu.global.add.u32 [%0], 1;\n}" :: "l"(p), "r"(lane) : "memory");
}
__device__ __forceinline__ uint32_t pack2h(float lo, float hi) { uint32_t r; asm("cvt.rn.f16x2.f32 %0, %1, %2;" : "=r"(r) : "f"(hi), "f"(lo)); return r; }
template <bool H> __device__ __forceinline__ uint32_t pk(float lo, float hi) { return H ? pack2h(lo, hi) : pack2(lo, hi); }
template <int N, bool H> __device__ __forceinline__ void stage_out(const float* d, uint32_t dst, int warp, int lane) {
  const uint32_t sa = dst + ((lane >> 4) * 8 + (lane & 7)) * 128 + (((2 * warp + ((lane >> 3) & 1)) ^ (lane & 7)) << 4);
#pragma unroll
  for (int m = 0; m < N / 16; m++)
    stsm4t(sa + m * 2048, pk<H>(d[8 * m], d[8 * m + 1]), pk<H>(d[8 * m + 2], d[8 * m + 3]), pk<H>(d[8 * m + 4], d[8 * m + 5]), pk<H>(d[8 * m + 6], d[8 * m + 7]));
}
template <int N> __device__ __forceinline__ void acc_live(float* d) {
#pragma unroll
  for (int i = 0; i < N / 2; i++) asm volatile("" : "+f"(d[i]) :: "memory");
}
struct Ring {
  uint32_t sl, ph;
  template <int NS> __device__ __forceinline__ void step() { if (++sl == NS) { sl = 0; ph ^= 1; } }
};

#define KOFF(x) (DESC_LO(BO_O) + ((x) >> 2) * 512 + ((x) & 3) * 2)
template <int N, int P>
__device__ __forceinline__ void op_pass(const uint32_t* W, uint32_t bar, Dsc alo, Dsc blo, Dsc xlo, bool x2, Ring& rg, int wg, int warp, int lane, int r) {
  float acc[N / 2];
  blo.e = xlo.e = fresh<P + N / 64 * 5>(r);
  const Dsc tlo = blo + uni(rg.sl) * (OP_SLOT / 16), b2 = blo + (r & 1) * 1536;
  if (P == 0) mbar_waitu(bar + 8 * (BB_OFULL + 2 + (r & 1)), (r >> 1) & 1);
  CTS(5 * P);
  bar_sync(NB_PP + wg, 256);
  wg_fence();
#define OP_R(x, b) MM<N>::template rs<KOFF(4 * (x >> 1) + (x & 1)), (x != (P ? 0 : 4))>(acc, W + 32 * P + 4 * x, b);
#define OP_S(x, b) MM<N>::template ss<DESC_LO(BO_RES) + (6 * P + x) * 128, KOFF(4 * (x >> 1) + 2 + (x & 1)), 1>(acc, alo, b);
#define OP_T(x) MM<N>::template ss<DESC_LO(BO_RING_OP) + x * 128, KOFF(14 + x), 1>(acc, tlo, blo);
#define OP_B2() OP_R(4, b2) OP_S(4, b2) OP_R(5, b2) OP_S(5, b2)
  if (P == 0) { OP_B2() mbar_waitu(bar + 8 * BB_OFULL, r & 1); }
  OP_R(0, blo) OP_S(0, blo) OP_R(1, blo) OP_S(1, blo) OP_R(2, blo) OP_S(2, blo) OP_R(3, blo) OP_S(3, blo)
  if (P == 0) mbar_waitu(bar + 8 * (BB_OFULL + 1), r & 1);
  if (P == 4) wg_commit();
  if (P & 3) { OP_B2() }
  if (P == 1 && x2) MM<N>::template ss<DESC_LO(BO_RES) + 30 * 128, DESC_LO(BO_CARRY), 1>(acc, alo, xlo);
  mbar_waitu(bar + 8 * (BB_FULL + rg.sl), rg.ph);
  OP_R(6, blo) OP_T(0) OP_R(7, blo) OP_T(1)
  if (P == 4) { wg_commit(); wg_wait<1>(); bar_arrive(NB_EARLY, 288); CTS(21); wg_fence(); }
  OP_T(2) OP_T(3)
  if (P == 0) MM<N>::template rs<DESC_LO(BO_CARRY), 1>(acc, W + 160, xlo);
  OP_T(4) OP_T(5)
  if (P == 4) { wg_commit(); OP_B2() }
  wg_commit();
  bar_arrive(NB_PP + 1 - wg, 256);
  CTS(5 * P + 2);
  if (P == 4) { wg_wait<1>(); bar_arrive(NB_LAST, 288); }
  bar_sync(NB_FREE + wg, 160);
  wg_wait<0>();
  acc_live<N>(acc);
  mbar_arrive_if(lane == 0, bar + 8 * (BB_USED + rg.sl));
  CTS(5 * P + 3);
  stage_out<N, false>(acc, SMEM0 + BO_STG + wg * 8192, warp, lane);
  bar_arrive(NB_STAGED + wg, 160);
  CTS(5 * P + 4);
  rg.step<NS_OP>(); rg.step<NS_OP>();
}
template <int N>
__device__ __forceinline__ void op_round(const uint32_t* W, uint32_t bar, Dsc alo, Dsc blo, Dsc xlo, bool x2, Ring& rg, int wg, int warp, int lane, int r) {
  op_pass<N, 0>(W, bar, alo, blo, xlo, x2, rg, wg, warp, lane, r);
  op_pass<N, 1>(W, bar, alo, blo, xlo, x2, rg, wg, warp, lane, r);
  op_pass<N, 2>(W, bar, alo, blo, xlo, x2, rg, wg, warp, lane, r);
  op_pass<N, 3>(W, bar, alo, blo, xlo, x2, rg, wg, warp, lane, r);
  op_pass<N, 4>(W, bar, alo, blo, xlo, x2, rg, wg, warp, lane, r);
}
__device__ __forceinline__ void carry_in(uint32_t sb, int wg, int warp, int lane) {
  const int row = (lane >> 1) & 3;
  if (lane < 16) {
    const uint4 v = lds128(sb + BO_CARRY + (wg * 4 + warp) * 256 + lane * 16);
    sts128(sb + BO_H + wg * 8192 + (lane >> 3) * 4096 + row * 128 + (((2 * warp + (lane & 1)) ^ row) << 4), v.x, v.y, v.z, v.w);
  }
  __syncwarp();
}
template <int N, int Z>
__device__ __forceinline__ void p1_pair(float* acc, const uint32_t* W, uint32_t bar, Dsc alo, Dsc blo, int lane, int r) {
  constexpr uint32_t ZOFF = DESC_LO(BO_RING_MLP + (N == 64 ? (Z == 1 ? -1 : (4 - Z) & 3) * 16384 : (Z / 2 * 2 % 3) * 16384 + (Z & 1) * 4096));
  blo.e = fresh<10 + Z / 3 + N / 64 * 2>(r);
  mbar_waitu(bar + 8 * (BB_FULL + Z), r & 1);
  CTS(40 + Z);
  wg_fence();
#define P1_B(k) \
  MM<N, true>::template rs<ZOFF + k * 512, (2 * Z + k != 0)>(acc, W + 16 * Z + 8 * k, blo); \
  MM<N, true>::template ss<DESC_LO(BO_W1) + (2 * Z + k) * 512, ZOFF + k * 512 + 4, 1>(acc, alo, blo); \
  MM<N, true>::template rs<ZOFF + k * 512 + 2, 1>(acc, W + 16 * Z + 8 * k + 4, blo); \
  MM<N, true>::template ss<DESC_LO(BO_W1) + (2 * Z + k) * 512 + 128, ZOFF + k * 512 + 6, 1>(acc, alo, blo);
  P1_B(0)
  if (N == 64 && (Z == 1 || Z == 2)) { wg_commit(); wg_wait<1>(); mbar_arrive_if(lane == 0, bar + 8 * (BB_EMPTY + Z - 1)); wg_fence(); }
  P1_B(1)
  wg_commit();
}
template <int N>
__device__ __forceinline__ void phase1(const uint32_t* W, uint32_t sb, Dsc alo, Dsc blo, int half, int wg, int warp, int lane, bool shift, int off, int rb, int r) {
  float acc[N / 2];
  const uint32_t bar = sb + BO_BAR;
  CTS(30);
  p1_pair<N, 0>(acc, W, bar, alo, blo, lane, r);
  p1_pair<N, 1>(acc, W, bar, alo, blo, lane, r);
  p1_pair<N, 2>(acc, W, bar, alo, blo, lane, r);
  if (N == 64 && !wg) { mbar_waitu(bar + 8 * (BB_SFREE + 4), (rb + 1) & 1); if (shift) carry_in(sb, wg, warp, lane); }
  p1_pair<N, 3>(acc, W, bar, alo, blo, lane, r);
  if (N == 32 || wg) { mbar_waitu(bar + 8 * (BB_SFREE + 4 + wg), (rb + 1) & 1); if (shift) carry_in(sb, wg, warp, lane); }
  if (N == 32) mbar_arrive_if(lane < 2, bar + 8 * (BB_EMPTY + lane));
  p1_pair<N, 4>(acc, W, bar, alo, blo, lane, r);
  const int c = (lane >> 3) & 1, i0 = (lane >> 4) * 8 + (lane & 7) + off;
  uint32_t a0 = sb + BO_H + wg * 8192 + half * 4096 + i0 * 128 + (((2 * warp + c) ^ (i0 & 7)) << 4);
  uint32_t a1 = i0 >= 16 ? sb + BO_CARRY + (wg * 4 + warp) * 256 + half * 128 + (i0 - 16) * 32 + c * 16 : a0 + 2048, a3 = a1 + (i0 >= 16 ? 128 : 4096);
  asm volatile("" : "+r"(a0), "+r"(a1), "+r"(a3));
  mbar_waitu(bar + 8 * BB_STAT, r & 1);
  const uint32_t sa = sb + BO_STAT + (lane & 3) * 32 + half * 16;
  const uint4 t0 = lds128(sa), t1 = N == 64 ? lds128(sa + 16) : t0;
  const uint32_t t[8] = {t0.x, t0.y, t0.z, t0.w, t1.x, t1.y, t1.z, t1.w};
  { const uint32_t k4[4] = {a0, a1, a3, sa}; keep4(k4, lane); }
  wg_wait<0>();
  acc_live<N>(acc);
  CTS(32);
#pragma unroll
  for (int m = 0; m < N / 16; m++) {
    const float* d = acc + 8 * m;
    stsm4t(m == 1 ? a1 : m == 3 ? a3 : a0 + m * 2048, gelu2(pack2h(d[0], d[1]), t[2 * m]), gelu2(pack2h(d[2], d[3]), t[2 * m]),
           gelu2(pack2h(d[4], d[5]), t[2 * m + 1]), gelu2(pack2h(d[6], d[7]), t[2 * m + 1]));
  }
}
template <int N, int P>
__device__ __forceinline__ void p2_mma(float* acc, const uint32_t* W, Dsc alo, Dsc blo, int r) {
  blo.e = fresh<P + N / 64 * 5>(r);
  MM<N, true>::template rs<DESC_LO(BO_H), 0>(acc, W + 80 + 16 * P, blo);     MM<N, true>::template ss<DESC_LO(0) + P * 1024, DESC_LO(BO_H) + 512, 1>(acc, alo, blo);
  MM<N, true>::template rs<DESC_LO(BO_H) + 2, 1>(acc, W + 84 + 16 * P, blo); MM<N, true>::template ss<DESC_LO(0) + P * 1024 + 128, DESC_LO(BO_H) + 514, 1>(acc, alo, blo);
  MM<N, true>::template rs<DESC_LO(BO_H) + 4, 1>(acc, W + 88 + 16 * P, blo); MM<N, true>::template ss<DESC_LO(0) + P * 1024 + 512, DESC_LO(BO_H) + 516, 1>(acc, alo, blo);
  MM<N, true>::template rs<DESC_LO(BO_H) + 6, 1>(acc, W + 92 + 16 * P, blo); MM<N, true>::template ss<DESC_LO(0) + P * 1024 + 640, DESC_LO(BO_H) + 518, 1>(acc, alo, blo);
}
template <int N, int P, int T>
__device__ __forceinline__ void p2_pass(const uint32_t* W, uint32_t bar, Dsc alo, Dsc blo, int wg, int warp, int lane, int r) {
  float acc[N / 2], ac2[N / 2];
  CTS(5 * P);
  if (P || wg) bar_sync(NB_PP + wg, 256);
  wg_fence();
  p2_mma<N, P>(acc, W, alo, blo, r);
  wg_commit();
  if constexpr (T == 2) { p2_mma<N, P + 1>(ac2, W, alo, blo, r); wg_commit(); }
  if (P < 4 || !wg) bar_arrive(NB_PP + 1 - wg, 256);
  CTS(5 * P + 2);
  if (T == 1 && (P == 2 || P == 3)) mbar_waitu(bar + 8 * (BB_SFREE + 2 * (P - 2) + wg), r & 1);
  wg_wait<T - 1>();
  acc_live<N>(acc);
  if (P == 4) bar_sync(NB_H, 256);
  CTS(5 * P + 3);
  constexpr int K = P / T & 1;
  stage_out<N, true>(acc, SMEM0 + (P == 4 ? BO_H : BO_RING_MLP + (2 - K) * 16384) + wg * 8192, warp, lane);
  if constexpr (T == 2) {
    wg_wait<0>();
    acc_live<N>(ac2);
    stage_out<N, true>(ac2, SMEM0 + BO_RING_MLP + (2 - K) * 16384 + wg * 8192 + 4096, warp, lane);
  }
  bar_arrive(NB_STAGED + (P == 4 ? 4 : 2 * K) + wg, 160);
  CTS(5 * P + 4);
}
template <int N>
__device__ __forceinline__ void phase2(const uint32_t* W, uint32_t bar, Dsc alo, Dsc blo, int wg, int warp, int lane, int r) {
  if constexpr (N == 64) {
    p2_pass<N, 0, 1>(W, bar, alo, blo, wg, warp, lane, r);
    p2_pass<N, 1, 1>(W, bar, alo, blo, wg, warp, lane, r);
    p2_pass<N, 2, 1>(W, bar, alo, blo, wg, warp, lane, r);
    p2_pass<N, 3, 1>(W, bar, alo, blo, wg, warp, lane, r);
  } else {
    p2_pass<N, 0, 2>(W, bar, alo, blo, wg, warp, lane, r);
    p2_pass<N, 2, 2>(W, bar, alo, blo, wg, warp, lane, r);
  }
  p2_pass<N, 4, 1>(W, bar, alo, blo, wg, warp, lane, r);
}

__device__ __forceinline__ void ldg4(uint32_t* v, const void* p) {
  asm volatile("ld.relaxed.gpu.global.v4.u32 {%0,%1,%2,%3}, [%4];" : "=r"(v[0]), "=r"(v[1]), "=r"(v[2]), "=r"(v[3]) : "l"(p) : "memory"); }
__device__ __forceinline__ void stg4(void* p, const uint32_t* v) {
  asm volatile("st.global.v4.u32 [%0], {%1,%2,%3,%4};" :: "l"(p), "r"(v[0]), "r"(v[1]), "r"(v[2]), "r"(v[3]) : "memory"); }
struct RowPtr {
  unsigned char *p, *q, *t;
  __device__ __forceinline__ void ld(uint32_t* v, int o) const {
    ldg4(v, p + o); ldg4(v + 4, q + o);
    asm volatile("ld.relaxed.gpu.global.v2.u32 {%0,%1}, [%2];" : "=r"(v[8]), "=r"(v[9]) : "l"(t + o) : "memory");
  }
  __device__ __forceinline__ void st(const uint32_t* w, int o) const {
    stg4(p + o, w); stg4(q + o, w + 4);
    asm volatile("st.global.v2.u32 [%0], {%1,%2};" :: "l"(t + o), "r"(w[8]), "r"(w[9]) : "memory");
  }
};
__device__ __forceinline__ RowPtr row_img(int r, int n, int lane) {
  unsigned char* b = &g_acc[0][r % RD][n * 128];
  unsigned char* p = b + (uint32_t)((lane >> 3) * 8192 + (((lane ^ n) & 7) << 4));
  return {p, p + 32768, b + (uint32_t)(65536 + (lane >> 4) * 8192 + ((((lane >> 1) ^ n) & 7) << 4) + (lane & 1) * 8)};
}
__device__ __forceinline__ RowPtr row_ext(const void* lin, bool xn, int layer, int tok, int lane) {
  unsigned char* b = xn ? reinterpret_cast<unsigned char*>(&g_xn[layer][0]) + (uint32_t)((tok >> 5) * 40960 + ((tok >> 3) & 3) * 2560 + (tok & 7) * 32)
                        : (unsigned char*)lin + (uint32_t)(tok * 1280);
  const uint32_t o = (lane >> 1) * 256 + ((lane ^ (tok >> 2)) & 1) * 16;
  return {b + (uint32_t)(xn ? o + (lane >= 20 ? 7680 : 0) : lane * 16),
          b + (uint32_t)(xn ? o + 4096 + 7680 + (lane >= 8 ? 7680 : 0) + (lane >= 28 ? 7680 : 0) : lane * 16 + 512),
          b + (uint32_t)(xn ? (lane >> 2) * 256 + ((lane & 3) ^ ((tok >> 1) & 2)) * 8 + 8192 + 3 * 7680 : lane * 8 + 1024)};
}
__device__ __forceinline__ float2 h2f(uint32_t w) {
  float2 f; asm("{\n.reg .f16 l, h;\nmov.b32 {l, h}, %2;\ncvt.f32.f16 %0, l;\ncvt.f32.f16 %1, h;\n}" : "=f"(f.x), "=f"(f.y) : "r"(w)); return f; }
__device__ __forceinline__ float rsq(float x) { float y; asm("rsqrt.approx.ftz.f32 %0, %1;" : "=f"(y) : "f"(x)); return y; }
__device__ __forceinline__ void red_if(uint32_t v, const void* a) {
  asm volatile("{\n.reg .pred q;\nsetp.ne.u32 q, %1, 0;\n@q red.relaxed.gpu.global.add.u32 [%0], %1;\n}" :: "l"(a), "r"(v) : "memory"); }
__device__ __forceinline__ uint32_t dep0(uint32_t w, int lane) { uint32_t z; asm volatile("shr.b32 %0, %1, %2;" : "=r"(z) : "r"(w), "r"(lane + 32)); return z; }
__device__ __forceinline__ int lane_of(uint32_t w) {
  int lane; asm volatile("{\n.reg .u32 t;\nmov.u32 t, %%laneid;\nshr.u32 %0, %1, 20;\nadd.u32 %0, %0, t;\n}" : "=r"(lane) : "r"(w)); return lane; }
#define BUF (RD * TILE_B)
__device__ __forceinline__ int await(uint32_t v, const uint32_t* p, uint32_t target, bool lazy) {
  int n = 0;
  while (!__all_sync(~0u, v >= target)) {
    if (lazy) __nanosleep(200);
    if (++n > SPIN_LIMIT) FAIL();
    v = ld_relaxed(p);
  }
  asm volatile("fence.acquire.gpu;" ::: "memory");
  return lane_of(v);
}
template <int W> __device__ __forceinline__ void sum2(float& s, float& q, int lane) {
  const bool up = lane & (W / 2);
  float e = (up ? q : s) + __shfl_xor_sync(~0u, up ? s : q, W / 2);
#pragma unroll
  for (int o = W / 4; o; o >>= 1) e += __shfl_xor_sync(~0u, e, o);
  const float f = __shfl_xor_sync(~0u, e, W / 2);
  s = up ? f : e; q = up ? e : f;
}
template <int TYPE>
__device__ __forceinline__ void rrow(int r, int row, int tok, int lane, const uint32_t* go, int role, const __nv_bfloat16* x, __nv_bfloat16* out) {
  const int half = TYPE == 3 ? 0 : row >> 5;
  float v[20];
  float2 st = make_float2(1.f, 0.f);
  {
    uint32_t a[10], c[10], u[10], sh = 16;
    if (TYPE == 2) row_img(front(r) + RD - ((row & 31) < 2), (row & 32) + ((row - 2) & 31), lane).ld(u, 3 * BUF);
    else row_ext(x, half, 1, tok, lane).ld(u, 0);
    if (TYPE == 2 || (TYPE == 0 && half))
      asm volatile("ld.relaxed.gpu.global.v2.f32 {%0,%1}, [%2];" : "=f"(st.x), "=f"(st.y) : "l"(g_stat + tok) : "memory");
    RowPtr ap = row_img(r, row, lane);
    const uint32_t g0 = TYPE != 3 ? ld_relaxed(go) : 0;
    if (TYPE != 3) {
      asm volatile("" : "+l"(ap.p), "+l"(ap.t));
      ap.q = ap.p + 32768;
      lane = await(g0, go, NOP * NW12 * NW34, false); BTS2(r, 8 + 2 * TYPE); RTS(0);
      ap.ld(a, TYPE ? 2 * BUF : 0);
    }
    if (TYPE == 0) {
      ap.ld(c, BUF);
      const uint32_t one = 0x3f803f80u | dep0(c[9], lane);
#pragma unroll
      for (int i = 0; i < 10; i++) asm volatile("fma.rn.bf16x2 %0, %0, %1, %2;" : "+r"(a[i]) : "r"(one), "r"(c[i]));
      sh |= dep0(a[9], lane);
    }
    const uint32_t z = TYPE == 2 ? dep0(a[9], lane) : 0;
#pragma unroll
    for (int i = 0; i < 10; i++) {
      if (TYPE == 2) { const float2 g = h2f(u[i] | z), h = h2f(a[i] | z); v[2 * i] = fmaf(h.x, 0.5f, g.x * st.x); v[2 * i + 1] = fmaf(h.y, 0.5f, g.y * st.x); continue; }
      float p = __uint_as_float(u[i] << sh), q = __uint_as_float(u[i] & (0xffffu << sh));
      if (TYPE == 0) { p = fmaf(p, st.x, bf_lo(a[i])); q = fmaf(q, st.x, bf_hi(a[i])); }
      v[2 * i] = p; v[2 * i + 1] = q;
    }
  }
  RTSD(1, v[19]);
  float s = 0.f, q = 0.f;
#pragma unroll
  for (int i = 0; i < 5; i++) {
    s += (v[4 * i] + v[4 * i + 1]) + (v[4 * i + 2] + v[4 * i + 3]);
    q += fmaf(v[4 * i], v[4 * i], v[4 * i + 1] * v[4 * i + 1]) + fmaf(v[4 * i + 2], v[4 * i + 2], v[4 * i + 3] * v[4 * i + 3]);
  }
  if (!(TYPE == 2 && half)) sum2<32>(s, q, lane);
  const float mean = s * (1.f / DM), var = fmaxf(q * (1.f / DM) - mean * mean, 0.f), rs = rsq(var + 1e-5f);
  const float k = TYPE == 0 ? 2.f * rs : half ? 1.f : rs, mr = TYPE && half ? st.y : -mean * k;
  RTSD(2, rs);
  uint32_t w[10];
#pragma unroll
  for (int i = 0; i < 10; i++) w[i] = pk<TYPE == 0>(fmaf(v[2 * i], k, mr), fmaf(v[2 * i + 1], k, mr));
  if (TYPE) row_ext(out, !half, TYPE == 2, tok, lane).st(w, 0);
  else {
    row_img(r, row, lane).st(w, 3 * BUF);
    const int q = r + ((row & 31) >= 30);
    row_img(q + (half && q >= NSEG), (row & 32) + ((row + 2) & 31), lane).st(w, 2 * BUF);
    if (lane == 1) g_st2[0][r % RD][row] = (__float_as_uint(0.5f * rsq(fmaf(var * rs, rs, 1e-5f))) & ~127u) | (r + 1);
  }
  if (TYPE != 3 && lane == 0) g_stat[tok] = make_float2((var + 1e-5f) * rs * (TYPE ? 1.f : 0.5f), mean + st.y);
}
__device__ __forceinline__ void r2rows(int r, int row, int lane, const uint32_t* go) {
  const int n = row + (lane >> 4);
  const unsigned char* ap = &g_acc[2][r % RD][0] + (uint32_t)(n * 128 + ((lane >> 3) & 1) * 8192 + (((lane ^ n) & 7) << 4));
  const uint32_t* sp = &g_st2[1][r % RD][n];
  asm volatile("" : "+l"(ap), "+l"(sp));
  await(0, go, NOP * NW12 * NW34, false);
  BTS2(r, 10);
  uint32_t a[20];
#pragma unroll
  for (int i = 0; i < 5; i++) ldg4(a + 4 * i, ap + i * 16384);
  const uint32_t z = dep0(a[19], lane);
  float s = 0.f, q = 0.f, q2 = 0.f;
#pragma unroll
  for (int i = 0; i < 20; i++) { const float2 h = h2f(a[i] | z); s += h.x + h.y; q = fmaf(h.x, h.x, q); q2 = fmaf(h.y, h.y, q2); }
  q += q2;
  sum2<16>(s, q, lane);
  const float mean = s * (0.5f / DM), rs = rsq(fmaxf(q * (0.25f / DM) - mean * mean, 0.f) + 1e-5f);
  if ((lane & 15) == 0) asm volatile("st.relaxed.gpu.global.u32 [%0], %1;" :: "l"(sp), "r"((__float_as_uint(0.5f * rs) & ~127u) | (r + 1)) : "memory");
}
__device__ __forceinline__ void r3rows(int r, int row, int tok, int lane, __nv_bfloat16* out) {
  const int n = row + (lane >> 4), m = 32 + ((n - 2) & 31);
  const unsigned char* ap = &g_acc[0][r % RD][0] + (uint32_t)(n * 128 + ((lane >> 3) & 1) * 8192 + (((lane ^ n) & 7) << 4));
  const unsigned char* zp = &g_acc[3][(r + RD - (row == 32)) % RD][0] + (uint32_t)(m * 128 + ((lane >> 3) & 1) * 8192 + (((lane ^ m) & 7) << 4));
  unsigned char* op = reinterpret_cast<unsigned char*>(out) + (uint32_t)((tok + (lane >> 4)) * 1280 + (lane & 15) * 16);
  float2 st;
  asm volatile("ld.relaxed.gpu.global.v2.f32 {%0,%1}, [%2];" : "=f"(st.x), "=f"(st.y) : "l"(g_stat + tok + (lane >> 4)) : "memory");
#pragma unroll 1
  for (int i0 = 0; i0 < 2; i0++) {
    uint32_t a[12], u[12];
#pragma unroll
    for (int i = 0; i < 3; i++) { ldg4(a + 4 * i, ap + 2 * BUF + i * 16384); ldg4(u + 4 * i, zp + i * 16384); }
    uint32_t z = dep0(u[11], lane);
#pragma unroll
    for (int i = 0; i < 12; i++) {
      const float2 h = h2f(a[i] | z), g = h2f(u[i] | z);
      a[i] = pack2(fmaf(h.x, 0.5f, fmaf(g.x, st.x, st.y)), fmaf(h.y, 0.5f, fmaf(g.y, st.x, st.y)));
      if (i & 1) z = dep0(a[i], lane);
    }
    if (i0 == 0) stg4(op, a);
    stg4(op + 256, a + 4); stg4(op + 512, a + 8);
    ap += 32768; zp += 32768; op += 512;
  }
}
template <int TYPE>
__device__ __forceinline__ void rloop(int row, int cp, int role, const __nv_bfloat16* x, __nv_bfloat16* out) {
  constexpr int ST = TYPE == 4 ? 2 : TYPE;
  const int r0 = row & 32 ? LAG : 0;
  uint32_t v = 0;
  static_assert(NSEG + RD - 2 >= NSTEP, "no signals");
#pragma unroll 1
  for (int r = r0; r < (TYPE == 0 ? r0 + NSEG : TYPE == 4 ? NSEG : TYPE == 2 || r0 ? NR : NSEG + 1); r++) {
    if (TYPE == 2 && r == NSEG + 1) row += 32;
    if (TYPE == 1 && r0 && r == NSEG) continue;
    const int tok = ((TYPE ? front(r) : r) - (row & 32 ? LAG : 0)) * 32 + (row & 31) - (TYPE ? 2 : 0);
    const bool valid = TYPE == 0 || (unsigned)tok < S_LEN;
    const uint32_t* go = &g_f[F_R1 + 4 * ST + cp][r];
    const uint32_t* first = TYPE == 2 ? &g_f[F_R2 + cp][r] : TYPE ? go : (const uint32_t*)&g_xready[NSEG + r - r0][0];
    if constexpr (TYPE == 1) { r2rows(r, row, lane_of(r), go); BTS2(r, 11); continue; }
    if constexpr (TYPE == 4) {
      const int lane = await(v, go, NOP * NW12 * NW34, false);
      BTS2(r, 8 + 2 * ST); RTS(0);
      if (valid) r3rows(r, row, tok, lane, out);
    } else if constexpr (TYPE != 1) {
      if (TYPE || row >= 32) await(v, first, TYPE ? NOP * NW12 * NW34 : 32, true);
      if (valid) rrow<TYPE>(r, row, tok, lane_of(r), go, role, x, out);
    }
    if (TYPE > 1 && row >= 32 && r + RD - 2 >= NSTEP) { v = 0; BTS2(r, 13); continue; }
    const int lane = lane_of(r);
    const void* f = lane ? (const void*)&g_xready[NSEG + (tok >> 5)][0] : (const void*)&g_f[TYPE ? F_DONE : F_Z][r];
    asm volatile("" : "+l"(f));
    __syncwarp();
    RTS(3);
    v = ld_relaxed(first + (TYPE ? 1 : 8));
    asm volatile("fence.release.gpu;" ::: "memory");
    RTS(4);
    red_if(lane == 0 || (TYPE == 2 && lane == 1 && valid) ? (TYPE & 5 ? 2 : 1) : 0, f);
    RTS(5);
    RTS_OUT();
    BTS2(r, 9 + 2 * ST);
  }
}

#define BULK_ADD(T, dst, src, len) asm volatile("{\n.reg .pred e;\nelect.sync _|e, 0xffffffff;\n@e cp.reduce.async.bulk.global.shared::cta.bulk_group.add.noftz." T " [%0], [%1], %2;\n}" \
                                               :: "l"(dst), "r"(src), "r"(len) : "memory")
#define COMMIT() asm volatile("cp.async.bulk.commit_group;" ::: "memory")
#define DRAINED(n) do { asm volatile("cp.async.bulk.wait_group.read " #n ";" ::: "memory"); __syncwarp(); } while (0)
#define WRITTEN() do { asm volatile("cp.async.bulk.wait_group 0;\nfence.proxy.async.global;" ::: "memory"); __syncwarp(); } while (0)
__device__ __forceinline__ void wait_flags(const uint32_t* p, uint32_t target) {
  int n = 0;
  while (!__all_sync(~0u, ld_relaxed(p) >= target)) { if (++n > SPIN_LIMIT) FAIL(); }
  asm volatile("fence.acquire.gpu;" ::: "memory");
  asm volatile("fence.proxy.async.global;" ::: "memory");
}
__global__ void __launch_bounds__(512, 1) bworker_kernel(const __grid_constant__ BParams P) {
  extern __shared__ __align__(1024) unsigned char smem_raw[];
  const uint32_t sb = SMEM0, bar = sb + BO_BAR;
  const int wg = __shfl_sync(~0u, threadIdx.x >> 7, 0), warp = __shfl_sync(~0u, (threadIdx.x >> 5) & 3, 0);
  if (threadIdx.x == 0) {
    if (smem_u32(smem_raw) != SMEM0) FAIL();
    uint32_t smid; asm volatile("mov.u32 %0, %%smid;" : "=r"(smid));
    const uint32_t nb = ld_relaxed(&g_tpc[(smid >> 1) & 127]);
    const bool single = nb > 1, far = nb == 0 && (smid < 64 || smid >= 124);
    int kind = far || (single && atomicAdd(&g_f[F_MISC][35], 1u) < 3) ? 0 : 1;
    int rc = single || (smid >> 1) == 16 || (smid >> 1) == 63 ? 1 : far ? 2 : 0;
    uint32_t i = atomicAdd(&g_f[F_MISC][32 + kind], 1u), o = atomicAdd(&g_f[F_MISC][36 + rc], 1u);
    while (i >= (kind == 0 ? NOP : kind == 1 ? NW12 : NW34)) { kind = (kind + 1) % 3; i = atomicAdd(&g_f[F_MISC][32 + kind], 1u); }
    while (o >= (rc == 0 ? 16 : rc == 1 ? 8 : 12)) { rc = (rc + 1) % 3; o = atomicAdd(&g_f[F_MISC][36 + rc], 1u); }
    sts64(sb + BO_BOX, i + (kind == 0 ? 0 : kind == 1 ? NOP : NOP + NW12), o + (rc ? 8 + 8 * rc : 0));
    for (int k = 0; k < BB_NUM; k++) mbar_init(bar + 8 * k, k >= BB_USED ? 4 : k >= BB_EMPTY ? 8 : k >= BB_ZFREE && kind ? 2 : 1);
    asm volatile("fence.mbarrier_init.release.cluster;" ::: "memory");
  }
  if (threadIdx.x < 128) sts128(sb + BO_CARRY + threadIdx.x * 16, 0u, 0u, 0u, 0u);
  auto ln0 = [&](int t) {
    const int lane = lane_of(t);
    if (lane < 20 && t + 128 < S_LEN) asm volatile("prefetch.global.L2 [%0];" :: "l"(P.x + (t + (t < 4 * NBC ? 4 * NBC : 128)) * DM + (lane >> 1) * 64));
    rrow<3>(0, 0, t, lane, nullptr, 0, P.x, nullptr);
    __syncwarp();
    asm volatile("fence.release.gpu;" ::: "memory");
    red_if(lane == 0, &g_xready[t >> 5][0]);
  };
  if (wg == 2) ln0(blockIdx.x * 4 + warp);
  fence_async();
  __syncthreads();
  const int role = uni(lds32(sb + BO_BOX));
  if (threadIdx.x < 32) BTS(94, 1);
  const bool op = role < NOP, w12 = role < NOP + NW12;
  const int j = op ? role : w12 ? role - NOP : role - NOP - NW12;
  const int rot = op ? (j ? 2 * ((j + 1) % 5) : 0) : 2 * (j % 5);
  if (wg == 3) {
    asm volatile("setmaxnreg.dec.sync.aligned.u32 24;");
    LANE_INIT();
    if (warp < 2) {
      auto announce = [&](int r, int it, bool mg) {
        const uint32_t* f = &g_f[(op ? F_R1 : w12 ? F_R2 : F_R3) + (lane & 3)][r + ((lane >> 2) & 1)];
        asm volatile("" : "+l"(f));
        if (warp == 0) { mbar_arrive_if(lane == 0, bar + 8 * BB_DONE); return; }
        mbar_waitw(bar + 8 * BB_DONE, it & 1);
        PTS(60);
        asm volatile("fence.release.gpu;" ::: "memory");
        red_if(lane >= (mg ? 8 : 4) ? 0 : op ? NW12 * NW34 : w12 ? NOP * NW34 : NOP * NW12, f);
        PTS(61);
        BTS(r, 4);
      };
      if (op) {
        int mt = rot + warp;
        bar_arrive(NB_FREE + warp, 160);
#pragma unroll 1
        for (int r = 0; r < NSTEP; r++) {
          const uint32_t len = fmask(r) == 3 ? 8192 : 4096;
          unsigned char* acc = &g_acc[j & 1][r % RD][fmask(r) == 2 ? 4096 : 0];
#pragma unroll 1
          for (int p = 0; p < 5; p++) {
            bar_sync(NB_STAGED + warp, 160);
            PTS(50 + 2 * p + warp);
            fence_async();
            BULK_ADD("bf16", acc + mt * 8192, sb + BO_STG + warp * 8192, len);
            COMMIT();
            PTS(64 + 50 + 2 * p + warp);
            mt = mt >= 8 ? mt - 8 : mt + 2;
            DRAINED(0);
            bar_arrive(NB_FREE + warp, 160);
          }
          WRITTEN();
          announce(r, r, false);
        }
      } else {
#pragma unroll 1
        for (int r = 0, it = 0; r < NR; r++, it++) {
          const bool mg = merged(w12, r);
          const uint32_t len = bmask(r) == 3 ? 8192 : 4096;
          unsigned char* acc = &g_acc[2][r % RD][bmask(r) == 2 ? 4096 : 0];
          if (!w12) mbar_waitw(bar + 8 * BB_GO, it & 1);
          int mt = rot + warp;
          const bool pairs = len != 8192 && !mg;
#pragma unroll 1
          for (int p = pairs ? 2 : 0; p < 5; p++) {
            const uint32_t src = sb + (p == 4 ? BO_H : BO_RING_MLP + (2 - (p & 1)) * 16384) + warp * 8192;
            bar_sync(NB_STAGED + (p == 4 ? 4 : 2 * (p & 1)) + warp, 160);
            PTS(50 + 2 * p + warp);
            fence_async();
            BULK_ADD("f16", acc + mt * 8192, src, len);
            if (mg) BULK_ADD("f16", &g_acc[2][(r + 1) % RD][4096 + mt * 8192], src + 4096, len);
            mt = mt >= 8 ? mt - 8 : mt + 2;
            if (pairs && p < 4) { BULK_ADD("f16", acc + mt * 8192, src + 4096, len); mt = mt >= 8 ? mt - 8 : mt + 2; }
            COMMIT();
            PTS(64 + 50 + 2 * p + warp);
            if (p == 4 && !pairs) break;
            DRAINED(1);
            mbar_arrive_if(lane == 0 && p, bar + 8 * (p < 3 ? BB_SFREE + 2 * (p - 1) + warp : BB_ZFREE + (p >> 1)));
            mbar_arrive_if(lane == 0 && pairs && p == 2, bar + 8 * (BB_SFREE + warp));
            if (p == 3 && !pairs) { DRAINED(0); mbar_arrive_if(lane == 0, bar + 8 * (BB_ZFREE + 2)); }
          }
          WRITTEN();
          mbar_arrive_if(lane == 0, bar + 8 * (BB_SFREE + 4 + warp));
          announce(r, it, mg);
          r += mg;
        }
      }
    } else {
      if (op && warp == 2) {
        unsigned char* wt = g_wt + j * (10 * OP_SLOT);
#pragma unroll 1
        for (int m0 = 0; m0 < 10; m0 += 3) {
          const int nu = m0 < 9 ? 9 : 3;
          mbar_expect_if(lane == 0, bar + 8 * BB_TMP, nu * 4096);
#pragma unroll 1
          for (int k = 0; k < nu; k++) tma2d_e(sb + BO_RING_OP + k * 4096, &P.wmap[0], (m0 + k / 3) * 64, 320 * j + 224 + 32 * (k % 3), bar + 8 * BB_TMP);
          mbar_waitw(bar + 8 * BB_TMP, m0 & 1);
          bulk_s2g_e(wt + m0 * OP_SLOT, sb + BO_RING_OP, nu * 4096);
          COMMIT();
          WRITTEN();
        }
        asm volatile("fence.acq_rel.gpu;" ::: "memory");
        int sl = 0, ph = 1, mt = rot;
#pragma unroll 1
        for (int r = -1; r < NSTEP; r++) {
#pragma unroll 1
          for (int n = r < 0 ? 7 : 0; n < (r + 1 < NSTEP ? 10 : 7); n++) {
            mbar_waitw(bar + 8 * (BB_USED + sl), ph);
            mbar_expect_if(lane == 0, bar + 8 * (BB_FULL + sl), OP_SLOT);
            bulk_g2s_e(sb + BO_RING_OP + sl * OP_SLOT, wt + mt * OP_SLOT, OP_SLOT, bar + 8 * (BB_FULL + sl));
            if (++sl == 3) { sl = 0; ph ^= 1; }
            mt = mt == 9 ? 0 : mt + 1;
          }
        }
      } else if (op) {
        mbar_waitw(bar + 8 * BB_START, 0);
#pragma unroll 1
        for (int r = 0; r < NSTEP; r++) {
          const int rb = r - RD + 2;
          const uint32_t len = fmask(r) == 3 ? 8192 : 4096;
          const unsigned char* src = g_o + (uint32_t)(r % RO * (96 * 8192) + 5 * j * len);
          wait_flags(lane < 2 ? &g_f[F_O + (lane ? NOP : j)][r] : rb >= 0 ? &g_f[F_DONE][rb] : &g_f[F_MISC][0],
                     lane < 2 ? (lane ? 1 : 5) : rb >= 0 ? rtarget(bmask(rb)) : NBC * 8);
          PTS1(35);
          auto two = [&](int k, uint32_t mb) {
            bulk_g2s_e(sb + BO_O + k * 8192, src + k * len, len == 8192 ? 16384 : 4096, mb);
            if (len != 8192) bulk_g2s_e(sb + BO_O + k * 8192 + 8192, src + k * len + 4096, 4096, mb);
          };
          mbar_expect_if(lane == 0, bar + 8 * (BB_OFULL + 2 + (r & 1)), len);
          bulk_g2s_e(sb + BO_O + (r & 1 ? 5 : 2) * 8192, src + 2 * len, len, bar + 8 * (BB_OFULL + 2 + (r & 1)));
          if (r) bar_sync(NB_EARLY, 288);
          mbar_expect_if(lane < 2, bar + 8 * (BB_OFULL + lane), 2 * len + (lane ? len / 4 : 0));
          two(0, bar + 8 * BB_OFULL);
          PTS(62); PTS1(38);
          const unsigned char* sx = src + (95 - 5 * j) * len + (j + 1) / 5 * 1024;
          if (r) bar_sync(NB_LAST, 288);
          two(3, bar + 8 * (BB_OFULL + 1));
          bulk_g2s_e(sb + BO_CARRY, sx, 1024, bar + 8 * (BB_OFULL + 1));
          if (len == 8192) bulk_g2s_e(sb + BO_CARRY + 1024, sx + 4096, 1024, bar + 8 * (BB_OFULL + 1));
          if (r && r + 1 < NSTEP) {
            mbar_waitw(bar + 8 * (BB_USED + (10 * r - 2) % 3), (10 * r - 2) / 3 & 1);
            mbar_waitw(bar + 8 * (BB_USED + (10 * r - 1) % 3), (10 * r - 1) / 3 & 1);
          }
          PTS1(64 + 35);
          BTS(r, 0);
        }
      } else if (warp == 2) {
#pragma unroll 1
        for (int r = 0, it = 0; r < NR; r++, it++) {
          const bool mg = merged(w12, r);
          const int rf = w12 ? front(r) : r, mk = !w12 ? bmask(r) : r == NSEG ? 0 : fmask(rf), pf = w12 ? rf : it;
          const bool full = mk == 3 || mg;
          if (mk) {
            const unsigned char* src = &g_acc[w12 ? 3 : 2][rf % RD][mk == 2 ? 4096 : 0];
            wait_flags(&g_f[w12 ? F_Z : F_R2 + (j & 3)][rf + mg], w12 ? rtarget(mk) : NOP * NW12 * NW34);
#pragma unroll 1
            for (int z = 0; z < 5; z++) {
              const int k = full ? z - (z > 0) : z >> 1;
              const uint32_t fb = bar + 8 * (BB_FULL + z), dst = sb + BO_RING_MLP + 2 * k % 3 * 16384 + (!full ? (z & 1) * 4096 : z == 1 ? -16384 : 0);
              if (full ? z != 1 : !(z & 1)) mbar_waitw(bar + 8 * (k < 3 ? BB_ZFREE + k : BB_EMPTY), (k < 3 ? it + 1 : pf) & 1);
              if (z == 0) PTS(62);
              mbar_expect_if(lane == 0, fb, !full ? 8192 : z == 4 ? 32768 : 16384);
              bulk_g2s_e(dst, src + z * 16384, mk == 3 ? 16384 : 4096, fb);
              if (mk != 3) bulk_g2s_e(dst + 8192, src + z * 16384 + 8192, 4096, fb);
              if (mg) {
                const unsigned char* s2 = &g_acc[2][(r + 1) % RD][4096 + z * 16384];
                bulk_g2s_e(dst + 4096, s2, 4096, fb); bulk_g2s_e(dst + 12288, s2 + 8192, 4096, fb);
              }
              if (full && z == 4) { mbar_waitw(bar + 8 * (BB_EMPTY + 1), pf & 1); bulk_g2s_e(sb + BO_RING_MLP - 16384, g_wx[role - NOP], 16384, fb); }
              if (z == 0) BTS(r, 0);
            }
          }
          if (!w12) {
#pragma unroll 1
            for (int z = full ? 2 : 0; z < 5; z++) mbar_waitw(bar + 8 * (BB_FULL + z), it & 1);
            red_if(lane == 0, &g_f[F_GOT][r]);
#pragma unroll 1
            for (int c = j; c < (r + RD < NSTEP ? 80 : 0); c += NW34) bulk_s2g_e(&g_acc[c / 40][r % RD][c % 40 * 2048], sb + BO_CARRY, 2048);
            COMMIT();
            wait_flags(&g_f[F_GOT][r], NW34);
            mbar_arrive_if(lane == 0, bar + 8 * BB_GO);
            WRITTEN();
          }
          mbar_waitw(bar + 8 * BB_DONE, (it + 1) & 1);
          mbar_arrive_if(lane == 0, bar + 8 * BB_DONE);
          r += mg;
        }
      } else {
#pragma unroll 1
        for (int r0 = 0, it = 0; r0 < (w12 ? NSTEP : NR); r0++, it++) {
          const bool mg = merged(w12, r0), idle = !mg && !((w12 ? fmask(r0) : bmask(r0)) >> (lane >> 4) & 1);
          const int r = r0 + (mg ? lane >> 4 : 0);
          r0 += mg;
          uint32_t t0, t1;
          int n = 0;
          mbar_waitw(bar + 8 * BB_FULL, it & 1);
          do {
            asm volatile("ld.relaxed.gpu.global.v2.u32 {%0,%1}, [%2];" : "=r"(t0), "=r"(t1) : "l"(&g_st2[!w12][r % RD][2 * (mg ? lane | 16 : lane)]) : "memory");
            if (++n > SPIN_LIMIT) FAIL();
          } while (!__all_sync(~0u, idle || (((t0 ^ (r + 1)) | (t1 ^ (r + 1))) & 127) == 0));
          sts32(sb + BO_STAT + (lane & 3) * 32 + (lane >> 2) * 4, pack2h(__uint_as_float(t0), __uint_as_float(t1)));
          __syncwarp();
          mbar_arrive_if(lane == 0, bar + 8 * BB_STAT);
          PTS(63);
        }
      }
    }
    bar_arrive(NB_END, 512);
  } else if (wg == 2) {
    asm volatile("setmaxnreg.dec.sync.aligned.u32 40;");
    const int ord = uni(lds32(sb + BO_BOX + 4));
    const int g2 = warp * 12 + ord - 24, gw = ord < 16 ? warp * 16 + ord : ord < 24 ? 80 + warp * 8 + ord : g2 < 32 ? 64 + g2 : 96 + g2;
    const int row = gw < 64 ? gw : gw < 96 ? gw - 64 : gw < 128 ? 2 * gw - 192 : 2 * gw - 224;
    if (row >= 32) {
#pragma unroll 1
      for (int t = 4 * NBC + (gw < 64 ? gw - 32 : gw - 80); t < S_LEN; t += 64) ln0(t);
    }
    if (gw < 64) rloop<0>(row, gw & 3, role, P.x, P.out);
    else if (gw < 96) rloop<2>(row, gw & 3, role, P.x, P.out);
    else if (gw < 128) rloop<1>(row, gw & 3, role, P.x, P.out);
    else rloop<4>(row, gw & 3, role, P.x, P.out);
    asm volatile("griddepcontrol.wait;" ::: "memory");
    const int t = threadIdx.x & 127;
    for (int i = (blockIdx.x * 128 + t) * 4; i < 4 * NCL * 2560; i += NBC * 512)
      *reinterpret_cast<uint4*>(&g_part[0][0][0][0] + i) = make_uint4(0u, 0u, 0u, 0u);
    bar_sync(NB_END, 512);
    if (t == 0) {
      uint32_t n;
      asm volatile("atom.acq_rel.gpu.global.add.u32 %0, [%1], 1;" : "=r"(n) : "l"(&g_f[F_MISC][64]) : "memory");
      sts32(sb + BO_BOX, n);
    }
    bar_sync(NB_END2, 128);
    if (lds32(sb + BO_BOX) == NBC - 1) {
      for (int i = t; i < F_NUM * 24; i += 128) reinterpret_cast<uint4*>(&g_f[0][0])[i] = make_uint4(0u, 0u, 0u, 0u);
      g_xready[t][0] = 0; g_tpc[t] = 0;
    }
  } else {
    asm volatile("setmaxnreg.inc.sync.aligned.u32 224;");
    LANE_INIT();
    for (int i = blockIdx.x * 256 + threadIdx.x; i < 2 * RD * TILE_B / 16; i += NBC * 256) reinterpret_cast<uint4*>(&g_acc[0][0][0])[i] = make_uint4(0u, 0u, 0u, 0u);
    warp_signal(&g_f[F_MISC][0], lane);
    const int mt0 = (rot + wg) % 10;
    auto boxes = [&](int ss) {
      const int nb = op && ss ? 3 : 4;
      const uint32_t base = sb + (ss ? BO_RES + wg * OP_RES : wg * 83968);
      mbar_expect_if(warp == 0 && lane == 0, bar + 8 * (BB_W + wg), nb * 20480 + (op ? 2048 : 0));
      bar_sync(NB_H, 256);
      if (warp < nb) {
#pragma unroll 1
        for (int i = warp; i < 5 * nb; i += nb) {
          const int p = op ? i / nb : (i - 10) >> 1, mt = (mt0 + 2 * p) % 10;
          const bool first = !op && i < 10;
          tma2d_e(op || !ss ? base + i * 4096 : sb + (first ? BO_W1 : -81920) + (2 * i + wg) * 4096, &P.wmap[op ? 0 : (w12 ? 1 : 3) + !first], first ? 128 * j + 64 * wg : mt * 64,
                  op ? 320 * j + 64 * warp + 32 * ss : first ? 64 * i + 32 * ss : 128 * j + 32 * (i & 1) + 64 * ss, bar + 8 * (BB_W + wg));
        }
      }
      if (op && warp == 3) tma2d_e(base + nb * 20480, &P.wo16, (mt0 + 2 * ss) % 10 * 64, 95 * 64 + (j + 1) / 5 * 16, bar + 8 * (BB_W + wg));
      mbar_waitw(bar + 8 * (BB_W + wg), ss);
    };
    uint32_t W[164];
    boxes(0);
    load_w<41>(W, sb + wg * 83968, warp, lane);
    fence_async();
    boxes(1);
    if (!op) {
      float cs[2] = {0.f, 0.f};
      const uint32_t a0 = sb + BO_W1 + wg * 4096 + ((lane >> 4) * 8 + (lane & 7)) * 128 + (((warp * 2 + ((lane >> 3) & 1)) ^ (lane & 7)) << 4);
#pragma unroll
      for (int i = 0; i < 80; i++) cs[i & 1] += bf_lo(W[i]) + bf_hi(W[i]);
#pragma unroll 1
      for (int i = 0; i < 60; i++) {
        uint32_t t[4];
        const uint32_t ad = a0 + (i % 20 >> 1) * 8192 + (i & 1) * 2048 - (i >= 40 ? BO_W1 : 0);
        ldsm4t(t[0], t[1], t[2], t[3], ad);
#pragma unroll
        for (int k = 0; k < 4; k++) {
          if (i < 20) cs[k & 1] += bf_lo(t[k]) + bf_hi(t[k]);
          const float mu = i < 40 ? cs[k & 1] : 0.f;
          t[k] = pack2h(bf_lo(t[k]) - mu, bf_hi(t[k]) - mu);
        }
        if (i >= 20) stsm4t(ad, t[0], t[1], t[2], t[3]);
        if (i == 19) {
#pragma unroll
          for (int k = 0; k < 2; k++) { cs[k] += __shfl_xor_sync(~0u, cs[k], 1); cs[k] += __shfl_xor_sync(~0u, cs[k], 2); cs[k] *= 1.f / DM; }
        }
      }
      const uint32_t z = dep0(__float_as_uint(cs[0]), lane);
#pragma unroll
      for (int i = 0; i < 80; i++) { W[i] = pack2h(bf_lo(W[i] | z) - cs[i & 1], bf_hi(W[i] | z) - cs[i & 1]); W[80 + i] = pack2h(bf_lo(W[80 + i]), bf_hi(W[80 + i])); }
      fence_async();
      bar_sync(NB_H, 256);
      if (wg + warp == 0) { bulk_s2g_e(g_wx[role - NOP], sb + BO_RING_MLP - 16384, 16384); COMMIT(); WRITTEN(); asm volatile("fence.acq_rel.gpu;" ::: "memory"); }
    }
    if (warp == 0) BTS(94, 6 + wg);
    const Dsc blo = {P.desc, 1}, alo = blo + wg * (op ? OP_RES / 16 : 256);
    if (op) {
      Ring rg = {(uint32_t)wg, 0};
      mbar_arrive_if(lane == 0, bar + 8 * BB_START);
      if (wg) bar_arrive(NB_PP, 256);
      const Dsc xlo = {P.desc32, 1};
#pragma unroll 1
      for (int r = 0; r < NSTEP; r++) {
        asm volatile("" : "+r"(lane));
        if (fmask(r) == 3) op_round<64>(W, bar, alo, blo, xlo, j == 0, rg, wg, warp, lane, r);
        else op_round<32>(W, bar, alo, blo, xlo, j == 0, rg, wg, warp, lane, r);
        if (warp == 0) BTS(r, 2 + wg);
      }
    } else {
      const int q4 = (128 * j + 64 * wg + 16 * warp) / 160, off = w12 ? (0x0413 >> (4 * q4)) & 7 : 0;
#pragma unroll 1
      for (int r0 = 0, r = 0; r0 < NR; r0++, r++) {
        asm volatile("" : "+r"(lane));
        const bool mg = merged(w12, r0);
        const int bm = mg ? 3 : bmask(r0), rf = w12 ? front(r) : r, fm = !w12 ? bm : r == NSEG ? 0 : fmask(rf);
        if (fm == 3) phase1<64>(W, sb, alo, blo, 0, wg, warp, lane, w12, off, r, rf);
        else if (fm) phase1<32>(W, sb, alo, blo, fm >> 1, wg, warp, lane, w12, off, r, rf);
        else { mbar_waitu(bar + 8 * (BB_SFREE + 4 + wg), (r + 1) & 1); carry_in(sb, wg, warp, lane); }
        CTS(33);
        fence_async();
        bar_sync(NB_H, 256);
        mbar_arrive_if(wg == 1 && warp == 0 && lane < 2, bar + 8 * BB_ZFREE);
        if (wg + warp == 0) BTS(r0, 1);
        if (bm == 3) phase2<64>(W, bar, alo, blo, wg, warp, lane, r);
        else phase2<32>(W, bar, alo, blo + (bm >> 1) * 256, wg, warp, lane, r);
        if (warp == 0) BTS(r0, 2 + wg);
        r0 += mg;
      }
    }
    CTS_OUT();
    bar_arrive(NB_END, 512);
  }
}

typedef CUresult (*EncodeFn)(CUtensorMap*, CUtensorMapDataType, cuuint32_t, void*, const cuuint64_t*, const cuuint64_t*, const cuuint32_t*,
                             const cuuint32_t*, CUtensorMapInterleave, CUtensorMapSwizzle, CUtensorMapL2promotion, CUtensorMapFloatOOBfill);
static void make_map(EncodeFn fn, CUtensorMap* tm, const void* ptr, uint64_t cols, uint64_t rows, uint32_t bc, uint32_t br) {
  cuuint64_t dims[2] = {cols, rows}; cuuint64_t strides[1] = {cols * 2}; cuuint32_t box[2] = {bc, br}; cuuint32_t es[2] = {1, 1};
  fn(tm, CU_TENSOR_MAP_DATA_TYPE_BFLOAT16, 2, const_cast<void*>(ptr), dims, strides, box, es, CU_TENSOR_MAP_INTERLEAVE_NONE,
     CU_TENSOR_MAP_SWIZZLE_128B, CU_TENSOR_MAP_L2_PROMOTION_L2_256B, CU_TENSOR_MAP_FLOAT_OOB_FILL_NONE);
}
#define dbg_a_only 0
extern "C" void kernel_launch(void* const* d_in, const int* in_sizes, int n_in, void* d_out, int out_size) {
  void* fnp = nullptr; cudaDriverEntryPointQueryResult qr;
  cudaGetDriverEntryPoint("cuTensorMapEncodeTiled", &fnp, cudaEnableDefault, &qr);
  EncodeFn fn = (EncodeFn)fnp;
  cudaStream_t st = cudaStreamPerThread;
  cudaFuncSetAttribute(bworker_kernel, cudaFuncAttributeMaxDynamicSharedMemorySize, B_SMEM);
  {
    AMaps M;
    for (int i = 0; i < 3; i++) make_map(fn, &M.w16[i], d_in[2 + i], HD, DM, 64, 16);
    M.wv = (const __nv_bfloat16*)d_in[4];
    make_map(fn, &M.wo32, d_in[5], DM, HD, 64, 32);
    const uint32_t hi[5] = {dhi(TILE_SBO, 3), dhi(1024, 1), dhi(1024, 0), dhi(PL_SZ, 0), dhi(896, 0)};
    for (int i = 0; i < 5; i++) M.d[i] = (uint64_t)hi[i] << 32;
    cudaFuncSetAttribute(acore_kernel, cudaFuncAttributeMaxDynamicSharedMemorySize, A_SMEM);
    cudaFuncSetAttribute(acore_kernel, cudaFuncAttributeNonPortableClusterSizeAllowed, 1);
    cudaLaunchConfig_t cfg = {};
    cfg.gridDim = dim3(CL_SIZE * NCL); cfg.blockDim = dim3(512); cfg.dynamicSmemBytes = A_SMEM; cfg.stream = st;
    cudaLaunchAttribute at[1]; at[0].id = cudaLaunchAttributeClusterDimension;
    at[0].val.clusterDim.x = CL_SIZE; at[0].val.clusterDim.y = 1; at[0].val.clusterDim.z = 1;
    cfg.attrs = at; cfg.numAttrs = 1;
    cudaLaunchKernelEx(&cfg, acore_kernel, M, (const __nv_bfloat16*)d_in[1], dbg_a_only ? 0 : 1);
  }
  if (!dbg_a_only) {
    BParams P;
    make_map(fn, &P.wmap[0], d_in[5], DM, HD, 64, 32);
    make_map(fn, &P.wo16, d_in[5], DM, HD, 64, 16);
    make_map(fn, &P.wmap[1], d_in[8], DM, DM, 64, 32);
    make_map(fn, &P.wmap[2], d_in[9], DM, DM, 64, 32);
    make_map(fn, &P.wmap[3], d_in[10], FF, DM, 64, 32);
    make_map(fn, &P.wmap[4], d_in[11], DM, FF, 64, 32);
    P.x = (const __nv_bfloat16*)d_in[0];
    P.out = (__nv_bfloat16*)d_out;
    P.desc = (uint64_t)dhi(1024, 1) << 32;
    P.desc32 = (uint64_t)dhi(256, 3) << 32;
    cudaLaunchConfig_t cfg = {};
    cfg.gridDim = dim3(NBC); cfg.blockDim = dim3(512); cfg.dynamicSmemBytes = B_SMEM; cfg.stream = st;
    cudaLaunchAttribute at[1]; at[0].id = cudaLaunchAttributeProgrammaticStreamSerialization; at[0].val.programmaticStreamSerializationAllowed = 1;
    cfg.attrs = at; cfg.numAttrs = 1;
    cudaLaunchKernelEx(&cfg, bworker_kernel, P);
  }
}
```

```cpp
#include <cuda_runtime.h>
#include <cuda_bf16.h>
#include <cuda.h>
#include <stdint.h>

#define S_LEN 2048
#define DM 640
#define NH 32
#define DH 192
#define HD 6144
#define NSEG 64
#define FF 1536

__device__ __forceinline__ uint32_t smem_u32(const void* p) { return (uint32_t)__cvta_generic_to_shared(p); }
__device__ __forceinline__ uint32_t mapa(uint32_t a, uint32_t r) {
  uint32_t o; asm volatile("mapa.shared::cluster.u32 %0, %1, %2;" : "=r"(o) : "r"(a), "r"(r)); return o; }
__device__ __forceinline__ void mbar_init(uint32_t b, uint32_t c) {
  asm volatile("mbarrier.init.shared::cta.b64 [%0], %1;" :: "r"(b), "r"(c) : "memory"); }
__device__ __forceinline__ void mbar_expect(uint32_t b, uint32_t tx) {
  asm volatile("mbarrier.arrive.expect_tx.shared::cta.b64 _, [%0], %1;" :: "r"(b), "r"(tx) : "memory"); }
__device__ __forceinline__ void mbar_expect_if(bool p, uint32_t b, uint32_t tx) {
  asm volatile("{\n.reg .pred q;\nsetp.ne.u32 q, %2, 0;\n@q mbarrier.arrive.expect_tx.shared::cta.b64 _, [%0], %1;\n}" :: "r"(b), "r"(tx), "r"((uint32_t)p) : "memory"); }
__device__ __forceinline__ void mbar_arrive_if(bool p, uint32_t b) {
  asm volatile("{\n.reg .pred q;\nsetp.ne.u32 q, %1, 0;\n@q mbarrier.arrive.shared::cta.b64 _, [%0];\n}" :: "r"(b), "r"((uint32_t)p) : "memory"); }
__device__ __forceinline__ void mbar_arrive_remote_if(bool p, uint32_t rb) {
  asm volatile("{\n.reg .pred q;\nsetp.ne.u32 q, %1, 0;\n@q mbarrier.arrive.relaxed.cluster.shared::cluster.b64 _, [%0];\n}" :: "r"(rb), "r"((uint32_t)p) : "memory"); }
#define SPIN_LIMIT 4000000
#define FAIL() asm volatile("st.global.u32 [%0], 0;" :: "l"(8ull) : "memory")
#define CFENCE() asm volatile("fence.proxy.async::generic.acquire.sync_restrict::shared::cluster.cluster;" ::: "memory")
#define TIMEOUT_ACT "@!p st.shared.u32 [%0+1], 0;"
#define WAIT_HINT ", 20000"
#define WAIT_LIM "200000"
__device__ __forceinline__ void mbar_slow(uint32_t b, uint32_t ph) {
  asm volatile("{\n.reg .pred p, q;\n.reg .u32 n;\nmov.u32 n, 0;\n"
               "WL:\nmbarrier.try_wait.parity.shared::cta.b64 p, [%0], %1" WAIT_HINT ";\nadd.u32 n, n, 1;\nsetp.lt.and.u32 q, n, " WAIT_LIM ", !p;\n@q bra.uni WL;\n"
               TIMEOUT_ACT "\n}" :: "r"(b), "r"(ph) : "memory"); }
__device__ __forceinline__ void mbar_waitw(uint32_t b, uint32_t ph) {
  asm volatile("{\n.reg .pred p, q;\n.reg .u32 n;\nmbarrier.try_wait.parity.shared::cta.b64 p, [%0], %1;\n@p bra.uni WD;\nmov.u32 n, 0;\n"
               "WL:\nmbarrier.try_wait.parity.shared::cta.b64 p, [%0], %1" WAIT_HINT ";\nadd.u32 n, n, 1;\nsetp.lt.and.u32 q, n, " WAIT_LIM ", !p;\n@q bra.uni WL;\n"
               TIMEOUT_ACT "\nWD:\n}" :: "r"(b), "r"(ph) : "memory"); }
__device__ __forceinline__ void mbar_waitw2(uint32_t b0, uint32_t b1, uint32_t ph) {
  uint32_t ok;
  asm volatile("{\n.reg .pred p, r;\nmbarrier.try_wait.parity.shared::cta.b64 p, [%1], %3;\nmbarrier.try_wait.parity.shared::cta.b64 r, [%2], %3;\n"
               "and.pred p, p, r;\nselp.u32 %0, 1, 0, p;\n}" : "=r"(ok) : "r"(b0), "r"(b1), "r"(ph) : "memory");
  if (__builtin_expect(!__all_sync(~0u, ok), 0)) { mbar_slow(b0, ph); mbar_slow(b1, ph); }
}
__device__ __forceinline__ void mbar_waitu(uint32_t b, uint32_t ph) {
  asm volatile("{\n.reg .pred p;\nmbarrier.try_wait.parity.shared::cta.b64 p, [%0], %1;\n@p bra.uni WD;\n"
               "WL:\nmbarrier.try_wait.parity.shared::cta.b64 p, [%0], %1" WAIT_HINT ";\n@!p bra.uni WL;\nWD:\n}" :: "r"(b), "r"(ph) : "memory"); }
__device__ __forceinline__ void mbar_waitu2(uint32_t b0, uint32_t b1, uint32_t ph) {
  asm volatile("{\n.reg .pred p, r;\nWL:\nmbarrier.try_wait.parity.shared::cta.b64 p, [%0], %2;\nmbarrier.try_wait.parity.shared::cta.b64 r, [%1], %2;\n"
               "and.pred p, p, r;\n@!p bra.uni WL;\n}" :: "r"(b0), "r"(b1), "r"(ph) : "memory"); }
__device__ __forceinline__ void mbar_waitw4(uint32_t b, uint32_t ph) { mbar_waitw2(b, b + 8, ph); mbar_waitw2(b + 16, b + 24, ph); }
__device__ __forceinline__ uint32_t clock32() { uint32_t t; asm volatile("mov.u32 %0, %%clock;" : "=r"(t) :: "memory"); return t; }
template <int L> __device__ __forceinline__ uint32_t lop3(uint32_t a, uint32_t b, uint32_t c) {
  uint32_t r; asm("lop3.b32 %0, %1, %2, %3, %4;" : "=r"(r) : "r"(a), "r"(b), "r"(c), "n"(L)); return r; }
__device__ __forceinline__ void st_async_v2_if(bool p, uint32_t a, uint32_t v0, uint32_t v1, uint32_t mb) {
  asm volatile("{\n.reg .pred q;\nsetp.ne.u32 q, %4, 0;\n@q st.async.weak.shared::cluster.mbarrier::complete_tx::bytes.v2.b32 [%0], {%1,%2}, [%3];\n}"
               :: "r"(a), "r"(v0), "r"(v1), "r"(mb), "r"((uint32_t)p) : "memory"); }
__device__ __forceinline__ void keep4(const uint32_t* r, int lane) {
  asm volatile("{\n.reg .pred q;\nsetp.lt.s32 q, %4, 0;\n@q st.shared.v4.b32 [%4], {%0,%1,%2,%3};\n}" :: "r"(r[0]), "r"(r[1]), "r"(r[2]), "r"(r[3]), "r"(lane) : "memory"); }
__device__ __forceinline__ void fence_sched(int i) {
  asm volatile("{\n.reg .pred q;\nsetp.gt.s32 q, %0, 4096;\n@q st.shared.u32 [%0], 0;\n}" :: "r"(i) : "memory"); }
__device__ __forceinline__ uint32_t hmax2bf(uint32_t a, uint32_t b) { uint32_t r; asm("max.bf16x2 %0, %1, %2;" : "=r"(r) : "r"(a), "r"(b)); return r; }
__device__ __forceinline__ uint32_t uni(uint32_t x) { return __shfl_sync(~0u, x, 0); }
__device__ __forceinline__ void bulk_g2s_mc_e(uint32_t dst, const void* src, uint32_t bytes, uint32_t mb, uint16_t mask) {
  asm volatile("{\n.reg .pred e;\nelect.sync _|e, 0xffffffff;\n"
               "@e cp.async.bulk.shared::cluster.global.mbarrier::complete_tx::bytes.multicast::cluster [%0], [%1], %2, [%3], %4;\n}"
               :: "r"(dst), "l"(src), "r"(bytes), "r"(mb), "h"(mask) : "memory"); }
__device__ __forceinline__ void bulk_s2g_e(void* dst, uint32_t src, uint32_t bytes) {
  asm volatile("{\n.reg .pred e;\nelect.sync _|e, 0xffffffff;\n@e cp.async.bulk.global.shared::cta.bulk_group [%0], [%1], %2;\n}"
               :: "l"(dst), "r"(src), "r"(bytes) : "memory"); }
__device__ __forceinline__ void bulk_g2s_e(uint32_t dst, const void* src, uint32_t bytes, uint32_t mb) {
  asm volatile("{\n.reg .pred e;\nelect.sync _|e, 0xffffffff;\n@e cp.async.bulk.shared::cluster.global.mbarrier::complete_tx::bytes [%0], [%1], %2, [%3];\n}"
               :: "r"(dst), "l"(src), "r"(bytes), "r"(mb) : "memory"); }
#define STREAM_HINT 1
__device__ __forceinline__ void bulk_s2g_es(void* dst, uint32_t src, uint32_t bytes) {
  asm volatile("{\n.reg .pred e;\n.reg .b64 pol;\ncreatepolicy.fractional.L2::evict_first.b64 pol;\nelect.sync _|e, 0xffffffff;\n"
               "@e cp.async.bulk.global.shared::cta.bulk_group.L2::cache_hint [%0], [%1], %2, pol;\n}" :: "l"(dst), "r"(src), "r"(bytes) : "memory");
}
__device__ __forceinline__ void tma2d_e(uint32_t dst, const CUtensorMap* tm, int c0, int c1, uint32_t mb) {
  asm volatile("{\n.reg .pred e;\nelect.sync _|e, 0xffffffff;\n"
               "@e cp.async.bulk.tensor.2d.shared::cluster.global.mbarrier::complete_tx::bytes [%0], [%1, {%3, %4}], [%2];\n}"
               :: "r"(dst), "l"((uint64_t)tm), "r"(mb), "r"(c0), "r"(c1) : "memory"); }
__device__ __forceinline__ uint32_t hadd2bf(uint32_t a, uint32_t b) {
  uint32_t r; asm("add.rn.bf16x2 %0, %1, %2;" : "=r"(r) : "r"(a), "r"(b)); return r; }
__device__ __forceinline__ void cluster_sync_all() {
  asm volatile("barrier.cluster.arrive.release.aligned;\nbarrier.cluster.wait.acquire.aligned;" ::: "memory"); }
__device__ __forceinline__ void bar_arrive(int id, int n) { asm volatile("bar.arrive %0, %1;" :: "r"(id), "r"(n) : "memory"); }
__device__ __forceinline__ void bar_sync(int id, int n) { asm volatile("bar.sync %0, %1;" :: "r"(id), "r"(n) : "memory"); }
__device__ __forceinline__ void fence_async() { asm volatile("fence.proxy.async.shared::cta;" ::: "memory"); }
__device__ __forceinline__ void st_async_b32(uint32_t a, uint32_t v, uint32_t mb) {
  asm volatile("st.async.weak.shared::cluster.mbarrier::complete_tx::bytes.b32 [%0], %1, [%2];" :: "r"(a), "r"(v), "r"(mb) : "memory"); }
__device__ __forceinline__ void st_async_v2(uint32_t a, uint32_t v0, uint32_t v1, uint32_t mb) {
  asm volatile("st.async.weak.shared::cluster.mbarrier::complete_tx::bytes.v2.b32 [%0], {%1,%2}, [%3];" :: "r"(a), "r"(v0), "r"(v1), "r"(mb) : "memory"); }
__device__ __forceinline__ void st_async_v4(uint32_t a, uint32_t v0, uint32_t v1, uint32_t v2, uint32_t v3, uint32_t mb) {
  asm volatile("st.async.weak.shared::cluster.mbarrier::complete_tx::bytes.v4.b32 [%0], {%1,%2,%3,%4}, [%5];" :: "r"(a), "r"(v0), "r"(v1), "r"(v2), "r"(v3), "r"(mb) : "memory"); }
__device__ __forceinline__ void ldsm4t(uint32_t& r0, uint32_t& r1, uint32_t& r2, uint32_t& r3, uint32_t a) {
  asm volatile("ldmatrix.sync.aligned.m8n8.x4.trans.shared.b16 {%0,%1,%2,%3}, [%4];" : "=r"(r0), "=r"(r1), "=r"(r2), "=r"(r3) : "r"(a) : "memory"); }
__device__ __forceinline__ void stsm2t(uint32_t a, uint32_t r0, uint32_t r1) {
  asm volatile("stmatrix.sync.aligned.m8n8.x2.trans.shared.b16 [%0], {%1,%2};" :: "r"(a), "r"(r0), "r"(r1) : "memory"); }
__device__ __forceinline__ void stsm4t(uint32_t a, uint32_t r0, uint32_t r1, uint32_t r2, uint32_t r3) {
  asm volatile("stmatrix.sync.aligned.m8n8.x4.trans.shared.b16 [%0], {%1,%2,%3,%4};" :: "r"(a), "r"(r0), "r"(r1), "r"(r2), "r"(r3) : "memory"); }
__device__ __forceinline__ uint32_t movm(uint32_t a) {
  uint32_t d; asm volatile("movmatrix.sync.aligned.m8n8.trans.b16 %0, %1;" : "=r"(d) : "r"(a)); return d; }
__device__ __forceinline__ uint32_t pack2(float lo, float hi) {
  uint32_t r; asm("cvt.rn.bf16x2.f32 %0, %1, %2;" : "=r"(r) : "f"(hi), "f"(lo)); return r; }
__device__ __forceinline__ uint32_t pack2v(float lo, float hi) {
  uint32_t r; asm volatile("cvt.rn.bf16x2.f32 %0, %1, %2;" : "=r"(r) : "f"(hi), "f"(lo)); return r; }
__device__ __forceinline__ float bf_lo(uint32_t w) { return __uint_as_float(w << 16); }
__device__ __forceinline__ float bf_hi(uint32_t w) { return __uint_as_float(w & 0xffff0000u); }
__device__ __forceinline__ uint4 lds128(uint32_t a) {
  uint4 v; asm volatile("ld.shared.v4.b32 {%0,%1,%2,%3}, [%4];" : "=r"(v.x), "=r"(v.y), "=r"(v.z), "=r"(v.w) : "r"(a) : "memory"); return v; }
__device__ __forceinline__ float rcpf(float x) { float y; asm("rcp.approx.ftz.f32 %0, %1;" : "=f"(y) : "f"(x)); return y; }
__device__ __forceinline__ void sts64(uint32_t a, uint32_t x, uint32_t y) { asm volatile("st.shared.v2.b32 [%0], {%1,%2};" :: "r"(a), "r"(x), "r"(y) : "memory"); }
__device__ __forceinline__ float ex2(float x) { float y; asm("ex2.approx.ftz.f32 %0, %1;" : "=f"(y) : "f"(x)); return y; }
__device__ __forceinline__ uint32_t lds32(uint32_t a) {
  uint32_t v; asm volatile("ld.shared.b32 %0, [%1];" : "=r"(v) : "r"(a) : "memory"); return v; }
__device__ __forceinline__ uint2 lds64(uint32_t a) {
  uint2 v; asm volatile("ld.shared.v2.b32 {%0,%1}, [%2];" : "=r"(v.x), "=r"(v.y) : "r"(a) : "memory"); return v; }
__device__ __forceinline__ void sts128(uint32_t a, uint32_t x, uint32_t y, uint32_t z, uint32_t w) {
  asm volatile("st.shared.v4.b32 [%0], {%1,%2,%3,%4};" :: "r"(a), "r"(x), "r"(y), "r"(z), "r"(w) : "memory"); }
__device__ __forceinline__ void sts32(uint32_t a, uint32_t x) { asm volatile("st.shared.b32 [%0], %1;" :: "r"(a), "r"(x) : "memory"); }
__device__ __forceinline__ void tma2d(uint32_t dst, const CUtensorMap* tm, int c0, int c1, uint32_t mb) {
  asm volatile("cp.async.bulk.tensor.2d.shared::cluster.global.mbarrier::complete_tx::bytes [%0], [%1, {%3, %4}], [%2];"
               :: "r"(dst), "l"((uint64_t)tm), "r"(mb), "r"(c0), "r"(c1) : "memory"); }
__device__ __forceinline__ void tma2d_prefetch(const CUtensorMap* tm, int c0, int c1) {
  asm volatile("cp.async.bulk.prefetch.tensor.2d.L2.global.tile [%0, {%1, %2}];" :: "l"((uint64_t)tm), "r"(c0), "r"(c1) : "memory"); }
__device__ __forceinline__ void wg_fence() { asm volatile("wgmma.fence.sync.aligned;" ::: "memory"); }
__device__ __forceinline__ void wg_commit() { asm volatile("wgmma.commit_group.sync.aligned;" ::: "memory"); }
template <int N> __device__ __forceinline__ void wg_wait() { asm volatile("wgmma.wait_group.sync.aligned %0;" :: "n"(N) : "memory"); }

#define ACC4(d) "+f"(d[0]),"+f"(d[1]),"+f"(d[2]),"+f"(d[3])
#define ACC8(d) ACC4(d), ACC4((d + 4))
#define ACC16(d) ACC8(d), ACC8((d + 8))
#define ACC20(d) ACC16(d), ACC4((d + 16))
#define ACC24(d) ACC16(d), ACC8((d + 16))
#define SMEM0 0x400
__host__ __device__ constexpr uint32_t dlo(uint32_t off, uint32_t lbo) { return ((SMEM0 + off) >> 4) | ((lbo >> 4) << 16); }
__host__ __device__ constexpr uint32_t dhi(uint32_t sbo, uint32_t swz) { return (sbo >> 4) | (swz << 30); }
#define R4S "{%0,%1,%2,%3}"
#define R8S "{%0,%1,%2,%3,%4,%5,%6,%7}"
#define R16S "{%0,%1,%2,%3,%4,%5,%6,%7,%8,%9,%10,%11,%12,%13,%14,%15}"
#define R20S "{%0,%1,%2,%3,%4,%5,%6,%7,%8,%9,%10,%11,%12,%13,%14,%15,%16,%17,%18,%19}"
#define R24S "{%0,%1,%2,%3,%4,%5,%6,%7,%8,%9,%10,%11,%12,%13,%14,%15,%16,%17,%18,%19,%20,%21,%22,%23}"
#define ACC32(d) ACC16(d), ACC16((d + 16))
#define R32S "{%0,%1,%2,%3,%4,%5,%6,%7,%8,%9,%10,%11,%12,%13,%14,%15,%16,%17,%18,%19,%20,%21,%22,%23,%24,%25,%26,%27,%28,%29,%30,%31}"
struct Dsc {
  uint64_t b; uint32_t e;
  __device__ __forceinline__ Dsc operator+(uint32_t o) const { return {b + o, e}; }
};
template <int K> __device__ __forceinline__ uint32_t fresh(int i) {
  uint32_t e; asm volatile("{\n.reg .u32 t;\nadd.u32 t, %1, %2;\nshr.u32 %0, t, %3;\n}" : "=r"(e) : "r"(i), "n"((256 << K) + 1), "n"(8 + K)); return e; }
template <int N, bool H = false> struct MM;
#define DEF_MM(N, H, T, ACCM, RS_, I0, I1, I2, I3, I4, I5, I6, I7)                                                                \
  template <> struct MM<N, H> {                                                                                                   \
    template <uint32_t BLO, int ACC>                                                                                              \
    static __device__ __forceinline__ void rs(float* d, const uint32_t* a, Dsc b0) {                                              \
      asm volatile("{\n.reg .b64 b;\nmad.wide.u32 b, %" #I7 ", %" #I5 ", %" #I4 ";\n"                                             \
                   "wgmma.mma_async.sync.aligned.m64n" #N "k16.f32." T "." T " " RS_ ", {%" #I0 ",%" #I1 ",%" #I2 ",%" #I3 "}, b, %" #I6 ", 1, 1, 0;\n}" \
                   : ACCM(d) : "r"(a[0]), "r"(a[1]), "r"(a[2]), "r"(a[3]), "l"(b0.b), "n"(BLO), "n"(ACC), "r"(b0.e)); }           \
    template <uint32_t ALO, uint32_t BLO, int ACC, int TA = 1>                                                                    \
    static __device__ __forceinline__ void ss(float* d, Dsc a0, Dsc b0) {                                                         \
      asm volatile("{\n.reg .b64 a, b;\nmad.wide.u32 a, %" #I6 ", %" #I1 ", %" #I0 ";\nmad.wide.u32 b, %" #I6 ", %" #I3 ", %" #I2 ";\n" \
                   "wgmma.mma_async.sync.aligned.m64n" #N "k16.f32." T "." T " " RS_ ", a, b, %" #I4 ", 1, 1, %" #I5 ", 0;\n}"    \
                   : ACCM(d) : "l"(a0.b), "n"(ALO), "l"(b0.b), "n"(BLO), "n"(ACC), "n"(TA), "r"(b0.e)); }                         \
  };
DEF_MM(8, false, "bf16", ACC4, R4S, 4, 5, 6, 7, 8, 9, 10, 11)
DEF_MM(16, false, "bf16", ACC8, R8S, 8, 9, 10, 11, 12, 13, 14, 15)
DEF_MM(32, false, "bf16", ACC16, R16S, 16, 17, 18, 19, 20, 21, 22, 23)
DEF_MM(40, false, "bf16", ACC20, R20S, 20, 21, 22, 23, 24, 25, 26, 27)
DEF_MM(48, false, "bf16", ACC24, R24S, 24, 25, 26, 27, 28, 29, 30, 31)
DEF_MM(64, false, "bf16", ACC32, R32S, 32, 33, 34, 35, 36, 37, 38, 39)
DEF_MM(32, true, "f16", ACC16, R16S, 16, 17, 18, 19, 20, 21, 22, 23)
DEF_MM(64, true, "f16", ACC32, R32S, 32, 33, 34, 35, 36, 37, 38, 39)

#define LAG 10
#define NSTEP (NSEG + LAG)
#define NR (NSTEP + 2)
__device__ __align__(1024) __nv_bfloat16 g_xn[2][S_LEN * DM];
#define RO 16
static_assert(RO > LAG + 1, "ring");
__device__ __align__(1024) unsigned char g_o[RO * 96 * 8192];
__device__ __align__(1024) uint32_t g_part[6][7][40][64];
#define RD 16
static_assert(2 * RD <= NSEG && NR < 96, "the tags of the last lap differ from those of the first");
#define TILE_B 81920
__device__ __align__(1024) float2 g_stat[S_LEN];
__device__ __align__(1024) uint32_t g_st2[2][RD][64];
__device__ __align__(1024) unsigned char g_acc[4][RD][TILE_B];
#define NOP 19
#define NW12 5
#define NW34 12
#define NBC (NOP + NW12 + NW34)
__device__ __align__(1024) unsigned char g_wt[NOP * 10 * 12288];
__device__ __align__(1024) unsigned char g_wx[NW12 + NW34][16384];
enum { F_O = 0, F_R1 = NOP + 1, F_R2 = F_R1 + 4, F_R3 = F_R2 + 4, F_Z = F_R3 + 4, F_DONE, F_GOT, F_MISC, F_NUM };
__device__ __align__(128) uint32_t g_f[F_NUM][96];
__device__ __align__(128) int g_xready[129][8];
__device__ uint32_t g_tpc[128];
#define TS(i)
#define TSV(i, v)
#define TSN(i)
#define TSD(i, dep)
#define BTS(k, i)
#define BTS2(k, i)
#define RTS(i)
#define RTSD(i, dep)
#define RTS_OUT()
#define CTS(i)
#define PTS(i)
#define PTS1(i)
#define CTS_OUT()
#define GTS(i)

#define CL_SIZE 15
#define NCL 7
#define SSQ 13
#define SSV 16
#define PL_SZ 5376
#define TILE_SBO 2560
#define TILE_GRP 15360
#define WS_SZ ((2 * SSQ + SSV) * 2048)
#define OFF_QK (OFF_WO + 26 * 2048)
#define OFF_TILE 0
#define OFF_WS (4 * TILE_GRP)
#define OFF_WO (OFF_WS + WS_SZ)
#define OFF_PL (OFF_QK + 20480)
#define OFF_BAR (OFF_PL + 2 * PL_SZ)
#define STG_Q OFF_TILE
#define STG_K OFF_WO
#define VA 14
#define STG_V2 (OFF_TILE + 27 * 2048)
#define OFF_O (OFF_PL + 4352)
#define LAND(k) (((k) >> 1) * TILE_GRP + ((k) & 1) * 1280)
#define LAND_F (5 * TILE_SBO)
#define OFF_XL (OFF_TILE + 3 * TILE_GRP)
#define OFF_XF (OFF_XL + LAND_F)
#define OFF_WT ((OFF_XL + TILE_SBO + 1023) & ~1023)
#define OFF_TAB (OFF_BAR + 240)
#define OFF_INV (OFF_TAB + 64)
#define OFF_TS (OFF_INV + 128)
#define A_SMEM 232448
static_assert(WS_SZ + 72 * 1024 + 2 * PL_SZ + 4 * TILE_GRP + 512 == A_SMEM && OFF_WS % 1024 == 0 && OFF_WO % 1024 == 0 && SSQ == 13, "smem map");
enum { B_W0 = 0, B_W1, B_F1, B_F2 = B_F1 + 4, B_R1 = B_F2 + 4, B_R2, B_MEMFREE, B_LANDFREE, B_OPEER, B_PLFREE, B_XFREE, B_SB, B_WOF = B_SB + 6, B_WTF, B_RS, B_NUM = B_RS + 4 };
static_assert(B_NUM <= 30, "barriers");
enum { N_C = 0, N_SISS, N_QK, N_V, N_PM, N_TURN, N_PI, N_VGO, N_O, N_PX, N_AB, N_SDONE, N_VDONE, N_G3, N_P, N_OX };

__device__ __forceinline__ bool is_dual(int j) { return j >= LAG && j < NSEG; }
__device__ __forceinline__ int sched_l(int j) { return j < NSEG ? j : NSEG + j - LAG; }
__device__ __forceinline__ int sched_f(int j) { return NSEG + j - LAG; }
__device__ __forceinline__ void wait_cnt(const int* p, int target) {
  int v, n = 0;
  do {
    asm volatile("ld.relaxed.gpu.global.b32 %0, [%1];" : "=r"(v) : "l"(p) : "memory");
    if (v >= target) break;
    if (++n > SPIN_LIMIT) FAIL();
  } while (true);
  asm volatile("fence.acquire.gpu;" ::: "memory");
  asm volatile("fence.proxy.async.global;" ::: "memory");
}
__device__ __forceinline__ void red_release(void* p, uint32_t v) { asm volatile("red.release.gpu.global.add.u32 [%0], %1;" :: "l"(p), "r"(v) : "memory"); }
__device__ __forceinline__ void red_relaxed(void* p, uint32_t v) { asm volatile("red.relaxed.gpu.global.add.u32 [%0], %1;" :: "l"(p), "r"(v) : "memory"); }
#define VMASK 0xa5294a5294ull
__host__ __device__ constexpr int popc40(unsigned long long m) { int c = 0; for (; m; m &= m - 1) c++; return c; }
static_assert(popc40(VMASK) == SSV, "mask");
__host__ __device__ constexpr int ss_idx(int ks, int n) { return n == SSV ? popc40(VMASK & ((1ull << ks) - 1)) : ks * n / 40; }
__host__ __device__ constexpr bool is_ss(int ks, int n) { return ss_idx(ks + 1, n) != ss_idx(ks, n); }
__host__ __device__ constexpr int rs_idx(int ks, int n) { return ks - ss_idx(ks, n); }

#define SL2 (0.07216878364870322f * 1.4426950408889634f)

struct Desc { Dsc tile, unit, k1, pl, p; };
__device__ __forceinline__ Desc make_desc(const uint64_t* h, uint32_t u, uint32_t e) {
  return {{h[0], e}, {h[1] + u * 128, e}, {h[2], e}, {h[3], e}, {h[4], e}};
}
template <int N, int NSS, int RG, int KS, int K1, int K0 = 0>
__device__ __forceinline__ void proj(float* acc, const uint32_t* W, const Desc& D) {
  if constexpr (KS < K1) {
    constexpr uint32_t BLO = dlo(OFF_TILE + (KS / 10) * TILE_GRP + RG * TILE_SBO + (KS % 10) * 256, 128);
    if constexpr (is_ss(KS, NSS)) MM<N>::template ss<dlo(OFF_WS + ss_idx(KS, NSS) * 2048, 0), BLO, (KS != K0)>(acc, D.unit, D.tile);
    else MM<N>::template rs<BLO, (KS != K0)>(acc, W + rs_idx(KS, NSS) * 4, D.tile);
    proj<N, NSS, RG, KS + 1, K1, K0>(acc, W, D);
  }
}
#define VST 17
template <int KS>
__device__ __forceinline__ void ld_rest(uint32_t* W, const uint32_t* p) {
  if constexpr (KS < 40) {
    if constexpr (!is_ss(KS, SSV) && rs_idx(KS, SSV) >= VST) {
#pragma unroll
      for (int i = 0; i < 4; i++) W[4 * rs_idx(KS, SSV) + i] = __ldg(p + (KS * 16 + (i >> 1) * 8) * (HD / 2) + (i & 1) * 4);
    }
    ld_rest<KS + 1>(W, p);
  }
}
template <int N>
__device__ __forceinline__ void load_w(uint32_t* W, uint32_t stage, int warp, int lane) {
  const int kr = (lane >> 4) * 8 + (lane & 7);
  const int cb = warp * 2 + ((lane >> 3) & 1);
  const uint32_t a0 = stage + kr * 128 + ((cb ^ (lane & 7)) << 4);
#pragma unroll
  for (int i = 0; i < N; i++) ldsm4t(W[4 * i], W[4 * i + 1], W[4 * i + 2], W[4 * i + 3], a0 + i * 2048);
}
template <int N, int G, int U, int OS, int ACC>
__device__ __forceinline__ void wo4(float* d, const Desc& D) {
  constexpr uint32_t WA = (U >= 4 ? OFF_WO + (U - 4) * 2048 : OFF_WT) - G * SSQ * 2048, OB = OS == 0 ? OFF_O : OS == 1 ? OFF_XL : OFF_XF;
  Dsc b = OS ? D.k1 : D.pl;
  b.e = fresh<(U < 16 ? U / 4 : U / 8 - 2) + (N == 8 ? 4 : 0)>(D.unit.e);
  MM<N>::template ss<dlo(WA, 0), dlo(OB, 128), ACC>(d, D.unit, b);
  MM<N>::template ss<dlo(WA + 2048, 0), dlo(OB + 256, 128), 1>(d, D.unit, b);
  MM<N>::template ss<dlo(WA + 4096, 0), dlo(OB + 512, 128), 1>(d, D.unit, b);
  MM<N>::template ss<dlo(WA + 6144, 0), dlo(OB + 768, 128), 1>(d, D.unit, b);
}
__device__ __forceinline__ void wo_coord(int i, int t3, int head, int& c0, int& c1) {
  const int g = i >> 1;
  const int blk = g == 0 ? 9 : (g < 4 ? g - 1 : (g - 4) >> 1) * 3 + t3;
  int sl = g < 4 ? t3 : (g & 1) ? t3 + 1 : t3 + 2;
  if (sl >= 3) sl -= 3;
  c0 = blk * 64; c1 = head * DH + sl * 64 + (i & 1) * 32;
}
__device__ __forceinline__ void tok_softmax(uint32_t sb, int job, int lane) {
  const bool w1 = job & 1;
  const int dg = (lane >> 2) - (lane & 3) * 2;
  const uint32_t lo = sb + OFF_PL + (job >> 1) * PL_SZ + (job & 1) * 1792, l8 = lo + 512 + lane * 8, pa = lo + lane * 4;
  const uint32_t km = job & 2 ? 640 : 512;
  float x[14];
  {
    const uint4 a = lds128(lo + lane * 16);
    const uint2 e = lds64(l8);
    const uint32_t c = lds32(768 + pa);
    x[0] = bf_lo(a.x); x[1] = bf_hi(a.x); x[2] = bf_lo(a.y); x[3] = bf_hi(a.y); x[4] = bf_lo(a.z); x[5] = bf_hi(a.z); x[6] = bf_lo(a.w); x[7] = bf_hi(a.w);
    x[8] = bf_lo(c); x[9] = bf_hi(c); x[10] = bf_lo(e.x); x[11] = bf_hi(e.x); x[12] = bf_lo(e.y); x[13] = bf_hi(e.y);
  }
  if (dg < 0) { x[8] = -INFINITY; if (w1) x[4] = -INFINITY; else x[10] = -INFINITY; }
  if (dg < 1) { x[9] = -INFINITY; if (w1) x[5] = -INFINITY; else x[11] = -INFINITY; }
  const float m4 = fmaxf(x[8], x[9]);
  float m0 = fmaxf(fmaxf(fmaxf(x[0], x[1]), fmaxf(x[2], x[3])), fmaxf(fmaxf(x[4], x[5]), fmaxf(x[6], x[7])));
  float m1 = fmaxf(fmaxf(x[10], x[11]), fmaxf(x[12], x[13]));
  if (w1) m1 = fmaxf(m1, m4); else m0 = fmaxf(m0, m4);
  m0 = fmaxf(m0, __shfl_xor_sync(~0u, m0, 1)); m1 = fmaxf(m1, __shfl_xor_sync(~0u, m1, 1));
  sts32(pa + (w1 ? 384 : 896 + 128), 0u); sts32(pa + 1152 - km, 0u); sts32(pa + 896 + 1152 - km, 0u); sts64(l8 + 896 - 256, 0u, 0u);
  m0 = fmaxf(m0, __shfl_xor_sync(~0u, m0, 2)); m1 = fmaxf(m1, __shfl_xor_sync(~0u, m1, 2));
  m0 *= -SL2; m1 *= -SL2;
#pragma unroll
  for (int j = 0; j < 14; j++) x[j] = ex2(fmaf(x[j], SL2, j < 8 ? m0 : j >= 10 ? m1 : w1 ? m1 : m0));
  const float l4s = x[8] + x[9];
  float l0 = ((x[0] + x[1]) + (x[2] + x[3])) + ((x[4] + x[5]) + (x[6] + x[7])), l1 = (x[10] + x[11]) + (x[12] + x[13]);
  if (w1) l1 += l4s; else l0 += l4s;
  l0 += __shfl_xor_sync(~0u, l0, 1); l1 += __shfl_xor_sync(~0u, l1, 1);
  l0 += __shfl_xor_sync(~0u, l0, 2); l1 += __shfl_xor_sync(~0u, l1, 2);
  l0 = rcpf(l0); l1 = rcpf(l1);
#pragma unroll
  for (int j = 0; j < 7; j++) {
    const float iv = j < 4 ? l0 : j > 4 ? l1 : w1 ? l1 : l0;
    sts32(pa + (j < 3 ? j * 128 : j == 3 ? km : j == 4 ? (w1 ? 896 + 128 : 384) : j == 5 ? 896 : 896 + km), pack2(x[2 * j] * iv, x[2 * j + 1] * iv));
  }
}
template <int N>
__device__ __forceinline__ void wo_phase(uint32_t sb, int wg, int warp, int lane, uint32_t par, uint32_t r1, const Desc& D) {
  const uint32_t bar = sb + OFF_BAR;
  float x[N / 2], y[N / 2];
  const uint2 ta = lds64(sb + OFF_TAB + (wg * 4 + warp) * 8);
  uint32_t xa = (ta.x & ~255u) + lane * 8, xb = (ta.x & 0xFF0000FFu) + SMEM0 + OFF_BAR, ya = (ta.y & ~255u) + lane * 8, yb = (ta.y & 0xFF0000FFu) + SMEM0 + OFF_BAR;
  asm volatile("" : "+r"(xa), "+r"(xb), "+r"(ya), "+r"(yb));
  auto scat = [&](uint32_t ad, uint32_t mb, const float* d) {
    st_async_v2(ad, pack2(d[0], d[1]), pack2(d[2], d[3]), mb);
    if (N == 16) st_async_v2(ad + LAND_F, pack2(d[4], d[5]), pack2(d[6], d[7]), mb);
  };
  if (wg == 0) {
    bar_sync(N_O, 384);
    wg_fence(); wo4<N, 0, 4, 0, 0>(x, D); wo4<N, 0, 8, 0, 0>(y, D); wg_commit();
    mbar_waitu(bar + 8 * B_OPEER, par);
    CFENCE(); wg_fence(); wo4<N, 0, 16, 1, 1>(x, D); wo4<N, 0, 20, 2, 1>(x, D); wg_commit();
    wo4<N, 0, 24, 1, 1>(y, D); wg_commit();
    mbar_waitu2(bar + 8 * B_WOF, bar + 8 * B_MEMFREE, par);
    wg_fence(); wo4<N, 0, 28, 2, 1>(y, D); wg_commit();
    bar_arrive(N_AB, 256);
    wg_wait<2>(); scat(xa, xb, x);
    wg_wait<0>(); scat(ya, yb, y);
  } else {
    bar_sync(N_O, 384);
    wg_fence(); wo4<N, 1, 0, 0, 0>(x, D); wg_commit(); wo4<N, 1, 12, 0, 0>(y, D); wg_commit();
    wg_wait<1>(); mbar_arrive_remote_if(lane == 0, r1);
    mbar_waitu(bar + 8 * B_MEMFREE, par);
    scat(xa, xb, x);
    bar_sync(N_AB, 256);
    CFENCE(); wg_fence(); wo4<N, 1, 32, 1, 1>(y, D); wo4<N, 1, 36, 2, 1>(y, D); wg_commit();
    bar_arrive(N_TURN, 256);
    wg_wait<0>(); scat(ya, yb, y);
  }
}
#define DS_DUAL 10
#define DS_SINGLE 20
#define POLL_GAP 100
#define POLL_GAPD 0
#define TOK_DELAY 250
#define UMAX 40
#define VD1 10
#define VS2 20
#define VS1 4
struct AMaps { CUtensorMap w16[3], wo32; uint64_t d[5]; const __nv_bfloat16* wv; };
__global__ void __launch_bounds__(512, 1)
acore_kernel(const __grid_constant__ AMaps M, const __nv_bfloat16* __restrict__ mem0, int sync_b) {
  extern __shared__ __align__(1024) unsigned char smem_raw[];
  const uint32_t sb = smem_u32(smem_raw);
  GTS(24);
  if (threadIdx.x == 480) {
    uint32_t smid; asm volatile("mov.u32 %0, %%smid;" : "=r"(smid));
    g_tpc[(smid >> 1) & 127] = blockIdx.x - CL_SIZE < 3 * CL_SIZE && blockIdx.x % CL_SIZE >= 12 ? 1 : 2;
    asm volatile("griddepcontrol.launch_dependents;");
  }
  const int lane0 = threadIdx.x & 31;
#define LANE_INIT() int lane; asm volatile("mov.u32 %0, %%laneid;" : "=r"(lane))
  const int warp = __shfl_sync(~0u, (threadIdx.x >> 5) & 3, 0);
  const int cl = blockIdx.x / CL_SIZE;
  const uint32_t rank = blockIdx.x - cl * CL_SIZE;
  const int nh = cl >= 1 && cl <= 3 ? 4 : 5;
  const int nA = 3 * nh;
  const int wg = __shfl_sync(~0u, (int)rank < nA ? threadIdx.x >> 7 : 4, 0);
  const int head = (cl < 4 ? (cl ? 1 + 4 * cl : 0) : 5 * cl - 3) + rank / 3;
  const int t3 = rank % 3;
  const int col0 = head * DH + t3 * 64;
  const uint32_t bar = sb + OFF_BAR;
  const uint32_t rb0 = SMEM0;
  const uint16_t mcmask = (uint16_t)((1u << nA) - 1);
  const uint32_t nxt = sb + ((t3 == 2 ? -2 : 1) << 24), prv = sb + ((t3 == 0 ? 2 : -1) << 24);
  const int ig = (int)rank - (nA - 4);

  if (threadIdx.x == 0) {
    if (mapa(sb, nA - 1) != rb0 + ((nA - 1) << 24) || mapa(sb, 0) != rb0 || mapa(sb, 1) != rb0 + (1u << 24) || sb != SMEM0 + (rank << 24)) FAIL();
    for (int i = 0; i < B_NUM; i++)
      mbar_init(bar + 8 * i, i == B_R1 ? 4 * nA : i == B_R2 ? 12 * nA : i == B_MEMFREE ? nA : i == B_LANDFREE ? 4 * nA : i == B_PLFREE || i == B_XFREE ? 2 : 1);
    asm volatile("fence.mbarrier_init.release.cluster;" ::: "memory");
    mbar_expect(bar + 8 * B_W0, (80 + SSV + VST) * 2048);
  }
  __syncthreads();
  if (lane0 == 0) {
    const int w12 = wg * 4 + warp;
    if (w12 < 10) {
#pragma unroll 1
      for (int ks = 4 * w12; ks < 4 * w12 + 4; ks++) {
        const bool ss = is_ss(ks, SSQ);
        tma2d(ss ? sb + OFF_WS + ss_idx(ks, SSQ) * 2048 : sb + STG_Q + rs_idx(ks, SSQ) * 2048, &M.w16[0], col0, ks * 16, bar + 8 * B_W0);
        tma2d(ss ? sb + OFF_WS + (SSQ + ss_idx(ks, SSQ)) * 2048 : sb + STG_K + rs_idx(ks, SSQ) * 2048, &M.w16[1], col0, ks * 16, bar + 8 * B_W0);
        if (is_ss(ks, SSV)) tma2d(sb + OFF_WS + (2 * SSQ + ss_idx(ks, SSV)) * 2048, &M.w16[2], col0, ks * 16, bar + 8 * B_W0);
        else if (rs_idx(ks, SSV) < VST) tma2d(sb + (rs_idx(ks, SSV) < VA ? STG_K + 27 * 2048 : STG_V2 - VA * 2048) + rs_idx(ks, SSV) * 2048, &M.w16[2], col0, ks * 16, bar + 8 * B_W0);
      }
    }
  }
  if (lane0 < 2 && wg < 2) {
    const int u = 4 * (wg ? (lane0 ? 6 + t3 : 9) : (lane0 ? 3 + t3 : t3)) + warp;
    const int li = (u >= nA) + (u >= 2 * nA) + (u >= 3 * nA);
    sts32(sb + OFF_TAB + (wg * 4 + warp) * 8 + lane0 * 4,
          rb0 + ((u - li * nA) << 24) + OFF_TILE + LAND(li + (u >= 36 ? t3 : 0)) + (rank / 3) * 256 + 8 * (B_RS + li));
  }
  __syncthreads();
  GTS(25);

  auto issue_tok = [&](int sc, int fb, int rel = -1, uint32_t ph = 0) {
    if (sync_b) wait_cnt(&g_xready[sc][0], 32);
    if (rel >= 0) mbar_waitu(bar + 8 * rel, ph);
    bulk_g2s_mc_e(sb + OFF_TILE + ig * TILE_GRP + TILE_SBO, &g_xn[0][0] + uni(sc * (32 * DM)) + ig * 5120, 10240, bar + 8 * (fb + ig), mcmask);
  };
#define POLL(d, q) _Pragma("unroll") for (int k = 0; k < NCL; k++) \
      asm volatile("ld.relaxed.gpu.global.v2.b32 {%0,%1}, [%2];" : "=r"(d[k].x), "=r"(d[k].y) : "l"(q + k * 2560) : "memory")
#define L3(L, a, b, c) lop3<L>(a, b, c)
#define TAGS(L, d) L3(L, L3(L, L3(L, d[0].x, d[0].y, d[1].x), L3(L, d[1].y, d[2].x, d[2].y), L3(L, d[3].x, d[3].y, d[4].x)), L3(L, d[4].y, d[5].x, d[5].y), L3(L, d[6].x, d[6].y, d[6].y))
    auto deliver = [&](uint2* pa, const uint32_t* gq, int u, int c, int dc, int ds, int step, bool first, int lane) {
      const uint32_t off = uni(OFF_TILE + ((u * 205) >> 11) * (TILE_GRP - TILE_SBO) + u * 256 + dc * LAND_F), boff = uni(OFF_BAR + 8 * (B_F1 + ((u * 205) >> 11)));
      const uint32_t* mi = &g_part[4][0][0][0] + uni((c * NCL + cl) * 2560 + u * 64);
      mbar_waitu(bar + 8 * B_LANDFREE, step & 1);
      int n = 0;
      while (true) {
        const bool ok = __all_sync(~0u, ((step & 2 ? ~TAGS(0xFE, pa) : TAGS(0x80, pa)) & 1) != 0);
        if (ok) break;
        if (++n > SPIN_LIMIT) FAIL();
        POLL(pa, gq);
      }
      if (warp == 0 && first) { TS(19); TSV(10, n); }
      const uint32_t w0 = hadd2bf(hadd2bf(hadd2bf(pa[0].x, pa[1].x), hadd2bf(pa[2].x, pa[3].x)), hadd2bf(hadd2bf(pa[4].x, pa[5].x), pa[6].x));
      const uint32_t w1 = hadd2bf(hadd2bf(hadd2bf(pa[0].y, pa[1].y), hadd2bf(pa[2].y, pa[3].y)), hadd2bf(hadd2bf(pa[4].y, pa[5].y), pa[6].y));
      if (u < ds) {
        const uint32_t da = SMEM0 + off + lane * 8, db = SMEM0 + boff;
#pragma unroll
        for (int d = 0; d < 12; d++) st_async_v2((d << 24) + da, w0, w1, (d << 24) + db);
#pragma unroll
        for (int d = 12; d < 15; d++) st_async_v2_if(nA == 15, (d << 24) + da, w0, w1, (d << 24) + db);
      } else {
        *reinterpret_cast<uint2*>(const_cast<uint32_t*>(gq) + ((4 - 2 * (step & 1)) * NCL + cl) * 2560) = make_uint2(w0, w1);
        asm volatile("fence.proxy.async.global;" ::: "memory");
        __syncwarp();
        bulk_g2s_mc_e(sb + off, mi, 256, sb + boff, mcmask);
      }
    };
#define REL(b, g) mbar_arrive_remote_if(lane == 0, rb0 + ((nA - 4 + (g)) << 24) + OFF_BAR + 8 * (b))

  if (wg < 2) {
    asm volatile("setmaxnreg.inc.sync.aligned.u32 160;");
    LANE_INIT();
    uint32_t W[4 * (40 - SSQ)];
    mbar_waitw(bar + 8 * B_W0, 0);
    GTS(26);
    load_w<40 - SSQ>(W, sb + (wg ? STG_K : STG_Q), warp, lane);
    fence_async();
    bar_sync(1, 384);
    cluster_sync_all();
#define DESC(k) const Desc D = make_desc(M.d, min(wg, 2) * SSQ, fresh<k>(step))
    GTS(27);
#pragma unroll 1
    for (int step = -1; step < NSTEP; step++) {
      const uint32_t par = step & 1;
      asm volatile("" : "+r"(lane));
      const bool dual = is_dual(step), has_next = step + 1 < NSTEP;
#define QK_SA (sb + OFF_QK + wg * 15360 + (2 * warp + ((lane >> 3) & 1)) * 128 + (lane & 7) * 16)
#define QK_F (wg ? -5120 : 5120)
#define QK_S12 ((wg ? (lane >> 4) : 1 + 2 * (lane >> 4)) * 1024)
#define QK_S34 ((wg ? 2 + (lane >> 4) : 2 - 2 * (lane >> 4)) * 1024)
      if (step >= 0) {
        if (dual) {
          DESC(0);
          float acc[24];
          mbar_waitu(bar + 8 * (B_F1 + 0), par);
          if (wg + warp == 0) { TS(0); TSN(1); }
          CFENCE(); wg_fence(); proj<48, SSQ, 0, 0, 10>(acc, W, D); wg_commit();
          mbar_waitu(bar + 8 * (B_F1 + 1), par);
          CFENCE(); wg_fence(); proj<48, SSQ, 0, 10, 20>(acc, W, D); wg_commit();
          mbar_waitu(bar + 8 * (B_F1 + 2), par);
          CFENCE(); wg_fence(); proj<48, SSQ, 0, 20, 30>(acc, W, D); wg_commit();
          mbar_waitu(bar + 8 * (B_F1 + 3), par);
          if (wg + warp == 0) TS(2);
          CFENCE(); wg_fence(); proj<48, SSQ, 0, 30, 40>(acc, W, D); wg_commit();
          bar_arrive(N_VGO, 384);
          mbar_waitu(bar + 8 * B_PLFREE, par);
          const uint32_t sa = QK_SA, s0 = sa + 4096 + (lane >> 4) * QK_F, s1 = sa + QK_F + QK_S12, s2 = sa + QK_F + QK_S34;
          wg_wait<0>();
          if (wg + warp == 0) TS(3);
          stsm4t(s0, pack2(acc[0], acc[1]), pack2(acc[2], acc[3]), pack2(acc[20], acc[21]), pack2(acc[22], acc[23]));
          stsm4t(s1, pack2(acc[4], acc[5]), pack2(acc[6], acc[7]), pack2(acc[8], acc[9]), pack2(acc[10], acc[11]));
          stsm4t(s2, pack2(acc[12], acc[13]), pack2(acc[14], acc[15]), pack2(acc[16], acc[17]), pack2(acc[18], acc[19]));
        } else {
          DESC(1);
          float acc[4];
          mbar_waitu(bar + 8 * (B_F1 + 0), par);
          if (wg + warp == 0) { TS(0); TSN(1); }
          CFENCE(); wg_fence(); proj<8, SSQ, 0, 0, 10>(acc, W, D); wg_commit();
          mbar_waitu(bar + 8 * (B_F1 + 1), par);
          CFENCE(); wg_fence(); proj<8, SSQ, 0, 10, 20>(acc, W, D); wg_commit();
          mbar_waitu(bar + 8 * (B_F1 + 2), par);
          CFENCE(); wg_fence(); proj<8, SSQ, 0, 20, 30>(acc, W, D); wg_commit();
          mbar_waitu(bar + 8 * (B_F1 + 3), par);
          if (wg + warp == 0) TS(2);
          CFENCE(); wg_fence(); proj<8, SSQ, 0, 30, 40>(acc, W, D); wg_commit();
          bar_arrive(N_VGO, 384);
          mbar_waitu(bar + 8 * B_PLFREE, par);
          const uint32_t s0 = QK_SA + 4096;
          wg_wait<0>();
          if (wg + warp == 0) TS(3);
          stsm2t(s0, pack2(acc[0], acc[1]), pack2(acc[2], acc[3]));
        }
        fence_async();
        bar_sync(N_QK, 256);
        if (wg == 0 || dual) {
          float s[20];
          DESC(2);
          const Dsc ab = D.k1 + wg * 192, bb = D.k1 + (1 - wg) * 320;
          wg_fence();
          MM<40>::ss<dlo(OFF_QK, 128), dlo(OFF_QK + 10240, 128), 0, 0>(s, ab, bb);
          MM<40>::ss<dlo(OFF_QK + 256, 128), dlo(OFF_QK + 10240 + 256, 128), 1, 0>(s, ab, bb);
          MM<40>::ss<dlo(OFF_QK + 512, 128), dlo(OFF_QK + 10240 + 512, 128), 1, 0>(s, ab, bb);
          MM<40>::ss<dlo(OFF_QK + 768, 128), dlo(OFF_QK + 10240 + 768, 128), 1, 0>(s, ab, bb);
          wg_commit();
          bar_arrive(N_SISS, 384);
          const int rw = (warp - wg) & 3;
          const uint32_t bo = OFF_BAR + 8 * (B_SB + 3 * wg + rw), lo = OFF_PL + wg * PL_SZ + rw * 1792;
          const uint32_t km = wg ? 640 : 512;
          uint32_t l16 = lo + lane * 16, l4 = lo + lane * 4;
          mbar_expect_if(lane == 0 && rw < 3, sb + bo, rw < 2 ? 1792 : 1280);
          asm volatile("" : "+r"(l16), "+r"(l4));
          if (rw == 2) {
            wg_wait<0>();
            if (wg == 0) TSD(4, __float_as_uint(s[0]));
            const uint32_t w0 = pack2(s[0], s[1]), w1 = pack2(s[4], s[5]), w2 = pack2(s[8], s[9]), w3 = pack2(s[12], s[13]), w4 = pack2(s[16], s[17]);
            {
              st_async_v4(nxt + 896 + l16, w0, w1, w2, w3, nxt + bo);
              st_async_v4(prv + l16, w0, w1, w2, w3, prv + bo);
              st_async_b32(nxt + 896 + 768 + l4, w4, nxt + bo);
              st_async_b32(prv + 768 + l4, w4, prv + bo);
            }
            bar_arrive(N_SDONE, 256);
            mbar_waitu(sb + bo, (step - wg * LAG) & 1);
            if (wg == 0) TS(5);
            float x[10], m0;
            {
              const uint4 a = lds128(sb + l16), b = lds128(sb + 896 + l16);
              const uint32_t c = lds32(sb + 768 + l4), d = lds32(sb + 896 + 768 + l4);
              const uint32_t e0 = hadd2bf(hadd2bf(a.x, b.x), w0), e1 = hadd2bf(hadd2bf(a.y, b.y), w1), e2 = hadd2bf(hadd2bf(a.z, b.z), w2),
                             e3 = hadd2bf(hadd2bf(a.w, b.w), w3), e4 = hadd2bf(hadd2bf(c, d), w4);
              const uint32_t em = hmax2bf(hmax2bf(hmax2bf(e0, e1), hmax2bf(e2, e3)), e4);
              m0 = fmaxf(bf_lo(em), bf_hi(em));
              x[0] = bf_lo(e0); x[1] = bf_hi(e0); x[2] = bf_lo(e1); x[3] = bf_hi(e1); x[4] = bf_lo(e2);
              x[5] = bf_hi(e2); x[6] = bf_lo(e3); x[7] = bf_hi(e3); x[8] = bf_lo(e4); x[9] = bf_hi(e4);
            }
            m0 = fmaxf(m0, __shfl_xor_sync(~0u, m0, 1));
            sts32(sb + l4 + 1152 - km, 0u);
            m0 = fmaxf(m0, __shfl_xor_sync(~0u, m0, 2));
            m0 *= -SL2;
#pragma unroll
            for (int j = 0; j < 5; j++) {
              x[2 * j] = ex2(fmaf(x[2 * j], SL2, m0)); x[2 * j + 1] = ex2(fmaf(x[2 * j + 1], SL2, m0));
              sts32(sb + l4 + (j < 4 ? j * 128 : km), pack2(x[2 * j], x[2 * j + 1]));
            }
            float l = ((x[0] + x[1]) + (x[2] + x[3])) + ((x[4] + x[5]) + ((x[6] + x[7]) + (x[8] + x[9])));
            l += __shfl_xor_sync(~0u, l, 1);
            fence_async();
            sts32(sb + OFF_INV + wg * 64 + (lane >> 1) * 4, __float_as_uint(l));
            bar_arrive(N_PM, dual ? 224 : 192);
            if (wg == 0) TS(6);
          } else if (rw < 2) {
            const bool w1 = rw == 1;
            const uint32_t l8 = lo + 512 + lane * 8;
            uint32_t tw[7];
            wg_wait<0>();
            bar_arrive(N_SDONE, 256);
            tw[0] = pack2(s[0], s[1]); tw[1] = pack2(s[4], s[5]); tw[2] = pack2(s[8], s[9]); tw[3] = pack2(s[16], s[17]);
            tw[4] = w1 ? pack2(s[6], s[7]) : pack2(s[12], s[13]); tw[5] = pack2(s[2], s[3]); tw[6] = pack2(s[18], s[19]);
            { const uint32_t t0 = clock32(); while (clock32() - t0 < TOK_DELAY) {} }
            st_async_v4(nxt + 896 + l16, tw[0], tw[1], tw[2], tw[3], nxt + bo);
            st_async_v4(prv + l16, tw[0], tw[1], tw[2], tw[3], prv + bo);
            st_async_v2(nxt + 896 + l8, tw[5], tw[6], nxt + bo);
            st_async_v2(prv + l8, tw[5], tw[6], prv + bo);
            st_async_b32(nxt + 896 + 768 + l4, tw[4], nxt + bo);
            st_async_b32(prv + 768 + l4, tw[4], prv + bo);
            mbar_waitu(sb + bo, (step - wg * LAG) & 1);
            const uint4 a = lds128(sb + l16), b = lds128(sb + 896 + l16);
            const uint2 e = lds64(sb + l8), f = lds64(sb + 896 + l8);
            const uint32_t c = lds32(sb + 768 + l4), d = lds32(sb + 896 + 768 + l4);
            sts128(sb + l16, hadd2bf(hadd2bf(a.x, b.x), tw[0]), hadd2bf(hadd2bf(a.y, b.y), tw[1]), hadd2bf(hadd2bf(a.z, b.z), tw[2]), hadd2bf(hadd2bf(a.w, b.w), tw[3]));
            sts64(sb + l8, hadd2bf(hadd2bf(e.x, f.x), tw[5]), hadd2bf(hadd2bf(e.y, f.y), tw[6]));
            sts32(sb + 768 + l4, hadd2bf(hadd2bf(c, d), tw[4]));
            bar_arrive(N_PX, dual ? 256 : 192);
            if (wg + warp == 0) TS(9);
          } else {
            wg_wait<0>();
            if (wg == 0) {
              mbar_expect_if(lane < 3 && has_next, bar + 8 * (lane == 2 ? B_OPEER : B_WOF + lane), lane == 2 ? (dual ? 4096 : 2048) : lane ? 8192 : 20480);
              auto fetch = [&](int i, int n, uint32_t dst, int mb) {
                int c0, c1; wo_coord(i, t3, head, c0, c1);
                tma2d_e(dst, &M.wo32, c0, c1, bar + 8 * mb); if (n == 2) tma2d_e(dst + 4096, &M.wo32, c0, c1 + 32, bar + 8 * mb);
              };
              bar_sync(N_G3, 160);
              if (has_next) {
                fetch(0, 2, sb + OFF_WT, B_WTF);
                mbar_arrive_remote_if(lane < 2, (lane ? nxt : prv) + OFF_BAR + 8 * B_XFREE);
              }
              bar_sync(N_SDONE, 256);
              if (has_next) {
                fetch(15, 1, sb + OFF_QK, B_WOF); fetch(16, 2, sb + OFF_QK + 4096, B_WOF); fetch(18, 2, sb + OFF_QK + 12288, B_WOF);
                mbar_waitu(bar + 8 * B_XFREE, par);
              }
              bar_arrive(N_PM, dual ? 224 : 192);
              bar_sync(N_VDONE, 160);
              mbar_arrive_remote_if(lane < nA && has_next, rb0 + (lane << 24) + OFF_BAR + 8 * B_MEMFREE);
              if (has_next) mbar_waitu(bar + 8 * B_WTF, par);
            } else {
              bar_arrive(N_SDONE, 256);
              if ((unsigned)ig < 3) issue_tok(sched_l(step + 1), B_F2, B_R1, (step - LAG) & 1);
            }
          }
        } else {
          bar_arrive(N_SISS, 384);
          bar_arrive(N_SDONE, 256);
        }
        if (has_next) {
          if (step == 0) mbar_waitw(bar + 8 * B_W1, 0);
          const uint32_t r1 = rb0 + ((nA - 1) << 24) + OFF_BAR + 8 * B_R1;
          if (dual) { DESC(3); wo_phase<16>(sb, wg, warp, lane, par, r1, D); } else { DESC(4); wo_phase<8>(sb, wg, warp, lane, par, r1, D); }
          bar_arrive(N_C, 288);
          if (warp == 0) TS(7 + wg);
        }
      }
      if (has_next) {
        DESC(5);
        float acc[16];
        mbar_waitu(bar + 8 * B_F2, par ^ 1);
        wg_fence(); proj<32, SSQ, 1, 0, 10>(acc, W, D); wg_commit();
        mbar_waitu(bar + 8 * (B_F2 + 1), par ^ 1);
        wg_fence(); proj<32, SSQ, 1, 10, 14>(acc, W, D); wg_commit();
        wg_wait<1>(); REL(B_R2, 0);
        wg_fence(); proj<32, SSQ, 1, 14, 20>(acc, W, D); wg_commit();
        mbar_waitu(bar + 8 * (B_F2 + 2), par ^ 1);
        wg_fence(); proj<32, SSQ, 1, 20, 24>(acc, W, D); wg_commit();
        wg_wait<1>(); REL(B_R2, 1);
        wg_fence(); proj<32, SSQ, 1, 24, 30>(acc, W, D); wg_commit();
        mbar_waitu(bar + 8 * (B_F2 + 3), par ^ 1);
        wg_fence(); proj<32, SSQ, 1, 30, 34>(acc, W, D); wg_commit();
        wg_wait<1>(); REL(B_R2, 2);
        wg_fence(); proj<32, SSQ, 1, 34, 40>(acc, W, D); wg_commit();
        const uint32_t sa = QK_SA, s1 = sa + QK_S12, s2 = sa + QK_S34;
        wg_wait<0>(); REL(B_R2, 3);
        if (warp == 0) TS(11 + wg);
        stsm4t(s1, pack2(acc[0], acc[1]), pack2(acc[2], acc[3]), pack2(acc[4], acc[5]), pack2(acc[6], acc[7]));
        stsm4t(s2, pack2(acc[8], acc[9]), pack2(acc[10], acc[11]), pack2(acc[12], acc[13]), pack2(acc[14], acc[15]));
      }
    }
    GTS(28);
    cluster_sync_all();
  } else if (wg == 2) {
    asm volatile("setmaxnreg.inc.sync.aligned.u32 160;");
    LANE_INIT();
    uint32_t W[4 * (40 - SSV)];
    ld_rest<0>(W, reinterpret_cast<const uint32_t*>(M.wv + (lane >> 2) * HD + col0 + warp * 16) + (lane & 3));
    uint4 m0[5];
#pragma unroll
    for (int i = 0; i < 5; i++) {
      const int t = i * 128 + warp * 32 + lane;
      m0[i] = __ldg(reinterpret_cast<const uint4*>(mem0 + ((t >> 1) & 7) * DM + (t >> 4) * 16 + ((t ^ (t >> 3)) & 1) * 8));
    }
    mbar_waitw(bar + 8 * B_W0, 0);
    load_w<VA>(W, sb + STG_K + 27 * 2048, warp, lane);
    load_w<VST - VA>(W + 4 * VA, sb + STG_V2, warp, lane);
    fence_async();
    mbar_expect_if(warp + lane == 0, bar + 8 * B_W1, 26 * 2048);
    bar_sync(1, 384);
#pragma unroll
    for (int i = 0; i < 5; i++) {
      const int t = i * 128 + warp * 32 + lane;
      sts128(sb + OFF_TILE + (t / 160) * (TILE_GRP - TILE_SBO) + t * 16, m0[i].x, m0[i].y, m0[i].z, m0[i].w);
    }
#pragma unroll
    for (int i = 4 * VST; i < 4 * (40 - SSV); i++) W[i] = movm(W[i]);
    fence_async();
    mbar_arrive_if(lane == 0, bar + 8 * (B_F1 + warp));
    mbar_expect_if(lane == 0, bar + 8 * (B_F2 + warp), 10240);
    mbar_arrive_if(warp == 3 && lane < 2, bar + 8 * B_PLFREE);
    cluster_sync_all();
    uint32_t vl[8];
    {
      const int step = warp;
      DESC(0);
      float v[16];
      mbar_waitw4(bar + 8 * B_F2, 0);
      wg_fence(); proj<32, SSV, 1, 0, 40>(v, W, D); wg_commit();
      wg_wait<0>();
      mbar_arrive_remote_if(lane < 4, rb0 + ((nA - 4 + lane) << 24) + OFF_BAR + 8 * B_R2);
#pragma unroll
      for (int j = 0; j < 8; j++) vl[j] = pack2v(v[2 * j], v[2 * j + 1]);
      if (warp == 0 && (unsigned)ig < 3) issue_tok(1, B_F2, B_R2, 0);
    }
#pragma unroll 1
    for (int step = 0; step < NSTEP; step++) {
      const uint32_t par = step & 1;
      asm volatile("" : "+r"(lane));
      const bool dual = is_dual(step), has_next = step + 1 < NSTEP;
      mbar_expect_if(lane == 0 && has_next, bar + 8 * (B_F2 + warp), 10240);
      if (warp == 0 && ig == 3 && dual && sync_b) wait_cnt(&g_xready[sched_l(step + 1)][0], 32);
      bar_sync(N_VGO, 384);
      CFENCE();
#define F1_BYTES (is_dual(step + 1) ? 15360 : 2560)
#define ARM() do { \
        mbar_expect_if(lane == 0 && has_next, bar + 8 * (B_F1 + warp), F1_BYTES); \
        mbar_expect_if(lane == 0 && has_next && warp * nA + (int)rank < 40, bar + 8 * (B_RS + warp), (warp * nA + (int)rank >= 36 ? nA : nh) * (dual ? 512 : 256)); } while (0)
#define O_ADDR() uint32_t oa = sb + OFF_O + (lane >> 4) * PL_SZ + warp * 256 + (lane & 15) * 16, xo = (lane >> 4) * 1024 + warp * 256 + (lane & 15) * 16; \
        asm volatile("" : "+r"(oa), "+r"(xo))
#define O_READY(act) do { if (has_next) { const uint4 ov = lds128(oa); \
        if (act) { st_async_v4(nxt + OFF_XL + xo, ov.x, ov.y, ov.z, ov.w, nxt + OFF_BAR + 8 * B_OPEER); \
                   st_async_v4(prv + OFF_XF + xo, ov.x, ov.y, ov.z, ov.w, prv + OFF_BAR + 8 * B_OPEER); } \
        fence_async(); bar_arrive(N_O, 384); } \
        if (warp == 0) TS(15); } while (0)
#define TOK_L3() if (warp == 0 && ig == 3 && has_next) { mbar_waitu(bar + 8 * B_R1, par); asm volatile("fence.proxy.async.global;" ::: "memory"); \
        bulk_g2s_mc_e(sb + OFF_TILE + 3 * TILE_GRP + TILE_SBO, &g_xn[0][0] + uni(sched_l(step + 1) * (32 * DM)) + 3 * 5120, 10240, bar + 8 * (B_F2 + 3), mcmask); }
#define OX_ADDR() const bool ox = head * 3 + t3 == 95; \
        const uint32_t oxa = sb + OFF_PL + (ox ? warp * 1024 + (lane & 7) * 32 + ((((lane >> 3) ^ (lane >> 2)) & 1) << 4) : (lane & 7) * 128 + (((warp * 2 + ((lane >> 3) & 1)) ^ (lane & 7)) << 4)); \
        const uint32_t s1 = oxa + ((lane < 16 ? 3072 : 0) >> (ox ? 2 : 0)), s2 = oxa + ((lane < 16 ? 2048 : 1024) >> (ox ? 2 : 0))
      if (dual) {
        uint32_t vf[8], vm[4], vn[8];
        {
          DESC(0);
          float v[24];
          ARM();
          wg_fence(); proj<48, SSV, 0, 30, 40, 30>(v, W, D); wg_commit();
          proj<48, SSV, 0, 0, VD1 - 10, 30>(v, W, D);
          bar_sync(N_SISS, 384);
          proj<48, SSV, 0, VD1 - 10, VD1 - 7, 30>(v, W, D); wg_commit();
          wg_wait<1>(); bar_arrive(N_G3, 160);
          wg_fence(); proj<48, SSV, 0, VD1 - 7, 10, 30>(v, W, D); wg_commit();
          proj<48, SSV, 0, 10, 13, 30>(v, W, D); wg_commit();
          wg_wait<1>(); REL(B_R1, 0);
          wg_fence(); proj<48, SSV, 0, 13, 20, 30>(v, W, D); wg_commit();
          proj<48, SSV, 0, 20, 23, 30>(v, W, D); wg_commit();
          wg_wait<1>(); REL(B_R1, 1);
          wg_fence(); proj<48, SSV, 0, 23, 30, 30>(v, W, D); wg_commit();
          wg_wait<0>(); REL(B_R1, 2);
          bar_arrive(N_VDONE, 160);
          if (warp == 0) TS(14);
#pragma unroll
          for (int j = 4; j < 8; j++) vf[j] = pack2v(v[4 + 2 * j], v[5 + 2 * j]);
          keep4(vf + 4, lane);
          vm[0] = pack2v(v[0], v[1]); vm[1] = pack2v(v[2], v[3]); vm[2] = pack2v(v[20], v[21]); vm[3] = pack2v(v[22], v[23]);
          keep4(vm, lane);
#pragma unroll
          for (int j = 0; j < 4; j++) vf[j] = pack2v(v[4 + 2 * j], v[5 + 2 * j]);
          keep4(vf, lane);
        }
        {
          DESC(1);
          float o[8];
          O_ADDR();
          bar_sync(N_PM, 224);
          wg_fence();
          MM<8>::rs<dlo(OFF_PL + 3584, 128), 0>(o, vl, D.p);
          MM<8>::rs<dlo(OFF_PL + PL_SZ + 3584, 128), 0>(o + 4, vf, D.p);
          MM<8>::rs<dlo(OFF_PL + 3584 + 256, 128), 1>(o, vl + 4, D.p);
          MM<8>::rs<dlo(OFF_PL + PL_SZ + 3584 + 256, 128), 1>(o + 4, vf + 4, D.p);
          MM<8>::rs<dlo(OFF_PL + 3584 + 512, 128), 1>(o, vm, D.p);
          MM<8>::rs<dlo(OFF_PL + PL_SZ + 3584 + 512, 128), 1>(o + 4, vm, D.p);
          wg_commit();
          fence_sched(step);
          const uint4 il = lds128(sb + OFF_INV + (lane & 3) * 16), jf = lds128(sb + OFF_INV + 64 + (lane & 3) * 16);
          const float i0 = rcpf(__uint_as_float(il.x) + __uint_as_float(il.y)), i1 = rcpf(__uint_as_float(il.z) + __uint_as_float(il.w));
          const float j0 = rcpf(__uint_as_float(jf.x) + __uint_as_float(jf.y)), j1 = rcpf(__uint_as_float(jf.z) + __uint_as_float(jf.w));
          { const uint32_t k4[4] = {__float_as_uint(i0), __float_as_uint(i1), __float_as_uint(j0), __float_as_uint(j1)}; keep4(k4, lane | (oa ^ xo)); }
          wg_wait<0>();
          stsm4t(oa, pack2(o[0] * i0, o[1] * i1), pack2(o[2] * i0, o[3] * i1), pack2(o[4] * j0, o[5] * j1), pack2(o[6] * j0, o[7] * j1));
          O_READY(true);
          TOK_L3();
        }
        {
          DESC(2);
          float v[16];
          bar_sync(N_TURN, 256);
          mbar_waitu(bar + 8 * B_F2, par ^ 1);
          wg_fence(); proj<32, SSV, 1, 0, 10>(v, W, D); wg_commit();
          mbar_waitu(bar + 8 * (B_F2 + 1), par ^ 1);
          wg_fence(); proj<32, SSV, 1, 10, 14>(v, W, D); wg_commit();
          wg_wait<1>(); REL(B_R2, 0);
          wg_fence(); proj<32, SSV, 1, 14, 20>(v, W, D); wg_commit();
          mbar_waitu(bar + 8 * (B_F2 + 2), par ^ 1);
          wg_fence(); proj<32, SSV, 1, 20, 24>(v, W, D); wg_commit();
          wg_wait<1>(); REL(B_R2, 1);
          wg_fence(); proj<32, SSV, 1, 24, 30>(v, W, D); wg_commit();
          mbar_waitu(bar + 8 * (B_F2 + 3), par ^ 1);
          wg_fence(); proj<32, SSV, 1, 30, 34>(v, W, D); wg_commit();
          wg_wait<1>(); REL(B_R2, 2);
          wg_fence(); proj<32, SSV, 1, 34, 40>(v, W, D); wg_commit();
          wg_wait<0>(); REL(B_R2, 3);
#pragma unroll
          for (int j = 0; j < 8; j++) vn[j] = pack2v(v[2 * j], v[2 * j + 1]);
          keep4(vn, lane); keep4(vn + 4, lane);
          if (warp == 0) TS(18);
        }
        DESC(3);
        uint32_t ow[16];
        bar_sync(N_P, 256);
        fence_async();
#define PV16(i, off, va) { float o[8]; wg_fence(); \
          MM<16>::rs<dlo(OFF_PL + (off), 128), 0>(o, va, D.p); \
          MM<16>::rs<dlo(OFF_PL + (off) + 256, 128), 1>(o, va + 4, D.p); \
          MM<16>::rs<dlo(OFF_PL + (off) + 512, 128), 1>(o, vm, D.p); \
          wg_commit(); wg_wait<0>(); \
          _Pragma("unroll") for (int j = 0; j < 4; j++) ow[4 * (i) + j] = pack2v(o[2 * j], o[2 * j + 1]); \
          keep4(ow + 4 * (i), lane); }
        PV16(0, 0, vl) PV16(1, 1792, vl) PV16(2, PL_SZ, vf) PV16(3, PL_SZ + 1792, vf)
        OX_ADDR();
        bar_sync(N_V, 128);
        stsm4t(s1, ow[0], ow[1], ow[2], ow[3]);
        stsm4t(s2, ow[4], ow[5], ow[6], ow[7]);
        stsm4t(s1 + PL_SZ, ow[8], ow[9], ow[10], ow[11]);
        stsm4t(s2 + PL_SZ, ow[12], ow[13], ow[14], ow[15]);
#pragma unroll
        for (int j = 0; j < 8; j++) vl[j] = vn[j];
      } else {
        uint32_t vm[4], vn[8], here;
        {
          DESC(4);
          float v[4];
          wg_fence(); proj<8, SSV, 0, 30, 40, 30>(v, W, D); wg_commit();
          proj<8, SSV, 0, 0, VS1, 30>(v, W, D); wg_commit();
          ARM();
          bar_sync(N_SISS, 384);
          wg_wait<1>(); bar_arrive(N_G3, 160);
          wg_fence(); proj<8, SSV, 0, VS1, 30, 30>(v, W, D); wg_commit();
          asm volatile("{\n.reg .pred p, r;\nmbarrier.test_wait.parity.shared::cta.b64 p, [%1], %2;\nmbarrier.test_wait.parity.shared::cta.b64 r, [%1+8], %2;\n"
                       "and.pred p, p, r;\nmbarrier.test_wait.parity.shared::cta.b64 r, [%1+16], %2;\nand.pred p, p, r;\nbar.red.and.pred p, %3, 128, p;\nselp.u32 %0, 1, 0, p;\n}"
                       : "=r"(here) : "r"(bar + 8 * B_F2), "r"(par ^ 1), "n"((int)N_V) : "memory");
          here = uni(here) || !has_next;
          wg_wait<0>();
          bar_arrive(N_VDONE, 160);
          vm[0] = pack2v(v[0], v[1]); vm[1] = pack2v(v[2], v[3]); vm[2] = pack2v(v[1], v[0]); vm[3] = pack2v(v[3], v[2]);
        }
        DESC(5);
        float v[16];
        {
          wg_fence(); proj<32, SSV, 1, 0, VS2>(v, W, D); wg_commit();
          {
            float o[4];
            O_ADDR();
            bar_sync(N_PM, 192);
            if (warp == 0) TS(14);
            wg_fence();
            MM<8>::rs<dlo(OFF_PL + 3584, 128), 0>(o, vl, D.p);
            MM<8>::rs<dlo(OFF_PL + 3584 + 256, 128), 1>(o, vl + 4, D.p);
            MM<8>::rs<dlo(OFF_PL + 3584 + 512, 128), 1>(o, vm, D.p);
            wg_commit();
            fence_sched(step);
            const uint4 il = lds128(sb + OFF_INV + (lane & 3) * 16);
            const float i0 = rcpf(__uint_as_float(il.x) + __uint_as_float(il.y)), i1 = rcpf(__uint_as_float(il.z) + __uint_as_float(il.w));
            { const uint32_t k4[4] = {__float_as_uint(i0), __float_as_uint(i1), oa, xo}; keep4(k4, lane); }
            wg_wait<0>();
            stsm2t(oa, pack2(o[0] * i0, o[1] * i1), pack2(o[2] * i0, o[3] * i1));
            O_READY(lane < 16);
            if (here) TOK_L3();
          }
          if (has_next) {
            mbar_arrive_remote_if(lane < VS2 / 10 && here, rb0 + ((nA - 4 + lane) << 24) + OFF_BAR + 8 * B_R2);
            bar_sync(N_TURN, 256);
          }
          if (!here) {
            DESC(6);
            mbar_waitu2(bar + 8 * B_F2, bar + 8 * (B_F2 + 1), par ^ 1);
            TOK_L3();
            mbar_waitu(bar + 8 * (B_F2 + 2), par ^ 1);
            wg_fence(); proj<32, SSV, 1, 0, VS2>(v, W, D); wg_commit();
            wg_wait<0>();
            mbar_arrive_remote_if(lane < VS2 / 10, rb0 + ((nA - 4 + lane) << 24) + OFF_BAR + 8 * B_R2);
          }
          if (VS2 < 30) { wg_fence(); proj<32, SSV, 1, VS2, 30>(v, W, D); wg_commit(); }
          if (has_next) mbar_waitu(bar + 8 * (B_F2 + 3), par ^ 1);
          if (VS2 < 30) { wg_wait<0>(); if (has_next) REL(B_R2, 2); }
          wg_fence(); proj<32, SSV, 1, 30, 40>(v, W, D); wg_commit();
          wg_wait<0>();
          if (has_next) REL(B_R2, 3);
#pragma unroll
          for (int j = 0; j < 8; j++) vn[j] = pack2v(v[2 * j], v[2 * j + 1]);
          keep4(vn, lane); keep4(vn + 4, lane);
          if (warp == 0) TS(18);
        }
        float o[16];
        bar_sync(N_P, 256);
        fence_async();
        wg_fence();
        MM<32>::rs<dlo(OFF_PL, 128), 0>(o, vl, D.p);
        MM<32>::rs<dlo(OFF_PL + 256, 128), 1>(o, vl + 4, D.p);
        MM<32>::rs<dlo(OFF_PL + 512, 128), 1>(o, vm, D.p);
        wg_commit();
        OX_ADDR();
        wg_wait<0>();
        bar_sync(N_V, 128);
        stsm4t(s1, pack2(o[0], o[1]), pack2(o[2], o[3]), pack2(o[4], o[5]), pack2(o[6], o[7]));
        stsm4t(s2, pack2(o[8], o[9]), pack2(o[10], o[11]), pack2(o[12], o[13]), pack2(o[14], o[15]));
#pragma unroll
        for (int j = 0; j < 8; j++) vl[j] = vn[j];
      }
      bar_arrive(N_OX, 160);
      if (warp == 0) TS(16);
    }
    cluster_sync_all();
  } else {
    asm volatile("setmaxnreg.dec.sync.aligned.u32 32;");
    if (wg > 3) return;
    LANE_INIT();
    struct RsJob { uint32_t* gp; uint32_t la, mb; int n; };
    auto rs_prep = [&](int step, int s, int c) {
      RsJob j;
      const int u = s * nA + rank;
      j.gp = &g_part[0][0][0][0] + (uint32_t)((((step & 1) * 2 + c) * NCL + cl) * 2560 + u * 64 + (lane >> 2) * 8 + (lane & 3));
      j.la = sb + OFF_TILE + c * LAND_F + LAND(s) + lane * 8;
      j.mb = bar + 8 * (B_RS + s);
      j.n = u >= 40 ? 0 : u >= 36 ? 3 : 1;
      asm volatile("" : "+l"(j.gp), "+r"(j.la));
      return j;
    };
    auto rs_sum = [&](RsJob j, int step) {
      if (j.n) {
        auto five = [&](uint32_t la) {
          uint2 p[5];
#pragma unroll
          for (int i = 0; i < 4; i++) p[i] = lds64(la + i * 256);
          asm volatile("{\n.reg .pred q;\nsetp.eq.s32 q, %3, 5;\nmov.u32 %0, 0;\nmov.u32 %1, 0;\n@q ld.shared.v2.b32 {%0,%1}, [%2];\n}"
                       : "=r"(p[4].x), "=r"(p[4].y) : "r"(la + 1024), "r"(nh) : "memory");
          return make_uint2(hadd2bf(hadd2bf(p[0].x, p[1].x), hadd2bf(hadd2bf(p[2].x, p[3].x), p[4].x)),
                            hadd2bf(hadd2bf(p[0].y, p[1].y), hadd2bf(hadd2bf(p[2].y, p[3].y), p[4].y)));
        };
        const uint32_t tag = ((step >> 1) & 1) ^ 1;
        mbar_waitw(j.mb, step & 1);
        uint2 t = five(j.la);
        if (j.n > 1) {
          const uint2 a = five(j.la + (nh == 5 ? 1280 : TILE_GRP - 1280)), b = five(j.la + TILE_GRP);
          t.x = hadd2bf(t.x, hadd2bf(a.x, b.x)); t.y = hadd2bf(t.y, hadd2bf(a.y, b.y));
        }
        const uint32_t t0 = (movm(t.x) & ~1u) | tag, t1 = (movm(t.y) & ~1u) | tag;
        asm volatile("st.relaxed.gpu.global.b32 [%0], %1;" :: "l"(j.gp), "r"(lane & 16 ? t1 : t0) : "memory");
        asm volatile("st.relaxed.gpu.global.b32 [%0], %1;" :: "l"(j.gp + 4), "r"(lane & 16 ? t0 : t1) : "memory");
      }
    };
    if (warp * nA + (int)rank < 40) {
#pragma unroll
      for (int e = LAG; e < LAG + 2; e++)
        if ((e >> 1) & 1) *reinterpret_cast<uint2*>(&g_part[(e & 1) * 2 + 1][cl][warp * nA + rank][lane * 2]) = make_uint2(1u, 1u);
      __threadfence();
    }
    if (warp == 2 && ig >= 0 && sync_b) wait_cnt(&g_xready[0][0], 32);
    cluster_sync_all();
    if (warp == 2 && ig >= 0) bulk_g2s_mc_e(sb + OFF_TILE + ig * TILE_GRP + TILE_SBO, &g_xn[0][0] + ig * 5120, 10240, bar + 8 * (B_F2 + ig), mcmask);
    bar_sync(N_PI, 128);
#pragma unroll 1
    for (int i = warp; i < 20; i += 4) {
      int c0, c1; wo_coord(i, t3, head, c0, c1);
      if (i >= 2 && i < 15) tma2d_e(sb + OFF_WO + (i - 2) * 4096, &M.wo32, c0, c1, bar + 8 * B_W1);
      else if (lane == 0) tma2d_prefetch(&M.wo32, c0, c1);
      __syncwarp();
    }
#pragma unroll 1
    for (int step = 0; step < NSTEP; step++) {
      const uint32_t par = step & 1;
      asm volatile("" : "+r"(lane));
      const bool dual = is_dual(step), has_next = step + 1 < NSTEP;
      {
        bar_sync(N_PX, dual ? 256 : 192);
        if (dual || warp >= 2) tok_softmax(sb, dual ? warp : warp - 2, lane);
        bar_arrive(N_P, 256);
        asm volatile("" : "+r"(lane));
        if (has_next) {
          if (step + 2 == LAG && lane < 20) asm volatile("prefetch.global.L2 [%0];" :: "l"(mem0 + (warp * 20 + lane) * 64));
          const int nw = ig >= 0 ? 3 : 4, j0 = warp < nw ? warp : 8;
          const int sh = dual ? 1 : 0;
          rs_sum(rs_prep(step, j0 >> sh, j0 & sh), step);
          if (warp == 0) TS(17);
          if (dual) rs_sum(rs_prep(step, (j0 + nw) >> 1, (j0 + nw) & 1), step);
          if (warp == 0) { bar_sync(N_C, 288); }
          mbar_arrive_remote_if(lane < nA, rb0 + (lane << 24) + OFF_BAR + 8 * B_LANDFREE);
          const uint32_t gap = dual ? POLL_GAPD : POLL_GAP;
          if (gap) { const uint32_t t0 = clock32(); while (clock32() - t0 < gap) {} }
#pragma unroll 1
          for (int j = j0; j < (dual ? 8 : 4); j += nw) {
            const int u = (j >> sh) * nA + rank, c = j & sh;
            if (u < UMAX && (c || step + 1 != NSEG)) {
              const uint32_t* gq = &g_part[0][0][0][0] + (uint32_t)((par * 2 + c) * NCL * 2560 + u * 64 + lane * 2);
              uint2 pa[NCL];
              POLL(pa, gq);
              deliver(pa, gq, u, c, step + 1 < NSEG ? c : 0, dual ? DS_DUAL : DS_SINGLE, step, j == 0, lane);
            }
            if (warp == 0 && j == 0) TS(13);
          }
          if (warp >= nw && (is_dual(step + 1) || (ig < 3 && step + 2 < NSTEP))) {
            issue_tok(is_dual(step + 1) ? sched_f(step + 1) : sched_l(step + 2), is_dual(step + 1) ? B_F1 : B_F2, B_R2, par ^ 1);
          }
          if (step + 1 == LAG && UMAX) {
            uint4 v[5];
#pragma unroll
            for (int i = 0; i < 5; i++) { const int t = warp * 160 + i * 32 + lane; v[i] = *reinterpret_cast<const uint4*>(mem0 + ((t >> 1) & 7) * DM + (t >> 4) * 16 + ((t ^ (t >> 3)) & 1) * 8); }
            mbar_waitu(bar + 8 * B_LANDFREE, par);
#pragma unroll
            for (int i = 0; i < 5; i++)
              st_async_v4(sb + OFF_TILE + LAND_F + warp * TILE_GRP + (i * 32 + lane) * 16, v[i].x, v[i].y, v[i].z, v[i].w, bar + 8 * (B_F1 + warp));
          }
        }
      }
      if (warp == (ig >= 0 && !is_dual(step + 1) ? 2 : 3)) {
        unsigned char* o0 = g_o + uni(step % RO * (96 * 8192) + (head * 3 + t3) * (dual ? 8192 : 4096));
        bar_sync(N_OX, 160);
        fence_async();
        bulk_s2g_es(o0, sb + OFF_PL, 4096);
        if (dual) bulk_s2g_es(o0 + 4096, sb + OFF_PL + PL_SZ, 4096);
        asm volatile("cp.async.bulk.commit_group;" ::: "memory");
        asm volatile("cp.async.bulk.wait_group.read 0;" ::: "memory");
        __syncwarp();
        mbar_arrive_remote_if(lane < 2, (lane ? nxt : prv) + OFF_BAR + 8 * B_PLFREE);
        asm volatile("cp.async.bulk.wait_group 0;" ::: "memory");
        asm volatile("fence.proxy.async.global;" ::: "memory");
        __syncwarp();
        if (lane == 0) red_release(&g_f[F_O + (head * 3 + t3) / 5][step], 1u);
        __syncwarp();
      }
    }
    cluster_sync_all();
  }
}

__device__ __forceinline__ uint32_t gelu2(uint32_t y, uint32_t s) {
  uint32_t g;
  asm("{\n.reg .b32 x, u, a, b;\nmov.b32 a, 0x28912891;\nmov.b32 b, 0x3a623a62;\nmul.rn.f16x2 x, %1, %2;\nmul.rn.f16x2 u, x, x;\nfma.rn.f16x2 u, u, a, b;\n"
      "mul.rn.f16x2 u, u, x;\ntanh.approx.f16x2 u, u;\nfma.rn.f16x2 %0, x, u, x;\n}" : "=r"(g) : "r"(y), "r"(s));
  return g; }

struct BParams {
  CUtensorMap wmap[5];
  CUtensorMap wo16;
  const __nv_bfloat16* x;
  __nv_bfloat16* out;
  uint64_t desc, desc32;
};
#define BO_O 0
#define BO_RES (6 * 8192)
#define OP_RES 63488
#define BO_STG (BO_RES + 2 * OP_RES)
#define BO_RING_OP (BO_STG + 16384)
#define OP_SLOT 12288
#define NS_OP 3
#define BO_H 81920
#define BO_W1 (BO_H + 16384)
#define BO_RING_MLP (BO_W1 + 81920)
#define BO_BAR 229376
#define BO_BOX (BO_BAR + 248)
#define BO_CARRY (BO_BAR + 512)
#define BO_STAT (BO_CARRY + 2048)
#define B_SMEM (BO_STAT + 256)
static_assert(B_SMEM <= 232448 && BO_RING_OP + NS_OP * OP_SLOT == BO_BAR && BO_RING_MLP + 3 * 16384 == BO_BAR && 2 * 83968 <= BO_RING_MLP, "smem");
enum { BB_W = 0, BB_FULL = 2, BB_TMP = BB_FULL + 3, BB_OFULL = BB_FULL + 5, BB_SFREE = BB_OFULL,
       BB_STAT = BB_SFREE + 6, BB_GO, BB_ZFREE, BB_DONE = BB_ZFREE + 3,
       BB_EMPTY, BB_START = BB_EMPTY, BB_USED = BB_EMPTY + 2, BB_NUM = BB_USED + 3 };
enum { NB_PP = 1, NB_H = 3, NB_END = 4, NB_END2 = 5, NB_STAGED = 6, NB_FREE = 8, NB_EARLY = 10, NB_LAST = 11 };

#define DESC_LO(off) (((SMEM0 + (off)) >> 4) | (1u << 16))

__device__ __forceinline__ uint32_t ld_relaxed(const uint32_t* p) { uint32_t v; asm volatile("ld.relaxed.gpu.global.b32 %0, [%1];" : "=r"(v) : "l"(p) : "memory"); return v; }
__device__ __forceinline__ int front(int r) { return r - (r > NSEG); }
__device__ __forceinline__ int fmask(int r) { return (r < NSEG) | ((r >= LAG && r < NSTEP) << 1); }
__device__ __forceinline__ int bmask(int r) { return (r <= NSEG) | ((r >= LAG && r != NSEG) << 1); }
#define NMERGE 3
__device__ __forceinline__ bool merged(bool w12, int r) { return !w12 && r > NSEG && r < NSEG + 2 * NMERGE; }
__device__ __forceinline__ uint32_t rtarget(int mask) { return mask == 3 ? 64 : 32; }
__device__ __forceinline__ void warp_signal(uint32_t* p, int lane) {
  __syncwarp();
  asm volatile("{\n.reg .pred q;\nsetp.eq.u32 q, %1, 0;\n@q red.release.gpu.global.add.u32 [%0], 1;\n}" :: "l"(p), "r"(lane) : "memory");
}
__device__ __forceinline__ uint32_t pack2h(float lo, float hi) { uint32_t r; asm("cvt.rn.f16x2.f32 %0, %1, %2;" : "=r"(r) : "f"(hi), "f"(lo)); return r; }
template <bool H> __device__ __forceinline__ uint32_t pk(float lo, float hi) { return H ? pack2h(lo, hi) : pack2(lo, hi); }
template <int N, bool H> __device__ __forceinline__ void stage_out(const float* d, uint32_t dst, int warp, int lane) {
  const uint32_t sa = dst + ((lane >> 4) * 8 + (lane & 7)) * 128 + (((2 * warp + ((lane >> 3) & 1)) ^ (lane & 7)) << 4);
#pragma unroll
  for (int m = 0; m < N / 16; m++)
    stsm4t(sa + m * 2048, pk<H>(d[8 * m], d[8 * m + 1]), pk<H>(d[8 * m + 2], d[8 * m + 3]), pk<H>(d[8 * m + 4], d[8 * m + 5]), pk<H>(d[8 * m + 6], d[8 * m + 7]));
}
template <int N> __device__ __forceinline__ void acc_live(float* d) {
#pragma unroll
  for (int i = 0; i < N / 2; i++) asm volatile("" : "+f"(d[i]) :: "memory");
}
struct Ring {
  uint32_t sl, ph;
  template <int NS> __device__ __forceinline__ void step() { if (++sl == NS) { sl = 0; ph ^= 1; } }
};

#define KOFF(x) (DESC_LO(BO_O) + ((x) >> 2) * 512 + ((x) & 3) * 2)
template <int N, int P>
__device__ __forceinline__ void op_pass(const uint32_t* W, uint32_t bar, Dsc alo, Dsc blo, Dsc xlo, bool x2, Ring& rg, int wg, int warp, int lane, int r) {
  float acc[N / 2];
  blo.e = xlo.e = fresh<P + N / 64 * 5>(r);
  const Dsc tlo = blo + uni(rg.sl) * (OP_SLOT / 16), b2 = blo + (r & 1) * 1536;
  if (P == 0) mbar_waitu(bar + 8 * (BB_OFULL + 2 + (r & 1)), (r >> 1) & 1);
  CTS(5 * P);
  bar_sync(NB_PP + wg, 256);
  wg_fence();
#define OP_R(x, b) MM<N>::template rs<KOFF(4 * (x >> 1) + (x & 1)), (x != (P ? 0 : 4))>(acc, W + 32 * P + 4 * x, b);
#define OP_S(x, b) MM<N>::template ss<DESC_LO(BO_RES) + (6 * P + x) * 128, KOFF(4 * (x >> 1) + 2 + (x & 1)), 1>(acc, alo, b);
#define OP_T(x) MM<N>::template ss<DESC_LO(BO_RING_OP) + x * 128, KOFF(14 + x), 1>(acc, tlo, blo);
#define OP_B2() OP_R(4, b2) OP_S(4, b2) OP_R(5, b2) OP_S(5, b2)
  if (P == 0) { OP_B2() mbar_waitu(bar + 8 * BB_OFULL, r & 1); }
  OP_R(0, blo) OP_S(0, blo) OP_R(1, blo) OP_S(1, blo) OP_R(2, blo) OP_S(2, blo) OP_R(3, blo) OP_S(3, blo)
  if (P == 0) mbar_waitu(bar + 8 * (BB_OFULL + 1), r & 1);
  if (P == 4) wg_commit();
  if (P & 3) { OP_B2() }
  if (P == 1 && x2) MM<N>::template ss<DESC_LO(BO_RES) + 30 * 128, DESC_LO(BO_CARRY), 1>(acc, alo, xlo);
  mbar_waitu(bar + 8 * (BB_FULL + rg.sl), rg.ph);
  OP_R(6, blo) OP_T(0) OP_R(7, blo) OP_T(1)
  if (P == 4) { wg_commit(); wg_wait<1>(); bar_arrive(NB_EARLY, 288); CTS(21); wg_fence(); }
  OP_T(2) OP_T(3)
  if (P == 0) MM<N>::template rs<DESC_LO(BO_CARRY), 1>(acc, W + 160, xlo);
  OP_T(4) OP_T(5)
  if (P == 4) { wg_commit(); OP_B2() }
  wg_commit();
  bar_arrive(NB_PP + 1 - wg, 256);
  CTS(5 * P + 2);
  if (P == 4) { wg_wait<1>(); bar_arrive(NB_LAST, 288); }
  bar_sync(NB_FREE + wg, 160);
  wg_wait<0>();
  acc_live<N>(acc);
  mbar_arrive_if(lane == 0, bar + 8 * (BB_USED + rg.sl));
  CTS(5 * P + 3);
  stage_out<N, false>(acc, SMEM0 + BO_STG + wg * 8192, warp, lane);
  bar_arrive(NB_STAGED + wg, 160);
  CTS(5 * P + 4);
  rg.step<NS_OP>(); rg.step<NS_OP>();
}
template <int N>
__device__ __forceinline__ void op_round(const uint32_t* W, uint32_t bar, Dsc alo, Dsc blo, Dsc xlo, bool x2, Ring& rg, int wg, int warp, int lane, int r) {
  op_pass<N, 0>(W, bar, alo, blo, xlo, x2, rg, wg, warp, lane, r);
  op_pass<N, 1>(W, bar, alo, blo, xlo, x2, rg, wg, warp, lane, r);
  op_pass<N, 2>(W, bar, alo, blo, xlo, x2, rg, wg, warp, lane, r);
  op_pass<N, 3>(W, bar, alo, blo, xlo, x2, rg, wg, warp, lane, r);
  op_pass<N, 4>(W, bar, alo, blo, xlo, x2, rg, wg, warp, lane, r);
}
__device__ __forceinline__ void carry_in(uint32_t sb, int wg, int warp, int lane) {
  const int row = (lane >> 1) & 3;
  if (lane < 16) {
    const uint4 v = lds128(sb + BO_CARRY + (wg * 4 + warp) * 256 + lane * 16);
    sts128(sb + BO_H + wg * 8192 + (lane >> 3) * 4096 + row * 128 + (((2 * warp + (lane & 1)) ^ row) << 4), v.x, v.y, v.z, v.w);
  }
  __syncwarp();
}
template <int N, int Z>
__device__ __forceinline__ void p1_pair(float* acc, const uint32_t* W, uint32_t bar, Dsc alo, Dsc blo, int lane, int r) {
  constexpr uint32_t ZOFF = DESC_LO(BO_RING_MLP + (N == 64 ? (Z == 1 ? -1 : (4 - Z) & 3) * 16384 : (Z / 2 * 2 % 3) * 16384 + (Z & 1) * 4096));
  blo.e = fresh<10 + Z / 3 + N / 64 * 2>(r);
  mbar_waitu(bar + 8 * (BB_FULL + Z), r & 1);
  CTS(40 + Z);
  wg_fence();
#define P1_B(k) \
  MM<N, true>::template rs<ZOFF + k * 512, (2 * Z + k != 0)>(acc, W + 16 * Z + 8 * k, blo); \
  MM<N, true>::template ss<DESC_LO(BO_W1) + (2 * Z + k) * 512, ZOFF + k * 512 + 4, 1>(acc, alo, blo); \
  MM<N, true>::template rs<ZOFF + k * 512 + 2, 1>(acc, W + 16 * Z + 8 * k + 4, blo); \
  MM<N, true>::template ss<DESC_LO(BO_W1) + (2 * Z + k) * 512 + 128, ZOFF + k * 512 + 6, 1>(acc, alo, blo);
  P1_B(0)
  if (N == 64 && (Z == 1 || Z == 2)) { wg_commit(); wg_wait<1>(); mbar_arrive_if(lane == 0, bar + 8 * (BB_EMPTY + Z - 1)); wg_fence(); }
  P1_B(1)
  wg_commit();
}
template <int N>
__device__ __forceinline__ void phase1(const uint32_t* W, uint32_t sb, Dsc alo, Dsc blo, int half, int wg, int warp, int lane, bool shift, int off, int rb, int r) {
  float acc[N / 2];
  const uint32_t bar = sb + BO_BAR;
  CTS(30);
  p1_pair<N, 0>(acc, W, bar, alo, blo, lane, r);
  p1_pair<N, 1>(acc, W, bar, alo, blo, lane, r);
  p1_pair<N, 2>(acc, W, bar, alo, blo, lane, r);
  if (N == 64 && !wg) { mbar_waitu(bar + 8 * (BB_SFREE + 4), (rb + 1) & 1); if (shift) carry_in(sb, wg, warp, lane); }
  p1_pair<N, 3>(acc, W, bar, alo, blo, lane, r);
  if (N == 32 || wg) { mbar_waitu(bar + 8 * (BB_SFREE + 4 + wg), (rb + 1) & 1); if (shift) carry_in(sb, wg, warp, lane); }
  if (N == 32) mbar_arrive_if(lane < 2, bar + 8 * (BB_EMPTY + lane));
  p1_pair<N, 4>(acc, W, bar, alo, blo, lane, r);
  const int c = (lane >> 3) & 1, i0 = (lane >> 4) * 8 + (lane & 7) + off;
  uint32_t a0 = sb + BO_H + wg * 8192 + half * 4096 + i0 * 128 + (((2 * warp + c) ^ (i0 & 7)) << 4);
  uint32_t a1 = i0 >= 16 ? sb + BO_CARRY + (wg * 4 + warp) * 256 + half * 128 + (i0 - 16) * 32 + c * 16 : a0 + 2048, a3 = a1 + (i0 >= 16 ? 128 : 4096);
  asm volatile("" : "+r"(a0), "+r"(a1), "+r"(a3));
  mbar_waitu(bar + 8 * BB_STAT, r & 1);
  const uint32_t sa = sb + BO_STAT + (lane & 3) * 32 + half * 16;
  const uint4 t0 = lds128(sa), t1 = N == 64 ? lds128(sa + 16) : t0;
  const uint32_t t[8] = {t0.x, t0.y, t0.z, t0.w, t1.x, t1.y, t1.z, t1.w};
  { const uint32_t k4[4] = {a0, a1, a3, sa}; keep4(k4, lane); }
  wg_wait<0>();
  acc_live<N>(acc);
  CTS(32);
#pragma unroll
  for (int m = 0; m < N / 16; m++) {
    const float* d = acc + 8 * m;
    stsm4t(m == 1 ? a1 : m == 3 ? a3 : a0 + m * 2048, gelu2(pack2h(d[0], d[1]), t[2 * m]), gelu2(pack2h(d[2], d[3]), t[2 * m]),
           gelu2(pack2h(d[4], d[5]), t[2 * m + 1]), gelu2(pack2h(d[6], d[7]), t[2 * m + 1]));
  }
}
template <int N, int P>
__device__ __forceinline__ void p2_mma(float* acc, const uint32_t* W, Dsc alo, Dsc blo, int r) {
  blo.e = fresh<P + N / 64 * 5>(r);
  MM<N, true>::template rs<DESC_LO(BO_H), 0>(acc, W + 80 + 16 * P, blo);     MM<N, true>::template ss<DESC_LO(0) + P * 1024, DESC_LO(BO_H) + 512, 1>(acc, alo, blo);
  MM<N, true>::template rs<DESC_LO(BO_H) + 2, 1>(acc, W + 84 + 16 * P, blo); MM<N, true>::template ss<DESC_LO(0) + P * 1024 + 128, DESC_LO(BO_H) + 514, 1>(acc, alo, blo);
  MM<N, true>::template rs<DESC_LO(BO_H) + 4, 1>(acc, W + 88 + 16 * P, blo); MM<N, true>::template ss<DESC_LO(0) + P * 1024 + 512, DESC_LO(BO_H) + 516, 1>(acc, alo, blo);
  MM<N, true>::template rs<DESC_LO(BO_H) + 6, 1>(acc, W + 92 + 16 * P, blo); MM<N, true>::template ss<DESC_LO(0) + P * 1024 + 640, DESC_LO(BO_H) + 518, 1>(acc, alo, blo);
}
template <int N, int P, int T>
__device__ __forceinline__ void p2_pass(const uint32_t* W, uint32_t bar, Dsc alo, Dsc blo, int wg, int warp, int lane, int r) {
  float acc[N / 2], ac2[N / 2];
  CTS(5 * P);
  if (P || wg) bar_sync(NB_PP + wg, 256);
  wg_fence();
  p2_mma<N, P>(acc, W, alo, blo, r);
  wg_commit();
  if constexpr (T == 2) { p2_mma<N, P + 1>(ac2, W, alo, blo, r); wg_commit(); }
  if (P < 4 || !wg) bar_arrive(NB_PP + 1 - wg, 256);
  CTS(5 * P + 2);
  if (T == 1 && (P == 2 || P == 3)) mbar_waitu(bar + 8 * (BB_SFREE + 2 * (P - 2) + wg), r & 1);
  wg_wait<T - 1>();
  acc_live<N>(acc);
  if (P == 4) bar_sync(NB_H, 256);
  CTS(5 * P + 3);
  constexpr int K = P / T & 1;
  stage_out<N, true>(acc, SMEM0 + (P == 4 ? BO_H : BO_RING_MLP + (2 - K) * 16384) + wg * 8192, warp, lane);
  if constexpr (T == 2) {
    wg_wait<0>();
    acc_live<N>(ac2);
    stage_out<N, true>(ac2, SMEM0 + BO_RING_MLP + (2 - K) * 16384 + wg * 8192 + 4096, warp, lane);
  }
  bar_arrive(NB_STAGED + (P == 4 ? 4 : 2 * K) + wg, 160);
  CTS(5 * P + 4);
}
template <int N>
__device__ __forceinline__ void phase2(const uint32_t* W, uint32_t bar, Dsc alo, Dsc blo, int wg, int warp, int lane, int r) {
  if constexpr (N == 64) {
    p2_pass<N, 0, 1>(W, bar, alo, blo, wg, warp, lane, r);
    p2_pass<N, 1, 1>(W, bar, alo, blo, wg, warp, lane, r);
    p2_pass<N, 2, 1>(W, bar, alo, blo, wg, warp, lane, r);
    p2_pass<N, 3, 1>(W, bar, alo, blo, wg, warp, lane, r);
  } else {
    p2_pass<N, 0, 2>(W, bar, alo, blo, wg, warp, lane, r);
    p2_pass<N, 2, 2>(W, bar, alo, blo, wg, warp, lane, r);
  }
  p2_pass<N, 4, 1>(W, bar, alo, blo, wg, warp, lane, r);
}

__device__ __forceinline__ void ldg4(uint32_t* v, const void* p) {
  asm volatile("ld.relaxed.gpu.global.v4.u32 {%0,%1,%2,%3}, [%4];" : "=r"(v[0]), "=r"(v[1]), "=r"(v[2]), "=r"(v[3]) : "l"(p) : "memory"); }
__device__ __forceinline__ void stg4(void* p, const uint32_t* v) {
  asm volatile("st.global.v4.u32 [%0], {%1,%2,%3,%4};" :: "l"(p), "r"(v[0]), "r"(v[1]), "r"(v[2]), "r"(v[3]) : "memory"); }
struct RowPtr {
  unsigned char *p, *q, *t;
  __device__ __forceinline__ void ld(uint32_t* v, int o) const {
    ldg4(v, p + o); ldg4(v + 4, q + o);
    asm volatile("ld.relaxed.gpu.global.v2.u32 {%0,%1}, [%2];" : "=r"(v[8]), "=r"(v[9]) : "l"(t + o) : "memory");
  }
  __device__ __forceinline__ void st(const uint32_t* w, int o) const {
    stg4(p + o, w); stg4(q + o, w + 4);
    asm volatile("st.global.v2.u32 [%0], {%1,%2};" :: "l"(t + o), "r"(w[8]), "r"(w[9]) : "memory");
  }
};
__device__ __forceinline__ RowPtr row_img(int r, int n, int lane) {
  unsigned char* b = &g_acc[0][r % RD][n * 128];
  unsigned char* p = b + (uint32_t)((lane >> 3) * 8192 + (((lane ^ n) & 7) << 4));
  return {p, p + 32768, b + (uint32_t)(65536 + (lane >> 4) * 8192 + ((((lane >> 1) ^ n) & 7) << 4) + (lane & 1) * 8)};
}
__device__ __forceinline__ RowPtr row_ext(const void* lin, bool xn, int layer, int tok, int lane) {
  unsigned char* b = xn ? reinterpret_cast<unsigned char*>(&g_xn[layer][0]) + (uint32_t)((tok >> 5) * 40960 + ((tok >> 3) & 3) * 2560 + (tok & 7) * 32)
                        : (unsigned char*)lin + (uint32_t)(tok * 1280);
  const uint32_t o = (lane >> 1) * 256 + ((lane ^ (tok >> 2)) & 1) * 16;
  return {b + (uint32_t)(xn ? o + (lane >= 20 ? 7680 : 0) : lane * 16),
          b + (uint32_t)(xn ? o + 4096 + 7680 + (lane >= 8 ? 7680 : 0) + (lane >= 28 ? 7680 : 0) : lane * 16 + 512),
          b + (uint32_t)(xn ? (lane >> 2) * 256 + ((lane & 3) ^ ((tok >> 1) & 2)) * 8 + 8192 + 3 * 7680 : lane * 8 + 1024)};
}
__device__ __forceinline__ float2 h2f(uint32_t w) {
  float2 f; asm("{\n.reg .f16 l, h;\nmov.b32 {l, h}, %2;\ncvt.f32.f16 %0, l;\ncvt.f32.f16 %1, h;\n}" : "=f"(f.x), "=f"(f.y) : "r"(w)); return f; }
__device__ __forceinline__ float rsq(float x) { float y; asm("rsqrt.approx.ftz.f32 %0, %1;" : "=f"(y) : "f"(x)); return y; }
__device__ __forceinline__ void red_if(uint32_t v, const void* a) {
  asm volatile("{\n.reg .pred q;\nsetp.ne.u32 q, %1, 0;\n@q red.relaxed.gpu.global.add.u32 [%0], %1;\n}" :: "l"(a), "r"(v) : "memory"); }
__device__ __forceinline__ uint32_t dep0(uint32_t w, int lane) { uint32_t z; asm volatile("shr.b32 %0, %1, %2;" : "=r"(z) : "r"(w), "r"(lane + 32)); return z; }
__device__ __forceinline__ int lane_of(uint32_t w) {
  int lane; asm volatile("{\n.reg .u32 t;\nmov.u32 t, %%laneid;\nshr.u32 %0, %1, 20;\nadd.u32 %0, %0, t;\n}" : "=r"(lane) : "r"(w)); return lane; }
#define BUF (RD * TILE_B)
__device__ __forceinline__ int await(uint32_t v, const uint32_t* p, uint32_t target, bool lazy) {
  int n = 0;
  while (!__all_sync(~0u, v >= target)) {
    if (lazy) __nanosleep(200);
    if (++n > SPIN_LIMIT) FAIL();
    v = ld_relaxed(p);
  }
  asm volatile("fence.acquire.gpu;" ::: "memory");
  return lane_of(v);
}
template <int W> __device__ __forceinline__ void sum2(float& s, float& q, int lane) {
  const bool up = lane & (W / 2);
  float e = (up ? q : s) + __shfl_xor_sync(~0u, up ? s : q, W / 2);
#pragma unroll
  for (int o = W / 4; o; o >>= 1) e += __shfl_xor_sync(~0u, e, o);
  const float f = __shfl_xor_sync(~0u, e, W / 2);
  s = up ? f : e; q = up ? e : f;
}
template <int TYPE>
__device__ __forceinline__ void rrow(int r, int row, int tok, int lane, const uint32_t* go, int role, const __nv_bfloat16* x, __nv_bfloat16* out) {
  const int half = TYPE == 3 ? 0 : row >> 5;
  float v[20];
  float2 st = make_float2(1.f, 0.f);
  {
    uint32_t a[10], c[10], u[10], sh = 16;
    if (TYPE == 2) row_img(front(r) + RD - ((row & 31) < 2), (row & 32) + ((row - 2) & 31), lane).ld(u, 3 * BUF);
    else row_ext(x, half, 1, tok, lane).ld(u, 0);
    if (TYPE == 2 || (TYPE == 0 && half))
      asm volatile("ld.relaxed.gpu.global.v2.f32 {%0,%1}, [%2];" : "=f"(st.x), "=f"(st.y) : "l"(g_stat + tok) : "memory");
    RowPtr ap = row_img(r, row, lane);
    const uint32_t g0 = TYPE != 3 ? ld_relaxed(go) : 0;
    if (TYPE != 3) {
      asm volatile("" : "+l"(ap.p), "+l"(ap.t));
      ap.q = ap.p + 32768;
      lane = await(g0, go, NOP * NW12 * NW34, false); BTS2(r, 8 + 2 * TYPE); RTS(0);
      ap.ld(a, TYPE ? 2 * BUF : 0);
    }
    if (TYPE == 0) {
      ap.ld(c, BUF);
      const uint32_t one = 0x3f803f80u | dep0(c[9], lane);
#pragma unroll
      for (int i = 0; i < 10; i++) asm volatile("fma.rn.bf16x2 %0, %0, %1, %2;" : "+r"(a[i]) : "r"(one), "r"(c[i]));
      sh |= dep0(a[9], lane);
    }
    const uint32_t z = TYPE == 2 ? dep0(a[9], lane) : 0;
#pragma unroll
    for (int i = 0; i < 10; i++) {
      if (TYPE == 2) { const float2 g = h2f(u[i] | z), h = h2f(a[i] | z); v[2 * i] = fmaf(h.x, 0.5f, g.x * st.x); v[2 * i + 1] = fmaf(h.y, 0.5f, g.y * st.x); continue; }
      float p = __uint_as_float(u[i] << sh), q = __uint_as_float(u[i] & (0xffffu << sh));
      if (TYPE == 0) { p = fmaf(p, st.x, bf_lo(a[i])); q = fmaf(q, st.x, bf_hi(a[i])); }
      v[2 * i] = p; v[2 * i + 1] = q;
    }
  }
  RTSD(1, v[19]);
  float s = 0.f, q = 0.f;
#pragma unroll
  for (int i = 0; i < 5; i++) {
    s += (v[4 * i] + v[4 * i + 1]) + (v[4 * i + 2] + v[4 * i + 3]);
    q += fmaf(v[4 * i], v[4 * i], v[4 * i + 1] * v[4 * i + 1]) + fmaf(v[4 * i + 2], v[4 * i + 2], v[4 * i + 3] * v[4 * i + 3]);
  }
  if (!(TYPE == 2 && half)) sum2<32>(s, q, lane);
  const float mean = s * (1.f / DM), var = fmaxf(q * (1.f / DM) - mean * mean, 0.f), rs = rsq(var + 1e-5f);
  const float k = TYPE == 0 ? 2.f * rs : half ? 1.f : rs, mr = TYPE && half ? st.y : -mean * k;
  RTSD(2, rs);
  uint32_t w[10];
#pragma unroll
  for (int i = 0; i < 10; i++) w[i] = pk<TYPE == 0>(fmaf(v[2 * i], k, mr), fmaf(v[2 * i + 1], k, mr));
  if (TYPE) row_ext(out, !half, TYPE == 2, tok, lane).st(w, 0);
  else {
    row_img(r, row, lane).st(w, 3 * BUF);
    const int q = r + ((row & 31) >= 30);
    row_img(q + (half && q >= NSEG), (row & 32) + ((row + 2) & 31), lane).st(w, 2 * BUF);
    if (lane == 1) g_st2[0][r % RD][row] = (__float_as_uint(0.5f * rsq(fmaf(var * rs, rs, 1e-5f))) & ~127u) | (r + 1);
  }
  if (TYPE != 3 && lane == 0) g_stat[tok] = make_float2((var + 1e-5f) * rs * (TYPE ? 1.f : 0.5f), mean + st.y);
}
__device__ __forceinline__ void r2rows(int r, int row, int lane, const uint32_t* go) {
  const int n = row + (lane >> 4);
  const unsigned char* ap = &g_acc[2][r % RD][0] + (uint32_t)(n * 128 + ((lane >> 3) & 1) * 8192 + (((lane ^ n) & 7) << 4));
  const uint32_t* sp = &g_st2[1][r % RD][n];
  asm volatile("" : "+l"(ap), "+l"(sp));
  await(0, go, NOP * NW12 * NW34, false);
  BTS2(r, 10);
  uint32_t a[20];
#pragma unroll
  for (int i = 0; i < 5; i++) ldg4(a + 4 * i, ap + i * 16384);
  const uint32_t z = dep0(a[19], lane);
  float s = 0.f, q = 0.f, q2 = 0.f;
#pragma unroll
  for (int i = 0; i < 20; i++) { const float2 h = h2f(a[i] | z); s += h.x + h.y; q = fmaf(h.x, h.x, q); q2 = fmaf(h.y, h.y, q2); }
  q += q2;
  sum2<16>(s, q, lane);
  const float mean = s * (0.5f / DM), rs = rsq(fmaxf(q * (0.25f / DM) - mean * mean, 0.f) + 1e-5f);
  if ((lane & 15) == 0) asm volatile("st.relaxed.gpu.global.u32 [%0], %1;" :: "l"(sp), "r"((__float_as_uint(0.5f * rs) & ~127u) | (r + 1)) : "memory");
}
__device__ __forceinline__ void r3rows(int r, int row, int tok, int lane, __nv_bfloat16* out) {
  const int n = row + (lane >> 4), m = 32 + ((n - 2) & 31);
  const unsigned char* ap = &g_acc[0][r % RD][0] + (uint32_t)(n * 128 + ((lane >> 3) & 1) * 8192 + (((lane ^ n) & 7) << 4));
  const unsigned char* zp = &g_acc[3][(r + RD - (row == 32)) % RD][0] + (uint32_t)(m * 128 + ((lane >> 3) & 1) * 8192 + (((lane ^ m) & 7) << 4));
  unsigned char* op = reinterpret_cast<unsigned char*>(out) + (uint32_t)((tok + (lane >> 4)) * 1280 + (lane & 15) * 16);
  float2 st;
  asm volatile("ld.relaxed.gpu.global.v2.f32 {%0,%1}, [%2];" : "=f"(st.x), "=f"(st.y) : "l"(g_stat + tok + (lane >> 4)) : "memory");
#pragma unroll 1
  for (int i0 = 0; i0 < 2; i0++) {
    uint32_t a[12], u[12];
#pragma unroll
    for (int i = 0; i < 3; i++) { ldg4(a + 4 * i, ap + 2 * BUF + i * 16384); ldg4(u + 4 * i, zp + i * 16384); }
    uint32_t z = dep0(u[11], lane);
#pragma unroll
    for (int i = 0; i < 12; i++) {
      const float2 h = h2f(a[i] | z), g = h2f(u[i] | z);
      a[i] = pack2(fmaf(h.x, 0.5f, fmaf(g.x, st.x, st.y)), fmaf(h.y, 0.5f, fmaf(g.y, st.x, st.y)));
      if (i & 1) z = dep0(a[i], lane);
    }
    if (i0 == 0) stg4(op, a);
    stg4(op + 256, a + 4); stg4(op + 512, a + 8);
    ap += 32768; zp += 32768; op += 512;
  }
}
template <int TYPE>
__device__ __forceinline__ void rloop(int row, int cp, int role, const __nv_bfloat16* x, __nv_bfloat16* out) {
  constexpr int ST = TYPE == 4 ? 2 : TYPE;
  const int r0 = row & 32 ? LAG : 0;
  uint32_t v = 0;
  static_assert(NSEG + RD - 2 >= NSTEP, "no signals");
#pragma unroll 1
  for (int r = r0; r < (TYPE == 0 ? r0 + NSEG : TYPE == 4 ? NSEG : TYPE == 2 || r0 ? NR : NSEG + 1); r++) {
    if (TYPE == 2 && r == NSEG + 1) row += 32;
    if (TYPE == 1 && r0 && r == NSEG) continue;
    const int tok = ((TYPE ? front(r) : r) - (row & 32 ? LAG : 0)) * 32 + (row & 31) - (TYPE ? 2 : 0);
    const bool valid = TYPE == 0 || (unsigned)tok < S_LEN;
    const uint32_t* go = &g_f[F_R1 + 4 * ST + cp][r];
    const uint32_t* first = TYPE == 2 ? &g_f[F_R2 + cp][r] : TYPE ? go : (const uint32_t*)&g_xready[NSEG + r - r0][0];
    if constexpr (TYPE == 1) { r2rows(r, row, lane_of(r), go); BTS2(r, 11); continue; }
    if constexpr (TYPE == 4) {
      const int lane = await(v, go, NOP * NW12 * NW34, false);
      BTS2(r, 8 + 2 * ST); RTS(0);
      if (valid) r3rows(r, row, tok, lane, out);
    } else if constexpr (TYPE != 1) {
      if (TYPE || row >= 32) await(v, first, TYPE ? NOP * NW12 * NW34 : 32, true);
      if (valid) rrow<TYPE>(r, row, tok, lane_of(r), go, role, x, out);
    }
    if (TYPE > 1 && row >= 32 && r + RD - 2 >= NSTEP) { v = 0; BTS2(r, 13); continue; }
    const int lane = lane_of(r);
    const void* f = lane ? (const void*)&g_xready[NSEG + (tok >> 5)][0] : (const void*)&g_f[TYPE ? F_DONE : F_Z][r];
    asm volatile("" : "+l"(f));
    __syncwarp();
    RTS(3);
    v = ld_relaxed(first + (TYPE ? 1 : 8));
    asm volatile("fence.release.gpu;" ::: "memory");
    RTS(4);
    red_if(lane == 0 || (TYPE == 2 && lane == 1 && valid) ? (TYPE & 5 ? 2 : 1) : 0, f);
    RTS(5);
    RTS_OUT();
    BTS2(r, 9 + 2 * ST);
  }
}

#define BULK_ADD(T, dst, src, len) asm volatile("{\n.reg .pred e;\nelect.sync _|e, 0xffffffff;\n@e cp.reduce.async.bulk.global.shared::cta.bulk_group.add.noftz." T " [%0], [%1], %2;\n}" \
                                               :: "l"(dst), "r"(src), "r"(len) : "memory")
#define COMMIT() asm volatile("cp.async.bulk.commit_group;" ::: "memory")
#define DRAINED(n) do { asm volatile("cp.async.bulk.wait_group.read " #n ";" ::: "memory"); __syncwarp(); } while (0)
#define WRITTEN() do { asm volatile("cp.async.bulk.wait_group 0;\nfence.proxy.async.global;" ::: "memory"); __syncwarp(); } while (0)
__device__ __forceinline__ void wait_flags(const uint32_t* p, uint32_t target) {
  int n = 0;
  while (!__all_sync(~0u, ld_relaxed(p) >= target)) { if (++n > SPIN_LIMIT) FAIL(); }
  asm volatile("fence.acquire.gpu;" ::: "memory");
  asm volatile("fence.proxy.async.global;" ::: "memory");
}
__global__ void __launch_bounds__(512, 1) bworker_kernel(const __grid_constant__ BParams P) {
  extern __shared__ __align__(1024) unsigned char smem_raw[];
  const uint32_t sb = SMEM0, bar = sb + BO_BAR;
  const int wg = __shfl_sync(~0u, threadIdx.x >> 7, 0), warp = __shfl_sync(~0u, (threadIdx.x >> 5) & 3, 0);
  if (threadIdx.x == 0) {
    if (smem_u32(smem_raw) != SMEM0) FAIL();
    uint32_t smid; asm volatile("mov.u32 %0, %%smid;" : "=r"(smid));
    const uint32_t nb = ld_relaxed(&g_tpc[(smid >> 1) & 127]);
    const bool single = nb > 1, far = nb == 0 && (smid < 64 || smid >= 124);
    int kind = far || (single && atomicAdd(&g_f[F_MISC][35], 1u) < 3) ? 0 : 1;
    int rc = single || (smid >> 1) == 16 || (smid >> 1) == 63 ? 1 : far ? 2 : 0;
    uint32_t i = atomicAdd(&g_f[F_MISC][32 + kind], 1u), o = atomicAdd(&g_f[F_MISC][36 + rc], 1u);
    while (i >= (kind == 0 ? NOP : kind == 1 ? NW12 : NW34)) { kind = (kind + 1) % 3; i = atomicAdd(&g_f[F_MISC][32 + kind], 1u); }
    while (o >= (rc == 0 ? 16 : rc == 1 ? 8 : 12)) { rc = (rc + 1) % 3; o = atomicAdd(&g_f[F_MISC][36 + rc], 1u); }
    sts64(sb + BO_BOX, i + (kind == 0 ? 0 : kind == 1 ? NOP : NOP + NW12), o + (rc ? 8 + 8 * rc : 0));
    for (int k = 0; k < BB_NUM; k++) mbar_init(bar + 8 * k, k >= BB_USED ? 4 : k >= BB_EMPTY ? 8 : k >= BB_ZFREE && kind ? 2 : 1);
    asm volatile("fence.mbarrier_init.release.cluster;" ::: "memory");
  }
  if (threadIdx.x < 128) sts128(sb + BO_CARRY + threadIdx.x * 16, 0u, 0u, 0u, 0u);
  auto ln0 = [&](int t) {
    const int lane = lane_of(t);
    if (lane < 20 && t + 128 < S_LEN) asm volatile("prefetch.global.L2 [%0];" :: "l"(P.x + (t + (t < 4 * NBC ? 4 * NBC : 128)) * DM + (lane >> 1) * 64));
    rrow<3>(0, 0, t, lane, nullptr, 0, P.x, nullptr);
    __syncwarp();
    asm volatile("fence.release.gpu;" ::: "memory");
    red_if(lane == 0, &g_xready[t >> 5][0]);
  };
  if (wg == 2) ln0(blockIdx.x * 4 + warp);
  fence_async();
  __syncthreads();
  const int role = uni(lds32(sb + BO_BOX));
  if (threadIdx.x < 32) BTS(94, 1);
  const bool op = role < NOP, w12 = role < NOP + NW12;
  const int j = op ? role : w12 ? role - NOP : role - NOP - NW12;
  const int rot = op ? (j ? 2 * ((j + 1) % 5) : 0) : 2 * (j % 5);
  if (wg == 3) {
    asm volatile("setmaxnreg.dec.sync.aligned.u32 24;");
    LANE_INIT();
    if (warp < 2) {
      auto announce = [&](int r, int it, bool mg) {
        const uint32_t* f = &g_f[(op ? F_R1 : w12 ? F_R2 : F_R3) + (lane & 3)][r + ((lane >> 2) & 1)];
        asm volatile("" : "+l"(f));
        if (warp == 0) { mbar_arrive_if(lane == 0, bar + 8 * BB_DONE); return; }
        mbar_waitw(bar + 8 * BB_DONE, it & 1);
        PTS(60);
        asm volatile("fence.release.gpu;" ::: "memory");
        red_if(lane >= (mg ? 8 : 4) ? 0 : op ? NW12 * NW34 : w12 ? NOP * NW34 : NOP * NW12, f);
        PTS(61);
        BTS(r, 4);
      };
      if (op) {
        int mt = rot + warp;
        bar_arrive(NB_FREE + warp, 160);
#pragma unroll 1
        for (int r = 0; r < NSTEP; r++) {
          const uint32_t len = fmask(r) == 3 ? 8192 : 4096;
          unsigned char* acc = &g_acc[j & 1][r % RD][fmask(r) == 2 ? 4096 : 0];
#pragma unroll 1
          for (int p = 0; p < 5; p++) {
            bar_sync(NB_STAGED + warp, 160);
            PTS(50 + 2 * p + warp);
            fence_async();
            BULK_ADD("bf16", acc + mt * 8192, sb + BO_STG + warp * 8192, len);
            COMMIT();
            PTS(64 + 50 + 2 * p + warp);
            mt = mt >= 8 ? mt - 8 : mt + 2;
            DRAINED(0);
            bar_arrive(NB_FREE + warp, 160);
          }
          WRITTEN();
          announce(r, r, false);
        }
      } else {
#pragma unroll 1
        for (int r = 0, it = 0; r < NR; r++, it++) {
          const bool mg = merged(w12, r);
          const uint32_t len = bmask(r) == 3 ? 8192 : 4096;
          unsigned char* acc = &g_acc[2][r % RD][bmask(r) == 2 ? 4096 : 0];
          if (!w12) mbar_waitw(bar + 8 * BB_GO, it & 1);
          int mt = rot + warp;
          const bool pairs = len != 8192 && !mg;
#pragma unroll 1
          for (int p = pairs ? 2 : 0; p < 5; p++) {
            const uint32_t src = sb + (p == 4 ? BO_H : BO_RING_MLP + (2 - (p & 1)) * 16384) + warp * 8192;
            bar_sync(NB_STAGED + (p == 4 ? 4 : 2 * (p & 1)) + warp, 160);
            PTS(50 + 2 * p + warp);
            fence_async();
            BULK_ADD("f16", acc + mt * 8192, src, len);
            if (mg) BULK_ADD("f16", &g_acc[2][(r + 1) % RD][4096 + mt * 8192], src + 4096, len);
            mt = mt >= 8 ? mt - 8 : mt + 2;
            if (pairs && p < 4) { BULK_ADD("f16", acc + mt * 8192, src + 4096, len); mt = mt >= 8 ? mt - 8 : mt + 2; }
            COMMIT();
            PTS(64 + 50 + 2 * p + warp);
            if (p == 4 && !pairs) break;
            DRAINED(1);
            mbar_arrive_if(lane == 0 && p, bar + 8 * (p < 3 ? BB_SFREE + 2 * (p - 1) + warp : BB_ZFREE + (p >> 1)));
            mbar_arrive_if(lane == 0 && pairs && p == 2, bar + 8 * (BB_SFREE + warp));
            if (p == 3 && !pairs) { DRAINED(0); mbar_arrive_if(lane == 0, bar + 8 * (BB_ZFREE + 2)); }
          }
          WRITTEN();
          mbar_arrive_if(lane == 0, bar + 8 * (BB_SFREE + 4 + warp));
          announce(r, it, mg);
          r += mg;
        }
      }
    } else {
      if (op && warp == 2) {
        unsigned char* wt = g_wt + j * (10 * OP_SLOT);
#pragma unroll 1
        for (int m0 = 0; m0 < 10; m0 += 3) {
          const int nu = m0 < 9 ? 9 : 3;
          mbar_expect_if(lane == 0, bar + 8 * BB_TMP, nu * 4096);
#pragma unroll 1
          for (int k = 0; k < nu; k++) tma2d_e(sb + BO_RING_OP + k * 4096, &P.wmap[0], (m0 + k / 3) * 64, 320 * j + 224 + 32 * (k % 3), bar + 8 * BB_TMP);
          mbar_waitw(bar + 8 * BB_TMP, m0 & 1);
          bulk_s2g_e(wt + m0 * OP_SLOT, sb + BO_RING_OP, nu * 4096);
          COMMIT();
          WRITTEN();
        }
        asm volatile("fence.acq_rel.gpu;" ::: "memory");
        int sl = 0, ph = 1, mt = rot;
#pragma unroll 1
        for (int r = -1; r < NSTEP; r++) {
#pragma unroll 1
          for (int n = r < 0 ? 7 : 0; n < (r + 1 < NSTEP ? 10 : 7); n++) {
            mbar_waitw(bar + 8 * (BB_USED + sl), ph);
            mbar_expect_if(lane == 0, bar + 8 * (BB_FULL + sl), OP_SLOT);
            bulk_g2s_e(sb + BO_RING_OP + sl * OP_SLOT, wt + mt * OP_SLOT, OP_SLOT, bar + 8 * (BB_FULL + sl));
            if (++sl == 3) { sl = 0; ph ^= 1; }
            mt = mt == 9 ? 0 : mt + 1;
          }
        }
      } else if (op) {
        mbar_waitw(bar + 8 * BB_START, 0);
#pragma unroll 1
        for (int r = 0; r < NSTEP; r++) {
          const int rb = r - RD + 2;
          const uint32_t len = fmask(r) == 3 ? 8192 : 4096;
          const unsigned char* src = g_o + (uint32_t)(r % RO * (96 * 8192) + 5 * j * len);
          wait_flags(lane < 2 ? &g_f[F_O + (lane ? NOP : j)][r] : rb >= 0 ? &g_f[F_DONE][rb] : &g_f[F_MISC][0],
                     lane < 2 ? (lane ? 1 : 5) : rb >= 0 ? rtarget(bmask(rb)) : NBC * 8);
          PTS1(35);
          auto two = [&](int k, uint32_t mb) {
            bulk_g2s_e(sb + BO_O + k * 8192, src + k * len, len == 8192 ? 16384 : 4096, mb);
            if (len != 8192) bulk_g2s_e(sb + BO_O + k * 8192 + 8192, src + k * len + 4096, 4096, mb);
          };
          mbar_expect_if(lane == 0, bar + 8 * (BB_OFULL + 2 + (r & 1)), len);
          bulk_g2s_e(sb + BO_O + (r & 1 ? 5 : 2) * 8192, src + 2 * len, len, bar + 8 * (BB_OFULL + 2 + (r & 1)));
          if (r) bar_sync(NB_EARLY, 288);
          mbar_expect_if(lane < 2, bar + 8 * (BB_OFULL + lane), 2 * len + (lane ? len / 4 : 0));
          two(0, bar + 8 * BB_OFULL);
          PTS(62); PTS1(38);
          const unsigned char* sx = src + (95 - 5 * j) * len + (j + 1) / 5 * 1024;
          if (r) bar_sync(NB_LAST, 288);
          two(3, bar + 8 * (BB_OFULL + 1));
          bulk_g2s_e(sb + BO_CARRY, sx, 1024, bar + 8 * (BB_OFULL + 1));
          if (len == 8192) bulk_g2s_e(sb + BO_CARRY + 1024, sx + 4096, 1024, bar + 8 * (BB_OFULL + 1));
          if (r && r + 1 < NSTEP) {
            mbar_waitw(bar + 8 * (BB_USED + (10 * r - 2) % 3), (10 * r - 2) / 3 & 1);
            mbar_waitw(bar + 8 * (BB_USED + (10 * r - 1) % 3), (10 * r - 1) / 3 & 1);
          }
          PTS1(64 + 35);
          BTS(r, 0);
        }
      } else if (warp == 2) {
#pragma unroll 1
        for (int r = 0, it = 0; r < NR; r++, it++) {
          const bool mg = merged(w12, r);
          const int rf = w12 ? front(r) : r, mk = !w12 ? bmask(r) : r == NSEG ? 0 : fmask(rf), pf = w12 ? rf : it;
          const bool full = mk == 3 || mg;
          if (mk) {
            const unsigned char* src = &g_acc[w12 ? 3 : 2][rf % RD][mk == 2 ? 4096 : 0];
            wait_flags(&g_f[w12 ? F_Z : F_R2 + (j & 3)][rf + mg], w12 ? rtarget(mk) : NOP * NW12 * NW34);
#pragma unroll 1
            for (int z = 0; z < 5; z++) {
              const int k = full ? z - (z > 0) : z >> 1;
              const uint32_t fb = bar + 8 * (BB_FULL + z), dst = sb + BO_RING_MLP + 2 * k % 3 * 16384 + (!full ? (z & 1) * 4096 : z == 1 ? -16384 : 0);
              if (full ? z != 1 : !(z & 1)) mbar_waitw(bar + 8 * (k < 3 ? BB_ZFREE + k : BB_EMPTY), (k < 3 ? it + 1 : pf) & 1);
              if (z == 0) PTS(62);
              mbar_expect_if(lane == 0, fb, !full ? 8192 : z == 4 ? 32768 : 16384);
              bulk_g2s_e(dst, src + z * 16384, mk == 3 ? 16384 : 4096, fb);
              if (mk != 3) bulk_g2s_e(dst + 8192, src + z * 16384 + 8192, 4096, fb);
              if (mg) {
                const unsigned char* s2 = &g_acc[2][(r + 1) % RD][4096 + z * 16384];
                bulk_g2s_e(dst + 4096, s2, 4096, fb); bulk_g2s_e(dst + 12288, s2 + 8192, 4096, fb);
              }
              if (full && z == 4) { mbar_waitw(bar + 8 * (BB_EMPTY + 1), pf & 1); bulk_g2s_e(sb + BO_RING_MLP - 16384, g_wx[role - NOP], 16384, fb); }
              if (z == 0) BTS(r, 0);
            }
          }
          if (!w12) {
#pragma unroll 1
            for (int z = full ? 2 : 0; z < 5; z++) mbar_waitw(bar + 8 * (BB_FULL + z), it & 1);
            red_if(lane == 0, &g_f[F_GOT][r]);
#pragma unroll 1
            for (int c = j; c < (r + RD < NSTEP ? 80 : 0); c += NW34) bulk_s2g_e(&g_acc[c / 40][r % RD][c % 40 * 2048], sb + BO_CARRY, 2048);
            COMMIT();
            wait_flags(&g_f[F_GOT][r], NW34);
            mbar_arrive_if(lane == 0, bar + 8 * BB_GO);
            WRITTEN();
          }
          mbar_waitw(bar + 8 * BB_DONE, (it + 1) & 1);
          mbar_arrive_if(lane == 0, bar + 8 * BB_DONE);
          r += mg;
        }
      } else {
#pragma unroll 1
        for (int r0 = 0, it = 0; r0 < (w12 ? NSTEP : NR); r0++, it++) {
          const bool mg = merged(w12, r0), idle = !mg && !((w12 ? fmask(r0) : bmask(r0)) >> (lane >> 4) & 1);
          const int r = r0 + (mg ? lane >> 4 : 0);
          r0 += mg;
          uint32_t t0, t1;
          int n = 0;
          mbar_waitw(bar + 8 * BB_FULL, it & 1);
          do {
            asm volatile("ld.relaxed.gpu.global.v2.u32 {%0,%1}, [%2];" : "=r"(t0), "=r"(t1) : "l"(&g_st2[!w12][r % RD][2 * (mg ? lane | 16 : lane)]) : "memory");
            if (++n > SPIN_LIMIT) FAIL();
          } while (!__all_sync(~0u, idle || (((t0 ^ (r + 1)) | (t1 ^ (r + 1))) & 127) == 0));
          sts32(sb + BO_STAT + (lane & 3) * 32 + (lane >> 2) * 4, pack2h(__uint_as_float(t0), __uint_as_float(t1)));
          __syncwarp();
          mbar_arrive_if(lane == 0, bar + 8 * BB_STAT);
          PTS(63);
        }
      }
    }
    bar_arrive(NB_END, 512);
  } else if (wg == 2) {
    asm volatile("setmaxnreg.dec.sync.aligned.u32 40;");
    const int ord = uni(lds32(sb + BO_BOX + 4));
    const int g2 = warp * 12 + ord - 24, gw = ord < 16 ? warp * 16 + ord : ord < 24 ? 80 + warp * 8 + ord : g2 < 32 ? 64 + g2 : 96 + g2;
    const int row = gw < 64 ? gw : gw < 96 ? gw - 64 : gw < 128 ? 2 * gw - 192 : 2 * gw - 224;
    if (row >= 32) {
#pragma unroll 1
      for (int t = 4 * NBC + (gw < 64 ? gw - 32 : gw - 80); t < S_LEN; t += 64) ln0(t);
    }
    if (gw < 64) rloop<0>(row, gw & 3, role, P.x, P.out);
    else if (gw < 96) rloop<2>(row, gw & 3, role, P.x, P.out);
    else if (gw < 128) rloop<1>(row, gw & 3, role, P.x, P.out);
    else rloop<4>(row, gw & 3, role, P.x, P.out);
    asm volatile("griddepcontrol.wait;" ::: "memory");
    const int t = threadIdx.x & 127;
    for (int i = (blockIdx.x * 128 + t) * 4; i < 4 * NCL * 2560; i += NBC * 512)
      *reinterpret_cast<uint4*>(&g_part[0][0][0][0] + i) = make_uint4(0u, 0u, 0u, 0u);
    bar_sync(NB_END, 512);
    if (t == 0) {
      uint32_t n;
      asm volatile("atom.acq_rel.gpu.global.add.u32 %0, [%1], 1;" : "=r"(n) : "l"(&g_f[F_MISC][64]) : "memory");
      sts32(sb + BO_BOX, n);
    }
    bar_sync(NB_END2, 128);
    if (lds32(sb + BO_BOX) == NBC - 1) {
      for (int i = t; i < F_NUM * 24; i += 128) reinterpret_cast<uint4*>(&g_f[0][0])[i] = make_uint4(0u, 0u, 0u, 0u);
      g_xready[t][0] = 0; g_tpc[t] = 0;
    }
  } else {
    asm volatile("setmaxnreg.inc.sync.aligned.u32 224;");
    LANE_INIT();
    for (int i = blockIdx.x * 256 + threadIdx.x; i < 2 * RD * TILE_B / 16; i += NBC * 256) reinterpret_cast<uint4*>(&g_acc[0][0][0])[i] = make_uint4(0u, 0u, 0u, 0u);
    warp_signal(&g_f[F_MISC][0], lane);
    const int mt0 = (rot + wg) % 10;
    auto boxes = [&](int ss) {
      const int nb = op && ss ? 3 : 4;
      const uint32_t base = sb + (ss ? BO_RES + wg * OP_RES : wg * 83968);
      mbar_expect_if(warp == 0 && lane == 0, bar + 8 * (BB_W + wg), nb * 20480 + (op ? 2048 : 0));
      bar_sync(NB_H, 256);
      if (warp < nb) {
#pragma unroll 1
        for (int i = warp; i < 5 * nb; i += nb) {
          const int p = op ? i / nb : (i - 10) >> 1, mt = (mt0 + 2 * p) % 10;
          const bool first = !op && i < 10;
          tma2d_e(op || !ss ? base + i * 4096 : sb + (first ? BO_W1 : -81920) + (2 * i + wg) * 4096, &P.wmap[op ? 0 : (w12 ? 1 : 3) + !first], first ? 128 * j + 64 * wg : mt * 64,
                  op ? 320 * j + 64 * warp + 32 * ss : first ? 64 * i + 32 * ss : 128 * j + 32 * (i & 1) + 64 * ss, bar + 8 * (BB_W + wg));
        }
      }
      if (op && warp == 3) tma2d_e(base + nb * 20480, &P.wo16, (mt0 + 2 * ss) % 10 * 64, 95 * 64 + (j + 1) / 5 * 16, bar + 8 * (BB_W + wg));
      mbar_waitw(bar + 8 * (BB_W + wg), ss);
    };
    uint32_t W[164];
    boxes(0);
    load_w<41>(W, sb + wg * 83968, warp, lane);
    fence_async();
    boxes(1);
    if (!op) {
      float cs[2] = {0.f, 0.f};
      const uint32_t a0 = sb + BO_W1 + wg * 4096 + ((lane >> 4) * 8 + (lane & 7)) * 128 + (((warp * 2 + ((lane >> 3) & 1)) ^ (lane & 7)) << 4);
#pragma unroll
      for (int i = 0; i < 80; i++) cs[i & 1] += bf_lo(W[i]) + bf_hi(W[i]);
#pragma unroll 1
      for (int i = 0; i < 60; i++) {
        uint32_t t[4];
        const uint32_t ad = a0 + (i % 20 >> 1) * 8192 + (i & 1) * 2048 - (i >= 40 ? BO_W1 : 0);
        ldsm4t(t[0], t[1], t[2], t[3], ad);
#pragma unroll
        for (int k = 0; k < 4; k++) {
          if (i < 20) cs[k & 1] += bf_lo(t[k]) + bf_hi(t[k]);
          const float mu = i < 40 ? cs[k & 1] : 0.f;
          t[k] = pack2h(bf_lo(t[k]) - mu, bf_hi(t[k]) - mu);
        }
        if (i >= 20) stsm4t(ad, t[0], t[1], t[2], t[3]);
        if (i == 19) {
#pragma unroll
          for (int k = 0; k < 2; k++) { cs[k] += __shfl_xor_sync(~0u, cs[k], 1); cs[k] += __shfl_xor_sync(~0u, cs[k], 2); cs[k] *= 1.f / DM; }
        }
      }
      const uint32_t z = dep0(__float_as_uint(cs[0]), lane);
#pragma unroll
      for (int i = 0; i < 80; i++) { W[i] = pack2h(bf_lo(W[i] | z) - cs[i & 1], bf_hi(W[i] | z) - cs[i & 1]); W[80 + i] = pack2h(bf_lo(W[80 + i]), bf_hi(W[80 + i])); }
      fence_async();
      bar_sync(NB_H, 256);
      if (wg + warp == 0) { bulk_s2g_e(g_wx[role - NOP], sb + BO_RING_MLP - 16384, 16384); COMMIT(); WRITTEN(); asm volatile("fence.acq_rel.gpu;" ::: "memory"); }
    }
    if (warp == 0) BTS(94, 6 + wg);
    const Dsc blo = {P.desc, 1}, alo = blo + wg * (op ? OP_RES / 16 : 256);
    if (op) {
      Ring rg = {(uint32_t)wg, 0};
      mbar_arrive_if(lane == 0, bar + 8 * BB_START);
      if (wg) bar_arrive(NB_PP, 256);
      const Dsc xlo = {P.desc32, 1};
#pragma unroll 1
      for (int r = 0; r < NSTEP; r++) {
        asm volatile("" : "+r"(lane));
        if (fmask(r) == 3) op_round<64>(W, bar, alo, blo, xlo, j == 0, rg, wg, warp, lane, r);
        else op_round<32>(W, bar, alo, blo, xlo, j == 0, rg, wg, warp, lane, r);
        if (warp == 0) BTS(r, 2 + wg);
      }
    } else {
      const int q4 = (128 * j + 64 * wg + 16 * warp) / 160, off = w12 ? (0x0413 >> (4 * q4)) & 7 : 0;
#pragma unroll 1
      for (int r0 = 0, r = 0; r0 < NR; r0++, r++) {
        asm volatile("" : "+r"(lane));
        const bool mg = merged(w12, r0);
        const int bm = mg ? 3 : bmask(r0), rf = w12 ? front(r) : r, fm = !w12 ? bm : r == NSEG ? 0 : fmask(rf);
        if (fm == 3) phase1<64>(W, sb, alo, blo, 0, wg, warp, lane, w12, off, r, rf);
        else if (fm) phase1<32>(W, sb, alo, blo, fm >> 1, wg, warp, lane, w12, off, r, rf);
        else { mbar_waitu(bar + 8 * (BB_SFREE + 4 + wg), (r + 1) & 1); carry_in(sb, wg, warp, lane); }
        CTS(33);
        fence_async();
        bar_sync(NB_H, 256);
        mbar_arrive_if(wg == 1 && warp == 0 && lane < 2, bar + 8 * BB_ZFREE);
        if (wg + warp == 0) BTS(r0, 1);
        if (bm == 3) phase2<64>(W, bar, alo, blo, wg, warp, lane, r);
        else phase2<32>(W, bar, alo, blo + (bm >> 1) * 256, wg, warp, lane, r);
        if (warp == 0) BTS(r0, 2 + wg);
        r0 += mg;
      }
    }
    CTS_OUT();
    bar_arrive(NB_END, 512);
  }
}

typedef CUresult (*EncodeFn)(CUtensorMap*, CUtensorMapDataType, cuuint32_t, void*, const cuuint64_t*, const cuuint64_t*, const cuuint32_t*,
                             const cuuint32_t*, CUtensorMapInterleave, CUtensorMapSwizzle, CUtensorMapL2promotion, CUtensorMapFloatOOBfill);
static void make_map(EncodeFn fn, CUtensorMap* tm, const void* ptr, uint64_t cols, uint64_t rows, uint32_t bc, uint32_t br) {
  cuuint64_t dims[2] = {cols, rows}; cuuint64_t strides[1] = {cols * 2}; cuuint32_t box[2] = {bc, br}; cuuint32_t es[2] = {1, 1};
  fn(tm, CU_TENSOR_MAP_DATA_TYPE_BFLOAT16, 2, const_cast<void*>(ptr), dims, strides, box, es, CU_TENSOR_MAP_INTERLEAVE_NONE,
     CU_TENSOR_MAP_SWIZZLE_128B, CU_TENSOR_MAP_L2_PROMOTION_L2_256B, CU_TENSOR_MAP_FLOAT_OOB_FILL_NONE);
}
#define dbg_a_only 0
extern "C" void kernel_launch(void* const* d_in, const int* in_sizes, int n_in, void* d_out, int out_size) {
  void* fnp = nullptr; cudaDriverEntryPointQueryResult qr;
  cudaGetDriverEntryPoint("cuTensorMapEncodeTiled", &fnp, cudaEnableDefault, &qr);
  EncodeFn fn = (EncodeFn)fnp;
  cudaStream_t st = cudaStreamPerThread;
  cudaFuncSetAttribute(bworker_kernel, cudaFuncAttributeMaxDynamicSharedMemorySize, B_SMEM);
  {
    AMaps M;
    for (int i = 0; i < 3; i++) make_map(fn, &M.w16[i], d_in[2 + i], HD, DM, 64, 16);
    M.wv = (const __nv_bfloat16*)d_in[4];
    make_map(fn, &M.wo32, d_in[5], DM, HD, 64, 32);
    const uint32_t hi[5] = {dhi(TILE_SBO, 3), dhi(1024, 1), dhi(1024, 0), dhi(PL_SZ, 0), dhi(896, 0)};
    for (int i = 0; i < 5; i++) M.d[i] = (uint64_t)hi[i] << 32;
    cudaFuncSetAttribute(acore_kernel, cudaFuncAttributeMaxDynamicSharedMemorySize, A_SMEM);
    cudaFuncSetAttribute(acore_kernel, cudaFuncAttributeNonPortableClusterSizeAllowed, 1);
    cudaLaunchConfig_t cfg = {};
    cfg.gridDim = dim3(CL_SIZE * NCL); cfg.blockDim = dim3(512); cfg.dynamicSmemBytes = A_SMEM; cfg.stream = st;
    cudaLaunchAttribute at[1]; at[0].id = cudaLaunchAttributeClusterDimension;
    at[0].val.clusterDim.x = CL_SIZE; at[0].val.clusterDim.y = 1; at[0].val.clusterDim.z = 1;
    cfg.attrs = at; cfg.numAttrs = 1;
    cudaLaunchKernelEx(&cfg, acore_kernel, M, (const __nv_bfloat16*)d_in[1], dbg_a_only ? 0 : 1);
  }
  if (!dbg_a_only) {
    BParams P;
    make_map(fn, &P.wmap[0], d_in[5], DM, HD, 64, 32);
    make_map(fn, &P.wo16, d_in[5], DM, HD, 64, 16);
    make_map(fn, &P.wmap[1], d_in[8], DM, DM, 64, 32);
    make_map(fn, &P.wmap[2], d_in[9], DM, DM, 64, 32);
    make_map(fn, &P.wmap[3], d_in[10], FF, DM, 64, 32);
    make_map(fn, &P.wmap[4], d_in[11], DM, FF, 64, 32);
    P.x = (const __nv_bfloat16*)d_in[0];
    P.out = (__nv_bfloat16*)d_out;
    P.desc = (uint64_t)dhi(1024, 1) << 32;
    P.desc32 = (uint64_t)dhi(256, 3) << 32;
    cudaLaunchConfig_t cfg = {};
    cfg.gridDim = dim3(NBC); cfg.blockDim = dim3(512); cfg.dynamicSmemBytes = B_SMEM; cfg.stream = st;
    cudaLaunchAttribute at[1]; at[0].id = cudaLaunchAttributeProgrammaticStreamSerialization; at[0].val.programmaticStreamSerializationAllowed = 1;
    cfg.attrs = at; cfg.numAttrs = 1;
    cudaLaunchKernelEx(&cfg, bworker_kernel, P);
  }
}
```
